```python
import torch

def _softmax(x, axis=-1):
    return torch.softmax(x, dim=axis)

def _gelu(x):
    return torch.nn.functional.gelu(x, approximate='tanh')

def _silu(x):
    return torch.nn.functional.silu(x)

def _sigmoid(x):
    return torch.sigmoid(x)

def _layernorm(x, axis=-1, eps=1e-05):
    m = x.mean(dim=axis, keepdim=True)
    v = x.var(dim=axis, keepdim=True, unbiased=False)
    return (x - m) / torch.sqrt(v + eps)

def _scatter_add(tgt, idx, src, axis=0):
    return tgt.clone().index_add_(axis, idx, src)

def _segment_sum(src, seg, n):
    out = torch.zeros((n,) + src.shape[1:], dtype=src.dtype)
    return out.index_add_(0, seg, src)

def _pad(x, pw):
    flat = tuple((v for pair in reversed(pw) for v in pair))
    return torch.nn.functional.pad(x, flat)
kernel_name = 'concat_heads__memory_aug_recurrent_mem_tr__ssm_conv_s4__prompt'

def setup_inputs():

    _w = lambda a: (lambda t: t.to(torch.bfloat16) if t.is_floating_point() else t)(torch.as_tensor(a))

    def _A_setup():
        B, S, Dm = (1, 2048, 1024)
        H, Dh = (32, 128)
        M, seg = (8, 32)
        seg = min(seg, S)
        S = S // seg * seg
        return {'x': _w((lambda *s: torch.randn(*s, dtype=torch.bfloat16) * 0.05)(B, S, Dm)), 'mem0': _w((lambda *s: torch.randn(*s, dtype=torch.bfloat16) * 0.4)(B, M, Dm)), 'Wq': _w((lambda *s: torch.randn(*s, dtype=torch.bfloat16) * 6.4)(Dm, H, Dh) * Dm ** (-0.5)), 'Wk': _w((lambda *s: torch.randn(*s, dtype=torch.bfloat16) * 6.4)(Dm, H, Dh) * Dm ** (-0.5)), 'Wv': _w((lambda *s: torch.randn(*s, dtype=torch.bfloat16) * 0.4)(Dm, H, Dh) * Dm ** (-0.5)), 'Wo': _w((lambda *s: torch.randn(*s, dtype=torch.bfloat16) * 0.4)(H, Dh, Dm) * (H * Dh) ** (-0.5)), 'seg_len': seg}
    _A_in = _A_setup()

    def _B_setup():
        B, L, D, N = (1, 2048, 1024, 128)
        A_re = -(lambda _x: torch.exp(torch.as_tensor(_x)))((lambda *s: torch.randn(*s, dtype=torch.bfloat16) * 6.4)(D, N))
        A_im = torch.pi * (lambda *s: torch.randn(*s, dtype=torch.bfloat16) * 0.05)(D, N)
        B_re = (lambda *s: torch.randn(*s, dtype=torch.bfloat16) * 0.1)(D, N)
        B_im = (lambda *s: torch.randn(*s, dtype=torch.bfloat16) * 0.1)(D, N)
        C_re = (lambda *s: torch.randn(*s, dtype=torch.bfloat16) * 0.1)(D, N)
        C_im = (lambda *s: torch.randn(*s, dtype=torch.bfloat16) * 0.1)(D, N)
        log_dt = (lambda *s: torch.randn(*s, dtype=torch.bfloat16) * 0.05)(D) * 0.5 - 4.0
        Dskip = (lambda *s: torch.randn(*s, dtype=torch.bfloat16) * 0.05)(D)
        return {'u': _w((lambda *s: torch.randn(*s, dtype=torch.bfloat16) * 0.05)(B, L, D)), 'A_re': _w(A_re), 'A_im': _w(A_im), 'B_re': _w(B_re), 'B_im': _w(B_im), 'C_re': _w(C_re), 'C_im': _w(C_im), 'log_dt': _w(log_dt), 'Dskip': _w(Dskip)}
    _B_in = _B_setup()
    return {'A_x': _A_in['x'], 'A_mem0': _A_in['mem0'], 'A_Wq': _A_in['Wq'], 'A_Wk': _A_in['Wk'], 'A_Wv': _A_in['Wv'], 'A_Wo': _A_in['Wo'], 'A_seg_len': _A_in['seg_len'], 'B_u': _B_in['u'], 'B_A_re': _B_in['A_re'], 'B_A_im': _B_in['A_im'], 'B_B_re': _B_in['B_re'], 'B_B_im': _B_in['B_im'], 'B_C_re': _B_in['C_re'], 'B_C_im': _B_in['C_im'], 'B_log_dt': _B_in['log_dt'], 'B_Dskip': _B_in['Dskip']}

def reference(A_x, A_mem0, A_Wq, A_Wk, A_Wv, A_Wo, A_seg_len, B_u, B_A_re, B_A_im, B_B_re, B_B_im, B_C_re, B_C_im, B_log_dt, B_Dskip):

    def _A_ref(x, mem0, Wq, Wk, Wv, Wo, seg_len):
        B, S, Dm = x.shape
        H, Dh = (Wq.shape[1], Wq.shape[2])
        M = mem0.shape[1]
        scale = Dh ** (-0.5)
        n_seg = S // seg_len
        L = M + seg_len
        idx = torch.arange(L)
        mask = (idx[:, None] < M) | (idx[:, None] >= idx[None, :])
        mem = mem0
        outs = []
        for s in range(n_seg):
            xs = x[:, s * seg_len:(s + 1) * seg_len, :].clone()
            h = torch.concatenate([mem, xs], axis=1)
            q = torch.einsum('btd,dhe->bhte', h, Wq)
            k = torch.einsum('btd,dhe->bhte', h, Wk)
            v = torch.einsum('btd,dhe->bhte', h, Wv)
            scores = torch.einsum('bhqe,bhke->bhqk', q, k) * scale
            scores = torch.where(mask[None, None], scores, -1000000000.0)
            p = _softmax(scores, axis=-1)
            o = torch.einsum('bhqk,bhke->bhqe', p, v)
            o = torch.einsum('bhte,hed->btd', o, Wo)
            mem = o[:, :M, :].clone()
            outs.append(o[:, M:, :])
        return torch.concatenate(outs, axis=1)

    def _B_ref(u, A_re, A_im, B_re, B_im, C_re, C_im, log_dt, Dskip):
        Bsz, L, D = u.shape
        dt = torch.exp(log_dt)[:, None]
        A = A_re + 1j * A_im
        Bc = B_re + 1j * B_im
        Cc = C_re + 1j * C_im
        logdA = dt * A
        dB = dt * Bc
        l = (lambda x, dt: x.to(dt))(torch.arange(L), A_re.dtype)
        P = torch.exp(logdA[:, :, None] * l[None, None, :])
        K = torch.einsum('dn,dnl,dn->dl', Cc, P, dB).real
        L2 = 2 * L
        Kp = _pad(K, ((0, 0), (0, L)))
        up = (lambda x, *d: x.permute(*d))(u, 0, 2, 1)
        up = _pad(up, ((0, 0), (0, 0), (0, L)))
        Kf = (lambda x, axes=(-2, -1): torch.fft.rfft2(x.float(), dim=axes))(Kp[:, None, :], axes=(-2, -1))
        Uf = (lambda x, axes=(-2, -1): torch.fft.rfft2(x.float(), dim=axes))(up[:, :, None, :], axes=(-2, -1))
        Yf = Uf * Kf[None, :, :, :]
        y = (lambda x, s, axes=(-2, -1): torch.fft.irfft2(x, s=s, dim=axes).to(torch.bfloat16))(Yf, (1, L2), axes=(-2, -1))[:, :, 0, :L]
        y = (lambda x, *d: x.permute(*d))(y, 0, 2, 1) + u * Dskip[None, None, :]
        return y
    a = _A_ref(A_x, A_mem0, A_Wq, A_Wk, A_Wv, A_Wo, A_seg_len)
    b = _B_ref(B_u, B_A_re, B_A_im, B_B_re, B_B_im, B_C_re, B_C_im, B_log_dt, B_Dskip)
    return torch.concatenate([a, b], axis=-1)
```

```cpp
#include <cuda_runtime.h>
#include <cuda_bf16.h>
#include <stdint.h>
#include <stdio.h>
#include <string.h>

typedef __nv_bfloat16 bf16;

constexpr int S_LEN = 2048, DM = 1024, NH = 32, DH = 128, HD = 4096, NSEG = 64;
constexpr uint32_t SENT = 0xFFFFFFFFu;
constexpr int SPIN_LIMIT = 1 << 18;

__device__ __align__(1024) bf16 g_qx[S_LEN * HD];
__device__ __align__(1024) bf16 g_kx[S_LEN * HD];
__device__ __align__(1024) bf16 g_vx[S_LEN * HD];
__device__ __align__(1024) bf16 g_ox[S_LEN * HD];
__device__ __align__(1024) bf16 g_km[NSEG * NH * 8 * DH];
__device__ __align__(1024) bf16 g_vm[NSEG * NH * 8 * DH];
__device__ __align__(1024) char g_ring[2 << 20];
__device__ int g_side[256];
__device__ __align__(1024) float g_K[DM * S_LEN];

__device__ __forceinline__ uint32_t smem_u32(const void* p) { return (uint32_t)__cvta_generic_to_shared(p); }
__device__ __forceinline__ uint32_t clk() { uint32_t c; asm volatile("mov.u32 %0, %%clock;" : "=r"(c)::"memory"); return c; }
__device__ __forceinline__ uint32_t pack_bf16(float lo, float hi) {
    uint32_t r; asm("cvt.rn.bf16x2.f32 %0, %1, %2;" : "=r"(r) : "f"(hi), "f"(lo)); return r;
}
__device__ __forceinline__ uint32_t movm(uint32_t a) {
    uint32_t d; asm volatile("movmatrix.sync.aligned.m8n8.trans.b16 %0, %1;" : "=r"(d) : "r"(a)); return d;
}
__device__ __forceinline__ void mma16(float (&d)[4], const uint32_t (&a)[4], uint32_t b0, uint32_t b1) {
    asm volatile("mma.sync.aligned.m16n8k16.row.col.f32.bf16.bf16.f32 {%0,%1,%2,%3}, {%4,%5,%6,%7}, {%8,%9}, {%0,%1,%2,%3};"
        : "+f"(d[0]), "+f"(d[1]), "+f"(d[2]), "+f"(d[3]) : "r"(a[0]), "r"(a[1]), "r"(a[2]), "r"(a[3]), "r"(b0), "r"(b1));
}
__device__ __forceinline__ void mma16z(float (&d)[4], const uint32_t (&a)[4], uint32_t b0, uint32_t b1) {
    asm volatile("mma.sync.aligned.m16n8k16.row.col.f32.bf16.bf16.f32 {%0,%1,%2,%3}, {%4,%5,%6,%7}, {%8,%9}, {%10,%10,%10,%10};"
        : "=f"(d[0]), "=f"(d[1]), "=f"(d[2]), "=f"(d[3]) : "r"(a[0]), "r"(a[1]), "r"(a[2]), "r"(a[3]), "r"(b0), "r"(b1), "f"(0.f));
}
__device__ __forceinline__ void mma8z(float (&d)[4], uint32_t a0, uint32_t a1, uint32_t b0) {
    asm volatile("mma.sync.aligned.m16n8k8.row.col.f32.bf16.bf16.f32 {%0,%1,%2,%3}, {%4,%5}, {%6}, {%7,%7,%7,%7};"
        : "=f"(d[0]), "=f"(d[1]), "=f"(d[2]), "=f"(d[3]) : "r"(a0), "r"(a1), "r"(b0), "f"(0.f));
}
__device__ __forceinline__ void ldsm4t(uint32_t (&r)[4], uint32_t addr) {
    asm volatile("ldmatrix.sync.aligned.m8n8.x4.trans.shared.b16 {%0,%1,%2,%3}, [%4];"
        : "=r"(r[0]), "=r"(r[1]), "=r"(r[2]), "=r"(r[3]) : "r"(addr) : "memory");
}
__device__ __forceinline__ void ldsm4(uint32_t (&r)[4], uint32_t addr) {
    asm volatile("ldmatrix.sync.aligned.m8n8.x4.shared.b16 {%0,%1,%2,%3}, [%4];"
        : "=r"(r[0]), "=r"(r[1]), "=r"(r[2]), "=r"(r[3]) : "r"(addr) : "memory");
}
__device__ __forceinline__ float lds32(uint32_t a) {
    float v; asm volatile("ld.shared.f32 %0, [%1];" : "=f"(v) : "r"(a) : "memory"); return v;
}
__device__ __forceinline__ void st_async1(uint32_t dst, float v, uint32_t bar) {
    asm volatile("st.async.shared::cluster.mbarrier::complete_tx::bytes.f32 [%0], %1, [%2];" ::"r"(dst), "f"(v), "r"(bar) : "memory");
}
__device__ __forceinline__ void cp16(uint32_t dst, const void* src) {
    asm volatile("cp.async.cg.shared.global [%0], [%1], 16;" ::"r"(dst), "l"(src) : "memory");
}
__device__ __forceinline__ void sts128(uint32_t a, const float (&v)[4]) {
    asm volatile("st.shared.v4.f32 [%0], {%1,%2,%3,%4};" ::"r"(a), "f"(v[0]), "f"(v[1]), "f"(v[2]), "f"(v[3]) : "memory");
}
__device__ __forceinline__ float4 lds128(uint32_t a) {
    float4 v; asm volatile("ld.shared.v4.f32 {%0,%1,%2,%3}, [%4];" : "=f"(v.x), "=f"(v.y), "=f"(v.z), "=f"(v.w) : "r"(a) : "memory"); return v;
}
__device__ __forceinline__ void sts64(uint32_t a, float x, float y) {
    asm volatile("st.shared.v2.f32 [%0], {%1,%2};" ::"r"(a), "f"(x), "f"(y) : "memory");
}
__device__ __forceinline__ float2 lds64(uint32_t a) {
    float2 v; asm volatile("ld.shared.v2.f32 {%0,%1}, [%2];" : "=f"(v.x), "=f"(v.y) : "r"(a) : "memory"); return v;
}
__device__ __forceinline__ void bar_sync(int id, int n) { asm volatile("bar.sync %0, %1;" ::"r"(id), "r"(n) : "memory"); }
__device__ __forceinline__ void bar_arrive(int id, int n) { asm volatile("bar.arrive %0, %1;" ::"r"(id), "r"(n) : "memory"); }
__device__ __forceinline__ uint32_t mapa(uint32_t a, uint32_t r) {
    uint32_t o; asm("mapa.shared::cluster.u32 %0, %1, %2;" : "=r"(o) : "r"(a), "r"(r)); return o;
}
__device__ __forceinline__ void st_async4(uint32_t dst, float4 v, uint32_t bar) {
    asm volatile("st.async.shared::cluster.mbarrier::complete_tx::bytes.v4.f32 [%0], {%1,%2,%3,%4}, [%5];"
        ::"r"(dst), "f"(v.x), "f"(v.y), "f"(v.z), "f"(v.w), "r"(bar) : "memory");
}
__device__ __forceinline__ void mbar_init(uint32_t bar, int n) { asm volatile("mbarrier.init.shared.b64 [%0], %1;" ::"r"(bar), "r"(n) : "memory"); }
__device__ __forceinline__ void mbar_expect(uint32_t bar, int bytes) {
    asm volatile("mbarrier.arrive.expect_tx.shared.b64 _, [%0], %1;" ::"r"(bar), "r"(bytes) : "memory");
}
__device__ __forceinline__ void bulk_load(uint32_t dst, const void* src, int bytes, uint32_t bar) {
    asm volatile("cp.async.bulk.shared::cluster.global.mbarrier::complete_tx::bytes [%0], [%1], %2, [%3];"
        ::"r"(dst), "l"(src), "r"(bytes), "r"(bar) : "memory");
}
__device__ __forceinline__ bool mbar_try(uint32_t bar, uint32_t par) {
    uint32_t ok;
    asm volatile("{.reg .pred p; mbarrier.try_wait.parity.shared::cta.b64 p, [%1], %2; selp.u32 %0, 1, 0, p;}"
        : "=r"(ok) : "r"(bar), "r"(par) : "memory");
    return ok;
}
__device__ __forceinline__ void mbar_wait(uint32_t bar, uint32_t par) {
    if (!mbar_try(bar, par))
        for (int it = 0; it < SPIN_LIMIT && !mbar_try(bar, par); it++) {}
}
__device__ __forceinline__ float4 add4(float4 a, float4 b) { return make_float4(a.x + b.x, a.y + b.y, a.z + b.z, a.w + b.w); }
__device__ __forceinline__ float ex2(float x) { float y; asm("ex2.approx.ftz.f32 %0, %1;" : "=f"(y) : "f"(x)); return y; }

constexpr int CH_NRES = 46;
constexpr int CH_PART = CH_NRES * 512;
constexpr int CH_WREG = CH_PART + 8 * 512;
constexpr int CH_SX = 8 * CH_WREG;
constexpr int CH_MX = CH_SX + 3 * 1280;
constexpr int CH_XS = CH_MX + 3 * 512;
constexpr int CH_BAR = CH_XS + 5632;
constexpr int CH_SMEM = CH_BAR + 48;

__device__ __forceinline__ char* ring_base() { return (char*)(((uintptr_t)g_ring + (1 << 20) - 1) & ~(uintptr_t)((1 << 20) - 1)); }
__device__ __forceinline__ uint32_t ring_off(int chunk, int side) {
    uint32_t o = ((chunk & 1) << 13) | ((chunk >> 1) << 16);
    uint32_t par = ((o >> 13) ^ (o >> 16) ^ (o >> 17) ^ (o >> 19) ^ side) & 1;
    return o | (par << 12);
}
__device__ __forceinline__ uint2 ld_poll(const char* p) {
    unsigned long long v; asm volatile("ld.relaxed.gpu.global.b64 %0, [%1];" : "=l"(v) : "l"(p) : "memory");
    return make_uint2((uint32_t)v, (uint32_t)(v >> 32));
}
__device__ __forceinline__ void st_pub(char* p, uint32_t x, uint32_t y) {
    unsigned long long v = ((unsigned long long)y << 32) | x;
    asm volatile("st.relaxed.gpu.global.b64 [%0], %1;" ::"l"(p), "l"(v) : "memory");
}
template <int N>
__device__ __forceinline__ void poll_issue(uint2 (&b)[N], const char* p, bool lastvalid) {
#pragma unroll
    for (int i = 0; i < N; i++) {
        if (i < N - 1 || lastvalid) b[i] = ld_poll(p + i * 256);
        else b[i] = make_uint2(0, 0);
    }
}
template <int N>
__device__ __forceinline__ int poll_check(uint2 (&b)[N], const char* p) {
    int it = 0;
    uint32_t mx = b[0].x;
#pragma unroll
    for (int i = 1; i < N; i++) mx = max(mx, b[i].x);
    if (__any_sync(0xffffffffu, mx == SENT)) {
        while (it++ < SPIN_LIMIT) {
#pragma unroll
            for (int i = 0; i < N; i++)
                if (b[i].x == SENT) b[i] = ld_poll(p + i * 256);
            mx = b[0].x;
#pragma unroll
            for (int i = 1; i < N; i++) mx = max(mx, b[i].x);
            if (!__any_sync(0xffffffffu, mx == SENT)) break;
        }
    }
    return it;
}
__device__ __forceinline__ float4 sum8(uint32_t a) {
    float4 v[8];
#pragma unroll
    for (int i = 0; i < 8; i++) v[i] = lds128(a + i * CH_WREG);
    return add4(add4(add4(v[0], v[1]), add4(v[2], v[3])), add4(add4(v[4], v[5]), add4(v[6], v[7])));
}
template <int N>
__device__ __forceinline__ uint32_t delay(uint32_t a) {
    uint32_t z = 0;
#pragma unroll
    for (int i = 0; i < N; i++) asm volatile("ld.volatile.shared.u32 %0, [%1];" : "=r"(z) : "r"(a + z) : "memory");
    return z;
}

#define TIM(i)
#define GT(i, z)
#define POLLCHK(N, arr, p, i) poll_check<N>(arr, p)

template <bool B> struct BoolC { static constexpr bool value = B; };
#define DLM 6
#define DLO 8
#define NPRE_O 4
template <bool PV>
__device__ __forceinline__ void chain_loop(const uint32_t (&wa)[40][4], const uint32_t sb, const int w, const int lane, const int rank,
                                           const int h, const int side) {
    const int nq = rank == 0 ? 6 : 5, u0 = rank == 0 ? 0 : 1 + 5 * rank, v0 = rank == 0 ? -6 : 3 * rank - 6;
    const int gw = rank * 8 + w;
    const uint32_t wl = sb + w * CH_WREG + lane * 16;
    const uint32_t pl = sb + CH_PART + w * 512 + lane * 16;
    const uint32_t barS = sb + CH_BAR, barM = barS + 8, barX = barS + 16, zero = barS + 24;
    char* const ring = ring_base();
    const char* const m_rd = ring + ring_off(24 + w, side) + lane * 8;
    const char* const o_rd = ring + ring_off(gw, side) + lane * 8;
    char* pub;
    if (PV) {
        int ks = h * 8 + v0 + w, cw = ks < 176 ? ks / 11 : 16 + (ks - 176) / 10, c0 = cw < 16 ? 11 * cw : 176 + 10 * (cw - 16);
        pub = ring + (ring_off(cw, 0) & ~4096u) + (ks - c0) * 256 + lane * 8;
    } else {
        int ks = 2 * h + w;
        pub = ring + (ring_off(24 + (ks >> 3), 0) & ~4096u) + (ks & 7) * 256 + lane * 8;
    }
    const uint32_t xs = sb + CH_XS + (PV ? nq * 512 + (w - nq) * 1024 : w * 512) + lane * 16;
    bf16* kvo = (PV ? g_vm + 128 * (v0 + w) : g_km + 64 * (u0 + w)) + h * 1024 + 2 * lane;
    const bool mown = !PV && w == rank && rank < 2;
    auto xload = [&](int s) {
        mbar_expect(barX, 8192 - nq * 512);
        bulk_load(sb + CH_XS, g_kx + (size_t)(s * NH + h) * 4096 + u0 * 256, nq * 512, barX);
        bulk_load(sb + CH_XS + nq * 512, g_vx + (size_t)(s * NH + h) * 4096 + (v0 + nq) * 512, (8 - nq) * 1024, barX);
    };
    if (!PV && w == 2 && lane == 0) xload(0);
    uint32_t sw[8][4];
#pragma unroll
    for (int i = 0; i < 8; i++) ldsm4t(sw[i], wl + i * 512);
    mbar_wait(barX, 0);

    auto step = [&](const int s, auto lastc) {
        constexpr bool last = decltype(lastc)::value;
        const uint32_t slot = (s & 3) << 14;
        uint2 b[8];
        const uint32_t z0 = delay<DLM>(zero);
        TIM(0);
        poll_issue<8>(b, m_rd + slot + z0, true);
        GT(0, z0);
        if (!last) {
            if (PV) { if (w == 7 && lane == 0) mbar_expect(barS, 3 * 1280); }
            else {
                if (w == (rank & 1) && lane == 0) mbar_expect(barM, rank < 2 ? 2 * 512 : 8);
                if (mown) { st_pub(pub + (slot ^ 0x8000), SENT, SENT); st_pub(pub + (slot ^ 0x8000) + 4096, SENT, SENT); }
            }
        }
        POLLCHK(8, b, m_rd + slot, 0);
        TIM(1);
        {
            float acc[6][4];
#pragma unroll
            for (int kk = 0; kk < 8; kk++) {
                const int j = (2 * kk) & 7;
                if (kk == 0) { mma16z(acc[5], sw[0], b[0].x, b[0].y); mma16z(acc[4], sw[1], b[0].x, b[0].y); }
                else { mma16(acc[5], sw[j], b[kk].x, b[kk].y); mma16(acc[4], sw[j + 1], b[kk].x, b[kk].y); }
#pragma unroll
                for (int i = 0; i < 4; i++) {
                    if (kk == 0) mma16z(acc[i], wa[i * 8], b[0].x, b[0].y);
                    else mma16(acc[i], wa[i * 8 + kk], b[kk].x, b[kk].y);
                    if (i < 2) ldsm4t(sw[j + i], wl + (8 + 2 * kk + i) * 512);
                }
            }
#pragma unroll
            for (int i = 0; i < 6; i++) sts128(wl + CH_PART + ((i + 4) % 6) * 512, acc[(i + 4) % 6]);
        }
        TIM(2);
        float va[4][4];
        uint32_t kf;
        if (!PV) {
            uint32_t xf[4];
            bar_sync(1, 256);
            float4 v[8];
#pragma unroll
            for (int i = 0; i < 8; i++) v[i] = lds128(pl + i * CH_WREG);
            ldsm4(xf, xs);
            float4 r = add4(add4(add4(v[0], v[1]), add4(v[2], v[3])), add4(add4(v[4], v[5]), add4(v[6], v[7])));
            uint32_t qf = movm(pack_bf16(r.x, r.y));
            kf = movm(pack_bf16(r.z, r.w));
            if (!last) {
                float s0[4], s1[4], s2[4], s3[4], s4[4];
                mma8z(s0, qf, 0, xf[0]); mma8z(s1, qf, 0, xf[1]); mma8z(s2, qf, 0, xf[2]); mma8z(s3, qf, 0, xf[3]);
                mma8z(s4, qf, 0, kf);
                const float x0[4] = {s0[0], s0[1], s1[0], s1[1]}, x1[4] = {s2[0], s2[1], s3[0], s3[1]};
                sts128(pl, x0); sts128(pl + CH_WREG, x1);
                sts64(pl + 2 * CH_WREG - lane * 8, s4[0], s4[1]);
                bar_arrive(2, nq * 32 + 64);
            }
            TIM(4);
        } else {
            bar_sync(1, 256);
        }
        {
            const float z = __uint_as_float(delay<1>(zero));
#pragma unroll
            for (int i = 0; i < 4; i++) va[i][0] = va[i][1] = va[i][2] = va[i][3] = z;
        }
#pragma unroll
        for (int kk = 0; kk < 8; kk++) {
            mma16(va[kk & 1], sw[kk], b[kk].x, b[kk].y);
            mma16(va[2 + (kk & 1)], wa[32 + kk], b[kk].x, b[kk].y);
        }
#pragma unroll
        for (int j = 0; j < 4; j++) { va[0][j] += va[1][j]; va[2][j] += va[3][j]; }
        sts128(wl + CH_PART + 6 * 512, va[0]);
        sts128(wl + CH_PART + 7 * 512, va[2]);
        TIM(6);
        uint32_t vm0, vm1;
        uint32_t so[10][4];
        if (PV) {
            uint32_t vt0[4], vt1[4];
            ldsm4t(vt0, xs); ldsm4t(vt1, xs + 512);
            if (w >= 6 && !last) {
                const uint32_t sa = sb + CH_PART + (w - 6) * CH_WREG + lane * 16, sc = sb + CH_PART + 2 * CH_WREG + (w - 6) * 128 + lane * 4;
                const uint32_t da = sb + CH_SX + rank * 1280 + (w - 6) * 512 + lane * 16, dc = sb + CH_SX + rank * 1280 + 1024 + (w - 6) * 128 + lane * 4;
                bar_sync(2, nq * 32 + 64);
                float4 v[6]; float c[6];
#pragma unroll
                for (int i = 0; i < 6; i++) {
                    v[i] = (i < 5 || rank == 0) ? lds128(sa + i * 512) : make_float4(0, 0, 0, 0);
                    c[i] = (i < 5 || rank == 0) ? lds32(sc + i * 512) : 0.f;
                }
                float4 sv = add4(add4(add4(v[0], v[1]), add4(v[2], v[3])), add4(v[4], v[5]));
                float cv = ((c[0] + c[1]) + (c[2] + c[3])) + (c[4] + c[5]);
#pragma unroll
                for (int d = 1; d < 4; d++) {
                    const int dr = rank + d - (rank + d > 2 ? 3 : 0);
                    st_async4(mapa(da, dr), sv, mapa(barS, dr)); st_async1(mapa(dc, dr), cv, mapa(barS, dr));
                }
                TIM(5);
            }
            bar_sync(3, 256);
            float4 r = sum8(pl);
            vm0 = pack_bf16(r.x, r.y); vm1 = pack_bf16(r.z, r.w);
            TIM(7);
            if (!last) {
#pragma unroll
                for (int i = 0; i < NPRE_O; i++) ldsm4t(so[i], wl + (24 + i) * 512);
                mbar_wait(barS, s & 1);
                TIM(8);
                const uint32_t sx = sb + CH_SX + lane * 16;
                float4 a0 = lds128(sx), a1 = lds128(sx + 1280), a2 = lds128(sx + 2560);
                float4 b0 = lds128(sx + 512), b1 = lds128(sx + 512 + 1280), b2 = lds128(sx + 512 + 2560);
                float2 c0 = lds64(sx + 1024 - lane * 8), c1 = lds64(sx + 1024 + 1280 - lane * 8), c2 = lds64(sx + 1024 + 2560 - lane * 8);
                a0 = add4(add4(a0, a1), a2); b0 = add4(add4(b0, b1), b2);
                float sc[10] = {a0.x, a0.y, a0.z, a0.w, b0.x, b0.y, b0.z, b0.w, c0.x + c1.x + c2.x, c0.y + c1.y + c2.y};
                float mx = fmaxf(fmaxf(fmaxf(sc[0], sc[1]), fmaxf(sc[2], sc[3])), fmaxf(fmaxf(sc[4], sc[5]), fmaxf(sc[6], sc[7])));
                mx = fmaxf(mx, fmaxf(sc[8], sc[9]));
                mx = fmaxf(fmaxf(mx, __shfl_xor_sync(0xffffffffu, mx, 1)),
                           fmaxf(__shfl_xor_sync(0xffffffffu, mx, 2), __shfl_xor_sync(0xffffffffu, mx, 3)));
                const float cs = 0.08838834764831845f * 1.4426950408889634f;
                const float mb = -mx * cs;
#pragma unroll
                for (int j = 0; j < 10; j++) sc[j] = ex2(fmaf(sc[j], cs, mb));
                uint32_t pf[5];
#pragma unroll
                for (int j = 0; j < 5; j++) pf[j] = pack_bf16(sc[2 * j], sc[2 * j + 1]);
                float o0[4], o1[4], o2[4], o3[4], o4[4], o5[4];
                const uint32_t p0[4] = {pf[0], 0, pf[1], 0}, p1[4] = {pf[2], 0, pf[3], 0};
                mma16z(o0, p0, vt0[0], vt0[1]); mma16z(o1, p0, vt1[0], vt1[1]);
                mma16z(o2, p1, vt0[2], vt0[3]); mma16z(o3, p1, vt1[2], vt1[3]);
                mma8z(o4, pf[4], 0, vm0); mma8z(o5, pf[4], 0, vm1);
                float sum = (((sc[0] + sc[1]) + (sc[2] + sc[3])) + ((sc[4] + sc[5]) + (sc[6] + sc[7]))) + (sc[8] + sc[9]);
                sum = (sum + __shfl_xor_sync(0xffffffffu, sum, 1)) + (__shfl_xor_sync(0xffffffffu, sum, 2) + __shfl_xor_sync(0xffffffffu, sum, 3));
                const float inv = __fdividef(1.f, sum);
                const uint32_t ox = pack_bf16((o0[0] + o2[0] + o4[0]) * inv, (o0[1] + o2[1] + o4[1]) * inv);
                const uint32_t oy = pack_bf16((o1[0] + o3[0] + o5[0]) * inv, (o1[1] + o3[1] + o5[1]) * inv);
                st_pub(pub + slot, ox, oy); st_pub(pub + slot + 4096, ox, oy);
                bar_arrive(4, 256);
#pragma unroll
                for (int i = NPRE_O; i < 10; i++) ldsm4t(so[i], wl + (24 + i) * 512);
            }
            ((uint32_t*)kvo)[0] = movm(vm0); ((uint32_t*)kvo)[32] = movm(vm1);
        } else {
            *(uint32_t*)kvo = kf;
            if (last) bar_arrive(3, 256);
            else {
                bar_sync(3, 256);
                if (w == 2 && lane == 0) xload(s + 1);
                const uint32_t z = delay<2>(zero);
                GT(1, z);
#pragma unroll
                for (int i = 0; i < 10; i++) ldsm4t(so[i], wl + z + (24 + i) * 512);
                bar_sync(4, 256);
            }
        }
        if (last) return;
        uint2 c[11];
        const uint32_t z1 = delay<PV ? (DLO > 2 ? DLO - 2 : 0) : DLO>(zero);
        TIM(9);
        poll_issue<11>(c, o_rd + slot + z1, rank < 2);
        GT(2, z1);
        kvo += NH * 8 * DH;
        POLLCHK(11, c, o_rd + slot, 1);
        TIM(10);
        {
            float acc[4][4];
#pragma unroll
            for (int f = 0; f < 22; f++) {
                const int kk = f >> 1, a = f & 3;
                if (f < 4) mma16z(acc[a], so[f % 10], c[kk].x, c[kk].y);
                else mma16(acc[a], so[f % 10], c[kk].x, c[kk].y);
                if (f + 10 < 22) ldsm4t(so[f % 10], wl + (24 + f + 10) * 512);
            }
#pragma unroll
            for (int i = 0; i < 2; i++) {
#pragma unroll
                for (int j = 0; j < 4; j++) acc[i][j] += acc[i + 2][j];
                sts128(wl + CH_PART + i * 512, acc[i]);
            }
        }
        TIM(11);
        if (!PV && w < 2) {
            bar_sync(5, 256);
            float4 r = sum8(pl);
            if (!mown) {
                st_async4(mapa(sb + CH_MX + rank * 512 + lane * 16, w), r, mapa(barM, w));
                if (rank < 2 && lane == 0) st_async1(mapa(sb + CH_MX + rank * 4, 2), r.x, mapa(barM, 2));
            }
            bar_arrive(7, 256);
#pragma unroll
            for (int i = 0; i < 8; i++) ldsm4t(sw[i], wl + i * 512);
            mbar_wait(barX, (s + 1) & 1);
            if (!mown) {
                if (rank == 2 && w == 0) mbar_wait(barM, s & 1);
            } else {
                TIM(12);
                mbar_wait(barM, s & 1);
                TIM(13);
                float4 x = lds128(sb + CH_MX + (rank ^ 1) * 512 + lane * 16), y = lds128(sb + CH_MX + 2 * 512 + lane * 16);
                r = add4(add4(x, r), y);
                const uint32_t mx = movm(pack_bf16(r.x, r.y)), my = movm(pack_bf16(r.z, r.w));
                const uint32_t ns = (slot + 0x4000) & 0xC000;
                st_pub(pub + ns, mx, my); st_pub(pub + ns + 4096, mx, my);
                TIM(14);
            }
        } else {
            bar_arrive(5, 256);
            if (PV) { st_pub(pub + (slot ^ 0x8000), SENT, SENT); st_pub(pub + (slot ^ 0x8000) + 4096, SENT, SENT); }
            bar_sync(7, 256);
#pragma unroll
            for (int i = 0; i < 8; i++) ldsm4t(sw[i], wl + i * 512);
            GT(3, sw[0][0]);
            mbar_wait(barX, (s + 1) & 1);
        }
        bar_sync(6, 256);
    };
#pragma unroll 1
    for (int s = 0; s < NSEG - 1; s++) step(s, BoolC<false>());
    step(NSEG - 1, BoolC<true>());
}

__global__ void __cluster_dims__(3, 1, 1) __launch_bounds__(256, 1)
chain_kernel(const bf16* __restrict__ Wq, const bf16* __restrict__ Wk, const bf16* __restrict__ Wv, const bf16* __restrict__ Wo,
             int dly_o, int dly_m, int aware) {
    extern __shared__ __align__(1024) unsigned char smem[];
    const uint32_t sb = smem_u32(smem);
    const int tid = threadIdx.x, lane = tid & 31;
    const int w = __shfl_sync(0xffffffffu, tid >> 5, 0);
    int rank; asm("mov.u32 %0, %%cluster_ctarank;" : "=r"(rank));
    const int h = blockIdx.x / 3;
    const int nq = rank == 0 ? 6 : 5;
    const int u0 = rank == 0 ? 0 : 1 + 5 * rank;
    const int v0 = rank == 0 ? -6 : 3 * rank - 6;
    const int gw = rank * 8 + w;
    const int ks0 = gw < 16 ? 11 * gw : 176 + 10 * (gw - 16);
    const int nko = gw < 16 ? 11 : 10;
    const uint32_t wr = sb + w * CH_WREG;
    if (tid == 0) {
        mbar_init(sb + CH_BAR, 1); mbar_init(sb + CH_BAR + 8, 1); mbar_init(sb + CH_BAR + 16, 1);
        *(int*)(smem + CH_BAR + 24) = 0;
        asm volatile("fence.mbarrier_init.release.cluster;" ::: "memory");
    }
    uint32_t smid; asm("mov.u32 %0, %%smid;" : "=r"(smid));
    const int side = __shfl_sync(0xffffffffu, aware ? g_side[smid] ^ (aware - 1) : 0, 0);

    uint32_t wa[40][4];
    {
        const int r8 = lane & 7, p = lane >> 3;
        const bf16* src[4]; int tile[4], half[4];
#pragma unroll
        for (int q = 0; q < 4; q++) {
            int e = 4 * q + p;
            if (e < nq) { tile[q] = e; half[q] = 0; src[q] = Wq + h * DH + 8 * (u0 + e); }
            else if (e < 2 * nq) { tile[q] = e - nq; half[q] = 1; src[q] = Wk + h * DH + 8 * (u0 + e - nq); }
            else { int f = e - 2 * nq; tile[q] = nq + (f >> 1); half[q] = f & 1; src[q] = Wv + h * DH + 16 * (v0 + tile[q]) + 8 * half[q]; }
            src[q] += (size_t)(128 * w + r8) * HD;
        }
        const bf16* so = Wo + (size_t)(16 * ks0 + r8) * DM + 32 * h + 8 * p;
        const uint32_t dso = (p >> 1) * 512 + (p & 1) * 128 + r8 * 16;
#pragma unroll 1
        for (int kh = 0; kh < 16; kh++)
#pragma unroll
            for (int q = 0; q < 4; q++)
                if (tile[q] < 4 || tile[q] == 7) cp16(wr + (min(tile[q], 4) * 8 + (kh >> 1)) * 512 + ((kh & 1) * 2 + half[q]) * 128 + r8 * 16, src[q] + (size_t)kh * 8 * HD);
        asm volatile("cp.async.wait_all;" ::: "memory");
        __syncwarp();
#pragma unroll
        for (int i = 0; i < 40; i++) ldsm4t(wa[i], wr + i * 512 + lane * 16);
        __syncwarp();
#pragma unroll 1
        for (int kh = 0; kh < 16; kh++)
#pragma unroll
            for (int q = 0; q < 4; q++)
                if (tile[q] >= 4 && tile[q] < 7) cp16(wr + (tile[q] == 6 ? 16 + (kh >> 1) : (kh >> 1) * 2 + 5 - tile[q]) * 512 + ((kh & 1) * 2 + half[q]) * 128 + r8 * 16, src[q] + (size_t)kh * 8 * HD);
#pragma unroll 1
        for (int kh = 0; kh < 22; kh++) {
            uint32_t d = wr + (24 + (kh >> 1) * 2) * 512 + (kh & 1) * 256 + dso;
            if (kh < 2 * nko) cp16(d, so + (size_t)kh * 8 * DM);
            else asm volatile("st.shared.v4.u32 [%0], {%1,%1,%1,%1};" ::"r"(d), "r"(0) : "memory");
        }
        asm volatile("cp.async.wait_all;" ::: "memory");
    }
    __syncthreads();
    asm volatile("barrier.cluster.arrive.aligned; barrier.cluster.wait.aligned;" ::: "memory");
    if (w >= nq) chain_loop<true>(wa, sb, w, lane, rank, h, side);
    else chain_loop<false>(wa, sb, w, lane, rank, h, side);
}

__global__ void prep_kernel(const bf16* __restrict__ mem0) {
    int i = blockIdx.x * blockDim.x + threadIdx.x, n = gridDim.x * blockDim.x;
    char* ring = ring_base();
    for (int k = i; k < (1 << 17); k += n) {
        uint2 v = make_uint2(SENT, SENT);
        int off = k * 8, chunk = ((off >> 13) & 1) | ((off >> 16) << 1), slot = (off >> 14) & 3, in = off & 4095;
        if (chunk >= 24 && slot == 0 && in < 2048) {
            int ks = (chunk - 24) * 8 + (in >> 8), lane = (in >> 3) & 31;
            const uint32_t* p = (const uint32_t*)(mem0 + (lane >> 2) * DM + 16 * ks + 2 * (lane & 3));
            v.x = p[0]; v.y = p[4];
            if (v.x == SENT) v.x = 0x7FFF7FFFu;
        }
        *(uint2*)(ring + off) = v;
    }
}
__global__ void side_kernel() {
    if (threadIdx.x) return;
    uint32_t smid; asm("mov.u32 %0, %%smid;" : "=r"(smid));
    char* ring = ring_base();
    uint32_t* p0 = (uint32_t*)(ring + ring_off(smid & 15, 0) + 3072 + (smid >> 4) * 64);
    uint32_t* p1 = (uint32_t*)(ring + ring_off(smid & 15, 1) + 3072 + (smid >> 4) * 64);
    int b0 = 1 << 30, b1 = 1 << 30; uint32_t v = 0;
    for (int r = 0; r < 4; r++) {
        uint32_t t0 = clk(); v = atomicExch(p0 + (v == 5), r); uint32_t t1 = v == 77 ? clk() + 1 : clk(); b0 = min(b0, (int)(t1 - t0));
        t0 = clk(); v = atomicExch(p1 + (v == 5), r); t1 = v == 77 ? clk() + 1 : clk(); b1 = min(b1, (int)(t1 - t0));
    }
    g_side[smid] = b1 < b0;
}

__global__ void naive_gemm(const bf16* __restrict__ A, const bf16* __restrict__ B, bf16* __restrict__ C, int K, int N, int ldc) {
    __shared__ float As[16][65], Bs[16][65];
    int tx = threadIdx.x & 15, ty = threadIdx.x >> 4, m0 = blockIdx.y * 64, n0 = blockIdx.x * 64;
    float acc[4][4] = {};
    for (int k0 = 0; k0 < K; k0 += 16) {
        for (int e = threadIdx.x; e < 1024; e += 256) {
            As[e & 15][e >> 4] = __bfloat162float(A[(size_t)(m0 + (e >> 4)) * K + k0 + (e & 15)]);
            Bs[e >> 6][e & 63] = __bfloat162float(B[(size_t)(k0 + (e >> 6)) * N + n0 + (e & 63)]);
        }
        __syncthreads();
        for (int k = 0; k < 16; k++)
            for (int i = 0; i < 4; i++)
                for (int j = 0; j < 4; j++) acc[i][j] += As[k][ty * 4 + i] * Bs[k][tx * 4 + j];
        __syncthreads();
    }
    for (int i = 0; i < 4; i++)
        for (int j = 0; j < 4; j++) {
            int r = m0 + ty * 4 + i, c = n0 + tx * 4 + j;
            C[ldc ? (size_t)r * ldc + c : (size_t)((r >> 5) * 512 + (c >> 3)) * 256 + (r & 31) * 8 + (c & 7)] = __float2bfloat16(acc[i][j]);
        }
}
__global__ void naive_attn() {
    int s = blockIdx.x, h = blockIdx.y, tid = threadIdx.x;
    __shared__ float k[40][129], v[40][129], p[32][41];
    const bf16* q = g_qx + (size_t)(s * 32) * HD + h * DH;
    for (int r = 0; r < 40; r++) {
        int im = (s * NH + h) * 1024 + (tid >> 3) * 64 + r * 8 + (tid & 7), ix = (s * NH + h) * 4096 + (tid >> 3) * 256 + (r - 8) * 8 + (tid & 7);
        k[r][tid] = __bfloat162float(r < 8 ? g_km[im] : g_kx[ix]);
        v[r][tid] = __bfloat162float(r < 8 ? g_vm[im] : g_vx[ix]);
    }
    __syncthreads();
    for (int e = tid; e < 32 * 40; e += 128) {
        int r = e / 40, c = e % 40; float a = 0;
        for (int d = 0; d < 128; d++) a += __bfloat162float(q[(size_t)r * HD + d]) * k[c][d];
        p[r][c] = (c <= r + 8) ? a * 0.08838834764831845f : -1e9f;
    }
    __syncthreads();
    if (tid < 32) {
        float mx = -1e30f, sum = 0;
        for (int c = 0; c < 40; c++) mx = fmaxf(mx, p[tid][c]);
        for (int c = 0; c < 40; c++) { p[tid][c] = __expf(p[tid][c] - mx); sum += p[tid][c]; }
        for (int c = 0; c < 40; c++) p[tid][c] /= sum;
    }
    __syncthreads();
    for (int r = 0; r < 32; r++) {
        float a = 0;
        for (int c = 0; c < 40; c++) a += p[r][c] * v[c][tid];
        g_ox[(size_t)(s * 32 + r) * HD + h * DH + tid] = __float2bfloat16(a);
    }
}
__global__ void naive_kgen(const bf16* Are, const bf16* Aim, const bf16* Bre, const bf16* Bim, const bf16* Cre, const bf16* Cim, const bf16* ldt) {
    int d = blockIdx.x;
    __shared__ float zr[128], zi[128], cr[128], ci[128];
    float dt = __bfloat162float(__float2bfloat16(expf(__bfloat162float(ldt[d]))));
    if (threadIdx.x < 128) {
        int i = d * 128 + threadIdx.x;
        zr[threadIdx.x] = dt * __bfloat162float(Are[i]); zi[threadIdx.x] = dt * __bfloat162float(Aim[i]);
        float br = dt * __bfloat162float(Bre[i]), bi = dt * __bfloat162float(Bim[i]), a = __bfloat162float(Cre[i]), b = __bfloat162float(Cim[i]);
        cr[threadIdx.x] = a * br - b * bi; ci[threadIdx.x] = a * bi + b * br;
    }
    __syncthreads();
    for (int l = threadIdx.x; l < S_LEN; l += blockDim.x) {
        float lf = __bfloat162float(__float2bfloat16((float)l)), acc = 0;
        for (int n = 0; n < 128; n++) {
            float e = expf(zr[n] * lf), sn, cn;
            sincosf(zi[n] * lf, &sn, &cn);
            acc += e * (cr[n] * cn - ci[n] * sn);
        }
        g_K[d * S_LEN + l] = acc;
    }
}
__global__ void naive_conv(const bf16* u, const bf16* Dskip, bf16* out) {
    int d = blockIdx.x;
    __shared__ float K[2048], U[2048];
    for (int l = threadIdx.x; l < S_LEN; l += blockDim.x) { K[l] = g_K[d * S_LEN + l]; U[l] = __bfloat162float(u[l * DM + d]); }
    __syncthreads();
    float ds = __bfloat162float(Dskip[d]);
    for (int l = threadIdx.x; l < S_LEN; l += blockDim.x) {
        float acc = 0;
        for (int j = 0; j <= l; j++) acc += K[j] * U[l - j];
        float y = __bfloat162float(__float2bfloat16(acc)) + __bfloat162float(__float2bfloat16(U[l] * ds));
        out[(size_t)l * 2048 + 1024 + d] = __float2bfloat16(y);
    }
}

extern "C" void kernel_launch(void* const* d_in, const int* in_sizes, int n_in, void* d_out, int out_size) {
    const bf16* x = (const bf16*)d_in[0];
    const bf16* mem0 = (const bf16*)d_in[1];
    const bf16 *Wq = (const bf16*)d_in[2], *Wk = (const bf16*)d_in[3], *Wv = (const bf16*)d_in[4], *Wo = (const bf16*)d_in[5];
    const bf16* u = (const bf16*)d_in[7];
    bf16* out = (bf16*)d_out;
    static bf16 *qx = nullptr, *kx, *vx, *ox;
    if (!qx) {
        cudaGetSymbolAddress((void**)&qx, g_qx); cudaGetSymbolAddress((void**)&kx, g_kx);
        cudaGetSymbolAddress((void**)&vx, g_vx); cudaGetSymbolAddress((void**)&ox, g_ox);
        cudaFuncSetAttribute(chain_kernel, cudaFuncAttributeMaxDynamicSharedMemorySize, CH_SMEM);
    }
    int dly_o = 0, dly_m = 0, aware = 1;
    naive_gemm<<<dim3(64, 32), 256>>>(x, Wq, qx, DM, HD, HD);
    naive_gemm<<<dim3(64, 32), 256>>>(x, Wk, kx, DM, HD, 0);
    naive_gemm<<<dim3(64, 32), 256>>>(x, Wv, vx, DM, HD, 0);
    prep_kernel<<<132, 256>>>(mem0);
    side_kernel<<<132, 32>>>();
    chain_kernel<<<96, 256, CH_SMEM>>>(Wq, Wk, Wv, Wo, dly_o, dly_m, aware);
    naive_attn<<<dim3(64, 32), 128>>>();
    naive_gemm<<<dim3(16, 32), 256>>>(ox, Wo, out, HD, DM, 2048);
    naive_kgen<<<1024, 256>>>((const bf16*)d_in[8], (const bf16*)d_in[9], (const bf16*)d_in[10], (const bf16*)d_in[11],
                              (const bf16*)d_in[12], (const bf16*)d_in[13], (const bf16*)d_in[14]);
    naive_conv<<<1024, 256>>>(u, (const bf16*)d_in[15], out);
}
```

```cpp
#include <cuda.h>
#include <cuda_runtime.h>
#include <cuda_bf16.h>
#include <stdint.h>
#include <stdio.h>
#include <string.h>

typedef __nv_bfloat16 bf16;

constexpr int S_LEN = 2048, DM = 1024, NH = 32, DH = 128, HD = 4096, NSEG = 64;
constexpr uint32_t SENT = 0xFFFFFFFFu;
constexpr int SPIN_LIMIT = 1 << 18;

__device__ __align__(1024) bf16 g_kx[S_LEN * HD];
__device__ __align__(1024) bf16 g_vx[S_LEN * HD];
__device__ __align__(1024) bf16 g_ox[S_LEN * HD];
__device__ __align__(1024) bf16 g_km[NSEG * NH * 8 * DH];
__device__ __align__(1024) bf16 g_vm[NSEG * NH * 8 * DH];
__device__ __align__(1024) char g_ring[2 << 20];
__device__ int g_side[256];
constexpr int C_QA_NEXT = 0, C_O_NEXT = 16, C_CHAIN = 32, C_QA_DONE = 64, C_S4_NEXT = 96, N_CTR = 128;
__device__ int g_ctr[N_CTR];
#define S4_FIRST 20

__device__ __forceinline__ uint32_t smem_u32(const void* p) { return (uint32_t)__cvta_generic_to_shared(p); }
__device__ __forceinline__ uint32_t clk() { uint32_t c; asm volatile("mov.u32 %0, %%clock;" : "=r"(c)::"memory"); return c; }
__device__ __forceinline__ uint32_t pack_bf16(float lo, float hi) {
    uint32_t r; asm("cvt.rn.bf16x2.f32 %0, %1, %2;" : "=r"(r) : "f"(hi), "f"(lo)); return r;
}
__device__ __forceinline__ uint32_t movm(uint32_t a) {
    uint32_t d; asm volatile("movmatrix.sync.aligned.m8n8.trans.b16 %0, %1;" : "=r"(d) : "r"(a)); return d;
}
__device__ __forceinline__ void mma16(float (&d)[4], const uint32_t (&a)[4], uint32_t b0, uint32_t b1) {
    asm volatile("mma.sync.aligned.m16n8k16.row.col.f32.bf16.bf16.f32 {%0,%1,%2,%3}, {%4,%5,%6,%7}, {%8,%9}, {%0,%1,%2,%3};"
        : "+f"(d[0]), "+f"(d[1]), "+f"(d[2]), "+f"(d[3]) : "r"(a[0]), "r"(a[1]), "r"(a[2]), "r"(a[3]), "r"(b0), "r"(b1));
}
__device__ __forceinline__ void mma16z(float (&d)[4], const uint32_t (&a)[4], uint32_t b0, uint32_t b1) {
    asm volatile("mma.sync.aligned.m16n8k16.row.col.f32.bf16.bf16.f32 {%0,%1,%2,%3}, {%4,%5,%6,%7}, {%8,%9}, {%10,%10,%10,%10};"
        : "=f"(d[0]), "=f"(d[1]), "=f"(d[2]), "=f"(d[3]) : "r"(a[0]), "r"(a[1]), "r"(a[2]), "r"(a[3]), "r"(b0), "r"(b1), "f"(0.f));
}
__device__ __forceinline__ void mma8z(float (&d)[4], uint32_t a0, uint32_t a1, uint32_t b0) {
    asm volatile("mma.sync.aligned.m16n8k8.row.col.f32.bf16.bf16.f32 {%0,%1,%2,%3}, {%4,%5}, {%6}, {%7,%7,%7,%7};"
        : "=f"(d[0]), "=f"(d[1]), "=f"(d[2]), "=f"(d[3]) : "r"(a0), "r"(a1), "r"(b0), "f"(0.f));
}
__device__ __forceinline__ void ldsm4t(uint32_t (&r)[4], uint32_t addr) {
    asm volatile("ldmatrix.sync.aligned.m8n8.x4.trans.shared.b16 {%0,%1,%2,%3}, [%4];"
        : "=r"(r[0]), "=r"(r[1]), "=r"(r[2]), "=r"(r[3]) : "r"(addr) : "memory");
}
__device__ __forceinline__ void ldsm4(uint32_t (&r)[4], uint32_t addr) {
    asm volatile("ldmatrix.sync.aligned.m8n8.x4.shared.b16 {%0,%1,%2,%3}, [%4];"
        : "=r"(r[0]), "=r"(r[1]), "=r"(r[2]), "=r"(r[3]) : "r"(addr) : "memory");
}
__device__ __forceinline__ float lds32(uint32_t a) {
    float v; asm volatile("ld.shared.f32 %0, [%1];" : "=f"(v) : "r"(a) : "memory"); return v;
}
__device__ __forceinline__ void st_async1(uint32_t dst, float v, uint32_t bar) {
    asm volatile("st.async.shared::cluster.mbarrier::complete_tx::bytes.f32 [%0], %1, [%2];" ::"r"(dst), "f"(v), "r"(bar) : "memory");
}
__device__ __forceinline__ void cp16(uint32_t dst, const void* src) {
    asm volatile("cp.async.cg.shared.global [%0], [%1], 16;" ::"r"(dst), "l"(src) : "memory");
}
__device__ __forceinline__ void sts128(uint32_t a, const float (&v)[4]) {
    asm volatile("st.shared.v4.f32 [%0], {%1,%2,%3,%4};" ::"r"(a), "f"(v[0]), "f"(v[1]), "f"(v[2]), "f"(v[3]) : "memory");
}
__device__ __forceinline__ float4 lds128(uint32_t a) {
    float4 v; asm volatile("ld.shared.v4.f32 {%0,%1,%2,%3}, [%4];" : "=f"(v.x), "=f"(v.y), "=f"(v.z), "=f"(v.w) : "r"(a) : "memory"); return v;
}
__device__ __forceinline__ void sts64(uint32_t a, float x, float y) {
    asm volatile("st.shared.v2.f32 [%0], {%1,%2};" ::"r"(a), "f"(x), "f"(y) : "memory");
}
__device__ __forceinline__ float2 lds64(uint32_t a) {
    float2 v; asm volatile("ld.shared.v2.f32 {%0,%1}, [%2];" : "=f"(v.x), "=f"(v.y) : "r"(a) : "memory"); return v;
}
__device__ __forceinline__ void bar_sync(int id, int n) { asm volatile("bar.sync %0, %1;" ::"r"(id), "r"(n) : "memory"); }
__device__ __forceinline__ void bar_arrive(int id, int n) { asm volatile("bar.arrive %0, %1;" ::"r"(id), "r"(n) : "memory"); }
__device__ __forceinline__ uint32_t mapa(uint32_t a, uint32_t r) {
    uint32_t o; asm("mapa.shared::cluster.u32 %0, %1, %2;" : "=r"(o) : "r"(a), "r"(r)); return o;
}
__device__ __forceinline__ void st_async4(uint32_t dst, float4 v, uint32_t bar) {
    asm volatile("st.async.shared::cluster.mbarrier::complete_tx::bytes.v4.f32 [%0], {%1,%2,%3,%4}, [%5];"
        ::"r"(dst), "f"(v.x), "f"(v.y), "f"(v.z), "f"(v.w), "r"(bar) : "memory");
}
__device__ __forceinline__ void mbar_init(uint32_t bar, int n) { asm volatile("mbarrier.init.shared.b64 [%0], %1;" ::"r"(bar), "r"(n) : "memory"); }
__device__ __forceinline__ void mbar_expect(uint32_t bar, int bytes) {
    asm volatile("mbarrier.arrive.expect_tx.shared.b64 _, [%0], %1;" ::"r"(bar), "r"(bytes) : "memory");
}
__device__ __forceinline__ void bulk_load(uint32_t dst, const void* src, int bytes, uint32_t bar) {
    asm volatile("cp.async.bulk.shared::cluster.global.mbarrier::complete_tx::bytes [%0], [%1], %2, [%3];"
        ::"r"(dst), "l"(src), "r"(bytes), "r"(bar) : "memory");
}
__device__ __forceinline__ bool mbar_try(uint32_t bar, uint32_t par) {
    uint32_t ok;
    asm volatile("{.reg .pred p; mbarrier.try_wait.parity.shared::cta.b64 p, [%1], %2; selp.u32 %0, 1, 0, p;}"
        : "=r"(ok) : "r"(bar), "r"(par) : "memory");
    return ok;
}
__device__ __forceinline__ void mbar_wait(uint32_t bar, uint32_t par) {
    if (!mbar_try(bar, par))
        for (int it = 0; it < SPIN_LIMIT && !mbar_try(bar, par); it++) {}
}
__device__ __forceinline__ void mbar_wait_long(uint32_t bar, uint32_t par) {
    for (int it = 0; it < (1 << 24) && !mbar_try(bar, par); it++) {}
}
__device__ __forceinline__ float4 add4(float4 a, float4 b) { return make_float4(a.x + b.x, a.y + b.y, a.z + b.z, a.w + b.w); }
__device__ __forceinline__ float ex2(float x) { float y; asm("ex2.approx.ftz.f32 %0, %1;" : "=f"(y) : "f"(x)); return y; }

__device__ __forceinline__ void wgmma256(float (&d)[128], uint64_t da, uint64_t db, int acc) {
    asm volatile("{.reg .pred p; setp.ne.b32 p, %130, 0;\n"
        "wgmma.mma_async.sync.aligned.m64n256k16.f32.bf16.bf16 {"
        "%0,%1,%2,%3,%4,%5,%6,%7,%8,%9,%10,%11,%12,%13,%14,%15,"
        "%16,%17,%18,%19,%20,%21,%22,%23,%24,%25,%26,%27,%28,%29,%30,%31,"
        "%32,%33,%34,%35,%36,%37,%38,%39,%40,%41,%42,%43,%44,%45,%46,%47,"
        "%48,%49,%50,%51,%52,%53,%54,%55,%56,%57,%58,%59,%60,%61,%62,%63,"
        "%64,%65,%66,%67,%68,%69,%70,%71,%72,%73,%74,%75,%76,%77,%78,%79,"
        "%80,%81,%82,%83,%84,%85,%86,%87,%88,%89,%90,%91,%92,%93,%94,%95,"
        "%96,%97,%98,%99,%100,%101,%102,%103,%104,%105,%106,%107,%108,%109,%110,%111,"
        "%112,%113,%114,%115,%116,%117,%118,%119,%120,%121,%122,%123,%124,%125,%126,%127"
        "}, %128, %129, p, 1, 1, 0, 1;}"
        : "+f"(d[0]), "+f"(d[1]), "+f"(d[2]), "+f"(d[3]), "+f"(d[4]), "+f"(d[5]), "+f"(d[6]), "+f"(d[7]), "+f"(d[8]), "+f"(d[9]), "+f"(d[10]), "+f"(d[11]), "+f"(d[12]), "+f"(d[13]), "+f"(d[14]), "+f"(d[15]), "+f"(d[16]), "+f"(d[17]), "+f"(d[18]), "+f"(d[19]), "+f"(d[20]), "+f"(d[21]), "+f"(d[22]), "+f"(d[23]), "+f"(d[24]), "+f"(d[25]), "+f"(d[26]), "+f"(d[27]), "+f"(d[28]), "+f"(d[29]), "+f"(d[30]), "+f"(d[31]), "+f"(d[32]), "+f"(d[33]), "+f"(d[34]), "+f"(d[35]), "+f"(d[36]), "+f"(d[37]), "+f"(d[38]), "+f"(d[39]), "+f"(d[40]), "+f"(d[41]), "+f"(d[42]), "+f"(d[43]), "+f"(d[44]), "+f"(d[45]), "+f"(d[46]), "+f"(d[47]), "+f"(d[48]), "+f"(d[49]), "+f"(d[50]), "+f"(d[51]), "+f"(d[52]), "+f"(d[53]), "+f"(d[54]), "+f"(d[55]), "+f"(d[56]), "+f"(d[57]), "+f"(d[58]), "+f"(d[59]), "+f"(d[60]), "+f"(d[61]), "+f"(d[62]), "+f"(d[63]), "+f"(d[64]), "+f"(d[65]), "+f"(d[66]), "+f"(d[67]), "+f"(d[68]), "+f"(d[69]), "+f"(d[70]), "+f"(d[71]), "+f"(d[72]), "+f"(d[73]), "+f"(d[74]), "+f"(d[75]), "+f"(d[76]), "+f"(d[77]), "+f"(d[78]), "+f"(d[79]), "+f"(d[80]), "+f"(d[81]), "+f"(d[82]), "+f"(d[83]), "+f"(d[84]), "+f"(d[85]), "+f"(d[86]), "+f"(d[87]), "+f"(d[88]), "+f"(d[89]), "+f"(d[90]), "+f"(d[91]), "+f"(d[92]), "+f"(d[93]), "+f"(d[94]), "+f"(d[95]), "+f"(d[96]), "+f"(d[97]), "+f"(d[98]), "+f"(d[99]), "+f"(d[100]), "+f"(d[101]), "+f"(d[102]), "+f"(d[103]), "+f"(d[104]), "+f"(d[105]), "+f"(d[106]), "+f"(d[107]), "+f"(d[108]), "+f"(d[109]), "+f"(d[110]), "+f"(d[111]), "+f"(d[112]), "+f"(d[113]), "+f"(d[114]), "+f"(d[115]), "+f"(d[116]), "+f"(d[117]), "+f"(d[118]), "+f"(d[119]), "+f"(d[120]), "+f"(d[121]), "+f"(d[122]), "+f"(d[123]), "+f"(d[124]), "+f"(d[125]), "+f"(d[126]), "+f"(d[127])
        : "l"(da), "l"(db), "r"(acc));
}
__device__ __forceinline__ void wgmma128(float (&d)[64], uint64_t da, uint64_t db, int acc) {
    asm volatile("{.reg .pred p; setp.ne.b32 p, %66, 0;\n"
        "wgmma.mma_async.sync.aligned.m64n128k16.f32.bf16.bf16 {"
        "%0,%1,%2,%3,%4,%5,%6,%7,%8,%9,%10,%11,%12,%13,%14,%15,"
        "%16,%17,%18,%19,%20,%21,%22,%23,%24,%25,%26,%27,%28,%29,%30,%31,"
        "%32,%33,%34,%35,%36,%37,%38,%39,%40,%41,%42,%43,%44,%45,%46,%47,"
        "%48,%49,%50,%51,%52,%53,%54,%55,%56,%57,%58,%59,%60,%61,%62,%63"
        "}, %64, %65, p, 1, 1, 0, 1;}"
        : "+f"(d[0]), "+f"(d[1]), "+f"(d[2]), "+f"(d[3]), "+f"(d[4]), "+f"(d[5]), "+f"(d[6]), "+f"(d[7]), "+f"(d[8]), "+f"(d[9]), "+f"(d[10]), "+f"(d[11]), "+f"(d[12]), "+f"(d[13]), "+f"(d[14]), "+f"(d[15]), "+f"(d[16]), "+f"(d[17]), "+f"(d[18]), "+f"(d[19]), "+f"(d[20]), "+f"(d[21]), "+f"(d[22]), "+f"(d[23]), "+f"(d[24]), "+f"(d[25]), "+f"(d[26]), "+f"(d[27]), "+f"(d[28]), "+f"(d[29]), "+f"(d[30]), "+f"(d[31]), "+f"(d[32]), "+f"(d[33]), "+f"(d[34]), "+f"(d[35]), "+f"(d[36]), "+f"(d[37]), "+f"(d[38]), "+f"(d[39]), "+f"(d[40]), "+f"(d[41]), "+f"(d[42]), "+f"(d[43]), "+f"(d[44]), "+f"(d[45]), "+f"(d[46]), "+f"(d[47]), "+f"(d[48]), "+f"(d[49]), "+f"(d[50]), "+f"(d[51]), "+f"(d[52]), "+f"(d[53]), "+f"(d[54]), "+f"(d[55]), "+f"(d[56]), "+f"(d[57]), "+f"(d[58]), "+f"(d[59]), "+f"(d[60]), "+f"(d[61]), "+f"(d[62]), "+f"(d[63])
        : "l"(da), "l"(db), "r"(acc));
}
__device__ __forceinline__ void wg_fence() { asm volatile("wgmma.fence.sync.aligned;" ::: "memory"); }
__device__ __forceinline__ void wg_commit() { asm volatile("wgmma.commit_group.sync.aligned;" ::: "memory"); }
template <int N> __device__ __forceinline__ void wg_wait() { asm volatile("wgmma.wait_group.sync.aligned %0;" ::"n"(N) : "memory"); }
__device__ __forceinline__ uint64_t mkdesc(uint32_t addr, uint32_t lbo, uint32_t sbo, uint32_t sw) {
    return (uint64_t)((addr & 0x3FFFF) >> 4) | ((uint64_t)(lbo >> 4) << 16) | ((uint64_t)(sbo >> 4) << 32) | ((uint64_t)sw << 62);
}
__device__ __forceinline__ void tma2d(uint32_t dst, const CUtensorMap* m, int c0, int c1, uint32_t bar) {
    asm volatile("cp.async.bulk.tensor.2d.shared::cluster.global.mbarrier::complete_tx::bytes [%0], [%1, {%2, %3}], [%4];"
        ::"r"(dst), "l"(m), "r"(c0), "r"(c1), "r"(bar) : "memory");
}
__device__ __forceinline__ void tma3d(uint32_t dst, const CUtensorMap* m, int c0, int c1, int c2, uint32_t bar) {
    asm volatile("cp.async.bulk.tensor.3d.shared::cluster.global.mbarrier::complete_tx::bytes [%0], [%1, {%2, %3, %4}], [%5];"
        ::"r"(dst), "l"(m), "r"(c0), "r"(c1), "r"(c2), "r"(bar) : "memory");
}
__device__ __forceinline__ void tma3d_mc(uint32_t dst, const CUtensorMap* m, int c0, int c1, int c2, uint32_t bar, uint16_t mask) {
    asm volatile("cp.async.bulk.tensor.3d.shared::cluster.global.mbarrier::complete_tx::bytes.multicast::cluster [%0], [%1, {%2, %3, %4}], [%5], %6;"
        ::"r"(dst), "l"(m), "r"(c0), "r"(c1), "r"(c2), "r"(bar), "h"(mask) : "memory");
}
__device__ __forceinline__ void mbar_arrive(uint32_t bar) { asm volatile("mbarrier.arrive.shared.b64 _, [%0];" ::"r"(bar) : "memory"); }
__device__ __forceinline__ void mbar_arrive_remote(uint32_t bar) {
    asm volatile("mbarrier.arrive.shared::cluster.b64 _, [%0];" ::"r"(bar) : "memory");
}
template <int R> __device__ __forceinline__ void reg_inc() { asm volatile("setmaxnreg.inc.sync.aligned.u32 %0;" ::"n"(R)); }
template <int R> __device__ __forceinline__ void reg_dec() { asm volatile("setmaxnreg.dec.sync.aligned.u32 %0;" ::"n"(R)); }

constexpr int CH_NRES = 46;
constexpr int CH_PART = CH_NRES * 512;
constexpr int CH_WREG = CH_PART + 8 * 512;
constexpr int CH_SX = 8 * CH_WREG;
constexpr int CH_MX = CH_SX + 3 * 1280;
constexpr int CH_XS = CH_MX + 3 * 512;
constexpr int CH_BAR = CH_XS + 5632;
constexpr int CH_SMEM = CH_BAR + 48;

__device__ __forceinline__ char* ring_base() { return (char*)(((uintptr_t)g_ring + (1 << 20) - 1) & ~(uintptr_t)((1 << 20) - 1)); }
__device__ __forceinline__ uint32_t ring_off(int chunk, int side) {
    uint32_t o = ((chunk & 1) << 13) | ((chunk >> 1) << 16);
    uint32_t par = ((o >> 13) ^ (o >> 16) ^ (o >> 17) ^ (o >> 19) ^ side) & 1;
    return o | (par << 12);
}
__device__ __forceinline__ uint2 ld_poll(const char* p) {
    unsigned long long v; asm volatile("ld.relaxed.gpu.global.b64 %0, [%1];" : "=l"(v) : "l"(p) : "memory");
    return make_uint2((uint32_t)v, (uint32_t)(v >> 32));
}
__device__ __forceinline__ void st_pub(char* p, uint32_t x, uint32_t y) {
    unsigned long long v = ((unsigned long long)y << 32) | x;
    asm volatile("st.relaxed.gpu.global.b64 [%0], %1;" ::"l"(p), "l"(v) : "memory");
}
template <int N>
__device__ __forceinline__ void poll_issue(uint2 (&b)[N], const char* p, bool lastvalid) {
#pragma unroll
    for (int i = 0; i < N; i++) {
        if (i < N - 1 || lastvalid) b[i] = ld_poll(p + i * 256);
        else b[i] = make_uint2(0, 0);
    }
}
template <int N>
__device__ __forceinline__ int poll_check(uint2 (&b)[N], const char* p) {
    int it = 0;
    uint32_t mx = b[0].x;
#pragma unroll
    for (int i = 1; i < N; i++) mx = max(mx, b[i].x);
    if (__any_sync(0xffffffffu, mx == SENT)) {
        while (it++ < SPIN_LIMIT) {
#pragma unroll
            for (int i = 0; i < N; i++)
                if (b[i].x == SENT) b[i] = ld_poll(p + i * 256);
            mx = b[0].x;
#pragma unroll
            for (int i = 1; i < N; i++) mx = max(mx, b[i].x);
            if (!__any_sync(0xffffffffu, mx == SENT)) break;
        }
    }
    return it;
}
__device__ __forceinline__ float4 sum8(uint32_t a) {
    float4 v[8];
#pragma unroll
    for (int i = 0; i < 8; i++) v[i] = lds128(a + i * CH_WREG);
    return add4(add4(add4(v[0], v[1]), add4(v[2], v[3])), add4(add4(v[4], v[5]), add4(v[6], v[7])));
}
template <int N>
__device__ __forceinline__ uint32_t delay(uint32_t a) {
    uint32_t z = 0;
#pragma unroll
    for (int i = 0; i < N; i++) asm volatile("ld.volatile.shared.u32 %0, [%1];" : "=r"(z) : "r"(a + z) : "memory");
    return z;
}

#define TIM(i)
#define GT(i, z)
#define POLLCHK(N, arr, p, i) poll_check<N>(arr, p)

template <bool B> struct BoolC { static constexpr bool value = B; };
#define DLM 6
#define DLO 8
#define NPRE_O 4
template <bool PV>
__device__ __forceinline__ void chain_loop(const uint32_t (&wa)[40][4], const uint32_t sb, const int w, const int lane, const int rank,
                                           const int h, const int side) {
    const int nq = rank == 0 ? 6 : 5, u0 = rank == 0 ? 0 : 1 + 5 * rank, v0 = rank == 0 ? -6 : 3 * rank - 6;
    const int gw = rank * 8 + w;
    const uint32_t wl = sb + w * CH_WREG + lane * 16;
    const uint32_t pl = sb + CH_PART + w * 512 + lane * 16;
    const uint32_t barS = sb + CH_BAR, barM = barS + 8, barX = barS + 16, zero = barS + 24;
    char* const ring = ring_base();
    const char* const m_rd = ring + ring_off(24 + w, side) + lane * 8;
    const char* const o_rd = ring + ring_off(gw, side) + lane * 8;
    char* pub;
    if (PV) {
        int ks = h * 8 + v0 + w, cw = ks < 176 ? ks / 11 : 16 + (ks - 176) / 10, c0 = cw < 16 ? 11 * cw : 176 + 10 * (cw - 16);
        pub = ring + (ring_off(cw, 0) & ~4096u) + (ks - c0) * 256 + lane * 8;
    } else {
        int ks = 2 * h + w;
        pub = ring + (ring_off(24 + (ks >> 3), 0) & ~4096u) + (ks & 7) * 256 + lane * 8;
    }
    const uint32_t xs = sb + CH_XS + (PV ? nq * 512 + (w - nq) * 1024 : w * 512) + lane * 16;
    bf16* kvo = (PV ? g_vm + 128 * (v0 + w) : g_km + 64 * (u0 + w)) + h * 1024 + 2 * lane;
    const bool mown = !PV && w == rank && rank < 2;
    auto xload = [&](int s) {
        mbar_expect(barX, 8192 - nq * 512);
        bulk_load(sb + CH_XS, g_kx + (size_t)(s * NH + h) * 4096 + u0 * 256, nq * 512, barX);
        bulk_load(sb + CH_XS + nq * 512, g_vx + (size_t)(s * NH + h) * 4096 + (v0 + nq) * 512, (8 - nq) * 1024, barX);
    };
    if (!PV && w == 2 && lane == 0) xload(0);
    uint32_t sw[8][4];
#pragma unroll
    for (int i = 0; i < 8; i++) ldsm4t(sw[i], wl + i * 512);
    mbar_wait(barX, 0);

    auto step = [&](const int s, auto lastc) {
        constexpr bool last = decltype(lastc)::value;
        const uint32_t slot = (s & 3) << 14;
        uint2 b[8];
        const uint32_t z0 = delay<DLM>(zero);
        TIM(0);
        poll_issue<8>(b, m_rd + slot + z0, true);
        GT(0, z0);
        if (!last) {
            if (PV) { if (w == 7 && lane == 0) mbar_expect(barS, 3 * 1280); }
            else {
                if (w == (rank & 1) && lane == 0) mbar_expect(barM, rank < 2 ? 2 * 512 : 8);
                if (mown) { st_pub(pub + (slot ^ 0x8000), SENT, SENT); st_pub(pub + (slot ^ 0x8000) + 4096, SENT, SENT); }
            }
        }
        POLLCHK(8, b, m_rd + slot, 0);
        TIM(1);
        {
            float acc[6][4];
#pragma unroll
            for (int kk = 0; kk < 8; kk++) {
                const int j = (2 * kk) & 7;
                if (kk == 0) { mma16z(acc[5], sw[0], b[0].x, b[0].y); mma16z(acc[4], sw[1], b[0].x, b[0].y); }
                else { mma16(acc[5], sw[j], b[kk].x, b[kk].y); mma16(acc[4], sw[j + 1], b[kk].x, b[kk].y); }
#pragma unroll
                for (int i = 0; i < 4; i++) {
                    if (kk == 0) mma16z(acc[i], wa[i * 8], b[0].x, b[0].y);
                    else mma16(acc[i], wa[i * 8 + kk], b[kk].x, b[kk].y);
                    if (i < 2) ldsm4t(sw[j + i], wl + (8 + 2 * kk + i) * 512);
                }
            }
#pragma unroll
            for (int i = 0; i < 6; i++) sts128(wl + CH_PART + ((i + 4) % 6) * 512, acc[(i + 4) % 6]);
        }
        TIM(2);
        float va[4][4];
        uint32_t kf;
        if (!PV) {
            uint32_t xf[4];
            bar_sync(1, 256);
            float4 v[8];
#pragma unroll
            for (int i = 0; i < 8; i++) v[i] = lds128(pl + i * CH_WREG);
            ldsm4(xf, xs);
            float4 r = add4(add4(add4(v[0], v[1]), add4(v[2], v[3])), add4(add4(v[4], v[5]), add4(v[6], v[7])));
            uint32_t qf = movm(pack_bf16(r.x, r.y));
            kf = movm(pack_bf16(r.z, r.w));
            if (!last) {
                float s0[4], s1[4], s2[4], s3[4], s4[4];
                mma8z(s0, qf, 0, xf[0]); mma8z(s1, qf, 0, xf[1]); mma8z(s2, qf, 0, xf[2]); mma8z(s3, qf, 0, xf[3]);
                mma8z(s4, qf, 0, kf);
                const float x0[4] = {s0[0], s0[1], s1[0], s1[1]}, x1[4] = {s2[0], s2[1], s3[0], s3[1]};
                sts128(pl, x0); sts128(pl + CH_WREG, x1);
                sts64(pl + 2 * CH_WREG - lane * 8, s4[0], s4[1]);
                bar_arrive(2, nq * 32 + 64);
            }
            TIM(4);
        } else {
            bar_sync(1, 256);
        }
        {
            const float z = __uint_as_float(delay<1>(zero));
#pragma unroll
            for (int i = 0; i < 4; i++) va[i][0] = va[i][1] = va[i][2] = va[i][3] = z;
        }
#pragma unroll
        for (int kk = 0; kk < 8; kk++) {
            mma16(va[kk & 1], sw[kk], b[kk].x, b[kk].y);
            mma16(va[2 + (kk & 1)], wa[32 + kk], b[kk].x, b[kk].y);
        }
#pragma unroll
        for (int j = 0; j < 4; j++) { va[0][j] += va[1][j]; va[2][j] += va[3][j]; }
        sts128(wl + CH_PART + 6 * 512, va[0]);
        sts128(wl + CH_PART + 7 * 512, va[2]);
        TIM(6);
        uint32_t vm0, vm1;
        uint32_t so[10][4];
        if (PV) {
            uint32_t vt0[4], vt1[4];
            ldsm4t(vt0, xs); ldsm4t(vt1, xs + 512);
            if (w >= 6 && !last) {
                const uint32_t sa = sb + CH_PART + (w - 6) * CH_WREG + lane * 16, sc = sb + CH_PART + 2 * CH_WREG + (w - 6) * 128 + lane * 4;
                const uint32_t da = sb + CH_SX + rank * 1280 + (w - 6) * 512 + lane * 16, dc = sb + CH_SX + rank * 1280 + 1024 + (w - 6) * 128 + lane * 4;
                bar_sync(2, nq * 32 + 64);
                float4 v[6]; float c[6];
#pragma unroll
                for (int i = 0; i < 6; i++) {
                    v[i] = (i < 5 || rank == 0) ? lds128(sa + i * 512) : make_float4(0, 0, 0, 0);
                    c[i] = (i < 5 || rank == 0) ? lds32(sc + i * 512) : 0.f;
                }
                float4 sv = add4(add4(add4(v[0], v[1]), add4(v[2], v[3])), add4(v[4], v[5]));
                float cv = ((c[0] + c[1]) + (c[2] + c[3])) + (c[4] + c[5]);
#pragma unroll
                for (int d = 1; d < 4; d++) {
                    const int dr = rank + d - (rank + d > 2 ? 3 : 0);
                    st_async4(mapa(da, dr), sv, mapa(barS, dr)); st_async1(mapa(dc, dr), cv, mapa(barS, dr));
                }
                TIM(5);
            }
            bar_sync(3, 256);
            float4 r = sum8(pl);
            vm0 = pack_bf16(r.x, r.y); vm1 = pack_bf16(r.z, r.w);
            TIM(7);
            if (!last) {
#pragma unroll
                for (int i = 0; i < NPRE_O; i++) ldsm4t(so[i], wl + (24 + i) * 512);
                mbar_wait(barS, s & 1);
                TIM(8);
                const uint32_t sx = sb + CH_SX + lane * 16;
                float4 a0 = lds128(sx), a1 = lds128(sx + 1280), a2 = lds128(sx + 2560);
                float4 b0 = lds128(sx + 512), b1 = lds128(sx + 512 + 1280), b2 = lds128(sx + 512 + 2560);
                float2 c0 = lds64(sx + 1024 - lane * 8), c1 = lds64(sx + 1024 + 1280 - lane * 8), c2 = lds64(sx + 1024 + 2560 - lane * 8);
                a0 = add4(add4(a0, a1), a2); b0 = add4(add4(b0, b1), b2);
                float sc[10] = {a0.x, a0.y, a0.z, a0.w, b0.x, b0.y, b0.z, b0.w, c0.x + c1.x + c2.x, c0.y + c1.y + c2.y};
                float mx = fmaxf(fmaxf(fmaxf(sc[0], sc[1]), fmaxf(sc[2], sc[3])), fmaxf(fmaxf(sc[4], sc[5]), fmaxf(sc[6], sc[7])));
                mx = fmaxf(mx, fmaxf(sc[8], sc[9]));
                mx = fmaxf(fmaxf(mx, __shfl_xor_sync(0xffffffffu, mx, 1)),
                           fmaxf(__shfl_xor_sync(0xffffffffu, mx, 2), __shfl_xor_sync(0xffffffffu, mx, 3)));
                const float cs = 0.08838834764831845f * 1.4426950408889634f;
                const float mb = -mx * cs;
#pragma unroll
                for (int j = 0; j < 10; j++) sc[j] = ex2(fmaf(sc[j], cs, mb));
                uint32_t pf[5];
#pragma unroll
                for (int j = 0; j < 5; j++) pf[j] = pack_bf16(sc[2 * j], sc[2 * j + 1]);
                float o0[4], o1[4], o2[4], o3[4], o4[4], o5[4];
                const uint32_t p0[4] = {pf[0], 0, pf[1], 0}, p1[4] = {pf[2], 0, pf[3], 0};
                mma16z(o0, p0, vt0[0], vt0[1]); mma16z(o1, p0, vt1[0], vt1[1]);
                mma16z(o2, p1, vt0[2], vt0[3]); mma16z(o3, p1, vt1[2], vt1[3]);
                mma8z(o4, pf[4], 0, vm0); mma8z(o5, pf[4], 0, vm1);
                float sum = (((sc[0] + sc[1]) + (sc[2] + sc[3])) + ((sc[4] + sc[5]) + (sc[6] + sc[7]))) + (sc[8] + sc[9]);
                sum = (sum + __shfl_xor_sync(0xffffffffu, sum, 1)) + (__shfl_xor_sync(0xffffffffu, sum, 2) + __shfl_xor_sync(0xffffffffu, sum, 3));
                const float inv = __fdividef(1.f, sum);
                const uint32_t ox = pack_bf16((o0[0] + o2[0] + o4[0]) * inv, (o0[1] + o2[1] + o4[1]) * inv);
                const uint32_t oy = pack_bf16((o1[0] + o3[0] + o5[0]) * inv, (o1[1] + o3[1] + o5[1]) * inv);
                st_pub(pub + slot, ox, oy); st_pub(pub + slot + 4096, ox, oy);
                bar_arrive(4, 256);
#pragma unroll
                for (int i = NPRE_O; i < 10; i++) ldsm4t(so[i], wl + (24 + i) * 512);
            }
            ((uint32_t*)kvo)[0] = movm(vm0); ((uint32_t*)kvo)[32] = movm(vm1);
        } else {
            *(uint32_t*)kvo = kf;
            if (last) bar_arrive(3, 256);
            else {
                bar_sync(3, 256);
                if (w == 2 && lane == 0) xload(s + 1);
                const uint32_t z = delay<2>(zero);
                GT(1, z);
#pragma unroll
                for (int i = 0; i < 10; i++) ldsm4t(so[i], wl + z + (24 + i) * 512);
                if (w == 3 && lane == 0 && (s & 3) == 0 && s) { __threadfence(); atomicAdd(g_ctr + C_CHAIN + (s >> 2) - 1, 1); }
                bar_sync(4, 256);
            }
        }
        if (last) return;
        uint2 c[11];
        const uint32_t z1 = delay<PV ? (DLO > 2 ? DLO - 2 : 0) : DLO>(zero);
        TIM(9);
        poll_issue<11>(c, o_rd + slot + z1, rank < 2);
        GT(2, z1);
        kvo += NH * 8 * DH;
        POLLCHK(11, c, o_rd + slot, 1);
        TIM(10);
        {
            float acc[4][4];
#pragma unroll
            for (int f = 0; f < 22; f++) {
                const int kk = f >> 1, a = f & 3;
                if (f < 4) mma16z(acc[a], so[f % 10], c[kk].x, c[kk].y);
                else mma16(acc[a], so[f % 10], c[kk].x, c[kk].y);
                if (f + 10 < 22) ldsm4t(so[f % 10], wl + (24 + f + 10) * 512);
            }
#pragma unroll
            for (int i = 0; i < 2; i++) {
#pragma unroll
                for (int j = 0; j < 4; j++) acc[i][j] += acc[i + 2][j];
                sts128(wl + CH_PART + i * 512, acc[i]);
            }
        }
        TIM(11);
        if (!PV && w < 2) {
            bar_sync(5, 256);
            float4 r = sum8(pl);
            if (!mown) {
                st_async4(mapa(sb + CH_MX + rank * 512 + lane * 16, w), r, mapa(barM, w));
                if (rank < 2 && lane == 0) st_async1(mapa(sb + CH_MX + rank * 4, 2), r.x, mapa(barM, 2));
            }
            bar_arrive(7, 256);
#pragma unroll
            for (int i = 0; i < 8; i++) ldsm4t(sw[i], wl + i * 512);
            mbar_wait(barX, (s + 1) & 1);
            if (!mown) {
                if (rank == 2 && w == 0) mbar_wait(barM, s & 1);
            } else {
                TIM(12);
                mbar_wait(barM, s & 1);
                TIM(13);
                float4 x = lds128(sb + CH_MX + (rank ^ 1) * 512 + lane * 16), y = lds128(sb + CH_MX + 2 * 512 + lane * 16);
                r = add4(add4(x, r), y);
                const uint32_t mx = movm(pack_bf16(r.x, r.y)), my = movm(pack_bf16(r.z, r.w));
                const uint32_t ns = (slot + 0x4000) & 0xC000;
                st_pub(pub + ns, mx, my); st_pub(pub + ns + 4096, mx, my);
                TIM(14);
            }
        } else {
            bar_arrive(5, 256);
            if (PV) { st_pub(pub + (slot ^ 0x8000), SENT, SENT); st_pub(pub + (slot ^ 0x8000) + 4096, SENT, SENT); }
            bar_sync(7, 256);
#pragma unroll
            for (int i = 0; i < 8; i++) ldsm4t(sw[i], wl + i * 512);
            GT(3, sw[0][0]);
            mbar_wait(barX, (s + 1) & 1);
        }
        bar_sync(6, 256);
    };
#pragma unroll 1
    for (int s = 0; s < NSEG - 1; s++) step(s, BoolC<false>());
    step(NSEG - 1, BoolC<true>());
    bar_sync(6, 256);
    if (!PV && w == 3 && lane == 0) { __threadfence(); atomicAdd(g_ctr + C_CHAIN + 15, 1); }
}

__global__ void __cluster_dims__(3, 1, 1) __launch_bounds__(256, 1)
chain_kernel(const bf16* __restrict__ Wq, const bf16* __restrict__ Wk, const bf16* __restrict__ Wv, const bf16* __restrict__ Wo,
             int aware) {
    extern __shared__ __align__(1024) unsigned char smem[];
    const uint32_t sb = smem_u32(smem);
    const int tid = threadIdx.x, lane = tid & 31;
    const int w = __shfl_sync(0xffffffffu, tid >> 5, 0);
    int rank; asm("mov.u32 %0, %%cluster_ctarank;" : "=r"(rank));
    const int h = blockIdx.x / 3;
    const int nq = rank == 0 ? 6 : 5;
    const int u0 = rank == 0 ? 0 : 1 + 5 * rank;
    const int v0 = rank == 0 ? -6 : 3 * rank - 6;
    const int gw = rank * 8 + w;
    const int ks0 = gw < 16 ? 11 * gw : 176 + 10 * (gw - 16);
    const int nko = gw < 16 ? 11 : 10;
    const uint32_t wr = sb + w * CH_WREG;
    if (tid == 0) {
        mbar_init(sb + CH_BAR, 1); mbar_init(sb + CH_BAR + 8, 1); mbar_init(sb + CH_BAR + 16, 1);
        *(int*)(smem + CH_BAR + 24) = 0;
        asm volatile("fence.mbarrier_init.release.cluster;" ::: "memory");
    }
    __threadfence();
    asm volatile("griddepcontrol.launch_dependents;" ::: "memory");
    uint32_t smid; asm("mov.u32 %0, %%smid;" : "=r"(smid));
    const int side = __shfl_sync(0xffffffffu, aware ? g_side[smid] ^ (aware - 1) : 0, 0);

    uint32_t wa[40][4];
    {
        const int r8 = lane & 7, p = lane >> 3;
        const bf16* src[4]; int tile[4], half[4];
#pragma unroll
        for (int q = 0; q < 4; q++) {
            int e = 4 * q + p;
            if (e < nq) { tile[q] = e; half[q] = 0; src[q] = Wq + h * DH + 8 * (u0 + e); }
            else if (e < 2 * nq) { tile[q] = e - nq; half[q] = 1; src[q] = Wk + h * DH + 8 * (u0 + e - nq); }
            else { int f = e - 2 * nq; tile[q] = nq + (f >> 1); half[q] = f & 1; src[q] = Wv + h * DH + 16 * (v0 + tile[q]) + 8 * half[q]; }
            src[q] += (size_t)(128 * w + r8) * HD;
        }
        const bf16* so = Wo + (size_t)(16 * ks0 + r8) * DM + 32 * h + 8 * p;
        const uint32_t dso = (p >> 1) * 512 + (p & 1) * 128 + r8 * 16;
#pragma unroll 1
        for (int kh = 0; kh < 16; kh++)
#pragma unroll
            for (int q = 0; q < 4; q++)
                if (tile[q] < 4 || tile[q] == 7) cp16(wr + (min(tile[q], 4) * 8 + (kh >> 1)) * 512 + ((kh & 1) * 2 + half[q]) * 128 + r8 * 16, src[q] + (size_t)kh * 8 * HD);
        asm volatile("cp.async.wait_all;" ::: "memory");
        __syncwarp();
#pragma unroll
        for (int i = 0; i < 40; i++) ldsm4t(wa[i], wr + i * 512 + lane * 16);
        __syncwarp();
#pragma unroll 1
        for (int kh = 0; kh < 16; kh++)
#pragma unroll
            for (int q = 0; q < 4; q++)
                if (tile[q] >= 4 && tile[q] < 7) cp16(wr + (tile[q] == 6 ? 16 + (kh >> 1) : (kh >> 1) * 2 + 5 - tile[q]) * 512 + ((kh & 1) * 2 + half[q]) * 128 + r8 * 16, src[q] + (size_t)kh * 8 * HD);
#pragma unroll 1
        for (int kh = 0; kh < 22; kh++) {
            uint32_t d = wr + (24 + (kh >> 1) * 2) * 512 + (kh & 1) * 256 + dso;
            if (kh < 2 * nko) cp16(d, so + (size_t)kh * 8 * DM);
            else asm volatile("st.shared.v4.u32 [%0], {%1,%1,%1,%1};" ::"r"(d), "r"(0) : "memory");
        }
        asm volatile("cp.async.wait_all;" ::: "memory");
    }
    asm volatile("griddepcontrol.wait;" ::: "memory");
    asm volatile("fence.proxy.async;" ::: "memory");
    __syncthreads();
    asm volatile("barrier.cluster.arrive.aligned; barrier.cluster.wait.aligned;" ::: "memory");
    if (w >= nq) chain_loop<true>(wa, sb, w, lane, rank, h, side);
    else chain_loop<false>(wa, sb, w, lane, rank, h, side);
}

constexpr int G_STAGE = 49152, G_NST = 4;
constexpr int G_STG = G_NST * G_STAGE;
constexpr int G_BAR = G_STG + 32768;
constexpr int G_SMEM = G_BAR + 128 + 1024;

__global__ void __launch_bounds__(384, 1)
kv_kernel(const __grid_constant__ CUtensorMap mx, const __grid_constant__ CUtensorMap mk, const __grid_constant__ CUtensorMap mv,
          const bf16* __restrict__ mem0) {
    extern __shared__ unsigned char smem_raw[];
    const uint32_t sb = (smem_u32(smem_raw) + 1023) & ~1023u;
    const uint32_t full = sb + G_BAR, empty = full + 32;
    const int tid = threadIdx.x, wg = tid >> 7, lane = tid & 31;
    if (tid == 0)
        for (int i = 0; i < G_NST; i++) { mbar_init(full + 8 * i, 1); mbar_init(empty + 8 * i, 2); }
    __syncthreads();
    if (wg == 0) {
        reg_dec<40>();
        if (tid == 0) {
            asm volatile("fence.proxy.async;" ::: "memory");
            int it = 0;
            for (int p = blockIdx.x; p < 512; p += gridDim.x) {
                const int m0 = (p & 15) * 128, nt = p >> 4;
                const CUtensorMap* mw = nt < 16 ? &mk : &mv;
                const int ng = (nt & 15) * 4;
                for (int kb = 0; kb < 16; kb++, it++) {
                    const int st = it & 3;
                    mbar_wait(empty + 8 * st, ((it >> 2) & 1) ^ 1);
                    mbar_expect(full + 8 * st, G_STAGE);
                    const uint32_t a = sb + st * G_STAGE;
                    tma2d(a, &mx, kb * 64, m0, full + 8 * st);
                    tma3d(a + 16384, mw, 0, kb * 64, ng, full + 8 * st);
                    tma3d(a + 32768, mw, 0, kb * 64, ng + 2, full + 8 * st);
                }
            }
        } else if (tid >= 32) {
            char* ring = ring_base();
            for (int k = blockIdx.x * 96 + tid - 32; k < (1 << 17); k += gridDim.x * 96) {
                uint2 v = make_uint2(SENT, SENT);
                int off = k * 8, chunk = ((off >> 13) & 1) | ((off >> 16) << 1), slot = (off >> 14) & 3, in = off & 4095;
                if (in >= 3072) continue;
                if (chunk >= 24 && slot == 0 && in < 2048) {
                    int ks = (chunk - 24) * 8 + (in >> 8), l = (in >> 3) & 31;
                    const uint32_t* p = (const uint32_t*)(mem0 + (l >> 2) * DM + 16 * ks + 2 * (l & 3));
                    v.x = p[0]; v.y = p[4];
                    if (v.x == SENT) v.x = 0x7FFF7FFFu;
                }
                *(uint2*)(ring + off) = v;
            }
            if (blockIdx.x == 0)
                for (int k = tid - 32; k < N_CTR; k += 96) g_ctr[k] = 0;
            if (tid == 32) {
                uint32_t smid; asm("mov.u32 %0, %%smid;" : "=r"(smid));
                uint32_t* p0 = (uint32_t*)(ring + ring_off(smid & 15, 0) + 3072 + (smid >> 4) * 64);
                uint32_t* p1 = (uint32_t*)(ring + ring_off(smid & 15, 1) + 3072 + (smid >> 4) * 64);
                *p0 = 0; *p1 = 0;
                int b0 = 1 << 30, b1 = 1 << 30; uint32_t v = 0;
                for (int r = 0; r < 24; r++) {
                    uint32_t t0 = clk(); v = atomicExch(p0 + (v == 50), r); uint32_t t1 = v == 77 ? clk() + 1 : clk(); b0 = min(b0, (int)(t1 - t0));
                    t0 = clk(); v = atomicExch(p1 + (v == 50), r); t1 = v == 77 ? clk() + 1 : clk(); b1 = min(b1, (int)(t1 - t0));
                }
                g_side[smid] = b1 < b0;
            }
            __threadfence();
            bar_sync(1, 96);
            asm volatile("griddepcontrol.launch_dependents;" ::: "memory");
        }
    } else {
        reg_inc<232>();
        const int wi = (tid >> 5) & 3;
        float acc[128];
        uint32_t pk[64];
        uint32_t* dst = nullptr;
        int it = 0;
        for (int p = blockIdx.x; p < 512; p += gridDim.x) {
#pragma unroll
            for (int kb = 0; kb < 16; kb++, it++) {
                const int st = kb & 3;
                mbar_wait(full + 8 * st, (it >> 2) & 1);
                const uint64_t da = mkdesc(sb + st * G_STAGE + (wg - 1) * 8192, 16, 1024, 1);
                const uint64_t db = mkdesc(sb + st * G_STAGE + 16384, 8192, 1024, 1);
                wg_fence();
#pragma unroll
                for (int k = 0; k < 4; k++) wgmma256(acc, da + k * 2, db + k * 128, kb | k);
                wg_commit();
                if (dst) {
#pragma unroll
                    for (int j = 0; j < 4; j++) dst[(kb * 2 + (j >> 1)) * 128 + (j & 1) * 32] = pk[kb * 4 + j];
                }
                if (kb > 0) {
                    wg_wait<1>();
                    if ((tid & 127) == 0) mbar_arrive(empty + 8 * ((kb - 1) & 3));
                }
            }
            wg_wait<0>();
            if ((tid & 127) == 0) mbar_arrive(empty + 8 * 3);
#pragma unroll
            for (int j = 0; j < 64; j++) pk[j] = pack_bf16(acc[2 * j], acc[2 * j + 1]);
            const int row = (p & 15) * 128 + (wg - 1) * 64 + wi * 16, nt = p >> 4;
            dst = (uint32_t*)(nt < 16 ? g_kx : g_vx) + (size_t)((row >> 5) * 512 + (nt & 15) * 32) * 128 + (row & 31) * 4 + lane;
        }
#pragma unroll
        for (int j = 0; j < 64; j++) dst[(j >> 1) * 128 + (j & 1) * 32] = pk[j];
    }
}

#define WLOG(e)
struct S4Params { const bf16 *Are, *Aim, *Bre, *Bim, *Cre, *Cim, *ldt, *dsk; };
constexpr int IT_QA = 0, IT_O = 1, IT_S4 = 2, IT_END = 3;
#define O_WIDE 11
__device__ __forceinline__ int o_items(int b) { return b < O_WIDE ? 4 : 8; }
__device__ __forceinline__ int ld_acq(const int* p) { int v; asm volatile("ld.acquire.gpu.global.s32 %0, [%1];" : "=r"(v) : "l"(p) : "memory"); return v; }
__device__ __forceinline__ void wait_ctr(const int* p, int n) {
    for (int it = 0; it < (1 << 22) && ld_acq(p) < n; it++) __nanosleep(64);
}
__device__ __forceinline__ void stsm4(uint32_t addr, uint32_t a, uint32_t b, uint32_t c, uint32_t d) {
    asm volatile("stmatrix.sync.aligned.m8n8.x4.shared.b16 [%0], {%1,%2,%3,%4};" ::"r"(addr), "r"(a), "r"(b), "r"(c), "r"(d) : "memory");
}
__device__ __forceinline__ void stsm4t(uint32_t addr, uint32_t a, uint32_t b, uint32_t c, uint32_t d) {
    asm volatile("stmatrix.sync.aligned.m8n8.x4.trans.shared.b16 [%0], {%1,%2,%3,%4};" ::"r"(addr), "r"(a), "r"(b), "r"(c), "r"(d) : "memory");
}
__device__ __forceinline__ void tma2d_store(const CUtensorMap* m, uint32_t src, int c0, int c1) {
    asm volatile("cp.async.bulk.tensor.2d.global.shared::cta.bulk_group [%0, {%2, %3}], [%1];" ::"l"(m), "r"(src), "r"(c0), "r"(c1) : "memory");
}
__device__ __forceinline__ void mma8(float (&d)[4], uint32_t a0, uint32_t a1, uint32_t b0) {
    asm volatile("mma.sync.aligned.m16n8k8.row.col.f32.bf16.bf16.f32 {%0,%1,%2,%3}, {%4,%5}, {%6}, {%0,%1,%2,%3};"
        : "+f"(d[0]), "+f"(d[1]), "+f"(d[2]), "+f"(d[3]) : "r"(a0), "r"(a1), "r"(b0));
}

__device__ __forceinline__ void attn_head(const uint32_t (&q)[32], uint32_t sk, uint32_t sv, uint32_t fullv, uint32_t parv, uint32_t emptyk,
                                          int wi, int lane, uint32_t* dst) {
    const int g = lane >> 2, t = lane & 3, hi = wi & 1;
    float s[5][4];
#pragma unroll
    for (int j = 0; j < 5; j++) s[j][0] = s[j][1] = s[j][2] = s[j][3] = 0.f;
#pragma unroll
    for (int k2 = 0; k2 < 4; k2++) {
        uint32_t km[4];
        ldsm4(km, sk + 8192 + k2 * 512 + lane * 16);
#pragma unroll
        for (int i = 0; i < 2; i++) {
            const int ks = 2 * k2 + i;
            const uint32_t a[4] = {q[4 * ks], q[4 * ks + 1], q[4 * ks + 2], q[4 * ks + 3]};
            uint32_t b[4];
            const uint32_t ad = sk + ks * 1024 + ((lane >> 3) & 1) * 512 + (lane >> 4) * 128 + (lane & 7) * 16;
            ldsm4(b, ad);
            mma16(s[4], a, km[2 * i], km[2 * i + 1]);
            mma16(s[0], a, b[0], b[1]); mma16(s[1], a, b[2], b[3]);
            if (hi) { ldsm4(b, ad + 256); mma16(s[2], a, b[0], b[1]); mma16(s[3], a, b[2], b[3]); }
        }
    }
    __syncwarp();
    if (lane == 0) mbar_arrive(emptyk);
    const int r0 = hi * 16 + g;
    float m0 = fmaxf(s[4][0], s[4][1]), m1 = fmaxf(s[4][2], s[4][3]);
#pragma unroll
    for (int j = 0; j < 4; j++) {
        const int c = 8 * j + 2 * t;
        if (c > r0) s[j][0] = -INFINITY;
        if (c + 1 > r0) s[j][1] = -INFINITY;
        if (c > r0 + 8) s[j][2] = -INFINITY;
        if (c + 1 > r0 + 8) s[j][3] = -INFINITY;
        m0 = fmaxf(m0, fmaxf(s[j][0], s[j][1])); m1 = fmaxf(m1, fmaxf(s[j][2], s[j][3]));
    }
    m0 = fmaxf(m0, __shfl_xor_sync(0xffffffffu, m0, 1)); m1 = fmaxf(m1, __shfl_xor_sync(0xffffffffu, m1, 1));
    m0 = fmaxf(m0, __shfl_xor_sync(0xffffffffu, m0, 2)); m1 = fmaxf(m1, __shfl_xor_sync(0xffffffffu, m1, 2));
    const float cs = 0.08838834764831845f * 1.4426950408889634f;
    m0 *= -cs; m1 *= -cs;
    float l0 = 0, l1 = 0;
#pragma unroll
    for (int j = 0; j < 5; j++) {
        s[j][0] = ex2(fmaf(s[j][0], cs, m0)); s[j][1] = ex2(fmaf(s[j][1], cs, m0));
        s[j][2] = ex2(fmaf(s[j][2], cs, m1)); s[j][3] = ex2(fmaf(s[j][3], cs, m1));
        l0 += s[j][0] + s[j][1]; l1 += s[j][2] + s[j][3];
    }
    l0 += __shfl_xor_sync(0xffffffffu, l0, 1); l1 += __shfl_xor_sync(0xffffffffu, l1, 1);
    l0 += __shfl_xor_sync(0xffffffffu, l0, 2); l1 += __shfl_xor_sync(0xffffffffu, l1, 2);
    l0 = __fdividef(1.f, l0); l1 = __fdividef(1.f, l1);
    uint32_t p[10];
#pragma unroll
    for (int j = 0; j < 5; j++) { p[2 * j] = pack_bf16(s[j][0] * l0, s[j][1] * l0); p[2 * j + 1] = pack_bf16(s[j][2] * l1, s[j][3] * l1); }
    const uint32_t p0[4] = {p[0], p[1], p[2], p[3]}, p1[4] = {p[4], p[5], p[6], p[7]};
    mbar_wait(fullv, parv);
#pragma unroll
    for (int u4 = 0; u4 < 4; u4++) {
        uint32_t vm[4];
        ldsm4t(vm, sv + 8192 + u4 * 512 + lane * 16);
#pragma unroll
        for (int i = 0; i < 4; i++) {
            const int u = 4 * u4 + i;
            uint32_t b[4];
            ldsm4t(b, sv + u * 512 + lane * 16);
            float o[4];
            mma16z(o, p0, b[0], b[1]);
            if (hi) mma16(o, p1, b[2], b[3]);
            mma8(o, p[8], p[9], vm[i]);
            dst[(u >> 3) * 4096 + (u & 7) * 32] = pack_bf16(o[0], o[1]);
            dst[(u >> 3) * 4096 + (u & 7) * 32 + 256] = pack_bf16(o[2], o[3]);
        }
    }
}

template <int BN, int NKB, bool BLOCKED_A>
__device__ __forceinline__ void mainloop(float (&acc)[BN / 2], uint32_t sb, int wgi, uint32_t full, uint32_t empty, int& it, bool elect) {
#pragma unroll
    for (int j = 0; j < BN / 2; j++) acc[j] = 0.f;
#pragma unroll 1
    for (int k4 = 0; k4 < NKB; k4 += 4) {
#pragma unroll
        for (int st = 0; st < 4; st++, it++) {
            mbar_wait(full + 8 * st, (it >> 2) & 1);
            const uint64_t da = BLOCKED_A ? mkdesc(sb + st * G_STAGE + wgi * 8192, 128, 1024, 0) : mkdesc(sb + st * G_STAGE + wgi * 8192, 16, 1024, 1);
            const uint64_t db = mkdesc(sb + st * G_STAGE + 16384, 8192, 1024, 1);
            wg_fence();
#pragma unroll
            for (int k = 0; k < 4; k++) {
                if constexpr (BN == 256) wgmma256(acc, da + k * (BLOCKED_A ? 16 : 2), db + k * 128, 1);
                else wgmma128(acc, da + k * (BLOCKED_A ? 16 : 2), db + k * 128, 1);
            }
            wg_commit();
            if (k4 | st) {
                wg_wait<1>();
                if (elect) mbar_arrive(empty + 8 * ((st + 3) & 3));
            }
        }
    }
    wg_wait<0>();
    if (elect) mbar_arrive(empty + 8 * 3);
}

template <int BN>
__device__ __forceinline__ void o_item(uint32_t sb, int wgi, int wi, int lane, uint32_t full, uint32_t empty, int& it, const CUtensorMap* mout,
                                       int row0, int col0) {
    float acc[BN / 2];
    mainloop<BN, 64, true>(acc, sb, wgi, full, empty, it, lane == 0);
    const uint32_t stg = sb + G_STG + (wgi * 4 + wi) * 4096;
    const int r = lane & 15, cu = lane >> 4;
#pragma unroll
    for (int hf = 0; hf < BN / 128; hf++) {
        if (lane == 0) asm volatile("cp.async.bulk.wait_group.read 0;" ::: "memory");
        __syncwarp();
#pragma unroll
        for (int j = 0; j < 8; j++) {
            const float* a = acc + hf * 64 + j * 8;
            stsm4(stg + (j >> 2) * 2048 + r * 128 + ((((j & 3) * 2 + cu) ^ (r & 7)) << 4),
                  pack_bf16(a[0], a[1]), pack_bf16(a[2], a[3]), pack_bf16(a[4], a[5]), pack_bf16(a[6], a[7]));
        }
        asm volatile("fence.proxy.async.shared::cta;" ::: "memory");
        __syncwarp();
        if (lane == 0) {
            tma2d_store(mout, stg, col0 + hf * 128, row0 + wgi * 64 + wi * 16);
            tma2d_store(mout, stg + 2048, col0 + hf * 128 + 64, row0 + wgi * 64 + wi * 16);
            asm volatile("cp.async.bulk.commit_group;" ::: "memory");
        }
    }
}

constexpr int S4_RAW = 0;
constexpr int S4_CH = 32768;
constexpr int S4_UT = 0;
constexpr int S4_WD = 5120;
constexpr int S4_STRIDE = 5120 + 8320 + 16;

__device__ __forceinline__ float2 cmul(float2 a, float2 b) { return make_float2(a.x * b.x - a.y * b.y, a.x * b.y + a.y * b.x); }
__device__ __forceinline__ float2 csq(float2 a) { return make_float2(a.x * a.x - a.y * a.y, (a.x + a.x) * a.y); }
__device__ __forceinline__ float2 cexp_t(float lr, float turns) {
    float f = (turns - rintf(turns)) * 6.283185307179586f, e = ex2(lr);
    return make_float2(e * __cosf(f), e * __sinf(f));
}
template <int H0>
__device__ __forceinline__ void s4_conv_phase(float (&acc)[16][4], uint32_t (&bw)[4][8], uint32_t& ap, uint32_t ut, uint32_t wd) {
#pragma unroll 1
    for (int E = 8 * H0; E < 8 * H0 + 8; E++) {
        uint32_t nw[4][8];
#pragma unroll
        for (int h = H0; h < 4; h++) {
            uint32_t x[4];
            ldsm4(x, ut + (8 * h - E - 1) * 16); nw[h][0] = x[0]; nw[h][1] = x[1]; nw[h][2] = x[2]; nw[h][3] = x[3];
            ldsm4(x, ut + (8 * h - E - 1) * 16 + 2560); nw[h][4] = x[0]; nw[h][5] = x[1]; nw[h][6] = x[2]; nw[h][7] = x[3];
        }
#pragma unroll
        for (int i = 0; i < 4; i++) {
            uint32_t a[4];
            a[0] = a[3] = __float_as_uint(lds32(wd + E * 256 + i * 64));
            a[1] = __float_as_uint(lds32(wd + E * 256 + i * 64 + 32));
            a[2] = ap; ap = a[1];
#pragma unroll
            for (int h = H0; h < 4; h++)
#pragma unroll
                for (int tau = 0; tau < 4; tau++) {
                    const int r = tau - i;
                    if (r >= 0) mma16(acc[4 * h + tau], a, bw[h][2 * r], bw[h][2 * r + 1]);
                    else mma16(acc[4 * h + tau], a, nw[h][2 * (r + 4)], nw[h][2 * (r + 4) + 1]);
                }
        }
#pragma unroll
        for (int h = H0; h < 4; h++)
#pragma unroll
            for (int j = 0; j < 8; j++) bw[h][j] = nw[h][j];
    }
}

__device__ __forceinline__ void s4_item(uint32_t sb, int cw, int lane, int item, const S4Params& P, uint32_t full, uint32_t par, const CUtensorMap* my) {
    const int g = lane >> 2, t = lane & 3, d = item * 8 + cw;
    const uint32_t ch = sb + S4_CH + cw * S4_STRIDE;
    const float dt = __bfloat162float(__float2bfloat16(expf(__bfloat162float(P.ldt[d]))));
#pragma unroll
    for (int i = 0; i < 4; i++) {
        const int n = d * 128 + i * 32 + lane;
        const float br = dt * __bfloat162float(P.Bre[n]), bi = dt * __bfloat162float(P.Bim[n]);
        const float cr = __bfloat162float(P.Cre[n]), ci = __bfloat162float(P.Cim[n]);
        const float v[4] = {dt * __bfloat162float(P.Are[n]) * 1.4426950408889634f, dt * __bfloat162float(P.Aim[n]) * 0.15915494309189535f,
                            cr * br - ci * bi, cr * bi + ci * br};
        sts128(ch + S4_WD + (i * 32 + lane) * 16, v);
    }
    __syncwarp();
    float kd[5][4], k2048 = 0.f;
#pragma unroll
    for (int j = 0; j < 5; j++) kd[j][0] = kd[j][1] = kd[j][2] = kd[j][3] = 0.f;
    const float x0 = (float)g, x1 = (float)(g + 8);
#pragma unroll 1
    for (int ks = 0; ks < 16; ks++) {
        uint32_t a[4][4], b[5][2];
#pragma unroll
        for (int i = 0; i < 2; i++) {
            const float4 p = lds128(ch + S4_WD + (ks * 8 + i * 4 + t) * 16);
            const float2 c = make_float2(p.z, p.w);
            float2 e0 = cexp_t(p.x * x0, p.y * x0), e1 = cexp_t(p.x * x1, p.y * x1);
#pragma unroll
            for (int j = 0; j < 4; j++) {
                a[j][2 * i] = pack_bf16(e0.x, e0.y); a[j][2 * i + 1] = pack_bf16(e1.x, e1.y);
                e0 = csq(e0); e1 = csq(e1);
            }
            float2 m = cmul(c, e0);
            b[0][i] = pack_bf16(m.x, -m.y);
#pragma unroll
            for (int j = 0; j < 4; j++) {
                m = cmul(c, e1);
                b[j + 1][i] = pack_bf16(m.x, -m.y);
                e1 = csq(e1);
            }
            k2048 += c.x * e1.x - c.y * e1.y;
        }
        mma16(kd[0], a[0], b[0][0], b[0][1]);
#pragma unroll
        for (int j = 0; j < 4; j++) mma16(kd[j + 1], a[j], b[j + 1][0], b[j + 1][1]);
    }
    k2048 += __shfl_xor_sync(0xffffffffu, k2048, 1);
    k2048 += __shfl_xor_sync(0xffffffffu, k2048, 2);
    {
        const uint32_t ta = ch + S4_UT + (lane & 7) * 32 + ((lane >> 3) & 1) * 16 + (lane >> 4) * 256;
        stsm4t(ta, pack_bf16(kd[0][0], kd[0][1]), pack_bf16(kd[0][2], kd[0][3]), pack_bf16(kd[1][0], kd[1][1]), pack_bf16(kd[1][2], kd[1][3]));
        stsm4t(ta + 512, pack_bf16(kd[2][0], kd[2][1]), pack_bf16(kd[2][2], kd[2][3]), pack_bf16(kd[3][0], kd[3][1]), pack_bf16(kd[3][2], kd[3][3]));
        stsm4t(ta + 1024, pack_bf16(kd[4][0], kd[4][1]), pack_bf16(kd[4][2], kd[4][3]), pack_bf16(k2048, 0.f), 0);
    }
    __syncwarp();
    {
        uint32_t prev = 0;
        if (lane < 16) asm volatile("st.shared.u32 [%0], %1;" ::"r"(ch + S4_WD + lane * 4), "r"(0) : "memory");
#pragma unroll 4
        for (int i = 0; i < 64; i++) {
            const int x = i * 32 + lane, sh = max(0, 24 - __clz(x));
            const int idx = sh ? 128 * sh + ((x + (1 << (sh - 1)) - 1 + ((x >> sh) & 1)) >> sh) : x;
            uint32_t k; asm volatile("ld.shared.u16 %0, [%1];" : "=r"(k) : "r"(ch + S4_UT + idx * 2) : "memory");
            const uint32_t up = __shfl_sync(0xffffffffu, lane == 31 ? prev : k, (lane + 31) & 31);
            prev = k;
            asm volatile("st.shared.u32 [%0], %1;" ::"r"(ch + S4_WD + 64 + x * 4), "r"(k | (up << 16)) : "memory");
        }
    }
    bar_sync(2, 256);
    if (lane < 8) {
#pragma unroll
        for (int i = 0; i < 8; i++) asm volatile("st.shared.v4.u32 [%0], {%1,%1,%1,%1};" ::"r"(ch + S4_UT + i * 640 + lane * 16), "r"(0) : "memory");
    }
    mbar_wait(full, par);
    const uint32_t traw = sb + S4_RAW + cw * 4096 + lane * 16;
    const uint32_t tch = sb + S4_CH + (lane & 7) * S4_STRIDE + S4_UT + (lane >> 3) * 640 + (8 + cw * 4) * 16;
#pragma unroll
    for (int i = 0; i < 8; i++) {
        uint32_t x[4];
        ldsm4t(x, traw + i * 512);
        stsm4(tch + (i & 1) * 2560 + (i >> 1) * 16, x[0], x[1], x[2], x[3]);
    }
    bar_sync(2, 256);
    float acc[16][4];
#pragma unroll
    for (int j = 0; j < 16; j++) acc[j][0] = acc[j][1] = acc[j][2] = acc[j][3] = 0.f;
    const uint32_t ut = ch + S4_UT + (lane >> 3) * 640 + (8 + (lane & 7)) * 16, wd = ch + S4_WD + 64 + (g - 2 * t) * 4;
    uint32_t bw[4][8], ap = 0;
#pragma unroll
    for (int h = 0; h < 4; h++) {
        uint32_t x[4];
        ldsm4(x, ut + 8 * h * 16); bw[h][0] = x[0]; bw[h][1] = x[1]; bw[h][2] = x[2]; bw[h][3] = x[3];
        ldsm4(x, ut + 8 * h * 16 + 2560); bw[h][4] = x[0]; bw[h][5] = x[1]; bw[h][6] = x[2]; bw[h][7] = x[3];
    }
    s4_conv_phase<0>(acc, bw, ap, ut, wd);
    s4_conv_phase<1>(acc, bw, ap, ut, wd);
    s4_conv_phase<2>(acc, bw, ap, ut, wd);
    s4_conv_phase<3>(acc, bw, ap, ut, wd);
    __syncwarp();
#pragma unroll
    for (int j = 0; j < 16; j += 2)
        stsm4t(ut + (j >> 2) * 128 + (j & 2) * 1280, pack_bf16(acc[j][0], acc[j][1]), pack_bf16(acc[j][2], acc[j][3]),
               pack_bf16(acc[j + 1][0], acc[j + 1][1]), pack_bf16(acc[j + 1][2], acc[j + 1][3]));
    bar_sync(2, 256);
    const __nv_bfloat162 dk = *(const __nv_bfloat162*)(P.dsk + item * 8 + 2 * t);
#pragma unroll
    for (int i = 0; i < 8; i++) {
        uint32_t y[4], u[4];
        ldsm4t(y, tch + (i & 1) * 2560 + (i >> 1) * 16);
        ldsm4(u, traw + i * 512);
#pragma unroll
        for (int j = 0; j < 4; j++) {
            __nv_bfloat162 r = __hadd2_rn(*(__nv_bfloat162*)&y[j], __hmul2_rn(*(__nv_bfloat162*)&u[j], dk));
            y[j] = *(uint32_t*)&r;
        }
        stsm4(traw + i * 512, y[0], y[1], y[2], y[3]);
    }
    asm volatile("fence.proxy.async.shared::cta;" ::: "memory");
    __syncwarp();
    if (lane == 0) {
        tma2d_store(my, sb + S4_RAW + cw * 4096, DM + item * 8, cw * 256);
        asm volatile("cp.async.bulk.commit_group;" ::: "memory");
        asm volatile("cp.async.bulk.wait_group.read 0;" ::: "memory");
    }
    bar_sync(2, 256);
}

__global__ void __launch_bounds__(384, 1)
worker_kernel(const __grid_constant__ CUtensorMap mx, const __grid_constant__ CUtensorMap mq, const __grid_constant__ CUtensorMap mo,
              const __grid_constant__ CUtensorMap mout, const __grid_constant__ CUtensorMap mu, const __grid_constant__ CUtensorMap my,
              const __grid_constant__ S4Params P) {
    extern __shared__ unsigned char smem_raw[];
    const uint32_t sb = (smem_u32(smem_raw) + 1023) & ~1023u;
    const uint32_t full = sb + G_BAR, empty = full + 32, ifull = full + 64, iempty = full + 80, islot = full + 96;
    const int tid = threadIdx.x, wg = tid >> 7, lane = tid & 31;
    if (tid == 0) {
        for (int i = 0; i < G_NST; i++) { mbar_init(full + 8 * i, 1); mbar_init(empty + 8 * i, 8); }
        for (int i = 0; i < 2; i++) { mbar_init(ifull + 8 * i, 1); mbar_init(iempty + 8 * i, 8); }
    }
    __syncthreads();
    if (wg == 0) {
        reg_dec<40>();
        if (tid < 32) {
            int it = 0;
            for (int n = 0;; n++) {
                int item = -1;
                for (int spin = 0; item < 0; spin++) {
                    const int b = lane & 15;
                    const int taken = ld_acq(g_ctr + (lane < 16 ? C_QA_NEXT : C_O_NEXT) + b);
                    const int prog = ld_acq(g_ctr + C_CHAIN + b);
                    const int s4 = ld_acq(g_ctr + C_S4_NEXT);
                    const uint32_t left = __ballot_sync(0xffffffffu, taken < (lane < 16 ? 16 : o_items(b)));
                    const uint32_t done = __ballot_sync(0xffffffffu, prog >= 96) & 0xffff;
                    const uint32_t qa_ok = left & 0xffff & ((done << 1) | (s4 >= S4_FIRST ? 1 : 0));
                    const uint32_t o_ok = (left >> 16) & done & ~left;
                    int got = -1;
                    if (qa_ok) {
                        const int bb = __ffs(qa_ok) - 1;
                        if (lane == 0) { int i = atomicAdd(g_ctr + C_QA_NEXT + bb, 1); if (i < 16) got = (IT_QA << 16) | (bb << 8) | i; }
                    } else if (o_ok) {
                        const int bb = __ffs(o_ok) - 1;
                        if (lane == 0) { int i = atomicAdd(g_ctr + C_O_NEXT + bb, 1); if (i < o_items(bb)) got = (IT_O << 16) | (bb << 8) | i; }
                    } else if (s4 < 128) {
                        if (lane == 0) { int i = atomicAdd(g_ctr + C_S4_NEXT, 1); if (i < 128) got = (IT_S4 << 16) | i; }
                    } else if (!left || spin > (1 << 20)) got = IT_END << 16;
                    else __nanosleep(200);
                    item = __shfl_sync(0xffffffffu, got, 0);
                }
                if (lane == 0) {
                    mbar_wait(iempty + 8 * (n & 1), ((n >> 1) & 1) ^ 1);
                    asm volatile("st.shared.u32 [%0], %1;" ::"r"(islot + 4 * (n & 1)), "r"(item) : "memory");
                    mbar_arrive(ifull + 8 * (n & 1));
                    const int type = item >> 16, b = (item >> 8) & 255, i = item & 255;
                    if (type == IT_QA) {
                        for (int kb = 0; kb < 16; kb++, it++) {
                            const int st = it & 3;
                            mbar_wait(empty + 8 * st, ((it >> 2) & 1) ^ 1);
                            mbar_expect(full + 8 * st, G_STAGE);
                            const uint32_t a = sb + st * G_STAGE;
                            tma2d(a, &mx, kb * 64, b * 128, full + 8 * st);
                            tma3d(a + 16384, &mq, 0, kb * 64, i * 4, full + 8 * st);
                            tma3d(a + 32768, &mq, 0, kb * 64, i * 4 + 2, full + 8 * st);
                        }
                        wait_ctr(g_ctr + C_CHAIN + b, 96);
                        asm volatile("fence.proxy.async;" ::: "memory");
                        for (int st = 0; st < 4; st++, it++) {
                            mbar_wait(empty + 8 * st, ((it >> 2) & 1) ^ 1);
                            mbar_expect(full + 8 * st, 4 * 10240);
                            for (int sg = 0; sg < 4; sg++) {
                                const int sh = (b * 4 + sg) * NH + i * 2 + (st >> 1);
                                bulk_load(sb + st * G_STAGE + sg * 10240, ((st & 1) ? g_vx : g_kx) + (size_t)sh * 4096, 8192, full + 8 * st);
                                bulk_load(sb + st * G_STAGE + sg * 10240 + 8192, ((st & 1) ? g_vm : g_km) + (size_t)sh * 1024, 2048, full + 8 * st);
                            }
                        }
                    } else if (type == IT_O) {
                        const bool wide = b < O_WIDE;
                        wait_ctr(g_ctr + C_QA_DONE + b, 128);
                        asm volatile("fence.proxy.async;" ::: "memory");
                        for (int kb = 0; kb < 64; kb++, it++) {
                            const int st = it & 3;
                            mbar_wait(empty + 8 * st, ((it >> 2) & 1) ^ 1);
                            mbar_expect(full + 8 * st, wide ? G_STAGE : 32768);
                            const uint32_t a = sb + st * G_STAGE;
                            bulk_load(a, g_ox + (size_t)(b * 64 + kb) * 8192, 16384, full + 8 * st);
                            tma3d(a + 16384, &mo, 0, kb * 64, wide ? i * 4 : i * 2, full + 8 * st);
                            if (wide) tma3d(a + 32768, &mo, 0, kb * 64, i * 4 + 2, full + 8 * st);
                        }
                    } else if (type == IT_S4) {
                        for (int st = 0; st < 4; st++) mbar_wait(empty + 8 * st, ((it >> 2) & 1) ^ 1);
                        mbar_expect(full, 32768);
                        for (int j = 0; j < 8; j++) tma2d(sb + S4_RAW + j * 4096, &mu, i * 8, j * 256, full);
                        for (int st = 1; st < 4; st++) mbar_arrive(full + 8 * st);
                        it += 4;
                    }
                }
                __syncwarp();
                if (item >> 16 == IT_END) break;
            }
            asm volatile("griddepcontrol.wait;" ::: "memory");
        }
    } else {
        reg_inc<232>();
        const int wgi = wg - 1, wi = (tid >> 5) & 3;
        int it = 0;
        for (int n = 0;; n++) {
            mbar_wait_long(ifull + 8 * (n & 1), (n >> 1) & 1);
            int item; asm volatile("ld.shared.u32 %0, [%1];" : "=r"(item) : "r"(islot + 4 * (n & 1)) : "memory");
            __syncwarp();
            if (lane == 0) mbar_arrive(iempty + 8 * (n & 1));
            const int type = item >> 16, b = (item >> 8) & 255, i = item & 255;
            WLOG(0);
            if (type == IT_QA) {
                float acc[128];
                mainloop<256, 16, false>(acc, sb, wgi, full, empty, it, lane == 0);
                uint32_t q0[32], q1[32];
#pragma unroll
                for (int j = 0; j < 32; j++) { q0[j] = pack_bf16(acc[2 * j], acc[2 * j + 1]); q1[j] = pack_bf16(acc[64 + 2 * j], acc[65 + 2 * j]); }
                const uint32_t par = (it >> 2) & 1, so = (wgi * 2 + (wi >> 1)) * 10240;
                uint32_t* dst = (uint32_t*)g_ox + (size_t)(b * 64 + i * 4) * 4096 + (wgi * 8 + wi * 2) * 256 + lane;
                mbar_wait_long(full, par);
                attn_head(q0, sb + so, sb + G_STAGE + so, full + 8, par, empty, wi, lane, dst);
                __syncwarp();
                if (lane == 0) mbar_arrive(empty + 8);
                mbar_wait(full + 16, par);
                attn_head(q1, sb + 2 * G_STAGE + so, sb + 3 * G_STAGE + so, full + 24, par, empty + 16, wi, lane, dst + 2 * 4096);
                __syncwarp();
                if (lane == 0) { mbar_arrive(empty + 24); __threadfence(); atomicAdd(g_ctr + C_QA_DONE + b, 1); }
                it += 4;
            } else if (type == IT_O) {
                mbar_wait_long(full, (it >> 2) & 1);
                if (b < O_WIDE) o_item<256>(sb, wgi, wi, lane, full, empty, it, &mout, b * 128, i * 256);
                else o_item<128>(sb, wgi, wi, lane, full, empty, it, &mout, b * 128, i * 128);
            } else if (type == IT_S4) {
                const uint32_t par = (it >> 2) & 1;
                mbar_wait(full + 8, par);
                s4_item(sb, wgi * 4 + wi, lane, i, P, full, par, &my);
                if (lane == 0) { mbar_arrive(empty); mbar_arrive(empty + 8); mbar_arrive(empty + 16); mbar_arrive(empty + 24); }
                it += 4;
            } else break;
            WLOG(1);
        }
        if (lane == 0) asm volatile("cp.async.bulk.wait_group 0;" ::: "memory");
    }
}

typedef CUresult (*EncodeFn)(CUtensorMap*, CUtensorMapDataType, cuuint32_t, void*, const cuuint64_t*, const cuuint64_t*, const cuuint32_t*,
                             const cuuint32_t*, CUtensorMapInterleave, CUtensorMapSwizzle, CUtensorMapL2promotion, CUtensorMapFloatOOBfill);
static EncodeFn get_encode() {
    void* fn = nullptr; cudaDriverEntryPointQueryResult st;
    cudaGetDriverEntryPoint("cuTensorMapEncodeTiled", &fn, cudaEnableDefault, &st);
    return (EncodeFn)fn;
}
static void map_act(EncodeFn enc, CUtensorMap* m, const void* p, int rows, int cols, int boxr) {
    cuuint64_t dim[2] = {(cuuint64_t)cols, (cuuint64_t)rows}, str[1] = {(cuuint64_t)cols * 2};
    cuuint32_t box[2] = {64, (cuuint32_t)boxr}, es[2] = {1, 1};
    enc(m, CU_TENSOR_MAP_DATA_TYPE_BFLOAT16, 2, (void*)p, dim, str, box, es, CU_TENSOR_MAP_INTERLEAVE_NONE, CU_TENSOR_MAP_SWIZZLE_128B,
        CU_TENSOR_MAP_L2_PROMOTION_L2_128B, CU_TENSOR_MAP_FLOAT_OOB_FILL_NONE);
}
static void map_w(EncodeFn enc, CUtensorMap* m, const void* p, int k, int n) {
    cuuint64_t dim[3] = {64, (cuuint64_t)k, (cuuint64_t)n / 64}, str[2] = {(cuuint64_t)n * 2, 128};
    cuuint32_t box[3] = {64, 64, 2}, es[3] = {1, 1, 1};
    enc(m, CU_TENSOR_MAP_DATA_TYPE_BFLOAT16, 3, (void*)p, dim, str, box, es, CU_TENSOR_MAP_INTERLEAVE_NONE, CU_TENSOR_MAP_SWIZZLE_128B,
        CU_TENSOR_MAP_L2_PROMOTION_L2_256B, CU_TENSOR_MAP_FLOAT_OOB_FILL_NONE);
}

static void map_box(EncodeFn enc, CUtensorMap* m, const void* p, int rows, int ld, int boxc, int boxr, CUtensorMapSwizzle sw) {
    cuuint64_t dim[2] = {(cuuint64_t)ld, (cuuint64_t)rows}, str[1] = {(cuuint64_t)ld * 2};
    cuuint32_t box[2] = {(cuuint32_t)boxc, (cuuint32_t)boxr}, es[2] = {1, 1};
    enc(m, CU_TENSOR_MAP_DATA_TYPE_BFLOAT16, 2, (void*)p, dim, str, box, es, CU_TENSOR_MAP_INTERLEAVE_NONE, sw,
        CU_TENSOR_MAP_L2_PROMOTION_NONE, CU_TENSOR_MAP_FLOAT_OOB_FILL_NONE);
}

extern "C" void kernel_launch(void* const* d_in, const int* in_sizes, int n_in, void* d_out, int out_size) {
    const bf16* x = (const bf16*)d_in[0];
    const bf16* mem0 = (const bf16*)d_in[1];
    const bf16 *Wq = (const bf16*)d_in[2], *Wk = (const bf16*)d_in[3], *Wv = (const bf16*)d_in[4], *Wo = (const bf16*)d_in[5];
    static EncodeFn enc = nullptr;
    static int nsm = 0;
    if (!enc) {
        enc = get_encode();
        cudaDeviceGetAttribute(&nsm, cudaDevAttrMultiProcessorCount, 0);
        cudaFuncSetAttribute(chain_kernel, cudaFuncAttributeMaxDynamicSharedMemorySize, CH_SMEM);
        cudaFuncSetAttribute(kv_kernel, cudaFuncAttributeMaxDynamicSharedMemorySize, G_SMEM);
        cudaFuncSetAttribute(worker_kernel, cudaFuncAttributeMaxDynamicSharedMemorySize, G_SMEM);
    }
    CUtensorMap mx, mq, mk, mv, mo, mout, mu, my;
    map_act(enc, &mx, x, S_LEN, DM, 128);
    map_w(enc, &mq, Wq, DM, HD); map_w(enc, &mk, Wk, DM, HD); map_w(enc, &mv, Wv, DM, HD); map_w(enc, &mo, Wo, HD, DM);
    map_box(enc, &mout, d_out, S_LEN, 2 * DM, 64, 16, CU_TENSOR_MAP_SWIZZLE_128B);
    map_box(enc, &mu, d_in[7], S_LEN, DM, 8, 256, CU_TENSOR_MAP_SWIZZLE_NONE);
    map_box(enc, &my, d_out, S_LEN, 2 * DM, 8, 256, CU_TENSOR_MAP_SWIZZLE_NONE);
    S4Params P = {(const bf16*)d_in[8], (const bf16*)d_in[9], (const bf16*)d_in[10], (const bf16*)d_in[11],
                  (const bf16*)d_in[12], (const bf16*)d_in[13], (const bf16*)d_in[14], (const bf16*)d_in[15]};
    int aware = 1, pdl = 1;
    cudaLaunchAttribute at[1];
    at[0].id = cudaLaunchAttributeProgrammaticStreamSerialization;
    at[0].val.programmaticStreamSerializationAllowed = 1;
    cudaLaunchConfig_t cfg = {};
    cfg.stream = cudaStreamPerThread;
    cfg.gridDim = dim3(nsm); cfg.blockDim = dim3(384); cfg.dynamicSmemBytes = G_SMEM;
    cudaLaunchKernelEx(&cfg, kv_kernel, mx, mk, mv, mem0);
    cfg.attrs = at; cfg.numAttrs = pdl;
    cfg.gridDim = dim3(96); cfg.blockDim = dim3(256); cfg.dynamicSmemBytes = CH_SMEM;
    cudaLaunchKernelEx(&cfg, chain_kernel, Wq, Wk, Wv, Wo, aware);
    cfg.gridDim = dim3(nsm); cfg.blockDim = dim3(384); cfg.dynamicSmemBytes = G_SMEM;
    cudaLaunchKernelEx(&cfg, worker_kernel, mx, mq, mo, mout, mu, my, P);
}
```

```cpp
#include <cuda.h>
#include <cuda_runtime.h>
#include <cuda_bf16.h>
#include <stdint.h>
#include <stdio.h>
#include <string.h>

typedef __nv_bfloat16 bf16;

constexpr int S_LEN = 2048, DM = 1024, NH = 32, DH = 128, HD = 4096, NSEG = 64;
constexpr uint32_t SENT = 0xFFFFFFFFu;
constexpr int SPIN_LIMIT = 1 << 18;

__device__ __align__(1024) bf16 g_kx[S_LEN * HD];
__device__ __align__(1024) bf16 g_vx[S_LEN * HD];
__device__ __align__(1024) bf16 g_ox[S_LEN * HD];
__device__ __align__(1024) bf16 g_km[NSEG * NH * 8 * DH];
__device__ __align__(1024) bf16 g_vm[NSEG * NH * 8 * DH];
__device__ __align__(1024) char g_ring[2 << 20];
__device__ int g_side[256];
constexpr int C_QA_NEXT = 0, C_O_NEXT = 16, C_CHAIN = 32, C_QA_DONE = 64, C_S4_NEXT = 96, N_CTR = 128;
__device__ int g_ctr[N_CTR];
#define S4_FIRST 20

__device__ __forceinline__ uint32_t smem_u32(const void* p) { return (uint32_t)__cvta_generic_to_shared(p); }
__device__ __forceinline__ uint32_t clk() { uint32_t c; asm volatile("mov.u32 %0, %%clock;" : "=r"(c)::"memory"); return c; }
__device__ __forceinline__ uint32_t pack_bf16(float lo, float hi) {
    uint32_t r; asm("cvt.rn.bf16x2.f32 %0, %1, %2;" : "=r"(r) : "f"(hi), "f"(lo)); return r;
}
__device__ __forceinline__ uint32_t movm(uint32_t a) {
    uint32_t d; asm volatile("movmatrix.sync.aligned.m8n8.trans.b16 %0, %1;" : "=r"(d) : "r"(a)); return d;
}
__device__ __forceinline__ void mma16(float (&d)[4], const uint32_t (&a)[4], uint32_t b0, uint32_t b1) {
    asm volatile("mma.sync.aligned.m16n8k16.row.col.f32.bf16.bf16.f32 {%0,%1,%2,%3}, {%4,%5,%6,%7}, {%8,%9}, {%0,%1,%2,%3};"
        : "+f"(d[0]), "+f"(d[1]), "+f"(d[2]), "+f"(d[3]) : "r"(a[0]), "r"(a[1]), "r"(a[2]), "r"(a[3]), "r"(b0), "r"(b1));
}
__device__ __forceinline__ void mma16z(float (&d)[4], const uint32_t (&a)[4], uint32_t b0, uint32_t b1) {
    asm volatile("mma.sync.aligned.m16n8k16.row.col.f32.bf16.bf16.f32 {%0,%1,%2,%3}, {%4,%5,%6,%7}, {%8,%9}, {%10,%10,%10,%10};"
        : "=f"(d[0]), "=f"(d[1]), "=f"(d[2]), "=f"(d[3]) : "r"(a[0]), "r"(a[1]), "r"(a[2]), "r"(a[3]), "r"(b0), "r"(b1), "f"(0.f));
}
__device__ __forceinline__ void mma8z(float (&d)[4], uint32_t a0, uint32_t a1, uint32_t b0) {
    asm volatile("mma.sync.aligned.m16n8k8.row.col.f32.bf16.bf16.f32 {%0,%1,%2,%3}, {%4,%5}, {%6}, {%7,%7,%7,%7};"
        : "=f"(d[0]), "=f"(d[1]), "=f"(d[2]), "=f"(d[3]) : "r"(a0), "r"(a1), "r"(b0), "f"(0.f));
}
__device__ __forceinline__ void ldsm4t(uint32_t (&r)[4], uint32_t addr) {
    asm volatile("ldmatrix.sync.aligned.m8n8.x4.trans.shared.b16 {%0,%1,%2,%3}, [%4];"
        : "=r"(r[0]), "=r"(r[1]), "=r"(r[2]), "=r"(r[3]) : "r"(addr) : "memory");
}
__device__ __forceinline__ void ldsm4(uint32_t (&r)[4], uint32_t addr) {
    asm volatile("ldmatrix.sync.aligned.m8n8.x4.shared.b16 {%0,%1,%2,%3}, [%4];"
        : "=r"(r[0]), "=r"(r[1]), "=r"(r[2]), "=r"(r[3]) : "r"(addr) : "memory");
}
__device__ __forceinline__ float lds32(uint32_t a) {
    float v; asm volatile("ld.shared.f32 %0, [%1];" : "=f"(v) : "r"(a) : "memory"); return v;
}
__device__ __forceinline__ void st_async1(uint32_t dst, float v, uint32_t bar) {
    asm volatile("st.async.shared::cluster.mbarrier::complete_tx::bytes.f32 [%0], %1, [%2];" ::"r"(dst), "f"(v), "r"(bar) : "memory");
}
__device__ __forceinline__ void cp16(uint32_t dst, const void* src) {
    asm volatile("cp.async.cg.shared.global [%0], [%1], 16;" ::"r"(dst), "l"(src) : "memory");
}
__device__ __forceinline__ void sts128(uint32_t a, const float (&v)[4]) {
    asm volatile("st.shared.v4.f32 [%0], {%1,%2,%3,%4};" ::"r"(a), "f"(v[0]), "f"(v[1]), "f"(v[2]), "f"(v[3]) : "memory");
}
__device__ __forceinline__ float4 lds128(uint32_t a) {
    float4 v; asm volatile("ld.shared.v4.f32 {%0,%1,%2,%3}, [%4];" : "=f"(v.x), "=f"(v.y), "=f"(v.z), "=f"(v.w) : "r"(a) : "memory"); return v;
}
__device__ __forceinline__ void sts64(uint32_t a, float x, float y) {
    asm volatile("st.shared.v2.f32 [%0], {%1,%2};" ::"r"(a), "f"(x), "f"(y) : "memory");
}
__device__ __forceinline__ float2 lds64(uint32_t a) {
    float2 v; asm volatile("ld.shared.v2.f32 {%0,%1}, [%2];" : "=f"(v.x), "=f"(v.y) : "r"(a) : "memory"); return v;
}
__device__ __forceinline__ void bar_sync(int id, int n) { asm volatile("bar.sync %0, %1;" ::"r"(id), "r"(n) : "memory"); }
__device__ __forceinline__ void bar_arrive(int id, int n) { asm volatile("bar.arrive %0, %1;" ::"r"(id), "r"(n) : "memory"); }
__device__ __forceinline__ uint32_t mapa(uint32_t a, uint32_t r) {
    uint32_t o; asm("mapa.shared::cluster.u32 %0, %1, %2;" : "=r"(o) : "r"(a), "r"(r)); return o;
}
__device__ __forceinline__ void st_async4(uint32_t dst, float4 v, uint32_t bar) {
    asm volatile("st.async.shared::cluster.mbarrier::complete_tx::bytes.v4.f32 [%0], {%1,%2,%3,%4}, [%5];"
        ::"r"(dst), "f"(v.x), "f"(v.y), "f"(v.z), "f"(v.w), "r"(bar) : "memory");
}
__device__ __forceinline__ void mbar_init(uint32_t bar, int n) { asm volatile("mbarrier.init.shared.b64 [%0], %1;" ::"r"(bar), "r"(n) : "memory"); }
__device__ __forceinline__ void mbar_expect(uint32_t bar, int bytes) {
    asm volatile("mbarrier.arrive.expect_tx.shared.b64 _, [%0], %1;" ::"r"(bar), "r"(bytes) : "memory");
}
__device__ __forceinline__ void bulk_load(uint32_t dst, const void* src, int bytes, uint32_t bar) {
    asm volatile("cp.async.bulk.shared::cluster.global.mbarrier::complete_tx::bytes [%0], [%1], %2, [%3];"
        ::"r"(dst), "l"(src), "r"(bytes), "r"(bar) : "memory");
}
__device__ __forceinline__ bool mbar_try(uint32_t bar, uint32_t par) {
    uint32_t ok;
    asm volatile("{.reg .pred p; mbarrier.try_wait.parity.shared::cta.b64 p, [%1], %2; selp.u32 %0, 1, 0, p;}"
        : "=r"(ok) : "r"(bar), "r"(par) : "memory");
    return ok;
}
__device__ __forceinline__ void mbar_wait(uint32_t bar, uint32_t par) {
    if (!mbar_try(bar, par))
        for (int it = 0; it < SPIN_LIMIT && !mbar_try(bar, par); it++) {}
}
__device__ __forceinline__ void mbar_wait_long(uint32_t bar, uint32_t par) {
    for (int it = 0; it < (1 << 24) && !mbar_try(bar, par); it++) {}
}
__device__ __forceinline__ float4 add4(float4 a, float4 b) { return make_float4(a.x + b.x, a.y + b.y, a.z + b.z, a.w + b.w); }
__device__ __forceinline__ float ex2(float x) { float y; asm("ex2.approx.ftz.f32 %0, %1;" : "=f"(y) : "f"(x)); return y; }

__device__ __forceinline__ void wgmma256(float (&d)[128], uint64_t da, uint64_t db, int acc) {
    asm volatile("{.reg .pred p; setp.ne.b32 p, %130, 0;\n"
        "wgmma.mma_async.sync.aligned.m64n256k16.f32.bf16.bf16 {"
        "%0,%1,%2,%3,%4,%5,%6,%7,%8,%9,%10,%11,%12,%13,%14,%15,"
        "%16,%17,%18,%19,%20,%21,%22,%23,%24,%25,%26,%27,%28,%29,%30,%31,"
        "%32,%33,%34,%35,%36,%37,%38,%39,%40,%41,%42,%43,%44,%45,%46,%47,"
        "%48,%49,%50,%51,%52,%53,%54,%55,%56,%57,%58,%59,%60,%61,%62,%63,"
        "%64,%65,%66,%67,%68,%69,%70,%71,%72,%73,%74,%75,%76,%77,%78,%79,"
        "%80,%81,%82,%83,%84,%85,%86,%87,%88,%89,%90,%91,%92,%93,%94,%95,"
        "%96,%97,%98,%99,%100,%101,%102,%103,%104,%105,%106,%107,%108,%109,%110,%111,"
        "%112,%113,%114,%115,%116,%117,%118,%119,%120,%121,%122,%123,%124,%125,%126,%127"
        "}, %128, %129, p, 1, 1, 0, 1;}"
        : "+f"(d[0]), "+f"(d[1]), "+f"(d[2]), "+f"(d[3]), "+f"(d[4]), "+f"(d[5]), "+f"(d[6]), "+f"(d[7]), "+f"(d[8]), "+f"(d[9]), "+f"(d[10]), "+f"(d[11]), "+f"(d[12]), "+f"(d[13]), "+f"(d[14]), "+f"(d[15]), "+f"(d[16]), "+f"(d[17]), "+f"(d[18]), "+f"(d[19]), "+f"(d[20]), "+f"(d[21]), "+f"(d[22]), "+f"(d[23]), "+f"(d[24]), "+f"(d[25]), "+f"(d[26]), "+f"(d[27]), "+f"(d[28]), "+f"(d[29]), "+f"(d[30]), "+f"(d[31]), "+f"(d[32]), "+f"(d[33]), "+f"(d[34]), "+f"(d[35]), "+f"(d[36]), "+f"(d[37]), "+f"(d[38]), "+f"(d[39]), "+f"(d[40]), "+f"(d[41]), "+f"(d[42]), "+f"(d[43]), "+f"(d[44]), "+f"(d[45]), "+f"(d[46]), "+f"(d[47]), "+f"(d[48]), "+f"(d[49]), "+f"(d[50]), "+f"(d[51]), "+f"(d[52]), "+f"(d[53]), "+f"(d[54]), "+f"(d[55]), "+f"(d[56]), "+f"(d[57]), "+f"(d[58]), "+f"(d[59]), "+f"(d[60]), "+f"(d[61]), "+f"(d[62]), "+f"(d[63]), "+f"(d[64]), "+f"(d[65]), "+f"(d[66]), "+f"(d[67]), "+f"(d[68]), "+f"(d[69]), "+f"(d[70]), "+f"(d[71]), "+f"(d[72]), "+f"(d[73]), "+f"(d[74]), "+f"(d[75]), "+f"(d[76]), "+f"(d[77]), "+f"(d[78]), "+f"(d[79]), "+f"(d[80]), "+f"(d[81]), "+f"(d[82]), "+f"(d[83]), "+f"(d[84]), "+f"(d[85]), "+f"(d[86]), "+f"(d[87]), "+f"(d[88]), "+f"(d[89]), "+f"(d[90]), "+f"(d[91]), "+f"(d[92]), "+f"(d[93]), "+f"(d[94]), "+f"(d[95]), "+f"(d[96]), "+f"(d[97]), "+f"(d[98]), "+f"(d[99]), "+f"(d[100]), "+f"(d[101]), "+f"(d[102]), "+f"(d[103]), "+f"(d[104]), "+f"(d[105]), "+f"(d[106]), "+f"(d[107]), "+f"(d[108]), "+f"(d[109]), "+f"(d[110]), "+f"(d[111]), "+f"(d[112]), "+f"(d[113]), "+f"(d[114]), "+f"(d[115]), "+f"(d[116]), "+f"(d[117]), "+f"(d[118]), "+f"(d[119]), "+f"(d[120]), "+f"(d[121]), "+f"(d[122]), "+f"(d[123]), "+f"(d[124]), "+f"(d[125]), "+f"(d[126]), "+f"(d[127])
        : "l"(da), "l"(db), "r"(acc));
}
__device__ __forceinline__ void wgmma128(float (&d)[64], uint64_t da, uint64_t db, int acc) {
    asm volatile("{.reg .pred p; setp.ne.b32 p, %66, 0;\n"
        "wgmma.mma_async.sync.aligned.m64n128k16.f32.bf16.bf16 {"
        "%0,%1,%2,%3,%4,%5,%6,%7,%8,%9,%10,%11,%12,%13,%14,%15,"
        "%16,%17,%18,%19,%20,%21,%22,%23,%24,%25,%26,%27,%28,%29,%30,%31,"
        "%32,%33,%34,%35,%36,%37,%38,%39,%40,%41,%42,%43,%44,%45,%46,%47,"
        "%48,%49,%50,%51,%52,%53,%54,%55,%56,%57,%58,%59,%60,%61,%62,%63"
        "}, %64, %65, p, 1, 1, 0, 1;}"
        : "+f"(d[0]), "+f"(d[1]), "+f"(d[2]), "+f"(d[3]), "+f"(d[4]), "+f"(d[5]), "+f"(d[6]), "+f"(d[7]), "+f"(d[8]), "+f"(d[9]), "+f"(d[10]), "+f"(d[11]), "+f"(d[12]), "+f"(d[13]), "+f"(d[14]), "+f"(d[15]), "+f"(d[16]), "+f"(d[17]), "+f"(d[18]), "+f"(d[19]), "+f"(d[20]), "+f"(d[21]), "+f"(d[22]), "+f"(d[23]), "+f"(d[24]), "+f"(d[25]), "+f"(d[26]), "+f"(d[27]), "+f"(d[28]), "+f"(d[29]), "+f"(d[30]), "+f"(d[31]), "+f"(d[32]), "+f"(d[33]), "+f"(d[34]), "+f"(d[35]), "+f"(d[36]), "+f"(d[37]), "+f"(d[38]), "+f"(d[39]), "+f"(d[40]), "+f"(d[41]), "+f"(d[42]), "+f"(d[43]), "+f"(d[44]), "+f"(d[45]), "+f"(d[46]), "+f"(d[47]), "+f"(d[48]), "+f"(d[49]), "+f"(d[50]), "+f"(d[51]), "+f"(d[52]), "+f"(d[53]), "+f"(d[54]), "+f"(d[55]), "+f"(d[56]), "+f"(d[57]), "+f"(d[58]), "+f"(d[59]), "+f"(d[60]), "+f"(d[61]), "+f"(d[62]), "+f"(d[63])
        : "l"(da), "l"(db), "r"(acc));
}
__device__ __forceinline__ void wg_fence() { asm volatile("wgmma.fence.sync.aligned;" ::: "memory"); }
__device__ __forceinline__ void wg_commit() { asm volatile("wgmma.commit_group.sync.aligned;" ::: "memory"); }
template <int N> __device__ __forceinline__ void wg_wait() { asm volatile("wgmma.wait_group.sync.aligned %0;" ::"n"(N) : "memory"); }
__device__ __forceinline__ uint64_t mkdesc(uint32_t addr, uint32_t lbo, uint32_t sbo, uint32_t sw) {
    return (uint64_t)((addr & 0x3FFFF) >> 4) | ((uint64_t)(lbo >> 4) << 16) | ((uint64_t)(sbo >> 4) << 32) | ((uint64_t)sw << 62);
}
__device__ __forceinline__ void tma2d(uint32_t dst, const CUtensorMap* m, int c0, int c1, uint32_t bar) {
    asm volatile("cp.async.bulk.tensor.2d.shared::cluster.global.mbarrier::complete_tx::bytes [%0], [%1, {%2, %3}], [%4];"
        ::"r"(dst), "l"(m), "r"(c0), "r"(c1), "r"(bar) : "memory");
}
__device__ __forceinline__ void tma3d(uint32_t dst, const CUtensorMap* m, int c0, int c1, int c2, uint32_t bar) {
    asm volatile("cp.async.bulk.tensor.3d.shared::cluster.global.mbarrier::complete_tx::bytes [%0], [%1, {%2, %3, %4}], [%5];"
        ::"r"(dst), "l"(m), "r"(c0), "r"(c1), "r"(c2), "r"(bar) : "memory");
}
__device__ __forceinline__ void tma3d_mc(uint32_t dst, const CUtensorMap* m, int c0, int c1, int c2, uint32_t bar, uint16_t mask) {
    asm volatile("cp.async.bulk.tensor.3d.shared::cluster.global.mbarrier::complete_tx::bytes.multicast::cluster [%0], [%1, {%2, %3, %4}], [%5], %6;"
        ::"r"(dst), "l"(m), "r"(c0), "r"(c1), "r"(c2), "r"(bar), "h"(mask) : "memory");
}
__device__ __forceinline__ void mbar_arrive(uint32_t bar) { asm volatile("mbarrier.arrive.shared.b64 _, [%0];" ::"r"(bar) : "memory"); }
__device__ __forceinline__ void mbar_arrive_remote(uint32_t bar) {
    asm volatile("mbarrier.arrive.shared::cluster.b64 _, [%0];" ::"r"(bar) : "memory");
}
template <int R> __device__ __forceinline__ void reg_inc() { asm volatile("setmaxnreg.inc.sync.aligned.u32 %0;" ::"n"(R)); }
template <int R> __device__ __forceinline__ void reg_dec() { asm volatile("setmaxnreg.dec.sync.aligned.u32 %0;" ::"n"(R)); }

constexpr int CH_NRES = 46;
constexpr int CH_PART = CH_NRES * 512;
constexpr int CH_WREG = CH_PART + 8 * 512;
constexpr int CH_SX = 8 * CH_WREG;
constexpr int CH_MX = CH_SX + 3 * 1280;
constexpr int CH_XS = CH_MX + 3 * 512;
constexpr int CH_BAR = CH_XS + 5632;
constexpr int CH_SMEM = CH_BAR + 48;

__device__ __forceinline__ char* ring_base() { return (char*)(((uintptr_t)g_ring + (1 << 20) - 1) & ~(uintptr_t)((1 << 20) - 1)); }
__device__ __forceinline__ uint32_t ring_off(int chunk, int side) {
    uint32_t o = ((chunk & 1) << 13) | ((chunk >> 1) << 16);
    uint32_t par = ((o >> 13) ^ (o >> 16) ^ (o >> 17) ^ (o >> 19) ^ side) & 1;
    return o | (par << 12);
}
__device__ __forceinline__ uint2 ld_poll(const char* p) {
    unsigned long long v; asm volatile("ld.relaxed.gpu.global.b64 %0, [%1];" : "=l"(v) : "l"(p) : "memory");
    return make_uint2((uint32_t)v, (uint32_t)(v >> 32));
}
__device__ __forceinline__ void st_pub(char* p, uint32_t x, uint32_t y) {
    unsigned long long v = ((unsigned long long)y << 32) | x;
    asm volatile("st.relaxed.gpu.global.b64 [%0], %1;" ::"l"(p), "l"(v) : "memory");
}
template <int N>
__device__ __forceinline__ void poll_issue(uint2 (&b)[N], const char* p, bool lastvalid) {
#pragma unroll
    for (int i = 0; i < N; i++) {
        if (i < N - 1 || lastvalid) b[i] = ld_poll(p + i * 256);
        else b[i] = make_uint2(0, 0);
    }
}
template <int N>
__device__ __forceinline__ int poll_check(uint2 (&b)[N], const char* p) {
    int it = 0;
    uint32_t mx = b[0].x;
#pragma unroll
    for (int i = 1; i < N; i++) mx = max(mx, b[i].x);
    if (__any_sync(0xffffffffu, mx == SENT)) {
        while (it++ < SPIN_LIMIT) {
#pragma unroll
            for (int i = 0; i < N; i++)
                if (b[i].x == SENT) b[i] = ld_poll(p + i * 256);
            mx = b[0].x;
#pragma unroll
            for (int i = 1; i < N; i++) mx = max(mx, b[i].x);
            if (!__any_sync(0xffffffffu, mx == SENT)) break;
        }
    }
    return it;
}
__device__ __forceinline__ float4 sum8(uint32_t a) {
    float4 v[8];
#pragma unroll
    for (int i = 0; i < 8; i++) v[i] = lds128(a + i * CH_WREG);
    return add4(add4(add4(v[0], v[1]), add4(v[2], v[3])), add4(add4(v[4], v[5]), add4(v[6], v[7])));
}
template <int N>
__device__ __forceinline__ uint32_t delay(uint32_t a) {
    uint32_t z = 0;
#pragma unroll
    for (int i = 0; i < N; i++) asm volatile("ld.volatile.shared.u32 %0, [%1];" : "=r"(z) : "r"(a + z) : "memory");
    return z;
}

#define TIM(i)
#define GT(i, z)
#define POLLCHK(N, arr, p, i) poll_check<N>(arr, p)

template <bool B> struct BoolC { static constexpr bool value = B; };
#define DLM 6
#define DLO 8
#define NPRE_O 4
template <bool PV>
__device__ __forceinline__ void chain_loop(const uint32_t (&wa)[40][4], const uint32_t sb, const int w, const int lane, const int rank,
                                           const int h, const int side) {
    const int nq = rank == 0 ? 6 : 5, u0 = rank == 0 ? 0 : 1 + 5 * rank, v0 = rank == 0 ? -6 : 3 * rank - 6;
    const int gw = rank * 8 + w;
    const uint32_t wl = sb + w * CH_WREG + lane * 16;
    const uint32_t pl = sb + CH_PART + w * 512 + lane * 16;
    const uint32_t barS = sb + CH_BAR, barM = barS + 8, barX = barS + 16, zero = barS + 24;
    char* const ring = ring_base();
    const char* const m_rd = ring + ring_off(24 + w, side) + lane * 8;
    const char* const o_rd = ring + ring_off(gw, side) + lane * 8;
    char* pub;
    if (PV) {
        int ks = h * 8 + v0 + w, cw = ks < 176 ? ks / 11 : 16 + (ks - 176) / 10, c0 = cw < 16 ? 11 * cw : 176 + 10 * (cw - 16);
        pub = ring + (ring_off(cw, 0) & ~4096u) + (ks - c0) * 256 + lane * 8;
    } else {
        int ks = 2 * h + w;
        pub = ring + (ring_off(24 + (ks >> 3), 0) & ~4096u) + (ks & 7) * 256 + lane * 8;
    }
    const uint32_t xs = sb + CH_XS + (PV ? nq * 512 + (w - nq) * 1024 : w * 512) + lane * 16;
    bf16* kvo = (PV ? g_vm + 128 * (v0 + w) : g_km + 64 * (u0 + w)) + h * 1024 + 2 * lane;
    const bool mown = !PV && w == rank && rank < 2;
    auto xload = [&](int s) {
        mbar_expect(barX, 8192 - nq * 512);
        bulk_load(sb + CH_XS, g_kx + (size_t)(s * NH + h) * 4096 + u0 * 256, nq * 512, barX);
        bulk_load(sb + CH_XS + nq * 512, g_vx + (size_t)(s * NH + h) * 4096 + (v0 + nq) * 512, (8 - nq) * 1024, barX);
    };
    if (!PV && w == 2 && lane == 0) xload(0);
    uint32_t sw[8][4];
#pragma unroll
    for (int i = 0; i < 8; i++) ldsm4t(sw[i], wl + i * 512);
    mbar_wait(barX, 0);

    auto step = [&](const int s, auto lastc) {
        constexpr bool last = decltype(lastc)::value;
        const uint32_t slot = (s & 3) << 14;
        uint2 b[8];
        const uint32_t z0 = delay<DLM>(zero);
        TIM(0);
        poll_issue<8>(b, m_rd + slot + z0, true);
        GT(0, z0);
        if (!last) {
            if (PV) { if (w == 7 && lane == 0) mbar_expect(barS, 3 * 1280); }
            else {
                if (w == (rank & 1) && lane == 0) mbar_expect(barM, rank < 2 ? 2 * 512 : 8);
                if (mown) { st_pub(pub + (slot ^ 0x8000), SENT, SENT); st_pub(pub + (slot ^ 0x8000) + 4096, SENT, SENT); }
            }
        }
        POLLCHK(8, b, m_rd + slot, 0);
        TIM(1);
        {
            float acc[6][4];
#pragma unroll
            for (int kk = 0; kk < 8; kk++) {
                const int j = (2 * kk) & 7;
                if (kk == 0) { mma16z(acc[5], sw[0], b[0].x, b[0].y); mma16z(acc[4], sw[1], b[0].x, b[0].y); }
                else { mma16(acc[5], sw[j], b[kk].x, b[kk].y); mma16(acc[4], sw[j + 1], b[kk].x, b[kk].y); }
#pragma unroll
                for (int i = 0; i < 4; i++) {
                    if (kk == 0) mma16z(acc[i], wa[i * 8], b[0].x, b[0].y);
                    else mma16(acc[i], wa[i * 8 + kk], b[kk].x, b[kk].y);
                    if (i < 2) ldsm4t(sw[j + i], wl + (8 + 2 * kk + i) * 512);
                }
            }
#pragma unroll
            for (int i = 0; i < 6; i++) sts128(wl + CH_PART + ((i + 4) % 6) * 512, acc[(i + 4) % 6]);
        }
        TIM(2);
        float va[4][4];
        uint32_t kf;
        if (!PV) {
            uint32_t xf[4];
            bar_sync(1, 256);
            float4 v[8];
#pragma unroll
            for (int i = 0; i < 8; i++) v[i] = lds128(pl + i * CH_WREG);
            ldsm4(xf, xs);
            float4 r = add4(add4(add4(v[0], v[1]), add4(v[2], v[3])), add4(add4(v[4], v[5]), add4(v[6], v[7])));
            uint32_t qf = movm(pack_bf16(r.x, r.y));
            kf = movm(pack_bf16(r.z, r.w));
            if (!last) {
                float s0[4], s1[4], s2[4], s3[4], s4[4];
                mma8z(s0, qf, 0, xf[0]); mma8z(s1, qf, 0, xf[1]); mma8z(s2, qf, 0, xf[2]); mma8z(s3, qf, 0, xf[3]);
                mma8z(s4, qf, 0, kf);
                const float x0[4] = {s0[0], s0[1], s1[0], s1[1]}, x1[4] = {s2[0], s2[1], s3[0], s3[1]};
                sts128(pl, x0); sts128(pl + CH_WREG, x1);
                sts64(pl + 2 * CH_WREG - lane * 8, s4[0], s4[1]);
                bar_arrive(2, nq * 32 + 64);
            }
            TIM(4);
        } else {
            bar_sync(1, 256);
        }
        {
            const float z = __uint_as_float(delay<1>(zero));
#pragma unroll
            for (int i = 0; i < 4; i++) va[i][0] = va[i][1] = va[i][2] = va[i][3] = z;
        }
#pragma unroll
        for (int kk = 0; kk < 8; kk++) {
            mma16(va[kk & 1], sw[kk], b[kk].x, b[kk].y);
            mma16(va[2 + (kk & 1)], wa[32 + kk], b[kk].x, b[kk].y);
        }
#pragma unroll
        for (int j = 0; j < 4; j++) { va[0][j] += va[1][j]; va[2][j] += va[3][j]; }
        sts128(wl + CH_PART + 6 * 512, va[0]);
        sts128(wl + CH_PART + 7 * 512, va[2]);
        TIM(6);
        uint32_t vm0, vm1;
        uint32_t so[10][4];
        if (PV) {
            uint32_t vt0[4], vt1[4];
            ldsm4t(vt0, xs); ldsm4t(vt1, xs + 512);
            if (w >= 6 && !last) {
                const uint32_t sa = sb + CH_PART + (w - 6) * CH_WREG + lane * 16, sc = sb + CH_PART + 2 * CH_WREG + (w - 6) * 128 + lane * 4;
                const uint32_t da = sb + CH_SX + rank * 1280 + (w - 6) * 512 + lane * 16, dc = sb + CH_SX + rank * 1280 + 1024 + (w - 6) * 128 + lane * 4;
                bar_sync(2, nq * 32 + 64);
                float4 v[6]; float c[6];
#pragma unroll
                for (int i = 0; i < 6; i++) {
                    v[i] = (i < 5 || rank == 0) ? lds128(sa + i * 512) : make_float4(0, 0, 0, 0);
                    c[i] = (i < 5 || rank == 0) ? lds32(sc + i * 512) : 0.f;
                }
                float4 sv = add4(add4(add4(v[0], v[1]), add4(v[2], v[3])), add4(v[4], v[5]));
                float cv = ((c[0] + c[1]) + (c[2] + c[3])) + (c[4] + c[5]);
#pragma unroll
                for (int d = 1; d < 4; d++) {
                    const int dr = rank + d - (rank + d > 2 ? 3 : 0);
                    st_async4(mapa(da, dr), sv, mapa(barS, dr)); st_async1(mapa(dc, dr), cv, mapa(barS, dr));
                }
                TIM(5);
            }
            bar_sync(3, 256);
            float4 r = sum8(pl);
            vm0 = pack_bf16(r.x, r.y); vm1 = pack_bf16(r.z, r.w);
            TIM(7);
            if (!last) {
#pragma unroll
                for (int i = 0; i < NPRE_O; i++) ldsm4t(so[i], wl + (24 + i) * 512);
                mbar_wait(barS, s & 1);
                TIM(8);
                const uint32_t sx = sb + CH_SX + lane * 16;
                float4 a0 = lds128(sx), a1 = lds128(sx + 1280), a2 = lds128(sx + 2560);
                float4 b0 = lds128(sx + 512), b1 = lds128(sx + 512 + 1280), b2 = lds128(sx + 512 + 2560);
                float2 c0 = lds64(sx + 1024 - lane * 8), c1 = lds64(sx + 1024 + 1280 - lane * 8), c2 = lds64(sx + 1024 + 2560 - lane * 8);
                a0 = add4(add4(a0, a1), a2); b0 = add4(add4(b0, b1), b2);
                float sc[10] = {a0.x, a0.y, a0.z, a0.w, b0.x, b0.y, b0.z, b0.w, c0.x + c1.x + c2.x, c0.y + c1.y + c2.y};
                float mx = fmaxf(fmaxf(fmaxf(sc[0], sc[1]), fmaxf(sc[2], sc[3])), fmaxf(fmaxf(sc[4], sc[5]), fmaxf(sc[6], sc[7])));
                mx = fmaxf(mx, fmaxf(sc[8], sc[9]));
                mx = fmaxf(fmaxf(mx, __shfl_xor_sync(0xffffffffu, mx, 1)),
                           fmaxf(__shfl_xor_sync(0xffffffffu, mx, 2), __shfl_xor_sync(0xffffffffu, mx, 3)));
                const float cs = 0.08838834764831845f * 1.4426950408889634f;
                const float mb = -mx * cs;
#pragma unroll
                for (int j = 0; j < 10; j++) sc[j] = ex2(fmaf(sc[j], cs, mb));
                uint32_t pf[5];
#pragma unroll
                for (int j = 0; j < 5; j++) pf[j] = pack_bf16(sc[2 * j], sc[2 * j + 1]);
                float o0[4], o1[4], o2[4], o3[4], o4[4], o5[4];
                const uint32_t p0[4] = {pf[0], 0, pf[1], 0}, p1[4] = {pf[2], 0, pf[3], 0};
                mma16z(o0, p0, vt0[0], vt0[1]); mma16z(o1, p0, vt1[0], vt1[1]);
                mma16z(o2, p1, vt0[2], vt0[3]); mma16z(o3, p1, vt1[2], vt1[3]);
                mma8z(o4, pf[4], 0, vm0); mma8z(o5, pf[4], 0, vm1);
                float sum = (((sc[0] + sc[1]) + (sc[2] + sc[3])) + ((sc[4] + sc[5]) + (sc[6] + sc[7]))) + (sc[8] + sc[9]);
                sum = (sum + __shfl_xor_sync(0xffffffffu, sum, 1)) + (__shfl_xor_sync(0xffffffffu, sum, 2) + __shfl_xor_sync(0xffffffffu, sum, 3));
                const float inv = __fdividef(1.f, sum);
                const uint32_t ox = pack_bf16((o0[0] + o2[0] + o4[0]) * inv, (o0[1] + o2[1] + o4[1]) * inv);
                const uint32_t oy = pack_bf16((o1[0] + o3[0] + o5[0]) * inv, (o1[1] + o3[1] + o5[1]) * inv);
                st_pub(pub + slot, ox, oy); st_pub(pub + slot + 4096, ox, oy);
                bar_arrive(4, 256);
#pragma unroll
                for (int i = NPRE_O; i < 10; i++) ldsm4t(so[i], wl + (24 + i) * 512);
            }
            ((uint32_t*)kvo)[0] = movm(vm0); ((uint32_t*)kvo)[32] = movm(vm1);
        } else {
            *(uint32_t*)kvo = kf;
            if (last) bar_arrive(3, 256);
            else {
                bar_sync(3, 256);
                if (w == 2 && lane == 0) xload(s + 1);
                const uint32_t z = delay<2>(zero);
                GT(1, z);
#pragma unroll
                for (int i = 0; i < 10; i++) ldsm4t(so[i], wl + z + (24 + i) * 512);
                if (w == 3 && lane == 0 && (s & 3) == 0 && s) { __threadfence(); atomicAdd(g_ctr + C_CHAIN + (s >> 2) - 1, 1); }
                bar_sync(4, 256);
            }
        }
        if (last) return;
        uint2 c[11];
        const uint32_t z1 = delay<PV ? (DLO > 2 ? DLO - 2 : 0) : DLO>(zero);
        TIM(9);
        poll_issue<11>(c, o_rd + slot + z1, rank < 2);
        GT(2, z1);
        kvo += NH * 8 * DH;
        POLLCHK(11, c, o_rd + slot, 1);
        TIM(10);
        {
            float acc[4][4];
#pragma unroll
            for (int f = 0; f < 22; f++) {
                const int kk = f >> 1, a = f & 3;
                if (f < 4) mma16z(acc[a], so[f % 10], c[kk].x, c[kk].y);
                else mma16(acc[a], so[f % 10], c[kk].x, c[kk].y);
                if (f + 10 < 22) ldsm4t(so[f % 10], wl + (24 + f + 10) * 512);
            }
#pragma unroll
            for (int i = 0; i < 2; i++) {
#pragma unroll
                for (int j = 0; j < 4; j++) acc[i][j] += acc[i + 2][j];
                sts128(wl + CH_PART + i * 512, acc[i]);
            }
        }
        TIM(11);
        if (!PV && w < 2) {
            bar_sync(5, 256);
            float4 r = sum8(pl);
            if (!mown) {
                st_async4(mapa(sb + CH_MX + rank * 512 + lane * 16, w), r, mapa(barM, w));
                if (rank < 2 && lane == 0) st_async1(mapa(sb + CH_MX + rank * 4, 2), r.x, mapa(barM, 2));
            }
            bar_arrive(7, 256);
#pragma unroll
            for (int i = 0; i < 8; i++) ldsm4t(sw[i], wl + i * 512);
            mbar_wait(barX, (s + 1) & 1);
            if (!mown) {
                if (rank == 2 && w == 0) mbar_wait(barM, s & 1);
            } else {
                TIM(12);
                mbar_wait(barM, s & 1);
                TIM(13);
                float4 x = lds128(sb + CH_MX + (rank ^ 1) * 512 + lane * 16), y = lds128(sb + CH_MX + 2 * 512 + lane * 16);
                r = add4(add4(x, r), y);
                const uint32_t mx = movm(pack_bf16(r.x, r.y)), my = movm(pack_bf16(r.z, r.w));
                const uint32_t ns = (slot + 0x4000) & 0xC000;
                st_pub(pub + ns, mx, my); st_pub(pub + ns + 4096, mx, my);
                TIM(14);
            }
        } else {
            bar_arrive(5, 256);
            if (PV) { st_pub(pub + (slot ^ 0x8000), SENT, SENT); st_pub(pub + (slot ^ 0x8000) + 4096, SENT, SENT); }
            bar_sync(7, 256);
#pragma unroll
            for (int i = 0; i < 8; i++) ldsm4t(sw[i], wl + i * 512);
            GT(3, sw[0][0]);
            mbar_wait(barX, (s + 1) & 1);
        }
        bar_sync(6, 256);
    };
#pragma unroll 1
    for (int s = 0; s < NSEG - 1; s++) step(s, BoolC<false>());
    step(NSEG - 1, BoolC<true>());
    bar_sync(6, 256);
    if (!PV && w == 3 && lane == 0) { __threadfence(); atomicAdd(g_ctr + C_CHAIN + 15, 1); }
}

__global__ void __cluster_dims__(3, 1, 1) __launch_bounds__(256, 1)
chain_kernel(const bf16* __restrict__ Wq, const bf16* __restrict__ Wk, const bf16* __restrict__ Wv, const bf16* __restrict__ Wo,
             int aware) {
    extern __shared__ __align__(1024) unsigned char smem[];
    const uint32_t sb = smem_u32(smem);
    const int tid = threadIdx.x, lane = tid & 31;
    const int w = __shfl_sync(0xffffffffu, tid >> 5, 0);
    int rank; asm("mov.u32 %0, %%cluster_ctarank;" : "=r"(rank));
    const int h = blockIdx.x / 3;
    const int nq = rank == 0 ? 6 : 5;
    const int u0 = rank == 0 ? 0 : 1 + 5 * rank;
    const int v0 = rank == 0 ? -6 : 3 * rank - 6;
    const int gw = rank * 8 + w;
    const int ks0 = gw < 16 ? 11 * gw : 176 + 10 * (gw - 16);
    const int nko = gw < 16 ? 11 : 10;
    const uint32_t wr = sb + w * CH_WREG;
    if (tid == 0) {
        mbar_init(sb + CH_BAR, 1); mbar_init(sb + CH_BAR + 8, 1); mbar_init(sb + CH_BAR + 16, 1);
        *(int*)(smem + CH_BAR + 24) = 0;
        asm volatile("fence.mbarrier_init.release.cluster;" ::: "memory");
    }
    __threadfence();
    asm volatile("griddepcontrol.launch_dependents;" ::: "memory");
    uint32_t smid; asm("mov.u32 %0, %%smid;" : "=r"(smid));
    const int side = __shfl_sync(0xffffffffu, aware ? g_side[smid] ^ (aware - 1) : 0, 0);

    uint32_t wa[40][4];
    {
        const int r8 = lane & 7, p = lane >> 3;
        const bf16* src[4]; int tile[4], half[4];
#pragma unroll
        for (int q = 0; q < 4; q++) {
            int e = 4 * q + p;
            if (e < nq) { tile[q] = e; half[q] = 0; src[q] = Wq + h * DH + 8 * (u0 + e); }
            else if (e < 2 * nq) { tile[q] = e - nq; half[q] = 1; src[q] = Wk + h * DH + 8 * (u0 + e - nq); }
            else { int f = e - 2 * nq; tile[q] = nq + (f >> 1); half[q] = f & 1; src[q] = Wv + h * DH + 16 * (v0 + tile[q]) + 8 * half[q]; }
            src[q] += (size_t)(128 * w + r8) * HD;
        }
        const bf16* so = Wo + (size_t)(16 * ks0 + r8) * DM + 32 * h + 8 * p;
        const uint32_t dso = (p >> 1) * 512 + (p & 1) * 128 + r8 * 16;
#pragma unroll 1
        for (int kh = 0; kh < 16; kh++)
#pragma unroll
            for (int q = 0; q < 4; q++)
                if (tile[q] < 4 || tile[q] == 7) cp16(wr + (min(tile[q], 4) * 8 + (kh >> 1)) * 512 + ((kh & 1) * 2 + half[q]) * 128 + r8 * 16, src[q] + (size_t)kh * 8 * HD);
        asm volatile("cp.async.wait_all;" ::: "memory");
        __syncwarp();
#pragma unroll
        for (int i = 0; i < 40; i++) ldsm4t(wa[i], wr + i * 512 + lane * 16);
        __syncwarp();
#pragma unroll 1
        for (int kh = 0; kh < 16; kh++)
#pragma unroll
            for (int q = 0; q < 4; q++)
                if (tile[q] >= 4 && tile[q] < 7) cp16(wr + (tile[q] == 6 ? 16 + (kh >> 1) : (kh >> 1) * 2 + 5 - tile[q]) * 512 + ((kh & 1) * 2 + half[q]) * 128 + r8 * 16, src[q] + (size_t)kh * 8 * HD);
#pragma unroll 1
        for (int kh = 0; kh < 22; kh++) {
            uint32_t d = wr + (24 + (kh >> 1) * 2) * 512 + (kh & 1) * 256 + dso;
            if (kh < 2 * nko) cp16(d, so + (size_t)kh * 8 * DM);
            else asm volatile("st.shared.v4.u32 [%0], {%1,%1,%1,%1};" ::"r"(d), "r"(0) : "memory");
        }
        asm volatile("cp.async.wait_all;" ::: "memory");
    }
    asm volatile("griddepcontrol.wait;" ::: "memory");
    asm volatile("fence.proxy.async;" ::: "memory");
    __syncthreads();
    asm volatile("barrier.cluster.arrive.aligned; barrier.cluster.wait.aligned;" ::: "memory");
    if (w >= nq) chain_loop<true>(wa, sb, w, lane, rank, h, side);
    else chain_loop<false>(wa, sb, w, lane, rank, h, side);
}

constexpr int G_STAGE = 49152, G_NST = 4;
constexpr int G_STG = G_NST * G_STAGE;
constexpr int G_BAR = G_STG + 32768;
constexpr int G_SMEM = G_BAR + 128 + 1024;

__global__ void __launch_bounds__(384, 1)
kv_kernel(const __grid_constant__ CUtensorMap mx, const __grid_constant__ CUtensorMap mk, const __grid_constant__ CUtensorMap mv,
          const bf16* __restrict__ mem0) {
    extern __shared__ unsigned char smem_raw[];
    const uint32_t sb = (smem_u32(smem_raw) + 1023) & ~1023u;
    const uint32_t full = sb + G_BAR, empty = full + 32;
    const int tid = threadIdx.x, wg = tid >> 7, lane = tid & 31;
    if (tid == 0)
        for (int i = 0; i < G_NST; i++) { mbar_init(full + 8 * i, 1); mbar_init(empty + 8 * i, 2); }
    __syncthreads();
    if (wg == 0) {
        reg_dec<40>();
        if (tid == 0) {
            asm volatile("fence.proxy.async;" ::: "memory");
            int it = 0;
            for (int p = blockIdx.x; p < 512; p += gridDim.x) {
                const int m0 = (p & 15) * 128, nt = p >> 4;
                const CUtensorMap* mw = nt < 16 ? &mk : &mv;
                const int ng = (nt & 15) * 4;
                for (int kb = 0; kb < 16; kb++, it++) {
                    const int st = it & 3;
                    mbar_wait(empty + 8 * st, ((it >> 2) & 1) ^ 1);
                    mbar_expect(full + 8 * st, G_STAGE);
                    const uint32_t a = sb + st * G_STAGE;
                    tma2d(a, &mx, kb * 64, m0, full + 8 * st);
                    tma3d(a + 16384, mw, 0, kb * 64, ng, full + 8 * st);
                    tma3d(a + 32768, mw, 0, kb * 64, ng + 2, full + 8 * st);
                }
            }
        } else if (tid >= 32) {
            char* ring = ring_base();
            for (int k = blockIdx.x * 96 + tid - 32; k < (1 << 17); k += gridDim.x * 96) {
                uint2 v = make_uint2(SENT, SENT);
                int off = k * 8, chunk = ((off >> 13) & 1) | ((off >> 16) << 1), slot = (off >> 14) & 3, in = off & 4095;
                if (in >= 3072) continue;
                if (chunk >= 24 && slot == 0 && in < 2048) {
                    int ks = (chunk - 24) * 8 + (in >> 8), l = (in >> 3) & 31;
                    const uint32_t* p = (const uint32_t*)(mem0 + (l >> 2) * DM + 16 * ks + 2 * (l & 3));
                    v.x = p[0]; v.y = p[4];
                    if (v.x == SENT) v.x = 0x7FFF7FFFu;
                }
                *(uint2*)(ring + off) = v;
            }
            if (blockIdx.x == 0)
                for (int k = tid - 32; k < N_CTR; k += 96) g_ctr[k] = 0;
            if (tid == 32) {
                uint32_t smid; asm("mov.u32 %0, %%smid;" : "=r"(smid));
                uint32_t* p0 = (uint32_t*)(ring + ring_off(smid & 15, 0) + 3072 + (smid >> 4) * 64);
                uint32_t* p1 = (uint32_t*)(ring + ring_off(smid & 15, 1) + 3072 + (smid >> 4) * 64);
                *p0 = 0; *p1 = 0;
                int b0 = 1 << 30, b1 = 1 << 30; uint32_t v = 0;
                for (int r = 0; r < 24; r++) {
                    uint32_t t0 = clk(); v = atomicExch(p0 + (v == 50), r); uint32_t t1 = v == 77 ? clk() + 1 : clk(); b0 = min(b0, (int)(t1 - t0));
                    t0 = clk(); v = atomicExch(p1 + (v == 50), r); t1 = v == 77 ? clk() + 1 : clk(); b1 = min(b1, (int)(t1 - t0));
                }
                g_side[smid] = b1 < b0;
            }
            __threadfence();
            bar_sync(1, 96);
            asm volatile("griddepcontrol.launch_dependents;" ::: "memory");
        }
    } else {
        reg_inc<232>();
        const int wi = (tid >> 5) & 3;
        float acc[128];
        uint32_t pk[64];
        uint32_t* dst = nullptr;
        int it = 0;
        for (int p = blockIdx.x; p < 512; p += gridDim.x) {
#pragma unroll
            for (int kb = 0; kb < 16; kb++, it++) {
                const int st = kb & 3;
                mbar_wait(full + 8 * st, (it >> 2) & 1);
                const uint64_t da = mkdesc(sb + st * G_STAGE + (wg - 1) * 8192, 16, 1024, 1);
                const uint64_t db = mkdesc(sb + st * G_STAGE + 16384, 8192, 1024, 1);
                wg_fence();
#pragma unroll
                for (int k = 0; k < 4; k++) wgmma256(acc, da + k * 2, db + k * 128, kb | k);
                wg_commit();
                if (dst) {
#pragma unroll
                    for (int j = 0; j < 4; j++) dst[(kb * 2 + (j >> 1)) * 128 + (j & 1) * 32] = pk[kb * 4 + j];
                }
                if (kb > 0) {
                    wg_wait<1>();
                    if ((tid & 127) == 0) mbar_arrive(empty + 8 * ((kb - 1) & 3));
                }
            }
            wg_wait<0>();
            if ((tid & 127) == 0) mbar_arrive(empty + 8 * 3);
#pragma unroll
            for (int j = 0; j < 64; j++) pk[j] = pack_bf16(acc[2 * j], acc[2 * j + 1]);
            const int row = (p & 15) * 128 + (wg - 1) * 64 + wi * 16, nt = p >> 4;
            dst = (uint32_t*)(nt < 16 ? g_kx : g_vx) + (size_t)((row >> 5) * 512 + (nt & 15) * 32) * 128 + (row & 31) * 4 + lane;
        }
#pragma unroll
        for (int j = 0; j < 64; j++) dst[(j >> 1) * 128 + (j & 1) * 32] = pk[j];
    }
}

#define WLOG(e)
struct S4Params { const bf16 *Are, *Aim, *Bre, *Bim, *Cre, *Cim, *ldt, *dsk; };
constexpr int IT_QA = 0, IT_O = 1, IT_S4 = 2, IT_END = 3;
#define O_WIDE 11
__device__ __forceinline__ int o_items(int b) { return b < O_WIDE ? 4 : 8; }
__device__ __forceinline__ int ld_acq(const int* p) { int v; asm volatile("ld.acquire.gpu.global.s32 %0, [%1];" : "=r"(v) : "l"(p) : "memory"); return v; }
__device__ __forceinline__ void wait_ctr(const int* p, int n) {
    for (int it = 0; it < (1 << 22) && ld_acq(p) < n; it++) __nanosleep(64);
}
__device__ __forceinline__ void stsm4(uint32_t addr, uint32_t a, uint32_t b, uint32_t c, uint32_t d) {
    asm volatile("stmatrix.sync.aligned.m8n8.x4.shared.b16 [%0], {%1,%2,%3,%4};" ::"r"(addr), "r"(a), "r"(b), "r"(c), "r"(d) : "memory");
}
__device__ __forceinline__ void stsm4t(uint32_t addr, uint32_t a, uint32_t b, uint32_t c, uint32_t d) {
    asm volatile("stmatrix.sync.aligned.m8n8.x4.trans.shared.b16 [%0], {%1,%2,%3,%4};" ::"r"(addr), "r"(a), "r"(b), "r"(c), "r"(d) : "memory");
}
__device__ __forceinline__ void tma2d_store(const CUtensorMap* m, uint32_t src, int c0, int c1) {
    asm volatile("cp.async.bulk.tensor.2d.global.shared::cta.bulk_group [%0, {%2, %3}], [%1];" ::"l"(m), "r"(src), "r"(c0), "r"(c1) : "memory");
}
__device__ __forceinline__ void mma8(float (&d)[4], uint32_t a0, uint32_t a1, uint32_t b0) {
    asm volatile("mma.sync.aligned.m16n8k8.row.col.f32.bf16.bf16.f32 {%0,%1,%2,%3}, {%4,%5}, {%6}, {%0,%1,%2,%3};"
        : "+f"(d[0]), "+f"(d[1]), "+f"(d[2]), "+f"(d[3]) : "r"(a0), "r"(a1), "r"(b0));
}

__device__ __forceinline__ void attn_head(const uint32_t (&q)[32], uint32_t sk, uint32_t sv, uint32_t fullv, uint32_t parv, uint32_t emptyk,
                                          int wi, int lane, uint32_t* dst) {
    const int g = lane >> 2, t = lane & 3, hi = wi & 1;
    float s[5][4];
#pragma unroll
    for (int j = 0; j < 5; j++) s[j][0] = s[j][1] = s[j][2] = s[j][3] = 0.f;
#pragma unroll
    for (int k2 = 0; k2 < 4; k2++) {
        uint32_t km[4];
        ldsm4(km, sk + 8192 + k2 * 512 + lane * 16);
#pragma unroll
        for (int i = 0; i < 2; i++) {
            const int ks = 2 * k2 + i;
            const uint32_t a[4] = {q[4 * ks], q[4 * ks + 1], q[4 * ks + 2], q[4 * ks + 3]};
            uint32_t b[4];
            const uint32_t ad = sk + ks * 1024 + ((lane >> 3) & 1) * 512 + (lane >> 4) * 128 + (lane & 7) * 16;
            ldsm4(b, ad);
            mma16(s[4], a, km[2 * i], km[2 * i + 1]);
            mma16(s[0], a, b[0], b[1]); mma16(s[1], a, b[2], b[3]);
            if (hi) { ldsm4(b, ad + 256); mma16(s[2], a, b[0], b[1]); mma16(s[3], a, b[2], b[3]); }
        }
    }
    __syncwarp();
    if (lane == 0) mbar_arrive(emptyk);
    const int r0 = hi * 16 + g;
    float m0 = fmaxf(s[4][0], s[4][1]), m1 = fmaxf(s[4][2], s[4][3]);
#pragma unroll
    for (int j = 0; j < 4; j++) {
        const int c = 8 * j + 2 * t;
        if (c > r0) s[j][0] = -INFINITY;
        if (c + 1 > r0) s[j][1] = -INFINITY;
        if (c > r0 + 8) s[j][2] = -INFINITY;
        if (c + 1 > r0 + 8) s[j][3] = -INFINITY;
        m0 = fmaxf(m0, fmaxf(s[j][0], s[j][1])); m1 = fmaxf(m1, fmaxf(s[j][2], s[j][3]));
    }
    m0 = fmaxf(m0, __shfl_xor_sync(0xffffffffu, m0, 1)); m1 = fmaxf(m1, __shfl_xor_sync(0xffffffffu, m1, 1));
    m0 = fmaxf(m0, __shfl_xor_sync(0xffffffffu, m0, 2)); m1 = fmaxf(m1, __shfl_xor_sync(0xffffffffu, m1, 2));
    const float cs = 0.08838834764831845f * 1.4426950408889634f;
    m0 *= -cs; m1 *= -cs;
    float l0 = 0, l1 = 0;
#pragma unroll
    for (int j = 0; j < 5; j++) {
        s[j][0] = ex2(fmaf(s[j][0], cs, m0)); s[j][1] = ex2(fmaf(s[j][1], cs, m0));
        s[j][2] = ex2(fmaf(s[j][2], cs, m1)); s[j][3] = ex2(fmaf(s[j][3], cs, m1));
        l0 += s[j][0] + s[j][1]; l1 += s[j][2] + s[j][3];
    }
    l0 += __shfl_xor_sync(0xffffffffu, l0, 1); l1 += __shfl_xor_sync(0xffffffffu, l1, 1);
    l0 += __shfl_xor_sync(0xffffffffu, l0, 2); l1 += __shfl_xor_sync(0xffffffffu, l1, 2);
    l0 = __fdividef(1.f, l0); l1 = __fdividef(1.f, l1);
    uint32_t p[10];
#pragma unroll
    for (int j = 0; j < 5; j++) { p[2 * j] = pack_bf16(s[j][0] * l0, s[j][1] * l0); p[2 * j + 1] = pack_bf16(s[j][2] * l1, s[j][3] * l1); }
    const uint32_t p0[4] = {p[0], p[1], p[2], p[3]}, p1[4] = {p[4], p[5], p[6], p[7]};
    mbar_wait(fullv, parv);
#pragma unroll
    for (int u4 = 0; u4 < 4; u4++) {
        uint32_t vm[4];
        ldsm4t(vm, sv + 8192 + u4 * 512 + lane * 16);
#pragma unroll
        for (int i = 0; i < 4; i++) {
            const int u = 4 * u4 + i;
            uint32_t b[4];
            ldsm4t(b, sv + u * 512 + lane * 16);
            float o[4];
            mma16z(o, p0, b[0], b[1]);
            if (hi) mma16(o, p1, b[2], b[3]);
            mma8(o, p[8], p[9], vm[i]);
            dst[(u >> 3) * 4096 + (u & 7) * 32] = pack_bf16(o[0], o[1]);
            dst[(u >> 3) * 4096 + (u & 7) * 32 + 256] = pack_bf16(o[2], o[3]);
        }
    }
}

template <int BN, int NKB, bool BLOCKED_A>
__device__ __forceinline__ void mainloop(float (&acc)[BN / 2], uint32_t sb, int wgi, uint32_t full, uint32_t empty, int& it, bool elect) {
#pragma unroll
    for (int j = 0; j < BN / 2; j++) acc[j] = 0.f;
#pragma unroll 1
    for (int k4 = 0; k4 < NKB; k4 += 4) {
#pragma unroll
        for (int st = 0; st < 4; st++, it++) {
            mbar_wait(full + 8 * st, (it >> 2) & 1);
            const uint64_t da = BLOCKED_A ? mkdesc(sb + st * G_STAGE + wgi * 8192, 128, 1024, 0) : mkdesc(sb + st * G_STAGE + wgi * 8192, 16, 1024, 1);
            const uint64_t db = mkdesc(sb + st * G_STAGE + 16384, 8192, 1024, 1);
            wg_fence();
#pragma unroll
            for (int k = 0; k < 4; k++) {
                if constexpr (BN == 256) wgmma256(acc, da + k * (BLOCKED_A ? 16 : 2), db + k * 128, 1);
                else wgmma128(acc, da + k * (BLOCKED_A ? 16 : 2), db + k * 128, 1);
            }
            wg_commit();
            if (k4 | st) {
                wg_wait<1>();
                if (elect) mbar_arrive(empty + 8 * ((st + 3) & 3));
            }
        }
    }
    wg_wait<0>();
    if (elect) mbar_arrive(empty + 8 * 3);
}

template <int BN>
__device__ __forceinline__ void o_item(uint32_t sb, int wgi, int wi, int lane, uint32_t full, uint32_t empty, int& it, const CUtensorMap* mout,
                                       int row0, int col0) {
    float acc[BN / 2];
    mainloop<BN, 64, true>(acc, sb, wgi, full, empty, it, lane == 0);
    const uint32_t stg = sb + G_STG + (wgi * 4 + wi) * 4096;
    const int r = lane & 15, cu = lane >> 4;
#pragma unroll
    for (int hf = 0; hf < BN / 128; hf++) {
        if (lane == 0) asm volatile("cp.async.bulk.wait_group.read 0;" ::: "memory");
        __syncwarp();
#pragma unroll
        for (int j = 0; j < 8; j++) {
            const float* a = acc + hf * 64 + j * 8;
            stsm4(stg + (j >> 2) * 2048 + r * 128 + ((((j & 3) * 2 + cu) ^ (r & 7)) << 4),
                  pack_bf16(a[0], a[1]), pack_bf16(a[2], a[3]), pack_bf16(a[4], a[5]), pack_bf16(a[6], a[7]));
        }
        asm volatile("fence.proxy.async.shared::cta;" ::: "memory");
        __syncwarp();
        if (lane == 0) {
            tma2d_store(mout, stg, col0 + hf * 128, row0 + wgi * 64 + wi * 16);
            tma2d_store(mout, stg + 2048, col0 + hf * 128 + 64, row0 + wgi * 64 + wi * 16);
            asm volatile("cp.async.bulk.commit_group;" ::: "memory");
        }
    }
}

constexpr int S4_RAW = G_STG;
constexpr int S4_CH = 0;
constexpr int S4_UT = 0;
constexpr int S4_WD = 5120;
constexpr int S4_STRIDE = 5120 + 8320 + 16;

__device__ __forceinline__ float2 cmul(float2 a, float2 b) { return make_float2(a.x * b.x - a.y * b.y, a.x * b.y + a.y * b.x); }
__device__ __forceinline__ float2 csq(float2 a) { return make_float2(a.x * a.x - a.y * a.y, (a.x + a.x) * a.y); }
__device__ __forceinline__ float2 cexp_t(float lr, float turns) {
    float f = (turns - rintf(turns)) * 6.283185307179586f, e = ex2(lr);
    return make_float2(e * __cosf(f), e * __sinf(f));
}
__device__ __forceinline__ void s4_lda(uint32_t (&a)[4], uint32_t ad) {
    asm volatile("ld.shared.u32 %0, [%4]; ld.shared.u32 %1, [%4+32]; ld.shared.u32 %2, [%4+-32]; ld.volatile.shared.u32 %3, [%4];"
        : "=r"(a[0]), "=r"(a[1]), "=r"(a[2]), "=r"(a[3]) : "r"(ad) : "memory");
}
template <int H0>
__device__ __forceinline__ void s4_conv_step(float (&acc)[16][4], const uint32_t (&bw)[4][2][4], uint32_t (&nw)[4][2][4], uint32_t (&a)[2][4],
                                             uint32_t ut, uint32_t wd) {
#pragma unroll
    for (int h = H0; h < 4; h++) { ldsm4(nw[h][1], ut + (8 * h - 1) * 16 + 2560); ldsm4(nw[h][0], ut + (8 * h - 1) * 16); }
#pragma unroll
    for (int i = 0; i < 4; i++) {
        s4_lda(a[(i + 1) & 1], wd + (i + 1) * 64);
#pragma unroll
        for (int tau = 3; tau >= 0; tau--)
#pragma unroll
            for (int h = H0; h < 4; h++) {
                const int r = (tau - i) & 3;
                if (tau >= i) mma16(acc[4 * h + tau], a[i & 1], bw[h][r >> 1][2 * (r & 1)], bw[h][r >> 1][2 * (r & 1) + 1]);
                else mma16(acc[4 * h + tau], a[i & 1], nw[h][r >> 1][2 * (r & 1)], nw[h][r >> 1][2 * (r & 1) + 1]);
            }
    }
}
template <int H0>
__device__ __forceinline__ void s4_conv_phase(float (&acc)[16][4], uint32_t (&bw)[4][2][4], uint32_t (&a)[2][4], uint32_t ut, uint32_t wd) {
#pragma unroll 1
    for (int E = 8 * H0; E < 8 * H0 + 8; E += 2) {
        uint32_t nw[4][2][4];
        s4_conv_step<H0>(acc, bw, nw, a, ut - E * 16, wd + E * 256);
        s4_conv_step<H0>(acc, nw, bw, a, ut - E * 16 - 16, wd + E * 256 + 256);
    }
}

__device__ __forceinline__ void s4_item(uint32_t sb, int cw, int lane, int item, const S4Params& P, uint32_t ubar, uint32_t par, const CUtensorMap* mu,
                                        const CUtensorMap* my) {
    const int g = lane >> 2, t = lane & 3, d = item * 8 + cw;
    const uint32_t ch = sb + S4_CH + cw * S4_STRIDE;
    if (lane == 0) {
        asm volatile("cp.async.bulk.wait_group.read 0;" ::: "memory");
        mbar_expect(ubar, 4096);
        tma2d(sb + S4_RAW + cw * 4096, mu, item * 8, cw * 256, ubar);
    }
    const float dt = __bfloat162float(__float2bfloat16(expf(__bfloat162float(P.ldt[d]))));
#pragma unroll
    for (int i = 0; i < 4; i++) {
        const int n = d * 128 + i * 32 + lane;
        const float br = dt * __bfloat162float(P.Bre[n]), bi = dt * __bfloat162float(P.Bim[n]);
        const float cr = __bfloat162float(P.Cre[n]), ci = __bfloat162float(P.Cim[n]);
        const float v[4] = {dt * __bfloat162float(P.Are[n]) * 1.4426950408889634f, dt * __bfloat162float(P.Aim[n]) * 0.15915494309189535f,
                            cr * br - ci * bi, cr * bi + ci * br};
        sts128(ch + S4_WD + (i * 32 + lane) * 16, v);
    }
    __syncwarp();
    float kd[5][4], k2048 = 0.f;
#pragma unroll
    for (int j = 0; j < 5; j++) kd[j][0] = kd[j][1] = kd[j][2] = kd[j][3] = 0.f;
    const float x0 = (float)g, x1 = (float)(g + 8);
#pragma unroll 1
    for (int ks = 0; ks < 16; ks++) {
        uint32_t a[4][4], b[5][2];
#pragma unroll
        for (int i = 0; i < 2; i++) {
            const float4 p = lds128(ch + S4_WD + (ks * 8 + i * 4 + t) * 16);
            const float2 c = make_float2(p.z, p.w);
            float2 e0 = cexp_t(p.x * x0, p.y * x0), e1 = cexp_t(p.x * x1, p.y * x1);
#pragma unroll
            for (int j = 0; j < 4; j++) {
                a[j][2 * i] = pack_bf16(e0.x, e0.y); a[j][2 * i + 1] = pack_bf16(e1.x, e1.y);
                e0 = csq(e0); e1 = csq(e1);
            }
            float2 m = cmul(c, e0);
            b[0][i] = pack_bf16(m.x, -m.y);
#pragma unroll
            for (int j = 0; j < 4; j++) {
                m = cmul(c, e1);
                b[j + 1][i] = pack_bf16(m.x, -m.y);
                e1 = csq(e1);
            }
            k2048 += c.x * e1.x - c.y * e1.y;
        }
        mma16(kd[0], a[0], b[0][0], b[0][1]);
#pragma unroll
        for (int j = 0; j < 4; j++) mma16(kd[j + 1], a[j], b[j + 1][0], b[j + 1][1]);
    }
    k2048 += __shfl_xor_sync(0xffffffffu, k2048, 1);
    k2048 += __shfl_xor_sync(0xffffffffu, k2048, 2);
    {
        const uint32_t ta = ch + S4_UT + (lane & 7) * 32 + ((lane >> 3) & 1) * 16 + (lane >> 4) * 256;
        stsm4t(ta, pack_bf16(kd[0][0], kd[0][1]), pack_bf16(kd[0][2], kd[0][3]), pack_bf16(kd[1][0], kd[1][1]), pack_bf16(kd[1][2], kd[1][3]));
        stsm4t(ta + 512, pack_bf16(kd[2][0], kd[2][1]), pack_bf16(kd[2][2], kd[2][3]), pack_bf16(kd[3][0], kd[3][1]), pack_bf16(kd[3][2], kd[3][3]));
        stsm4t(ta + 1024, pack_bf16(kd[4][0], kd[4][1]), pack_bf16(kd[4][2], kd[4][3]), pack_bf16(k2048, 0.f), 0);
    }
    __syncwarp();
    if (lane < 16) asm volatile("st.shared.u32 [%0], %1;" ::"r"(ch + S4_WD + lane * 4), "r"(0) : "memory");
#pragma unroll
    for (int i = 0; i < 16; i++) {
        const int sh = i < 2 ? 0 : i < 4 ? 1 : i < 8 ? 2 : 3;
        uint32_t k[5];
#pragma unroll
        for (int j = 0; j < 5; j++) {
            const int x = i * 128 + lane * 4 + j - 1;
            int idx = sh ? 128 * sh + ((x + (1 << sh >> 1) - 1 + ((x >> sh) & 1)) >> sh) : x;
            if (i == 2 && j == 0 && lane == 0) idx = 255;
            asm volatile("ld.shared.u16 %0, [%1];" : "=r"(k[j]) : "r"(ch + S4_UT + max(idx, 0) * 2) : "memory");
        }
        if (i == 0 && lane == 0) k[0] = 0;
        asm volatile("st.shared.v4.u32 [%0], {%1,%2,%3,%4};" ::"r"(ch + S4_WD + 64 + i * 512 + lane * 16), "r"(k[1] | (k[0] << 16)),
                     "r"(k[2] | (k[1] << 16)), "r"(k[3] | (k[2] << 16)), "r"(k[4] | (k[3] << 16)) : "memory");
    }
    bar_sync(2, 256);
    if (lane < 8) {
#pragma unroll
        for (int i = 0; i < 8; i++) asm volatile("st.shared.v4.u32 [%0], {%1,%1,%1,%1};" ::"r"(ch + S4_UT + i * 640 + lane * 16), "r"(0) : "memory");
    }
    mbar_wait(ubar, par);
    const uint32_t traw = sb + S4_RAW + cw * 4096 + lane * 16;
    const uint32_t tch = sb + S4_CH + (lane & 7) * S4_STRIDE + S4_UT + (lane >> 3) * 640 + (8 + cw * 4) * 16;
#pragma unroll
    for (int i = 0; i < 8; i++) {
        uint32_t x[4];
        ldsm4t(x, traw + i * 512);
        stsm4(tch + (i & 1) * 2560 + (i >> 1) * 16, x[0], x[1], x[2], x[3]);
    }
    bar_sync(2, 256);
    float acc[16][4];
#pragma unroll
    for (int j = 0; j < 16; j++) acc[j][0] = acc[j][1] = acc[j][2] = acc[j][3] = 0.f;
    const uint32_t ut = ch + S4_UT + (lane >> 3) * 640 + (8 + (lane & 7)) * 16, wd = ch + S4_WD + 64 + (g - 2 * t) * 4;
    uint32_t bw[4][2][4], aw[2][4];
#pragma unroll
    for (int h = 0; h < 4; h++) { ldsm4(bw[h][0], ut + 8 * h * 16); ldsm4(bw[h][1], ut + 8 * h * 16 + 2560); }
    s4_lda(aw[0], wd);
    s4_conv_phase<0>(acc, bw, aw, ut, wd);
    s4_conv_phase<1>(acc, bw, aw, ut, wd);
    s4_conv_phase<2>(acc, bw, aw, ut, wd);
    if (lane == 0) mbar_arrive(ubar - 104 + 32 + 24);
    s4_conv_phase<3>(acc, bw, aw, ut, wd);
    __syncwarp();
#pragma unroll
    for (int j = 0; j < 16; j += 2)
        stsm4t(ut + (j >> 2) * 128 + (j & 2) * 1280, pack_bf16(acc[j][0], acc[j][1]), pack_bf16(acc[j][2], acc[j][3]),
               pack_bf16(acc[j + 1][0], acc[j + 1][1]), pack_bf16(acc[j + 1][2], acc[j + 1][3]));
    bar_sync(2, 256);
    const __nv_bfloat162 dk = *(const __nv_bfloat162*)(P.dsk + item * 8 + 2 * t);
#pragma unroll
    for (int i = 0; i < 8; i++) {
        uint32_t y[4], u[4];
        ldsm4t(y, tch + (i & 1) * 2560 + (i >> 1) * 16);
        ldsm4(u, traw + i * 512);
#pragma unroll
        for (int j = 0; j < 4; j++) {
            __nv_bfloat162 r = __hadd2_rn(*(__nv_bfloat162*)&y[j], __hmul2_rn(*(__nv_bfloat162*)&u[j], dk));
            y[j] = *(uint32_t*)&r;
        }
        stsm4(traw + i * 512, y[0], y[1], y[2], y[3]);
    }
    asm volatile("fence.proxy.async.shared::cta;" ::: "memory");
    __syncwarp();
    if (lane == 0) {
        tma2d_store(my, sb + S4_RAW + cw * 4096, DM + item * 8, cw * 256);
        asm volatile("cp.async.bulk.commit_group;" ::: "memory");
    }
}

__global__ void __launch_bounds__(384, 1)
worker_kernel(const __grid_constant__ CUtensorMap mx, const __grid_constant__ CUtensorMap mq, const __grid_constant__ CUtensorMap mo,
              const __grid_constant__ CUtensorMap mout, const __grid_constant__ CUtensorMap mu, const __grid_constant__ CUtensorMap my,
              const __grid_constant__ S4Params P) {
    extern __shared__ unsigned char smem_raw[];
    const uint32_t sb = (smem_u32(smem_raw) + 1023) & ~1023u;
    const uint32_t full = sb + G_BAR, empty = full + 32, ifull = full + 64, iempty = full + 80, islot = full + 96, ubar = full + 104;
    const int tid = threadIdx.x, wg = tid >> 7, lane = tid & 31;
    if (tid == 0) {
        for (int i = 0; i < G_NST; i++) { mbar_init(full + 8 * i, 1); mbar_init(empty + 8 * i, 8); }
        for (int i = 0; i < 2; i++) { mbar_init(ifull + 8 * i, 1); mbar_init(iempty + 8 * i, 8); }
        mbar_init(ubar, 8);
        asm volatile("fence.proxy.async;" ::: "memory");
    }
    __syncthreads();
    if (wg == 0) {
        reg_dec<40>();
        if (tid < 32) {
            int it = 0;
            for (int n = 0;; n++) {
                int item = -1;
                for (int spin = 0; item < 0; spin++) {
                    const int b = lane & 15;
                    const int taken = ld_acq(g_ctr + (lane < 16 ? C_QA_NEXT : C_O_NEXT) + b);
                    const int prog = ld_acq(g_ctr + C_CHAIN + b);
                    const int s4 = ld_acq(g_ctr + C_S4_NEXT);
                    const uint32_t left = __ballot_sync(0xffffffffu, taken < (lane < 16 ? 16 : o_items(b)));
                    const uint32_t done = __ballot_sync(0xffffffffu, prog >= 96) & 0xffff;
                    const uint32_t qa_ok = left & 0xffff & ((done << 1) | (s4 >= S4_FIRST ? 1 : 0));
                    const uint32_t o_ok = (left >> 16) & done & ~left;
                    int got = -1;
                    if (qa_ok) {
                        const int bb = __ffs(qa_ok) - 1;
                        if (lane == 0) { int i = atomicAdd(g_ctr + C_QA_NEXT + bb, 1); if (i < 16) got = (IT_QA << 16) | (bb << 8) | i; }
                    } else if (o_ok) {
                        const int bb = __ffs(o_ok) - 1;
                        if (lane == 0) { int i = atomicAdd(g_ctr + C_O_NEXT + bb, 1); if (i < o_items(bb)) got = (IT_O << 16) | (bb << 8) | i; }
                    } else if (s4 < 128) {
                        if (lane == 0) { int i = atomicAdd(g_ctr + C_S4_NEXT, 1); if (i < 128) got = (IT_S4 << 16) | i; }
                    } else if (!left || spin > (1 << 20)) got = IT_END << 16;
                    else __nanosleep(200);
                    item = __shfl_sync(0xffffffffu, got, 0);
                }
                if (lane == 0) {
                    mbar_wait(iempty + 8 * (n & 1), ((n >> 1) & 1) ^ 1);
                    asm volatile("st.shared.u32 [%0], %1;" ::"r"(islot + 4 * (n & 1)), "r"(item) : "memory");
                    mbar_arrive(ifull + 8 * (n & 1));
                    const int type = item >> 16, b = (item >> 8) & 255, i = item & 255;
                    if (type == IT_QA) {
                        for (int kb = 0; kb < 16; kb++, it++) {
                            const int st = it & 3;
                            mbar_wait(empty + 8 * st, ((it >> 2) & 1) ^ 1);
                            mbar_expect(full + 8 * st, G_STAGE);
                            const uint32_t a = sb + st * G_STAGE;
                            tma2d(a, &mx, kb * 64, b * 128, full + 8 * st);
                            tma3d(a + 16384, &mq, 0, kb * 64, i * 4, full + 8 * st);
                            tma3d(a + 32768, &mq, 0, kb * 64, i * 4 + 2, full + 8 * st);
                        }
                        wait_ctr(g_ctr + C_CHAIN + b, 96);
                        asm volatile("fence.proxy.async;" ::: "memory");
                        for (int st = 0; st < 4; st++, it++) {
                            mbar_wait(empty + 8 * st, ((it >> 2) & 1) ^ 1);
                            mbar_expect(full + 8 * st, 4 * 10240);
                            for (int sg = 0; sg < 4; sg++) {
                                const int sh = (b * 4 + sg) * NH + i * 2 + (st >> 1);
                                bulk_load(sb + st * G_STAGE + sg * 10240, ((st & 1) ? g_vx : g_kx) + (size_t)sh * 4096, 8192, full + 8 * st);
                                bulk_load(sb + st * G_STAGE + sg * 10240 + 8192, ((st & 1) ? g_vm : g_km) + (size_t)sh * 1024, 2048, full + 8 * st);
                            }
                        }
                    } else if (type == IT_O) {
                        const bool wide = b < O_WIDE;
                        wait_ctr(g_ctr + C_QA_DONE + b, 128);
                        asm volatile("fence.proxy.async;" ::: "memory");
                        for (int kb = 0; kb < 64; kb++, it++) {
                            const int st = it & 3;
                            mbar_wait(empty + 8 * st, ((it >> 2) & 1) ^ 1);
                            mbar_expect(full + 8 * st, wide ? G_STAGE : 32768);
                            const uint32_t a = sb + st * G_STAGE;
                            bulk_load(a, g_ox + (size_t)(b * 64 + kb) * 8192, 16384, full + 8 * st);
                            tma3d(a + 16384, &mo, 0, kb * 64, wide ? i * 4 : i * 2, full + 8 * st);
                            if (wide) tma3d(a + 32768, &mo, 0, kb * 64, i * 4 + 2, full + 8 * st);
                        }
                    } else if (type == IT_S4) {
                        for (int st = 0; st < 4; st++) mbar_wait(empty + 8 * st, ((it >> 2) & 1) ^ 1);
                        for (int st = 0; st < 4; st++) mbar_arrive(full + 8 * st);
                        it += 4;
                        mbar_wait_long(empty + 24, ((it >> 2) & 1) ^ 1);
                    }
                }
                __syncwarp();
                if (item >> 16 == IT_END) break;
            }
            asm volatile("griddepcontrol.wait;" ::: "memory");
        }
    } else {
        reg_inc<232>();
        const int wgi = wg - 1, wi = (tid >> 5) & 3;
        int it = 0, ns4 = 0;
        for (int n = 0;; n++) {
            mbar_wait_long(ifull + 8 * (n & 1), (n >> 1) & 1);
            int item; asm volatile("ld.shared.u32 %0, [%1];" : "=r"(item) : "r"(islot + 4 * (n & 1)) : "memory");
            __syncwarp();
            if (lane == 0) mbar_arrive(iempty + 8 * (n & 1));
            const int type = item >> 16, b = (item >> 8) & 255, i = item & 255;
            WLOG(0);
            if (type == IT_QA) {
                float acc[128];
                mainloop<256, 16, false>(acc, sb, wgi, full, empty, it, lane == 0);
                uint32_t q0[32], q1[32];
#pragma unroll
                for (int j = 0; j < 32; j++) { q0[j] = pack_bf16(acc[2 * j], acc[2 * j + 1]); q1[j] = pack_bf16(acc[64 + 2 * j], acc[65 + 2 * j]); }
                const uint32_t par = (it >> 2) & 1, so = (wgi * 2 + (wi >> 1)) * 10240;
                uint32_t* dst = (uint32_t*)g_ox + (size_t)(b * 64 + i * 4) * 4096 + (wgi * 8 + wi * 2) * 256 + lane;
                mbar_wait_long(full, par);
                attn_head(q0, sb + so, sb + G_STAGE + so, full + 8, par, empty, wi, lane, dst);
                __syncwarp();
                if (lane == 0) mbar_arrive(empty + 8);
                mbar_wait(full + 16, par);
                attn_head(q1, sb + 2 * G_STAGE + so, sb + 3 * G_STAGE + so, full + 24, par, empty + 16, wi, lane, dst + 2 * 4096);
                __syncwarp();
                if (lane == 0) { mbar_arrive(empty + 24); __threadfence(); atomicAdd(g_ctr + C_QA_DONE + b, 1); }
                it += 4;
            } else if (type == IT_O) {
                mbar_wait_long(full, (it >> 2) & 1);
                if (b < O_WIDE) o_item<256>(sb, wgi, wi, lane, full, empty, it, &mout, b * 128, i * 256);
                else o_item<128>(sb, wgi, wi, lane, full, empty, it, &mout, b * 128, i * 128);
            } else if (type == IT_S4) {
                mbar_wait(full, (it >> 2) & 1);
                s4_item(sb, wgi * 4 + wi, lane, i, P, ubar, ns4++ & 1, &mu, &my);
                if (lane == 0) { mbar_arrive(empty); mbar_arrive(empty + 8); mbar_arrive(empty + 16); }
                it += 4;
            } else break;
            WLOG(1);
        }
        if (lane == 0) asm volatile("cp.async.bulk.wait_group 0;" ::: "memory");
    }
}

typedef CUresult (*EncodeFn)(CUtensorMap*, CUtensorMapDataType, cuuint32_t, void*, const cuuint64_t*, const cuuint64_t*, const cuuint32_t*,
                             const cuuint32_t*, CUtensorMapInterleave, CUtensorMapSwizzle, CUtensorMapL2promotion, CUtensorMapFloatOOBfill);
static EncodeFn get_encode() {
    void* fn = nullptr; cudaDriverEntryPointQueryResult st;
    cudaGetDriverEntryPoint("cuTensorMapEncodeTiled", &fn, cudaEnableDefault, &st);
    return (EncodeFn)fn;
}
static void map_act(EncodeFn enc, CUtensorMap* m, const void* p, int rows, int cols, int boxr) {
    cuuint64_t dim[2] = {(cuuint64_t)cols, (cuuint64_t)rows}, str[1] = {(cuuint64_t)cols * 2};
    cuuint32_t box[2] = {64, (cuuint32_t)boxr}, es[2] = {1, 1};
    enc(m, CU_TENSOR_MAP_DATA_TYPE_BFLOAT16, 2, (void*)p, dim, str, box, es, CU_TENSOR_MAP_INTERLEAVE_NONE, CU_TENSOR_MAP_SWIZZLE_128B,
        CU_TENSOR_MAP_L2_PROMOTION_L2_128B, CU_TENSOR_MAP_FLOAT_OOB_FILL_NONE);
}
static void map_w(EncodeFn enc, CUtensorMap* m, const void* p, int k, int n) {
    cuuint64_t dim[3] = {64, (cuuint64_t)k, (cuuint64_t)n / 64}, str[2] = {(cuuint64_t)n * 2, 128};
    cuuint32_t box[3] = {64, 64, 2}, es[3] = {1, 1, 1};
    enc(m, CU_TENSOR_MAP_DATA_TYPE_BFLOAT16, 3, (void*)p, dim, str, box, es, CU_TENSOR_MAP_INTERLEAVE_NONE, CU_TENSOR_MAP_SWIZZLE_128B,
        CU_TENSOR_MAP_L2_PROMOTION_L2_256B, CU_TENSOR_MAP_FLOAT_OOB_FILL_NONE);
}

static void map_box(EncodeFn enc, CUtensorMap* m, const void* p, int rows, int ld, int boxc, int boxr, CUtensorMapSwizzle sw) {
    cuuint64_t dim[2] = {(cuuint64_t)ld, (cuuint64_t)rows}, str[1] = {(cuuint64_t)ld * 2};
    cuuint32_t box[2] = {(cuuint32_t)boxc, (cuuint32_t)boxr}, es[2] = {1, 1};
    enc(m, CU_TENSOR_MAP_DATA_TYPE_BFLOAT16, 2, (void*)p, dim, str, box, es, CU_TENSOR_MAP_INTERLEAVE_NONE, sw,
        CU_TENSOR_MAP_L2_PROMOTION_NONE, CU_TENSOR_MAP_FLOAT_OOB_FILL_NONE);
}

extern "C" void kernel_launch(void* const* d_in, const int* in_sizes, int n_in, void* d_out, int out_size) {
    const bf16* x = (const bf16*)d_in[0];
    const bf16* mem0 = (const bf16*)d_in[1];
    const bf16 *Wq = (const bf16*)d_in[2], *Wk = (const bf16*)d_in[3], *Wv = (const bf16*)d_in[4], *Wo = (const bf16*)d_in[5];
    static EncodeFn enc = nullptr;
    static int nsm = 0;
    if (!enc) {
        enc = get_encode();
        cudaDeviceGetAttribute(&nsm, cudaDevAttrMultiProcessorCount, 0);
        cudaFuncSetAttribute(chain_kernel, cudaFuncAttributeMaxDynamicSharedMemorySize, CH_SMEM);
        cudaFuncSetAttribute(kv_kernel, cudaFuncAttributeMaxDynamicSharedMemorySize, G_SMEM);
        cudaFuncSetAttribute(worker_kernel, cudaFuncAttributeMaxDynamicSharedMemorySize, G_SMEM);
    }
    CUtensorMap mx, mq, mk, mv, mo, mout, mu, my;
    map_act(enc, &mx, x, S_LEN, DM, 128);
    map_w(enc, &mq, Wq, DM, HD); map_w(enc, &mk, Wk, DM, HD); map_w(enc, &mv, Wv, DM, HD); map_w(enc, &mo, Wo, HD, DM);
    map_box(enc, &mout, d_out, S_LEN, 2 * DM, 64, 16, CU_TENSOR_MAP_SWIZZLE_128B);
    map_box(enc, &mu, d_in[7], S_LEN, DM, 8, 256, CU_TENSOR_MAP_SWIZZLE_NONE);
    map_box(enc, &my, d_out, S_LEN, 2 * DM, 8, 256, CU_TENSOR_MAP_SWIZZLE_NONE);
    S4Params P = {(const bf16*)d_in[8], (const bf16*)d_in[9], (const bf16*)d_in[10], (const bf16*)d_in[11],
                  (const bf16*)d_in[12], (const bf16*)d_in[13], (const bf16*)d_in[14], (const bf16*)d_in[15]};
    int aware = 1, pdl = 1;
    cudaLaunchAttribute at[1];
    at[0].id = cudaLaunchAttributeProgrammaticStreamSerialization;
    at[0].val.programmaticStreamSerializationAllowed = 1;
    cudaLaunchConfig_t cfg = {};
    cfg.stream = cudaStreamPerThread;
    cfg.gridDim = dim3(nsm); cfg.blockDim = dim3(384); cfg.dynamicSmemBytes = G_SMEM;
    cudaLaunchKernelEx(&cfg, kv_kernel, mx, mk, mv, mem0);
    cfg.attrs = at; cfg.numAttrs = pdl;
    cfg.gridDim = dim3(96); cfg.blockDim = dim3(256); cfg.dynamicSmemBytes = CH_SMEM;
    cudaLaunchKernelEx(&cfg, chain_kernel, Wq, Wk, Wv, Wo, aware);
    cfg.gridDim = dim3(nsm); cfg.blockDim = dim3(384); cfg.dynamicSmemBytes = G_SMEM;
    cudaLaunchKernelEx(&cfg, worker_kernel, mx, mq, mo, mout, mu, my, P);
}
```

```cpp
#include <cuda.h>
#include <cuda_runtime.h>
#include <cuda_bf16.h>
#include <stdint.h>
#include <stdio.h>
#include <string.h>

typedef __nv_bfloat16 bf16;

constexpr int S_LEN = 2048, DM = 1024, NH = 32, DH = 128, HD = 4096, NSEG = 64;
constexpr uint32_t SENT = 0xFFFFFFFFu;
constexpr int SPIN_LIMIT = 1 << 18;

__device__ __align__(1024) bf16 g_kx[S_LEN * HD];
__device__ __align__(1024) bf16 g_vx[S_LEN * HD];
__device__ __align__(1024) bf16 g_ox[S_LEN * HD];
__device__ __align__(1024) bf16 g_km[NSEG * NH * 8 * DH];
__device__ __align__(1024) bf16 g_vm[NSEG * NH * 8 * DH];
__device__ __align__(1024) char g_ring[2 << 20];
__device__ int g_side[256];
constexpr int C_QA_NEXT = 0, C_O_NEXT = 16, C_CHAIN = 32, C_QA_DONE = 64, C_S4_NEXT = 96, N_CTR = 128;
__device__ int g_ctr[N_CTR];
#define S4_FIRST 20

__device__ __forceinline__ uint32_t smem_u32(const void* p) { return (uint32_t)__cvta_generic_to_shared(p); }
__device__ __forceinline__ uint32_t clk() { uint32_t c; asm volatile("mov.u32 %0, %%clock;" : "=r"(c)::"memory"); return c; }
__device__ __forceinline__ uint32_t pack_bf16(float lo, float hi) {
    uint32_t r; asm("cvt.rn.bf16x2.f32 %0, %1, %2;" : "=r"(r) : "f"(hi), "f"(lo)); return r;
}
__device__ __forceinline__ uint32_t movm(uint32_t a) {
    uint32_t d; asm volatile("movmatrix.sync.aligned.m8n8.trans.b16 %0, %1;" : "=r"(d) : "r"(a)); return d;
}
__device__ __forceinline__ void mma16(float (&d)[4], const uint32_t (&a)[4], uint32_t b0, uint32_t b1) {
    asm volatile("mma.sync.aligned.m16n8k16.row.col.f32.bf16.bf16.f32 {%0,%1,%2,%3}, {%4,%5,%6,%7}, {%8,%9}, {%0,%1,%2,%3};"
        : "+f"(d[0]), "+f"(d[1]), "+f"(d[2]), "+f"(d[3]) : "r"(a[0]), "r"(a[1]), "r"(a[2]), "r"(a[3]), "r"(b0), "r"(b1));
}
__device__ __forceinline__ void mma16z(float (&d)[4], const uint32_t (&a)[4], uint32_t b0, uint32_t b1) {
    asm volatile("mma.sync.aligned.m16n8k16.row.col.f32.bf16.bf16.f32 {%0,%1,%2,%3}, {%4,%5,%6,%7}, {%8,%9}, {%10,%10,%10,%10};"
        : "=f"(d[0]), "=f"(d[1]), "=f"(d[2]), "=f"(d[3]) : "r"(a[0]), "r"(a[1]), "r"(a[2]), "r"(a[3]), "r"(b0), "r"(b1), "f"(0.f));
}
__device__ __forceinline__ void mma8z(float (&d)[4], uint32_t a0, uint32_t a1, uint32_t b0) {
    asm volatile("mma.sync.aligned.m16n8k8.row.col.f32.bf16.bf16.f32 {%0,%1,%2,%3}, {%4,%5}, {%6}, {%7,%7,%7,%7};"
        : "=f"(d[0]), "=f"(d[1]), "=f"(d[2]), "=f"(d[3]) : "r"(a0), "r"(a1), "r"(b0), "f"(0.f));
}
__device__ __forceinline__ void ldsm4t(uint32_t (&r)[4], uint32_t addr) {
    asm volatile("ldmatrix.sync.aligned.m8n8.x4.trans.shared.b16 {%0,%1,%2,%3}, [%4];"
        : "=r"(r[0]), "=r"(r[1]), "=r"(r[2]), "=r"(r[3]) : "r"(addr) : "memory");
}
__device__ __forceinline__ void ldsm4(uint32_t (&r)[4], uint32_t addr) {
    asm volatile("ldmatrix.sync.aligned.m8n8.x4.shared.b16 {%0,%1,%2,%3}, [%4];"
        : "=r"(r[0]), "=r"(r[1]), "=r"(r[2]), "=r"(r[3]) : "r"(addr) : "memory");
}
__device__ __forceinline__ float lds32(uint32_t a) {
    float v; asm volatile("ld.shared.f32 %0, [%1];" : "=f"(v) : "r"(a) : "memory"); return v;
}
__device__ __forceinline__ void st_async1(uint32_t dst, float v, uint32_t bar) {
    asm volatile("st.async.shared::cluster.mbarrier::complete_tx::bytes.f32 [%0], %1, [%2];" ::"r"(dst), "f"(v), "r"(bar) : "memory");
}
__device__ __forceinline__ void cp16(uint32_t dst, const void* src) {
    asm volatile("cp.async.cg.shared.global [%0], [%1], 16;" ::"r"(dst), "l"(src) : "memory");
}
__device__ __forceinline__ void sts128(uint32_t a, const float (&v)[4]) {
    asm volatile("st.shared.v4.f32 [%0], {%1,%2,%3,%4};" ::"r"(a), "f"(v[0]), "f"(v[1]), "f"(v[2]), "f"(v[3]) : "memory");
}
__device__ __forceinline__ float4 lds128(uint32_t a) {
    float4 v; asm volatile("ld.shared.v4.f32 {%0,%1,%2,%3}, [%4];" : "=f"(v.x), "=f"(v.y), "=f"(v.z), "=f"(v.w) : "r"(a) : "memory"); return v;
}
__device__ __forceinline__ void sts64(uint32_t a, float x, float y) {
    asm volatile("st.shared.v2.f32 [%0], {%1,%2};" ::"r"(a), "f"(x), "f"(y) : "memory");
}
__device__ __forceinline__ float2 lds64(uint32_t a) {
    float2 v; asm volatile("ld.shared.v2.f32 {%0,%1}, [%2];" : "=f"(v.x), "=f"(v.y) : "r"(a) : "memory"); return v;
}
__device__ __forceinline__ void bar_sync(int id, int n) { asm volatile("bar.sync %0, %1;" ::"r"(id), "r"(n) : "memory"); }
__device__ __forceinline__ void bar_arrive(int id, int n) { asm volatile("bar.arrive %0, %1;" ::"r"(id), "r"(n) : "memory"); }
__device__ __forceinline__ uint32_t mapa(uint32_t a, uint32_t r) {
    uint32_t o; asm("mapa.shared::cluster.u32 %0, %1, %2;" : "=r"(o) : "r"(a), "r"(r)); return o;
}
__device__ __forceinline__ void st_async4(uint32_t dst, float4 v, uint32_t bar) {
    asm volatile("st.async.shared::cluster.mbarrier::complete_tx::bytes.v4.f32 [%0], {%1,%2,%3,%4}, [%5];"
        ::"r"(dst), "f"(v.x), "f"(v.y), "f"(v.z), "f"(v.w), "r"(bar) : "memory");
}
__device__ __forceinline__ void mbar_init(uint32_t bar, int n) { asm volatile("mbarrier.init.shared.b64 [%0], %1;" ::"r"(bar), "r"(n) : "memory"); }
__device__ __forceinline__ void mbar_expect(uint32_t bar, int bytes) {
    asm volatile("mbarrier.arrive.expect_tx.shared.b64 _, [%0], %1;" ::"r"(bar), "r"(bytes) : "memory");
}
__device__ __forceinline__ void bulk_load(uint32_t dst, const void* src, int bytes, uint32_t bar) {
    asm volatile("cp.async.bulk.shared::cluster.global.mbarrier::complete_tx::bytes [%0], [%1], %2, [%3];"
        ::"r"(dst), "l"(src), "r"(bytes), "r"(bar) : "memory");
}
__device__ __forceinline__ bool mbar_try(uint32_t bar, uint32_t par) {
    uint32_t ok;
    asm volatile("{.reg .pred p; mbarrier.try_wait.parity.shared::cta.b64 p, [%1], %2; selp.u32 %0, 1, 0, p;}"
        : "=r"(ok) : "r"(bar), "r"(par) : "memory");
    return ok;
}
__device__ __forceinline__ void mbar_wait(uint32_t bar, uint32_t par) {
    if (!mbar_try(bar, par))
        for (int it = 0; it < SPIN_LIMIT && !mbar_try(bar, par); it++) {}
}
__device__ __forceinline__ void mbar_wait_long(uint32_t bar, uint32_t par) {
    for (int it = 0; it < (1 << 24) && !mbar_try(bar, par); it++) {}
}
__device__ __forceinline__ float4 add4(float4 a, float4 b) { return make_float4(a.x + b.x, a.y + b.y, a.z + b.z, a.w + b.w); }
__device__ __forceinline__ float ex2(float x) { float y; asm("ex2.approx.ftz.f32 %0, %1;" : "=f"(y) : "f"(x)); return y; }

__device__ __forceinline__ void wgmma256(float (&d)[128], uint64_t da, uint64_t db, int acc) {
    asm volatile("{.reg .pred p; setp.ne.b32 p, %130, 0;\n"
        "wgmma.mma_async.sync.aligned.m64n256k16.f32.bf16.bf16 {"
        "%0,%1,%2,%3,%4,%5,%6,%7,%8,%9,%10,%11,%12,%13,%14,%15,"
        "%16,%17,%18,%19,%20,%21,%22,%23,%24,%25,%26,%27,%28,%29,%30,%31,"
        "%32,%33,%34,%35,%36,%37,%38,%39,%40,%41,%42,%43,%44,%45,%46,%47,"
        "%48,%49,%50,%51,%52,%53,%54,%55,%56,%57,%58,%59,%60,%61,%62,%63,"
        "%64,%65,%66,%67,%68,%69,%70,%71,%72,%73,%74,%75,%76,%77,%78,%79,"
        "%80,%81,%82,%83,%84,%85,%86,%87,%88,%89,%90,%91,%92,%93,%94,%95,"
        "%96,%97,%98,%99,%100,%101,%102,%103,%104,%105,%106,%107,%108,%109,%110,%111,"
        "%112,%113,%114,%115,%116,%117,%118,%119,%120,%121,%122,%123,%124,%125,%126,%127"
        "}, %128, %129, p, 1, 1, 0, 1;}"
        : "+f"(d[0]), "+f"(d[1]), "+f"(d[2]), "+f"(d[3]), "+f"(d[4]), "+f"(d[5]), "+f"(d[6]), "+f"(d[7]), "+f"(d[8]), "+f"(d[9]), "+f"(d[10]), "+f"(d[11]), "+f"(d[12]), "+f"(d[13]), "+f"(d[14]), "+f"(d[15]), "+f"(d[16]), "+f"(d[17]), "+f"(d[18]), "+f"(d[19]), "+f"(d[20]), "+f"(d[21]), "+f"(d[22]), "+f"(d[23]), "+f"(d[24]), "+f"(d[25]), "+f"(d[26]), "+f"(d[27]), "+f"(d[28]), "+f"(d[29]), "+f"(d[30]), "+f"(d[31]), "+f"(d[32]), "+f"(d[33]), "+f"(d[34]), "+f"(d[35]), "+f"(d[36]), "+f"(d[37]), "+f"(d[38]), "+f"(d[39]), "+f"(d[40]), "+f"(d[41]), "+f"(d[42]), "+f"(d[43]), "+f"(d[44]), "+f"(d[45]), "+f"(d[46]), "+f"(d[47]), "+f"(d[48]), "+f"(d[49]), "+f"(d[50]), "+f"(d[51]), "+f"(d[52]), "+f"(d[53]), "+f"(d[54]), "+f"(d[55]), "+f"(d[56]), "+f"(d[57]), "+f"(d[58]), "+f"(d[59]), "+f"(d[60]), "+f"(d[61]), "+f"(d[62]), "+f"(d[63]), "+f"(d[64]), "+f"(d[65]), "+f"(d[66]), "+f"(d[67]), "+f"(d[68]), "+f"(d[69]), "+f"(d[70]), "+f"(d[71]), "+f"(d[72]), "+f"(d[73]), "+f"(d[74]), "+f"(d[75]), "+f"(d[76]), "+f"(d[77]), "+f"(d[78]), "+f"(d[79]), "+f"(d[80]), "+f"(d[81]), "+f"(d[82]), "+f"(d[83]), "+f"(d[84]), "+f"(d[85]), "+f"(d[86]), "+f"(d[87]), "+f"(d[88]), "+f"(d[89]), "+f"(d[90]), "+f"(d[91]), "+f"(d[92]), "+f"(d[93]), "+f"(d[94]), "+f"(d[95]), "+f"(d[96]), "+f"(d[97]), "+f"(d[98]), "+f"(d[99]), "+f"(d[100]), "+f"(d[101]), "+f"(d[102]), "+f"(d[103]), "+f"(d[104]), "+f"(d[105]), "+f"(d[106]), "+f"(d[107]), "+f"(d[108]), "+f"(d[109]), "+f"(d[110]), "+f"(d[111]), "+f"(d[112]), "+f"(d[113]), "+f"(d[114]), "+f"(d[115]), "+f"(d[116]), "+f"(d[117]), "+f"(d[118]), "+f"(d[119]), "+f"(d[120]), "+f"(d[121]), "+f"(d[122]), "+f"(d[123]), "+f"(d[124]), "+f"(d[125]), "+f"(d[126]), "+f"(d[127])
        : "l"(da), "l"(db), "r"(acc));
}
__device__ __forceinline__ void wgmma128(float (&d)[64], uint64_t da, uint64_t db, int acc) {
    asm volatile("{.reg .pred p; setp.ne.b32 p, %66, 0;\n"
        "wgmma.mma_async.sync.aligned.m64n128k16.f32.bf16.bf16 {"
        "%0,%1,%2,%3,%4,%5,%6,%7,%8,%9,%10,%11,%12,%13,%14,%15,"
        "%16,%17,%18,%19,%20,%21,%22,%23,%24,%25,%26,%27,%28,%29,%30,%31,"
        "%32,%33,%34,%35,%36,%37,%38,%39,%40,%41,%42,%43,%44,%45,%46,%47,"
        "%48,%49,%50,%51,%52,%53,%54,%55,%56,%57,%58,%59,%60,%61,%62,%63"
        "}, %64, %65, p, 1, 1, 0, 1;}"
        : "+f"(d[0]), "+f"(d[1]), "+f"(d[2]), "+f"(d[3]), "+f"(d[4]), "+f"(d[5]), "+f"(d[6]), "+f"(d[7]), "+f"(d[8]), "+f"(d[9]), "+f"(d[10]), "+f"(d[11]), "+f"(d[12]), "+f"(d[13]), "+f"(d[14]), "+f"(d[15]), "+f"(d[16]), "+f"(d[17]), "+f"(d[18]), "+f"(d[19]), "+f"(d[20]), "+f"(d[21]), "+f"(d[22]), "+f"(d[23]), "+f"(d[24]), "+f"(d[25]), "+f"(d[26]), "+f"(d[27]), "+f"(d[28]), "+f"(d[29]), "+f"(d[30]), "+f"(d[31]), "+f"(d[32]), "+f"(d[33]), "+f"(d[34]), "+f"(d[35]), "+f"(d[36]), "+f"(d[37]), "+f"(d[38]), "+f"(d[39]), "+f"(d[40]), "+f"(d[41]), "+f"(d[42]), "+f"(d[43]), "+f"(d[44]), "+f"(d[45]), "+f"(d[46]), "+f"(d[47]), "+f"(d[48]), "+f"(d[49]), "+f"(d[50]), "+f"(d[51]), "+f"(d[52]), "+f"(d[53]), "+f"(d[54]), "+f"(d[55]), "+f"(d[56]), "+f"(d[57]), "+f"(d[58]), "+f"(d[59]), "+f"(d[60]), "+f"(d[61]), "+f"(d[62]), "+f"(d[63])
        : "l"(da), "l"(db), "r"(acc));
}
__device__ __forceinline__ void wg_fence() { asm volatile("wgmma.fence.sync.aligned;" ::: "memory"); }
__device__ __forceinline__ void wg_commit() { asm volatile("wgmma.commit_group.sync.aligned;" ::: "memory"); }
template <int N> __device__ __forceinline__ void wg_wait() { asm volatile("wgmma.wait_group.sync.aligned %0;" ::"n"(N) : "memory"); }
__device__ __forceinline__ uint64_t mkdesc(uint32_t addr, uint32_t lbo, uint32_t sbo, uint32_t sw) {
    return (uint64_t)((addr & 0x3FFFF) >> 4) | ((uint64_t)(lbo >> 4) << 16) | ((uint64_t)(sbo >> 4) << 32) | ((uint64_t)sw << 62);
}
__device__ __forceinline__ void tma2d(uint32_t dst, const CUtensorMap* m, int c0, int c1, uint32_t bar) {
    asm volatile("cp.async.bulk.tensor.2d.shared::cluster.global.mbarrier::complete_tx::bytes [%0], [%1, {%2, %3}], [%4];"
        ::"r"(dst), "l"(m), "r"(c0), "r"(c1), "r"(bar) : "memory");
}
__device__ __forceinline__ void tma3d(uint32_t dst, const CUtensorMap* m, int c0, int c1, int c2, uint32_t bar) {
    asm volatile("cp.async.bulk.tensor.3d.shared::cluster.global.mbarrier::complete_tx::bytes [%0], [%1, {%2, %3, %4}], [%5];"
        ::"r"(dst), "l"(m), "r"(c0), "r"(c1), "r"(c2), "r"(bar) : "memory");
}
__device__ __forceinline__ void tma3d_mc(uint32_t dst, const CUtensorMap* m, int c0, int c1, int c2, uint32_t bar, uint16_t mask) {
    asm volatile("cp.async.bulk.tensor.3d.shared::cluster.global.mbarrier::complete_tx::bytes.multicast::cluster [%0], [%1, {%2, %3, %4}], [%5], %6;"
        ::"r"(dst), "l"(m), "r"(c0), "r"(c1), "r"(c2), "r"(bar), "h"(mask) : "memory");
}
__device__ __forceinline__ void mbar_arrive(uint32_t bar) { asm volatile("mbarrier.arrive.shared.b64 _, [%0];" ::"r"(bar) : "memory"); }
__device__ __forceinline__ void mbar_arrive_remote(uint32_t bar) {
    asm volatile("mbarrier.arrive.shared::cluster.b64 _, [%0];" ::"r"(bar) : "memory");
}
template <int R> __device__ __forceinline__ void reg_inc() { asm volatile("setmaxnreg.inc.sync.aligned.u32 %0;" ::"n"(R)); }
template <int R> __device__ __forceinline__ void reg_dec() { asm volatile("setmaxnreg.dec.sync.aligned.u32 %0;" ::"n"(R)); }

constexpr int CH_NRES = 50;
constexpr int CH_WREG = CH_NRES * 512;
constexpr int CH_PART = 8 * CH_WREG;
constexpr int CH_SX = CH_PART + 16384;
constexpr int CH_MX = CH_SX + 3 * 1280;
constexpr int CH_XS = CH_MX + 3 * 512;
constexpr int CH_BAR = CH_XS + 5632;
constexpr int CH_SMEM = CH_BAR + 192;
constexpr int CH_THREADS = 384;

__device__ __forceinline__ char* ring_base() { return (char*)(((uintptr_t)g_ring + (1 << 20) - 1) & ~(uintptr_t)((1 << 20) - 1)); }
__device__ __forceinline__ uint32_t ring_off(int chunk, int side) {
    uint32_t o = ((chunk & 1) << 13) | ((chunk >> 1) << 16);
    uint32_t par = ((o >> 13) ^ (o >> 16) ^ (o >> 17) ^ (o >> 19) ^ side) & 1;
    return o | (par << 12);
}
__device__ __forceinline__ uint2 ld_poll(const char* p) {
    unsigned long long v; asm volatile("ld.relaxed.gpu.global.b64 %0, [%1];" : "=l"(v) : "l"(p) : "memory");
    return make_uint2((uint32_t)v, (uint32_t)(v >> 32));
}
__device__ __forceinline__ void st_pub(char* p, uint32_t x, uint32_t y) {
    unsigned long long v = ((unsigned long long)y << 32) | x;
    asm volatile("st.relaxed.gpu.global.b64 [%0], %1;" ::"l"(p), "l"(v) : "memory");
}
template <int N>
__device__ __forceinline__ void poll_issue(uint2 (&b)[N], const char* p, bool lastvalid) {
#pragma unroll
    for (int i = 0; i < N; i++) {
        if (i < N - 1 || lastvalid) b[i] = ld_poll(p + i * 256);
        else b[i] = make_uint2(0, 0);
    }
}
template <int N>
__device__ __forceinline__ int poll_check(uint2 (&b)[N], const char* p) {
    int it = 0;
    uint32_t mx = b[0].x;
#pragma unroll
    for (int i = 1; i < N; i++) mx = max(mx, b[i].x);
    if (__any_sync(0xffffffffu, mx == SENT)) {
        while (it++ < SPIN_LIMIT) {
#pragma unroll
            for (int i = 0; i < N; i++)
                if (b[i].x == SENT) b[i] = ld_poll(p + i * 256);
            mx = b[0].x;
#pragma unroll
            for (int i = 1; i < N; i++) mx = max(mx, b[i].x);
            if (!__any_sync(0xffffffffu, mx == SENT)) break;
        }
    }
    return it;
}
template <int N>
__device__ __forceinline__ uint32_t delay(uint32_t a) {
    uint32_t z = 0;
#pragma unroll
    for (int i = 0; i < N; i++) asm volatile("ld.volatile.shared.u32 %0, [%1];" : "=r"(z) : "r"(a + z) : "memory");
    return z;
}

#define TIM(i)
#define GT(i, z)
#define POLLCHK(N, arr, p, i) poll_check<N>(arr, p)

template <bool B> struct BoolC { static constexpr bool value = B; };
#define DLM 2
#define DLO 2
#define NFL 4
#define CPF 2
#define STAG 0
#define FPACE 1
constexpr int OB = 0;
#define FLAGS 0
template <int PACE>
__device__ __forceinline__ void preload(uint32_t (&sw)[12][4], uint32_t a, uint32_t zero) {
    uint32_t z = 0;
#pragma unroll
    for (int i = 0; i < 12; i++) {
        if (PACE && i % (PACE ? PACE : 1) == 0) z = delay<1>(zero + z);
        ldsm4t(sw[i], a + z + i * 512);
    }
}
__device__ __forceinline__ void stsm4(uint32_t addr, uint32_t a, uint32_t b, uint32_t c, uint32_t d) {
    asm volatile("stmatrix.sync.aligned.m8n8.x4.shared.b16 [%0], {%1,%2,%3,%4};" ::"r"(addr), "r"(a), "r"(b), "r"(c), "r"(d) : "memory");
}
__device__ __forceinline__ void stsm4t(uint32_t addr, uint32_t a, uint32_t b, uint32_t c, uint32_t d) {
    asm volatile("stmatrix.sync.aligned.m8n8.x4.trans.shared.b16 [%0], {%1,%2,%3,%4};" ::"r"(addr), "r"(a), "r"(b), "r"(c), "r"(d) : "memory");
}
__device__ __forceinline__ void st_part(uint32_t addr, const float (&x)[4], const float (&y)[4]) {
    stsm4(addr, pack_bf16(x[0], x[1]), pack_bf16(x[2], x[3]), pack_bf16(y[0], y[1]), pack_bf16(y[2], y[3]));
}
template <bool TR>
__device__ __forceinline__ void red_part(uint32_t& lo, uint32_t& hi, uint32_t addr, uint32_t eye) {
    uint32_t a[4][4];
#pragma unroll
    for (int j = 0; j < 4; j++) { if (TR) ldsm4t(a[j], addr + j * 512); else ldsm4(a[j], addr + j * 512); }
    float r0[4], r1[4];
    mma16z(r0, a[0], eye, eye); mma16z(r1, a[1], eye, eye);
    mma16(r0, a[2], eye, eye); mma16(r1, a[3], eye, eye);
    lo = pack_bf16(r0[0] + r1[0], r0[1] + r1[1]); hi = pack_bf16(r0[2] + r1[2], r0[3] + r1[3]);
}
__device__ __forceinline__ int o_chunk(int ks, int& pos) {
    const int cw = ks < 176 ? ks / 11 : 16 + (ks - 176) / 10;
    pos = ks - (cw < 16 ? 11 * cw : 176 + 10 * (cw - 16));
    return cw;
}

template <bool PV>
__device__ __forceinline__ void chain_loop(const uint32_t (&wa)[36][4], const uint32_t sb, const int w, const int lane, const int rank,
                                           const int h, const int side) {
    const int nq = rank == 0 ? 6 : 5, u0 = rank == 0 ? 0 : 1 + 5 * rank, v0 = rank == 0 ? -6 : 3 * rank - 6;
    const uint32_t l16 = sb + lane * 16;
    const uint32_t wl = l16 + w * CH_WREG;
    const uint32_t pw = sb + CH_PART + w * 256 + (lane >> 4) * 2048 + (lane & 15) * 16;
    const uint32_t pl = l16 + CH_PART + w * 2048;
    const uint32_t barS = sb + CH_BAR, barM = barS + 8, barX = barS + 16, zero = barS + 24;
    const uint32_t eye = ((lane >> 2) == 2 * (lane & 3)) ? 0x3F80u : ((lane >> 2) == 2 * (lane & 3) + 1) ? 0x3F800000u : 0u;
    char* const ring = ring_base() + lane * 8;
    const uint32_t m_rd = ring_off(24 + w, side), o_rd = ring_off(rank * 8 + w, side);
    uint32_t pub;
    if (PV) { int pos, cw = o_chunk(h * 8 + v0 + w, pos); pub = (ring_off(cw, 0) & ~4096u) + pos * 256; }
    else pub = (ring_off(24 + (h >> 2), 0) & ~4096u) + ((2 * h + w) & 7) * 256;
    const uint32_t xs = l16 + CH_XS + (PV ? nq * 512 + (w - nq) * 1024 : w * 512);
    char* const kvo = (char*)(PV ? g_vm + 128 * (v0 + w) : g_km + 64 * (u0 + w)) + h * 2048;
    const bool mown = !PV && w == rank && rank < 2;
    uint32_t sw[12][4];
#pragma unroll
    for (int i = 0; i < 12; i++) ldsm4t(sw[i], wl + i * 512);
    mbar_wait(barX, 0);

    auto step = [&](const int s, auto lastc) {
        constexpr bool last = decltype(lastc)::value;
        const uint32_t slot = (s & 3) << 14;
        uint2 b[8];
        TIM(0);
        poll_issue<8>(b, ring + (m_rd + slot + delay<FLAGS ? 0 : DLM>(zero) + (w >= 4 ? delay<STAG>(zero) : 0)), true);
        POLLCHK(8, b, ring + (m_rd + slot), 0);
        if (OB && !last) bar_arrive(8, 288);
        TIM(1);
        {
            float acc[6][4];
#pragma unroll
            for (int kk = 0; kk < 8; kk++) {
                const int j = (2 * kk) % 12;
                if (kk == 0) { mma16z(acc[5], sw[0], b[0].x, b[0].y); mma16z(acc[4], sw[1], b[0].x, b[0].y); }
                else { mma16(acc[5], sw[j], b[kk].x, b[kk].y); mma16(acc[4], sw[j + 1], b[kk].x, b[kk].y); }
#pragma unroll
                for (int i = 0; i < 4; i++) {
                    if (kk == 0) mma16z(acc[i], wa[i * 8], b[0].x, b[0].y);
                    else mma16(acc[i], wa[i * 8 + kk], b[kk].x, b[kk].y);
                    if (i < 2) ldsm4t(sw[j + i], wl + (12 + 2 * kk + i) * 512);
                }
            }
            st_part(pw + 4 * 2048, acc[4], acc[5]);
            st_part(pw, acc[0], acc[1]);
            st_part(pw + 2 * 2048, acc[2], acc[3]);
        }
        TIM(2);
        uint32_t kv0, kv1;
        if (!PV) {
            uint32_t xf[4];
            ldsm4(xf, xs);
            bar_sync(1, last ? 256 : 256 + OB);
            red_part<true>(kv1, kv0, pl, eye);
            if (!last) {
                float s0[4], s1[4], s2[4], s3[4], s4[4];
                mma8z(s0, kv1, 0, xf[0]); mma8z(s1, kv1, 0, xf[1]); mma8z(s2, kv1, 0, xf[2]); mma8z(s3, kv1, 0, xf[3]);
                mma8z(s4, kv1, 0, kv0);
                const float x0[4] = {s0[0], s0[1], s1[0], s1[1]}, x1[4] = {s2[0], s2[1], s3[0], s3[1]};
                sts128(pl, x0); sts128(pl + 512, x1);
                sts64(pl + 1024 - lane * 8, s4[0], s4[1]);
                bar_arrive(2, nq * 32 + 64 + OB);
            }
            TIM(4);
        } else {
            bar_sync(1, last ? 256 : 256 + OB);
        }
        {
            float va[4][4];
            const float z = __uint_as_float(delay<1>(zero));
#pragma unroll
            for (int i = 0; i < 4; i++) va[i][0] = va[i][1] = va[i][2] = va[i][3] = z;
#pragma unroll
            for (int kk = 0; kk < 8; kk++) {
                if (kk < 2) { mma16(va[kk & 1], wa[32 + 2 * kk], b[kk].x, b[kk].y); mma16(va[2 + (kk & 1)], wa[33 + 2 * kk], b[kk].x, b[kk].y); }
                else { mma16(va[kk & 1], sw[(2 * kk) % 12], b[kk].x, b[kk].y); mma16(va[2 + (kk & 1)], sw[(2 * kk + 1) % 12], b[kk].x, b[kk].y); }
            }
#pragma unroll
            for (int j = 0; j < 4; j++) { va[0][j] += va[1][j]; va[2][j] += va[3][j]; }
            st_part(pw + 6 * 2048, va[0], va[2]);
        }
        TIM(6);
        if (PV) {
            uint32_t vt0[4], vt1[4];
            ldsm4t(vt0, xs); ldsm4t(vt1, xs + 512);
            if (w >= 6 && !last) {
                const uint32_t sa = l16 + CH_PART + (w - 6) * 512, sc = sb + CH_PART + 1024 + (w - 6) * 128 + lane * 4;
                const uint32_t da = l16 + CH_SX + rank * 1280 + (w - 6) * 512, dc = sb + CH_SX + rank * 1280 + 1024 + (w - 6) * 128 + lane * 4;
                bar_sync(2, nq * 32 + 64 + OB);
                float4 v[6]; float c[6];
#pragma unroll
                for (int i = 0; i < 6; i++) v[i] = (i < 5 || rank == 0) ? lds128(sa + i * 2048) : make_float4(0, 0, 0, 0);
#pragma unroll
                for (int i = 0; i < 6; i++) c[i] = (i < 5 || rank == 0) ? lds32(sc + i * 2048) : 0.f;
                float4 sv = add4(add4(add4(v[0], v[1]), add4(v[2], v[3])), add4(v[4], v[5]));
                float cv = ((c[0] + c[1]) + (c[2] + c[3])) + (c[4] + c[5]);
#pragma unroll
                for (int d = 1; d < 4; d++) {
                    const int dr = rank + d - (rank + d > 2 ? 3 : 0);
                    st_async4(mapa(da, dr), sv, mapa(barS, dr)); st_async1(mapa(dc, dr), cv, mapa(barS, dr));
                }
                TIM(5);
            }
            bar_sync(3, last ? 256 : 320 + OB);
            red_part<false>(kv0, kv1, pl, eye);
            TIM(7);
            if (!last) {
                mbar_wait(barS, s & 1);
                TIM(8);
                const uint32_t sx = l16 + CH_SX;
                float4 a0 = lds128(sx), a1 = lds128(sx + 1280), a2 = lds128(sx + 2560);
                float4 b0 = lds128(sx + 512), b1 = lds128(sx + 512 + 1280), b2 = lds128(sx + 512 + 2560);
                float2 c0 = lds64(sx + 1024 - lane * 8), c1 = lds64(sx + 1024 + 1280 - lane * 8), c2 = lds64(sx + 1024 + 2560 - lane * 8);
                a0 = add4(add4(a0, a1), a2); b0 = add4(add4(b0, b1), b2);
                float sc[10] = {a0.x, a0.y, a0.z, a0.w, b0.x, b0.y, b0.z, b0.w, c0.x + c1.x + c2.x, c0.y + c1.y + c2.y};
                float mx = fmaxf(fmaxf(fmaxf(sc[0], sc[1]), fmaxf(sc[2], sc[3])), fmaxf(fmaxf(sc[4], sc[5]), fmaxf(sc[6], sc[7])));
                mx = fmaxf(mx, fmaxf(sc[8], sc[9]));
                mx = fmaxf(fmaxf(mx, __shfl_xor_sync(0xffffffffu, mx, 1)),
                           fmaxf(__shfl_xor_sync(0xffffffffu, mx, 2), __shfl_xor_sync(0xffffffffu, mx, 3)));
                const float cs = 0.08838834764831845f * 1.4426950408889634f;
                const float mb = -mx * cs;
#pragma unroll
                for (int j = 0; j < 10; j++) sc[j] = ex2(fmaf(sc[j], cs, mb));
                uint32_t pf[5];
#pragma unroll
                for (int j = 0; j < 5; j++) pf[j] = pack_bf16(sc[2 * j], sc[2 * j + 1]);
                float o0[4], o1[4], o2[4], o3[4], o4[4], o5[4];
                const uint32_t p0[4] = {pf[0], 0, pf[1], 0}, p1[4] = {pf[2], 0, pf[3], 0};
                mma16z(o0, p0, vt0[0], vt0[1]); mma16z(o1, p0, vt1[0], vt1[1]);
                mma16z(o2, p1, vt0[2], vt0[3]); mma16z(o3, p1, vt1[2], vt1[3]);
                mma8z(o4, pf[4], 0, kv0); mma8z(o5, pf[4], 0, kv1);
                float sum = (((sc[0] + sc[1]) + (sc[2] + sc[3])) + ((sc[4] + sc[5]) + (sc[6] + sc[7]))) + (sc[8] + sc[9]);
                sum = (sum + __shfl_xor_sync(0xffffffffu, sum, 1)) + (__shfl_xor_sync(0xffffffffu, sum, 2) + __shfl_xor_sync(0xffffffffu, sum, 3));
                const float inv = __fdividef(1.f, sum);
                const uint32_t ox = pack_bf16((o0[0] + o2[0] + o4[0]) * inv, (o0[1] + o2[1] + o4[1]) * inv);
                const uint32_t oy = pack_bf16((o1[0] + o3[0] + o5[0]) * inv, (o1[1] + o3[1] + o5[1]) * inv);
                st_pub(ring + (pub + slot), ox, oy); st_pub(ring + (pub + slot) + 4096, ox, oy);
                if (OB) bar_arrive(10, (9 - nq) * 32);
                preload<0>(sw, wl + 28 * 512, zero);
            }
            kv0 = movm(kv0); kv1 = movm(kv1);
        } else {
            *(uint32_t*)(kvo + (uint32_t)(s * (NH * 2048) + lane * 4)) = kv0;
            if (last) bar_arrive(3, 256);
            else {
                bar_sync(3, 320 + OB);
                preload<1>(sw, wl + 28 * 512, zero);
            }
        }
        uint2 c[11];
        if (!last) {
            bar_sync(4, 288 + OB);
            poll_issue<11>(c, ring + (o_rd + slot + delay<FLAGS ? 0 : DLO>(zero) + (w >= 4 ? delay<STAG>(zero) : 0)), rank < 2);
            TIM(9);
        }
        if (PV) { uint32_t* d = (uint32_t*)(kvo + (uint32_t)(s * (NH * 2048) + lane * 4)); d[0] = kv0; d[32] = kv1; }
        if (last) return;
        POLLCHK(11, c, ring + (o_rd + slot), 1);
        if (OB) bar_arrive(9, 288);
        TIM(10);
        {
            float acc[4][4];
#pragma unroll
            for (int f = 0; f < 22; f++) {
                const int kk = f >> 1, a = f & 3;
                if (f < 4) mma16z(acc[a], sw[f % 12], c[kk].x, c[kk].y);
                else mma16(acc[a], sw[f % 12], c[kk].x, c[kk].y);
                if (f + 12 < 22) ldsm4t(sw[f % 12], wl + (28 + f + 12) * 512);
            }
#pragma unroll
            for (int i = 0; i < 2; i++) {
#pragma unroll
                for (int j = 0; j < 4; j++) acc[i][j] += acc[i + 2][j];
                sts128(l16 + CH_PART + i * 4096 + w * 512, acc[i]);
            }
        }
        TIM(11);
        if (!PV && w < 2) {
            bar_sync(5, 288 + OB);
            float4 v[8];
#pragma unroll
            for (int i = 0; i < 8; i++) v[i] = lds128(l16 + CH_PART + w * 4096 + i * 512);
            float4 r = add4(add4(add4(v[0], v[1]), add4(v[2], v[3])), add4(add4(v[4], v[5]), add4(v[6], v[7])));
            if (!mown) st_async4(mapa(l16 + CH_MX + rank * 512, w), r, mapa(barM, w));
            bar_arrive(7, 256 + OB);
            if (mown) {
                TIM(12);
                mbar_wait(barM, s & 1);
                TIM(13);
                float4 x = lds128(l16 + CH_MX + (rank ^ 1) * 512), y = lds128(l16 + CH_MX + 2 * 512);
                r = add4(add4(x, r), y);
                const uint32_t mx = movm(pack_bf16(r.x, r.y)), my = movm(pack_bf16(r.z, r.w));
                const uint32_t ns = (slot + 0x4000) & 0xC000;
                st_pub(ring + (pub + ns), mx, my); st_pub(ring + (pub + ns) + 4096, mx, my);
                TIM(14);
            }
            preload<0>(sw, wl, zero);
        } else {
            bar_arrive(5, 288 + OB);
            bar_sync(7, 256 + OB);
            preload<2>(sw, wl, zero);
        }
        bar_sync(6, 320 + OB);
    };
#pragma unroll 1
    for (int s = 0; s < NSEG - 1; s++) step(s, BoolC<false>());
    step(NSEG - 1, BoolC<true>());
    bar_arrive(6, 288);
}

__device__ __forceinline__ uint32_t ld_flag(const char* p) {
    uint32_t a; asm volatile("ld.relaxed.gpu.global.u32 %0, [%1];" : "=r"(a) : "l"(p) : "memory"); return a;
}
template <int DLY>
__device__ __forceinline__ void wait_flags(const char* p, uint32_t v, uint32_t zero, int bar, int cnt) {
    uint32_t f0 = 0, f1 = 0, f2 = 0, f3 = 0, f4 = 0, f5 = 0;
#pragma unroll 1
    for (int it = 0; it < SPIN_LIMIT; it++) {
        if (f0 == v) break;
        f0 = ld_flag(p + delay<FPACE>(zero));
        if (f1 == v) break;
        f1 = ld_flag(p + delay<FPACE>(zero));
        if (f2 == v) break;
        f2 = ld_flag(p + delay<FPACE>(zero));
        if (NFL > 3) { if (f3 == v) break; f3 = ld_flag(p + delay<FPACE>(zero)); }
        if (NFL > 4) { if (f4 == v) break; f4 = ld_flag(p + delay<FPACE>(zero)); }
    }
    __syncwarp();
    bar_arrive(bar, cnt + delay<DLY>(zero));
    asm volatile("st.shared.v4.u32 [%0], {%1,%2,%3,%4};" ::"r"(zero + 8), "r"(f0 ^ f4), "r"(f1 ^ f5), "r"(f2), "r"(f3) : "memory");
}

__device__ __forceinline__ void chain_flags(const uint32_t sb, const int lane, const int rank, const int h, const int side) {
    const uint32_t zero = sb + CH_BAR + 24;
    char* const ring = ring_base();
    char* const po = ring + (ring_off(24 + h / 11, lane & 1) + 2048);
    char* const pm = ring + (ring_off(27, lane & 1) + 2048);
    const uint32_t fo = ring_off(24 + rank, side) + 2048, fm = ring_off(27, side) + 2048;
#pragma unroll 1
    for (int s = 1; s < NSEG; s++) {
        bar_sync(3, 320 + OB);
        if (!FLAGS) {
            bar_arrive(4, 288 + OB); bar_sync(5, 288 + OB);
            bar_arrive(6, 320 + OB + (rank == 2 ? delay<18>(zero) : 0));
            continue;
        }
        if (lane < 2) asm volatile("red.relaxed.gpu.global.add.u32 [%0], 1;" ::"l"(po) : "memory");
        wait_flags<DLO>(ring + fo, s * (rank == 2 ? 30 : 33), zero, 4, 288 + OB);
        bar_sync(5, 288 + OB);
        if (lane < 2) asm volatile("red.relaxed.gpu.global.add.u32 [%0], 1;" ::"l"(pm) : "memory");
        wait_flags<DLM>(ring + fm, s * 96, zero, 6, 320 + OB);
    }
}
__device__ __forceinline__ void chain_chores(const uint32_t sb, const int lane, const int rank, const int h) {
    const int nq = rank == 0 ? 6 : 5, u0 = rank == 0 ? 0 : 1 + 5 * rank, v0 = rank == 0 ? -6 : 3 * rank - 6;
    const uint32_t barS = sb + CH_BAR, barM = barS + 8, barX = barS + 16;
    auto xload = [&](int s) {
        mbar_expect(barX, 8192 - nq * 512);
        bulk_load(sb + CH_XS, g_kx + (size_t)(s * NH + h) * 4096 + u0 * 256, nq * 512, barX);
        bulk_load(sb + CH_XS + nq * 512, g_vx + (size_t)(s * NH + h) * 4096 + (v0 + nq) * 512, (8 - nq) * 1024, barX);
    };
    int pos, cw = o_chunk(h * 8 + v0 + min(max(5 + (lane >> 3), nq), 7), pos);
    if (lane >= 24 && rank < 2) { cw = 24 + (h >> 2); pos = (2 * h + rank) & 7; }
    char* const rb = ring_base() + ((ring_off(cw, 0) & ~4096u) + pos * 256 + (lane & 7) * 16);
    if (lane == 0) xload(0);
#pragma unroll 1
    for (int s = 0; s < NSEG - 1; s++) {
        if (lane == 0) {
            mbar_expect(barS, 3 * 1280);
            if (rank < 2) mbar_expect(barM, 2 * 512);
        }
#pragma unroll
        for (int i = 0; i < 4; i++)
            asm volatile("st.relaxed.gpu.global.v4.u32 [%0], {%1,%1,%1,%1};" ::"l"(rb + ((((s + 2) & 3) << 14) + (i >> 1) * 4096 + (i & 1) * 128)), "r"(SENT) : "memory");
        __threadfence();
        if (lane == 0 && (s & 3) == 0 && s) atomicAdd(g_ctr + C_CHAIN + (s >> 2) - 1, 1);
        bar_sync(3, 320 + OB);
        if (lane == 0) xload(s + 1);
        mbar_wait(barX, (s + 1) & 1);
        bar_sync(6, 320 + OB);
    }
    bar_sync(6, 288);
    __threadfence();
    if (lane == 0) atomicAdd(g_ctr + C_CHAIN + 15, 1);
}

__global__ void __cluster_dims__(3, 1, 1) __launch_bounds__(CH_THREADS, 1)
chain_kernel(const __grid_constant__ CUtensorMap mq, const __grid_constant__ CUtensorMap mk, const __grid_constant__ CUtensorMap mv,
             const __grid_constant__ CUtensorMap mo, const bf16* __restrict__ Wq, const bf16* __restrict__ Wk, const bf16* __restrict__ Wv,
             const bf16* __restrict__ Wo, int aware) {
    extern __shared__ __align__(1024) unsigned char smem[];
    const uint32_t sb = smem_u32(smem);
    const int tid = threadIdx.x, lane = tid & 31;
    const int w = __shfl_sync(0xffffffffu, tid >> 5, 0);
    int rank; asm("mov.u32 %0, %%cluster_ctarank;" : "=r"(rank));
    const int h = blockIdx.x / 3;
    if (tid == 0) {
        mbar_init(sb + CH_BAR, 1); mbar_init(sb + CH_BAR + 8, 1); mbar_init(sb + CH_BAR + 16, 1);
        for (int i = 0; i < 16; i++) mbar_init(sb + CH_BAR + 64 + i * 8, 1);
        *(int*)(smem + CH_BAR + 24) = 0;
        asm volatile("fence.mbarrier_init.release.cluster;" ::: "memory");
    }
    __threadfence();
    asm volatile("griddepcontrol.launch_dependents;" ::: "memory");
    uint32_t smid; asm("mov.u32 %0, %%smid;" : "=r"(smid));
    const int side = __shfl_sync(0xffffffffu, aware ? g_side[smid] ^ (aware - 1) : 0, 0);
    asm volatile("barrier.cluster.arrive.aligned; barrier.cluster.wait.aligned;" ::: "memory");

    if (w >= 8) {
        reg_dec<24>();
        if (w == 11) {
            for (int e = blockIdx.x + 96 * lane; e < CPF * 1024; e += 96 * 32) {
                const bf16* p = e < 1024 ? Wo : e < 2048 ? Wv : e < 3072 ? Wk : Wq;
                asm volatile("cp.async.bulk.prefetch.L2.global [%0], 8192;" ::"l"(p + (size_t)(e & 1023) * 4096) : "memory");
            }
        } else if (w == 8) chain_flags(sb, lane, rank, h, side);
        else if (w == 9) {
            asm volatile("griddepcontrol.wait;" ::: "memory");
            asm volatile("fence.proxy.async;" ::: "memory");
            chain_chores(sb, lane, rank, h);
        }
    } else {
        reg_inc<240>();
        const int nq = rank == 0 ? 6 : 5;
        const int u0 = rank == 0 ? 0 : 1 + 5 * rank;
        const int v0 = rank == 0 ? -6 : 3 * rank - 6;
        const int gw = rank * 8 + w;
        const int ks0 = gw < 16 ? 11 * gw : 176 + 10 * (gw - 16);
        const int nko = gw < 16 ? 11 : 10;
        const uint32_t wr = sb + w * CH_WREG, bar0 = sb + CH_BAR + 64 + w * 16, bar1 = bar0 + 8;
        uint32_t wa[36][4];
        const uint32_t vst = sb + CH_PART + w * 2048;
        const int cq = h * DH + 8 * u0, cv = h * DH + 16 * (v0 + 6);
        if (lane == 0) {
            mbar_expect(bar0, 18432);
            for (int i = 0; i < 4; i++) {
                tma2d(wr + 8192 + i * 2048, &mq, cq, 128 * w + 32 * i, bar0);
                tma2d(wr + 16384 + i * 2048, &mk, cq, 128 * w + 32 * i, bar0);
            }
            tma2d(vst, &mv, cv, 128 * w, bar0);
        }
        {
            const int r8 = lane >> 2, p = lane & 3;
            const bf16* src = p >= 2 ? ((p & 1) ? Wk : Wq) + cq + 32 : rank == 0 ? ((p & 1) ? Wk : Wq) + cq + 40 : Wv + cv - 16 + 8 * p;
            src += (size_t)(128 * w + r8) * HD;
#pragma unroll 4
            for (int kh = 0; kh < 16; kh++)
                cp16(wr + ((kh >> 1) * 2 + (p >> 1)) * 512 + ((kh & 1) * 2 + (p & 1)) * 128 + r8 * 16, src + (size_t)kh * 8 * HD);
        }
        const uint32_t lrow = ((lane >> 4) * 8 + (lane & 7)) * 64, lsw = (lane >> 1) & 3, lh = (lane >> 3) & 1;
        mbar_wait(bar0, 0);
#pragma unroll
        for (int i = 0; i < 32; i++) ldsm4t(wa[i], wr + 8192 + lh * 8192 + (i & 7) * 1024 + lrow + (((i >> 3) ^ lsw) << 4));
#pragma unroll
        for (int i = 0; i < 4; i++) ldsm4t(wa[32 + i], vst + (i >> 1) * 1024 + lrow + ((((i & 1) * 2 + lh) ^ lsw) << 4));
        asm volatile("fence.proxy.async.shared::cta;" ::"r"(wa[31][0]), "r"(wa[35][0]) : "memory");
        __syncwarp();
        if (lane == 0) {
            mbar_expect(bar1, 6144 + nko * 1024);
            for (int i = 0; i < 3; i++) tma2d(wr + 8192 + i * 2048, &mv, cv, 128 * w + 32 + 32 * i, bar1);
            for (int i = 0; i < nko; i++) tma2d(wr + 14336 + i * 1024, &mo, 32 * h, 16 * (ks0 + i), bar1);
        }
        mbar_wait(bar1, 0);
#pragma unroll 1
        for (int i = 0; i < 17; i++) {
            uint32_t x[4], y[4];
            ldsm4t(x, wr + 8192 + i * 1024 + lrow + ((lh ^ lsw) << 4));
            ldsm4t(y, wr + 8192 + i * 1024 + lrow + (((2 + lh) ^ lsw) << 4));
            if (i == 16 && nko == 10) x[0] = x[1] = x[2] = x[3] = y[0] = y[1] = y[2] = y[3] = 0;
            __syncwarp();
            stsm4t(wr + 8192 + i * 1024 + lane * 16, x[0], x[1], x[2], x[3]);
            stsm4t(wr + 8192 + i * 1024 + 512 + lane * 16, y[0], y[1], y[2], y[3]);
        }
        asm volatile("cp.async.wait_all;" ::: "memory");
        bar_sync(1, 256);
        if (w >= nq) chain_loop<true>(wa, sb, w, lane, rank, h, side);
        else chain_loop<false>(wa, sb, w, lane, rank, h, side);
    }
}

#define STM 1
__device__ __forceinline__ void st_stream(uint32_t* p, uint32_t v, uint64_t pol) {
    if (STM == 0) *p = v;
    else if (STM == 1) asm volatile("st.global.L2::cache_hint.u32 [%0], %1, %2;" ::"l"(p), "r"(v), "l"(pol) : "memory");
    else __stcs(p, v);
}
#define PF0 36
#define PFN 24
#define PFM 2
constexpr int G_STAGE = 49152, G_NST = 4;
constexpr int G_STG = G_NST * G_STAGE;
constexpr int G_BAR = G_STG + 32768;
constexpr int G_SMEM = G_BAR + 128 + 1024;

__global__ void __launch_bounds__(384, 1)
kv_kernel(const __grid_constant__ CUtensorMap mx, const __grid_constant__ CUtensorMap mk, const __grid_constant__ CUtensorMap mv,
          const bf16* __restrict__ mem0, const bf16* Wq, const bf16* Wk, const bf16* Wv, const bf16* Wo) {
    extern __shared__ unsigned char smem_raw[];
    const uint32_t sb = (smem_u32(smem_raw) + 1023) & ~1023u;
    const uint32_t full = sb + G_BAR, empty = full + 32;
    const int tid = threadIdx.x, wg = tid >> 7, lane = tid & 31;
    if (tid == 0)
        for (int i = 0; i < G_NST; i++) { mbar_init(full + 8 * i, 1); mbar_init(empty + 8 * i, 2); }
    __syncthreads();
    if (wg == 0) {
        reg_dec<40>();
        if (tid == 0) {
            asm volatile("fence.proxy.async;" ::: "memory");
            int it = 0;
            for (int p = blockIdx.x; p < 512; p += gridDim.x) {
                const int m0 = (p & 15) * 128, nt = p >> 4;
                const CUtensorMap* mw = nt < 16 ? &mk : &mv;
                const int ng = (nt & 15) * 4;
                for (int kb = 0; kb < 16; kb++, it++) {
                    const int st = it & 3;
                    mbar_wait(empty + 8 * st, ((it >> 2) & 1) ^ 1);
                    mbar_expect(full + 8 * st, G_STAGE);
                    const uint32_t a = sb + st * G_STAGE;
                    tma2d(a, &mx, kb * 64, m0, full + 8 * st);
                    tma3d(a + 16384, mw, 0, kb * 64, ng, full + 8 * st);
                    tma3d(a + 32768, mw, 0, kb * 64, ng + 2, full + 8 * st);
                    if (it >= PF0 && it < PF0 + PFN && blockIdx.x < 112) {
                        for (int e = (it - PF0) * 112 + blockIdx.x; e < PFM * 1024; e += PFN * 112) {
                            const bf16* w = e < 1024 ? Wq : e < 2048 ? Wk : e < 3072 ? Wo : Wv;
                            asm volatile("cp.async.bulk.prefetch.L2.global [%0], 8192;" ::"l"(w + (size_t)(e & 1023) * 4096) : "memory");
                        }
                    }
                }
            }
        } else if (tid >= 32) {
            char* ring = ring_base();
            for (int k = blockIdx.x * 96 + tid - 32; k < (1 << 17); k += gridDim.x * 96) {
                uint2 v = make_uint2(SENT, SENT);
                int off = k * 8, chunk = ((off >> 13) & 1) | ((off >> 16) << 1), slot = (off >> 14) & 3, in = off & 4095;
                if (in >= 3072) continue;
                if (chunk >= 24 && in >= 2048) v = make_uint2(0, 0);
                if (chunk >= 24 && slot == 0 && in < 2048) {
                    int ks = (chunk - 24) * 8 + (in >> 8), l = (in >> 3) & 31;
                    const uint32_t* p = (const uint32_t*)(mem0 + (l >> 2) * DM + 16 * ks + 2 * (l & 3));
                    v.x = p[0]; v.y = p[4];
                    if (v.x == SENT) v.x = 0x7FFF7FFFu;
                }
                *(uint2*)(ring + off) = v;
            }
            if (blockIdx.x == 0)
                for (int k = tid - 32; k < N_CTR; k += 96) g_ctr[k] = 0;
            if (tid == 32) {
                uint32_t smid; asm("mov.u32 %0, %%smid;" : "=r"(smid));
                uint32_t* p0 = (uint32_t*)(ring + ring_off(smid & 15, 0) + 3072 + (smid >> 4) * 64);
                uint32_t* p1 = (uint32_t*)(ring + ring_off(smid & 15, 1) + 3072 + (smid >> 4) * 64);
                *p0 = 0; *p1 = 0;
                int b0 = 1 << 30, b1 = 1 << 30; uint32_t v = 0;
                for (int r = 0; r < 24; r++) {
                    uint32_t t0 = clk(); v = atomicExch(p0 + (v == 50), r); uint32_t t1 = v == 77 ? clk() + 1 : clk(); b0 = min(b0, (int)(t1 - t0));
                    t0 = clk(); v = atomicExch(p1 + (v == 50), r); t1 = v == 77 ? clk() + 1 : clk(); b1 = min(b1, (int)(t1 - t0));
                }
                g_side[smid] = b1 < b0;
            }
            __threadfence();
            bar_sync(1, 96);
            asm volatile("griddepcontrol.launch_dependents;" ::: "memory");
        }
    } else {
        reg_inc<232>();
        const int wi = (tid >> 5) & 3;
        float acc[128];
        uint32_t pk[64];
        uint32_t* dst = nullptr;
        uint64_t pol; asm("createpolicy.fractional.L2::evict_first.b64 %0, 1.0;" : "=l"(pol));
        int it = 0;
        for (int p = blockIdx.x; p < 512; p += gridDim.x) {
#pragma unroll
            for (int kb = 0; kb < 16; kb++, it++) {
                const int st = kb & 3;
                mbar_wait(full + 8 * st, (it >> 2) & 1);
                const uint64_t da = mkdesc(sb + st * G_STAGE + (wg - 1) * 8192, 16, 1024, 1);
                const uint64_t db = mkdesc(sb + st * G_STAGE + 16384, 8192, 1024, 1);
                wg_fence();
#pragma unroll
                for (int k = 0; k < 4; k++) wgmma256(acc, da + k * 2, db + k * 128, kb | k);
                wg_commit();
                if (dst) {
#pragma unroll
                    for (int j = 0; j < 4; j++) st_stream(dst + (kb * 2 + (j >> 1)) * 128 + (j & 1) * 32, pk[kb * 4 + j], pol);
                }
                if (kb > 0) {
                    wg_wait<1>();
                    if ((tid & 127) == 0) mbar_arrive(empty + 8 * ((kb - 1) & 3));
                }
            }
            wg_wait<0>();
            if ((tid & 127) == 0) mbar_arrive(empty + 8 * 3);
#pragma unroll
            for (int j = 0; j < 64; j++) pk[j] = pack_bf16(acc[2 * j], acc[2 * j + 1]);
            const int row = (p & 15) * 128 + (wg - 1) * 64 + wi * 16, nt = p >> 4;
            dst = (uint32_t*)(nt < 16 ? g_kx : g_vx) + (size_t)((row >> 5) * 512 + (nt & 15) * 32) * 128 + (row & 31) * 4 + lane;
        }
#pragma unroll
        for (int j = 0; j < 64; j++) st_stream(dst + (j >> 1) * 128 + (j & 1) * 32, pk[j], pol);
    }
}

#define WLOG(e)
struct S4Params { const bf16 *Are, *Aim, *Bre, *Bim, *Cre, *Cim, *ldt, *dsk; };
constexpr int IT_QA = 0, IT_O = 1, IT_S4 = 2, IT_END = 3;
#define O_WIDE 11
__device__ __forceinline__ int o_items(int b) { return b < O_WIDE ? 4 : 8; }
__device__ __forceinline__ int ld_acq(const int* p) { int v; asm volatile("ld.acquire.gpu.global.s32 %0, [%1];" : "=r"(v) : "l"(p) : "memory"); return v; }
__device__ __forceinline__ void wait_ctr(const int* p, int n) {
    for (int it = 0; it < (1 << 22) && ld_acq(p) < n; it++) __nanosleep(64);
}
__device__ __forceinline__ void tma2d_store(const CUtensorMap* m, uint32_t src, int c0, int c1) {
    asm volatile("cp.async.bulk.tensor.2d.global.shared::cta.bulk_group [%0, {%2, %3}], [%1];" ::"l"(m), "r"(src), "r"(c0), "r"(c1) : "memory");
}
__device__ __forceinline__ void mma8(float (&d)[4], uint32_t a0, uint32_t a1, uint32_t b0) {
    asm volatile("mma.sync.aligned.m16n8k8.row.col.f32.bf16.bf16.f32 {%0,%1,%2,%3}, {%4,%5}, {%6}, {%0,%1,%2,%3};"
        : "+f"(d[0]), "+f"(d[1]), "+f"(d[2]), "+f"(d[3]) : "r"(a0), "r"(a1), "r"(b0));
}

__device__ __forceinline__ void attn_head(const uint32_t (&q)[32], uint32_t sk, uint32_t sv, uint32_t fullv, uint32_t parv, uint32_t emptyk,
                                          int wi, int lane, uint32_t* dst) {
    const int g = lane >> 2, t = lane & 3, hi = wi & 1;
    float s[5][4];
#pragma unroll
    for (int j = 0; j < 5; j++) s[j][0] = s[j][1] = s[j][2] = s[j][3] = 0.f;
#pragma unroll
    for (int k2 = 0; k2 < 4; k2++) {
        uint32_t km[4];
        ldsm4(km, sk + 8192 + k2 * 512 + lane * 16);
#pragma unroll
        for (int i = 0; i < 2; i++) {
            const int ks = 2 * k2 + i;
            const uint32_t a[4] = {q[4 * ks], q[4 * ks + 1], q[4 * ks + 2], q[4 * ks + 3]};
            uint32_t b[4];
            const uint32_t ad = sk + ks * 1024 + ((lane >> 3) & 1) * 512 + (lane >> 4) * 128 + (lane & 7) * 16;
            ldsm4(b, ad);
            mma16(s[4], a, km[2 * i], km[2 * i + 1]);
            mma16(s[0], a, b[0], b[1]); mma16(s[1], a, b[2], b[3]);
            if (hi) { ldsm4(b, ad + 256); mma16(s[2], a, b[0], b[1]); mma16(s[3], a, b[2], b[3]); }
        }
    }
    __syncwarp();
    if (lane == 0) mbar_arrive(emptyk);
    const int r0 = hi * 16 + g;
    float m0 = fmaxf(s[4][0], s[4][1]), m1 = fmaxf(s[4][2], s[4][3]);
#pragma unroll
    for (int j = 0; j < 4; j++) {
        const int c = 8 * j + 2 * t;
        if (c > r0) s[j][0] = -INFINITY;
        if (c + 1 > r0) s[j][1] = -INFINITY;
        if (c > r0 + 8) s[j][2] = -INFINITY;
        if (c + 1 > r0 + 8) s[j][3] = -INFINITY;
        m0 = fmaxf(m0, fmaxf(s[j][0], s[j][1])); m1 = fmaxf(m1, fmaxf(s[j][2], s[j][3]));
    }
    m0 = fmaxf(m0, __shfl_xor_sync(0xffffffffu, m0, 1)); m1 = fmaxf(m1, __shfl_xor_sync(0xffffffffu, m1, 1));
    m0 = fmaxf(m0, __shfl_xor_sync(0xffffffffu, m0, 2)); m1 = fmaxf(m1, __shfl_xor_sync(0xffffffffu, m1, 2));
    const float cs = 0.08838834764831845f * 1.4426950408889634f;
    m0 *= -cs; m1 *= -cs;
    float l0 = 0, l1 = 0;
#pragma unroll
    for (int j = 0; j < 5; j++) {
        s[j][0] = ex2(fmaf(s[j][0], cs, m0)); s[j][1] = ex2(fmaf(s[j][1], cs, m0));
        s[j][2] = ex2(fmaf(s[j][2], cs, m1)); s[j][3] = ex2(fmaf(s[j][3], cs, m1));
        l0 += s[j][0] + s[j][1]; l1 += s[j][2] + s[j][3];
    }
    l0 += __shfl_xor_sync(0xffffffffu, l0, 1); l1 += __shfl_xor_sync(0xffffffffu, l1, 1);
    l0 += __shfl_xor_sync(0xffffffffu, l0, 2); l1 += __shfl_xor_sync(0xffffffffu, l1, 2);
    l0 = __fdividef(1.f, l0); l1 = __fdividef(1.f, l1);
    uint32_t p[10];
#pragma unroll
    for (int j = 0; j < 5; j++) { p[2 * j] = pack_bf16(s[j][0] * l0, s[j][1] * l0); p[2 * j + 1] = pack_bf16(s[j][2] * l1, s[j][3] * l1); }
    const uint32_t p0[4] = {p[0], p[1], p[2], p[3]}, p1[4] = {p[4], p[5], p[6], p[7]};
    mbar_wait(fullv, parv);
#pragma unroll
    for (int u4 = 0; u4 < 4; u4++) {
        uint32_t vm[4];
        ldsm4t(vm, sv + 8192 + u4 * 512 + lane * 16);
#pragma unroll
        for (int i = 0; i < 4; i++) {
            const int u = 4 * u4 + i;
            uint32_t b[4];
            ldsm4t(b, sv + u * 512 + lane * 16);
            float o[4];
            mma16z(o, p0, b[0], b[1]);
            if (hi) mma16(o, p1, b[2], b[3]);
            mma8(o, p[8], p[9], vm[i]);
            dst[(u >> 3) * 4096 + (u & 7) * 32] = pack_bf16(o[0], o[1]);
            dst[(u >> 3) * 4096 + (u & 7) * 32 + 256] = pack_bf16(o[2], o[3]);
        }
    }
}

template <int BN, int NKB, bool BLOCKED_A>
__device__ __forceinline__ void mainloop(float (&acc)[BN / 2], uint32_t sb, int wgi, uint32_t full, uint32_t empty, int& it, bool elect) {
#pragma unroll
    for (int j = 0; j < BN / 2; j++) acc[j] = 0.f;
#pragma unroll 1
    for (int k4 = 0; k4 < NKB; k4 += 4) {
#pragma unroll
        for (int st = 0; st < 4; st++, it++) {
            mbar_wait(full + 8 * st, (it >> 2) & 1);
            const uint64_t da = BLOCKED_A ? mkdesc(sb + st * G_STAGE + wgi * 8192, 128, 1024, 0) : mkdesc(sb + st * G_STAGE + wgi * 8192, 16, 1024, 1);
            const uint64_t db = mkdesc(sb + st * G_STAGE + 16384, 8192, 1024, 1);
            wg_fence();
#pragma unroll
            for (int k = 0; k < 4; k++) {
                if constexpr (BN == 256) wgmma256(acc, da + k * (BLOCKED_A ? 16 : 2), db + k * 128, 1);
                else wgmma128(acc, da + k * (BLOCKED_A ? 16 : 2), db + k * 128, 1);
            }
            wg_commit();
            if (k4 | st) {
                wg_wait<1>();
                if (elect) mbar_arrive(empty + 8 * ((st + 3) & 3));
            }
        }
    }
    wg_wait<0>();
    if (elect) mbar_arrive(empty + 8 * 3);
}

template <int BN>
__device__ __forceinline__ void o_item(uint32_t sb, int wgi, int wi, int lane, uint32_t full, uint32_t empty, int& it, const CUtensorMap* mout,
                                       int row0, int col0) {
    float acc[BN / 2];
    mainloop<BN, 64, true>(acc, sb, wgi, full, empty, it, lane == 0);
    const uint32_t stg = sb + G_STG + (wgi * 4 + wi) * 4096;
    const int r = lane & 15, cu = lane >> 4;
#pragma unroll
    for (int hf = 0; hf < BN / 128; hf++) {
        if (lane == 0) asm volatile("cp.async.bulk.wait_group.read 0;" ::: "memory");
        __syncwarp();
#pragma unroll
        for (int j = 0; j < 8; j++) {
            const float* a = acc + hf * 64 + j * 8;
            stsm4(stg + (j >> 2) * 2048 + r * 128 + ((((j & 3) * 2 + cu) ^ (r & 7)) << 4),
                  pack_bf16(a[0], a[1]), pack_bf16(a[2], a[3]), pack_bf16(a[4], a[5]), pack_bf16(a[6], a[7]));
        }
        asm volatile("fence.proxy.async.shared::cta;" ::: "memory");
        __syncwarp();
        if (lane == 0) {
            tma2d_store(mout, stg, col0 + hf * 128, row0 + wgi * 64 + wi * 16);
            tma2d_store(mout, stg + 2048, col0 + hf * 128 + 64, row0 + wgi * 64 + wi * 16);
            asm volatile("cp.async.bulk.commit_group;" ::: "memory");
        }
    }
}

constexpr int S4_RAW = G_STG;
constexpr int S4_CH = 0;
constexpr int S4_UT = 0;
constexpr int S4_WD = 5120;
constexpr int S4_STRIDE = 5120 + 8320 + 16;

__device__ __forceinline__ float2 cmul(float2 a, float2 b) { return make_float2(a.x * b.x - a.y * b.y, a.x * b.y + a.y * b.x); }
__device__ __forceinline__ float2 csq(float2 a) { return make_float2(a.x * a.x - a.y * a.y, (a.x + a.x) * a.y); }
__device__ __forceinline__ float2 cexp_t(float lr, float turns) {
    float f = (turns - rintf(turns)) * 6.283185307179586f, e = ex2(lr);
    return make_float2(e * __cosf(f), e * __sinf(f));
}
__device__ __forceinline__ void s4_lda(uint32_t (&a)[4], uint32_t ad) {
    asm volatile("ld.shared.u32 %0, [%4]; ld.shared.u32 %1, [%4+32]; ld.shared.u32 %2, [%4+-32]; ld.volatile.shared.u32 %3, [%4];"
        : "=r"(a[0]), "=r"(a[1]), "=r"(a[2]), "=r"(a[3]) : "r"(ad) : "memory");
}
template <int H0>
__device__ __forceinline__ void s4_conv_step(float (&acc)[16][4], const uint32_t (&bw)[4][2][4], uint32_t (&nw)[4][2][4], uint32_t (&a)[2][4],
                                             uint32_t ut, uint32_t wd) {
#pragma unroll
    for (int h = H0; h < 4; h++) { ldsm4(nw[h][1], ut + (8 * h - 1) * 16 + 2560); ldsm4(nw[h][0], ut + (8 * h - 1) * 16); }
#pragma unroll
    for (int i = 0; i < 4; i++) {
        s4_lda(a[(i + 1) & 1], wd + (i + 1) * 64);
#pragma unroll
        for (int tau = 3; tau >= 0; tau--)
#pragma unroll
            for (int h = H0; h < 4; h++) {
                const int r = (tau - i) & 3;
                if (tau >= i) mma16(acc[4 * h + tau], a[i & 1], bw[h][r >> 1][2 * (r & 1)], bw[h][r >> 1][2 * (r & 1) + 1]);
                else mma16(acc[4 * h + tau], a[i & 1], nw[h][r >> 1][2 * (r & 1)], nw[h][r >> 1][2 * (r & 1) + 1]);
            }
    }
}
template <int H0>
__device__ __forceinline__ void s4_conv_phase(float (&acc)[16][4], uint32_t (&bw)[4][2][4], uint32_t (&a)[2][4], uint32_t ut, uint32_t wd) {
#pragma unroll 1
    for (int E = 8 * H0; E < 8 * H0 + 8; E += 2) {
        uint32_t nw[4][2][4];
        s4_conv_step<H0>(acc, bw, nw, a, ut - E * 16, wd + E * 256);
        s4_conv_step<H0>(acc, nw, bw, a, ut - E * 16 - 16, wd + E * 256 + 256);
    }
}

__device__ __forceinline__ void s4_item(uint32_t sb, int cw, int lane, int item, const S4Params& P, uint32_t ubar, uint32_t par, const CUtensorMap* mu,
                                        const CUtensorMap* my) {
    const int g = lane >> 2, t = lane & 3, d = item * 8 + cw;
    const uint32_t ch = sb + S4_CH + cw * S4_STRIDE;
    if (lane == 0) {
        asm volatile("cp.async.bulk.wait_group.read 0;" ::: "memory");
        mbar_expect(ubar, 4096);
        tma2d(sb + S4_RAW + cw * 4096, mu, item * 8, cw * 256, ubar);
    }
    const float dt = __bfloat162float(__float2bfloat16(expf(__bfloat162float(P.ldt[d]))));
#pragma unroll
    for (int i = 0; i < 4; i++) {
        const int n = d * 128 + i * 32 + lane;
        const float br = dt * __bfloat162float(P.Bre[n]), bi = dt * __bfloat162float(P.Bim[n]);
        const float cr = __bfloat162float(P.Cre[n]), ci = __bfloat162float(P.Cim[n]);
        const float v[4] = {dt * __bfloat162float(P.Are[n]) * 1.4426950408889634f, dt * __bfloat162float(P.Aim[n]) * 0.15915494309189535f,
                            cr * br - ci * bi, cr * bi + ci * br};
        sts128(ch + S4_WD + (i * 32 + lane) * 16, v);
    }
    __syncwarp();
    float kd[5][4], k2048 = 0.f;
#pragma unroll
    for (int j = 0; j < 5; j++) kd[j][0] = kd[j][1] = kd[j][2] = kd[j][3] = 0.f;
    const float x0 = (float)g, x1 = (float)(g + 8);
#pragma unroll 1
    for (int ks = 0; ks < 16; ks++) {
        uint32_t a[4][4], b[5][2];
#pragma unroll
        for (int i = 0; i < 2; i++) {
            const float4 p = lds128(ch + S4_WD + (ks * 8 + i * 4 + t) * 16);
            const float2 c = make_float2(p.z, p.w);
            float2 e0 = cexp_t(p.x * x0, p.y * x0), e1 = cexp_t(p.x * x1, p.y * x1);
#pragma unroll
            for (int j = 0; j < 4; j++) {
                a[j][2 * i] = pack_bf16(e0.x, e0.y); a[j][2 * i + 1] = pack_bf16(e1.x, e1.y);
                e0 = csq(e0); e1 = csq(e1);
            }
            float2 m = cmul(c, e0);
            b[0][i] = pack_bf16(m.x, -m.y);
#pragma unroll
            for (int j = 0; j < 4; j++) {
                m = cmul(c, e1);
                b[j + 1][i] = pack_bf16(m.x, -m.y);
                e1 = csq(e1);
            }
            k2048 += c.x * e1.x - c.y * e1.y;
        }
        mma16(kd[0], a[0], b[0][0], b[0][1]);
#pragma unroll
        for (int j = 0; j < 4; j++) mma16(kd[j + 1], a[j], b[j + 1][0], b[j + 1][1]);
    }
    k2048 += __shfl_xor_sync(0xffffffffu, k2048, 1);
    k2048 += __shfl_xor_sync(0xffffffffu, k2048, 2);
    {
        const uint32_t ta = ch + S4_UT + (lane & 7) * 32 + ((lane >> 3) & 1) * 16 + (lane >> 4) * 256;
        stsm4t(ta, pack_bf16(kd[0][0], kd[0][1]), pack_bf16(kd[0][2], kd[0][3]), pack_bf16(kd[1][0], kd[1][1]), pack_bf16(kd[1][2], kd[1][3]));
        stsm4t(ta + 512, pack_bf16(kd[2][0], kd[2][1]), pack_bf16(kd[2][2], kd[2][3]), pack_bf16(kd[3][0], kd[3][1]), pack_bf16(kd[3][2], kd[3][3]));
        stsm4t(ta + 1024, pack_bf16(kd[4][0], kd[4][1]), pack_bf16(kd[4][2], kd[4][3]), pack_bf16(k2048, 0.f), 0);
    }
    __syncwarp();
    if (lane < 16) asm volatile("st.shared.u32 [%0], %1;" ::"r"(ch + S4_WD + lane * 4), "r"(0) : "memory");
#pragma unroll
    for (int i = 0; i < 16; i++) {
        const int sh = i < 2 ? 0 : i < 4 ? 1 : i < 8 ? 2 : 3;
        uint32_t k[5];
#pragma unroll
        for (int j = 0; j < 5; j++) {
            const int x = i * 128 + lane * 4 + j - 1;
            int idx = sh ? 128 * sh + ((x + (1 << sh >> 1) - 1 + ((x >> sh) & 1)) >> sh) : x;
            if (i == 2 && j == 0 && lane == 0) idx = 255;
            asm volatile("ld.shared.u16 %0, [%1];" : "=r"(k[j]) : "r"(ch + S4_UT + max(idx, 0) * 2) : "memory");
        }
        if (i == 0 && lane == 0) k[0] = 0;
        asm volatile("st.shared.v4.u32 [%0], {%1,%2,%3,%4};" ::"r"(ch + S4_WD + 64 + i * 512 + lane * 16), "r"(k[1] | (k[0] << 16)),
                     "r"(k[2] | (k[1] << 16)), "r"(k[3] | (k[2] << 16)), "r"(k[4] | (k[3] << 16)) : "memory");
    }
    bar_sync(2, 256);
    if (lane < 8) {
#pragma unroll
        for (int i = 0; i < 8; i++) asm volatile("st.shared.v4.u32 [%0], {%1,%1,%1,%1};" ::"r"(ch + S4_UT + i * 640 + lane * 16), "r"(0) : "memory");
    }
    mbar_wait(ubar, par);
    const uint32_t traw = sb + S4_RAW + cw * 4096 + lane * 16;
    const uint32_t tch = sb + S4_CH + (lane & 7) * S4_STRIDE + S4_UT + (lane >> 3) * 640 + (8 + cw * 4) * 16;
#pragma unroll
    for (int i = 0; i < 8; i++) {
        uint32_t x[4];
        ldsm4t(x, traw + i * 512);
        stsm4(tch + (i & 1) * 2560 + (i >> 1) * 16, x[0], x[1], x[2], x[3]);
    }
    bar_sync(2, 256);
    float acc[16][4];
#pragma unroll
    for (int j = 0; j < 16; j++) acc[j][0] = acc[j][1] = acc[j][2] = acc[j][3] = 0.f;
    const uint32_t ut = ch + S4_UT + (lane >> 3) * 640 + (8 + (lane & 7)) * 16, wd = ch + S4_WD + 64 + (g - 2 * t) * 4;
    uint32_t bw[4][2][4], aw[2][4];
#pragma unroll
    for (int h = 0; h < 4; h++) { ldsm4(bw[h][0], ut + 8 * h * 16); ldsm4(bw[h][1], ut + 8 * h * 16 + 2560); }
    s4_lda(aw[0], wd);
    s4_conv_phase<0>(acc, bw, aw, ut, wd);
    s4_conv_phase<1>(acc, bw, aw, ut, wd);
    s4_conv_phase<2>(acc, bw, aw, ut, wd);
    if (lane == 0) mbar_arrive(ubar - 104 + 32 + 24);
    s4_conv_phase<3>(acc, bw, aw, ut, wd);
    __syncwarp();
#pragma unroll
    for (int j = 0; j < 16; j += 2)
        stsm4t(ut + (j >> 2) * 128 + (j & 2) * 1280, pack_bf16(acc[j][0], acc[j][1]), pack_bf16(acc[j][2], acc[j][3]),
               pack_bf16(acc[j + 1][0], acc[j + 1][1]), pack_bf16(acc[j + 1][2], acc[j + 1][3]));
    bar_sync(2, 256);
    const __nv_bfloat162 dk = *(const __nv_bfloat162*)(P.dsk + item * 8 + 2 * t);
#pragma unroll
    for (int i = 0; i < 8; i++) {
        uint32_t y[4], u[4];
        ldsm4t(y, tch + (i & 1) * 2560 + (i >> 1) * 16);
        ldsm4(u, traw + i * 512);
#pragma unroll
        for (int j = 0; j < 4; j++) {
            __nv_bfloat162 r = __hadd2_rn(*(__nv_bfloat162*)&y[j], __hmul2_rn(*(__nv_bfloat162*)&u[j], dk));
            y[j] = *(uint32_t*)&r;
        }
        stsm4(traw + i * 512, y[0], y[1], y[2], y[3]);
    }
    asm volatile("fence.proxy.async.shared::cta;" ::: "memory");
    __syncwarp();
    if (lane == 0) {
        tma2d_store(my, sb + S4_RAW + cw * 4096, DM + item * 8, cw * 256);
        asm volatile("cp.async.bulk.commit_group;" ::: "memory");
    }
}

__global__ void __launch_bounds__(384, 1)
worker_kernel(const __grid_constant__ CUtensorMap mx, const __grid_constant__ CUtensorMap mq, const __grid_constant__ CUtensorMap mo,
              const __grid_constant__ CUtensorMap mout, const __grid_constant__ CUtensorMap mu, const __grid_constant__ CUtensorMap my,
              const __grid_constant__ S4Params P) {
    extern __shared__ unsigned char smem_raw[];
    const uint32_t sb = (smem_u32(smem_raw) + 1023) & ~1023u;
    const uint32_t full = sb + G_BAR, empty = full + 32, ifull = full + 64, iempty = full + 80, islot = full + 96, ubar = full + 104;
    const int tid = threadIdx.x, wg = tid >> 7, lane = tid & 31;
    if (tid == 0) {
        for (int i = 0; i < G_NST; i++) { mbar_init(full + 8 * i, 1); mbar_init(empty + 8 * i, 8); }
        for (int i = 0; i < 2; i++) { mbar_init(ifull + 8 * i, 1); mbar_init(iempty + 8 * i, 8); }
        mbar_init(ubar, 8);
        asm volatile("fence.proxy.async;" ::: "memory");
    }
    __syncthreads();
    if (wg == 0) {
        reg_dec<40>();
        if (tid < 32) {
            int it = 0;
            for (int n = 0;; n++) {
                int item = -1;
                for (int spin = 0; item < 0; spin++) {
                    const int b = lane & 15;
                    const int taken = ld_acq(g_ctr + (lane < 16 ? C_QA_NEXT : C_O_NEXT) + b);
                    const int prog = ld_acq(g_ctr + C_CHAIN + b);
                    int s4 = ld_acq(g_ctr + C_S4_NEXT);
                    const uint32_t left = __ballot_sync(0xffffffffu, taken < (lane < 16 ? 16 : o_items(b)));
                    const uint32_t done = __ballot_sync(0xffffffffu, prog >= 96) & 0xffff;
                    uint32_t qa_ok = left & 0xffff & ((done << 1) | (s4 >= S4_FIRST ? 1 : 0));
                    uint32_t o_ok = (left >> 16) & done & ~left;
                    int got = -1;
                    if (qa_ok) {
                        const int bb = __ffs(qa_ok) - 1;
                        if (lane == 0) { int i = atomicAdd(g_ctr + C_QA_NEXT + bb, 1); if (i < 16) got = (IT_QA << 16) | (bb << 8) | i; }
                    } else if (o_ok) {
                        const int bb = __ffs(o_ok) - 1;
                        if (lane == 0) { int i = atomicAdd(g_ctr + C_O_NEXT + bb, 1); if (i < o_items(bb)) got = (IT_O << 16) | (bb << 8) | i; }
                    } else if (s4 < 128) {
                        if (lane == 0) { int i = atomicAdd(g_ctr + C_S4_NEXT, 1); if (i < 128) got = (IT_S4 << 16) | i; }
                    } else if (!left || spin > (1 << 20)) got = IT_END << 16;
                    else __nanosleep(200);
                    item = __shfl_sync(0xffffffffu, got, 0);
                }
                if (lane == 0) {
                    mbar_wait(iempty + 8 * (n & 1), ((n >> 1) & 1) ^ 1);
                    asm volatile("st.shared.u32 [%0], %1;" ::"r"(islot + 4 * (n & 1)), "r"(item) : "memory");
                    mbar_arrive(ifull + 8 * (n & 1));
                    const int type = item >> 16, b = (item >> 8) & 255, i = item & 255;
                    if (type == IT_QA) {
                        for (int kb = 0; kb < 16; kb++, it++) {
                            const int st = it & 3;
                            mbar_wait(empty + 8 * st, ((it >> 2) & 1) ^ 1);
                            mbar_expect(full + 8 * st, G_STAGE);
                            const uint32_t a = sb + st * G_STAGE;
                            tma2d(a, &mx, kb * 64, b * 128, full + 8 * st);
                            tma3d(a + 16384, &mq, 0, kb * 64, i * 4, full + 8 * st);
                            tma3d(a + 32768, &mq, 0, kb * 64, i * 4 + 2, full + 8 * st);
                        }
                        wait_ctr(g_ctr + C_CHAIN + b, 96);
                        asm volatile("fence.proxy.async;" ::: "memory");
                        for (int st = 0; st < 4; st++, it++) {
                            mbar_wait(empty + 8 * st, ((it >> 2) & 1) ^ 1);
                            mbar_expect(full + 8 * st, 4 * 10240);
                            for (int sg = 0; sg < 4; sg++) {
                                const int sh = (b * 4 + sg) * NH + i * 2 + (st >> 1);
                                bulk_load(sb + st * G_STAGE + sg * 10240, ((st & 1) ? g_vx : g_kx) + (size_t)sh * 4096, 8192, full + 8 * st);
                                bulk_load(sb + st * G_STAGE + sg * 10240 + 8192, ((st & 1) ? g_vm : g_km) + (size_t)sh * 1024, 2048, full + 8 * st);
                            }
                        }
                    } else if (type == IT_O) {
                        const bool wide = b < O_WIDE;
                        wait_ctr(g_ctr + C_QA_DONE + b, 128);
                        asm volatile("fence.proxy.async;" ::: "memory");
                        for (int kb = 0; kb < 64; kb++, it++) {
                            const int st = it & 3;
                            mbar_wait(empty + 8 * st, ((it >> 2) & 1) ^ 1);
                            mbar_expect(full + 8 * st, wide ? G_STAGE : 32768);
                            const uint32_t a = sb + st * G_STAGE;
                            bulk_load(a, g_ox + (size_t)(b * 64 + kb) * 8192, 16384, full + 8 * st);
                            tma3d(a + 16384, &mo, 0, kb * 64, wide ? i * 4 : i * 2, full + 8 * st);
                            if (wide) tma3d(a + 32768, &mo, 0, kb * 64, i * 4 + 2, full + 8 * st);
                        }
                    } else if (type == IT_S4) {
                        for (int st = 0; st < 4; st++) mbar_wait(empty + 8 * st, ((it >> 2) & 1) ^ 1);
                        for (int st = 0; st < 4; st++) mbar_arrive(full + 8 * st);
                        it += 4;
                        mbar_wait_long(empty + 24, ((it >> 2) & 1) ^ 1);
                    }
                }
                __syncwarp();
                if (item >> 16 == IT_END) break;
            }
            asm volatile("griddepcontrol.wait;" ::: "memory");
        }
    } else {
        reg_inc<232>();
        const int wgi = wg - 1, wi = (tid >> 5) & 3;
        int it = 0, ns4 = 0;
        for (int n = 0;; n++) {
            mbar_wait_long(ifull + 8 * (n & 1), (n >> 1) & 1);
            int item; asm volatile("ld.shared.u32 %0, [%1];" : "=r"(item) : "r"(islot + 4 * (n & 1)) : "memory");
            __syncwarp();
            if (lane == 0) mbar_arrive(iempty + 8 * (n & 1));
            const int type = item >> 16, b = (item >> 8) & 255, i = item & 255;
            WLOG(0);
            if (type == IT_QA) {
                float acc[128];
                mainloop<256, 16, false>(acc, sb, wgi, full, empty, it, lane == 0);
                uint32_t q0[32], q1[32];
#pragma unroll
                for (int j = 0; j < 32; j++) { q0[j] = pack_bf16(acc[2 * j], acc[2 * j + 1]); q1[j] = pack_bf16(acc[64 + 2 * j], acc[65 + 2 * j]); }
                const uint32_t par = (it >> 2) & 1, so = (wgi * 2 + (wi >> 1)) * 10240;
                uint32_t* dst = (uint32_t*)g_ox + (size_t)(b * 64 + i * 4) * 4096 + (wgi * 8 + wi * 2) * 256 + lane;
                mbar_wait_long(full, par);
                attn_head(q0, sb + so, sb + G_STAGE + so, full + 8, par, empty, wi, lane, dst);
                __syncwarp();
                if (lane == 0) mbar_arrive(empty + 8);
                mbar_wait(full + 16, par);
                attn_head(q1, sb + 2 * G_STAGE + so, sb + 3 * G_STAGE + so, full + 24, par, empty + 16, wi, lane, dst + 2 * 4096);
                __syncwarp();
                if (lane == 0) { mbar_arrive(empty + 24); __threadfence(); atomicAdd(g_ctr + C_QA_DONE + b, 1); }
                it += 4;
            } else if (type == IT_O) {
                mbar_wait_long(full, (it >> 2) & 1);
                if (b < O_WIDE) o_item<256>(sb, wgi, wi, lane, full, empty, it, &mout, b * 128, i * 256);
                else o_item<128>(sb, wgi, wi, lane, full, empty, it, &mout, b * 128, i * 128);
            } else if (type == IT_S4) {
                mbar_wait(full, (it >> 2) & 1);
                s4_item(sb, wgi * 4 + wi, lane, i, P, ubar, ns4++ & 1, &mu, &my);
                if (lane == 0) { mbar_arrive(empty); mbar_arrive(empty + 8); mbar_arrive(empty + 16); }
                it += 4;
            } else break;
            WLOG(1);
        }
        if (lane == 0) asm volatile("cp.async.bulk.wait_group 0;" ::: "memory");
    }
}

typedef CUresult (*EncodeFn)(CUtensorMap*, CUtensorMapDataType, cuuint32_t, void*, const cuuint64_t*, const cuuint64_t*, const cuuint32_t*,
                             const cuuint32_t*, CUtensorMapInterleave, CUtensorMapSwizzle, CUtensorMapL2promotion, CUtensorMapFloatOOBfill);
static EncodeFn get_encode() {
    void* fn = nullptr; cudaDriverEntryPointQueryResult st;
    cudaGetDriverEntryPoint("cuTensorMapEncodeTiled", &fn, cudaEnableDefault, &st);
    return (EncodeFn)fn;
}
static void map_act(EncodeFn enc, CUtensorMap* m, const void* p, int rows, int cols, int boxr) {
    cuuint64_t dim[2] = {(cuuint64_t)cols, (cuuint64_t)rows}, str[1] = {(cuuint64_t)cols * 2};
    cuuint32_t box[2] = {64, (cuuint32_t)boxr}, es[2] = {1, 1};
    enc(m, CU_TENSOR_MAP_DATA_TYPE_BFLOAT16, 2, (void*)p, dim, str, box, es, CU_TENSOR_MAP_INTERLEAVE_NONE, CU_TENSOR_MAP_SWIZZLE_128B,
        CU_TENSOR_MAP_L2_PROMOTION_L2_128B, CU_TENSOR_MAP_FLOAT_OOB_FILL_NONE);
}
static void map_w(EncodeFn enc, CUtensorMap* m, const void* p, int k, int n) {
    cuuint64_t dim[3] = {64, (cuuint64_t)k, (cuuint64_t)n / 64}, str[2] = {(cuuint64_t)n * 2, 128};
    cuuint32_t box[3] = {64, 64, 2}, es[3] = {1, 1, 1};
    enc(m, CU_TENSOR_MAP_DATA_TYPE_BFLOAT16, 3, (void*)p, dim, str, box, es, CU_TENSOR_MAP_INTERLEAVE_NONE, CU_TENSOR_MAP_SWIZZLE_128B,
        CU_TENSOR_MAP_L2_PROMOTION_L2_256B, CU_TENSOR_MAP_FLOAT_OOB_FILL_NONE);
}

static void map_box(EncodeFn enc, CUtensorMap* m, const void* p, int rows, int ld, int boxc, int boxr, CUtensorMapSwizzle sw) {
    cuuint64_t dim[2] = {(cuuint64_t)ld, (cuuint64_t)rows}, str[1] = {(cuuint64_t)ld * 2};
    cuuint32_t box[2] = {(cuuint32_t)boxc, (cuuint32_t)boxr}, es[2] = {1, 1};
    enc(m, CU_TENSOR_MAP_DATA_TYPE_BFLOAT16, 2, (void*)p, dim, str, box, es, CU_TENSOR_MAP_INTERLEAVE_NONE, sw,
        CU_TENSOR_MAP_L2_PROMOTION_NONE, CU_TENSOR_MAP_FLOAT_OOB_FILL_NONE);
}

extern "C" void kernel_launch(void* const* d_in, const int* in_sizes, int n_in, void* d_out, int out_size) {
    const bf16* x = (const bf16*)d_in[0];
    const bf16* mem0 = (const bf16*)d_in[1];
    const bf16 *Wq = (const bf16*)d_in[2], *Wk = (const bf16*)d_in[3], *Wv = (const bf16*)d_in[4], *Wo = (const bf16*)d_in[5];
    static EncodeFn enc = nullptr;
    static int nsm = 0;
    if (!enc) {
        enc = get_encode();
        cudaDeviceGetAttribute(&nsm, cudaDevAttrMultiProcessorCount, 0);
        cudaFuncSetAttribute(chain_kernel, cudaFuncAttributeMaxDynamicSharedMemorySize, CH_SMEM);
        cudaFuncSetAttribute(kv_kernel, cudaFuncAttributeMaxDynamicSharedMemorySize, G_SMEM);
        cudaFuncSetAttribute(worker_kernel, cudaFuncAttributeMaxDynamicSharedMemorySize, G_SMEM);
    }
    CUtensorMap mx, mq, mk, mv, mo, mout, mu, my;
    map_act(enc, &mx, x, S_LEN, DM, 128);
    map_w(enc, &mq, Wq, DM, HD); map_w(enc, &mk, Wk, DM, HD); map_w(enc, &mv, Wv, DM, HD); map_w(enc, &mo, Wo, HD, DM);
    map_box(enc, &mout, d_out, S_LEN, 2 * DM, 64, 16, CU_TENSOR_MAP_SWIZZLE_128B);
    map_box(enc, &mu, d_in[7], S_LEN, DM, 8, 256, CU_TENSOR_MAP_SWIZZLE_NONE);
    map_box(enc, &my, d_out, S_LEN, 2 * DM, 8, 256, CU_TENSOR_MAP_SWIZZLE_NONE);
    CUtensorMap cq, ck, cv, co;
    map_box(enc, &cq, Wq, DM, HD, 32, 32, CU_TENSOR_MAP_SWIZZLE_64B); map_box(enc, &ck, Wk, DM, HD, 32, 32, CU_TENSOR_MAP_SWIZZLE_64B);
    map_box(enc, &cv, Wv, DM, HD, 32, 32, CU_TENSOR_MAP_SWIZZLE_64B); map_box(enc, &co, Wo, HD, DM, 32, 16, CU_TENSOR_MAP_SWIZZLE_64B);
    S4Params P = {(const bf16*)d_in[8], (const bf16*)d_in[9], (const bf16*)d_in[10], (const bf16*)d_in[11],
                  (const bf16*)d_in[12], (const bf16*)d_in[13], (const bf16*)d_in[14], (const bf16*)d_in[15]};
    int aware = 1, pdl = 1;
    cudaLaunchAttribute at[1];
    at[0].id = cudaLaunchAttributeProgrammaticStreamSerialization;
    at[0].val.programmaticStreamSerializationAllowed = 1;
    cudaLaunchConfig_t cfg = {};
    cfg.stream = cudaStreamPerThread;
    cfg.gridDim = dim3(nsm); cfg.blockDim = dim3(384); cfg.dynamicSmemBytes = G_SMEM;
    cudaLaunchKernelEx(&cfg, kv_kernel, mx, mk, mv, mem0, Wq, Wk, Wv, Wo);
    cfg.attrs = at; cfg.numAttrs = pdl;
    cfg.gridDim = dim3(96); cfg.blockDim = dim3(CH_THREADS); cfg.dynamicSmemBytes = CH_SMEM;
    cudaLaunchKernelEx(&cfg, chain_kernel, cq, ck, cv, co, Wq, Wk, Wv, Wo, aware);
    cfg.gridDim = dim3(nsm); cfg.blockDim = dim3(384); cfg.dynamicSmemBytes = G_SMEM;
    cudaLaunchKernelEx(&cfg, worker_kernel, mx, mq, mo, mout, mu, my, P);
}
```

```cpp
#include <cuda.h>
#include <cuda_runtime.h>
#include <cuda_bf16.h>
#include <stdint.h>
#include <stdio.h>
#include <string.h>

typedef __nv_bfloat16 bf16;

constexpr int S_LEN = 2048, DM = 1024, NH = 32, DH = 128, HD = 4096, NSEG = 64;
constexpr uint32_t SENT = 0xFFFFFFFFu;
constexpr int SPIN_LIMIT = 1 << 18;

__device__ __align__(1024) bf16 g_kx[S_LEN * HD];
__device__ __align__(1024) bf16 g_vx[S_LEN * HD];
__device__ __align__(1024) bf16 g_ox[S_LEN * HD];
__device__ __align__(1024) bf16 g_km[NSEG * NH * 8 * DH];
__device__ __align__(1024) bf16 g_vm[NSEG * NH * 8 * DH];
__device__ __align__(1024) char g_ring[2 << 20];
__device__ int g_kvf[96 * 16];
constexpr int C_NEXT = 0, C_CHAIN = 32, C_QA_DONE = 64, N_CTR = 96;
__device__ int g_ctr[N_CTR];

__device__ __forceinline__ uint32_t smem_u32(const void* p) { return (uint32_t)__cvta_generic_to_shared(p); }
__device__ __forceinline__ uint32_t clk() { uint32_t c; asm volatile("mov.u32 %0, %%clock;" : "=r"(c)::"memory"); return c; }
__device__ __forceinline__ uint32_t pack_bf16(float lo, float hi) {
    uint32_t r; asm("cvt.rn.bf16x2.f32 %0, %1, %2;" : "=r"(r) : "f"(hi), "f"(lo)); return r;
}
__device__ __forceinline__ uint32_t movm(uint32_t a) {
    uint32_t d; asm volatile("movmatrix.sync.aligned.m8n8.trans.b16 %0, %1;" : "=r"(d) : "r"(a)); return d;
}
__device__ __forceinline__ void mma16(float (&d)[4], const uint32_t (&a)[4], uint32_t b0, uint32_t b1) {
    asm volatile("mma.sync.aligned.m16n8k16.row.col.f32.bf16.bf16.f32 {%0,%1,%2,%3}, {%4,%5,%6,%7}, {%8,%9}, {%0,%1,%2,%3};"
        : "+f"(d[0]), "+f"(d[1]), "+f"(d[2]), "+f"(d[3]) : "r"(a[0]), "r"(a[1]), "r"(a[2]), "r"(a[3]), "r"(b0), "r"(b1));
}
__device__ __forceinline__ void mma16z(float (&d)[4], const uint32_t (&a)[4], uint32_t b0, uint32_t b1) {
    asm volatile("mma.sync.aligned.m16n8k16.row.col.f32.bf16.bf16.f32 {%0,%1,%2,%3}, {%4,%5,%6,%7}, {%8,%9}, {%10,%10,%10,%10};"
        : "=f"(d[0]), "=f"(d[1]), "=f"(d[2]), "=f"(d[3]) : "r"(a[0]), "r"(a[1]), "r"(a[2]), "r"(a[3]), "r"(b0), "r"(b1), "f"(0.f));
}
__device__ __forceinline__ void mma8z(float (&d)[4], uint32_t a0, uint32_t a1, uint32_t b0) {
    asm volatile("mma.sync.aligned.m16n8k8.row.col.f32.bf16.bf16.f32 {%0,%1,%2,%3}, {%4,%5}, {%6}, {%7,%7,%7,%7};"
        : "=f"(d[0]), "=f"(d[1]), "=f"(d[2]), "=f"(d[3]) : "r"(a0), "r"(a1), "r"(b0), "f"(0.f));
}
__device__ __forceinline__ void ldsm4t(uint32_t (&r)[4], uint32_t addr) {
    asm volatile("ldmatrix.sync.aligned.m8n8.x4.trans.shared.b16 {%0,%1,%2,%3}, [%4];"
        : "=r"(r[0]), "=r"(r[1]), "=r"(r[2]), "=r"(r[3]) : "r"(addr) : "memory");
}
__device__ __forceinline__ void ldsm4(uint32_t (&r)[4], uint32_t addr) {
    asm volatile("ldmatrix.sync.aligned.m8n8.x4.shared.b16 {%0,%1,%2,%3}, [%4];"
        : "=r"(r[0]), "=r"(r[1]), "=r"(r[2]), "=r"(r[3]) : "r"(addr) : "memory");
}
__device__ __forceinline__ float lds32(uint32_t a) {
    float v; asm volatile("ld.shared.f32 %0, [%1];" : "=f"(v) : "r"(a) : "memory"); return v;
}
__device__ __forceinline__ void st_async1(uint32_t dst, float v, uint32_t bar) {
    asm volatile("st.async.shared::cluster.mbarrier::complete_tx::bytes.f32 [%0], %1, [%2];" ::"r"(dst), "f"(v), "r"(bar) : "memory");
}
__device__ __forceinline__ void cp16(uint32_t dst, const void* src) {
    asm volatile("cp.async.cg.shared.global [%0], [%1], 16;" ::"r"(dst), "l"(src) : "memory");
}
__device__ __forceinline__ void sts128(uint32_t a, const float (&v)[4]) {
    asm volatile("st.shared.v4.f32 [%0], {%1,%2,%3,%4};" ::"r"(a), "f"(v[0]), "f"(v[1]), "f"(v[2]), "f"(v[3]) : "memory");
}
__device__ __forceinline__ float4 lds128(uint32_t a) {
    float4 v; asm volatile("ld.shared.v4.f32 {%0,%1,%2,%3}, [%4];" : "=f"(v.x), "=f"(v.y), "=f"(v.z), "=f"(v.w) : "r"(a) : "memory"); return v;
}
__device__ __forceinline__ void sts64(uint32_t a, float x, float y) {
    asm volatile("st.shared.v2.f32 [%0], {%1,%2};" ::"r"(a), "f"(x), "f"(y) : "memory");
}
__device__ __forceinline__ float2 lds64(uint32_t a) {
    float2 v; asm volatile("ld.shared.v2.f32 {%0,%1}, [%2];" : "=f"(v.x), "=f"(v.y) : "r"(a) : "memory"); return v;
}
__device__ __forceinline__ void bar_sync(int id, int n) { asm volatile("bar.sync %0, %1;" ::"r"(id), "r"(n) : "memory"); }
__device__ __forceinline__ void bar_arrive(int id, int n) { asm volatile("bar.arrive %0, %1;" ::"r"(id), "r"(n) : "memory"); }
__device__ __forceinline__ uint32_t mapa(uint32_t a, uint32_t r) {
    uint32_t o; asm("mapa.shared::cluster.u32 %0, %1, %2;" : "=r"(o) : "r"(a), "r"(r)); return o;
}
__device__ __forceinline__ void st_async4(uint32_t dst, float4 v, uint32_t bar) {
    asm volatile("st.async.shared::cluster.mbarrier::complete_tx::bytes.v4.f32 [%0], {%1,%2,%3,%4}, [%5];"
        ::"r"(dst), "f"(v.x), "f"(v.y), "f"(v.z), "f"(v.w), "r"(bar) : "memory");
}
__device__ __forceinline__ void mbar_init(uint32_t bar, int n) { asm volatile("mbarrier.init.shared.b64 [%0], %1;" ::"r"(bar), "r"(n) : "memory"); }
__device__ __forceinline__ void mbar_expect(uint32_t bar, int bytes) {
    asm volatile("mbarrier.arrive.expect_tx.shared.b64 _, [%0], %1;" ::"r"(bar), "r"(bytes) : "memory");
}
__device__ __forceinline__ void bulk_load(uint32_t dst, const void* src, int bytes, uint32_t bar) {
    asm volatile("cp.async.bulk.shared::cluster.global.mbarrier::complete_tx::bytes [%0], [%1], %2, [%3];"
        ::"r"(dst), "l"(src), "r"(bytes), "r"(bar) : "memory");
}
__device__ __forceinline__ bool mbar_try(uint32_t bar, uint32_t par) {
    uint32_t ok;
    asm volatile("{.reg .pred p; mbarrier.try_wait.parity.shared::cta.b64 p, [%1], %2; selp.u32 %0, 1, 0, p;}"
        : "=r"(ok) : "r"(bar), "r"(par) : "memory");
    return ok;
}
__device__ __forceinline__ bool mbar_test(uint32_t bar, uint32_t par) {
    uint32_t ok;
    asm volatile("{.reg .pred p; mbarrier.test_wait.parity.shared::cta.b64 p, [%1], %2; selp.u32 %0, 1, 0, p;}"
        : "=r"(ok) : "r"(bar), "r"(par) : "memory");
    return ok;
}
__device__ __forceinline__ int ld_acq(const int* p) { int v; asm volatile("ld.acquire.gpu.global.s32 %0, [%1];" : "=r"(v) : "l"(p) : "memory"); return v; }
__device__ __forceinline__ void wait_ctr(const int* p, int n) {
    for (int it = 0; it < (1 << 20) && ld_acq(p) < n; it++) __nanosleep(64);
}
__device__ __forceinline__ void mbar_wait(uint32_t bar, uint32_t par) {
    if (!mbar_try(bar, par))
        for (int it = 0; it < SPIN_LIMIT && !mbar_try(bar, par); it++) {}
}
__device__ __forceinline__ void mbar_wait_long(uint32_t bar, uint32_t par) {
    for (int it = 0; it < (1 << 24) && !mbar_try(bar, par); it++) {}
}
__device__ __forceinline__ float4 add4(float4 a, float4 b) { return make_float4(a.x + b.x, a.y + b.y, a.z + b.z, a.w + b.w); }
__device__ __forceinline__ float ex2(float x) { float y; asm("ex2.approx.ftz.f32 %0, %1;" : "=f"(y) : "f"(x)); return y; }

__device__ __forceinline__ void wgmma256(float (&d)[128], uint64_t da, uint64_t db, int acc) {
    asm volatile("{.reg .pred p; setp.ne.b32 p, %130, 0;\n"
        "wgmma.mma_async.sync.aligned.m64n256k16.f32.bf16.bf16 {"
        "%0,%1,%2,%3,%4,%5,%6,%7,%8,%9,%10,%11,%12,%13,%14,%15,"
        "%16,%17,%18,%19,%20,%21,%22,%23,%24,%25,%26,%27,%28,%29,%30,%31,"
        "%32,%33,%34,%35,%36,%37,%38,%39,%40,%41,%42,%43,%44,%45,%46,%47,"
        "%48,%49,%50,%51,%52,%53,%54,%55,%56,%57,%58,%59,%60,%61,%62,%63,"
        "%64,%65,%66,%67,%68,%69,%70,%71,%72,%73,%74,%75,%76,%77,%78,%79,"
        "%80,%81,%82,%83,%84,%85,%86,%87,%88,%89,%90,%91,%92,%93,%94,%95,"
        "%96,%97,%98,%99,%100,%101,%102,%103,%104,%105,%106,%107,%108,%109,%110,%111,"
        "%112,%113,%114,%115,%116,%117,%118,%119,%120,%121,%122,%123,%124,%125,%126,%127"
        "}, %128, %129, p, 1, 1, 0, 1;}"
        : "+f"(d[0]), "+f"(d[1]), "+f"(d[2]), "+f"(d[3]), "+f"(d[4]), "+f"(d[5]), "+f"(d[6]), "+f"(d[7]), "+f"(d[8]), "+f"(d[9]), "+f"(d[10]), "+f"(d[11]), "+f"(d[12]), "+f"(d[13]), "+f"(d[14]), "+f"(d[15]), "+f"(d[16]), "+f"(d[17]), "+f"(d[18]), "+f"(d[19]), "+f"(d[20]), "+f"(d[21]), "+f"(d[22]), "+f"(d[23]), "+f"(d[24]), "+f"(d[25]), "+f"(d[26]), "+f"(d[27]), "+f"(d[28]), "+f"(d[29]), "+f"(d[30]), "+f"(d[31]), "+f"(d[32]), "+f"(d[33]), "+f"(d[34]), "+f"(d[35]), "+f"(d[36]), "+f"(d[37]), "+f"(d[38]), "+f"(d[39]), "+f"(d[40]), "+f"(d[41]), "+f"(d[42]), "+f"(d[43]), "+f"(d[44]), "+f"(d[45]), "+f"(d[46]), "+f"(d[47]), "+f"(d[48]), "+f"(d[49]), "+f"(d[50]), "+f"(d[51]), "+f"(d[52]), "+f"(d[53]), "+f"(d[54]), "+f"(d[55]), "+f"(d[56]), "+f"(d[57]), "+f"(d[58]), "+f"(d[59]), "+f"(d[60]), "+f"(d[61]), "+f"(d[62]), "+f"(d[63]), "+f"(d[64]), "+f"(d[65]), "+f"(d[66]), "+f"(d[67]), "+f"(d[68]), "+f"(d[69]), "+f"(d[70]), "+f"(d[71]), "+f"(d[72]), "+f"(d[73]), "+f"(d[74]), "+f"(d[75]), "+f"(d[76]), "+f"(d[77]), "+f"(d[78]), "+f"(d[79]), "+f"(d[80]), "+f"(d[81]), "+f"(d[82]), "+f"(d[83]), "+f"(d[84]), "+f"(d[85]), "+f"(d[86]), "+f"(d[87]), "+f"(d[88]), "+f"(d[89]), "+f"(d[90]), "+f"(d[91]), "+f"(d[92]), "+f"(d[93]), "+f"(d[94]), "+f"(d[95]), "+f"(d[96]), "+f"(d[97]), "+f"(d[98]), "+f"(d[99]), "+f"(d[100]), "+f"(d[101]), "+f"(d[102]), "+f"(d[103]), "+f"(d[104]), "+f"(d[105]), "+f"(d[106]), "+f"(d[107]), "+f"(d[108]), "+f"(d[109]), "+f"(d[110]), "+f"(d[111]), "+f"(d[112]), "+f"(d[113]), "+f"(d[114]), "+f"(d[115]), "+f"(d[116]), "+f"(d[117]), "+f"(d[118]), "+f"(d[119]), "+f"(d[120]), "+f"(d[121]), "+f"(d[122]), "+f"(d[123]), "+f"(d[124]), "+f"(d[125]), "+f"(d[126]), "+f"(d[127])
        : "l"(da), "l"(db), "r"(acc));
}
__device__ __forceinline__ void wgmma128(float (&d)[64], uint64_t da, uint64_t db, int acc) {
    asm volatile("{.reg .pred p; setp.ne.b32 p, %66, 0;\n"
        "wgmma.mma_async.sync.aligned.m64n128k16.f32.bf16.bf16 {"
        "%0,%1,%2,%3,%4,%5,%6,%7,%8,%9,%10,%11,%12,%13,%14,%15,"
        "%16,%17,%18,%19,%20,%21,%22,%23,%24,%25,%26,%27,%28,%29,%30,%31,"
        "%32,%33,%34,%35,%36,%37,%38,%39,%40,%41,%42,%43,%44,%45,%46,%47,"
        "%48,%49,%50,%51,%52,%53,%54,%55,%56,%57,%58,%59,%60,%61,%62,%63"
        "}, %64, %65, p, 1, 1, 0, 1;}"
        : "+f"(d[0]), "+f"(d[1]), "+f"(d[2]), "+f"(d[3]), "+f"(d[4]), "+f"(d[5]), "+f"(d[6]), "+f"(d[7]), "+f"(d[8]), "+f"(d[9]), "+f"(d[10]), "+f"(d[11]), "+f"(d[12]), "+f"(d[13]), "+f"(d[14]), "+f"(d[15]), "+f"(d[16]), "+f"(d[17]), "+f"(d[18]), "+f"(d[19]), "+f"(d[20]), "+f"(d[21]), "+f"(d[22]), "+f"(d[23]), "+f"(d[24]), "+f"(d[25]), "+f"(d[26]), "+f"(d[27]), "+f"(d[28]), "+f"(d[29]), "+f"(d[30]), "+f"(d[31]), "+f"(d[32]), "+f"(d[33]), "+f"(d[34]), "+f"(d[35]), "+f"(d[36]), "+f"(d[37]), "+f"(d[38]), "+f"(d[39]), "+f"(d[40]), "+f"(d[41]), "+f"(d[42]), "+f"(d[43]), "+f"(d[44]), "+f"(d[45]), "+f"(d[46]), "+f"(d[47]), "+f"(d[48]), "+f"(d[49]), "+f"(d[50]), "+f"(d[51]), "+f"(d[52]), "+f"(d[53]), "+f"(d[54]), "+f"(d[55]), "+f"(d[56]), "+f"(d[57]), "+f"(d[58]), "+f"(d[59]), "+f"(d[60]), "+f"(d[61]), "+f"(d[62]), "+f"(d[63])
        : "l"(da), "l"(db), "r"(acc));
}
__device__ __forceinline__ void wg_fence() { asm volatile("wgmma.fence.sync.aligned;" ::: "memory"); }
__device__ __forceinline__ void wg_commit() { asm volatile("wgmma.commit_group.sync.aligned;" ::: "memory"); }
template <int N> __device__ __forceinline__ void wg_wait() { asm volatile("wgmma.wait_group.sync.aligned %0;" ::"n"(N) : "memory"); }
__device__ __forceinline__ uint64_t mkdesc(uint32_t addr, uint32_t lbo, uint32_t sbo, uint32_t sw) {
    return (uint64_t)((addr & 0x3FFFF) >> 4) | ((uint64_t)(lbo >> 4) << 16) | ((uint64_t)(sbo >> 4) << 32) | ((uint64_t)sw << 62);
}
__device__ __forceinline__ void tma2d(uint32_t dst, const CUtensorMap* m, int c0, int c1, uint32_t bar) {
    asm volatile("cp.async.bulk.tensor.2d.shared::cluster.global.mbarrier::complete_tx::bytes [%0], [%1, {%2, %3}], [%4];"
        ::"r"(dst), "l"(m), "r"(c0), "r"(c1), "r"(bar) : "memory");
}
__device__ __forceinline__ void tma3d(uint32_t dst, const CUtensorMap* m, int c0, int c1, int c2, uint32_t bar) {
    asm volatile("cp.async.bulk.tensor.3d.shared::cluster.global.mbarrier::complete_tx::bytes [%0], [%1, {%2, %3, %4}], [%5];"
        ::"r"(dst), "l"(m), "r"(c0), "r"(c1), "r"(c2), "r"(bar) : "memory");
}
__device__ __forceinline__ void tma3d_mc(uint32_t dst, const CUtensorMap* m, int c0, int c1, int c2, uint32_t bar, uint16_t mask) {
    asm volatile("cp.async.bulk.tensor.3d.shared::cluster.global.mbarrier::complete_tx::bytes.multicast::cluster [%0], [%1, {%2, %3, %4}], [%5], %6;"
        ::"r"(dst), "l"(m), "r"(c0), "r"(c1), "r"(c2), "r"(bar), "h"(mask) : "memory");
}
__device__ __forceinline__ void mbar_arrive(uint32_t bar) { asm volatile("mbarrier.arrive.shared.b64 _, [%0];" ::"r"(bar) : "memory"); }
__device__ __forceinline__ void mbar_arrive_remote(uint32_t bar) {
    asm volatile("mbarrier.arrive.shared::cluster.b64 _, [%0];" ::"r"(bar) : "memory");
}
template <int R> __device__ __forceinline__ void reg_inc() { asm volatile("setmaxnreg.inc.sync.aligned.u32 %0;" ::"n"(R)); }
template <int R> __device__ __forceinline__ void reg_dec() { asm volatile("setmaxnreg.dec.sync.aligned.u32 %0;" ::"n"(R)); }

constexpr int CH_NRES = 50;
constexpr int CH_WREG = CH_NRES * 512;
constexpr int CH_PART = 8 * CH_WREG;
constexpr int CH_SX = CH_PART + 16384;
constexpr int CH_MX = CH_SX + 3 * 1280;
constexpr int CH_XS = CH_MX + 3 * 512;
constexpr int CH_BAR = CH_XS + 5632;
constexpr int CH_SMEM = CH_BAR + 192;
constexpr int CH_THREADS = 384;

__device__ __forceinline__ char* ring_base() { return (char*)(((uintptr_t)g_ring + (1 << 20) - 1) & ~(uintptr_t)((1 << 20) - 1)); }
__device__ __forceinline__ uint32_t ring_off(int chunk, int side) {
    uint32_t o = ((chunk & 1) << 13) | ((chunk >> 1) << 16);
    uint32_t par = ((o >> 13) ^ (o >> 16) ^ (o >> 17) ^ (o >> 19) ^ side) & 1;
    return o | (par << 12);
}
__device__ __forceinline__ uint2 ld_poll(const char* p) {
    unsigned long long v; asm volatile("ld.relaxed.gpu.global.b64 %0, [%1];" : "=l"(v) : "l"(p) : "memory");
    return make_uint2((uint32_t)v, (uint32_t)(v >> 32));
}
__device__ __forceinline__ void st_pub(char* p, uint32_t x, uint32_t y) {
    unsigned long long v = ((unsigned long long)y << 32) | x;
    asm volatile("st.relaxed.gpu.global.b64 [%0], %1;" ::"l"(p), "l"(v) : "memory");
}
template <int N>
__device__ __forceinline__ void poll_issue(uint2 (&b)[N], const char* p, bool lastvalid) {
#pragma unroll
    for (int i = 0; i < N; i++) {
        if (i < N - 1 || lastvalid) b[i] = ld_poll(p + i * 256);
        else b[i] = make_uint2(0, 0);
    }
}
template <int N>
__device__ __forceinline__ int poll_check(uint2 (&b)[N], const char* p) {
    int it = 0;
    uint32_t mx = b[0].x;
#pragma unroll
    for (int i = 1; i < N; i++) mx = max(mx, b[i].x);
    if (__any_sync(0xffffffffu, mx == SENT)) {
        while (it++ < SPIN_LIMIT) {
#pragma unroll
            for (int i = 0; i < N; i++)
                if (b[i].x == SENT) b[i] = ld_poll(p + i * 256);
            mx = b[0].x;
#pragma unroll
            for (int i = 1; i < N; i++) mx = max(mx, b[i].x);
            if (!__any_sync(0xffffffffu, mx == SENT)) break;
        }
    }
    return it;
}
template <int N>
__device__ __forceinline__ uint32_t delay(uint32_t a) {
    uint32_t z = 0;
#pragma unroll
    for (int i = 0; i < N; i++) asm volatile("ld.volatile.shared.u32 %0, [%1];" : "=r"(z) : "r"(a + z) : "memory");
    return z;
}

template <bool B> struct BoolC { static constexpr bool value = B; };
#define PFKV 0
#define LDW 2500
#define DLM 2
#define DLO 2
constexpr int OB = 0;
template <int PACE>
__device__ __forceinline__ void preload(uint32_t (&sw)[12][4], uint32_t a, uint32_t zero) {
    uint32_t z = 0;
#pragma unroll
    for (int i = 0; i < 12; i++) {
        if (PACE && i % (PACE ? PACE : 1) == 0) z = delay<1>(zero + z);
        ldsm4t(sw[i], a + z + i * 512);
    }
}
__device__ __forceinline__ void stsm4(uint32_t addr, uint32_t a, uint32_t b, uint32_t c, uint32_t d) {
    asm volatile("stmatrix.sync.aligned.m8n8.x4.shared.b16 [%0], {%1,%2,%3,%4};" ::"r"(addr), "r"(a), "r"(b), "r"(c), "r"(d) : "memory");
}
__device__ __forceinline__ void stsm4t(uint32_t addr, uint32_t a, uint32_t b, uint32_t c, uint32_t d) {
    asm volatile("stmatrix.sync.aligned.m8n8.x4.trans.shared.b16 [%0], {%1,%2,%3,%4};" ::"r"(addr), "r"(a), "r"(b), "r"(c), "r"(d) : "memory");
}
__device__ __forceinline__ void st_part(uint32_t addr, const float (&x)[4], const float (&y)[4]) {
    stsm4(addr, pack_bf16(x[0], x[1]), pack_bf16(x[2], x[3]), pack_bf16(y[0], y[1]), pack_bf16(y[2], y[3]));
}
template <bool TR>
__device__ __forceinline__ void red_part(uint32_t& lo, uint32_t& hi, uint32_t addr, uint32_t eye) {
    uint32_t a[4][4];
#pragma unroll
    for (int j = 0; j < 4; j++) { if (TR) ldsm4t(a[j], addr + j * 512); else ldsm4(a[j], addr + j * 512); }
    float r0[4], r1[4];
    mma16z(r0, a[0], eye, eye); mma16z(r1, a[1], eye, eye);
    mma16(r0, a[2], eye, eye); mma16(r1, a[3], eye, eye);
    lo = pack_bf16(r0[0] + r1[0], r0[1] + r1[1]); hi = pack_bf16(r0[2] + r1[2], r0[3] + r1[3]);
}
__device__ __forceinline__ int o_chunk(int ks, int& pos) {
    const int cw = ks < 176 ? ks / 11 : 16 + (ks - 176) / 10;
    pos = ks - (cw < 16 ? 11 * cw : 176 + 10 * (cw - 16));
    return cw;
}

template <bool PV>
__device__ __forceinline__ void chain_loop(const uint32_t (&wa)[36][4], const uint32_t sb, const int w, const int lane, const int rank,
                                           const int h, const int side) {
    const int nq = rank == 0 ? 6 : 5, u0 = rank == 0 ? 0 : 1 + 5 * rank, v0 = rank == 0 ? -6 : 3 * rank - 6;
    const uint32_t l16 = sb + lane * 16;
    const uint32_t wl = l16 + w * CH_WREG;
    const uint32_t pw = sb + CH_PART + w * 256 + (lane >> 4) * 2048 + (lane & 15) * 16;
    const uint32_t pl = l16 + CH_PART + w * 2048;
    const uint32_t barS = sb + CH_BAR, barM = barS + 8, zero = barS + 24;
    const uint32_t eye = ((lane >> 2) == 2 * (lane & 3)) ? 0x3F80u : ((lane >> 2) == 2 * (lane & 3) + 1) ? 0x3F800000u : 0u;
    char* const ring = ring_base() + lane * 8;
    const uint32_t m_rd = ring_off(24 + w, side), o_rd = ring_off(rank * 8 + w, side);
    uint32_t pub;
    if (PV) { int pos, cw = o_chunk(h * 8 + v0 + w, pos); pub = (ring_off(cw, 0) & ~4096u) + pos * 256; }
    else pub = (ring_off(24 + (h >> 2), 0) & ~4096u) + ((2 * h + w) & 7) * 256;
    const uint32_t xs = l16 + CH_XS + (PV ? nq * 512 + (w - nq) * 1024 : w * 512);
    char* const kvo = (char*)(PV ? g_vm + 128 * (v0 + w) : g_km + 64 * (u0 + w)) + h * 2048;
    const bool mown = !PV && w == rank && rank < 2;
    uint32_t sw[12][4];
#pragma unroll
    for (int i = 0; i < 12; i++) ldsm4t(sw[i], wl + i * 512);

    auto step = [&](const int s, auto lastc) {
        constexpr bool last = decltype(lastc)::value;
        const uint32_t slot = (s & 3) << 14;
        uint2 b[8];
        poll_issue<8>(b, ring + (m_rd + slot + delay<DLM>(zero)), true);
        poll_check<8>(b, ring + (m_rd + slot));
        if (OB && !last) bar_arrive(8, 288);
        {
            float acc[6][4];
#pragma unroll
            for (int kk = 0; kk < 8; kk++) {
                const int j = (2 * kk) % 12;
                if (kk == 0) { mma16z(acc[5], sw[0], b[0].x, b[0].y); mma16z(acc[4], sw[1], b[0].x, b[0].y); }
                else { mma16(acc[5], sw[j], b[kk].x, b[kk].y); mma16(acc[4], sw[j + 1], b[kk].x, b[kk].y); }
#pragma unroll
                for (int i = 0; i < 4; i++) {
                    if (kk == 0) mma16z(acc[i], wa[i * 8], b[0].x, b[0].y);
                    else mma16(acc[i], wa[i * 8 + kk], b[kk].x, b[kk].y);
                    if (i < 2) ldsm4t(sw[j + i], wl + (12 + 2 * kk + i) * 512);
                }
            }
            st_part(pw + 4 * 2048, acc[4], acc[5]);
            st_part(pw, acc[0], acc[1]);
            st_part(pw + 2 * 2048, acc[2], acc[3]);
        }
        uint32_t kv0, kv1;
        if (!PV) {
            uint32_t xf[4];
            ldsm4(xf, xs);
            bar_sync(1, last ? 256 : 256 + OB);
            red_part<true>(kv1, kv0, pl, eye);
            if (!last) {
                float s0[4], s1[4], s2[4], s3[4], s4[4];
                mma8z(s0, kv1, 0, xf[0]); mma8z(s1, kv1, 0, xf[1]); mma8z(s2, kv1, 0, xf[2]); mma8z(s3, kv1, 0, xf[3]);
                mma8z(s4, kv1, 0, kv0);
                const float x0[4] = {s0[0], s0[1], s1[0], s1[1]}, x1[4] = {s2[0], s2[1], s3[0], s3[1]};
                sts128(pl, x0); sts128(pl + 512, x1);
                sts64(pl + 1024 - lane * 8, s4[0], s4[1]);
                bar_arrive(2, nq * 32 + 64 + OB);
            }
        } else {
            bar_sync(1, last ? 256 : 256 + OB);
        }
        {
            float va[4][4];
            const float z = __uint_as_float(delay<1>(zero));
#pragma unroll
            for (int i = 0; i < 4; i++) va[i][0] = va[i][1] = va[i][2] = va[i][3] = z;
#pragma unroll
            for (int kk = 0; kk < 8; kk++) {
                if (kk < 2) { mma16(va[kk & 1], wa[32 + 2 * kk], b[kk].x, b[kk].y); mma16(va[2 + (kk & 1)], wa[33 + 2 * kk], b[kk].x, b[kk].y); }
                else { mma16(va[kk & 1], sw[(2 * kk) % 12], b[kk].x, b[kk].y); mma16(va[2 + (kk & 1)], sw[(2 * kk + 1) % 12], b[kk].x, b[kk].y); }
            }
#pragma unroll
            for (int j = 0; j < 4; j++) { va[0][j] += va[1][j]; va[2][j] += va[3][j]; }
            st_part(pw + 6 * 2048, va[0], va[2]);
        }
        if (PV) {
            uint32_t vt0[4], vt1[4];
            ldsm4t(vt0, xs); ldsm4t(vt1, xs + 512);
            if (w >= 6 && !last) {
                const uint32_t sa = l16 + CH_PART + (w - 6) * 512, sc = sb + CH_PART + 1024 + (w - 6) * 128 + lane * 4;
                const uint32_t da = l16 + CH_SX + rank * 1280 + (w - 6) * 512, dc = sb + CH_SX + rank * 1280 + 1024 + (w - 6) * 128 + lane * 4;
                bar_sync(2, nq * 32 + 64 + OB);
                float4 v[6]; float c[6];
#pragma unroll
                for (int i = 0; i < 6; i++) v[i] = (i < 5 || rank == 0) ? lds128(sa + i * 2048) : make_float4(0, 0, 0, 0);
#pragma unroll
                for (int i = 0; i < 6; i++) c[i] = (i < 5 || rank == 0) ? lds32(sc + i * 2048) : 0.f;
                float4 sv = add4(add4(add4(v[0], v[1]), add4(v[2], v[3])), add4(v[4], v[5]));
                float cv = ((c[0] + c[1]) + (c[2] + c[3])) + (c[4] + c[5]);
#pragma unroll
                for (int d = 1; d < 4; d++) {
                    const int dr = rank + d - (rank + d > 2 ? 3 : 0);
                    st_async4(mapa(da, dr), sv, mapa(barS, dr)); st_async1(mapa(dc, dr), cv, mapa(barS, dr));
                }
            }
            bar_sync(3, last ? 256 : 288 + OB);
            red_part<false>(kv0, kv1, pl, eye);
            if (!last) {
                mbar_wait(barS, s & 1);
                const uint32_t sx = l16 + CH_SX;
                float4 a0 = lds128(sx), a1 = lds128(sx + 1280), a2 = lds128(sx + 2560);
                float4 b0 = lds128(sx + 512), b1 = lds128(sx + 512 + 1280), b2 = lds128(sx + 512 + 2560);
                float2 c0 = lds64(sx + 1024 - lane * 8), c1 = lds64(sx + 1024 + 1280 - lane * 8), c2 = lds64(sx + 1024 + 2560 - lane * 8);
                a0 = add4(add4(a0, a1), a2); b0 = add4(add4(b0, b1), b2);
                float sc[10] = {a0.x, a0.y, a0.z, a0.w, b0.x, b0.y, b0.z, b0.w, c0.x + c1.x + c2.x, c0.y + c1.y + c2.y};
                float mx = fmaxf(fmaxf(fmaxf(sc[0], sc[1]), fmaxf(sc[2], sc[3])), fmaxf(fmaxf(sc[4], sc[5]), fmaxf(sc[6], sc[7])));
                mx = fmaxf(mx, fmaxf(sc[8], sc[9]));
                mx = fmaxf(fmaxf(mx, __shfl_xor_sync(0xffffffffu, mx, 1)),
                           fmaxf(__shfl_xor_sync(0xffffffffu, mx, 2), __shfl_xor_sync(0xffffffffu, mx, 3)));
                const float cs = 0.08838834764831845f * 1.4426950408889634f;
                const float mb = -mx * cs;
#pragma unroll
                for (int j = 0; j < 10; j++) sc[j] = ex2(fmaf(sc[j], cs, mb));
                uint32_t pf[5];
#pragma unroll
                for (int j = 0; j < 5; j++) pf[j] = pack_bf16(sc[2 * j], sc[2 * j + 1]);
                float o0[4], o1[4], o2[4], o3[4], o4[4], o5[4];
                const uint32_t p0[4] = {pf[0], 0, pf[1], 0}, p1[4] = {pf[2], 0, pf[3], 0};
                mma16z(o0, p0, vt0[0], vt0[1]); mma16z(o1, p0, vt1[0], vt1[1]);
                mma16z(o2, p1, vt0[2], vt0[3]); mma16z(o3, p1, vt1[2], vt1[3]);
                mma8z(o4, pf[4], 0, kv0); mma8z(o5, pf[4], 0, kv1);
                float sum = (((sc[0] + sc[1]) + (sc[2] + sc[3])) + ((sc[4] + sc[5]) + (sc[6] + sc[7]))) + (sc[8] + sc[9]);
                sum = (sum + __shfl_xor_sync(0xffffffffu, sum, 1)) + (__shfl_xor_sync(0xffffffffu, sum, 2) + __shfl_xor_sync(0xffffffffu, sum, 3));
                float inv; asm("rcp.approx.ftz.f32 %0, %1;" : "=f"(inv) : "f"(sum));
                const uint32_t ox = pack_bf16((o0[0] + o2[0] + o4[0]) * inv, (o0[1] + o2[1] + o4[1]) * inv);
                const uint32_t oy = pack_bf16((o1[0] + o3[0] + o5[0]) * inv, (o1[1] + o3[1] + o5[1]) * inv);
                st_pub(ring + (pub + slot), ox, oy); st_pub(ring + (pub + slot) + 4096, ox, oy);
                if (OB) bar_arrive(10, (9 - nq) * 32);
                preload<0>(sw, wl + 28 * 512, zero);
            }
            kv0 = movm(kv0); kv1 = movm(kv1);
        } else {
            *(uint32_t*)(kvo + (uint32_t)(s * (NH * 2048) + lane * 4)) = kv0;
            if (last) bar_arrive(3, 256);
            else {
                bar_sync(3, 288 + OB);
                preload<1>(sw, wl + 28 * 512, zero);
            }
        }
        uint2 c[11];
        if (!last) {
            bar_sync(4, 256 + OB);
            poll_issue<11>(c, ring + (o_rd + slot + delay<DLO>(zero)), rank < 2);
        }
        if (PV) { uint32_t* d = (uint32_t*)(kvo + (uint32_t)(s * (NH * 2048) + lane * 4)); d[0] = kv0; d[32] = kv1; }
        if (last) return;
        poll_check<11>(c, ring + (o_rd + slot));
        if (OB) bar_arrive(9, 288);
        {
            float acc[4][4];
#pragma unroll
            for (int f = 0; f < 22; f++) {
                const int kk = f >> 1, a = f & 3;
                if (f < 4) mma16z(acc[a], sw[f % 12], c[kk].x, c[kk].y);
                else mma16(acc[a], sw[f % 12], c[kk].x, c[kk].y);
                if (f + 12 < 22) ldsm4t(sw[f % 12], wl + (28 + f + 12) * 512);
            }
#pragma unroll
            for (int i = 0; i < 2; i++) {
#pragma unroll
                for (int j = 0; j < 4; j++) acc[i][j] += acc[i + 2][j];
                sts128(l16 + CH_PART + i * 4096 + w * 512, acc[i]);
            }
        }
        if (!PV && w < 2) {
            bar_sync(5, 288 + OB);
            float4 v[8];
#pragma unroll
            for (int i = 0; i < 8; i++) v[i] = lds128(l16 + CH_PART + w * 4096 + i * 512);
            float4 r = add4(add4(add4(v[0], v[1]), add4(v[2], v[3])), add4(add4(v[4], v[5]), add4(v[6], v[7])));
            if (!mown) st_async4(mapa(l16 + CH_MX + rank * 512, w), r, mapa(barM, w));
            bar_arrive(7, 256 + OB);
            if (mown) {
                mbar_wait(barM, s & 1);
                float4 x = lds128(l16 + CH_MX + (rank ^ 1) * 512), y = lds128(l16 + CH_MX + 2 * 512);
                r = add4(add4(x, r), y);
                const uint32_t mx = movm(pack_bf16(r.x, r.y)), my = movm(pack_bf16(r.z, r.w));
                const uint32_t ns = (slot + 0x4000) & 0xC000;
                st_pub(ring + (pub + ns), mx, my); st_pub(ring + (pub + ns) + 4096, mx, my);
            }
            preload<0>(sw, wl, zero);
        } else {
            bar_arrive(5, 288 + OB);
            bar_sync(7, 256 + OB);
            preload<2>(sw, wl, zero);
        }
        bar_sync(6, 320 + OB);
    };
#pragma unroll 1
    for (int s = 0; s < NSEG - 1; s++) step(s, BoolC<false>());
    step(NSEG - 1, BoolC<true>());
    bar_arrive(6, 288);
}

__device__ __forceinline__ void chain_pace(const uint32_t sb, const int lane, const int rank, const int aware) {
    const uint32_t zero = sb + CH_BAR + 24;
    if (lane == 0) {
        char* ring = ring_base();
        uint32_t* p0 = (uint32_t*)(ring + ring_off(blockIdx.x & 15, 0) + 3072 + (blockIdx.x >> 4) * 128);
        uint32_t* p1 = (uint32_t*)(ring + ring_off(blockIdx.x & 15, 1) + 3072 + (blockIdx.x >> 4) * 128);
        *p0 = 0; *p1 = 0;
        int b0 = 1 << 30, b1 = 1 << 30; uint32_t v = 0;
        for (int r = 0; r < 4 || (r < 256 && !mbar_test(sb + CH_BAR + 16, 0)); r++) {
            uint32_t t0 = clk(); v = atomicExch(p0 + (v == 500), r); uint32_t t1 = v == 777 ? clk() + 1 : clk(); b0 = min(b0, (int)(t1 - t0));
            t0 = clk(); v = atomicExch(p1 + (v == 500), r); t1 = v == 777 ? clk() + 1 : clk(); b1 = min(b1, (int)(t1 - t0));
            asm volatile("st.volatile.shared.u32 [%0], %1;" ::"r"(zero + 4), "r"(aware ? (b1 < b0) ^ (aware - 1) : 0) : "memory");
        }
    }
    __syncwarp();
#pragma unroll 1
    for (int s = 1; s < NSEG; s++) {
        bar_sync(5, 288 + OB);
        bar_arrive(6, 320 + OB + (rank == 2 ? delay<18>(zero) : 0));
    }
}
__device__ __forceinline__ char* reset_ptr(const int lane, const int rank, const int h) {
    const int nq = rank == 0 ? 6 : 5, v0 = rank == 0 ? -6 : 3 * rank - 6;
    int pos, cw = o_chunk(h * 8 + v0 + min(max(5 + (lane >> 3), nq), 7), pos);
    if (lane >= 24 && rank < 2) { cw = 24 + (h >> 2); pos = (2 * h + rank) & 7; }
    return ring_base() + ((ring_off(cw, 0) & ~4096u) + pos * 256 + (lane & 7) * 16);
}
__device__ __forceinline__ void chain_chores(const uint32_t sb, const int lane, const int rank, const int h, const bf16* __restrict__ mem0) {
    const int nq = rank == 0 ? 6 : 5, u0 = rank == 0 ? 0 : 1 + 5 * rank, v0 = rank == 0 ? -6 : 3 * rank - 6;
    const uint32_t barS = sb + CH_BAR, barM = barS + 8, barX = barS + 16;
    auto xload = [&](int s) {
        mbar_expect(barX, 8192 - nq * 512);
        bulk_load(sb + CH_XS, g_kx + (size_t)(s * NH + h) * 4096 + u0 * 256, nq * 512, barX);
        bulk_load(sb + CH_XS + nq * 512, g_vx + (size_t)(s * NH + h) * 4096 + (v0 + nq) * 512, (8 - nq) * 1024, barX);
    };
    char* const rb = reset_ptr(lane, rank, h);
    int* const kvf = g_kvf + blockIdx.x * 16;
    if (rank < 2) {
        const uint32_t* p = (const uint32_t*)(mem0 + (lane >> 2) * DM + 32 * h + 16 * rank + 2 * (lane & 3));
        char* d = ring_base() + ((ring_off(24 + (h >> 2), 0) & ~4096u) + ((2 * h + rank) & 7) * 256 + lane * 8);
        const uint32_t x = p[0] == SENT ? 0x7FFF7FFFu : p[0];
        st_pub(d, x, p[4]); st_pub(d + 4096, x, p[4]);
    }
    if (lane == 0) {
        wait_ctr(kvf, 2);
        asm volatile("fence.proxy.async;" ::: "memory");
        xload(0);
    }
#pragma unroll 1
    for (int s = 0; s < NSEG - 1; s++) {
        if (lane == 0) {
            mbar_expect(barS, 3 * 1280);
            if (rank < 2) mbar_expect(barM, 2 * 512);
        }
#pragma unroll
        for (int i = 0; i < 4; i++)
            asm volatile("st.relaxed.gpu.global.v4.u32 [%0], {%1,%1,%1,%1};" ::"l"(rb + ((((s + 2) & 3) << 14) + (i >> 1) * 4096 + (i & 1) * 128)), "r"(SENT) : "memory");
        __threadfence();
        if (lane == 0 && (s & 3) == 0 && s) atomicAdd(g_ctr + C_CHAIN + (s >> 2) - 1, 1);
        if (lane == 0 && (s & 3) == 3) { wait_ctr(kvf + (s >> 2) + 1, 2); asm volatile("fence.proxy.async;" ::: "memory"); }
        __syncwarp();
        bar_sync(3, 288 + OB);
        if (lane == 0) xload(s + 1);
        mbar_wait(barX, (s + 1) & 1);
        bar_sync(6, 320 + OB);
    }
    bar_sync(6, 288);
    __threadfence();
    if (lane == 0) atomicAdd(g_ctr + C_CHAIN + 15, 1);
}

__global__ void __cluster_dims__(3, 1, 1) __launch_bounds__(CH_THREADS, 1)
chain_kernel(const __grid_constant__ CUtensorMap mq, const __grid_constant__ CUtensorMap mk, const __grid_constant__ CUtensorMap mv,
             const __grid_constant__ CUtensorMap mo, const bf16* __restrict__ Wq, const bf16* __restrict__ Wk, const bf16* __restrict__ Wv,
             const bf16* __restrict__ mem0, int aware) {
    extern __shared__ __align__(1024) unsigned char smem[];
    const uint32_t sb = smem_u32(smem);
    const int tid = threadIdx.x, lane = tid & 31;
    const int w = __shfl_sync(0xffffffffu, tid >> 5, 0);
    int rank; asm("mov.u32 %0, %%cluster_ctarank;" : "=r"(rank));
    const int h = blockIdx.x / 3;
    if (tid == 0) {
        mbar_init(sb + CH_BAR, 1); mbar_init(sb + CH_BAR + 8, 1); mbar_init(sb + CH_BAR + 16, 1);
        for (int i = 0; i < 16; i++) mbar_init(sb + CH_BAR + 64 + i * 8, 1);
        *(int*)(smem + CH_BAR + 24) = 0; *(int*)(smem + CH_BAR + 28) = 0;
        asm volatile("fence.mbarrier_init.release.cluster;" ::: "memory");
    }
    if (w == 10 && PFKV) {
        const int e = lane * 96 + blockIdx.x;
        if (e < 2048) asm volatile("cp.async.bulk.prefetch.L2.global [%0], 8192;" ::"l"(((e & 1) ? Wv : Wk) + (size_t)(e >> 1) * HD) : "memory");
        if (PFKV > 1) __nanosleep(PFKV);
    }
    if (w == 9) {
        char* const rb = reset_ptr(lane, rank, h);
#pragma unroll
        for (int i = 0; i < 8; i++)
            asm volatile("st.relaxed.gpu.global.v4.u32 [%0], {%1,%1,%1,%1};" ::"l"(rb + (((i >> 2) << 14) + ((i >> 1) & 1) * 4096 + (i & 1) * 128)), "r"(SENT) : "memory");
        if (lane < 16) g_kvf[blockIdx.x * 16 + lane] = 0;
        if (blockIdx.x == 0)
            for (int k = lane; k < N_CTR; k += 32) g_ctr[k] = 0;
        __threadfence();
        __syncwarp();
        asm volatile("griddepcontrol.launch_dependents;" ::: "memory");
    }
    __syncthreads();
    asm volatile("barrier.cluster.arrive.relaxed.aligned;" ::: "memory");

    if (w >= 8) {
        reg_dec<24>();
        asm volatile("barrier.cluster.wait.aligned;" ::: "memory");
        if (w == 8) chain_pace(sb, lane, rank, aware);
        else if (w == 9) chain_chores(sb, lane, rank, h, mem0);
    } else {
        reg_inc<240>();
        const int nq = rank == 0 ? 6 : 5;
        const int u0 = rank == 0 ? 0 : 1 + 5 * rank;
        const int v0 = rank == 0 ? -6 : 3 * rank - 6;
        const int gw = rank * 8 + w;
        const int ks0 = gw < 16 ? 11 * gw : 176 + 10 * (gw - 16);
        const int nko = gw < 16 ? 11 : 10;
        const uint32_t wr = sb + w * CH_WREG, bar0 = sb + CH_BAR + 64 + w * 16, bar1 = bar0 + 8;
        uint32_t wa[36][4];
        const uint32_t vst = sb + CH_PART + w * 2048;
        const int cq = h * DH + 8 * u0, cv = h * DH + 16 * (v0 + 6);
        const int r8 = lane >> 2, p = lane & 3;
        const bf16* src = p >= 2 ? ((p & 1) ? Wk : Wq) + cq + 32 : rank == 0 ? ((p & 1) ? Wk : Wq) + cq + 40 : Wv + cv - 16 + 8 * p;
        src += (size_t)(128 * w + r8) * HD;
        auto cp_rows = [&](int kh) {
            cp16(wr + ((kh >> 1) * 2 + (p >> 1)) * 512 + ((kh & 1) * 2 + (p & 1)) * 128 + r8 * 16, src + (size_t)kh * 8 * HD);
        };
        if (LDW) __nanosleep(LDW);
#pragma unroll 1
        for (int i = 0; i < 9; i++) {
            const uint32_t bar = bar0 + (i & 1) * 8;
            if (i >= 2) mbar_wait(bar, ((i >> 1) - 1) & 1);
            if (lane == 0) {
                mbar_expect(bar, 2048);
                if (i < 8) tma2d(wr + 8192 + (i & 1) * 8192 + (i >> 1) * 2048, (i & 1) ? &mk : &mq, cq, 128 * w + 32 * (i >> 1), bar);
                else tma2d(vst, &mv, cv, 128 * w, bar);
            }
            if (i < 8) cp_rows(i);
        }
        const uint32_t lrow = ((lane >> 4) * 8 + (lane & 7)) * 64, lsw = (lane >> 1) & 3, lh = (lane >> 3) & 1;
        mbar_wait(bar1, 1); mbar_wait(bar0, 0);
#pragma unroll
        for (int i = 0; i < 32; i++) ldsm4t(wa[i], wr + 8192 + lh * 8192 + (i & 7) * 1024 + lrow + (((i >> 3) ^ lsw) << 4));
#pragma unroll
        for (int i = 0; i < 4; i++) ldsm4t(wa[32 + i], vst + (i >> 1) * 1024 + lrow + ((((i & 1) * 2 + lh) ^ lsw) << 4));
        asm volatile("fence.proxy.async.shared::cta;" ::"r"(wa[31][0]), "r"(wa[35][0]) : "memory");
        __syncwarp();
#pragma unroll 1
        for (int i = 9; i < 18; i++) {
            const uint32_t bar = bar0 + (i & 1) * 8;
            if (i >= 11) mbar_wait(bar, ((i >> 1) - 1) & 1);
            if (lane == 0) {
                const int j = 2 * (i - 12), nb = min(2, nko - j);
                mbar_expect(bar, i < 12 ? 2048 : nb * 1024);
                if (i < 12) tma2d(wr + 8192 + (i - 9) * 2048, &mv, cv, 128 * w + 32 * (i - 8), bar);
                else for (int e = 0; e < nb; e++) tma2d(wr + 14336 + (j + e) * 1024, &mo, 32 * h, 16 * (ks0 + j + e), bar);
            }
            if (i < 17) cp_rows(i - 1);
        }
        mbar_wait(bar0, 0); mbar_wait(bar1, 0);
#pragma unroll 1
        for (int i = 0; i < 17; i++) {
            uint32_t x[4], y[4];
            ldsm4t(x, wr + 8192 + i * 1024 + lrow + ((lh ^ lsw) << 4));
            ldsm4t(y, wr + 8192 + i * 1024 + lrow + (((2 + lh) ^ lsw) << 4));
            if (i == 16 && nko == 10) x[0] = x[1] = x[2] = x[3] = y[0] = y[1] = y[2] = y[3] = 0;
            __syncwarp();
            stsm4t(wr + 8192 + i * 1024 + lane * 16, x[0], x[1], x[2], x[3]);
            stsm4t(wr + 8192 + i * 1024 + 512 + lane * 16, y[0], y[1], y[2], y[3]);
        }
        asm volatile("cp.async.wait_all;" ::: "memory");
        asm volatile("barrier.cluster.wait.aligned;" ::: "memory");
        bar_sync(1, 256);
        mbar_wait_long(sb + CH_BAR + 16, 0);
        const int side = __shfl_sync(0xffffffffu, *(volatile int*)(smem + CH_BAR + 28), 0);
        if (w >= nq) chain_loop<true>(wa, sb, w, lane, rank, h, side);
        else chain_loop<false>(wa, sb, w, lane, rank, h, side);
    }
}

constexpr int G_STAGE = 49152, G_NST = 4;
constexpr int G_STG = G_NST * G_STAGE;
constexpr int G_BAR = G_STG + 32768;
constexpr int G_SMEM = G_BAR + 256 + 1024;

#define WLOG(e)
struct S4Params { const bf16 *Are, *Aim, *Bre, *Bim, *Cre, *Cim, *ldt, *dsk; };
constexpr int IT_QA = 0, IT_O = 1, IT_S4 = 2, IT_END = 3, IT_KV = 4;
#define O_WIDE 0
__device__ __forceinline__ void tma2d_store(const CUtensorMap* m, uint32_t src, int c0, int c1) {
    asm volatile("cp.async.bulk.tensor.2d.global.shared::cta.bulk_group [%0, {%2, %3}], [%1];" ::"l"(m), "r"(src), "r"(c0), "r"(c1) : "memory");
}
__device__ __forceinline__ void mma8(float (&d)[4], uint32_t a0, uint32_t a1, uint32_t b0) {
    asm volatile("mma.sync.aligned.m16n8k8.row.col.f32.bf16.bf16.f32 {%0,%1,%2,%3}, {%4,%5}, {%6}, {%0,%1,%2,%3};"
        : "+f"(d[0]), "+f"(d[1]), "+f"(d[2]), "+f"(d[3]) : "r"(a0), "r"(a1), "r"(b0));
}

__device__ __forceinline__ void attn_head(const uint32_t (&q)[32], uint32_t sk, uint32_t sv, uint32_t fullv, uint32_t parv, uint32_t emptyk,
                                          int wi, int lane, uint32_t* dst) {
    const int g = lane >> 2, t = lane & 3, hi = wi & 1;
    float s[5][4];
#pragma unroll
    for (int j = 0; j < 5; j++) s[j][0] = s[j][1] = s[j][2] = s[j][3] = 0.f;
#pragma unroll
    for (int k2 = 0; k2 < 4; k2++) {
        uint32_t km[4];
        ldsm4(km, sk + 8192 + k2 * 512 + lane * 16);
#pragma unroll
        for (int i = 0; i < 2; i++) {
            const int ks = 2 * k2 + i;
            const uint32_t a[4] = {q[4 * ks], q[4 * ks + 1], q[4 * ks + 2], q[4 * ks + 3]};
            uint32_t b[4];
            const uint32_t ad = sk + ks * 1024 + ((lane >> 3) & 1) * 512 + (lane >> 4) * 128 + (lane & 7) * 16;
            ldsm4(b, ad);
            mma16(s[4], a, km[2 * i], km[2 * i + 1]);
            mma16(s[0], a, b[0], b[1]); mma16(s[1], a, b[2], b[3]);
            if (hi) { ldsm4(b, ad + 256); mma16(s[2], a, b[0], b[1]); mma16(s[3], a, b[2], b[3]); }
        }
    }
    __syncwarp();
    if (lane == 0) mbar_arrive(emptyk);
    const int r0 = hi * 16 + g;
    float m0 = fmaxf(s[4][0], s[4][1]), m1 = fmaxf(s[4][2], s[4][3]);
#pragma unroll
    for (int j = 0; j < 4; j++) {
        const int c = 8 * j + 2 * t;
        if (c > r0) s[j][0] = -INFINITY;
        if (c + 1 > r0) s[j][1] = -INFINITY;
        if (c > r0 + 8) s[j][2] = -INFINITY;
        if (c + 1 > r0 + 8) s[j][3] = -INFINITY;
        m0 = fmaxf(m0, fmaxf(s[j][0], s[j][1])); m1 = fmaxf(m1, fmaxf(s[j][2], s[j][3]));
    }
    m0 = fmaxf(m0, __shfl_xor_sync(0xffffffffu, m0, 1)); m1 = fmaxf(m1, __shfl_xor_sync(0xffffffffu, m1, 1));
    m0 = fmaxf(m0, __shfl_xor_sync(0xffffffffu, m0, 2)); m1 = fmaxf(m1, __shfl_xor_sync(0xffffffffu, m1, 2));
    const float cs = 0.08838834764831845f * 1.4426950408889634f;
    m0 *= -cs; m1 *= -cs;
    float l0 = 0, l1 = 0;
#pragma unroll
    for (int j = 0; j < 5; j++) {
        s[j][0] = ex2(fmaf(s[j][0], cs, m0)); s[j][1] = ex2(fmaf(s[j][1], cs, m0));
        s[j][2] = ex2(fmaf(s[j][2], cs, m1)); s[j][3] = ex2(fmaf(s[j][3], cs, m1));
        l0 += s[j][0] + s[j][1]; l1 += s[j][2] + s[j][3];
    }
    l0 += __shfl_xor_sync(0xffffffffu, l0, 1); l1 += __shfl_xor_sync(0xffffffffu, l1, 1);
    l0 += __shfl_xor_sync(0xffffffffu, l0, 2); l1 += __shfl_xor_sync(0xffffffffu, l1, 2);
    l0 = __fdividef(1.f, l0); l1 = __fdividef(1.f, l1);
    uint32_t p[10];
#pragma unroll
    for (int j = 0; j < 5; j++) { p[2 * j] = pack_bf16(s[j][0] * l0, s[j][1] * l0); p[2 * j + 1] = pack_bf16(s[j][2] * l1, s[j][3] * l1); }
    const uint32_t p0[4] = {p[0], p[1], p[2], p[3]}, p1[4] = {p[4], p[5], p[6], p[7]};
    mbar_wait(fullv, parv);
#pragma unroll
    for (int u4 = 0; u4 < 4; u4++) {
        uint32_t vm[4];
        ldsm4t(vm, sv + 8192 + u4 * 512 + lane * 16);
#pragma unroll
        for (int i = 0; i < 4; i++) {
            const int u = 4 * u4 + i;
            uint32_t b[4];
            ldsm4t(b, sv + u * 512 + lane * 16);
            float o[4];
            mma16z(o, p0, b[0], b[1]);
            if (hi) mma16(o, p1, b[2], b[3]);
            mma8(o, p[8], p[9], vm[i]);
            dst[(u >> 3) * 4096 + (u & 7) * 32] = pack_bf16(o[0], o[1]);
            dst[(u >> 3) * 4096 + (u & 7) * 32 + 256] = pack_bf16(o[2], o[3]);
        }
    }
}

template <int BN, int NKB, bool BLOCKED_A>
__device__ __forceinline__ void mainloop(float (&acc)[BN / 2], uint32_t sb, int wgi, uint32_t full, uint32_t empty, int& it, bool elect) {
#pragma unroll
    for (int j = 0; j < BN / 2; j++) acc[j] = 0.f;
#pragma unroll 1
    for (int k4 = 0; k4 < NKB; k4 += 4) {
#pragma unroll
        for (int st = 0; st < 4; st++, it++) {
            mbar_wait(full + 8 * st, (it >> 2) & 1);
            const uint64_t da = BLOCKED_A ? mkdesc(sb + st * G_STAGE + wgi * 8192, 128, 1024, 0) : mkdesc(sb + st * G_STAGE + wgi * 8192, 16, 1024, 1);
            const uint64_t db = mkdesc(sb + st * G_STAGE + 16384, 8192, 1024, 1);
            wg_fence();
#pragma unroll
            for (int k = 0; k < 4; k++) {
                if constexpr (BN == 256) wgmma256(acc, da + k * (BLOCKED_A ? 16 : 2), db + k * 128, 1);
                else wgmma128(acc, da + k * (BLOCKED_A ? 16 : 2), db + k * 128, 1);
            }
            wg_commit();
            if (k4 | st) {
                wg_wait<1>();
                if (elect) mbar_arrive(empty + 8 * ((st + 3) & 3));
            }
        }
    }
    wg_wait<0>();
    if (elect) mbar_arrive(empty + 8 * 3);
}

template <int BN>
__device__ __forceinline__ void o_item(uint32_t sb, int wgi, int wi, int lane, uint32_t full, uint32_t empty, int& it, const CUtensorMap* mout,
                                       int row0, int col0) {
    float acc[BN / 2];
    mainloop<BN, 64, true>(acc, sb, wgi, full, empty, it, lane == 0);
    const uint32_t stg = sb + G_STG + (wgi * 4 + wi) * 4096;
    const int r = lane & 15, cu = lane >> 4;
#pragma unroll
    for (int hf = 0; hf < BN / 128; hf++) {
        if (lane == 0) asm volatile("cp.async.bulk.wait_group.read 0;" ::: "memory");
        __syncwarp();
#pragma unroll
        for (int j = 0; j < 8; j++) {
            const float* a = acc + hf * 64 + j * 8;
            stsm4(stg + (j >> 2) * 2048 + r * 128 + ((((j & 3) * 2 + cu) ^ (r & 7)) << 4),
                  pack_bf16(a[0], a[1]), pack_bf16(a[2], a[3]), pack_bf16(a[4], a[5]), pack_bf16(a[6], a[7]));
        }
        asm volatile("fence.proxy.async.shared::cta;" ::: "memory");
        __syncwarp();
        if (lane == 0) {
            tma2d_store(mout, stg, col0 + hf * 128, row0 + wgi * 64 + wi * 16);
            tma2d_store(mout, stg + 2048, col0 + hf * 128 + 64, row0 + wgi * 64 + wi * 16);
            asm volatile("cp.async.bulk.commit_group;" ::: "memory");
        }
    }
}

constexpr int S4_RAW = G_STG;
constexpr int S4_CH = 0;
constexpr int S4_UT = 0;
constexpr int S4_WD = 5120;
constexpr int S4_STRIDE = 5120 + 8320 + 16;

__device__ __forceinline__ float2 cmul(float2 a, float2 b) { return make_float2(a.x * b.x - a.y * b.y, a.x * b.y + a.y * b.x); }
__device__ __forceinline__ float2 csq(float2 a) { return make_float2(a.x * a.x - a.y * a.y, (a.x + a.x) * a.y); }
__device__ __forceinline__ float2 cexp_t(float lr, float turns) {
    float f = (turns - rintf(turns)) * 6.283185307179586f, e = ex2(lr);
    return make_float2(e * __cosf(f), e * __sinf(f));
}
__device__ __forceinline__ void s4_lda(uint32_t (&a)[4], uint32_t ad) {
    asm volatile("ld.shared.u32 %0, [%4]; ld.shared.u32 %1, [%4+32]; ld.shared.u32 %2, [%4+-32]; ld.volatile.shared.u32 %3, [%4];"
        : "=r"(a[0]), "=r"(a[1]), "=r"(a[2]), "=r"(a[3]) : "r"(ad) : "memory");
}
template <int H0>
__device__ __forceinline__ void s4_conv_step(float (&acc)[16][4], const uint32_t (&bw)[4][2][4], uint32_t (&nw)[4][2][4], uint32_t (&a)[2][4],
                                             uint32_t ut, uint32_t wd) {
#pragma unroll
    for (int h = H0; h < 4; h++) { ldsm4(nw[h][1], ut + (8 * h - 1) * 16 + 2560); ldsm4(nw[h][0], ut + (8 * h - 1) * 16); }
#pragma unroll
    for (int i = 0; i < 4; i++) {
        s4_lda(a[(i + 1) & 1], wd + (i + 1) * 64);
#pragma unroll
        for (int tau = 3; tau >= 0; tau--)
#pragma unroll
            for (int h = H0; h < 4; h++) {
                const int r = (tau - i) & 3;
                if (tau >= i) mma16(acc[4 * h + tau], a[i & 1], bw[h][r >> 1][2 * (r & 1)], bw[h][r >> 1][2 * (r & 1) + 1]);
                else mma16(acc[4 * h + tau], a[i & 1], nw[h][r >> 1][2 * (r & 1)], nw[h][r >> 1][2 * (r & 1) + 1]);
            }
    }
}
template <int H0>
__device__ __forceinline__ void s4_conv_phase(float (&acc)[16][4], uint32_t (&bw)[4][2][4], uint32_t (&a)[2][4], uint32_t ut, uint32_t wd) {
#pragma unroll 1
    for (int E = 8 * H0; E < 8 * H0 + 8; E += 2) {
        uint32_t nw[4][2][4];
        s4_conv_step<H0>(acc, bw, nw, a, ut - E * 16, wd + E * 256);
        s4_conv_step<H0>(acc, nw, bw, a, ut - E * 16 - 16, wd + E * 256 + 256);
    }
}

__device__ __forceinline__ void s4_item(uint32_t sb, int cw, int lane, int item, const S4Params& P, uint32_t ubar, uint32_t par, const CUtensorMap* mu,
                                        const CUtensorMap* my) {
    const int g = lane >> 2, t = lane & 3, d = item * 8 + cw;
    const uint32_t ch = sb + S4_CH + cw * S4_STRIDE;
    if (lane == 0) {
        asm volatile("cp.async.bulk.wait_group.read 0;" ::: "memory");
        mbar_expect(ubar, 4096);
        tma2d(sb + S4_RAW + cw * 4096, mu, item * 8, cw * 256, ubar);
    }
    const float dt = __bfloat162float(__float2bfloat16(expf(__bfloat162float(P.ldt[d]))));
#pragma unroll
    for (int i = 0; i < 4; i++) {
        const int n = d * 128 + i * 32 + lane;
        const float br = dt * __bfloat162float(P.Bre[n]), bi = dt * __bfloat162float(P.Bim[n]);
        const float cr = __bfloat162float(P.Cre[n]), ci = __bfloat162float(P.Cim[n]);
        const float v[4] = {dt * __bfloat162float(P.Are[n]) * 1.4426950408889634f, dt * __bfloat162float(P.Aim[n]) * 0.15915494309189535f,
                            cr * br - ci * bi, cr * bi + ci * br};
        sts128(ch + S4_WD + (i * 32 + lane) * 16, v);
    }
    __syncwarp();
    float kd[5][4], k2048 = 0.f;
#pragma unroll
    for (int j = 0; j < 5; j++) kd[j][0] = kd[j][1] = kd[j][2] = kd[j][3] = 0.f;
    const float x0 = (float)g, x1 = (float)(g + 8);
#pragma unroll 1
    for (int ks = 0; ks < 16; ks++) {
        uint32_t a[4][4], b[5][2];
#pragma unroll
        for (int i = 0; i < 2; i++) {
            const float4 p = lds128(ch + S4_WD + (ks * 8 + i * 4 + t) * 16);
            const float2 c = make_float2(p.z, p.w);
            float2 e0 = cexp_t(p.x * x0, p.y * x0), e1 = cexp_t(p.x * x1, p.y * x1);
#pragma unroll
            for (int j = 0; j < 4; j++) {
                a[j][2 * i] = pack_bf16(e0.x, e0.y); a[j][2 * i + 1] = pack_bf16(e1.x, e1.y);
                e0 = csq(e0); e1 = csq(e1);
            }
            float2 m = cmul(c, e0);
            b[0][i] = pack_bf16(m.x, -m.y);
#pragma unroll
            for (int j = 0; j < 4; j++) {
                m = cmul(c, e1);
                b[j + 1][i] = pack_bf16(m.x, -m.y);
                e1 = csq(e1);
            }
            k2048 += c.x * e1.x - c.y * e1.y;
        }
        mma16(kd[0], a[0], b[0][0], b[0][1]);
#pragma unroll
        for (int j = 0; j < 4; j++) mma16(kd[j + 1], a[j], b[j + 1][0], b[j + 1][1]);
    }
    k2048 += __shfl_xor_sync(0xffffffffu, k2048, 1);
    k2048 += __shfl_xor_sync(0xffffffffu, k2048, 2);
    {
        const uint32_t ta = ch + S4_UT + (lane & 7) * 32 + ((lane >> 3) & 1) * 16 + (lane >> 4) * 256;
        stsm4t(ta, pack_bf16(kd[0][0], kd[0][1]), pack_bf16(kd[0][2], kd[0][3]), pack_bf16(kd[1][0], kd[1][1]), pack_bf16(kd[1][2], kd[1][3]));
        stsm4t(ta + 512, pack_bf16(kd[2][0], kd[2][1]), pack_bf16(kd[2][2], kd[2][3]), pack_bf16(kd[3][0], kd[3][1]), pack_bf16(kd[3][2], kd[3][3]));
        stsm4t(ta + 1024, pack_bf16(kd[4][0], kd[4][1]), pack_bf16(kd[4][2], kd[4][3]), pack_bf16(k2048, 0.f), 0);
    }
    __syncwarp();
    if (lane < 16) asm volatile("st.shared.u32 [%0], %1;" ::"r"(ch + S4_WD + lane * 4), "r"(0) : "memory");
#pragma unroll
    for (int i = 0; i < 16; i++) {
        const int sh = i < 2 ? 0 : i < 4 ? 1 : i < 8 ? 2 : 3;
        uint32_t k[5];
#pragma unroll
        for (int j = 0; j < 5; j++) {
            const int x = i * 128 + lane * 4 + j - 1;
            int idx = sh ? 128 * sh + ((x + (1 << sh >> 1) - 1 + ((x >> sh) & 1)) >> sh) : x;
            if (i == 2 && j == 0 && lane == 0) idx = 255;
            asm volatile("ld.shared.u16 %0, [%1];" : "=r"(k[j]) : "r"(ch + S4_UT + max(idx, 0) * 2) : "memory");
        }
        if (i == 0 && lane == 0) k[0] = 0;
        asm volatile("st.shared.v4.u32 [%0], {%1,%2,%3,%4};" ::"r"(ch + S4_WD + 64 + i * 512 + lane * 16), "r"(k[1] | (k[0] << 16)),
                     "r"(k[2] | (k[1] << 16)), "r"(k[3] | (k[2] << 16)), "r"(k[4] | (k[3] << 16)) : "memory");
    }
    bar_sync(2, 256);
    if (lane < 8) {
#pragma unroll
        for (int i = 0; i < 8; i++) asm volatile("st.shared.v4.u32 [%0], {%1,%1,%1,%1};" ::"r"(ch + S4_UT + i * 640 + lane * 16), "r"(0) : "memory");
    }
    mbar_wait(ubar, par);
    const uint32_t traw = sb + S4_RAW + cw * 4096 + lane * 16;
    const uint32_t tch = sb + S4_CH + (lane & 7) * S4_STRIDE + S4_UT + (lane >> 3) * 640 + (8 + cw * 4) * 16;
#pragma unroll
    for (int i = 0; i < 8; i++) {
        uint32_t x[4];
        ldsm4t(x, traw + i * 512);
        stsm4(tch + (i & 1) * 2560 + (i >> 1) * 16, x[0], x[1], x[2], x[3]);
    }
    bar_sync(2, 256);
    float acc[16][4];
#pragma unroll
    for (int j = 0; j < 16; j++) acc[j][0] = acc[j][1] = acc[j][2] = acc[j][3] = 0.f;
    const uint32_t ut = ch + S4_UT + (lane >> 3) * 640 + (8 + (lane & 7)) * 16, wd = ch + S4_WD + 64 + (g - 2 * t) * 4;
    uint32_t bw[4][2][4], aw[2][4];
#pragma unroll
    for (int h = 0; h < 4; h++) { ldsm4(bw[h][0], ut + 8 * h * 16); ldsm4(bw[h][1], ut + 8 * h * 16 + 2560); }
    s4_lda(aw[0], wd);
    s4_conv_phase<0>(acc, bw, aw, ut, wd);
    s4_conv_phase<1>(acc, bw, aw, ut, wd);
    s4_conv_phase<2>(acc, bw, aw, ut, wd);
    if (lane == 0) mbar_arrive(ubar - 104 + 32 + 24);
    s4_conv_phase<3>(acc, bw, aw, ut, wd);
    __syncwarp();
#pragma unroll
    for (int j = 0; j < 16; j += 2)
        stsm4t(ut + (j >> 2) * 128 + (j & 2) * 1280, pack_bf16(acc[j][0], acc[j][1]), pack_bf16(acc[j][2], acc[j][3]),
               pack_bf16(acc[j + 1][0], acc[j + 1][1]), pack_bf16(acc[j + 1][2], acc[j + 1][3]));
    bar_sync(2, 256);
    const __nv_bfloat162 dk = *(const __nv_bfloat162*)(P.dsk + item * 8 + 2 * t);
#pragma unroll
    for (int i = 0; i < 8; i++) {
        uint32_t y[4], u[4];
        ldsm4t(y, tch + (i & 1) * 2560 + (i >> 1) * 16);
        ldsm4(u, traw + i * 512);
#pragma unroll
        for (int j = 0; j < 4; j++) {
            __nv_bfloat162 r = __hadd2_rn(*(__nv_bfloat162*)&y[j], __hmul2_rn(*(__nv_bfloat162*)&u[j], dk));
            y[j] = *(uint32_t*)&r;
        }
        stsm4(traw + i * 512, y[0], y[1], y[2], y[3]);
    }
    asm volatile("fence.proxy.async.shared::cta;" ::: "memory");
    __syncwarp();
    if (lane == 0) {
        tma2d_store(my, sb + S4_RAW + cw * 4096, DM + item * 8, cw * 256);
        asm volatile("cp.async.bulk.commit_group;" ::: "memory");
    }
}

__global__ void __launch_bounds__(384, 1)
worker_kernel(const __grid_constant__ CUtensorMap mx, const __grid_constant__ CUtensorMap mq, const __grid_constant__ CUtensorMap mk,
              const __grid_constant__ CUtensorMap mv, const __grid_constant__ CUtensorMap mo,
              const __grid_constant__ CUtensorMap mout, const __grid_constant__ CUtensorMap mu, const __grid_constant__ CUtensorMap my,
              const __grid_constant__ S4Params P) {
    extern __shared__ unsigned char smem_raw[];
    const uint32_t sb = (smem_u32(smem_raw) + 1023) & ~1023u;
    const uint32_t full = sb + G_BAR, empty = full + 32, ifull = full + 64, iempty = full + 80, islot = full + 96, ubar = full + 104, sigbar = full + 112, sigslot = full + 120;
    const int tid = threadIdx.x, wg = tid >> 7, lane = tid & 31;
    if (tid == 0) {
        for (int i = 0; i < G_NST; i++) { mbar_init(full + 8 * i, 1); mbar_init(empty + 8 * i, 8); }
        for (int i = 0; i < 2; i++) { mbar_init(ifull + 8 * i, 1); mbar_init(iempty + 8 * i, 8); }
        mbar_init(ubar, 8); mbar_init(sigbar, 8);
        asm volatile("fence.proxy.async;" ::: "memory");
    }
    __syncthreads();
    if (wg == 0) {
        reg_dec<40>();
        if (tid >= 32 && tid < 64) {
            for (int n = 0;; n++) {
                mbar_wait_long(sigbar, n & 1);
                int item; asm volatile("ld.shared.u32 %0, [%1];" : "=r"(item) : "r"(sigslot + 4 * (n & 1)) : "memory");
                const int type = item >> 16, b = (item >> 8) & 255, i = item & 255;
                if (type == IT_END) break;
                __threadfence();
                if (type == IT_KV) { if (lane < 6) atomicAdd(g_kvf + ((i & 15) * 6 + lane) * 16 + b, 1); }
                else if (lane == 0) atomicAdd(g_ctr + C_QA_DONE + b, 1);
            }
        } else if (tid < 32) {
            int it = 0;
            for (int n = 0;; n++) {
                int item = 0;
                if (lane == 0) {
                    const int q = (n == 0 && blockIdx.x < 32) ? blockIdx.x : 32 + atomicAdd(g_ctr + C_NEXT, 1);
                    if (q < 512) item = (IT_KV << 16) | ((q >> 5) << 8) | (q & 31);
                    else if (q < 768) item = (IT_QA << 16) | (((q - 512) >> 4) << 8) | (q & 15);
                    else if (q < 1024) {
                        const int j = (q - 768) >> 1;
                        item = (q & 1) ? (IT_S4 << 16) | j : (IT_O << 16) | ((j >> 3) << 8) | (j & 7);
                    } else item = IT_END << 16;
                }
                item = __shfl_sync(0xffffffffu, item, 0);
                if (lane == 0) {
                    mbar_wait(iempty + 8 * (n & 1), ((n >> 1) & 1) ^ 1);
                    asm volatile("st.shared.u32 [%0], %1;" ::"r"(islot + 4 * (n & 1)), "r"(item) : "memory");
                    mbar_arrive(ifull + 8 * (n & 1));
                    const int type = item >> 16, b = (item >> 8) & 255, i = item & 255;
                    if (type == IT_QA || type == IT_KV) {
                        const CUtensorMap* mw = type == IT_QA ? &mq : i < 16 ? &mk : &mv;
                        for (int kb = 0; kb < 16; kb++, it++) {
                            const int st = it & 3;
                            mbar_wait(empty + 8 * st, ((it >> 2) & 1) ^ 1);
                            mbar_expect(full + 8 * st, G_STAGE);
                            const uint32_t a = sb + st * G_STAGE;
                            tma2d(a, &mx, kb * 64, b * 128, full + 8 * st);
                            tma3d(a + 16384, mw, 0, kb * 64, (i & 15) * 4, full + 8 * st);
                            tma3d(a + 32768, mw, 0, kb * 64, (i & 15) * 4 + 2, full + 8 * st);
                            if (type == IT_QA && kb >= 4 && kb < 12)
                                asm volatile("cp.async.bulk.prefetch.L2.global [%0], 16384;"
                                    ::"l"(((kb & 1) ? g_vx : g_kx) + (size_t)((b * 4 + ((kb - 4) >> 1)) * NH + i * 2) * 4096) : "memory");
                        }
                    }
                    if (type == IT_QA) {
                        wait_ctr(g_ctr + C_CHAIN + b, 96);
                        asm volatile("fence.proxy.async;" ::: "memory");
                        for (int st = 0; st < 4; st++, it++) {
                            mbar_wait(empty + 8 * st, ((it >> 2) & 1) ^ 1);
                            mbar_expect(full + 8 * st, 4 * 10240);
                            for (int sg = 0; sg < 4; sg++) {
                                const int sh = (b * 4 + sg) * NH + i * 2 + (st >> 1);
                                bulk_load(sb + st * G_STAGE + sg * 10240, ((st & 1) ? g_vx : g_kx) + (size_t)sh * 4096, 8192, full + 8 * st);
                                bulk_load(sb + st * G_STAGE + sg * 10240 + 8192, ((st & 1) ? g_vm : g_km) + (size_t)sh * 1024, 2048, full + 8 * st);
                            }
                        }
                    } else if (type == IT_O) {
                        const bool wide = b < O_WIDE;
                        wait_ctr(g_ctr + C_QA_DONE + b, 16);
                        asm volatile("fence.proxy.async;" ::: "memory");
                        for (int kb = 0; kb < 64; kb++, it++) {
                            const int st = it & 3;
                            mbar_wait(empty + 8 * st, ((it >> 2) & 1) ^ 1);
                            mbar_expect(full + 8 * st, wide ? G_STAGE : 32768);
                            const uint32_t a = sb + st * G_STAGE;
                            bulk_load(a, g_ox + (size_t)(b * 64 + kb) * 8192, 16384, full + 8 * st);
                            tma3d(a + 16384, &mo, 0, kb * 64, wide ? i * 4 : i * 2, full + 8 * st);
                            if (wide) tma3d(a + 32768, &mo, 0, kb * 64, i * 4 + 2, full + 8 * st);
                        }
                    } else if (type == IT_S4) {
                        for (int st = 0; st < 4; st++) mbar_wait(empty + 8 * st, ((it >> 2) & 1) ^ 1);
                        for (int st = 0; st < 4; st++) mbar_arrive(full + 8 * st);
                        it += 4;
                        mbar_wait_long(empty + 24, ((it >> 2) & 1) ^ 1);
                    }
                }
                __syncwarp();
                if (item >> 16 == IT_END) break;
            }
            asm volatile("griddepcontrol.wait;" ::: "memory");
        }
    } else {
        reg_inc<232>();
        const int wgi = wg - 1, wi = (tid >> 5) & 3;
        int it = 0, ns4 = 0, nsig = 0, n = 0, item;
        auto next_item = [&]() {
            mbar_wait_long(ifull + 8 * (n & 1), (n >> 1) & 1);
            asm volatile("ld.shared.u32 %0, [%1];" : "=r"(item) : "r"(islot + 4 * (n & 1)) : "memory");
            __syncwarp();
            if (lane == 0) mbar_arrive(iempty + 8 * (n & 1));
        };
        auto signal = [&](int what) {
            if (tid == 128) asm volatile("st.shared.u32 [%0], %1;" ::"r"(sigslot + 4 * (nsig & 1)), "r"(what) : "memory");
            __syncwarp();
            if (lane == 0) mbar_arrive(sigbar);
            nsig++;
        };
        next_item();
        if (item >> 16 == IT_KV) {
            float acc[128];
            uint32_t pk[64];
            uint32_t* dst = nullptr;
            int prev = 0;
            do {
                WLOG(0);
#pragma unroll
                for (int kb = 0; kb < 16; kb++, it++) {
                    const int st = kb & 3;
                    mbar_wait(full + 8 * st, (it >> 2) & 1);
                    const uint64_t da = mkdesc(sb + st * G_STAGE + wgi * 8192, 16, 1024, 1);
                    const uint64_t db = mkdesc(sb + st * G_STAGE + 16384, 8192, 1024, 1);
                    wg_fence();
#pragma unroll
                    for (int k = 0; k < 4; k++) wgmma256(acc, da + k * 2, db + k * 128, kb | k);
                    wg_commit();
                    if (kb < 4 && dst) {
#pragma unroll
                        for (int j = 0; j < 16; j++) dst[(kb * 8 + (j >> 1)) * 128 + (j & 1) * 32] = pk[kb * 16 + j];
                        if (kb == 3) signal(prev);
                    }
                    if (kb > 0) {
                        wg_wait<1>();
                        if (lane == 0) mbar_arrive(empty + 8 * ((kb - 1) & 3));
                    }
                }
                wg_wait<0>();
                if (lane == 0) mbar_arrive(empty + 8 * 3);
#pragma unroll
                for (int j = 0; j < 64; j++) pk[j] = pack_bf16(acc[2 * j], acc[2 * j + 1]);
                const int row = ((item >> 8) & 255) * 128 + wgi * 64 + wi * 16, nt = item & 255;
                dst = (uint32_t*)(nt < 16 ? g_kx : g_vx) + (size_t)((row >> 5) * 512 + (nt & 15) * 32) * 128 + (row & 31) * 4 + lane;
                prev = item;
                if (n == 0) {
#pragma unroll
                    for (int j = 0; j < 64; j++) dst[(j >> 1) * 128 + (j & 1) * 32] = pk[j];
                    signal(prev);
                    dst = nullptr;
                }
                WLOG(1);
                n++;
                next_item();
            } while (item >> 16 == IT_KV);
            if (dst) {
#pragma unroll
                for (int j = 0; j < 64; j++) dst[(j >> 1) * 128 + (j & 1) * 32] = pk[j];
                signal(prev);
            }
        }
        for (;; n++, next_item()) {
            const int type = item >> 16, b = (item >> 8) & 255, i = item & 255;
            WLOG(0);
            if (type == IT_QA) {
                float acc[128];
                mainloop<256, 16, false>(acc, sb, wgi, full, empty, it, lane == 0);
                uint32_t q0[32], q1[32];
#pragma unroll
                for (int j = 0; j < 32; j++) { q0[j] = pack_bf16(acc[2 * j], acc[2 * j + 1]); q1[j] = pack_bf16(acc[64 + 2 * j], acc[65 + 2 * j]); }
                const uint32_t par = (it >> 2) & 1, so = (wgi * 2 + (wi >> 1)) * 10240;
                uint32_t* dst = (uint32_t*)g_ox + (size_t)(b * 64 + i * 4) * 4096 + (wgi * 8 + wi * 2) * 256 + lane;
                mbar_wait_long(full, par);
                attn_head(q0, sb + so, sb + G_STAGE + so, full + 8, par, empty, wi, lane, dst);
                __syncwarp();
                if (lane == 0) mbar_arrive(empty + 8);
                mbar_wait(full + 16, par);
                attn_head(q1, sb + 2 * G_STAGE + so, sb + 3 * G_STAGE + so, full + 24, par, empty + 16, wi, lane, dst + 2 * 4096);
                __syncwarp();
                if (lane == 0) mbar_arrive(empty + 24);
                signal(item);
                it += 4;
            } else if (type == IT_O) {
                mbar_wait_long(full, (it >> 2) & 1);
                if (b < O_WIDE) o_item<256>(sb, wgi, wi, lane, full, empty, it, &mout, b * 128, i * 256);
                else o_item<128>(sb, wgi, wi, lane, full, empty, it, &mout, b * 128, i * 128);
            } else if (type == IT_S4) {
                mbar_wait(full, (it >> 2) & 1);
                s4_item(sb, wgi * 4 + wi, lane, i, P, ubar, ns4++ & 1, &mu, &my);
                if (lane == 0) { mbar_arrive(empty); mbar_arrive(empty + 8); mbar_arrive(empty + 16); }
                it += 4;
            } else break;
            WLOG(1);
        }
        bar_sync(2, 256);
        signal(item);
        if (lane == 0) asm volatile("cp.async.bulk.wait_group 0;" ::: "memory");
    }
}

typedef CUresult (*EncodeFn)(CUtensorMap*, CUtensorMapDataType, cuuint32_t, void*, const cuuint64_t*, const cuuint64_t*, const cuuint32_t*,
                             const cuuint32_t*, CUtensorMapInterleave, CUtensorMapSwizzle, CUtensorMapL2promotion, CUtensorMapFloatOOBfill);
static EncodeFn get_encode() {
    void* fn = nullptr; cudaDriverEntryPointQueryResult st;
    cudaGetDriverEntryPoint("cuTensorMapEncodeTiled", &fn, cudaEnableDefault, &st);
    return (EncodeFn)fn;
}
static void map_act(EncodeFn enc, CUtensorMap* m, const void* p, int rows, int cols, int boxr) {
    cuuint64_t dim[2] = {(cuuint64_t)cols, (cuuint64_t)rows}, str[1] = {(cuuint64_t)cols * 2};
    cuuint32_t box[2] = {64, (cuuint32_t)boxr}, es[2] = {1, 1};
    enc(m, CU_TENSOR_MAP_DATA_TYPE_BFLOAT16, 2, (void*)p, dim, str, box, es, CU_TENSOR_MAP_INTERLEAVE_NONE, CU_TENSOR_MAP_SWIZZLE_128B,
        CU_TENSOR_MAP_L2_PROMOTION_L2_128B, CU_TENSOR_MAP_FLOAT_OOB_FILL_NONE);
}
static void map_w(EncodeFn enc, CUtensorMap* m, const void* p, int k, int n) {
    cuuint64_t dim[3] = {64, (cuuint64_t)k, (cuuint64_t)n / 64}, str[2] = {(cuuint64_t)n * 2, 128};
    cuuint32_t box[3] = {64, 64, 2}, es[3] = {1, 1, 1};
    enc(m, CU_TENSOR_MAP_DATA_TYPE_BFLOAT16, 3, (void*)p, dim, str, box, es, CU_TENSOR_MAP_INTERLEAVE_NONE, CU_TENSOR_MAP_SWIZZLE_128B,
        CU_TENSOR_MAP_L2_PROMOTION_L2_256B, CU_TENSOR_MAP_FLOAT_OOB_FILL_NONE);
}

static void map_box(EncodeFn enc, CUtensorMap* m, const void* p, int rows, int ld, int boxc, int boxr, CUtensorMapSwizzle sw) {
    cuuint64_t dim[2] = {(cuuint64_t)ld, (cuuint64_t)rows}, str[1] = {(cuuint64_t)ld * 2};
    cuuint32_t box[2] = {(cuuint32_t)boxc, (cuuint32_t)boxr}, es[2] = {1, 1};
    enc(m, CU_TENSOR_MAP_DATA_TYPE_BFLOAT16, 2, (void*)p, dim, str, box, es, CU_TENSOR_MAP_INTERLEAVE_NONE, sw,
        CU_TENSOR_MAP_L2_PROMOTION_NONE, CU_TENSOR_MAP_FLOAT_OOB_FILL_NONE);
}

extern "C" void kernel_launch(void* const* d_in, const int* in_sizes, int n_in, void* d_out, int out_size) {
    const bf16* x = (const bf16*)d_in[0];
    const bf16* mem0 = (const bf16*)d_in[1];
    const bf16 *Wq = (const bf16*)d_in[2], *Wk = (const bf16*)d_in[3], *Wv = (const bf16*)d_in[4], *Wo = (const bf16*)d_in[5];
    static EncodeFn enc = nullptr;
    static int nsm = 0;
    if (!enc) {
        enc = get_encode();
        cudaDeviceGetAttribute(&nsm, cudaDevAttrMultiProcessorCount, 0);
        cudaFuncSetAttribute(chain_kernel, cudaFuncAttributeMaxDynamicSharedMemorySize, CH_SMEM);
        cudaFuncSetAttribute(worker_kernel, cudaFuncAttributeMaxDynamicSharedMemorySize, G_SMEM);
    }
    CUtensorMap mx, mq, mk, mv, mo, mout, mu, my;
    map_act(enc, &mx, x, S_LEN, DM, 128);
    map_w(enc, &mq, Wq, DM, HD); map_w(enc, &mk, Wk, DM, HD); map_w(enc, &mv, Wv, DM, HD); map_w(enc, &mo, Wo, HD, DM);
    map_box(enc, &mout, d_out, S_LEN, 2 * DM, 64, 16, CU_TENSOR_MAP_SWIZZLE_128B);
    map_box(enc, &mu, d_in[7], S_LEN, DM, 8, 256, CU_TENSOR_MAP_SWIZZLE_NONE);
    map_box(enc, &my, d_out, S_LEN, 2 * DM, 8, 256, CU_TENSOR_MAP_SWIZZLE_NONE);
    CUtensorMap cq, ck, cv, co;
    map_box(enc, &cq, Wq, DM, HD, 32, 32, CU_TENSOR_MAP_SWIZZLE_64B); map_box(enc, &ck, Wk, DM, HD, 32, 32, CU_TENSOR_MAP_SWIZZLE_64B);
    map_box(enc, &cv, Wv, DM, HD, 32, 32, CU_TENSOR_MAP_SWIZZLE_64B); map_box(enc, &co, Wo, HD, DM, 32, 16, CU_TENSOR_MAP_SWIZZLE_64B);
    S4Params P = {(const bf16*)d_in[8], (const bf16*)d_in[9], (const bf16*)d_in[10], (const bf16*)d_in[11],
                  (const bf16*)d_in[12], (const bf16*)d_in[13], (const bf16*)d_in[14], (const bf16*)d_in[15]};
    int aware = 1;
    cudaLaunchAttribute at[1];
    at[0].id = cudaLaunchAttributeProgrammaticStreamSerialization;
    at[0].val.programmaticStreamSerializationAllowed = 1;
    cudaLaunchConfig_t cfg = {};
    cfg.stream = cudaStreamPerThread;
    cfg.gridDim = dim3(96); cfg.blockDim = dim3(CH_THREADS); cfg.dynamicSmemBytes = CH_SMEM;
    cudaLaunchKernelEx(&cfg, chain_kernel, cq, ck, cv, co, Wq, Wk, Wv, mem0, aware);
    cfg.attrs = at; cfg.numAttrs = 1;
    cfg.gridDim = dim3(nsm); cfg.blockDim = dim3(384); cfg.dynamicSmemBytes = G_SMEM;
    cudaLaunchKernelEx(&cfg, worker_kernel, mx, mq, mk, mv, mo, mout, mu, my, P);
}
```

```cpp
#include <cuda.h>
#include <cuda_runtime.h>
#include <cuda_bf16.h>
#include <stdint.h>
#include <stdio.h>
#include <string.h>

typedef __nv_bfloat16 bf16;

constexpr int S_LEN = 2048, DM = 1024, NH = 32, DH = 128, HD = 4096, NSEG = 64;
constexpr uint32_t SENT = 0xFFFFFFFFu;
constexpr int SPIN_LIMIT = 1 << 18;

__device__ __align__(1024) bf16 g_kx[S_LEN * HD];
__device__ __align__(1024) bf16 g_vx[S_LEN * HD];
__device__ __align__(1024) bf16 g_ox[S_LEN * HD];
__device__ __align__(1024) bf16 g_km[NSEG * NH * 8 * DH];
__device__ __align__(1024) bf16 g_vm[NSEG * NH * 8 * DH];
__device__ __align__(1024) bf16 g_kd[DM * 768];
__device__ __align__(1024) char g_ring[2 << 20];
__device__ int g_kvf[96 * 16];
constexpr int C_NEXT = 0, C_CHAIN = 32, C_QA_DONE = 64, N_CTR = 96;
__device__ int g_ctr[N_CTR];

__device__ __forceinline__ uint32_t smem_u32(const void* p) { return (uint32_t)__cvta_generic_to_shared(p); }
__device__ __forceinline__ uint32_t clk() { uint32_t c; asm volatile("mov.u32 %0, %%clock;" : "=r"(c)::"memory"); return c; }
__device__ __forceinline__ uint32_t pack_bf16(float lo, float hi) {
    uint32_t r; asm("cvt.rn.bf16x2.f32 %0, %1, %2;" : "=r"(r) : "f"(hi), "f"(lo)); return r;
}
__device__ __forceinline__ uint32_t movm(uint32_t a) {
    uint32_t d; asm volatile("movmatrix.sync.aligned.m8n8.trans.b16 %0, %1;" : "=r"(d) : "r"(a)); return d;
}
__device__ __forceinline__ void mma16(float (&d)[4], const uint32_t (&a)[4], uint32_t b0, uint32_t b1) {
    asm volatile("mma.sync.aligned.m16n8k16.row.col.f32.bf16.bf16.f32 {%0,%1,%2,%3}, {%4,%5,%6,%7}, {%8,%9}, {%0,%1,%2,%3};"
        : "+f"(d[0]), "+f"(d[1]), "+f"(d[2]), "+f"(d[3]) : "r"(a[0]), "r"(a[1]), "r"(a[2]), "r"(a[3]), "r"(b0), "r"(b1));
}
__device__ __forceinline__ void mma16z(float (&d)[4], const uint32_t (&a)[4], uint32_t b0, uint32_t b1) {
    asm volatile("mma.sync.aligned.m16n8k16.row.col.f32.bf16.bf16.f32 {%0,%1,%2,%3}, {%4,%5,%6,%7}, {%8,%9}, {%10,%10,%10,%10};"
        : "=f"(d[0]), "=f"(d[1]), "=f"(d[2]), "=f"(d[3]) : "r"(a[0]), "r"(a[1]), "r"(a[2]), "r"(a[3]), "r"(b0), "r"(b1), "f"(0.f));
}
__device__ __forceinline__ void mma8z(float (&d)[4], uint32_t a0, uint32_t a1, uint32_t b0) {
    asm volatile("mma.sync.aligned.m16n8k8.row.col.f32.bf16.bf16.f32 {%0,%1,%2,%3}, {%4,%5}, {%6}, {%7,%7,%7,%7};"
        : "=f"(d[0]), "=f"(d[1]), "=f"(d[2]), "=f"(d[3]) : "r"(a0), "r"(a1), "r"(b0), "f"(0.f));
}
__device__ __forceinline__ void ldsm4t(uint32_t (&r)[4], uint32_t addr) {
    asm volatile("ldmatrix.sync.aligned.m8n8.x4.trans.shared.b16 {%0,%1,%2,%3}, [%4];"
        : "=r"(r[0]), "=r"(r[1]), "=r"(r[2]), "=r"(r[3]) : "r"(addr) : "memory");
}
__device__ __forceinline__ void ldsm4(uint32_t (&r)[4], uint32_t addr) {
    asm volatile("ldmatrix.sync.aligned.m8n8.x4.shared.b16 {%0,%1,%2,%3}, [%4];"
        : "=r"(r[0]), "=r"(r[1]), "=r"(r[2]), "=r"(r[3]) : "r"(addr) : "memory");
}
__device__ __forceinline__ float lds32(uint32_t a) {
    float v; asm volatile("ld.shared.f32 %0, [%1];" : "=f"(v) : "r"(a) : "memory"); return v;
}
__device__ __forceinline__ void st_async1(uint32_t dst, float v, uint32_t bar) {
    asm volatile("st.async.shared::cluster.mbarrier::complete_tx::bytes.f32 [%0], %1, [%2];" ::"r"(dst), "f"(v), "r"(bar) : "memory");
}
__device__ __forceinline__ void cp16(uint32_t dst, const void* src) {
    asm volatile("cp.async.cg.shared.global [%0], [%1], 16;" ::"r"(dst), "l"(src) : "memory");
}
__device__ __forceinline__ void sts128(uint32_t a, const float (&v)[4]) {
    asm volatile("st.shared.v4.f32 [%0], {%1,%2,%3,%4};" ::"r"(a), "f"(v[0]), "f"(v[1]), "f"(v[2]), "f"(v[3]) : "memory");
}
__device__ __forceinline__ float4 lds128(uint32_t a) {
    float4 v; asm volatile("ld.shared.v4.f32 {%0,%1,%2,%3}, [%4];" : "=f"(v.x), "=f"(v.y), "=f"(v.z), "=f"(v.w) : "r"(a) : "memory"); return v;
}
__device__ __forceinline__ void sts64(uint32_t a, float x, float y) {
    asm volatile("st.shared.v2.f32 [%0], {%1,%2};" ::"r"(a), "f"(x), "f"(y) : "memory");
}
__device__ __forceinline__ float2 lds64(uint32_t a) {
    float2 v; asm volatile("ld.shared.v2.f32 {%0,%1}, [%2];" : "=f"(v.x), "=f"(v.y) : "r"(a) : "memory"); return v;
}
__device__ __forceinline__ void bar_sync(int id, int n) { asm volatile("bar.sync %0, %1;" ::"r"(id), "r"(n) : "memory"); }
__device__ __forceinline__ void bar_arrive(int id, int n) { asm volatile("bar.arrive %0, %1;" ::"r"(id), "r"(n) : "memory"); }
__device__ __forceinline__ uint32_t mapa(uint32_t a, uint32_t r) {
    uint32_t o; asm("mapa.shared::cluster.u32 %0, %1, %2;" : "=r"(o) : "r"(a), "r"(r)); return o;
}
__device__ __forceinline__ void st_async4(uint32_t dst, float4 v, uint32_t bar) {
    asm volatile("st.async.shared::cluster.mbarrier::complete_tx::bytes.v4.f32 [%0], {%1,%2,%3,%4}, [%5];"
        ::"r"(dst), "f"(v.x), "f"(v.y), "f"(v.z), "f"(v.w), "r"(bar) : "memory");
}
__device__ __forceinline__ void mbar_init(uint32_t bar, int n) { asm volatile("mbarrier.init.shared.b64 [%0], %1;" ::"r"(bar), "r"(n) : "memory"); }
__device__ __forceinline__ void mbar_expect(uint32_t bar, int bytes) {
    asm volatile("mbarrier.arrive.expect_tx.shared.b64 _, [%0], %1;" ::"r"(bar), "r"(bytes) : "memory");
}
__device__ __forceinline__ void bulk_load(uint32_t dst, const void* src, int bytes, uint32_t bar) {
    asm volatile("cp.async.bulk.shared::cluster.global.mbarrier::complete_tx::bytes [%0], [%1], %2, [%3];"
        ::"r"(dst), "l"(src), "r"(bytes), "r"(bar) : "memory");
}
__device__ __forceinline__ bool mbar_try(uint32_t bar, uint32_t par) {
    uint32_t ok;
    asm volatile("{.reg .pred p; mbarrier.try_wait.parity.shared::cta.b64 p, [%1], %2; selp.u32 %0, 1, 0, p;}"
        : "=r"(ok) : "r"(bar), "r"(par) : "memory");
    return ok;
}
__device__ __forceinline__ bool mbar_test(uint32_t bar, uint32_t par) {
    uint32_t ok;
    asm volatile("{.reg .pred p; mbarrier.test_wait.parity.shared::cta.b64 p, [%1], %2; selp.u32 %0, 1, 0, p;}"
        : "=r"(ok) : "r"(bar), "r"(par) : "memory");
    return ok;
}
__device__ __forceinline__ int ld_acq(const int* p) { int v; asm volatile("ld.acquire.gpu.global.s32 %0, [%1];" : "=r"(v) : "l"(p) : "memory"); return v; }
__device__ __forceinline__ void wait_ctr(const int* p, int n) {
    for (int it = 0; it < (1 << 20) && ld_acq(p) < n; it++) __nanosleep(64);
}
__device__ __forceinline__ void mbar_wait(uint32_t bar, uint32_t par) {
    if (!mbar_try(bar, par))
        for (int it = 0; it < SPIN_LIMIT && !mbar_try(bar, par); it++) {}
}
__device__ __forceinline__ void mbar_wait_long(uint32_t bar, uint32_t par) {
    for (int it = 0; it < (1 << 24) && !mbar_try(bar, par); it++) {}
}
__device__ __forceinline__ float4 add4(float4 a, float4 b) { return make_float4(a.x + b.x, a.y + b.y, a.z + b.z, a.w + b.w); }
__device__ __forceinline__ float ex2(float x) { float y; asm("ex2.approx.ftz.f32 %0, %1;" : "=f"(y) : "f"(x)); return y; }

__device__ __forceinline__ void wgmma256(float (&d)[128], uint64_t da, uint64_t db, int acc) {
    asm volatile("{.reg .pred p; setp.ne.b32 p, %130, 0;\n"
        "wgmma.mma_async.sync.aligned.m64n256k16.f32.bf16.bf16 {"
        "%0,%1,%2,%3,%4,%5,%6,%7,%8,%9,%10,%11,%12,%13,%14,%15,"
        "%16,%17,%18,%19,%20,%21,%22,%23,%24,%25,%26,%27,%28,%29,%30,%31,"
        "%32,%33,%34,%35,%36,%37,%38,%39,%40,%41,%42,%43,%44,%45,%46,%47,"
        "%48,%49,%50,%51,%52,%53,%54,%55,%56,%57,%58,%59,%60,%61,%62,%63,"
        "%64,%65,%66,%67,%68,%69,%70,%71,%72,%73,%74,%75,%76,%77,%78,%79,"
        "%80,%81,%82,%83,%84,%85,%86,%87,%88,%89,%90,%91,%92,%93,%94,%95,"
        "%96,%97,%98,%99,%100,%101,%102,%103,%104,%105,%106,%107,%108,%109,%110,%111,"
        "%112,%113,%114,%115,%116,%117,%118,%119,%120,%121,%122,%123,%124,%125,%126,%127"
        "}, %128, %129, p, 1, 1, 0, 1;}"
        : "+f"(d[0]), "+f"(d[1]), "+f"(d[2]), "+f"(d[3]), "+f"(d[4]), "+f"(d[5]), "+f"(d[6]), "+f"(d[7]), "+f"(d[8]), "+f"(d[9]), "+f"(d[10]), "+f"(d[11]), "+f"(d[12]), "+f"(d[13]), "+f"(d[14]), "+f"(d[15]), "+f"(d[16]), "+f"(d[17]), "+f"(d[18]), "+f"(d[19]), "+f"(d[20]), "+f"(d[21]), "+f"(d[22]), "+f"(d[23]), "+f"(d[24]), "+f"(d[25]), "+f"(d[26]), "+f"(d[27]), "+f"(d[28]), "+f"(d[29]), "+f"(d[30]), "+f"(d[31]), "+f"(d[32]), "+f"(d[33]), "+f"(d[34]), "+f"(d[35]), "+f"(d[36]), "+f"(d[37]), "+f"(d[38]), "+f"(d[39]), "+f"(d[40]), "+f"(d[41]), "+f"(d[42]), "+f"(d[43]), "+f"(d[44]), "+f"(d[45]), "+f"(d[46]), "+f"(d[47]), "+f"(d[48]), "+f"(d[49]), "+f"(d[50]), "+f"(d[51]), "+f"(d[52]), "+f"(d[53]), "+f"(d[54]), "+f"(d[55]), "+f"(d[56]), "+f"(d[57]), "+f"(d[58]), "+f"(d[59]), "+f"(d[60]), "+f"(d[61]), "+f"(d[62]), "+f"(d[63]), "+f"(d[64]), "+f"(d[65]), "+f"(d[66]), "+f"(d[67]), "+f"(d[68]), "+f"(d[69]), "+f"(d[70]), "+f"(d[71]), "+f"(d[72]), "+f"(d[73]), "+f"(d[74]), "+f"(d[75]), "+f"(d[76]), "+f"(d[77]), "+f"(d[78]), "+f"(d[79]), "+f"(d[80]), "+f"(d[81]), "+f"(d[82]), "+f"(d[83]), "+f"(d[84]), "+f"(d[85]), "+f"(d[86]), "+f"(d[87]), "+f"(d[88]), "+f"(d[89]), "+f"(d[90]), "+f"(d[91]), "+f"(d[92]), "+f"(d[93]), "+f"(d[94]), "+f"(d[95]), "+f"(d[96]), "+f"(d[97]), "+f"(d[98]), "+f"(d[99]), "+f"(d[100]), "+f"(d[101]), "+f"(d[102]), "+f"(d[103]), "+f"(d[104]), "+f"(d[105]), "+f"(d[106]), "+f"(d[107]), "+f"(d[108]), "+f"(d[109]), "+f"(d[110]), "+f"(d[111]), "+f"(d[112]), "+f"(d[113]), "+f"(d[114]), "+f"(d[115]), "+f"(d[116]), "+f"(d[117]), "+f"(d[118]), "+f"(d[119]), "+f"(d[120]), "+f"(d[121]), "+f"(d[122]), "+f"(d[123]), "+f"(d[124]), "+f"(d[125]), "+f"(d[126]), "+f"(d[127])
        : "l"(da), "l"(db), "r"(acc));
}
__device__ __forceinline__ void wgmma128(float (&d)[64], uint64_t da, uint64_t db, int acc) {
    asm volatile("{.reg .pred p; setp.ne.b32 p, %66, 0;\n"
        "wgmma.mma_async.sync.aligned.m64n128k16.f32.bf16.bf16 {"
        "%0,%1,%2,%3,%4,%5,%6,%7,%8,%9,%10,%11,%12,%13,%14,%15,"
        "%16,%17,%18,%19,%20,%21,%22,%23,%24,%25,%26,%27,%28,%29,%30,%31,"
        "%32,%33,%34,%35,%36,%37,%38,%39,%40,%41,%42,%43,%44,%45,%46,%47,"
        "%48,%49,%50,%51,%52,%53,%54,%55,%56,%57,%58,%59,%60,%61,%62,%63"
        "}, %64, %65, p, 1, 1, 0, 1;}"
        : "+f"(d[0]), "+f"(d[1]), "+f"(d[2]), "+f"(d[3]), "+f"(d[4]), "+f"(d[5]), "+f"(d[6]), "+f"(d[7]), "+f"(d[8]), "+f"(d[9]), "+f"(d[10]), "+f"(d[11]), "+f"(d[12]), "+f"(d[13]), "+f"(d[14]), "+f"(d[15]), "+f"(d[16]), "+f"(d[17]), "+f"(d[18]), "+f"(d[19]), "+f"(d[20]), "+f"(d[21]), "+f"(d[22]), "+f"(d[23]), "+f"(d[24]), "+f"(d[25]), "+f"(d[26]), "+f"(d[27]), "+f"(d[28]), "+f"(d[29]), "+f"(d[30]), "+f"(d[31]), "+f"(d[32]), "+f"(d[33]), "+f"(d[34]), "+f"(d[35]), "+f"(d[36]), "+f"(d[37]), "+f"(d[38]), "+f"(d[39]), "+f"(d[40]), "+f"(d[41]), "+f"(d[42]), "+f"(d[43]), "+f"(d[44]), "+f"(d[45]), "+f"(d[46]), "+f"(d[47]), "+f"(d[48]), "+f"(d[49]), "+f"(d[50]), "+f"(d[51]), "+f"(d[52]), "+f"(d[53]), "+f"(d[54]), "+f"(d[55]), "+f"(d[56]), "+f"(d[57]), "+f"(d[58]), "+f"(d[59]), "+f"(d[60]), "+f"(d[61]), "+f"(d[62]), "+f"(d[63])
        : "l"(da), "l"(db), "r"(acc));
}
__device__ __forceinline__ void wg_fence() { asm volatile("wgmma.fence.sync.aligned;" ::: "memory"); }
__device__ __forceinline__ void wg_commit() { asm volatile("wgmma.commit_group.sync.aligned;" ::: "memory"); }
template <int N> __device__ __forceinline__ void wg_wait() { asm volatile("wgmma.wait_group.sync.aligned %0;" ::"n"(N) : "memory"); }
__device__ __forceinline__ uint64_t mkdesc(uint32_t addr, uint32_t lbo, uint32_t sbo, uint32_t sw) {
    return (uint64_t)((addr & 0x3FFFF) >> 4) | ((uint64_t)(lbo >> 4) << 16) | ((uint64_t)(sbo >> 4) << 32) | ((uint64_t)sw << 62);
}
__device__ __forceinline__ void tma2d(uint32_t dst, const CUtensorMap* m, int c0, int c1, uint32_t bar) {
    asm volatile("cp.async.bulk.tensor.2d.shared::cluster.global.mbarrier::complete_tx::bytes [%0], [%1, {%2, %3}], [%4];"
        ::"r"(dst), "l"(m), "r"(c0), "r"(c1), "r"(bar) : "memory");
}
__device__ __forceinline__ void tma3d(uint32_t dst, const CUtensorMap* m, int c0, int c1, int c2, uint32_t bar) {
    asm volatile("cp.async.bulk.tensor.3d.shared::cluster.global.mbarrier::complete_tx::bytes [%0], [%1, {%2, %3, %4}], [%5];"
        ::"r"(dst), "l"(m), "r"(c0), "r"(c1), "r"(c2), "r"(bar) : "memory");
}
__device__ __forceinline__ void tma3d_mc(uint32_t dst, const CUtensorMap* m, int c0, int c1, int c2, uint32_t bar, uint16_t mask) {
    asm volatile("cp.async.bulk.tensor.3d.shared::cluster.global.mbarrier::complete_tx::bytes.multicast::cluster [%0], [%1, {%2, %3, %4}], [%5], %6;"
        ::"r"(dst), "l"(m), "r"(c0), "r"(c1), "r"(c2), "r"(bar), "h"(mask) : "memory");
}
__device__ __forceinline__ void mbar_arrive(uint32_t bar) { asm volatile("mbarrier.arrive.shared.b64 _, [%0];" ::"r"(bar) : "memory"); }
__device__ __forceinline__ void mbar_arrive_remote(uint32_t bar) {
    asm volatile("mbarrier.arrive.shared::cluster.b64 _, [%0];" ::"r"(bar) : "memory");
}
template <int R> __device__ __forceinline__ void reg_inc() { asm volatile("setmaxnreg.inc.sync.aligned.u32 %0;" ::"n"(R)); }
template <int R> __device__ __forceinline__ void reg_dec() { asm volatile("setmaxnreg.dec.sync.aligned.u32 %0;" ::"n"(R)); }

constexpr int CH_NRES = 50;
constexpr int CH_WREG = CH_NRES * 512;
constexpr int CH_PART = 8 * CH_WREG;
constexpr int CH_SX = CH_PART + 16384;
constexpr int CH_MX = CH_SX + 3 * 1280;
constexpr int CH_XS = CH_MX + 3 * 512;
constexpr int CH_BAR = CH_XS + 5632;
constexpr int CH_SMEM = CH_BAR + 192;
constexpr int CH_THREADS = 384;

__device__ __forceinline__ char* ring_base() { return (char*)(((uintptr_t)g_ring + (1 << 20) - 1) & ~(uintptr_t)((1 << 20) - 1)); }
__device__ __forceinline__ uint32_t ring_off(int chunk, int side) {
    uint32_t o = ((chunk & 1) << 13) | ((chunk >> 1) << 16);
    uint32_t par = ((o >> 13) ^ (o >> 16) ^ (o >> 17) ^ (o >> 19) ^ side) & 1;
    return o | (par << 12);
}
__device__ __forceinline__ uint2 ld_poll(const char* p) {
    unsigned long long v; asm volatile("ld.relaxed.gpu.global.b64 %0, [%1];" : "=l"(v) : "l"(p) : "memory");
    return make_uint2((uint32_t)v, (uint32_t)(v >> 32));
}
__device__ __forceinline__ void st_pub(char* p, uint32_t x, uint32_t y) {
    unsigned long long v = ((unsigned long long)y << 32) | x;
    asm volatile("st.relaxed.gpu.global.b64 [%0], %1;" ::"l"(p), "l"(v) : "memory");
}
template <int N>
__device__ __forceinline__ void poll_issue(uint2 (&b)[N], const char* p, bool lastvalid) {
#pragma unroll
    for (int i = 0; i < N; i++) {
        if (i < N - 1 || lastvalid) b[i] = ld_poll(p + i * 256);
        else b[i] = make_uint2(0, 0);
    }
}
template <int N>
__device__ __forceinline__ int poll_check(uint2 (&b)[N], const char* p) {
    int it = 0;
    uint32_t mx = b[0].x;
#pragma unroll
    for (int i = 1; i < N; i++) mx = max(mx, b[i].x);
    if (__any_sync(0xffffffffu, mx == SENT)) {
        while (it++ < SPIN_LIMIT) {
#pragma unroll
            for (int i = 0; i < N; i++)
                if (b[i].x == SENT) b[i] = ld_poll(p + i * 256);
            mx = b[0].x;
#pragma unroll
            for (int i = 1; i < N; i++) mx = max(mx, b[i].x);
            if (!__any_sync(0xffffffffu, mx == SENT)) break;
        }
    }
    return it;
}
template <int N>
__device__ __forceinline__ uint32_t delay(uint32_t a) {
    uint32_t z = 0;
#pragma unroll
    for (int i = 0; i < N; i++) asm volatile("ld.volatile.shared.u32 %0, [%1];" : "=r"(z) : "r"(a + z) : "memory");
    return z;
}

template <bool B> struct BoolC { static constexpr bool value = B; };
#define PFKV 0
#define LDW 1
#define KGS 3
#define DLM 2
#define DLO 2
constexpr int OB = 0;
template <int PACE>
__device__ __forceinline__ void preload(uint32_t (&sw)[12][4], uint32_t a, uint32_t zero) {
    uint32_t z = 0;
#pragma unroll
    for (int i = 0; i < 12; i++) {
        if (PACE && i % (PACE ? PACE : 1) == 0) z = delay<1>(zero + z);
        ldsm4t(sw[i], a + z + i * 512);
    }
}
__device__ __forceinline__ void stsm4(uint32_t addr, uint32_t a, uint32_t b, uint32_t c, uint32_t d) {
    asm volatile("stmatrix.sync.aligned.m8n8.x4.shared.b16 [%0], {%1,%2,%3,%4};" ::"r"(addr), "r"(a), "r"(b), "r"(c), "r"(d) : "memory");
}
__device__ __forceinline__ void stsm4t(uint32_t addr, uint32_t a, uint32_t b, uint32_t c, uint32_t d) {
    asm volatile("stmatrix.sync.aligned.m8n8.x4.trans.shared.b16 [%0], {%1,%2,%3,%4};" ::"r"(addr), "r"(a), "r"(b), "r"(c), "r"(d) : "memory");
}
__device__ __forceinline__ void st_part(uint32_t addr, const float (&x)[4], const float (&y)[4]) {
    stsm4(addr, pack_bf16(x[0], x[1]), pack_bf16(x[2], x[3]), pack_bf16(y[0], y[1]), pack_bf16(y[2], y[3]));
}
template <bool TR>
__device__ __forceinline__ void red_part(uint32_t& lo, uint32_t& hi, uint32_t addr, uint32_t eye) {
    uint32_t a[4][4];
#pragma unroll
    for (int j = 0; j < 4; j++) { if (TR) ldsm4t(a[j], addr + j * 512); else ldsm4(a[j], addr + j * 512); }
    float r0[4], r1[4];
    mma16z(r0, a[0], eye, eye); mma16z(r1, a[1], eye, eye);
    mma16(r0, a[2], eye, eye); mma16(r1, a[3], eye, eye);
    lo = pack_bf16(r0[0] + r1[0], r0[1] + r1[1]); hi = pack_bf16(r0[2] + r1[2], r0[3] + r1[3]);
}
__device__ __forceinline__ int o_chunk(int ks, int& pos) {
    const int cw = ks < 176 ? ks / 11 : 16 + (ks - 176) / 10;
    pos = ks - (cw < 16 ? 11 * cw : 176 + 10 * (cw - 16));
    return cw;
}

template <bool PV>
__device__ __forceinline__ void chain_loop(const uint32_t (&wa)[36][4], const uint32_t sb, const int w, const int lane, const int rank,
                                           const int h, const int side) {
    const int nq = rank == 0 ? 6 : 5, u0 = rank == 0 ? 0 : 1 + 5 * rank, v0 = rank == 0 ? -6 : 3 * rank - 6;
    const uint32_t l16 = sb + lane * 16;
    const uint32_t wl = l16 + w * CH_WREG;
    const uint32_t pw = sb + CH_PART + w * 256 + (lane >> 4) * 2048 + (lane & 15) * 16;
    const uint32_t pl = l16 + CH_PART + w * 2048;
    const uint32_t barS = sb + CH_BAR, barM = barS + 8, zero = barS + 24;
    const uint32_t eye = ((lane >> 2) == 2 * (lane & 3)) ? 0x3F80u : ((lane >> 2) == 2 * (lane & 3) + 1) ? 0x3F800000u : 0u;
    char* const ring = ring_base() + lane * 8;
    const uint32_t m_rd = ring_off(24 + w, side), o_rd = ring_off(rank * 8 + w, side);
    uint32_t pub;
    if (PV) { int pos, cw = o_chunk(h * 8 + v0 + w, pos); pub = (ring_off(cw, 0) & ~4096u) + pos * 256; }
    else pub = (ring_off(24 + (h >> 2), 0) & ~4096u) + ((2 * h + w) & 7) * 256;
    const uint32_t xs = l16 + CH_XS + (PV ? nq * 512 + (w - nq) * 1024 : w * 512);
    char* const kvo = (char*)(PV ? g_vm + 128 * (v0 + w) : g_km + 64 * (u0 + w)) + h * 2048;
    const bool mown = !PV && w == rank && rank < 2;
    uint32_t sw[12][4];
#pragma unroll
    for (int i = 0; i < 12; i++) ldsm4t(sw[i], wl + i * 512);

    auto step = [&](const int s, auto lastc) {
        constexpr bool last = decltype(lastc)::value;
        const uint32_t slot = (s & 3) << 14;
        uint2 b[8];
        poll_issue<8>(b, ring + (m_rd + slot + delay<DLM>(zero)), true);
        poll_check<8>(b, ring + (m_rd + slot));
        if (OB && !last) bar_arrive(8, 288);
        {
            float acc[6][4];
#pragma unroll
            for (int kk = 0; kk < 8; kk++) {
                const int j = (2 * kk) % 12;
                if (kk == 0) { mma16z(acc[5], sw[0], b[0].x, b[0].y); mma16z(acc[4], sw[1], b[0].x, b[0].y); }
                else { mma16(acc[5], sw[j], b[kk].x, b[kk].y); mma16(acc[4], sw[j + 1], b[kk].x, b[kk].y); }
#pragma unroll
                for (int i = 0; i < 4; i++) {
                    if (kk == 0) mma16z(acc[i], wa[i * 8], b[0].x, b[0].y);
                    else mma16(acc[i], wa[i * 8 + kk], b[kk].x, b[kk].y);
                    if (i < 2) ldsm4t(sw[j + i], wl + (12 + 2 * kk + i) * 512);
                }
            }
            st_part(pw + 4 * 2048, acc[4], acc[5]);
            st_part(pw, acc[0], acc[1]);
            st_part(pw + 2 * 2048, acc[2], acc[3]);
        }
        uint32_t kv0, kv1;
        if (!PV) {
            uint32_t xf[4];
            ldsm4(xf, xs);
            bar_sync(1, last ? 256 : 256 + OB);
            red_part<true>(kv1, kv0, pl, eye);
            if (!last) {
                float s0[4], s1[4], s2[4], s3[4], s4[4];
                mma8z(s0, kv1, 0, xf[0]); mma8z(s1, kv1, 0, xf[1]); mma8z(s2, kv1, 0, xf[2]); mma8z(s3, kv1, 0, xf[3]);
                mma8z(s4, kv1, 0, kv0);
                const float x0[4] = {s0[0], s0[1], s1[0], s1[1]}, x1[4] = {s2[0], s2[1], s3[0], s3[1]};
                sts128(pl, x0); sts128(pl + 512, x1);
                sts64(pl + 1024 - lane * 8, s4[0], s4[1]);
                bar_arrive(2, nq * 32 + 64 + OB);
            }
        } else {
            bar_sync(1, last ? 256 : 256 + OB);
        }
        {
            float va[4][4];
            const float z = __uint_as_float(delay<1>(zero));
#pragma unroll
            for (int i = 0; i < 4; i++) va[i][0] = va[i][1] = va[i][2] = va[i][3] = z;
#pragma unroll
            for (int kk = 0; kk < 8; kk++) {
                if (kk < 2) { mma16(va[kk & 1], wa[32 + 2 * kk], b[kk].x, b[kk].y); mma16(va[2 + (kk & 1)], wa[33 + 2 * kk], b[kk].x, b[kk].y); }
                else { mma16(va[kk & 1], sw[(2 * kk) % 12], b[kk].x, b[kk].y); mma16(va[2 + (kk & 1)], sw[(2 * kk + 1) % 12], b[kk].x, b[kk].y); }
            }
#pragma unroll
            for (int j = 0; j < 4; j++) { va[0][j] += va[1][j]; va[2][j] += va[3][j]; }
            st_part(pw + 6 * 2048, va[0], va[2]);
        }
        if (PV) {
            uint32_t vt0[4], vt1[4];
            ldsm4t(vt0, xs); ldsm4t(vt1, xs + 512);
            if (w >= 6 && !last) {
                const uint32_t sa = l16 + CH_PART + (w - 6) * 512, sc = sb + CH_PART + 1024 + (w - 6) * 128 + lane * 4;
                const uint32_t da = l16 + CH_SX + rank * 1280 + (w - 6) * 512, dc = sb + CH_SX + rank * 1280 + 1024 + (w - 6) * 128 + lane * 4;
                bar_sync(2, nq * 32 + 64 + OB);
                float4 v[6]; float c[6];
#pragma unroll
                for (int i = 0; i < 6; i++) v[i] = (i < 5 || rank == 0) ? lds128(sa + i * 2048) : make_float4(0, 0, 0, 0);
#pragma unroll
                for (int i = 0; i < 6; i++) c[i] = (i < 5 || rank == 0) ? lds32(sc + i * 2048) : 0.f;
                float4 sv = add4(add4(add4(v[0], v[1]), add4(v[2], v[3])), add4(v[4], v[5]));
                float cv = ((c[0] + c[1]) + (c[2] + c[3])) + (c[4] + c[5]);
#pragma unroll
                for (int d = 1; d < 4; d++) {
                    const int dr = rank + d - (rank + d > 2 ? 3 : 0);
                    st_async4(mapa(da, dr), sv, mapa(barS, dr)); st_async1(mapa(dc, dr), cv, mapa(barS, dr));
                }
            }
            bar_sync(3, last ? 256 : 288 + OB);
            red_part<false>(kv0, kv1, pl, eye);
            if (!last) {
                mbar_wait(barS, s & 1);
                const uint32_t sx = l16 + CH_SX;
                float4 a0 = lds128(sx), a1 = lds128(sx + 1280), a2 = lds128(sx + 2560);
                float4 b0 = lds128(sx + 512), b1 = lds128(sx + 512 + 1280), b2 = lds128(sx + 512 + 2560);
                float2 c0 = lds64(sx + 1024 - lane * 8), c1 = lds64(sx + 1024 + 1280 - lane * 8), c2 = lds64(sx + 1024 + 2560 - lane * 8);
                a0 = add4(add4(a0, a1), a2); b0 = add4(add4(b0, b1), b2);
                float sc[10] = {a0.x, a0.y, a0.z, a0.w, b0.x, b0.y, b0.z, b0.w, c0.x + c1.x + c2.x, c0.y + c1.y + c2.y};
                float mx = fmaxf(fmaxf(fmaxf(sc[0], sc[1]), fmaxf(sc[2], sc[3])), fmaxf(fmaxf(sc[4], sc[5]), fmaxf(sc[6], sc[7])));
                mx = fmaxf(mx, fmaxf(sc[8], sc[9]));
                mx = fmaxf(fmaxf(mx, __shfl_xor_sync(0xffffffffu, mx, 1)),
                           fmaxf(__shfl_xor_sync(0xffffffffu, mx, 2), __shfl_xor_sync(0xffffffffu, mx, 3)));
                const float cs = 0.08838834764831845f * 1.4426950408889634f;
                const float mb = -mx * cs;
#pragma unroll
                for (int j = 0; j < 10; j++) sc[j] = ex2(fmaf(sc[j], cs, mb));
                uint32_t pf[5];
#pragma unroll
                for (int j = 0; j < 5; j++) pf[j] = pack_bf16(sc[2 * j], sc[2 * j + 1]);
                float o0[4], o1[4], o2[4], o3[4], o4[4], o5[4];
                const uint32_t p0[4] = {pf[0], 0, pf[1], 0}, p1[4] = {pf[2], 0, pf[3], 0};
                mma16z(o0, p0, vt0[0], vt0[1]); mma16z(o1, p0, vt1[0], vt1[1]);
                mma16z(o2, p1, vt0[2], vt0[3]); mma16z(o3, p1, vt1[2], vt1[3]);
                mma8z(o4, pf[4], 0, kv0); mma8z(o5, pf[4], 0, kv1);
                float sum = (((sc[0] + sc[1]) + (sc[2] + sc[3])) + ((sc[4] + sc[5]) + (sc[6] + sc[7]))) + (sc[8] + sc[9]);
                sum = (sum + __shfl_xor_sync(0xffffffffu, sum, 1)) + (__shfl_xor_sync(0xffffffffu, sum, 2) + __shfl_xor_sync(0xffffffffu, sum, 3));
                float inv; asm("rcp.approx.ftz.f32 %0, %1;" : "=f"(inv) : "f"(sum));
                const uint32_t ox = pack_bf16((o0[0] + o2[0] + o4[0]) * inv, (o0[1] + o2[1] + o4[1]) * inv);
                const uint32_t oy = pack_bf16((o1[0] + o3[0] + o5[0]) * inv, (o1[1] + o3[1] + o5[1]) * inv);
                st_pub(ring + (pub + slot), ox, oy); st_pub(ring + (pub + slot) + 4096, ox, oy);
                if (OB) bar_arrive(10, (9 - nq) * 32);
                preload<0>(sw, wl + 28 * 512, zero);
            }
            kv0 = movm(kv0); kv1 = movm(kv1);
        } else {
            *(uint32_t*)(kvo + (uint32_t)(s * (NH * 2048) + lane * 4)) = kv0;
            if (last) bar_arrive(3, 256);
            else {
                bar_sync(3, 288 + OB);
                preload<1>(sw, wl + 28 * 512, zero);
            }
        }
        uint2 c[11];
        if (!last) {
            bar_sync(4, 256 + OB);
            poll_issue<11>(c, ring + (o_rd + slot + delay<DLO>(zero)), rank < 2);
        }
        if (PV) { uint32_t* d = (uint32_t*)(kvo + (uint32_t)(s * (NH * 2048) + lane * 4)); d[0] = kv0; d[32] = kv1; }
        if (last) return;
        poll_check<11>(c, ring + (o_rd + slot));
        if (OB) bar_arrive(9, 288);
        {
            float acc[4][4];
#pragma unroll
            for (int f = 0; f < 22; f++) {
                const int kk = f >> 1, a = f & 3;
                if (f < 4) mma16z(acc[a], sw[f % 12], c[kk].x, c[kk].y);
                else mma16(acc[a], sw[f % 12], c[kk].x, c[kk].y);
                if (f + 12 < 22) ldsm4t(sw[f % 12], wl + (28 + f + 12) * 512);
            }
#pragma unroll
            for (int i = 0; i < 2; i++) {
#pragma unroll
                for (int j = 0; j < 4; j++) acc[i][j] += acc[i + 2][j];
                sts128(l16 + CH_PART + i * 4096 + w * 512, acc[i]);
            }
        }
        if (!PV && w < 2) {
            bar_sync(5, 288 + OB);
            float4 v[8];
#pragma unroll
            for (int i = 0; i < 8; i++) v[i] = lds128(l16 + CH_PART + w * 4096 + i * 512);
            float4 r = add4(add4(add4(v[0], v[1]), add4(v[2], v[3])), add4(add4(v[4], v[5]), add4(v[6], v[7])));
            if (!mown) st_async4(mapa(l16 + CH_MX + rank * 512, w), r, mapa(barM, w));
            bar_arrive(7, 256 + OB);
            if (mown) {
                mbar_wait(barM, s & 1);
                float4 x = lds128(l16 + CH_MX + (rank ^ 1) * 512), y = lds128(l16 + CH_MX + 2 * 512);
                r = add4(add4(x, r), y);
                const uint32_t mx = movm(pack_bf16(r.x, r.y)), my = movm(pack_bf16(r.z, r.w));
                const uint32_t ns = (slot + 0x4000) & 0xC000;
                st_pub(ring + (pub + ns), mx, my); st_pub(ring + (pub + ns) + 4096, mx, my);
            }
            preload<0>(sw, wl, zero);
        } else {
            bar_arrive(5, 288 + OB);
            bar_sync(7, 256 + OB);
            preload<2>(sw, wl, zero);
        }
        bar_sync(6, 320 + OB);
    };
#pragma unroll 1
    for (int s = 0; s < NSEG - 1; s++) step(s, BoolC<false>());
    step(NSEG - 1, BoolC<true>());
    bar_arrive(6, 288);
}

__device__ __forceinline__ void chain_pace(const uint32_t sb, const int lane, const int rank, const int aware) {
    const uint32_t zero = sb + CH_BAR + 24;
    if (lane == 0) {
        char* ring = ring_base();
        uint32_t* p0 = (uint32_t*)(ring + ring_off(blockIdx.x & 15, 0) + 3072 + (blockIdx.x >> 4) * 128);
        uint32_t* p1 = (uint32_t*)(ring + ring_off(blockIdx.x & 15, 1) + 3072 + (blockIdx.x >> 4) * 128);
        *p0 = 0; *p1 = 0;
        int b0 = 1 << 30, b1 = 1 << 30; uint32_t v = 0;
        for (int r = 0; r < 4 || (r < 256 && !mbar_test(sb + CH_BAR + 16, 0)); r++) {
            uint32_t t0 = clk(); v = atomicExch(p0 + (v == 500), r); uint32_t t1 = v == 777 ? clk() + 1 : clk(); b0 = min(b0, (int)(t1 - t0));
            t0 = clk(); v = atomicExch(p1 + (v == 500), r); t1 = v == 777 ? clk() + 1 : clk(); b1 = min(b1, (int)(t1 - t0));
            asm volatile("st.volatile.shared.u32 [%0], %1;" ::"r"(zero + 4), "r"(aware ? (b1 < b0) ^ (aware - 1) : 0) : "memory");
        }
    }
    __syncwarp();
#pragma unroll 1
    for (int s = 1; s < NSEG; s++) {
        bar_sync(5, 288 + OB);
        bar_arrive(6, 320 + OB + (rank == 2 ? delay<18>(zero) : 0));
    }
}
__device__ __forceinline__ char* reset_ptr(const int lane, const int rank, const int h) {
    const int nq = rank == 0 ? 6 : 5, v0 = rank == 0 ? -6 : 3 * rank - 6;
    int pos, cw = o_chunk(h * 8 + v0 + min(max(5 + (lane >> 3), nq), 7), pos);
    if (lane >= 24 && rank < 2) { cw = 24 + (h >> 2); pos = (2 * h + rank) & 7; }
    return ring_base() + ((ring_off(cw, 0) & ~4096u) + pos * 256 + (lane & 7) * 16);
}
__device__ __forceinline__ void chain_chores(const uint32_t sb, const int lane, const int rank, const int h, const bf16* __restrict__ mem0) {
    const int nq = rank == 0 ? 6 : 5, u0 = rank == 0 ? 0 : 1 + 5 * rank, v0 = rank == 0 ? -6 : 3 * rank - 6;
    const uint32_t barS = sb + CH_BAR, barM = barS + 8, barX = barS + 16;
    auto xload = [&](int s) {
        mbar_expect(barX, 8192 - nq * 512);
        bulk_load(sb + CH_XS, g_kx + (size_t)(s * NH + h) * 4096 + u0 * 256, nq * 512, barX);
        bulk_load(sb + CH_XS + nq * 512, g_vx + (size_t)(s * NH + h) * 4096 + (v0 + nq) * 512, (8 - nq) * 1024, barX);
    };
    char* const rb = reset_ptr(lane, rank, h);
    int* const kvf = g_kvf + blockIdx.x * 16;
    if (rank < 2) {
        const uint32_t* p = (const uint32_t*)(mem0 + (lane >> 2) * DM + 32 * h + 16 * rank + 2 * (lane & 3));
        char* d = ring_base() + ((ring_off(24 + (h >> 2), 0) & ~4096u) + ((2 * h + rank) & 7) * 256 + lane * 8);
        const uint32_t x = p[0] == SENT ? 0x7FFF7FFFu : p[0];
        st_pub(d, x, p[4]); st_pub(d + 4096, x, p[4]);
    }
    if (lane == 0) {
        wait_ctr(kvf, 2);
        asm volatile("fence.proxy.async;" ::: "memory");
        xload(0);
    }
#pragma unroll 1
    for (int s = 0; s < NSEG - 1; s++) {
        if (lane == 0) {
            mbar_expect(barS, 3 * 1280);
            if (rank < 2) mbar_expect(barM, 2 * 512);
        }
#pragma unroll
        for (int i = 0; i < 4; i++)
            asm volatile("st.relaxed.gpu.global.v4.u32 [%0], {%1,%1,%1,%1};" ::"l"(rb + ((((s + 2) & 3) << 14) + (i >> 1) * 4096 + (i & 1) * 128)), "r"(SENT) : "memory");
        __threadfence();
        if (lane == 0 && (s & 3) == 0 && s) atomicAdd(g_ctr + C_CHAIN + (s >> 2) - 1, 1);
        if (lane == 0 && (s & 3) == 3) { wait_ctr(kvf + (s >> 2) + 1, 2); asm volatile("fence.proxy.async;" ::: "memory"); }
        __syncwarp();
        bar_sync(3, 288 + OB);
        if (lane == 0) xload(s + 1);
        mbar_wait(barX, (s + 1) & 1);
        bar_sync(6, 320 + OB);
    }
    bar_sync(6, 288);
    __threadfence();
    if (lane == 0) atomicAdd(g_ctr + C_CHAIN + 15, 1);
}

struct S4Params { const bf16 *Are, *Aim, *Bre, *Bim, *Cre, *Cim, *ldt, *dsk; };
__device__ __forceinline__ float2 cmul(float2 a, float2 b) { return make_float2(a.x * b.x - a.y * b.y, a.x * b.y + a.y * b.x); }
__device__ __forceinline__ float2 csq(float2 a) { return make_float2(a.x * a.x - a.y * a.y, (a.x + a.x) * a.y); }
__device__ __forceinline__ float2 cexp_t(float lr, float turns) {
    float f = (turns - rintf(turns)) * 6.283185307179586f, e = ex2(lr);
    return make_float2(e * __cosf(f), e * __sinf(f));
}
__device__ __forceinline__ float bf_at(uint2 v, int i) {
    const uint32_t w = i < 2 ? v.x : v.y;
    return __uint_as_float((i & 1) ? w & 0xFFFF0000u : w << 16);
}
__device__ __forceinline__ void kg_step(uint32_t (&a)[4][4], uint32_t (&b)[5][2], uint32_t pa, uint32_t pe, float x0) {
#pragma unroll
    for (int i = 0; i < 2; i++) {
        const float4 p = lds128(pa + i * 64);
        const float2 e8 = lds64(pe + i * 32), c = make_float2(p.z, p.w);
        const float mag = ex2(p.x * x0), ph = p.y * x0;
        float2 e0 = make_float2(mag * __cosf(ph), mag * __sinf(ph)), e1 = cmul(e0, e8);
#pragma unroll
        for (int j = 0; j < 4; j++) {
            a[j][2 * i] = pack_bf16(e0.x, e0.y); a[j][2 * i + 1] = pack_bf16(e1.x, e1.y);
            e0 = csq(e0); e1 = csq(e1);
        }
        float2 m = cmul(c, e0);
        b[0][i] = pack_bf16(m.x, -m.y);
#pragma unroll
        for (int j = 0; j < 4; j++) {
            m = cmul(c, e1);
            b[j + 1][i] = pack_bf16(m.x, -m.y);
            if (j < 3) e1 = csq(e1);
        }
    }
}
__device__ __forceinline__ void kg_mma(float (&kd)[5][4], const uint32_t (&a)[4][4], const uint32_t (&b)[5][2]) {
    mma16(kd[0], a[0], b[0][0], b[0][1]);
#pragma unroll
    for (int j = 0; j < 4; j++) mma16(kd[j + 1], a[j], b[j + 1][0], b[j + 1][1]);
}
struct KgRaw { uint2 v[6]; float ldt; };
__device__ __forceinline__ void kg_load(KgRaw& r, const S4Params& P, int d, int lane) {
    const bf16* src[6] = {P.Are, P.Aim, P.Bre, P.Bim, P.Cre, P.Cim};
#pragma unroll
    for (int j = 0; j < 6; j++) r.v[j] = __ldg((const uint2*)(src[j] + d * 128) + lane);
    r.ldt = __bfloat162float(P.ldt[d]);
}
__device__ __forceinline__ float kg_params(const KgRaw& r, uint32_t stg, int lane) {
    const float dt = __bfloat162float(__float2bfloat16(expf(r.ldt)));
    float k2048 = 0.f;
#pragma unroll
    for (int i = 0; i < 4; i++) {
        const float br = dt * bf_at(r.v[2], i), bi = dt * bf_at(r.v[3], i), cr = bf_at(r.v[4], i), ci = bf_at(r.v[5], i);
        const float zr = dt * bf_at(r.v[0], i) * 1.4426950408889634f;
        float zt = dt * bf_at(r.v[1], i) * 0.15915494309189535f;
        zt -= rintf(zt);
        const float v[4] = {zr, zt * 6.283185307179586f, cr * br - ci * bi, cr * bi + ci * br};
        const float2 e8 = cexp_t(8.f * zr, 8.f * zt), el = cexp_t(2048.f * zr, 2048.f * zt);
        k2048 += v[2] * el.x - v[3] * el.y;
        sts128(stg + (i * 32 + lane) * 16, v);
        sts64(stg + 2048 + (i * 32 + lane) * 8, e8.x, e8.y);
    }
#pragma unroll
    for (int o = 16; o; o >>= 1) k2048 += __shfl_xor_sync(0xffffffffu, k2048, o);
    __syncwarp();
    return k2048;
}
__device__ __forceinline__ void kg_store(const float (&kd)[5][4], float k2048, uint32_t stg, int d, int lane) {
    __syncwarp();
    const uint32_t ta = stg + (lane & 7) * 32 + ((lane >> 3) & 1) * 16 + (lane >> 4) * 256;
    stsm4t(ta, pack_bf16(kd[0][0], kd[0][1]), pack_bf16(kd[0][2], kd[0][3]), pack_bf16(kd[1][0], kd[1][1]), pack_bf16(kd[1][2], kd[1][3]));
    stsm4t(ta + 512, pack_bf16(kd[2][0], kd[2][1]), pack_bf16(kd[2][2], kd[2][3]), pack_bf16(kd[3][0], kd[3][1]), pack_bf16(kd[3][2], kd[3][3]));
    stsm4t(ta + 1024, pack_bf16(kd[4][0], kd[4][1]), pack_bf16(kd[4][2], kd[4][3]), pack_bf16(k2048, 0.f), 0);
    __syncwarp();
#pragma unroll
    for (int j = 0; j < 3; j++) ((float4*)(g_kd + d * 768))[j * 32 + lane] = lds128(stg + j * 512 + lane * 16);
    __syncwarp();
}

__global__ void __cluster_dims__(3, 1, 1) __launch_bounds__(CH_THREADS, 1)
chain_kernel(const __grid_constant__ CUtensorMap mq, const __grid_constant__ CUtensorMap mk, const __grid_constant__ CUtensorMap mv,
             const __grid_constant__ CUtensorMap mo, const bf16* __restrict__ Wq, const bf16* __restrict__ Wk, const bf16* __restrict__ Wv,
             const bf16* __restrict__ mem0, const __grid_constant__ S4Params P, int aware) {
    extern __shared__ __align__(1024) unsigned char smem[];
    const uint32_t sb = smem_u32(smem);
    const int tid = threadIdx.x, lane = tid & 31;
    const int w = __shfl_sync(0xffffffffu, tid >> 5, 0);
    int rank; asm("mov.u32 %0, %%cluster_ctarank;" : "=r"(rank));
    const int h = blockIdx.x / 3;
    if (tid == 0) {
        mbar_init(sb + CH_BAR, 1); mbar_init(sb + CH_BAR + 8, 1); mbar_init(sb + CH_BAR + 16, 1);
        for (int i = 0; i < 16; i++) mbar_init(sb + CH_BAR + 64 + i * 8, 1);
        *(int*)(smem + CH_BAR + 24) = 0; *(int*)(smem + CH_BAR + 28) = 0;
        asm volatile("fence.mbarrier_init.release.cluster;" ::: "memory");
    }
    if (w == 10 && PFKV) {
        const int e = lane * 96 + blockIdx.x;
        if (e < 2048) asm volatile("cp.async.bulk.prefetch.L2.global [%0], 8192;" ::"l"(((e & 1) ? Wv : Wk) + (size_t)(e >> 1) * HD) : "memory");
        if (PFKV > 1) __nanosleep(PFKV);
    }
    if (w == 9) {
        char* const rb = reset_ptr(lane, rank, h);
#pragma unroll
        for (int i = 0; i < 8; i++)
            asm volatile("st.relaxed.gpu.global.v4.u32 [%0], {%1,%1,%1,%1};" ::"l"(rb + (((i >> 2) << 14) + ((i >> 1) & 1) * 4096 + (i & 1) * 128)), "r"(SENT) : "memory");
        if (lane < 16) g_kvf[blockIdx.x * 16 + lane] = 0;
        if (blockIdx.x == 0)
            for (int k = lane; k < N_CTR; k += 32) g_ctr[k] = 0;
        __threadfence();
        __syncwarp();
        asm volatile("griddepcontrol.launch_dependents;" ::: "memory");
    }
    __syncthreads();
    asm volatile("barrier.cluster.arrive.relaxed.aligned;" ::: "memory");

    if (w >= 8) {
        reg_dec<24>();
        asm volatile("barrier.cluster.wait.aligned;" ::: "memory");
        if (w == 8) chain_pace(sb, lane, rank, aware);
        else if (w == 9) chain_chores(sb, lane, rank, h, mem0);
    } else {
        reg_inc<240>();
        const int nq = rank == 0 ? 6 : 5;
        const int u0 = rank == 0 ? 0 : 1 + 5 * rank;
        const int v0 = rank == 0 ? -6 : 3 * rank - 6;
        const int gw = rank * 8 + w;
        const int ks0 = gw < 16 ? 11 * gw : 176 + 10 * (gw - 16);
        const int nko = gw < 16 ? 11 : 10;
        const uint32_t wr = sb + w * CH_WREG, bar0 = sb + CH_BAR + 64 + w * 16, bar1 = bar0 + 8;
        uint32_t wa[36][4];
        const uint32_t vst = sb + CH_PART + w * 2048;
        const int cq = h * DH + 8 * u0, cv = h * DH + 16 * (v0 + 6);
        const int r8 = lane >> 2, p = lane & 3;
        const bf16* src = p >= 2 ? ((p & 1) ? Wk : Wq) + cq + 32 : rank == 0 ? ((p & 1) ? Wk : Wq) + cq + 40 : Wv + cv - 16 + 8 * p;
        src += (size_t)(128 * w + r8) * HD;
        auto cp_rows = [&](int kh) {
            cp16(wr + ((kh >> 1) * 2 + (p >> 1)) * 512 + ((kh & 1) * 2 + (p & 1)) * 128 + r8 * 16, src + (size_t)kh * 8 * HD);
        };
        {
            int d = blockIdx.x * 8 + w, t = 0;
            const int d1 = 768 + blockIdx.x * 3 + w, nt = (w < 3 && d1 < DM) ? 32 : 16;
            const uint32_t stg = wr + 4096;
            KgRaw raw, raw1;
            kg_load(raw, P, d, lane);
            kg_load(raw1, P, min(d1, DM - 1), lane);
            float kd[5][4], k2048;
#pragma unroll 1
            for (int i = -LDW; i < 9 || t < nt; i++) {
                if (i >= 0 && i < 9) {
                    const uint32_t bar = bar0 + (i & 1) * 8;
                    if (i >= 2) mbar_wait(bar, ((i >> 1) - 1) & 1);
                    if (lane == 0) {
                        mbar_expect(bar, 2048);
                        if (i < 8) tma2d(wr + 8192 + (i & 1) * 8192 + (i >> 1) * 2048, (i & 1) ? &mk : &mq, cq, 128 * w + 32 * (i >> 1), bar);
                        else tma2d(vst, &mv, cv, 128 * w, bar);
                    }
                    if (i < 8) cp_rows(i);
                }
#pragma unroll 1
                for (int e = min(t + KGS, nt); t < e; t++) {
                    if ((t & 15) == 0) {
                        k2048 = kg_params(raw, stg, lane);
#pragma unroll
                        for (int j = 0; j < 20; j++) kd[j >> 2][j & 3] = 0.f;
                    }
                    uint32_t ka[4][4], kb[5][2];
                    kg_step(ka, kb, stg + ((t & 15) * 8 + (lane & 3)) * 16, stg + 2048 + ((t & 15) * 8 + (lane & 3)) * 8, (float)(lane >> 2));
                    kg_mma(kd, ka, kb);
                    if ((t & 15) == 15) { kg_store(kd, k2048, stg, d, lane); raw = raw1; d = d1; }
                }
            }
        }
        const uint32_t lrow = ((lane >> 4) * 8 + (lane & 7)) * 64, lsw = (lane >> 1) & 3, lh = (lane >> 3) & 1;
        mbar_wait(bar1, 1); mbar_wait(bar0, 0);
#pragma unroll
        for (int i = 0; i < 32; i++) ldsm4t(wa[i], wr + 8192 + lh * 8192 + (i & 7) * 1024 + lrow + (((i >> 3) ^ lsw) << 4));
#pragma unroll
        for (int i = 0; i < 4; i++) ldsm4t(wa[32 + i], vst + (i >> 1) * 1024 + lrow + ((((i & 1) * 2 + lh) ^ lsw) << 4));
        asm volatile("fence.proxy.async.shared::cta;" ::"r"(wa[31][0]), "r"(wa[35][0]) : "memory");
        __syncwarp();
#pragma unroll 1
        for (int i = 9; i < 18; i++) {
            const uint32_t bar = bar0 + (i & 1) * 8;
            if (i >= 11) mbar_wait(bar, ((i >> 1) - 1) & 1);
            if (lane == 0) {
                const int j = 2 * (i - 12), nb = min(2, nko - j);
                mbar_expect(bar, i < 12 ? 2048 : nb * 1024);
                if (i < 12) tma2d(wr + 8192 + (i - 9) * 2048, &mv, cv, 128 * w + 32 * (i - 8), bar);
                else for (int e = 0; e < nb; e++) tma2d(wr + 14336 + (j + e) * 1024, &mo, 32 * h, 16 * (ks0 + j + e), bar);
            }
            if (i < 17) cp_rows(i - 1);
        }
        mbar_wait(bar0, 0); mbar_wait(bar1, 0);
#pragma unroll 1
        for (int i = 0; i < 17; i++) {
            uint32_t x[4], y[4];
            ldsm4t(x, wr + 8192 + i * 1024 + lrow + ((lh ^ lsw) << 4));
            ldsm4t(y, wr + 8192 + i * 1024 + lrow + (((2 + lh) ^ lsw) << 4));
            if (i == 16 && nko == 10) x[0] = x[1] = x[2] = x[3] = y[0] = y[1] = y[2] = y[3] = 0;
            __syncwarp();
            stsm4t(wr + 8192 + i * 1024 + lane * 16, x[0], x[1], x[2], x[3]);
            stsm4t(wr + 8192 + i * 1024 + 512 + lane * 16, y[0], y[1], y[2], y[3]);
        }
        asm volatile("cp.async.wait_all;" ::: "memory");
        asm volatile("barrier.cluster.wait.aligned;" ::: "memory");
        bar_sync(1, 256);
        mbar_wait_long(sb + CH_BAR + 16, 0);
        const int side = __shfl_sync(0xffffffffu, *(volatile int*)(smem + CH_BAR + 28), 0);
        if (w >= nq) chain_loop<true>(wa, sb, w, lane, rank, h, side);
        else chain_loop<false>(wa, sb, w, lane, rank, h, side);
    }
}

constexpr int G_STAGE = 49152, G_NST = 4;
constexpr int G_STG = G_NST * G_STAGE;
constexpr int G_BAR = G_STG + 32768;
constexpr int G_SMEM = G_BAR + 256 + 1024;

#define ST(id, w, i)
#define WLOG(e)
constexpr int IT_QA = 0, IT_O = 1, IT_S4 = 2, IT_END = 3, IT_KV = 4;
#define Q_A 11
#define Q_W1 9
#define O_WIDE 11
#define Q_S1 8
__device__ __forceinline__ int queue_item(int q) {
    if (q < 512) return (IT_KV << 16) | ((q >> 5) << 8) | (q & 31);
    q -= 512;
    if (q < Q_A * 16) return (IT_QA << 16) | ((q >> 4) << 8) | (q & 15);
    q -= Q_A * 16;
    if (q < Q_W1 * 4) return (IT_O << 16) | ((q >> 2) << 8) | (q & 3);
    q -= Q_W1 * 4;
    if (q < (16 - Q_A) * 16) return (IT_QA << 16) | ((Q_A + (q >> 4)) << 8) | (q & 15);
    q -= (16 - Q_A) * 16;
    if (q < (O_WIDE - Q_W1) * 4) return (IT_O << 16) | ((Q_W1 + (q >> 2)) << 8) | (q & 3);
    q -= (O_WIDE - Q_W1) * 4;
    if (q < Q_S1) return (IT_S4 << 16) | q;
    q -= Q_S1;
    if (q < (16 - O_WIDE) * 8) return (IT_O << 16) | ((O_WIDE + (q >> 3)) << 8) | (q & 7);
    q -= (16 - O_WIDE) * 8;
    if (q < 128 - Q_S1) return (IT_S4 << 16) | (Q_S1 + q);
    return IT_END << 16;
}
__device__ __forceinline__ void tma2d_store(const CUtensorMap* m, uint32_t src, int c0, int c1) {
    asm volatile("cp.async.bulk.tensor.2d.global.shared::cta.bulk_group [%0, {%2, %3}], [%1];" ::"l"(m), "r"(src), "r"(c0), "r"(c1) : "memory");
}
__device__ __forceinline__ void mma8(float (&d)[4], uint32_t a0, uint32_t a1, uint32_t b0) {
    asm volatile("mma.sync.aligned.m16n8k8.row.col.f32.bf16.bf16.f32 {%0,%1,%2,%3}, {%4,%5}, {%6}, {%0,%1,%2,%3};"
        : "+f"(d[0]), "+f"(d[1]), "+f"(d[2]), "+f"(d[3]) : "r"(a0), "r"(a1), "r"(b0));
}

__device__ __forceinline__ void attn_head(const uint32_t (&q)[32], uint32_t sk, uint32_t sv, uint32_t fullv, uint32_t parv, uint32_t emptyk,
                                          int wi, int lane, uint32_t* dst) {
    const int g = lane >> 2, t = lane & 3, hi = wi & 1;
    float s[5][4];
#pragma unroll
    for (int j = 0; j < 5; j++) s[j][0] = s[j][1] = s[j][2] = s[j][3] = 0.f;
#pragma unroll
    for (int k2 = 0; k2 < 4; k2++) {
        uint32_t km[4];
        ldsm4(km, sk + 8192 + k2 * 512 + lane * 16);
#pragma unroll
        for (int i = 0; i < 2; i++) {
            const int ks = 2 * k2 + i;
            const uint32_t a[4] = {q[4 * ks], q[4 * ks + 1], q[4 * ks + 2], q[4 * ks + 3]};
            uint32_t b[4];
            const uint32_t ad = sk + ks * 1024 + ((lane >> 3) & 1) * 512 + (lane >> 4) * 128 + (lane & 7) * 16;
            ldsm4(b, ad);
            mma16(s[4], a, km[2 * i], km[2 * i + 1]);
            mma16(s[0], a, b[0], b[1]); mma16(s[1], a, b[2], b[3]);
            if (hi) { ldsm4(b, ad + 256); mma16(s[2], a, b[0], b[1]); mma16(s[3], a, b[2], b[3]); }
        }
    }
    __syncwarp();
    if (lane == 0) mbar_arrive(emptyk);
    const int r0 = hi * 16 + g;
    float m0 = fmaxf(s[4][0], s[4][1]), m1 = fmaxf(s[4][2], s[4][3]);
#pragma unroll
    for (int j = 0; j < 4; j++) {
        const int c = 8 * j + 2 * t;
        if (c > r0) s[j][0] = -INFINITY;
        if (c + 1 > r0) s[j][1] = -INFINITY;
        if (c > r0 + 8) s[j][2] = -INFINITY;
        if (c + 1 > r0 + 8) s[j][3] = -INFINITY;
        m0 = fmaxf(m0, fmaxf(s[j][0], s[j][1])); m1 = fmaxf(m1, fmaxf(s[j][2], s[j][3]));
    }
    m0 = fmaxf(m0, __shfl_xor_sync(0xffffffffu, m0, 1)); m1 = fmaxf(m1, __shfl_xor_sync(0xffffffffu, m1, 1));
    m0 = fmaxf(m0, __shfl_xor_sync(0xffffffffu, m0, 2)); m1 = fmaxf(m1, __shfl_xor_sync(0xffffffffu, m1, 2));
    const float cs = 0.08838834764831845f * 1.4426950408889634f;
    m0 *= -cs; m1 *= -cs;
    float l0 = 0, l1 = 0;
#pragma unroll
    for (int j = 0; j < 5; j++) {
        s[j][0] = ex2(fmaf(s[j][0], cs, m0)); s[j][1] = ex2(fmaf(s[j][1], cs, m0));
        s[j][2] = ex2(fmaf(s[j][2], cs, m1)); s[j][3] = ex2(fmaf(s[j][3], cs, m1));
        l0 += s[j][0] + s[j][1]; l1 += s[j][2] + s[j][3];
    }
    l0 += __shfl_xor_sync(0xffffffffu, l0, 1); l1 += __shfl_xor_sync(0xffffffffu, l1, 1);
    l0 += __shfl_xor_sync(0xffffffffu, l0, 2); l1 += __shfl_xor_sync(0xffffffffu, l1, 2);
    l0 = __fdividef(1.f, l0); l1 = __fdividef(1.f, l1);
    uint32_t p[10];
#pragma unroll
    for (int j = 0; j < 5; j++) { p[2 * j] = pack_bf16(s[j][0] * l0, s[j][1] * l0); p[2 * j + 1] = pack_bf16(s[j][2] * l1, s[j][3] * l1); }
    const uint32_t p0[4] = {p[0], p[1], p[2], p[3]}, p1[4] = {p[4], p[5], p[6], p[7]};
    mbar_wait(fullv, parv);
#pragma unroll
    for (int u4 = 0; u4 < 4; u4++) {
        uint32_t vm[4];
        ldsm4t(vm, sv + 8192 + u4 * 512 + lane * 16);
#pragma unroll
        for (int i = 0; i < 4; i++) {
            const int u = 4 * u4 + i;
            uint32_t b[4];
            ldsm4t(b, sv + u * 512 + lane * 16);
            float o[4];
            mma16z(o, p0, b[0], b[1]);
            if (hi) mma16(o, p1, b[2], b[3]);
            mma8(o, p[8], p[9], vm[i]);
            dst[(u >> 3) * 4096 + (u & 7) * 32] = pack_bf16(o[0], o[1]);
            dst[(u >> 3) * 4096 + (u & 7) * 32 + 256] = pack_bf16(o[2], o[3]);
        }
    }
}

template <int BN, int NKB, bool BLOCKED_A>
__device__ __forceinline__ void mainloop(float (&acc)[BN / 2], uint32_t sb, int wgi, uint32_t full, uint32_t empty, int& it, bool elect) {
#pragma unroll
    for (int j = 0; j < BN / 2; j++) acc[j] = 0.f;
#pragma unroll 1
    for (int k4 = 0; k4 < NKB; k4 += 4) {
#pragma unroll
        for (int st = 0; st < 4; st++, it++) {
            mbar_wait(full + 8 * st, (it >> 2) & 1);
            const uint64_t da = BLOCKED_A ? mkdesc(sb + st * G_STAGE + wgi * 8192, 128, 1024, 0) : mkdesc(sb + st * G_STAGE + wgi * 8192, 16, 1024, 1);
            const uint64_t db = mkdesc(sb + st * G_STAGE + 16384, 8192, 1024, 1);
            wg_fence();
#pragma unroll
            for (int k = 0; k < 4; k++) {
                if constexpr (BN == 256) wgmma256(acc, da + k * (BLOCKED_A ? 16 : 2), db + k * 128, 1);
                else wgmma128(acc, da + k * (BLOCKED_A ? 16 : 2), db + k * 128, 1);
            }
            wg_commit();
            if (k4 | st) {
                wg_wait<1>();
                if (elect) mbar_arrive(empty + 8 * ((st + 3) & 3));
            }
        }
    }
    wg_wait<0>();
    if (elect) mbar_arrive(empty + 8 * 3);
}

template <int BN>
__device__ __forceinline__ void o_item(uint32_t sb, int wgi, int wi, int lane, uint32_t full, uint32_t empty, int& it, const CUtensorMap* mout,
                                       int row0, int col0) {
    float acc[BN / 2];
    mainloop<BN, 64, true>(acc, sb, wgi, full, empty, it, lane == 0);
    const uint32_t stg = sb + G_STG + (wgi * 4 + wi) * 4096;
    const int r = lane & 15, cu = lane >> 4;
#pragma unroll
    for (int hf = 0; hf < BN / 128; hf++) {
        if (lane == 0) asm volatile("cp.async.bulk.wait_group.read 0;" ::: "memory");
        __syncwarp();
#pragma unroll
        for (int j = 0; j < 8; j++) {
            const float* a = acc + hf * 64 + j * 8;
            stsm4(stg + (j >> 2) * 2048 + r * 128 + ((((j & 3) * 2 + cu) ^ (r & 7)) << 4),
                  pack_bf16(a[0], a[1]), pack_bf16(a[2], a[3]), pack_bf16(a[4], a[5]), pack_bf16(a[6], a[7]));
        }
        asm volatile("fence.proxy.async.shared::cta;" ::: "memory");
        __syncwarp();
        if (lane == 0) {
            tma2d_store(mout, stg, col0 + hf * 128, row0 + wgi * 64 + wi * 16);
            tma2d_store(mout, stg + 2048, col0 + hf * 128 + 64, row0 + wgi * 64 + wi * 16);
            asm volatile("cp.async.bulk.commit_group;" ::: "memory");
        }
    }
}

constexpr int S4_KD = 32768;
constexpr int S4_CH = 2 * G_STAGE;
constexpr int S4_HALF = 2304;
constexpr int S4_WD = 2 * S4_HALF;
constexpr int S4_STRIDE = S4_WD + 2304 + 16;
__device__ __forceinline__ uint32_t addz(uint32_t x, uint32_t z) { uint32_t r; asm volatile("add.u32 %0, %1, %2;" : "=r"(r) : "r"(x), "r"(z)); return r; }
__device__ __forceinline__ uint32_t lds16(uint32_t a) { uint32_t v; asm volatile("ld.shared.u16 %0, [%1];" : "=r"(v) : "r"(a) : "memory"); return v; }
__device__ __forceinline__ uint32_t ldsu(uint32_t a) { return __float_as_uint(lds32(a)); }

template <int E0, int NE, int KP>
__device__ __forceinline__ void s4_windows(float (&acc)[8][2][4], uint32_t ut, uint32_t kd, int rho, int w, int lane, uint32_t z) {
    const int gt = (lane >> 2) - 2 * (lane & 3), p0 = rho == 16 ? -3 : -2, c = (lane >> 3) + p0;
    uint32_t band[2][4], tw[2 * NE + 1], ta[NE][4];
    {
        uint32_t f[5];
#pragma unroll
        for (int m = 0; m < 5; m++) {
            const int d = 8 * (p0 + m - 1) - gt + rho;
            f[m] = (abs(d) <= w ? 0x3F80u : 0u) | (abs(d + 1) <= w ? 0x3F800000u : 0u);
        }
#pragma unroll
        for (int j = 0; j < 2; j++) { band[j][0] = f[2 * j + 1]; band[j][1] = addz(f[2 * j], z); band[j][2] = f[2 * j + 2]; band[j][3] = addz(f[2 * j + 1], z); }
    }
#pragma unroll
    for (int m = 0; m < 2 * NE + 1; m++) {
        const int q = 8 * (2 * E0 - 1 + m) + gt;
        const uint32_t lo = lds16(kd + q * KP), hi = lds16(kd + (q - 1) * KP);
        tw[m] = ((unsigned)(q - 16 * E0) < 16 * E0 ? lo : 0u) | ((unsigned)(q - 1 - 16 * E0) < 16 * E0 ? hi << 16 : 0u);
    }
#pragma unroll
    for (int e = 0; e < NE; e++) { ta[e][0] = tw[2 * e + 1]; ta[e][1] = tw[2 * e + 2]; ta[e][2] = addz(tw[2 * e], z); ta[e][3] = addz(tw[2 * e + 1], z); }
    const uint32_t ua = ut + (c & 1) * S4_HALF + (16 + (lane & 7) + (c >> 1)) * 16;
#pragma unroll
    for (int J = 0; J < 8 - E0; J++) {
        uint32_t u0[4], u1[4];
        ldsm4(u0, ua + J * 256); ldsm4(u1, ua + J * 256 + 128);
        float s0[4], s1[4];
        mma16z(s0, band[0], u0[0], u0[1]); mma16z(s1, band[0], u1[0], u1[1]);
        mma16(s0, band[1], u0[2], u0[3]); mma16(s1, band[1], u1[2], u1[3]);
        const uint32_t b00 = pack_bf16(s0[0], s0[1]), b01 = pack_bf16(s1[0], s1[1]), b10 = pack_bf16(s0[2], s0[3]), b11 = pack_bf16(s1[2], s1[3]);
#pragma unroll
        for (int e = 0; e < NE; e++)
            if (J + E0 + e < 8) { mma16(acc[J + E0 + e][0], ta[e], b00, b01); mma16(acc[J + E0 + e][1], ta[e], b10, b11); }
    }
}
template <int D0, int D1>
__device__ __forceinline__ void s4_dense(float (&acc)[8][2][4], uint32_t ua, const uint32_t (&b0)[4], const uint32_t (&b1)[4]) {
#pragma unroll
    for (int J = 0; J < 8 - D0; J++) {
        uint32_t a[4];
        ldsm4(a, ua + J * 256);
        mma16(acc[J + D0][0], a, b0[0], b0[1]); mma16(acc[J + D0][1], a, b0[2], b0[3]);
        if (J + D1 < 8) { mma16(acc[J + D1][0], a, b1[0], b1[1]); mma16(acc[J + D1][1], a, b1[2], b1[3]); }
    }
}
__device__ __forceinline__ void s4_words(uint32_t (&b)[4], uint32_t wd) {
    asm volatile("ld.shared.u32 %0, [%4]; ld.shared.u32 %1, [%4+-32]; ld.shared.u32 %2, [%4+32]; ld.volatile.shared.u32 %3, [%4];"
        : "=r"(b[0]), "=r"(b[1]), "=r"(b[2]), "=r"(b[3]) : "r"(wd) : "memory");
}

__device__ __forceinline__ void s4_item(uint32_t sb, int cw, int lane, int item, const bf16* __restrict__ dsk, uint32_t empty, const CUtensorMap* my) {
    const int gt = (lane >> 2) - 2 * (lane & 3);
    const uint32_t ch = sb + S4_CH + cw * S4_STRIDE, kd = sb + S4_KD + cw * 1536;
    const __nv_bfloat162 dk = __bfloat162bfloat162(dsk[item * 8 + cw]);
    ST(item, cw, 0);
    asm volatile("st.shared.v4.u32 [%0], {%1,%1,%1,%1};" ::"r"(ch + (lane >> 4) * S4_HALF + (lane & 15) * 16), "r"(0) : "memory");
    const uint32_t tch = sb + S4_CH + (lane & 7) * S4_STRIDE + ((lane >> 3) & 1) * S4_HALF + (16 + 16 * cw + (lane >> 4)) * 16;
#pragma unroll
    for (int i = 0; i < 8; i++) {
        uint32_t x[4];
        ldsm4t(x, sb + cw * 4096 + i * 512 + lane * 16);
        stsm4(tch + i * 32, x[0], x[1], x[2], x[3]);
    }
#pragma unroll 1
    for (int x0 = lane * 2 - 16; x0 < 560; x0 += 64) {
        uint32_t k[3];
#pragma unroll
        for (int j = 0; j < 3; j++) {
            const int x = x0 + j - 1, idx = x < 256 ? max(x, 0) : min(128 + ((x + ((x >> 1) & 1)) >> 1), 384);
            k[j] = lds16(kd + idx * 2);
            if ((unsigned)x > 514u) k[j] = 0;
        }
        asm volatile("st.shared.v2.u32 [%0], {%1,%2};" ::"r"(ch + S4_WD + 64 + x0 * 4), "r"(k[1] | (k[0] << 16)), "r"(k[2] | (k[1] << 16)) : "memory");
    }
    const uint32_t k1024 = lds16(kd + 1024);
    bar_sync(2, 256);
    ST(item, cw, 1);
    const uint32_t z = ldsu(ch);
    float acc[8][2][4];
#pragma unroll
    for (int j = 0; j < 16; j++) acc[j >> 1][j & 1][0] = acc[j >> 1][j & 1][1] = acc[j >> 1][j & 1][2] = acc[j >> 1][j & 1][3] = 0.f;
#pragma unroll 1
    for (int r = 1; r <= 4; r++) s4_windows<2, 3, 8>(acc, ch, kd + 512 + 2 * r, 4 * r, 2 - (r & 1), lane, z);
    ST(item, cw, 2);
#pragma unroll 1
    for (int r = 1; r <= 2; r++) s4_windows<4, 4, 4>(acc, ch, kd + 768 + 2 * r, 8 * r, 2 + r, lane, z);
    ST(item, cw, 3);
    const uint32_t ua = ch + (lane >> 4) * S4_HALF + (16 + (lane & 15)) * 16, wd = ch + S4_WD + 64 + gt * 4;
#pragma unroll 1
    for (int q = 0; q < 2; q++) {
        uint32_t b0[4], b1[4];
        s4_words(b0, wd + (q + 32) * 64);
#pragma unroll
        for (int j = 0; j < 4; j++) {
            const int x = 16 * q + gt + (j == 1 ? -8 : j == 2 ? 8 : 0) - 3;
            b1[j] = addz(((unsigned)x < 2u ? k1024 : 0u) | ((unsigned)(x - 1) < 2u ? k1024 << 16 : 0u), z);
        }
        s4_dense<2, 4>(acc, ua - q * 16, b0, b1);
    }
    {
        uint32_t b0[4], b1[4], c0[4], c1[4];
        s4_words(b0, wd); s4_words(b1, wd + 1024);
#pragma unroll 1
        for (int q = 0; q < 16; q += 2) {
            s4_words(c0, wd + q * 64 + 64); s4_words(c1, wd + q * 64 + 64 + 1024);
            s4_dense<0, 1>(acc, ua - q * 16, b0, b1);
            s4_words(b0, wd + q * 64 + 128); s4_words(b1, wd + q * 64 + 128 + 1024);
            s4_dense<0, 1>(acc, ua - q * 16 - 16, c0, c1);
            if (q == 8 && lane == 0) { mbar_arrive(empty); mbar_arrive(empty + 8); }
        }
    }
    ST(item, cw, 4);
    if (lane == 0) asm volatile("cp.async.bulk.wait_group.read 0;" ::: "memory");
    __syncwarp();
#pragma unroll
    for (int I = 0; I < 8; I++) {
        uint32_t u[4];
        ldsm4(u, ua + I * 256);
#pragma unroll
        for (int j = 0; j < 4; j++) {
            const uint32_t y = pack_bf16(acc[I][j >> 1][2 * (j & 1)], acc[I][j >> 1][2 * (j & 1) + 1]);
            const __nv_bfloat162 r = __hadd2_rn(*(const __nv_bfloat162*)&y, __hmul2_rn(*(const __nv_bfloat162*)&u[j], dk));
            u[j] = *(const uint32_t*)&r;
        }
        stsm4(ua + I * 256, u[0], u[1], u[2], u[3]);
    }
    bar_sync(2, 256);
#pragma unroll
    for (int i = 0; i < 8; i++) {
        uint32_t y[4];
        ldsm4t(y, tch + i * 32);
        stsm4(sb + G_STG + cw * 4096 + i * 512 + lane * 16, y[0], y[1], y[2], y[3]);
    }
    asm volatile("fence.proxy.async.shared::cta;" ::: "memory");
    __syncwarp();
    if (lane == 0) {
        mbar_arrive(empty + 16); mbar_arrive(empty + 24);
        tma2d_store(my, sb + G_STG + cw * 4096, DM + item * 8, cw * 256);
        asm volatile("cp.async.bulk.commit_group;" ::: "memory");
    }
    ST(item, cw, 5);
}

__global__ void __launch_bounds__(384, 1)
worker_kernel(const __grid_constant__ CUtensorMap mx, const __grid_constant__ CUtensorMap mq, const __grid_constant__ CUtensorMap mk,
              const __grid_constant__ CUtensorMap mv, const __grid_constant__ CUtensorMap mo,
              const __grid_constant__ CUtensorMap mout, const __grid_constant__ CUtensorMap mu, const __grid_constant__ CUtensorMap my,
              const bf16* __restrict__ dsk) {
    extern __shared__ unsigned char smem_raw[];
    const uint32_t sb = (smem_u32(smem_raw) + 1023) & ~1023u;
    const uint32_t full = sb + G_BAR, empty = full + 32, ifull = full + 64, iempty = full + 80, islot = full + 96, sigbar = full + 112, sigslot = full + 120;
    const int tid = threadIdx.x, wg = tid >> 7, lane = tid & 31;
    if (tid == 0) {
        for (int i = 0; i < G_NST; i++) { mbar_init(full + 8 * i, 1); mbar_init(empty + 8 * i, 8); }
        for (int i = 0; i < 2; i++) { mbar_init(ifull + 8 * i, 1); mbar_init(iempty + 8 * i, 8); }
        mbar_init(sigbar, 8);
        asm volatile("fence.proxy.async;" ::: "memory");
    }
    __syncthreads();
    if (wg == 0) {
        reg_dec<40>();
        if (tid >= 32 && tid < 64) {
            for (int n = 0;; n++) {
                mbar_wait_long(sigbar, n & 1);
                int item; asm volatile("ld.shared.u32 %0, [%1];" : "=r"(item) : "r"(sigslot + 4 * (n & 1)) : "memory");
                const int type = item >> 16, b = (item >> 8) & 255, i = item & 255;
                if (type == IT_END) break;
                __threadfence();
                if (type == IT_KV) { if (lane < 6) atomicAdd(g_kvf + ((i & 15) * 6 + lane) * 16 + b, 1); }
                else if (lane == 0) atomicAdd(g_ctr + C_QA_DONE + b, 1);
            }
        } else if (tid < 32) {
            int it = 0;
            for (int n = 0;; n++) {
                int item = 0;
                if (lane == 0) {
                    const int q = (n == 0 && blockIdx.x < 32) ? blockIdx.x : 32 + atomicAdd(g_ctr + C_NEXT, 1);
                    item = queue_item(q);
                }
                item = __shfl_sync(0xffffffffu, item, 0);
                if (lane == 0) {
                    mbar_wait(iempty + 8 * (n & 1), ((n >> 1) & 1) ^ 1);
                    asm volatile("st.shared.u32 [%0], %1;" ::"r"(islot + 4 * (n & 1)), "r"(item) : "memory");
                    mbar_arrive(ifull + 8 * (n & 1));
                    const int type = item >> 16, b = (item >> 8) & 255, i = item & 255;
                    if (type == IT_QA || type == IT_KV) {
                        const CUtensorMap* mw = type == IT_QA ? &mq : i < 16 ? &mk : &mv;
                        for (int kb = 0; kb < 16; kb++, it++) {
                            const int st = it & 3;
                            mbar_wait(empty + 8 * st, ((it >> 2) & 1) ^ 1);
                            mbar_expect(full + 8 * st, G_STAGE);
                            const uint32_t a = sb + st * G_STAGE;
                            tma2d(a, &mx, kb * 64, b * 128, full + 8 * st);
                            tma3d(a + 16384, mw, 0, kb * 64, (i & 15) * 4, full + 8 * st);
                            tma3d(a + 32768, mw, 0, kb * 64, (i & 15) * 4 + 2, full + 8 * st);
                            if (type == IT_QA && kb >= 4 && kb < 12)
                                asm volatile("cp.async.bulk.prefetch.L2.global [%0], 16384;"
                                    ::"l"(((kb & 1) ? g_vx : g_kx) + (size_t)((b * 4 + ((kb - 4) >> 1)) * NH + i * 2) * 4096) : "memory");
                        }
                    }
                    if (type == IT_QA) {
                        wait_ctr(g_ctr + C_CHAIN + b, 96);
                        asm volatile("fence.proxy.async;" ::: "memory");
                        for (int st = 0; st < 4; st++, it++) {
                            mbar_wait(empty + 8 * st, ((it >> 2) & 1) ^ 1);
                            mbar_expect(full + 8 * st, 4 * 10240);
                            for (int sg = 0; sg < 4; sg++) {
                                const int sh = (b * 4 + sg) * NH + i * 2 + (st >> 1);
                                bulk_load(sb + st * G_STAGE + sg * 10240, ((st & 1) ? g_vx : g_kx) + (size_t)sh * 4096, 8192, full + 8 * st);
                                bulk_load(sb + st * G_STAGE + sg * 10240 + 8192, ((st & 1) ? g_vm : g_km) + (size_t)sh * 1024, 2048, full + 8 * st);
                            }
                        }
                    } else if (type == IT_O) {
                        const bool wide = b < O_WIDE;
                        wait_ctr(g_ctr + C_QA_DONE + b, 16);
                        asm volatile("fence.proxy.async;" ::: "memory");
                        for (int kb = 0; kb < 64; kb++, it++) {
                            const int st = it & 3;
                            mbar_wait(empty + 8 * st, ((it >> 2) & 1) ^ 1);
                            mbar_expect(full + 8 * st, wide ? G_STAGE : 32768);
                            const uint32_t a = sb + st * G_STAGE;
                            bulk_load(a, g_ox + (size_t)(b * 64 + kb) * 8192, 16384, full + 8 * st);
                            tma3d(a + 16384, &mo, 0, kb * 64, wide ? i * 4 : i * 2, full + 8 * st);
                            if (wide) tma3d(a + 32768, &mo, 0, kb * 64, i * 4 + 2, full + 8 * st);
                        }
                    } else if (type == IT_S4) {
                        wait_ctr(g_ctr + C_CHAIN, 96);
                        asm volatile("fence.proxy.async;" ::: "memory");
                        mbar_wait(empty, ((it >> 2) & 1) ^ 1);
                        mbar_expect(full, 32768 + 12288);
                        bulk_load(sb + S4_KD, g_kd + i * 8 * 768, 12288, full);
                        for (int j = 0; j < 8; j++) tma2d(sb + j * 4096, &mu, i * 8, j * 256, full);
                        for (int st = 1; st < 4; st++) { mbar_wait(empty + 8 * st, ((it >> 2) & 1) ^ 1); mbar_arrive(full + 8 * st); }
                        it += 4;
                        mbar_wait_long(empty, ((it >> 2) & 1) ^ 1);
                    }
                }
                __syncwarp();
                if (item >> 16 == IT_END) break;
            }
            asm volatile("griddepcontrol.wait;" ::: "memory");
        }
    } else {
        reg_inc<232>();
        const int wu = __shfl_sync(0xffffffffu, tid >> 5, 0);
        const int wgi = (wu >> 2) - 1, wi = wu & 3;
        int it = 0, nsig = 0, n = 0, item;
        auto next_item = [&]() {
            mbar_wait_long(ifull + 8 * (n & 1), (n >> 1) & 1);
            asm volatile("ld.shared.u32 %0, [%1];" : "=r"(item) : "r"(islot + 4 * (n & 1)) : "memory");
            __syncwarp();
            if (lane == 0) mbar_arrive(iempty + 8 * (n & 1));
        };
        auto signal = [&](int what) {
            if (tid == 128) asm volatile("st.shared.u32 [%0], %1;" ::"r"(sigslot + 4 * (nsig & 1)), "r"(what) : "memory");
            __syncwarp();
            if (lane == 0) mbar_arrive(sigbar);
            nsig++;
        };
        next_item();
        if (item >> 16 == IT_KV) {
            float acc[128];
            uint32_t pk[64];
            uint32_t* dst = nullptr;
            int prev = 0;
            do {
                WLOG(0);
#pragma unroll
                for (int kb = 0; kb < 16; kb++, it++) {
                    const int st = kb & 3;
                    mbar_wait(full + 8 * st, (it >> 2) & 1);
                    const uint64_t da = mkdesc(sb + st * G_STAGE + wgi * 8192, 16, 1024, 1);
                    const uint64_t db = mkdesc(sb + st * G_STAGE + 16384, 8192, 1024, 1);
                    wg_fence();
#pragma unroll
                    for (int k = 0; k < 4; k++) wgmma256(acc, da + k * 2, db + k * 128, kb | k);
                    wg_commit();
                    if (kb < 4 && dst) {
#pragma unroll
                        for (int j = 0; j < 16; j++) dst[(kb * 8 + (j >> 1)) * 128 + (j & 1) * 32] = pk[kb * 16 + j];
                        if (kb == 3) signal(prev);
                    }
                    if (kb > 0) {
                        wg_wait<1>();
                        if (lane == 0) mbar_arrive(empty + 8 * ((kb - 1) & 3));
                    }
                }
                wg_wait<0>();
                if (lane == 0) mbar_arrive(empty + 8 * 3);
#pragma unroll
                for (int j = 0; j < 64; j++) pk[j] = pack_bf16(acc[2 * j], acc[2 * j + 1]);
                const int row = ((item >> 8) & 255) * 128 + wgi * 64 + wi * 16, nt = item & 255;
                dst = (uint32_t*)(nt < 16 ? g_kx : g_vx) + (size_t)((row >> 5) * 512 + (nt & 15) * 32) * 128 + (row & 31) * 4 + lane;
                prev = item;
                if (n == 0) {
#pragma unroll
                    for (int j = 0; j < 64; j++) dst[(j >> 1) * 128 + (j & 1) * 32] = pk[j];
                    signal(prev);
                    dst = nullptr;
                }
                WLOG(1);
                n++;
                next_item();
            } while (item >> 16 == IT_KV);
            if (dst) {
#pragma unroll
                for (int j = 0; j < 64; j++) dst[(j >> 1) * 128 + (j & 1) * 32] = pk[j];
                signal(prev);
            }
        }
        for (;; n++, next_item()) {
            const int type = item >> 16, b = (item >> 8) & 255, i = item & 255;
            WLOG(0);
            if (type == IT_QA) {
                float acc[128];
                const int sid = 128 + (b & 7) * 16 + i, cw = wgi * 4 + wi;
                ST(sid, cw, 0);
                ST(sid, cw, 1);
                mainloop<256, 16, false>(acc, sb, wgi, full, empty, it, lane == 0);
                ST(sid, cw, 2);
                uint32_t q0[32], q1[32];
#pragma unroll
                for (int j = 0; j < 32; j++) { q0[j] = pack_bf16(acc[2 * j], acc[2 * j + 1]); q1[j] = pack_bf16(acc[64 + 2 * j], acc[65 + 2 * j]); }
                const uint32_t par = (it >> 2) & 1, so = (wgi * 2 + (wi >> 1)) * 10240;
                uint32_t* dst = (uint32_t*)g_ox + (size_t)(b * 64 + i * 4) * 4096 + (wgi * 8 + wi * 2) * 256 + lane;
                mbar_wait_long(full, par);
                ST(sid, cw, 3);
                attn_head(q0, sb + so, sb + G_STAGE + so, full + 8, par, empty, wi, lane, dst);
                __syncwarp();
                if (lane == 0) mbar_arrive(empty + 8);
                ST(sid, cw, 4);
                mbar_wait(full + 16, par);
                ST(sid, cw, 5);
                attn_head(q1, sb + 2 * G_STAGE + so, sb + 3 * G_STAGE + so, full + 24, par, empty + 16, wi, lane, dst + 2 * 4096);
                __syncwarp();
                if (lane == 0) mbar_arrive(empty + 24);
                ST(sid, cw, 6);
                signal(item);
                it += 4;
            } else if (type == IT_O) {
                mbar_wait_long(full, (it >> 2) & 1);
                if (b < O_WIDE) o_item<256>(sb, wgi, wi, lane, full, empty, it, &mout, b * 128, i * 256);
                else o_item<128>(sb, wgi, wi, lane, full, empty, it, &mout, b * 128, i * 128);
            } else if (type == IT_S4) {
                mbar_wait_long(full, (it >> 2) & 1);
                mbar_wait(full + 24, (it >> 2) & 1);
                s4_item(sb, wgi * 4 + wi, lane, i, dsk, empty, &my);
                it += 4;
            } else break;
            WLOG(1);
        }
        bar_sync(2, 256);
        signal(item);
        if (lane == 0) asm volatile("cp.async.bulk.wait_group 0;" ::: "memory");
    }
}

typedef CUresult (*EncodeFn)(CUtensorMap*, CUtensorMapDataType, cuuint32_t, void*, const cuuint64_t*, const cuuint64_t*, const cuuint32_t*,
                             const cuuint32_t*, CUtensorMapInterleave, CUtensorMapSwizzle, CUtensorMapL2promotion, CUtensorMapFloatOOBfill);
static EncodeFn get_encode() {
    void* fn = nullptr; cudaDriverEntryPointQueryResult st;
    cudaGetDriverEntryPoint("cuTensorMapEncodeTiled", &fn, cudaEnableDefault, &st);
    return (EncodeFn)fn;
}
static void map_act(EncodeFn enc, CUtensorMap* m, const void* p, int rows, int cols, int boxr) {
    cuuint64_t dim[2] = {(cuuint64_t)cols, (cuuint64_t)rows}, str[1] = {(cuuint64_t)cols * 2};
    cuuint32_t box[2] = {64, (cuuint32_t)boxr}, es[2] = {1, 1};
    enc(m, CU_TENSOR_MAP_DATA_TYPE_BFLOAT16, 2, (void*)p, dim, str, box, es, CU_TENSOR_MAP_INTERLEAVE_NONE, CU_TENSOR_MAP_SWIZZLE_128B,
        CU_TENSOR_MAP_L2_PROMOTION_L2_128B, CU_TENSOR_MAP_FLOAT_OOB_FILL_NONE);
}
static void map_w(EncodeFn enc, CUtensorMap* m, const void* p, int k, int n) {
    cuuint64_t dim[3] = {64, (cuuint64_t)k, (cuuint64_t)n / 64}, str[2] = {(cuuint64_t)n * 2, 128};
    cuuint32_t box[3] = {64, 64, 2}, es[3] = {1, 1, 1};
    enc(m, CU_TENSOR_MAP_DATA_TYPE_BFLOAT16, 3, (void*)p, dim, str, box, es, CU_TENSOR_MAP_INTERLEAVE_NONE, CU_TENSOR_MAP_SWIZZLE_128B,
        CU_TENSOR_MAP_L2_PROMOTION_L2_256B, CU_TENSOR_MAP_FLOAT_OOB_FILL_NONE);
}

static void map_box(EncodeFn enc, CUtensorMap* m, const void* p, int rows, int ld, int boxc, int boxr, CUtensorMapSwizzle sw) {
    cuuint64_t dim[2] = {(cuuint64_t)ld, (cuuint64_t)rows}, str[1] = {(cuuint64_t)ld * 2};
    cuuint32_t box[2] = {(cuuint32_t)boxc, (cuuint32_t)boxr}, es[2] = {1, 1};
    enc(m, CU_TENSOR_MAP_DATA_TYPE_BFLOAT16, 2, (void*)p, dim, str, box, es, CU_TENSOR_MAP_INTERLEAVE_NONE, sw,
        CU_TENSOR_MAP_L2_PROMOTION_NONE, CU_TENSOR_MAP_FLOAT_OOB_FILL_NONE);
}

extern "C" void kernel_launch(void* const* d_in, const int* in_sizes, int n_in, void* d_out, int out_size) {
    const bf16* x = (const bf16*)d_in[0];
    const bf16* mem0 = (const bf16*)d_in[1];
    const bf16 *Wq = (const bf16*)d_in[2], *Wk = (const bf16*)d_in[3], *Wv = (const bf16*)d_in[4], *Wo = (const bf16*)d_in[5];
    static EncodeFn enc = nullptr;
    static int nsm = 0;
    if (!enc) {
        enc = get_encode();
        cudaDeviceGetAttribute(&nsm, cudaDevAttrMultiProcessorCount, 0);
        cudaFuncSetAttribute(chain_kernel, cudaFuncAttributeMaxDynamicSharedMemorySize, CH_SMEM);
        cudaFuncSetAttribute(worker_kernel, cudaFuncAttributeMaxDynamicSharedMemorySize, G_SMEM);
    }
    CUtensorMap mx, mq, mk, mv, mo, mout, mu, my;
    map_act(enc, &mx, x, S_LEN, DM, 128);
    map_w(enc, &mq, Wq, DM, HD); map_w(enc, &mk, Wk, DM, HD); map_w(enc, &mv, Wv, DM, HD); map_w(enc, &mo, Wo, HD, DM);
    map_box(enc, &mout, d_out, S_LEN, 2 * DM, 64, 16, CU_TENSOR_MAP_SWIZZLE_128B);
    map_box(enc, &mu, d_in[7], S_LEN, DM, 8, 256, CU_TENSOR_MAP_SWIZZLE_NONE);
    map_box(enc, &my, d_out, S_LEN, 2 * DM, 8, 256, CU_TENSOR_MAP_SWIZZLE_NONE);
    CUtensorMap cq, ck, cv, co;
    map_box(enc, &cq, Wq, DM, HD, 32, 32, CU_TENSOR_MAP_SWIZZLE_64B); map_box(enc, &ck, Wk, DM, HD, 32, 32, CU_TENSOR_MAP_SWIZZLE_64B);
    map_box(enc, &cv, Wv, DM, HD, 32, 32, CU_TENSOR_MAP_SWIZZLE_64B); map_box(enc, &co, Wo, HD, DM, 32, 16, CU_TENSOR_MAP_SWIZZLE_64B);
    S4Params P = {(const bf16*)d_in[8], (const bf16*)d_in[9], (const bf16*)d_in[10], (const bf16*)d_in[11],
                  (const bf16*)d_in[12], (const bf16*)d_in[13], (const bf16*)d_in[14], (const bf16*)d_in[15]};
    int aware = 1;
    cudaLaunchAttribute at[1];
    at[0].id = cudaLaunchAttributeProgrammaticStreamSerialization;
    at[0].val.programmaticStreamSerializationAllowed = 1;
    cudaLaunchConfig_t cfg = {};
    cfg.stream = cudaStreamPerThread;
    cfg.gridDim = dim3(96); cfg.blockDim = dim3(CH_THREADS); cfg.dynamicSmemBytes = CH_SMEM;
    cudaLaunchKernelEx(&cfg, chain_kernel, cq, ck, cv, co, Wq, Wk, Wv, mem0, P, aware);
    cfg.attrs = at; cfg.numAttrs = 1;
    cfg.gridDim = dim3(nsm); cfg.blockDim = dim3(384); cfg.dynamicSmemBytes = G_SMEM;
    cudaLaunchKernelEx(&cfg, worker_kernel, mx, mq, mk, mv, mo, mout, mu, my, P.dsk);
}
```

```cpp
#include <cuda.h>
#include <cuda_runtime.h>
#include <cuda_bf16.h>
#include <stdint.h>
#include <stdio.h>
#include <string.h>

typedef __nv_bfloat16 bf16;

constexpr int S_LEN = 2048, DM = 1024, NH = 32, DH = 128, HD = 4096, NSEG = 64;
constexpr uint32_t SENT = 0xFFFFFFFFu;
constexpr int SPIN_LIMIT = 1 << 18;
#define REALL 0

__device__ __align__(1024) bf16 g_kx[S_LEN * HD];
__device__ __align__(1024) bf16 g_vx[S_LEN * HD];
__device__ __align__(1024) bf16 g_ox[S_LEN * HD];
__device__ __align__(1024) bf16 g_km[NSEG * NH * 8 * DH];
__device__ __align__(1024) bf16 g_vm[NSEG * NH * 8 * DH];
__device__ __align__(1024) bf16 g_kd[DM * 768 + 8192];
__device__ __align__(1024) char g_ring[2 << 20];
__device__ int g_kvf[96 * 16];
constexpr int C_NEXT = 0, C_CHAIN = 32, C_QA_DONE = 64, N_CTR = 96;
__device__ int g_ctr[N_CTR];

__device__ __forceinline__ uint32_t smem_u32(const void* p) { return (uint32_t)__cvta_generic_to_shared(p); }
__device__ __forceinline__ uint32_t clk() { uint32_t c; asm volatile("mov.u32 %0, %%clock;" : "=r"(c)::"memory"); return c; }
__device__ __forceinline__ uint32_t pack_bf16(float lo, float hi) {
    uint32_t r; asm("cvt.rn.bf16x2.f32 %0, %1, %2;" : "=r"(r) : "f"(hi), "f"(lo)); return r;
}
__device__ __forceinline__ uint32_t movm(uint32_t a) {
    uint32_t d; asm volatile("movmatrix.sync.aligned.m8n8.trans.b16 %0, %1;" : "=r"(d) : "r"(a)); return d;
}
__device__ __forceinline__ void mma16(float (&d)[4], const uint32_t (&a)[4], uint32_t b0, uint32_t b1) {
    asm volatile("mma.sync.aligned.m16n8k16.row.col.f32.bf16.bf16.f32 {%0,%1,%2,%3}, {%4,%5,%6,%7}, {%8,%9}, {%0,%1,%2,%3};"
        : "+f"(d[0]), "+f"(d[1]), "+f"(d[2]), "+f"(d[3]) : "r"(a[0]), "r"(a[1]), "r"(a[2]), "r"(a[3]), "r"(b0), "r"(b1));
}
__device__ __forceinline__ void mma16z(float (&d)[4], const uint32_t (&a)[4], uint32_t b0, uint32_t b1) {
    asm volatile("mma.sync.aligned.m16n8k16.row.col.f32.bf16.bf16.f32 {%0,%1,%2,%3}, {%4,%5,%6,%7}, {%8,%9}, {%10,%10,%10,%10};"
        : "=f"(d[0]), "=f"(d[1]), "=f"(d[2]), "=f"(d[3]) : "r"(a[0]), "r"(a[1]), "r"(a[2]), "r"(a[3]), "r"(b0), "r"(b1), "f"(0.f));
}
__device__ __forceinline__ void mma8z(float (&d)[4], uint32_t a0, uint32_t a1, uint32_t b0) {
    asm volatile("mma.sync.aligned.m16n8k8.row.col.f32.bf16.bf16.f32 {%0,%1,%2,%3}, {%4,%5}, {%6}, {%7,%7,%7,%7};"
        : "=f"(d[0]), "=f"(d[1]), "=f"(d[2]), "=f"(d[3]) : "r"(a0), "r"(a1), "r"(b0), "f"(0.f));
}
__device__ __forceinline__ void ldsm4t(uint32_t (&r)[4], uint32_t addr) {
    asm volatile("ldmatrix.sync.aligned.m8n8.x4.trans.shared.b16 {%0,%1,%2,%3}, [%4];"
        : "=r"(r[0]), "=r"(r[1]), "=r"(r[2]), "=r"(r[3]) : "r"(addr) : "memory");
}
__device__ __forceinline__ void ldsm4(uint32_t (&r)[4], uint32_t addr) {
    asm volatile("ldmatrix.sync.aligned.m8n8.x4.shared.b16 {%0,%1,%2,%3}, [%4];"
        : "=r"(r[0]), "=r"(r[1]), "=r"(r[2]), "=r"(r[3]) : "r"(addr) : "memory");
}
__device__ __forceinline__ float lds32(uint32_t a) {
    float v; asm volatile("ld.shared.f32 %0, [%1];" : "=f"(v) : "r"(a) : "memory"); return v;
}
__device__ __forceinline__ void st_async1(uint32_t dst, float v, uint32_t bar) {
    asm volatile("st.async.shared::cluster.mbarrier::complete_tx::bytes.f32 [%0], %1, [%2];" ::"r"(dst), "f"(v), "r"(bar) : "memory");
}
__device__ __forceinline__ void cp16(uint32_t dst, const void* src) {
    asm volatile("cp.async.cg.shared.global [%0], [%1], 16;" ::"r"(dst), "l"(src) : "memory");
}
__device__ __forceinline__ void sts128(uint32_t a, const float (&v)[4]) {
    asm volatile("st.shared.v4.f32 [%0], {%1,%2,%3,%4};" ::"r"(a), "f"(v[0]), "f"(v[1]), "f"(v[2]), "f"(v[3]) : "memory");
}
__device__ __forceinline__ float4 lds128(uint32_t a) {
    float4 v; asm volatile("ld.shared.v4.f32 {%0,%1,%2,%3}, [%4];" : "=f"(v.x), "=f"(v.y), "=f"(v.z), "=f"(v.w) : "r"(a) : "memory"); return v;
}
__device__ __forceinline__ void sts64(uint32_t a, float x, float y) {
    asm volatile("st.shared.v2.f32 [%0], {%1,%2};" ::"r"(a), "f"(x), "f"(y) : "memory");
}
__device__ __forceinline__ float2 lds64(uint32_t a) {
    float2 v; asm volatile("ld.shared.v2.f32 {%0,%1}, [%2];" : "=f"(v.x), "=f"(v.y) : "r"(a) : "memory"); return v;
}
__device__ __forceinline__ void bar_sync(int id, int n) { asm volatile("bar.sync %0, %1;" ::"r"(id), "r"(n) : "memory"); }
__device__ __forceinline__ void bar_arrive(int id, int n) { asm volatile("bar.arrive %0, %1;" ::"r"(id), "r"(n) : "memory"); }
__device__ __forceinline__ uint32_t mapa(uint32_t a, uint32_t r) {
    uint32_t o; asm("mapa.shared::cluster.u32 %0, %1, %2;" : "=r"(o) : "r"(a), "r"(r)); return o;
}
__device__ __forceinline__ void st_async4(uint32_t dst, float4 v, uint32_t bar) {
    asm volatile("st.async.shared::cluster.mbarrier::complete_tx::bytes.v4.f32 [%0], {%1,%2,%3,%4}, [%5];"
        ::"r"(dst), "f"(v.x), "f"(v.y), "f"(v.z), "f"(v.w), "r"(bar) : "memory");
}
__device__ __forceinline__ void mbar_init(uint32_t bar, int n) { asm volatile("mbarrier.init.shared.b64 [%0], %1;" ::"r"(bar), "r"(n) : "memory"); }
__device__ __forceinline__ void mbar_expect(uint32_t bar, int bytes) {
    asm volatile("mbarrier.arrive.expect_tx.shared.b64 _, [%0], %1;" ::"r"(bar), "r"(bytes) : "memory");
}
__device__ __forceinline__ void bulk_load(uint32_t dst, const void* src, int bytes, uint32_t bar) {
    asm volatile("cp.async.bulk.shared::cluster.global.mbarrier::complete_tx::bytes [%0], [%1], %2, [%3];"
        ::"r"(dst), "l"(src), "r"(bytes), "r"(bar) : "memory");
}
__device__ __forceinline__ bool mbar_try(uint32_t bar, uint32_t par) {
    uint32_t ok;
    asm volatile("{.reg .pred p; mbarrier.try_wait.parity.shared::cta.b64 p, [%1], %2; selp.u32 %0, 1, 0, p;}"
        : "=r"(ok) : "r"(bar), "r"(par) : "memory");
    return ok;
}
__device__ __forceinline__ bool mbar_test(uint32_t bar, uint32_t par) {
    uint32_t ok;
    asm volatile("{.reg .pred p; mbarrier.test_wait.parity.shared::cta.b64 p, [%1], %2; selp.u32 %0, 1, 0, p;}"
        : "=r"(ok) : "r"(bar), "r"(par) : "memory");
    return ok;
}
__device__ __forceinline__ int ld_acq(const int* p) { int v; asm volatile("ld.acquire.gpu.global.s32 %0, [%1];" : "=r"(v) : "l"(p) : "memory"); return v; }
__device__ __forceinline__ void wait_ctr(const int* p, int n) {
    for (int it = 0; it < (1 << 20) && ld_acq(p) < n; it++) __nanosleep(64);
}
__device__ __forceinline__ void mbar_wait(uint32_t bar, uint32_t par) {
    if (!mbar_try(bar, par))
        for (int it = 0; it < SPIN_LIMIT && !mbar_try(bar, par); it++) {}
}
__device__ __forceinline__ void mbar_wait_long(uint32_t bar, uint32_t par) {
    for (int it = 0; it < (1 << 24) && !mbar_try(bar, par); it++) {}
}
__device__ __forceinline__ float4 add4(float4 a, float4 b) { return make_float4(a.x + b.x, a.y + b.y, a.z + b.z, a.w + b.w); }
__device__ __forceinline__ float ex2(float x) { float y; asm("ex2.approx.ftz.f32 %0, %1;" : "=f"(y) : "f"(x)); return y; }

__device__ __forceinline__ void wgmma256(float (&d)[128], uint64_t da, uint64_t db, int acc) {
    asm volatile("{.reg .pred p; setp.ne.b32 p, %130, 0;\n"
        "wgmma.mma_async.sync.aligned.m64n256k16.f32.bf16.bf16 {"
        "%0,%1,%2,%3,%4,%5,%6,%7,%8,%9,%10,%11,%12,%13,%14,%15,"
        "%16,%17,%18,%19,%20,%21,%22,%23,%24,%25,%26,%27,%28,%29,%30,%31,"
        "%32,%33,%34,%35,%36,%37,%38,%39,%40,%41,%42,%43,%44,%45,%46,%47,"
        "%48,%49,%50,%51,%52,%53,%54,%55,%56,%57,%58,%59,%60,%61,%62,%63,"
        "%64,%65,%66,%67,%68,%69,%70,%71,%72,%73,%74,%75,%76,%77,%78,%79,"
        "%80,%81,%82,%83,%84,%85,%86,%87,%88,%89,%90,%91,%92,%93,%94,%95,"
        "%96,%97,%98,%99,%100,%101,%102,%103,%104,%105,%106,%107,%108,%109,%110,%111,"
        "%112,%113,%114,%115,%116,%117,%118,%119,%120,%121,%122,%123,%124,%125,%126,%127"
        "}, %128, %129, p, 1, 1, 0, 1;}"
        : "+f"(d[0]), "+f"(d[1]), "+f"(d[2]), "+f"(d[3]), "+f"(d[4]), "+f"(d[5]), "+f"(d[6]), "+f"(d[7]), "+f"(d[8]), "+f"(d[9]), "+f"(d[10]), "+f"(d[11]), "+f"(d[12]), "+f"(d[13]), "+f"(d[14]), "+f"(d[15]), "+f"(d[16]), "+f"(d[17]), "+f"(d[18]), "+f"(d[19]), "+f"(d[20]), "+f"(d[21]), "+f"(d[22]), "+f"(d[23]), "+f"(d[24]), "+f"(d[25]), "+f"(d[26]), "+f"(d[27]), "+f"(d[28]), "+f"(d[29]), "+f"(d[30]), "+f"(d[31]), "+f"(d[32]), "+f"(d[33]), "+f"(d[34]), "+f"(d[35]), "+f"(d[36]), "+f"(d[37]), "+f"(d[38]), "+f"(d[39]), "+f"(d[40]), "+f"(d[41]), "+f"(d[42]), "+f"(d[43]), "+f"(d[44]), "+f"(d[45]), "+f"(d[46]), "+f"(d[47]), "+f"(d[48]), "+f"(d[49]), "+f"(d[50]), "+f"(d[51]), "+f"(d[52]), "+f"(d[53]), "+f"(d[54]), "+f"(d[55]), "+f"(d[56]), "+f"(d[57]), "+f"(d[58]), "+f"(d[59]), "+f"(d[60]), "+f"(d[61]), "+f"(d[62]), "+f"(d[63]), "+f"(d[64]), "+f"(d[65]), "+f"(d[66]), "+f"(d[67]), "+f"(d[68]), "+f"(d[69]), "+f"(d[70]), "+f"(d[71]), "+f"(d[72]), "+f"(d[73]), "+f"(d[74]), "+f"(d[75]), "+f"(d[76]), "+f"(d[77]), "+f"(d[78]), "+f"(d[79]), "+f"(d[80]), "+f"(d[81]), "+f"(d[82]), "+f"(d[83]), "+f"(d[84]), "+f"(d[85]), "+f"(d[86]), "+f"(d[87]), "+f"(d[88]), "+f"(d[89]), "+f"(d[90]), "+f"(d[91]), "+f"(d[92]), "+f"(d[93]), "+f"(d[94]), "+f"(d[95]), "+f"(d[96]), "+f"(d[97]), "+f"(d[98]), "+f"(d[99]), "+f"(d[100]), "+f"(d[101]), "+f"(d[102]), "+f"(d[103]), "+f"(d[104]), "+f"(d[105]), "+f"(d[106]), "+f"(d[107]), "+f"(d[108]), "+f"(d[109]), "+f"(d[110]), "+f"(d[111]), "+f"(d[112]), "+f"(d[113]), "+f"(d[114]), "+f"(d[115]), "+f"(d[116]), "+f"(d[117]), "+f"(d[118]), "+f"(d[119]), "+f"(d[120]), "+f"(d[121]), "+f"(d[122]), "+f"(d[123]), "+f"(d[124]), "+f"(d[125]), "+f"(d[126]), "+f"(d[127])
        : "l"(da), "l"(db), "r"(acc));
}
__device__ __forceinline__ void wgmma128(float (&d)[64], uint64_t da, uint64_t db, int acc) {
    asm volatile("{.reg .pred p; setp.ne.b32 p, %66, 0;\n"
        "wgmma.mma_async.sync.aligned.m64n128k16.f32.bf16.bf16 {"
        "%0,%1,%2,%3,%4,%5,%6,%7,%8,%9,%10,%11,%12,%13,%14,%15,"
        "%16,%17,%18,%19,%20,%21,%22,%23,%24,%25,%26,%27,%28,%29,%30,%31,"
        "%32,%33,%34,%35,%36,%37,%38,%39,%40,%41,%42,%43,%44,%45,%46,%47,"
        "%48,%49,%50,%51,%52,%53,%54,%55,%56,%57,%58,%59,%60,%61,%62,%63"
        "}, %64, %65, p, 1, 1, 0, 1;}"
        : "+f"(d[0]), "+f"(d[1]), "+f"(d[2]), "+f"(d[3]), "+f"(d[4]), "+f"(d[5]), "+f"(d[6]), "+f"(d[7]), "+f"(d[8]), "+f"(d[9]), "+f"(d[10]), "+f"(d[11]), "+f"(d[12]), "+f"(d[13]), "+f"(d[14]), "+f"(d[15]), "+f"(d[16]), "+f"(d[17]), "+f"(d[18]), "+f"(d[19]), "+f"(d[20]), "+f"(d[21]), "+f"(d[22]), "+f"(d[23]), "+f"(d[24]), "+f"(d[25]), "+f"(d[26]), "+f"(d[27]), "+f"(d[28]), "+f"(d[29]), "+f"(d[30]), "+f"(d[31]), "+f"(d[32]), "+f"(d[33]), "+f"(d[34]), "+f"(d[35]), "+f"(d[36]), "+f"(d[37]), "+f"(d[38]), "+f"(d[39]), "+f"(d[40]), "+f"(d[41]), "+f"(d[42]), "+f"(d[43]), "+f"(d[44]), "+f"(d[45]), "+f"(d[46]), "+f"(d[47]), "+f"(d[48]), "+f"(d[49]), "+f"(d[50]), "+f"(d[51]), "+f"(d[52]), "+f"(d[53]), "+f"(d[54]), "+f"(d[55]), "+f"(d[56]), "+f"(d[57]), "+f"(d[58]), "+f"(d[59]), "+f"(d[60]), "+f"(d[61]), "+f"(d[62]), "+f"(d[63])
        : "l"(da), "l"(db), "r"(acc));
}
__device__ __forceinline__ void wg_fence() { asm volatile("wgmma.fence.sync.aligned;" ::: "memory"); }
__device__ __forceinline__ void wg_commit() { asm volatile("wgmma.commit_group.sync.aligned;" ::: "memory"); }
template <int N> __device__ __forceinline__ void wg_wait() { asm volatile("wgmma.wait_group.sync.aligned %0;" ::"n"(N) : "memory"); }
__device__ __forceinline__ uint64_t mkdesc(uint32_t addr, uint32_t lbo, uint32_t sbo, uint32_t sw) {
    return (uint64_t)((addr & 0x3FFFF) >> 4) | ((uint64_t)(lbo >> 4) << 16) | ((uint64_t)(sbo >> 4) << 32) | ((uint64_t)sw << 62);
}
__device__ __forceinline__ void tma2d(uint32_t dst, const CUtensorMap* m, int c0, int c1, uint32_t bar) {
    asm volatile("cp.async.bulk.tensor.2d.shared::cluster.global.mbarrier::complete_tx::bytes [%0], [%1, {%2, %3}], [%4];"
        ::"r"(dst), "l"(m), "r"(c0), "r"(c1), "r"(bar) : "memory");
}
__device__ __forceinline__ void tma3d(uint32_t dst, const CUtensorMap* m, int c0, int c1, int c2, uint32_t bar) {
    asm volatile("cp.async.bulk.tensor.3d.shared::cluster.global.mbarrier::complete_tx::bytes [%0], [%1, {%2, %3, %4}], [%5];"
        ::"r"(dst), "l"(m), "r"(c0), "r"(c1), "r"(c2), "r"(bar) : "memory");
}
__device__ __forceinline__ void tma3d_mc(uint32_t dst, const CUtensorMap* m, int c0, int c1, int c2, uint32_t bar, uint16_t mask) {
    asm volatile("cp.async.bulk.tensor.3d.shared::cluster.global.mbarrier::complete_tx::bytes.multicast::cluster [%0], [%1, {%2, %3, %4}], [%5], %6;"
        ::"r"(dst), "l"(m), "r"(c0), "r"(c1), "r"(c2), "r"(bar), "h"(mask) : "memory");
}
__device__ __forceinline__ void mbar_arrive(uint32_t bar) { asm volatile("mbarrier.arrive.shared.b64 _, [%0];" ::"r"(bar) : "memory"); }
__device__ __forceinline__ void mbar_arrive_remote(uint32_t bar) {
    asm volatile("mbarrier.arrive.shared::cluster.b64 _, [%0];" ::"r"(bar) : "memory");
}
template <int R> __device__ __forceinline__ void reg_inc() { asm volatile("setmaxnreg.inc.sync.aligned.u32 %0;" ::"n"(R)); }
template <int R> __device__ __forceinline__ void reg_dec() { asm volatile("setmaxnreg.dec.sync.aligned.u32 %0;" ::"n"(R)); }

constexpr int CH_NRES = 50;
constexpr int CH_WREG = CH_NRES * 512;
constexpr int CH_PART = 8 * CH_WREG;
constexpr int CH_SX = CH_PART + 16384;
constexpr int CH_MX = CH_SX + 3 * 1280;
constexpr int CH_XS = CH_MX + 3 * 512;
constexpr int CH_BAR = CH_XS + 5632;
constexpr int CH_SMEM = CH_BAR + 192;
constexpr int CH_THREADS = 384;

__device__ __forceinline__ char* ring_base() { return (char*)(((uintptr_t)g_ring + (1 << 20) - 1) & ~(uintptr_t)((1 << 20) - 1)); }
__device__ __forceinline__ uint32_t ring_off(int chunk, int side) {
    uint32_t o = ((chunk & 1) << 13) | ((chunk >> 1) << 16);
    uint32_t par = ((o >> 13) ^ (o >> 16) ^ (o >> 17) ^ (o >> 19) ^ side) & 1;
    return o | (par << 12);
}
__device__ __forceinline__ uint2 ld_poll(const char* p) {
    unsigned long long v; asm volatile("ld.relaxed.gpu.global.b64 %0, [%1];" : "=l"(v) : "l"(p) : "memory");
    return make_uint2((uint32_t)v, (uint32_t)(v >> 32));
}
__device__ __forceinline__ void st_pub(char* p, uint32_t x, uint32_t y) {
    unsigned long long v = ((unsigned long long)y << 32) | x;
    asm volatile("st.relaxed.gpu.global.b64 [%0], %1;" ::"l"(p), "l"(v) : "memory");
}
template <int N>
__device__ __forceinline__ void poll_issue(uint2 (&b)[N], const char* p, bool lastvalid) {
#pragma unroll
    for (int i = 0; i < N; i++) {
        if (i < N - 1 || lastvalid) b[i] = ld_poll(p + i * 256);
        else b[i] = make_uint2(0, 0);
    }
}
template <int N>
__device__ __forceinline__ int poll_check(uint2 (&b)[N], const char* p) {
    int it = 0;
    uint32_t mx = b[0].x;
#pragma unroll
    for (int i = 1; i < N; i++) mx = max(mx, b[i].x);
    if (__any_sync(0xffffffffu, mx == SENT)) {
        do {
#pragma unroll
            for (int i = 0; i < N; i++)
                if ((REALL && i < 10) || b[i].x == SENT) b[i] = ld_poll(p + i * 256);
            mx = b[0].x;
#pragma unroll
            for (int i = 1; i < N; i++) mx = max(mx, b[i].x);
            it++;
        } while (__any_sync(0xffffffffu, mx == SENT && it < SPIN_LIMIT));
    }
    return it;
}
template <int N>
__device__ __forceinline__ uint32_t delay(uint32_t a) {
    uint32_t z = 0;
#pragma unroll
    for (int i = 0; i < N; i++) asm volatile("ld.volatile.shared.u32 %0, [%1];" : "=r"(z) : "r"(a + z) : "memory");
    return z;
}

template <bool B> struct BoolC { static constexpr bool value = B; };
#define PFKV 0
#define LDW 1
constexpr int KVN = 2;
#define FEN 1
#define XB 4
#define KEEP 100
#define VCH_P 4
#define VCH_C 2
#define SELFST 1
#define KGS 3
#define DLM 1
#define DLO 2
constexpr int OB = 0;
template <int PACE>
__device__ __forceinline__ void preload(uint32_t (&sw)[12][4], uint32_t a, uint32_t zero) {
    uint32_t z = 0;
#pragma unroll
    for (int i = 0; i < 12; i++) {
        if (PACE && i % (PACE ? PACE : 1) == 0) z = delay<1>(zero + z);
        ldsm4t(sw[i], a + z + i * 512);
    }
}
__device__ __forceinline__ void stsm4(uint32_t addr, uint32_t a, uint32_t b, uint32_t c, uint32_t d) {
    asm volatile("stmatrix.sync.aligned.m8n8.x4.shared.b16 [%0], {%1,%2,%3,%4};" ::"r"(addr), "r"(a), "r"(b), "r"(c), "r"(d) : "memory");
}
__device__ __forceinline__ void stsm4t(uint32_t addr, uint32_t a, uint32_t b, uint32_t c, uint32_t d) {
    asm volatile("stmatrix.sync.aligned.m8n8.x4.trans.shared.b16 [%0], {%1,%2,%3,%4};" ::"r"(addr), "r"(a), "r"(b), "r"(c), "r"(d) : "memory");
}
__device__ __forceinline__ void st_part(uint32_t addr, const float (&x)[4], const float (&y)[4]) {
    stsm4(addr, pack_bf16(x[0], x[1]), pack_bf16(x[2], x[3]), pack_bf16(y[0], y[1]), pack_bf16(y[2], y[3]));
}
template <bool TR>
__device__ __forceinline__ void red_part(uint32_t& lo, uint32_t& hi, uint32_t addr, uint32_t eye) {
    uint32_t a[4][4];
#pragma unroll
    for (int j = 0; j < 4; j++) { if (TR) ldsm4t(a[j], addr + j * 1024); else ldsm4(a[j], addr + j * 1024); }
    float r0[4], r1[4];
    mma16z(r0, a[0], eye, eye); mma16z(r1, a[1], eye, eye);
    mma16(r0, a[2], eye, eye); mma16(r1, a[3], eye, eye);
    lo = pack_bf16(r0[0] + r1[0], r0[1] + r1[1]); hi = pack_bf16(r0[2] + r1[2], r0[3] + r1[3]);
}
__device__ __forceinline__ int o_chunk(int ks, int& pos) {
    const int cw = ks < 176 ? ks / 11 : 16 + (ks - 176) / 10;
    pos = ks - (cw < 16 ? 11 * cw : 176 + 10 * (cw - 16));
    return cw;
}

template <bool PV>
__device__ __forceinline__ void chain_loop(const uint32_t (&wa)[36][4], const uint32_t sb, const int w, const int lane, const int rank,
                                           const int h, const int side) {
    const int nq = rank == 0 ? 6 : 5, u0 = rank == 0 ? 0 : 1 + 5 * rank, v0 = rank == 0 ? -6 : 3 * rank - 6;
    const uint32_t l16 = sb + lane * 16;
    const uint32_t wl = l16 + w * CH_WREG;
    const uint32_t pw = l16 + CH_PART + w * 512;
    const uint32_t pt = CH_PART + (w >> 1) * 4096 + (w & 1) * 256;
    const uint32_t barS = sb + CH_BAR, barM = barS + 8, zero = barS + 24;
    const uint32_t eye = ((lane >> 2) == 2 * (lane & 3)) ? 0x3F80u : ((lane >> 2) == 2 * (lane & 3) + 1) ? 0x3F800000u : 0u;
    char* const ring = ring_base() + lane * 8;
    const uint32_t m_rd = ring_off(24 + w, side), o_rd = ring_off(rank * 8 + w, side);
    uint32_t pub;
    if (PV) { int pos, cw = o_chunk(h * 8 + v0 + w, pos); pub = (ring_off(cw, 0) & ~4096u) + pos * 256; }
    else pub = (ring_off(24 + (h >> 2), 0) & ~4096u) + ((2 * h + w) & 7) * 256;
    const uint32_t xs = l16 + CH_XS + (PV ? nq * 512 + (w - nq) * 1024 : w * 512);
    char* const kvo = (char*)(PV ? g_vm + 128 * (v0 + w) : g_km + 64 * (u0 + w)) + h * 2048;
    const bool mown = !PV && w == rank && rank < 2;
    uint32_t sw[12][4];
#pragma unroll
    for (int i = 0; i < 12; i++) ldsm4t(sw[i], wl + i * 512);

    auto step = [&](const int s, auto lastc) {
        constexpr bool last = decltype(lastc)::value;
        const uint32_t slot = (s & 3) << 14;
        uint2 b[8];
        const char* pm = ring + (m_rd + slot + delay<DLM>(zero));
        poll_issue<8>(b, pm, true);
        poll_check<8>(b, pm);
        if ((OB || (XB & 1)) && !last) bar_arrive(8, 256 + OB);
        if (PV && !last && w == 7) bar_arrive(13, 64);
        {
            float acc[6][4];
#pragma unroll
            for (int kk = 0; kk < 8; kk++) {
                const int j = (2 * kk) % 12;
                if (kk == 0) { mma16z(acc[5], sw[0], b[0].x, b[0].y); mma16z(acc[4], sw[1], b[0].x, b[0].y); }
                else { mma16(acc[5], sw[j], b[kk].x, b[kk].y); mma16(acc[4], sw[j + 1], b[kk].x, b[kk].y); }
#pragma unroll
                for (int i = 0; i < 4; i++) {
                    if (kk == 0) mma16z(acc[i], wa[i * 8], b[0].x, b[0].y);
                    else mma16(acc[i], wa[i * 8 + kk], b[kk].x, b[kk].y);
                    if (i < 2) ldsm4t(sw[j + i], wl + (12 + 2 * kk + i) * 512);
                }
            }
            st_part(pw + 4 * 2048, acc[4], acc[5]);
            st_part(pw, acc[0], acc[1]);
            st_part(pw + 2 * 2048, acc[2], acc[3]);
        }
        uint32_t kv0, kv1;
        const uint32_t lp = l16 + (lane >> 4) * 256, pl = lp + pt;
        if (!PV) {
            uint32_t xf[4];
            ldsm4(xf, xs);
            bar_sync(1, last ? 256 : 256 + OB);
            red_part<true>(kv1, kv0, pl, eye);
            if (!last) {
                float s0[4], s1[4], s2[4], s3[4], s4[4];
                mma8z(s0, kv1, 0, xf[0]); mma8z(s1, kv1, 0, xf[1]); mma8z(s2, kv1, 0, xf[2]); mma8z(s3, kv1, 0, xf[3]);
                mma8z(s4, kv1, 0, kv0);
                const float x0[4] = {s0[0], s0[1], s1[0], s1[1]}, x1[4] = {s2[0], s2[1], s3[0], s3[1]};
                sts128(pl, x0); sts128(pl + 1024, x1);
                sts64(sb + pt + 2048 + lane * 8, s4[0], s4[1]);
                bar_arrive(2, nq * 32 + 64 + OB);
            }
        } else {
            bar_sync(1, last ? 256 : 256 + OB);
        }
        {
            float va[4][4];
            const float z = __uint_as_float(delay<1>(zero));
#pragma unroll
            for (int i = 0; i < 4; i++) va[i][0] = va[i][1] = va[i][2] = va[i][3] = z;
#pragma unroll
            for (int kk = 0; kk < 8; kk++) {
                const int c = (PV ? VCH_P : VCH_C) == 4 ? kk & 1 : 0;
                if (kk < 2) { mma16(va[c], wa[32 + 2 * kk], b[kk].x, b[kk].y); mma16(va[2 + c], wa[33 + 2 * kk], b[kk].x, b[kk].y); }
                else { mma16(va[c], sw[(2 * kk) % 12], b[kk].x, b[kk].y); mma16(va[2 + c], sw[(2 * kk + 1) % 12], b[kk].x, b[kk].y); }
            }
            if ((PV ? VCH_P : VCH_C) == 4) {
#pragma unroll
                for (int j = 0; j < 4; j++) { va[0][j] += va[1][j]; va[2][j] += va[3][j]; }
            }
            st_part(pw + 6 * 2048, va[0], va[2]);
        }
        if (PV) {
            uint32_t vt0[4], vt1[4];
            ldsm4t(vt0, xs); ldsm4t(vt1, xs + 512);
            if (w >= 6 && !last) {
                const uint32_t sa = lp + CH_PART + (w - 6) * 1024, sc = sb + CH_PART + 2048 + (w - 6) * 128 + lane * 4;
                const uint32_t da = l16 + CH_SX + rank * 1280 + (w - 6) * 512, dc = sb + CH_SX + rank * 1280 + 1024 + (w - 6) * 128 + lane * 4;
                bar_sync(2, nq * 32 + 64 + OB);
                float4 v[6]; float c[6];
#pragma unroll
                for (int i = 0; i < 6; i++) v[i] = (i < 5 || rank == 0) ? lds128(sa + (i >> 1) * 4096 + (i & 1) * 256) : make_float4(0, 0, 0, 0);
#pragma unroll
                for (int i = 0; i < 6; i++) c[i] = (i < 5 || rank == 0) ? lds32(sc + (i >> 1) * 4096 + (i & 1) * 256) : 0.f;
                float4 sv = add4(add4(add4(v[0], v[1]), add4(v[2], v[3])), add4(v[4], v[5]));
                float cv = ((c[0] + c[1]) + (c[2] + c[3])) + (c[4] + c[5]);
#pragma unroll
                for (int d = 1; d < (SELFST ? 3 : 4); d++) {
                    const int dr = rank + d - (rank + d > 2 ? 3 : 0);
                    st_async4(mapa(da, dr), sv, mapa(barS, dr)); st_async1(mapa(dc, dr), cv, mapa(barS, dr));
                }
                if (SELFST) {
                    const float t4[4] = {sv.x, sv.y, sv.z, sv.w};
                    sts128(da, t4);
                    asm volatile("st.shared.f32 [%0], %1;" ::"r"(dc), "f"(cv) : "memory");
                }
            }
            bar_sync(3, last ? 256 : 256 + OB);
            if (!last && w == 7) bar_arrive(12, 64);
            red_part<false>(kv0, kv1, pl, eye);
            if (!last) {
                mbar_wait(barS, s & 1);
                const uint32_t sx = l16 + CH_SX;
                float4 a0 = lds128(sx), a1 = lds128(sx + 1280), a2 = lds128(sx + 2560);
                float4 b0 = lds128(sx + 512), b1 = lds128(sx + 512 + 1280), b2 = lds128(sx + 512 + 2560);
                float2 c0 = lds64(sx + 1024 - lane * 8), c1 = lds64(sx + 1024 + 1280 - lane * 8), c2 = lds64(sx + 1024 + 2560 - lane * 8);
                a0 = add4(add4(a0, a1), a2); b0 = add4(add4(b0, b1), b2);
                float sc[10] = {a0.x, a0.y, a0.z, a0.w, b0.x, b0.y, b0.z, b0.w, c0.x + c1.x + c2.x, c0.y + c1.y + c2.y};
                float mx = fmaxf(fmaxf(fmaxf(sc[0], sc[1]), fmaxf(sc[2], sc[3])), fmaxf(fmaxf(sc[4], sc[5]), fmaxf(sc[6], sc[7])));
                mx = fmaxf(mx, fmaxf(sc[8], sc[9]));
                mx = fmaxf(fmaxf(mx, __shfl_xor_sync(0xffffffffu, mx, 1)),
                           fmaxf(__shfl_xor_sync(0xffffffffu, mx, 2), __shfl_xor_sync(0xffffffffu, mx, 3)));
                const float cs = 0.08838834764831845f * 1.4426950408889634f;
                const float mb = -mx * cs;
#pragma unroll
                for (int j = 0; j < 10; j++) sc[j] = ex2(fmaf(sc[j], cs, mb));
                uint32_t pf[5];
#pragma unroll
                for (int j = 0; j < 5; j++) pf[j] = pack_bf16(sc[2 * j], sc[2 * j + 1]);
                float o0[4], o1[4], o2[4], o3[4], o4[4], o5[4];
                const uint32_t p0[4] = {pf[0], 0, pf[1], 0}, p1[4] = {pf[2], 0, pf[3], 0};
                mma16z(o0, p0, vt0[0], vt0[1]); mma16z(o1, p0, vt1[0], vt1[1]);
                mma16z(o2, p1, vt0[2], vt0[3]); mma16z(o3, p1, vt1[2], vt1[3]);
                mma8z(o4, pf[4], 0, kv0); mma8z(o5, pf[4], 0, kv1);
                float sum = (((sc[0] + sc[1]) + (sc[2] + sc[3])) + ((sc[4] + sc[5]) + (sc[6] + sc[7]))) + (sc[8] + sc[9]);
                sum = (sum + __shfl_xor_sync(0xffffffffu, sum, 1)) + (__shfl_xor_sync(0xffffffffu, sum, 2) + __shfl_xor_sync(0xffffffffu, sum, 3));
                float inv; asm("rcp.approx.ftz.f32 %0, %1;" : "=f"(inv) : "f"(sum));
                const uint32_t ox = pack_bf16((o0[0] + o2[0] + o4[0]) * inv, (o0[1] + o2[1] + o4[1]) * inv);
                const uint32_t oy = pack_bf16((o1[0] + o3[0] + o5[0]) * inv, (o1[1] + o3[1] + o5[1]) * inv);
                st_pub(ring + (pub + slot), ox, oy); st_pub(ring + (pub + slot) + 4096, ox, oy);
                if (OB || (XB & 4)) bar_arrive(10, (8 - nq) * 32 + OB);
                preload<0>(sw, wl + 28 * 512, zero);
            }
            kv0 = movm(kv0); kv1 = movm(kv1);
        } else {
            *(uint32_t*)(kvo + (uint32_t)(s * (NH * 2048) + lane * 4)) = kv0;
            if (last) bar_arrive(3, 256);
            else {
                bar_sync(3, 256 + OB);
                preload<1>(sw, wl + 28 * 512, zero);
            }
        }
        uint2 c[11];
        const char* po;
        if (!last) {
            bar_sync(4, 256 + OB);
            po = ring + (o_rd + slot + delay<DLO>(zero));
            poll_issue<11>(c, po, rank < 2);
        }
        if (PV) { uint32_t* d = (uint32_t*)(kvo + (uint32_t)(s * (NH * 2048) + lane * 4)); d[0] = kv0; d[32] = kv1; }
        if (last) return;
        poll_check<11>(c, po);
        if (OB || (XB & 2)) bar_arrive(9, 256 + OB);
        {
            float acc[4][4];
#pragma unroll
            for (int f = 0; f < 22; f++) {
                const int kk = f >> 1, a = f & 3;
                if (f < 4) mma16z(acc[a], sw[f % 12], c[kk].x, c[kk].y);
                else mma16(acc[a], sw[f % 12], c[kk].x, c[kk].y);
                if (f + 12 < 22) ldsm4t(sw[f % 12], wl + (28 + f + 12) * 512);
            }
#pragma unroll
            for (int i = 0; i < 2; i++) {
#pragma unroll
                for (int j = 0; j < 4; j++) acc[i][j] += acc[i + 2][j];
                sts128(l16 + CH_PART + i * 4096 + w * 512, acc[i]);
            }
        }
        if (!PV && w < 2) {
            bar_sync(5, 288 + OB);
            float4 v[8];
#pragma unroll
            for (int i = 0; i < 8; i++) v[i] = lds128(l16 + CH_PART + w * 4096 + i * 512);
            float4 r = add4(add4(add4(v[0], v[1]), add4(v[2], v[3])), add4(add4(v[4], v[5]), add4(v[6], v[7])));
            if (!mown) st_async4(mapa(l16 + CH_MX + rank * 512, w), r, mapa(barM, w));
            bar_arrive(7, 256 + OB);
            if (mown) {
                mbar_wait(barM, s & 1);
                float4 x = lds128(l16 + CH_MX + (rank ^ 1) * 512), y = lds128(l16 + CH_MX + 2 * 512);
                r = add4(add4(x, r), y);
                const uint32_t mx = movm(pack_bf16(r.x, r.y)), my = movm(pack_bf16(r.z, r.w));
                const uint32_t ns = (slot + 0x4000) & 0xC000;
                st_pub(ring + (pub + ns), mx, my); st_pub(ring + (pub + ns) + 4096, mx, my);
            }
            preload<0>(sw, wl, zero);
        } else {
            bar_arrive(5, 288 + OB);
            bar_sync(7, 256 + OB);
            preload<2>(sw, wl, zero);
        }
        bar_sync(6, 320 + OB);
    };
#pragma unroll 1
    for (int s = 0; s < NSEG - 1; s++) step(s, BoolC<false>());
    step(NSEG - 1, BoolC<true>());
    bar_arrive(6, 288);
}

__device__ __forceinline__ void chain_pace(const uint32_t sb, const int lane, const int rank, const int aware) {
    const uint32_t zero = sb + CH_BAR + 24;
    if (lane == 0) {
        char* ring = ring_base();
        uint32_t* p0 = (uint32_t*)(ring + ring_off(blockIdx.x & 15, 0) + 3072 + (blockIdx.x >> 4) * 128);
        uint32_t* p1 = (uint32_t*)(ring + ring_off(blockIdx.x & 15, 1) + 3072 + (blockIdx.x >> 4) * 128);
        *p0 = 0; *p1 = 0;
        int b0 = 1 << 30, b1 = 1 << 30; uint32_t v = 0;
        for (int r = 0; r < 4 || (r < 256 && !mbar_test(sb + CH_BAR + 16, 0)); r++) {
            uint32_t t0 = clk(); v = atomicExch(p0 + (v == 500), r); uint32_t t1 = v == 777 ? clk() + 1 : clk(); b0 = min(b0, (int)(t1 - t0));
            t0 = clk(); v = atomicExch(p1 + (v == 500), r); t1 = v == 777 ? clk() + 1 : clk(); b1 = min(b1, (int)(t1 - t0));
            asm volatile("st.volatile.shared.u32 [%0], %1;" ::"r"(zero + 4), "r"(aware ? (b1 < b0) ^ (aware - 1) : 0) : "memory");
        }
    }
    __syncwarp();
#pragma unroll 1
    for (int s = 1; s < NSEG; s++) {
        bar_sync(5, 288 + OB);
        bar_arrive(6, 320 + OB + (rank == 2 ? delay<18>(zero) : 0));
    }
}
__device__ __forceinline__ char* reset_ptr(const int lane, const int rank, const int h) {
    const int nq = rank == 0 ? 6 : 5, v0 = rank == 0 ? -6 : 3 * rank - 6;
    int pos, cw = o_chunk(h * 8 + v0 + min(max(5 + (lane >> 3), nq), 7), pos);
    if (lane >= 24 && rank < 2) { cw = 24 + (h >> 2); pos = (2 * h + rank) & 7; }
    return ring_base() + ((ring_off(cw, 0) & ~4096u) + pos * 256 + (lane & 7) * 16);
}
__device__ __forceinline__ void chain_chores(const uint32_t sb, const int lane, const int rank, const int h, const bf16* __restrict__ mem0) {
    const int nq = rank == 0 ? 6 : 5, u0 = rank == 0 ? 0 : 1 + 5 * rank, v0 = rank == 0 ? -6 : 3 * rank - 6;
    const uint32_t barS = sb + CH_BAR, barM = barS + 8, barX = barS + 16;
    auto xload = [&](int s) {
        mbar_expect(barX, 8192 - nq * 512);
        bulk_load(sb + CH_XS, g_kx + (size_t)(s * NH + h) * 4096 + u0 * 256, nq * 512, barX);
        bulk_load(sb + CH_XS + nq * 512, g_vx + (size_t)(s * NH + h) * 4096 + (v0 + nq) * 512, (8 - nq) * 1024, barX);
    };
    char* const rb = reset_ptr(lane, rank, h);
    int* const kvf = g_kvf + blockIdx.x * 16;
    if (rank < 2) {
        const uint32_t* p = (const uint32_t*)(mem0 + (lane >> 2) * DM + 32 * h + 16 * rank + 2 * (lane & 3));
        char* d = ring_base() + ((ring_off(24 + (h >> 2), 0) & ~4096u) + ((2 * h + rank) & 7) * 256 + lane * 8);
        const uint32_t x = p[0] == SENT ? 0x7FFF7FFFu : p[0];
        st_pub(d, x, p[4]); st_pub(d + 4096, x, p[4]);
    }
    if (lane == 0) {
        if (!KVN) __nanosleep(18000);
        wait_ctr(kvf, KVN);
        asm volatile("fence.proxy.async;" ::: "memory");
        xload(0);
    }
#pragma unroll 1
    for (int s = 0; s < NSEG - 1; s++) {
        if (lane == 0) {
            mbar_expect(barS, (SELFST ? 2 : 3) * 1280);
            if (rank < 2) mbar_expect(barM, 2 * 512);
        }
        bar_sync(13, 64);
#pragma unroll
        for (int i = 0; i < 4; i++)
            asm volatile("st.relaxed.gpu.global.v4.u32 [%0], {%1,%1,%1,%1};" ::"l"(rb + ((((s + 2) & 3) << 14) + (i >> 1) * 4096 + (i & 1) * 128)), "r"(SENT) : "memory");
        if (FEN || (s & 3) == 0) __threadfence();
        if (lane == 0 && (s & 3) == 0 && s) atomicAdd(g_ctr + C_CHAIN + (s >> 2) - 1, 1);
        if (lane == 0 && (s & 3) == 3) { wait_ctr(kvf + (s >> 2) + 1, KVN); asm volatile("fence.proxy.async;" ::: "memory"); }
        __syncwarp();
        bar_sync(12, 64);
        if (lane == 0) xload(s + 1);
        mbar_wait(barX, (s + 1) & 1);
        bar_sync(6, 320 + OB);
    }
    bar_sync(6, 288);
    __threadfence();
    if (lane == 0) atomicAdd(g_ctr + C_CHAIN + 15, 1);
}

struct S4Params { const bf16 *Are, *Aim, *Bre, *Bim, *Cre, *Cim, *ldt, *dsk; };
__device__ __forceinline__ float2 cmul(float2 a, float2 b) { return make_float2(a.x * b.x - a.y * b.y, a.x * b.y + a.y * b.x); }
__device__ __forceinline__ float2 csq(float2 a) { return make_float2(a.x * a.x - a.y * a.y, (a.x + a.x) * a.y); }
__device__ __forceinline__ float2 cexp_t(float lr, float turns) {
    float f = (turns - rintf(turns)) * 6.283185307179586f, e = ex2(lr);
    return make_float2(e * __cosf(f), e * __sinf(f));
}
__device__ __forceinline__ float bf_at(uint2 v, int i) {
    const uint32_t w = i < 2 ? v.x : v.y;
    return __uint_as_float((i & 1) ? w & 0xFFFF0000u : w << 16);
}
__device__ __forceinline__ void kg_step(uint32_t (&a)[4][4], uint32_t (&b)[5][2], uint32_t pa, uint32_t pe, float x0) {
#pragma unroll
    for (int i = 0; i < 2; i++) {
        const float4 p = lds128(pa + i * 64);
        const float2 e8 = lds64(pe + i * 32), c = make_float2(p.z, p.w);
        const float mag = ex2(p.x * x0), ph = p.y * x0;
        float2 e0 = make_float2(mag * __cosf(ph), mag * __sinf(ph)), e1 = cmul(e0, e8);
#pragma unroll
        for (int j = 0; j < 4; j++) {
            a[j][2 * i] = pack_bf16(e0.x, e0.y); a[j][2 * i + 1] = pack_bf16(e1.x, e1.y);
            e0 = csq(e0); e1 = csq(e1);
        }
        float2 m = cmul(c, e0);
        b[0][i] = pack_bf16(m.x, -m.y);
#pragma unroll
        for (int j = 0; j < 4; j++) {
            m = cmul(c, e1);
            b[j + 1][i] = pack_bf16(m.x, -m.y);
            if (j < 3) e1 = csq(e1);
        }
    }
}
__device__ __forceinline__ void kg_mma(float (&kd)[5][4], const uint32_t (&a)[4][4], const uint32_t (&b)[5][2]) {
    mma16(kd[0], a[0], b[0][0], b[0][1]);
#pragma unroll
    for (int j = 0; j < 4; j++) mma16(kd[j + 1], a[j], b[j + 1][0], b[j + 1][1]);
}
struct KgRaw { uint2 v[6]; float ldt; };
__device__ __forceinline__ void kg_load(KgRaw& r, const S4Params& P, int d, int lane) {
    const bf16* src[6] = {P.Are, P.Aim, P.Bre, P.Bim, P.Cre, P.Cim};
#pragma unroll
    for (int j = 0; j < 6; j++) r.v[j] = __ldg((const uint2*)(src[j] + d * 128) + lane);
    r.ldt = __bfloat162float(P.ldt[d]);
}
__device__ __forceinline__ float kg_params(const KgRaw& r, uint32_t stg, int lane) {
    const float dt = __bfloat162float(__float2bfloat16(expf(r.ldt)));
    float k2048 = 0.f;
#pragma unroll
    for (int i = 0; i < 4; i++) {
        const float br = dt * bf_at(r.v[2], i), bi = dt * bf_at(r.v[3], i), cr = bf_at(r.v[4], i), ci = bf_at(r.v[5], i);
        const float zr = dt * bf_at(r.v[0], i) * 1.4426950408889634f;
        float zt = dt * bf_at(r.v[1], i) * 0.15915494309189535f;
        zt -= rintf(zt);
        const float v[4] = {zr, zt * 6.283185307179586f, cr * br - ci * bi, cr * bi + ci * br};
        const float2 e8 = cexp_t(8.f * zr, 8.f * zt), el = cexp_t(2048.f * zr, 2048.f * zt);
        k2048 += v[2] * el.x - v[3] * el.y;
        sts128(stg + (i * 32 + lane) * 16, v);
        sts64(stg + 2048 + (i * 32 + lane) * 8, e8.x, e8.y);
    }
#pragma unroll
    for (int o = 16; o; o >>= 1) k2048 += __shfl_xor_sync(0xffffffffu, k2048, o);
    __syncwarp();
    return k2048;
}
__device__ __forceinline__ void kg_store(const float (&kd)[5][4], float k2048, uint32_t stg, int d, int lane) {
    __syncwarp();
    const uint32_t ta = stg + (lane & 7) * 32 + ((lane >> 3) & 1) * 16 + (lane >> 4) * 256;
    stsm4t(ta, pack_bf16(kd[0][0], kd[0][1]), pack_bf16(kd[0][2], kd[0][3]), pack_bf16(kd[1][0], kd[1][1]), pack_bf16(kd[1][2], kd[1][3]));
    stsm4t(ta + 512, pack_bf16(kd[2][0], kd[2][1]), pack_bf16(kd[2][2], kd[2][3]), pack_bf16(kd[3][0], kd[3][1]), pack_bf16(kd[3][2], kd[3][3]));
    stsm4t(ta + 1024, pack_bf16(kd[4][0], kd[4][1]), pack_bf16(kd[4][2], kd[4][3]), pack_bf16(k2048, 0.f), 0);
    __syncwarp();
#pragma unroll
    for (int j = 0; j < 3; j++) ((float4*)(g_kd + d * 768))[j * 32 + lane] = lds128(stg + j * 512 + lane * 16);
    __syncwarp();
}

__global__ void __cluster_dims__(3, 1, 1) __launch_bounds__(CH_THREADS, 1)
chain_kernel(const __grid_constant__ CUtensorMap mq, const __grid_constant__ CUtensorMap mk, const __grid_constant__ CUtensorMap mv,
             const __grid_constant__ CUtensorMap mo, const bf16* __restrict__ Wq, const bf16* __restrict__ Wk, const bf16* __restrict__ Wv,
             const bf16* __restrict__ mem0, const __grid_constant__ S4Params P, int aware) {
    extern __shared__ __align__(1024) unsigned char smem[];
    const uint32_t sb = smem_u32(smem);
    const int tid = threadIdx.x, lane = tid & 31;
    const int w = __shfl_sync(0xffffffffu, tid >> 5, 0);
    int rank; asm("mov.u32 %0, %%cluster_ctarank;" : "=r"(rank));
    const int h = blockIdx.x / 3;
    if (tid == 0) {
        mbar_init(sb + CH_BAR, 1); mbar_init(sb + CH_BAR + 8, 1); mbar_init(sb + CH_BAR + 16, 1);
        for (int i = 0; i < 16; i++) mbar_init(sb + CH_BAR + 64 + i * 8, 1);
        *(int*)(smem + CH_BAR + 24) = 0; *(int*)(smem + CH_BAR + 28) = 0; *(int*)(smem + CH_BAR + 32) = 0;
        asm volatile("fence.mbarrier_init.release.cluster;" ::: "memory");
    }
    if (w == 10 && PFKV) {
        const int e = lane * 96 + blockIdx.x;
        if (e < 2048) asm volatile("cp.async.bulk.prefetch.L2.global [%0], 8192;" ::"l"(((e & 1) ? Wv : Wk) + (size_t)(e >> 1) * HD) : "memory");
        if (PFKV > 1) __nanosleep(PFKV);
    }
    if (w == 9) {
        char* const rb = reset_ptr(lane, rank, h);
#pragma unroll
        for (int i = 0; i < 8; i++)
            asm volatile("st.relaxed.gpu.global.v4.u32 [%0], {%1,%1,%1,%1};" ::"l"(rb + (((i >> 2) << 14) + ((i >> 1) & 1) * 4096 + (i & 1) * 128)), "r"(SENT) : "memory");
        if (lane < 16) g_kvf[blockIdx.x * 16 + lane] = 0;
        if (blockIdx.x == 0)
            for (int k = lane; k < N_CTR; k += 32) g_ctr[k] = 0;
        __threadfence();
        __syncwarp();
        asm volatile("griddepcontrol.launch_dependents;" ::: "memory");
    }
    __syncthreads();
    asm volatile("barrier.cluster.arrive.relaxed.aligned;" ::: "memory");

    if (w >= 8) {
        reg_dec<24>();
        asm volatile("barrier.cluster.wait.aligned;" ::: "memory");
        if (w == 8) chain_pace(sb, lane, rank, aware);
        else if (w == 9) {
            chain_chores(sb, lane, rank, h, mem0);
            asm volatile("st.volatile.shared.u32 [%0], %1;" ::"r"(sb + CH_BAR + 32), "r"(0x3F803F80) : "memory");
        } else if (w == 11 && KEEP) {
#pragma unroll 1
            for (int it = 0; it < (1 << 22); it++) {
                int d0, d1;
                const uint32_t x = delay<1>(sb + CH_BAR + 32);
                asm volatile("mma.sync.aligned.m8n8k16.row.col.s32.s8.s8.s32 {%0,%1}, {%2}, {%2}, {%3,%3};" : "=r"(d0), "=r"(d1) : "r"(x), "r"(0));
                if (d0 | d1) break;
                if ((XB & 8) && lane == 0) asm volatile("st.relaxed.gpu.global.u32 [%0], %1;" ::"l"(g_kd + DM * 768 + blockIdx.x * 64), "r"(it) : "memory");
                if ((XB & 16) && lane == 0) ld_acq((int*)(g_kd + DM * 768 + blockIdx.x * 64));
                __nanosleep(KEEP);
            }
        }
    } else {
        reg_inc<240>();
        const int nq = rank == 0 ? 6 : 5;
        const int u0 = rank == 0 ? 0 : 1 + 5 * rank;
        const int v0 = rank == 0 ? -6 : 3 * rank - 6;
        const int gw = rank * 8 + w;
        const int ks0 = gw < 16 ? 11 * gw : 176 + 10 * (gw - 16);
        const int nko = gw < 16 ? 11 : 10;
        const uint32_t wr = sb + w * CH_WREG, bar0 = sb + CH_BAR + 64 + w * 16, bar1 = bar0 + 8;
        uint32_t wa[36][4];
        const uint32_t vst = sb + CH_PART + w * 2048;
        const int cq = h * DH + 8 * u0, cv = h * DH + 16 * (v0 + 6);
        const int r8 = lane >> 2, p = lane & 3;
        const bf16* src = p >= 2 ? ((p & 1) ? Wk : Wq) + cq + 32 : rank == 0 ? ((p & 1) ? Wk : Wq) + cq + 40 : Wv + cv - 16 + 8 * p;
        src += (size_t)(128 * w + r8) * HD;
        auto cp_rows = [&](int kh) {
            cp16(wr + ((kh >> 1) * 2 + (p >> 1)) * 512 + ((kh & 1) * 2 + (p & 1)) * 128 + r8 * 16, src + (size_t)kh * 8 * HD);
        };
        {
            int d = blockIdx.x * 8 + w, t = 0;
            const int d1 = 768 + blockIdx.x * 3 + w, nt = (w < 3 && d1 < DM) ? 32 : 16;
            const uint32_t stg = wr + 4096;
            KgRaw raw, raw1;
            kg_load(raw, P, d, lane);
            kg_load(raw1, P, min(d1, DM - 1), lane);
            float kd[5][4], k2048;
#pragma unroll 1
            for (int i = -LDW; i < 9 || t < nt; i++) {
                if (i >= 0 && i < 9) {
                    const uint32_t bar = bar0 + (i & 1) * 8;
                    if (i >= 2) mbar_wait(bar, ((i >> 1) - 1) & 1);
                    if (lane == 0) {
                        mbar_expect(bar, 2048);
                        if (i < 8) tma2d(wr + 8192 + (i & 1) * 8192 + (i >> 1) * 2048, (i & 1) ? &mk : &mq, cq, 128 * w + 32 * (i >> 1), bar);
                        else tma2d(vst, &mv, cv, 128 * w, bar);
                    }
                    if (i < 8) cp_rows(i);
                }
#pragma unroll 1
                for (int e = min(t + KGS, nt); t < e; t++) {
                    if ((t & 15) == 0) {
                        k2048 = kg_params(raw, stg, lane);
#pragma unroll
                        for (int j = 0; j < 20; j++) kd[j >> 2][j & 3] = 0.f;
                    }
                    uint32_t ka[4][4], kb[5][2];
                    kg_step(ka, kb, stg + ((t & 15) * 8 + (lane & 3)) * 16, stg + 2048 + ((t & 15) * 8 + (lane & 3)) * 8, (float)(lane >> 2));
                    kg_mma(kd, ka, kb);
                    if ((t & 15) == 15) { kg_store(kd, k2048, stg, d, lane); raw = raw1; d = d1; }
                }
            }
        }
        const uint32_t lrow = ((lane >> 4) * 8 + (lane & 7)) * 64, lsw = (lane >> 1) & 3, lh = (lane >> 3) & 1;
        mbar_wait(bar1, 1); mbar_wait(bar0, 0);
#pragma unroll
        for (int i = 0; i < 32; i++) ldsm4t(wa[i], wr + 8192 + lh * 8192 + (i & 7) * 1024 + lrow + (((i >> 3) ^ lsw) << 4));
#pragma unroll
        for (int i = 0; i < 4; i++) ldsm4t(wa[32 + i], vst + (i >> 1) * 1024 + lrow + ((((i & 1) * 2 + lh) ^ lsw) << 4));
        asm volatile("fence.proxy.async.shared::cta;" ::"r"(wa[31][0]), "r"(wa[35][0]) : "memory");
        __syncwarp();
#pragma unroll 1
        for (int i = 9; i < 18; i++) {
            const uint32_t bar = bar0 + (i & 1) * 8;
            if (i >= 11) mbar_wait(bar, ((i >> 1) - 1) & 1);
            if (lane == 0) {
                const int j = 2 * (i - 12), nb = min(2, nko - j);
                mbar_expect(bar, i < 12 ? 2048 : nb * 1024);
                if (i < 12) tma2d(wr + 8192 + (i - 9) * 2048, &mv, cv, 128 * w + 32 * (i - 8), bar);
                else for (int e = 0; e < nb; e++) tma2d(wr + 14336 + (j + e) * 1024, &mo, 32 * h, 16 * (ks0 + j + e), bar);
            }
            if (i < 17) cp_rows(i - 1);
        }
        mbar_wait(bar0, 0); mbar_wait(bar1, 0);
#pragma unroll 1
        for (int i = 0; i < 17; i++) {
            uint32_t x[4], y[4];
            ldsm4t(x, wr + 8192 + i * 1024 + lrow + ((lh ^ lsw) << 4));
            ldsm4t(y, wr + 8192 + i * 1024 + lrow + (((2 + lh) ^ lsw) << 4));
            if (i == 16 && nko == 10) x[0] = x[1] = x[2] = x[3] = y[0] = y[1] = y[2] = y[3] = 0;
            __syncwarp();
            stsm4t(wr + 8192 + i * 1024 + lane * 16, x[0], x[1], x[2], x[3]);
            stsm4t(wr + 8192 + i * 1024 + 512 + lane * 16, y[0], y[1], y[2], y[3]);
        }
        asm volatile("cp.async.wait_all;" ::: "memory");
        asm volatile("barrier.cluster.wait.aligned;" ::: "memory");
        bar_sync(1, 256);
        mbar_wait_long(sb + CH_BAR + 16, 0);
        const int side = __shfl_sync(0xffffffffu, *(volatile int*)(smem + CH_BAR + 28), 0);
        if (w >= nq) chain_loop<true>(wa, sb, w, lane, rank, h, side);
        else chain_loop<false>(wa, sb, w, lane, rank, h, side);
    }
}

constexpr int G_STAGE = 49152, G_NST = 4;
constexpr int G_STG = G_NST * G_STAGE;
constexpr int G_BAR = G_STG + 32768;
constexpr int G_SMEM = G_BAR + 256 + 1024;

#define ST(id, w, i)
#define WLOG(e)
constexpr int IT_QA = 0, IT_O = 1, IT_S4 = 2, IT_END = 3, IT_KV = 4;
#define Q_A 11
#define Q_W1 9
#define O_WIDE 11
#define KVP 0
#define KVS 8
#define STM 0
__device__ __forceinline__ void st_out(uint32_t* p, uint32_t v) {
    if (STM == 0) *p = v;
    else if (STM == 1) __stcs(p, v);
    else asm volatile("st.global.L1::no_allocate.u32 [%0], %1;" ::"l"(p), "r"(v) : "memory");
}
#define Q_S1 8
__device__ __forceinline__ int queue_item(int q) {
    if (KVP && q >= KVP && q < 512) return (IT_KV << 16) | (((q >> 6) * 2 + (q & 1)) << 8) | ((q >> 1) & 31);
    if (q < 512) return (IT_KV << 16) | ((q >> 5) << 8) | (q & 31);
    q -= 512;
    if (q < Q_A * 16) return (IT_QA << 16) | ((q >> 4) << 8) | (q & 15);
    q -= Q_A * 16;
    if (q < Q_W1 * 4) return (IT_O << 16) | ((q >> 2) << 8) | (q & 3);
    q -= Q_W1 * 4;
    if (q < (16 - Q_A) * 16) return (IT_QA << 16) | ((Q_A + (q >> 4)) << 8) | (q & 15);
    q -= (16 - Q_A) * 16;
    if (q < (O_WIDE - Q_W1) * 4) return (IT_O << 16) | ((Q_W1 + (q >> 2)) << 8) | (q & 3);
    q -= (O_WIDE - Q_W1) * 4;
    if (q < Q_S1) return (IT_S4 << 16) | q;
    q -= Q_S1;
    if (q < (16 - O_WIDE) * 8) return (IT_O << 16) | ((O_WIDE + (q >> 3)) << 8) | (q & 7);
    q -= (16 - O_WIDE) * 8;
    if (q < 128 - Q_S1) return (IT_S4 << 16) | (Q_S1 + q);
    return IT_END << 16;
}
__device__ __forceinline__ void tma2d_store(const CUtensorMap* m, uint32_t src, int c0, int c1) {
    asm volatile("cp.async.bulk.tensor.2d.global.shared::cta.bulk_group [%0, {%2, %3}], [%1];" ::"l"(m), "r"(src), "r"(c0), "r"(c1) : "memory");
}
__device__ __forceinline__ void mma8(float (&d)[4], uint32_t a0, uint32_t a1, uint32_t b0) {
    asm volatile("mma.sync.aligned.m16n8k8.row.col.f32.bf16.bf16.f32 {%0,%1,%2,%3}, {%4,%5}, {%6}, {%0,%1,%2,%3};"
        : "+f"(d[0]), "+f"(d[1]), "+f"(d[2]), "+f"(d[3]) : "r"(a0), "r"(a1), "r"(b0));
}

__device__ __forceinline__ void attn_head(const uint32_t (&q)[32], uint32_t sk, uint32_t sv, uint32_t fullv, uint32_t parv, uint32_t emptyk,
                                          int wi, int lane, uint32_t* dst) {
    const int g = lane >> 2, t = lane & 3, hi = wi & 1;
    float s[5][4];
#pragma unroll
    for (int j = 0; j < 5; j++) s[j][0] = s[j][1] = s[j][2] = s[j][3] = 0.f;
#pragma unroll
    for (int k2 = 0; k2 < 4; k2++) {
        uint32_t km[4];
        ldsm4(km, sk + 8192 + k2 * 512 + lane * 16);
#pragma unroll
        for (int i = 0; i < 2; i++) {
            const int ks = 2 * k2 + i;
            const uint32_t a[4] = {q[4 * ks], q[4 * ks + 1], q[4 * ks + 2], q[4 * ks + 3]};
            uint32_t b[4];
            const uint32_t ad = sk + ks * 1024 + ((lane >> 3) & 1) * 512 + (lane >> 4) * 128 + (lane & 7) * 16;
            ldsm4(b, ad);
            mma16(s[4], a, km[2 * i], km[2 * i + 1]);
            mma16(s[0], a, b[0], b[1]); mma16(s[1], a, b[2], b[3]);
            if (hi) { ldsm4(b, ad + 256); mma16(s[2], a, b[0], b[1]); mma16(s[3], a, b[2], b[3]); }
        }
    }
    __syncwarp();
    if (lane == 0) mbar_arrive(emptyk);
    const int r0 = hi * 16 + g;
    float m0 = fmaxf(s[4][0], s[4][1]), m1 = fmaxf(s[4][2], s[4][3]);
#pragma unroll
    for (int j = 0; j < 4; j++) {
        const int c = 8 * j + 2 * t;
        if (c > r0) s[j][0] = -INFINITY;
        if (c + 1 > r0) s[j][1] = -INFINITY;
        if (c > r0 + 8) s[j][2] = -INFINITY;
        if (c + 1 > r0 + 8) s[j][3] = -INFINITY;
        m0 = fmaxf(m0, fmaxf(s[j][0], s[j][1])); m1 = fmaxf(m1, fmaxf(s[j][2], s[j][3]));
    }
    m0 = fmaxf(m0, __shfl_xor_sync(0xffffffffu, m0, 1)); m1 = fmaxf(m1, __shfl_xor_sync(0xffffffffu, m1, 1));
    m0 = fmaxf(m0, __shfl_xor_sync(0xffffffffu, m0, 2)); m1 = fmaxf(m1, __shfl_xor_sync(0xffffffffu, m1, 2));
    const float cs = 0.08838834764831845f * 1.4426950408889634f;
    m0 *= -cs; m1 *= -cs;
    float l0 = 0, l1 = 0;
#pragma unroll
    for (int j = 0; j < 5; j++) {
        s[j][0] = ex2(fmaf(s[j][0], cs, m0)); s[j][1] = ex2(fmaf(s[j][1], cs, m0));
        s[j][2] = ex2(fmaf(s[j][2], cs, m1)); s[j][3] = ex2(fmaf(s[j][3], cs, m1));
        l0 += s[j][0] + s[j][1]; l1 += s[j][2] + s[j][3];
    }
    l0 += __shfl_xor_sync(0xffffffffu, l0, 1); l1 += __shfl_xor_sync(0xffffffffu, l1, 1);
    l0 += __shfl_xor_sync(0xffffffffu, l0, 2); l1 += __shfl_xor_sync(0xffffffffu, l1, 2);
    l0 = __fdividef(1.f, l0); l1 = __fdividef(1.f, l1);
    uint32_t p[10];
#pragma unroll
    for (int j = 0; j < 5; j++) { p[2 * j] = pack_bf16(s[j][0] * l0, s[j][1] * l0); p[2 * j + 1] = pack_bf16(s[j][2] * l1, s[j][3] * l1); }
    const uint32_t p0[4] = {p[0], p[1], p[2], p[3]}, p1[4] = {p[4], p[5], p[6], p[7]};
    mbar_wait(fullv, parv);
#pragma unroll
    for (int u4 = 0; u4 < 4; u4++) {
        uint32_t vm[4];
        ldsm4t(vm, sv + 8192 + u4 * 512 + lane * 16);
#pragma unroll
        for (int i = 0; i < 4; i++) {
            const int u = 4 * u4 + i;
            uint32_t b[4];
            ldsm4t(b, sv + u * 512 + lane * 16);
            float o[4];
            mma16z(o, p0, b[0], b[1]);
            if (hi) mma16(o, p1, b[2], b[3]);
            mma8(o, p[8], p[9], vm[i]);
            dst[(u >> 3) * 4096 + (u & 7) * 32] = pack_bf16(o[0], o[1]);
            dst[(u >> 3) * 4096 + (u & 7) * 32 + 256] = pack_bf16(o[2], o[3]);
        }
    }
}

template <int BN, int NKB, bool BLOCKED_A>
__device__ __forceinline__ void mainloop(float (&acc)[BN / 2], uint32_t sb, int wgi, uint32_t full, uint32_t empty, int& it, bool elect) {
#pragma unroll
    for (int j = 0; j < BN / 2; j++) acc[j] = 0.f;
#pragma unroll 1
    for (int k4 = 0; k4 < NKB; k4 += 4) {
#pragma unroll
        for (int st = 0; st < 4; st++, it++) {
            mbar_wait(full + 8 * st, (it >> 2) & 1);
            const uint64_t da = BLOCKED_A ? mkdesc(sb + st * G_STAGE + wgi * 8192, 128, 1024, 0) : mkdesc(sb + st * G_STAGE + wgi * 8192, 16, 1024, 1);
            const uint64_t db = mkdesc(sb + st * G_STAGE + 16384, 8192, 1024, 1);
            wg_fence();
#pragma unroll
            for (int k = 0; k < 4; k++) {
                if constexpr (BN == 256) wgmma256(acc, da + k * (BLOCKED_A ? 16 : 2), db + k * 128, 1);
                else wgmma128(acc, da + k * (BLOCKED_A ? 16 : 2), db + k * 128, 1);
            }
            wg_commit();
            if (k4 | st) {
                wg_wait<1>();
                if (elect) mbar_arrive(empty + 8 * ((st + 3) & 3));
            }
        }
    }
    wg_wait<0>();
    if (elect) mbar_arrive(empty + 8 * 3);
}

template <int BN>
__device__ __forceinline__ void o_item(uint32_t sb, int wgi, int wi, int lane, uint32_t full, uint32_t empty, int& it, const CUtensorMap* mout,
                                       int row0, int col0) {
    float acc[BN / 2];
    mainloop<BN, 64, true>(acc, sb, wgi, full, empty, it, lane == 0);
    const uint32_t stg = sb + G_STG + (wgi * 4 + wi) * 4096;
    const int r = lane & 15, cu = lane >> 4;
#pragma unroll
    for (int hf = 0; hf < BN / 128; hf++) {
        if (lane == 0) asm volatile("cp.async.bulk.wait_group.read 0;" ::: "memory");
        __syncwarp();
#pragma unroll
        for (int j = 0; j < 8; j++) {
            const float* a = acc + hf * 64 + j * 8;
            stsm4(stg + (j >> 2) * 2048 + r * 128 + ((((j & 3) * 2 + cu) ^ (r & 7)) << 4),
                  pack_bf16(a[0], a[1]), pack_bf16(a[2], a[3]), pack_bf16(a[4], a[5]), pack_bf16(a[6], a[7]));
        }
        asm volatile("fence.proxy.async.shared::cta;" ::: "memory");
        __syncwarp();
        if (lane == 0) {
            tma2d_store(mout, stg, col0 + hf * 128, row0 + wgi * 64 + wi * 16);
            tma2d_store(mout, stg + 2048, col0 + hf * 128 + 64, row0 + wgi * 64 + wi * 16);
            asm volatile("cp.async.bulk.commit_group;" ::: "memory");
        }
    }
}

constexpr int S4_KD = 32768;
constexpr int S4_CH = 2 * G_STAGE;
constexpr int S4_HALF = 2304;
constexpr int S4_WD = 2 * S4_HALF;
constexpr int S4_STRIDE = S4_WD + 2304 + 16;
__device__ __forceinline__ uint32_t addz(uint32_t x, uint32_t z) { uint32_t r; asm volatile("add.u32 %0, %1, %2;" : "=r"(r) : "r"(x), "r"(z)); return r; }
__device__ __forceinline__ uint32_t lds16(uint32_t a) { uint32_t v; asm volatile("ld.shared.u16 %0, [%1];" : "=r"(v) : "r"(a) : "memory"); return v; }
__device__ __forceinline__ uint32_t ldsu(uint32_t a) { return __float_as_uint(lds32(a)); }

template <int E0, int NE, int KP>
__device__ __forceinline__ void s4_windows(float (&acc)[8][2][4], uint32_t ut, uint32_t kd, int rho, int w, int lane, uint32_t z) {
    const int gt = (lane >> 2) - 2 * (lane & 3), p0 = rho == 16 ? -3 : -2, c = (lane >> 3) + p0;
    uint32_t band[2][4], tw[2 * NE + 1], ta[NE][4];
    {
        uint32_t f[5];
#pragma unroll
        for (int m = 0; m < 5; m++) {
            const int d = 8 * (p0 + m - 1) - gt + rho;
            f[m] = (abs(d) <= w ? 0x3F80u : 0u) | (abs(d + 1) <= w ? 0x3F800000u : 0u);
        }
#pragma unroll
        for (int j = 0; j < 2; j++) { band[j][0] = f[2 * j + 1]; band[j][1] = addz(f[2 * j], z); band[j][2] = f[2 * j + 2]; band[j][3] = addz(f[2 * j + 1], z); }
    }
#pragma unroll
    for (int m = 0; m < 2 * NE + 1; m++) {
        const int q = 8 * (2 * E0 - 1 + m) + gt;
        const uint32_t lo = lds16(kd + q * KP), hi = lds16(kd + (q - 1) * KP);
        tw[m] = ((unsigned)(q - 16 * E0) < 16 * E0 ? lo : 0u) | ((unsigned)(q - 1 - 16 * E0) < 16 * E0 ? hi << 16 : 0u);
    }
#pragma unroll
    for (int e = 0; e < NE; e++) { ta[e][0] = tw[2 * e + 1]; ta[e][1] = tw[2 * e + 2]; ta[e][2] = addz(tw[2 * e], z); ta[e][3] = addz(tw[2 * e + 1], z); }
    const uint32_t ua = ut + (c & 1) * S4_HALF + (16 + (lane & 7) + (c >> 1)) * 16;
#pragma unroll
    for (int J = 0; J < 8 - E0; J++) {
        uint32_t u0[4], u1[4];
        ldsm4(u0, ua + J * 256); ldsm4(u1, ua + J * 256 + 128);
        float s0[4], s1[4];
        mma16z(s0, band[0], u0[0], u0[1]); mma16z(s1, band[0], u1[0], u1[1]);
        mma16(s0, band[1], u0[2], u0[3]); mma16(s1, band[1], u1[2], u1[3]);
        const uint32_t b00 = pack_bf16(s0[0], s0[1]), b01 = pack_bf16(s1[0], s1[1]), b10 = pack_bf16(s0[2], s0[3]), b11 = pack_bf16(s1[2], s1[3]);
#pragma unroll
        for (int e = 0; e < NE; e++)
            if (J + E0 + e < 8) { mma16(acc[J + E0 + e][0], ta[e], b00, b01); mma16(acc[J + E0 + e][1], ta[e], b10, b11); }
    }
}
template <int D0, int D1>
__device__ __forceinline__ void s4_dense(float (&acc)[8][2][4], uint32_t ua, const uint32_t (&b0)[4], const uint32_t (&b1)[4]) {
#pragma unroll
    for (int J = 0; J < 8 - D0; J++) {
        uint32_t a[4];
        ldsm4(a, ua + J * 256);
        mma16(acc[J + D0][0], a, b0[0], b0[1]); mma16(acc[J + D0][1], a, b0[2], b0[3]);
        if (J + D1 < 8) { mma16(acc[J + D1][0], a, b1[0], b1[1]); mma16(acc[J + D1][1], a, b1[2], b1[3]); }
    }
}
__device__ __forceinline__ void s4_words(uint32_t (&b)[4], uint32_t wd) {
    asm volatile("ld.shared.u32 %0, [%4]; ld.shared.u32 %1, [%4+-32]; ld.shared.u32 %2, [%4+32]; ld.volatile.shared.u32 %3, [%4];"
        : "=r"(b[0]), "=r"(b[1]), "=r"(b[2]), "=r"(b[3]) : "r"(wd) : "memory");
}

__device__ __forceinline__ void s4_item(uint32_t sb, int cw, int lane, int item, const bf16* __restrict__ dsk, uint32_t empty, const CUtensorMap* my) {
    const int gt = (lane >> 2) - 2 * (lane & 3);
    const uint32_t ch = sb + S4_CH + cw * S4_STRIDE, kd = sb + S4_KD + cw * 1536;
    const __nv_bfloat162 dk = __bfloat162bfloat162(dsk[item * 8 + cw]);
    ST(item, cw, 0);
    asm volatile("st.shared.v4.u32 [%0], {%1,%1,%1,%1};" ::"r"(ch + (lane >> 4) * S4_HALF + (lane & 15) * 16), "r"(0) : "memory");
    const uint32_t tch = sb + S4_CH + (lane & 7) * S4_STRIDE + ((lane >> 3) & 1) * S4_HALF + (16 + 16 * cw + (lane >> 4)) * 16;
#pragma unroll
    for (int i = 0; i < 8; i++) {
        uint32_t x[4];
        ldsm4t(x, sb + cw * 4096 + i * 512 + lane * 16);
        stsm4(tch + i * 32, x[0], x[1], x[2], x[3]);
    }
#pragma unroll 1
    for (int x0 = lane * 2 - 16; x0 < 560; x0 += 64) {
        uint32_t k[3];
#pragma unroll
        for (int j = 0; j < 3; j++) {
            const int x = x0 + j - 1, idx = x < 256 ? max(x, 0) : min(128 + ((x + ((x >> 1) & 1)) >> 1), 384);
            k[j] = lds16(kd + idx * 2);
            if ((unsigned)x > 514u) k[j] = 0;
        }
        asm volatile("st.shared.v2.u32 [%0], {%1,%2};" ::"r"(ch + S4_WD + 64 + x0 * 4), "r"(k[1] | (k[0] << 16)), "r"(k[2] | (k[1] << 16)) : "memory");
    }
    const uint32_t k1024 = lds16(kd + 1024);
    bar_sync(2, 256);
    ST(item, cw, 1);
    const uint32_t z = ldsu(ch);
    float acc[8][2][4];
#pragma unroll
    for (int j = 0; j < 16; j++) acc[j >> 1][j & 1][0] = acc[j >> 1][j & 1][1] = acc[j >> 1][j & 1][2] = acc[j >> 1][j & 1][3] = 0.f;
#pragma unroll 1
    for (int r = 1; r <= 4; r++) s4_windows<2, 3, 8>(acc, ch, kd + 512 + 2 * r, 4 * r, 2 - (r & 1), lane, z);
    ST(item, cw, 2);
#pragma unroll 1
    for (int r = 1; r <= 2; r++) s4_windows<4, 4, 4>(acc, ch, kd + 768 + 2 * r, 8 * r, 2 + r, lane, z);
    ST(item, cw, 3);
    const uint32_t ua = ch + (lane >> 4) * S4_HALF + (16 + (lane & 15)) * 16, wd = ch + S4_WD + 64 + gt * 4;
#pragma unroll 1
    for (int q = 0; q < 2; q++) {
        uint32_t b0[4], b1[4];
        s4_words(b0, wd + (q + 32) * 64);
#pragma unroll
        for (int j = 0; j < 4; j++) {
            const int x = 16 * q + gt + (j == 1 ? -8 : j == 2 ? 8 : 0) - 3;
            b1[j] = addz(((unsigned)x < 2u ? k1024 : 0u) | ((unsigned)(x - 1) < 2u ? k1024 << 16 : 0u), z);
        }
        s4_dense<2, 4>(acc, ua - q * 16, b0, b1);
    }
    {
        uint32_t b0[4], b1[4], c0[4], c1[4];
        s4_words(b0, wd); s4_words(b1, wd + 1024);
#pragma unroll 1
        for (int q = 0; q < 16; q += 2) {
            s4_words(c0, wd + q * 64 + 64); s4_words(c1, wd + q * 64 + 64 + 1024);
            s4_dense<0, 1>(acc, ua - q * 16, b0, b1);
            s4_words(b0, wd + q * 64 + 128); s4_words(b1, wd + q * 64 + 128 + 1024);
            s4_dense<0, 1>(acc, ua - q * 16 - 16, c0, c1);
            if (q == 8 && lane == 0) { mbar_arrive(empty); mbar_arrive(empty + 8); }
        }
    }
    ST(item, cw, 4);
    if (lane == 0) asm volatile("cp.async.bulk.wait_group.read 0;" ::: "memory");
    __syncwarp();
#pragma unroll
    for (int I = 0; I < 8; I++) {
        uint32_t u[4];
        ldsm4(u, ua + I * 256);
#pragma unroll
        for (int j = 0; j < 4; j++) {
            const uint32_t y = pack_bf16(acc[I][j >> 1][2 * (j & 1)], acc[I][j >> 1][2 * (j & 1) + 1]);
            const __nv_bfloat162 r = __hadd2_rn(*(const __nv_bfloat162*)&y, __hmul2_rn(*(const __nv_bfloat162*)&u[j], dk));
            u[j] = *(const uint32_t*)&r;
        }
        stsm4(ua + I * 256, u[0], u[1], u[2], u[3]);
    }
    bar_sync(2, 256);
#pragma unroll
    for (int i = 0; i < 8; i++) {
        uint32_t y[4];
        ldsm4t(y, tch + i * 32);
        stsm4(sb + G_STG + cw * 4096 + i * 512 + lane * 16, y[0], y[1], y[2], y[3]);
    }
    asm volatile("fence.proxy.async.shared::cta;" ::: "memory");
    __syncwarp();
    if (lane == 0) {
        mbar_arrive(empty + 16); mbar_arrive(empty + 24);
        tma2d_store(my, sb + G_STG + cw * 4096, DM + item * 8, cw * 256);
        asm volatile("cp.async.bulk.commit_group;" ::: "memory");
    }
    ST(item, cw, 5);
}

__global__ void __launch_bounds__(384, 1)
worker_kernel(const __grid_constant__ CUtensorMap mx, const __grid_constant__ CUtensorMap mq, const __grid_constant__ CUtensorMap mk,
              const __grid_constant__ CUtensorMap mv, const __grid_constant__ CUtensorMap mo,
              const __grid_constant__ CUtensorMap mout, const __grid_constant__ CUtensorMap mu, const __grid_constant__ CUtensorMap my,
              const bf16* __restrict__ dsk) {
    extern __shared__ unsigned char smem_raw[];
    const uint32_t sb = (smem_u32(smem_raw) + 1023) & ~1023u;
    const uint32_t full = sb + G_BAR, empty = full + 32, ifull = full + 64, iempty = full + 80, islot = full + 96, sigbar = full + 112, sigslot = full + 120;
    const int tid = threadIdx.x, wg = tid >> 7, lane = tid & 31;
    if (tid == 0) {
        for (int i = 0; i < G_NST; i++) { mbar_init(full + 8 * i, 1); mbar_init(empty + 8 * i, 8); }
        for (int i = 0; i < 2; i++) { mbar_init(ifull + 8 * i, 1); mbar_init(iempty + 8 * i, 8); }
        mbar_init(sigbar, 8);
        asm volatile("fence.proxy.async;" ::: "memory");
    }
    __syncthreads();
    if (wg == 0) {
        reg_dec<40>();
        if (tid >= 32 && tid < 64) {
            for (int n = 0;; n++) {
                mbar_wait_long(sigbar, n & 1);
                int item; asm volatile("ld.shared.u32 %0, [%1];" : "=r"(item) : "r"(sigslot + 4 * (n & 1)) : "memory");
                const int type = item >> 16, b = (item >> 8) & 255, i = item & 255;
                if (type == IT_END) break;
                __threadfence();
                if (type == IT_KV) { if (lane < 6) atomicAdd(g_kvf + ((i & 15) * 6 + lane) * 16 + b, 1); }
                else if (lane == 0) atomicAdd(g_ctr + C_QA_DONE + b, 1);
            }
        } else if (tid < 32) {
            int it = 0;
            if (!KVN) asm volatile("griddepcontrol.wait;" ::: "memory");
            for (int n = 0;; n++) {
                int item = 0;
                if (lane == 0) {
                    const int q = (n == 0 && blockIdx.x < 32) ? blockIdx.x : 32 + atomicAdd(g_ctr + C_NEXT, 1);
                    item = queue_item(q);
                }
                item = __shfl_sync(0xffffffffu, item, 0);
                if (lane == 0) {
                    mbar_wait(iempty + 8 * (n & 1), ((n >> 1) & 1) ^ 1);
                    asm volatile("st.shared.u32 [%0], %1;" ::"r"(islot + 4 * (n & 1)), "r"(item) : "memory");
                    mbar_arrive(ifull + 8 * (n & 1));
                    const int type = item >> 16, b = (item >> 8) & 255, i = item & 255;
                    if (type == IT_QA || type == IT_KV) {
                        const CUtensorMap* mw = type == IT_QA ? &mq : i < 16 ? &mk : &mv;
                        bool ready = false;
                        for (int kb = 0; kb < 16; kb++, it++) {
                            const int st = it & 3;
                            mbar_wait(empty + 8 * st, ((it >> 2) & 1) ^ 1);
                            mbar_expect(full + 8 * st, G_STAGE);
                            const uint32_t a = sb + st * G_STAGE;
                            tma2d(a, &mx, kb * 64, b * 128, full + 8 * st);
                            tma3d(a + 16384, mw, 0, kb * 64, (i & 15) * 4, full + 8 * st);
                            tma3d(a + 32768, mw, 0, kb * 64, (i & 15) * 4 + 2, full + 8 * st);
                            if (type == IT_QA && kb == 3) ready = ld_acq(g_ctr + C_CHAIN + b) >= 96;
                            if (type == IT_QA && kb >= 3 && kb < 11) {
                                const size_t sh = (b * 4 + ((kb - 3) & 3)) * NH + i * 2;
                                asm volatile("cp.async.bulk.prefetch.L2.global [%0], 16384;" ::"l"((kb >= 7 ? g_vx : g_kx) + sh * 4096) : "memory");
                                if (ready) asm volatile("cp.async.bulk.prefetch.L2.global [%0], 4096;" ::"l"((kb >= 7 ? g_vm : g_km) + sh * 1024) : "memory");
                            }
                        }
                    }
                    if (type == IT_QA) {
                        wait_ctr(g_ctr + C_CHAIN + b, 96);
                        asm volatile("fence.proxy.async;" ::: "memory");
                        for (int st = 0; st < 4; st++, it++) {
                            mbar_wait(empty + 8 * st, ((it >> 2) & 1) ^ 1);
                            mbar_expect(full + 8 * st, 4 * 10240);
                            for (int sg = 0; sg < 4; sg++) {
                                const int sh = (b * 4 + sg) * NH + i * 2 + (st >> 1);
                                bulk_load(sb + st * G_STAGE + sg * 10240, ((st & 1) ? g_vx : g_kx) + (size_t)sh * 4096, 8192, full + 8 * st);
                                bulk_load(sb + st * G_STAGE + sg * 10240 + 8192, ((st & 1) ? g_vm : g_km) + (size_t)sh * 1024, 2048, full + 8 * st);
                            }
                        }
                    } else if (type == IT_O) {
                        const bool wide = b < O_WIDE;
                        wait_ctr(g_ctr + C_QA_DONE + b, 16);
                        asm volatile("fence.proxy.async;" ::: "memory");
                        for (int kb = 0; kb < 64; kb++, it++) {
                            const int st = it & 3;
                            mbar_wait(empty + 8 * st, ((it >> 2) & 1) ^ 1);
                            mbar_expect(full + 8 * st, wide ? G_STAGE : 32768);
                            const uint32_t a = sb + st * G_STAGE;
                            bulk_load(a, g_ox + (size_t)(b * 64 + kb) * 8192, 16384, full + 8 * st);
                            tma3d(a + 16384, &mo, 0, kb * 64, wide ? i * 4 : i * 2, full + 8 * st);
                            if (wide) tma3d(a + 32768, &mo, 0, kb * 64, i * 4 + 2, full + 8 * st);
                        }
                    } else if (type == IT_S4) {
                        wait_ctr(g_ctr + C_CHAIN, 96);
                        asm volatile("fence.proxy.async;" ::: "memory");
                        mbar_wait(empty, ((it >> 2) & 1) ^ 1);
                        mbar_expect(full, 32768 + 12288);
                        bulk_load(sb + S4_KD, g_kd + i * 8 * 768, 12288, full);
                        for (int j = 0; j < 8; j++) tma2d(sb + j * 4096, &mu, i * 8, j * 256, full);
                        for (int st = 1; st < 4; st++) { mbar_wait(empty + 8 * st, ((it >> 2) & 1) ^ 1); mbar_arrive(full + 8 * st); }
                        it += 4;
                        mbar_wait_long(empty, ((it >> 2) & 1) ^ 1);
                    }
                }
                __syncwarp();
                if (item >> 16 == IT_END) break;
            }
            asm volatile("griddepcontrol.wait;" ::: "memory");
        }
    } else {
        reg_inc<232>();
        const int wu = __shfl_sync(0xffffffffu, tid >> 5, 0);
        const int wgi = (wu >> 2) - 1, wi = wu & 3;
        int it = 0, nsig = 0, n = 0, item;
        auto next_item = [&]() {
            mbar_wait_long(ifull + 8 * (n & 1), (n >> 1) & 1);
            asm volatile("ld.shared.u32 %0, [%1];" : "=r"(item) : "r"(islot + 4 * (n & 1)) : "memory");
            __syncwarp();
            if (lane == 0) mbar_arrive(iempty + 8 * (n & 1));
        };
        auto signal = [&](int what) {
            if (tid == 128) asm volatile("st.shared.u32 [%0], %1;" ::"r"(sigslot + 4 * (nsig & 1)), "r"(what) : "memory");
            __syncwarp();
            if (lane == 0) mbar_arrive(sigbar);
            nsig++;
        };
        next_item();
        if (item >> 16 == IT_KV) {
            float acc[128];
            uint32_t pk[64];
            uint32_t* dst = nullptr;
            int prev = 0;
            do {
                WLOG(0);
#pragma unroll
                for (int kb = 0; kb < 16; kb++, it++) {
                    const int st = kb & 3;
                    mbar_wait(full + 8 * st, (it >> 2) & 1);
                    const uint64_t da = mkdesc(sb + st * G_STAGE + wgi * 8192, 16, 1024, 1);
                    const uint64_t db = mkdesc(sb + st * G_STAGE + 16384, 8192, 1024, 1);
                    wg_fence();
#pragma unroll
                    for (int k = 0; k < 4; k++) wgmma256(acc, da + k * 2, db + k * 128, kb | k);
                    wg_commit();
                    if (kb < KVS && dst) {
#pragma unroll
                        for (int j = kb * (64 / KVS); j < (kb + 1) * (64 / KVS); j++) st_out(dst + (j >> 1) * 128 + (j & 1) * 32, pk[j]);
                        if (kb == KVS - 1) signal(prev);
                    }
                    if (kb > 0) {
                        wg_wait<1>();
                        if (lane == 0) mbar_arrive(empty + 8 * ((kb - 1) & 3));
                    }
                }
                wg_wait<0>();
                if (lane == 0) mbar_arrive(empty + 8 * 3);
#pragma unroll
                for (int j = 0; j < 64; j++) pk[j] = pack_bf16(acc[2 * j], acc[2 * j + 1]);
                const int row = ((item >> 8) & 255) * 128 + wgi * 64 + wi * 16, nt = item & 255;
                dst = (uint32_t*)(nt < 16 ? g_kx : g_vx) + (size_t)((row >> 5) * 512 + (nt & 15) * 32) * 128 + (row & 31) * 4 + lane;
                prev = item;
                if (n == 0) {
#pragma unroll
                    for (int j = 0; j < 64; j++) dst[(j >> 1) * 128 + (j & 1) * 32] = pk[j];
                    signal(prev);
                    dst = nullptr;
                }
                WLOG(1);
                n++;
                next_item();
            } while (item >> 16 == IT_KV);
            if (dst) {
#pragma unroll
                for (int j = 0; j < 64; j++) dst[(j >> 1) * 128 + (j & 1) * 32] = pk[j];
                signal(prev);
            }
        }
        for (;; n++, next_item()) {
            const int type = item >> 16, b = (item >> 8) & 255, i = item & 255;
            WLOG(0);
            if (type == IT_QA) {
                float acc[128];
                ST(sid, cw, 0);
                ST(sid, cw, 1);
                mainloop<256, 16, false>(acc, sb, wgi, full, empty, it, lane == 0);
                ST(sid, cw, 2);
                uint32_t q0[32], q1[32];
#pragma unroll
                for (int j = 0; j < 32; j++) { q0[j] = pack_bf16(acc[2 * j], acc[2 * j + 1]); q1[j] = pack_bf16(acc[64 + 2 * j], acc[65 + 2 * j]); }
                const uint32_t par = (it >> 2) & 1, so = (wgi * 2 + (wi >> 1)) * 10240;
                uint32_t* dst = (uint32_t*)g_ox + (size_t)(b * 64 + i * 4) * 4096 + (wgi * 8 + wi * 2) * 256 + lane;
                mbar_wait_long(full, par);
                ST(sid, cw, 3);
                attn_head(q0, sb + so, sb + G_STAGE + so, full + 8, par, empty, wi, lane, dst);
                __syncwarp();
                if (lane == 0) mbar_arrive(empty + 8);
                ST(sid, cw, 4);
                mbar_wait(full + 16, par);
                ST(sid, cw, 5);
                attn_head(q1, sb + 2 * G_STAGE + so, sb + 3 * G_STAGE + so, full + 24, par, empty + 16, wi, lane, dst + 2 * 4096);
                __syncwarp();
                if (lane == 0) mbar_arrive(empty + 24);
                ST(sid, cw, 6);
                signal(item);
                it += 4;
            } else if (type == IT_O) {
                mbar_wait_long(full, (it >> 2) & 1);
                if (b < O_WIDE) o_item<256>(sb, wgi, wi, lane, full, empty, it, &mout, b * 128, i * 256);
                else o_item<128>(sb, wgi, wi, lane, full, empty, it, &mout, b * 128, i * 128);
            } else if (type == IT_S4) {
                mbar_wait_long(full, (it >> 2) & 1);
                mbar_wait(full + 24, (it >> 2) & 1);
                s4_item(sb, wgi * 4 + wi, lane, i, dsk, empty, &my);
                it += 4;
            } else break;
            WLOG(1);
        }
        bar_sync(2, 256);
        signal(item);
        if (lane == 0) asm volatile("cp.async.bulk.wait_group 0;" ::: "memory");
    }
}

typedef CUresult (*EncodeFn)(CUtensorMap*, CUtensorMapDataType, cuuint32_t, void*, const cuuint64_t*, const cuuint64_t*, const cuuint32_t*,
                             const cuuint32_t*, CUtensorMapInterleave, CUtensorMapSwizzle, CUtensorMapL2promotion, CUtensorMapFloatOOBfill);
static EncodeFn get_encode() {
    void* fn = nullptr; cudaDriverEntryPointQueryResult st;
    cudaGetDriverEntryPoint("cuTensorMapEncodeTiled", &fn, cudaEnableDefault, &st);
    return (EncodeFn)fn;
}
static void map_act(EncodeFn enc, CUtensorMap* m, const void* p, int rows, int cols, int boxr) {
    cuuint64_t dim[2] = {(cuuint64_t)cols, (cuuint64_t)rows}, str[1] = {(cuuint64_t)cols * 2};
    cuuint32_t box[2] = {64, (cuuint32_t)boxr}, es[2] = {1, 1};
    enc(m, CU_TENSOR_MAP_DATA_TYPE_BFLOAT16, 2, (void*)p, dim, str, box, es, CU_TENSOR_MAP_INTERLEAVE_NONE, CU_TENSOR_MAP_SWIZZLE_128B,
        CU_TENSOR_MAP_L2_PROMOTION_L2_128B, CU_TENSOR_MAP_FLOAT_OOB_FILL_NONE);
}
static void map_w(EncodeFn enc, CUtensorMap* m, const void* p, int k, int n) {
    cuuint64_t dim[3] = {64, (cuuint64_t)k, (cuuint64_t)n / 64}, str[2] = {(cuuint64_t)n * 2, 128};
    cuuint32_t box[3] = {64, 64, 2}, es[3] = {1, 1, 1};
    enc(m, CU_TENSOR_MAP_DATA_TYPE_BFLOAT16, 3, (void*)p, dim, str, box, es, CU_TENSOR_MAP_INTERLEAVE_NONE, CU_TENSOR_MAP_SWIZZLE_128B,
        CU_TENSOR_MAP_L2_PROMOTION_L2_256B, CU_TENSOR_MAP_FLOAT_OOB_FILL_NONE);
}

static void map_box(EncodeFn enc, CUtensorMap* m, const void* p, int rows, int ld, int boxc, int boxr, CUtensorMapSwizzle sw) {
    cuuint64_t dim[2] = {(cuuint64_t)ld, (cuuint64_t)rows}, str[1] = {(cuuint64_t)ld * 2};
    cuuint32_t box[2] = {(cuuint32_t)boxc, (cuuint32_t)boxr}, es[2] = {1, 1};
    enc(m, CU_TENSOR_MAP_DATA_TYPE_BFLOAT16, 2, (void*)p, dim, str, box, es, CU_TENSOR_MAP_INTERLEAVE_NONE, sw,
        CU_TENSOR_MAP_L2_PROMOTION_NONE, CU_TENSOR_MAP_FLOAT_OOB_FILL_NONE);
}

extern "C" void kernel_launch(void* const* d_in, const int* in_sizes, int n_in, void* d_out, int out_size) {
    const bf16* x = (const bf16*)d_in[0];
    const bf16* mem0 = (const bf16*)d_in[1];
    const bf16 *Wq = (const bf16*)d_in[2], *Wk = (const bf16*)d_in[3], *Wv = (const bf16*)d_in[4], *Wo = (const bf16*)d_in[5];
    static EncodeFn enc = nullptr;
    static int nsm = 0;
    if (!enc) {
        enc = get_encode();
        cudaDeviceGetAttribute(&nsm, cudaDevAttrMultiProcessorCount, 0);
        cudaFuncSetAttribute(chain_kernel, cudaFuncAttributeMaxDynamicSharedMemorySize, CH_SMEM);
        cudaFuncSetAttribute(worker_kernel, cudaFuncAttributeMaxDynamicSharedMemorySize, G_SMEM);
    }
    CUtensorMap mx, mq, mk, mv, mo, mout, mu, my;
    map_act(enc, &mx, x, S_LEN, DM, 128);
    map_w(enc, &mq, Wq, DM, HD); map_w(enc, &mk, Wk, DM, HD); map_w(enc, &mv, Wv, DM, HD); map_w(enc, &mo, Wo, HD, DM);
    map_box(enc, &mout, d_out, S_LEN, 2 * DM, 64, 16, CU_TENSOR_MAP_SWIZZLE_128B);
    map_box(enc, &mu, d_in[7], S_LEN, DM, 8, 256, CU_TENSOR_MAP_SWIZZLE_NONE);
    map_box(enc, &my, d_out, S_LEN, 2 * DM, 8, 256, CU_TENSOR_MAP_SWIZZLE_NONE);
    CUtensorMap cq, ck, cv, co;
    map_box(enc, &cq, Wq, DM, HD, 32, 32, CU_TENSOR_MAP_SWIZZLE_64B); map_box(enc, &ck, Wk, DM, HD, 32, 32, CU_TENSOR_MAP_SWIZZLE_64B);
    map_box(enc, &cv, Wv, DM, HD, 32, 32, CU_TENSOR_MAP_SWIZZLE_64B); map_box(enc, &co, Wo, HD, DM, 32, 16, CU_TENSOR_MAP_SWIZZLE_64B);
    S4Params P = {(const bf16*)d_in[8], (const bf16*)d_in[9], (const bf16*)d_in[10], (const bf16*)d_in[11],
                  (const bf16*)d_in[12], (const bf16*)d_in[13], (const bf16*)d_in[14], (const bf16*)d_in[15]};
    int aware = 1;
    cudaLaunchAttribute at[1];
    at[0].id = cudaLaunchAttributeProgrammaticStreamSerialization;
    at[0].val.programmaticStreamSerializationAllowed = 1;
    cudaLaunchConfig_t cfg = {};
    cfg.stream = cudaStreamPerThread;
    cfg.gridDim = dim3(96); cfg.blockDim = dim3(CH_THREADS); cfg.dynamicSmemBytes = CH_SMEM;
    cudaLaunchKernelEx(&cfg, chain_kernel, cq, ck, cv, co, Wq, Wk, Wv, mem0, P, aware);
    cfg.attrs = at; cfg.numAttrs = 1;
    cfg.gridDim = dim3(nsm); cfg.blockDim = dim3(384); cfg.dynamicSmemBytes = G_SMEM;
    cudaLaunchKernelEx(&cfg, worker_kernel, mx, mq, mk, mv, mo, mout, mu, my, P.dsk);
}
```

```cpp
#include <cuda.h>
#include <cuda_runtime.h>
#include <cuda_bf16.h>
#include <stdint.h>
#include <stdio.h>
#include <string.h>

typedef __nv_bfloat16 bf16;

constexpr int S_LEN = 2048, DM = 1024, NH = 32, DH = 128, HD = 4096, NSEG = 64;
constexpr uint32_t SENT = 0xFFFFFFFFu;
constexpr int SPIN_LIMIT = 1 << 18;
#define REALL 0

__device__ __align__(1024) bf16 g_kx[S_LEN * HD];
__device__ __align__(1024) bf16 g_vx[S_LEN * HD];
__device__ __align__(1024) bf16 g_ox[S_LEN * HD];
__device__ __align__(1024) bf16 g_km[NSEG * NH * 8 * DH];
__device__ __align__(1024) bf16 g_vm[NSEG * NH * 8 * DH];
__device__ __align__(1024) bf16 g_kd[DM * 768 + 8192];
__device__ __align__(1024) char g_ring[2 << 20];
__device__ int g_kvf[96 * 16];
constexpr int C_NEXT = 0, C_CHAIN = 32, C_QA_DONE = 64, N_CTR = 96;
__device__ int g_ctr[N_CTR];

__device__ __forceinline__ uint32_t smem_u32(const void* p) { return (uint32_t)__cvta_generic_to_shared(p); }
__device__ __forceinline__ uint32_t clk() { uint32_t c; asm volatile("mov.u32 %0, %%clock;" : "=r"(c)::"memory"); return c; }
__device__ __forceinline__ uint32_t pack_bf16(float lo, float hi) {
    uint32_t r; asm("cvt.rn.bf16x2.f32 %0, %1, %2;" : "=r"(r) : "f"(hi), "f"(lo)); return r;
}
__device__ __forceinline__ uint32_t movm(uint32_t a) {
    uint32_t d; asm volatile("movmatrix.sync.aligned.m8n8.trans.b16 %0, %1;" : "=r"(d) : "r"(a)); return d;
}
__device__ __forceinline__ void mma16(float (&d)[4], const uint32_t (&a)[4], uint32_t b0, uint32_t b1) {
    asm volatile("mma.sync.aligned.m16n8k16.row.col.f32.bf16.bf16.f32 {%0,%1,%2,%3}, {%4,%5,%6,%7}, {%8,%9}, {%0,%1,%2,%3};"
        : "+f"(d[0]), "+f"(d[1]), "+f"(d[2]), "+f"(d[3]) : "r"(a[0]), "r"(a[1]), "r"(a[2]), "r"(a[3]), "r"(b0), "r"(b1));
}
__device__ __forceinline__ void mma16z(float (&d)[4], const uint32_t (&a)[4], uint32_t b0, uint32_t b1) {
    asm volatile("mma.sync.aligned.m16n8k16.row.col.f32.bf16.bf16.f32 {%0,%1,%2,%3}, {%4,%5,%6,%7}, {%8,%9}, {%10,%10,%10,%10};"
        : "=f"(d[0]), "=f"(d[1]), "=f"(d[2]), "=f"(d[3]) : "r"(a[0]), "r"(a[1]), "r"(a[2]), "r"(a[3]), "r"(b0), "r"(b1), "f"(0.f));
}
__device__ __forceinline__ void mma8z(float (&d)[4], uint32_t a0, uint32_t a1, uint32_t b0) {
    asm volatile("mma.sync.aligned.m16n8k8.row.col.f32.bf16.bf16.f32 {%0,%1,%2,%3}, {%4,%5}, {%6}, {%7,%7,%7,%7};"
        : "=f"(d[0]), "=f"(d[1]), "=f"(d[2]), "=f"(d[3]) : "r"(a0), "r"(a1), "r"(b0), "f"(0.f));
}
__device__ __forceinline__ void ldsm4t(uint32_t (&r)[4], uint32_t addr) {
    asm volatile("ldmatrix.sync.aligned.m8n8.x4.trans.shared.b16 {%0,%1,%2,%3}, [%4];"
        : "=r"(r[0]), "=r"(r[1]), "=r"(r[2]), "=r"(r[3]) : "r"(addr) : "memory");
}
__device__ __forceinline__ void ldsm4(uint32_t (&r)[4], uint32_t addr) {
    asm volatile("ldmatrix.sync.aligned.m8n8.x4.shared.b16 {%0,%1,%2,%3}, [%4];"
        : "=r"(r[0]), "=r"(r[1]), "=r"(r[2]), "=r"(r[3]) : "r"(addr) : "memory");
}
__device__ __forceinline__ float lds32(uint32_t a) {
    float v; asm volatile("ld.shared.f32 %0, [%1];" : "=f"(v) : "r"(a) : "memory"); return v;
}
__device__ __forceinline__ void st_async1(uint32_t dst, float v, uint32_t bar) {
    asm volatile("st.async.shared::cluster.mbarrier::complete_tx::bytes.f32 [%0], %1, [%2];" ::"r"(dst), "f"(v), "r"(bar) : "memory");
}
__device__ __forceinline__ void st_async2(uint32_t dst, float x, float y, uint32_t bar) {
    asm volatile("st.async.shared::cluster.mbarrier::complete_tx::bytes.v2.f32 [%0], {%1,%2}, [%3];" ::"r"(dst), "f"(x), "f"(y), "r"(bar) : "memory");
}
__device__ __forceinline__ void mma8(float (&d)[4], uint32_t a0, uint32_t a1, uint32_t b0) {
    asm volatile("mma.sync.aligned.m16n8k8.row.col.f32.bf16.bf16.f32 {%0,%1,%2,%3}, {%4,%5}, {%6}, {%0,%1,%2,%3};"
        : "+f"(d[0]), "+f"(d[1]), "+f"(d[2]), "+f"(d[3]) : "r"(a0), "r"(a1), "r"(b0));
}
__device__ __forceinline__ void cp16(uint32_t dst, const void* src) {
    asm volatile("cp.async.cg.shared.global [%0], [%1], 16;" ::"r"(dst), "l"(src) : "memory");
}
__device__ __forceinline__ void sts128(uint32_t a, const float (&v)[4]) {
    asm volatile("st.shared.v4.f32 [%0], {%1,%2,%3,%4};" ::"r"(a), "f"(v[0]), "f"(v[1]), "f"(v[2]), "f"(v[3]) : "memory");
}
__device__ __forceinline__ float4 lds128(uint32_t a) {
    float4 v; asm volatile("ld.shared.v4.f32 {%0,%1,%2,%3}, [%4];" : "=f"(v.x), "=f"(v.y), "=f"(v.z), "=f"(v.w) : "r"(a) : "memory"); return v;
}
__device__ __forceinline__ void sts64(uint32_t a, float x, float y) {
    asm volatile("st.shared.v2.f32 [%0], {%1,%2};" ::"r"(a), "f"(x), "f"(y) : "memory");
}
__device__ __forceinline__ float2 lds64(uint32_t a) {
    float2 v; asm volatile("ld.shared.v2.f32 {%0,%1}, [%2];" : "=f"(v.x), "=f"(v.y) : "r"(a) : "memory"); return v;
}
__device__ __forceinline__ void bar_sync(int id, int n) { asm volatile("bar.sync %0, %1;" ::"r"(id), "r"(n) : "memory"); }
__device__ __forceinline__ void bar_arrive(int id, int n) { asm volatile("bar.arrive %0, %1;" ::"r"(id), "r"(n) : "memory"); }
__device__ __forceinline__ uint32_t mapa(uint32_t a, uint32_t r) {
    uint32_t o; asm("mapa.shared::cluster.u32 %0, %1, %2;" : "=r"(o) : "r"(a), "r"(r)); return o;
}
__device__ __forceinline__ void st_async4(uint32_t dst, float4 v, uint32_t bar) {
    asm volatile("st.async.shared::cluster.mbarrier::complete_tx::bytes.v4.f32 [%0], {%1,%2,%3,%4}, [%5];"
        ::"r"(dst), "f"(v.x), "f"(v.y), "f"(v.z), "f"(v.w), "r"(bar) : "memory");
}
__device__ __forceinline__ void mbar_init(uint32_t bar, int n) { asm volatile("mbarrier.init.shared.b64 [%0], %1;" ::"r"(bar), "r"(n) : "memory"); }
__device__ __forceinline__ void mbar_expect(uint32_t bar, int bytes) {
    asm volatile("mbarrier.arrive.expect_tx.shared.b64 _, [%0], %1;" ::"r"(bar), "r"(bytes) : "memory");
}
__device__ __forceinline__ void bulk_load(uint32_t dst, const void* src, int bytes, uint32_t bar) {
    asm volatile("cp.async.bulk.shared::cluster.global.mbarrier::complete_tx::bytes [%0], [%1], %2, [%3];"
        ::"r"(dst), "l"(src), "r"(bytes), "r"(bar) : "memory");
}
__device__ __forceinline__ bool mbar_try(uint32_t bar, uint32_t par) {
    uint32_t ok;
    asm volatile("{.reg .pred p; mbarrier.try_wait.parity.shared::cta.b64 p, [%1], %2; selp.u32 %0, 1, 0, p;}"
        : "=r"(ok) : "r"(bar), "r"(par) : "memory");
    return ok;
}
__device__ __forceinline__ bool mbar_test(uint32_t bar, uint32_t par) {
    uint32_t ok;
    asm volatile("{.reg .pred p; mbarrier.test_wait.parity.shared::cta.b64 p, [%1], %2; selp.u32 %0, 1, 0, p;}"
        : "=r"(ok) : "r"(bar), "r"(par) : "memory");
    return ok;
}
__device__ __forceinline__ int ld_acq(const int* p) { int v; asm volatile("ld.acquire.gpu.global.s32 %0, [%1];" : "=r"(v) : "l"(p) : "memory"); return v; }
__device__ __forceinline__ void wait_ctr(const int* p, int n) {
    for (int it = 0; it < (1 << 20) && ld_acq(p) < n; it++) __nanosleep(64);
}
__device__ __forceinline__ void mbar_wait(uint32_t bar, uint32_t par) {
    if (!mbar_try(bar, par))
        for (int it = 0; it < SPIN_LIMIT && !mbar_try(bar, par); it++) {}
}
__device__ __forceinline__ void mbar_wait_long(uint32_t bar, uint32_t par) {
    for (int it = 0; it < (1 << 24) && !mbar_try(bar, par); it++) {}
}
__device__ __forceinline__ float4 add4(float4 a, float4 b) { return make_float4(a.x + b.x, a.y + b.y, a.z + b.z, a.w + b.w); }
__device__ __forceinline__ float ex2(float x) { float y; asm("ex2.approx.ftz.f32 %0, %1;" : "=f"(y) : "f"(x)); return y; }

__device__ __forceinline__ void wgmma256(float (&d)[128], uint64_t da, uint64_t db, int acc) {
    asm volatile("{.reg .pred p; setp.ne.b32 p, %130, 0;\n"
        "wgmma.mma_async.sync.aligned.m64n256k16.f32.bf16.bf16 {"
        "%0,%1,%2,%3,%4,%5,%6,%7,%8,%9,%10,%11,%12,%13,%14,%15,"
        "%16,%17,%18,%19,%20,%21,%22,%23,%24,%25,%26,%27,%28,%29,%30,%31,"
        "%32,%33,%34,%35,%36,%37,%38,%39,%40,%41,%42,%43,%44,%45,%46,%47,"
        "%48,%49,%50,%51,%52,%53,%54,%55,%56,%57,%58,%59,%60,%61,%62,%63,"
        "%64,%65,%66,%67,%68,%69,%70,%71,%72,%73,%74,%75,%76,%77,%78,%79,"
        "%80,%81,%82,%83,%84,%85,%86,%87,%88,%89,%90,%91,%92,%93,%94,%95,"
        "%96,%97,%98,%99,%100,%101,%102,%103,%104,%105,%106,%107,%108,%109,%110,%111,"
        "%112,%113,%114,%115,%116,%117,%118,%119,%120,%121,%122,%123,%124,%125,%126,%127"
        "}, %128, %129, p, 1, 1, 0, 1;}"
        : "+f"(d[0]), "+f"(d[1]), "+f"(d[2]), "+f"(d[3]), "+f"(d[4]), "+f"(d[5]), "+f"(d[6]), "+f"(d[7]), "+f"(d[8]), "+f"(d[9]), "+f"(d[10]), "+f"(d[11]), "+f"(d[12]), "+f"(d[13]), "+f"(d[14]), "+f"(d[15]), "+f"(d[16]), "+f"(d[17]), "+f"(d[18]), "+f"(d[19]), "+f"(d[20]), "+f"(d[21]), "+f"(d[22]), "+f"(d[23]), "+f"(d[24]), "+f"(d[25]), "+f"(d[26]), "+f"(d[27]), "+f"(d[28]), "+f"(d[29]), "+f"(d[30]), "+f"(d[31]), "+f"(d[32]), "+f"(d[33]), "+f"(d[34]), "+f"(d[35]), "+f"(d[36]), "+f"(d[37]), "+f"(d[38]), "+f"(d[39]), "+f"(d[40]), "+f"(d[41]), "+f"(d[42]), "+f"(d[43]), "+f"(d[44]), "+f"(d[45]), "+f"(d[46]), "+f"(d[47]), "+f"(d[48]), "+f"(d[49]), "+f"(d[50]), "+f"(d[51]), "+f"(d[52]), "+f"(d[53]), "+f"(d[54]), "+f"(d[55]), "+f"(d[56]), "+f"(d[57]), "+f"(d[58]), "+f"(d[59]), "+f"(d[60]), "+f"(d[61]), "+f"(d[62]), "+f"(d[63]), "+f"(d[64]), "+f"(d[65]), "+f"(d[66]), "+f"(d[67]), "+f"(d[68]), "+f"(d[69]), "+f"(d[70]), "+f"(d[71]), "+f"(d[72]), "+f"(d[73]), "+f"(d[74]), "+f"(d[75]), "+f"(d[76]), "+f"(d[77]), "+f"(d[78]), "+f"(d[79]), "+f"(d[80]), "+f"(d[81]), "+f"(d[82]), "+f"(d[83]), "+f"(d[84]), "+f"(d[85]), "+f"(d[86]), "+f"(d[87]), "+f"(d[88]), "+f"(d[89]), "+f"(d[90]), "+f"(d[91]), "+f"(d[92]), "+f"(d[93]), "+f"(d[94]), "+f"(d[95]), "+f"(d[96]), "+f"(d[97]), "+f"(d[98]), "+f"(d[99]), "+f"(d[100]), "+f"(d[101]), "+f"(d[102]), "+f"(d[103]), "+f"(d[104]), "+f"(d[105]), "+f"(d[106]), "+f"(d[107]), "+f"(d[108]), "+f"(d[109]), "+f"(d[110]), "+f"(d[111]), "+f"(d[112]), "+f"(d[113]), "+f"(d[114]), "+f"(d[115]), "+f"(d[116]), "+f"(d[117]), "+f"(d[118]), "+f"(d[119]), "+f"(d[120]), "+f"(d[121]), "+f"(d[122]), "+f"(d[123]), "+f"(d[124]), "+f"(d[125]), "+f"(d[126]), "+f"(d[127])
        : "l"(da), "l"(db), "r"(acc));
}
__device__ __forceinline__ void wgmma128(float (&d)[64], uint64_t da, uint64_t db, int acc) {
    asm volatile("{.reg .pred p; setp.ne.b32 p, %66, 0;\n"
        "wgmma.mma_async.sync.aligned.m64n128k16.f32.bf16.bf16 {"
        "%0,%1,%2,%3,%4,%5,%6,%7,%8,%9,%10,%11,%12,%13,%14,%15,"
        "%16,%17,%18,%19,%20,%21,%22,%23,%24,%25,%26,%27,%28,%29,%30,%31,"
        "%32,%33,%34,%35,%36,%37,%38,%39,%40,%41,%42,%43,%44,%45,%46,%47,"
        "%48,%49,%50,%51,%52,%53,%54,%55,%56,%57,%58,%59,%60,%61,%62,%63"
        "}, %64, %65, p, 1, 1, 0, 1;}"
        : "+f"(d[0]), "+f"(d[1]), "+f"(d[2]), "+f"(d[3]), "+f"(d[4]), "+f"(d[5]), "+f"(d[6]), "+f"(d[7]), "+f"(d[8]), "+f"(d[9]), "+f"(d[10]), "+f"(d[11]), "+f"(d[12]), "+f"(d[13]), "+f"(d[14]), "+f"(d[15]), "+f"(d[16]), "+f"(d[17]), "+f"(d[18]), "+f"(d[19]), "+f"(d[20]), "+f"(d[21]), "+f"(d[22]), "+f"(d[23]), "+f"(d[24]), "+f"(d[25]), "+f"(d[26]), "+f"(d[27]), "+f"(d[28]), "+f"(d[29]), "+f"(d[30]), "+f"(d[31]), "+f"(d[32]), "+f"(d[33]), "+f"(d[34]), "+f"(d[35]), "+f"(d[36]), "+f"(d[37]), "+f"(d[38]), "+f"(d[39]), "+f"(d[40]), "+f"(d[41]), "+f"(d[42]), "+f"(d[43]), "+f"(d[44]), "+f"(d[45]), "+f"(d[46]), "+f"(d[47]), "+f"(d[48]), "+f"(d[49]), "+f"(d[50]), "+f"(d[51]), "+f"(d[52]), "+f"(d[53]), "+f"(d[54]), "+f"(d[55]), "+f"(d[56]), "+f"(d[57]), "+f"(d[58]), "+f"(d[59]), "+f"(d[60]), "+f"(d[61]), "+f"(d[62]), "+f"(d[63])
        : "l"(da), "l"(db), "r"(acc));
}
__device__ __forceinline__ void wg_fence() { asm volatile("wgmma.fence.sync.aligned;" ::: "memory"); }
__device__ __forceinline__ void wg_commit() { asm volatile("wgmma.commit_group.sync.aligned;" ::: "memory"); }
template <int N> __device__ __forceinline__ void wg_wait() { asm volatile("wgmma.wait_group.sync.aligned %0;" ::"n"(N) : "memory"); }
__device__ __forceinline__ uint64_t mkdesc(uint32_t addr, uint32_t lbo, uint32_t sbo, uint32_t sw) {
    return (uint64_t)((addr & 0x3FFFF) >> 4) | ((uint64_t)(lbo >> 4) << 16) | ((uint64_t)(sbo >> 4) << 32) | ((uint64_t)sw << 62);
}
__device__ __forceinline__ void tma2d(uint32_t dst, const CUtensorMap* m, int c0, int c1, uint32_t bar) {
    asm volatile("cp.async.bulk.tensor.2d.shared::cluster.global.mbarrier::complete_tx::bytes [%0], [%1, {%2, %3}], [%4];"
        ::"r"(dst), "l"(m), "r"(c0), "r"(c1), "r"(bar) : "memory");
}
__device__ __forceinline__ void tma3d(uint32_t dst, const CUtensorMap* m, int c0, int c1, int c2, uint32_t bar) {
    asm volatile("cp.async.bulk.tensor.3d.shared::cluster.global.mbarrier::complete_tx::bytes [%0], [%1, {%2, %3, %4}], [%5];"
        ::"r"(dst), "l"(m), "r"(c0), "r"(c1), "r"(c2), "r"(bar) : "memory");
}
__device__ __forceinline__ void tma3d_mc(uint32_t dst, const CUtensorMap* m, int c0, int c1, int c2, uint32_t bar, uint16_t mask) {
    asm volatile("cp.async.bulk.tensor.3d.shared::cluster.global.mbarrier::complete_tx::bytes.multicast::cluster [%0], [%1, {%2, %3, %4}], [%5], %6;"
        ::"r"(dst), "l"(m), "r"(c0), "r"(c1), "r"(c2), "r"(bar), "h"(mask) : "memory");
}
__device__ __forceinline__ void mbar_arrive(uint32_t bar) { asm volatile("mbarrier.arrive.shared.b64 _, [%0];" ::"r"(bar) : "memory"); }
__device__ __forceinline__ void mbar_arrive_remote(uint32_t bar) {
    asm volatile("mbarrier.arrive.shared::cluster.b64 _, [%0];" ::"r"(bar) : "memory");
}
template <int R> __device__ __forceinline__ void reg_inc() { asm volatile("setmaxnreg.inc.sync.aligned.u32 %0;" ::"n"(R)); }
template <int R> __device__ __forceinline__ void reg_dec() { asm volatile("setmaxnreg.dec.sync.aligned.u32 %0;" ::"n"(R)); }

constexpr int CH_NRES = 50;
constexpr int CH_WREG = CH_NRES * 512;
constexpr int CH_PART = 8 * CH_WREG;
constexpr int CH_SX = CH_PART + 16384;
constexpr int CH_MX = CH_SX + 3 * 1280;
constexpr int CH_QK = CH_MX;
constexpr int CH_XS = CH_MX + 3 * 512;
constexpr int CH_BAR = CH_XS + 5632;
constexpr int CH_SMEM = CH_BAR + 192;
constexpr int CH_THREADS = 384;

__device__ __forceinline__ char* ring_base() { return (char*)(((uintptr_t)g_ring + (1 << 20) - 1) & ~(uintptr_t)((1 << 20) - 1)); }
__device__ __forceinline__ uint32_t ring_off(int chunk, int side) {
    uint32_t o = ((chunk & 1) << 13) | ((chunk >> 1) << 16);
    uint32_t par = ((o >> 13) ^ (o >> 16) ^ (o >> 17) ^ (o >> 19) ^ side) & 1;
    return o | (par << 12);
}
__device__ __forceinline__ uint2 ld_poll(const char* p) {
    unsigned long long v; asm volatile("ld.relaxed.gpu.global.b64 %0, [%1];" : "=l"(v) : "l"(p) : "memory");
    return make_uint2((uint32_t)v, (uint32_t)(v >> 32));
}
__device__ __forceinline__ void st_pub(char* p, uint32_t x, uint32_t y) {
    unsigned long long v = ((unsigned long long)y << 32) | x;
    asm volatile("st.relaxed.gpu.global.b64 [%0], %1;" ::"l"(p), "l"(v) : "memory");
}
template <int N>
__device__ __forceinline__ void poll_issue(uint2 (&b)[N], const char* p, bool lastvalid) {
#pragma unroll
    for (int i = 0; i < N; i++) {
        if (i < N - 1 || lastvalid) b[i] = ld_poll(p + i * 256);
        else b[i] = make_uint2(0, 0);
    }
}
template <int N>
__device__ __forceinline__ int poll_check(uint2 (&b)[N], const char* p) {
    int it = 0;
    uint32_t mx = b[0].x;
#pragma unroll
    for (int i = 1; i < N; i++) mx = max(mx, b[i].x);
    if (__any_sync(0xffffffffu, mx == SENT)) {
        do {
#pragma unroll
            for (int i = 0; i < N; i++)
                if ((REALL && i < 10) || b[i].x == SENT) b[i] = ld_poll(p + i * 256);
            mx = b[0].x;
#pragma unroll
            for (int i = 1; i < N; i++) mx = max(mx, b[i].x);
            it++;
        } while (__any_sync(0xffffffffu, mx == SENT && it < SPIN_LIMIT));
    }
    return it;
}
template <int N>
__device__ __forceinline__ uint32_t delay(uint32_t a) {
    uint32_t z = 0;
#pragma unroll
    for (int i = 0; i < N; i++) asm volatile("ld.volatile.shared.u32 %0, [%1];" : "=r"(z) : "r"(a + z) : "memory");
    return z;
}

#define PFKV 0
#define LDW 1
constexpr int KVN = 2;
#define FEN 1
#define XB 4
#define KEEP 100
#define VCH_P 4
#define VCH_C 2
#define KGS 3
#define DLM 1
#define DLO 2
constexpr int OB = 0;
template <int PACE>
__device__ __forceinline__ void preload(uint32_t (&sw)[12][4], uint32_t a, uint32_t zero) {
    uint32_t z = 0;
#pragma unroll
    for (int i = 0; i < 12; i++) {
        if (PACE && i % (PACE ? PACE : 1) == 0) z = delay<1>(zero + z);
        ldsm4t(sw[i], a + z + i * 512);
    }
}
__device__ __forceinline__ void stsm4(uint32_t addr, uint32_t a, uint32_t b, uint32_t c, uint32_t d) {
    asm volatile("stmatrix.sync.aligned.m8n8.x4.shared.b16 [%0], {%1,%2,%3,%4};" ::"r"(addr), "r"(a), "r"(b), "r"(c), "r"(d) : "memory");
}
__device__ __forceinline__ void stsm4t(uint32_t addr, uint32_t a, uint32_t b, uint32_t c, uint32_t d) {
    asm volatile("stmatrix.sync.aligned.m8n8.x4.trans.shared.b16 [%0], {%1,%2,%3,%4};" ::"r"(addr), "r"(a), "r"(b), "r"(c), "r"(d) : "memory");
}
__device__ __forceinline__ void st_part(uint32_t addr, const float (&x)[4], const float (&y)[4]) {
    stsm4(addr, pack_bf16(x[0], x[1]), pack_bf16(x[2], x[3]), pack_bf16(y[0], y[1]), pack_bf16(y[2], y[3]));
}
template <bool TR>
__device__ __forceinline__ void red_part(uint32_t& lo, uint32_t& hi, uint32_t addr, uint32_t eye) {
    uint32_t a[4][4];
#pragma unroll
    for (int j = 0; j < 4; j++) { if (TR) ldsm4t(a[j], addr + j * 1024); else ldsm4(a[j], addr + j * 1024); }
    float r0[4], r1[4], r2[4], r3[4];
    mma16z(r0, a[0], eye, eye); mma16z(r1, a[1], eye, eye); mma16z(r2, a[2], eye, eye); mma16z(r3, a[3], eye, eye);
#pragma unroll
    for (int j = 0; j < 4; j++) r0[j] = ((r0[j] + r1[j]) + r2[j]) + r3[j];
    lo = pack_bf16(r0[0], r0[1]); hi = pack_bf16(r0[2], r0[3]);
}
__device__ __forceinline__ int o_chunk(int ks, int& pos) {
    const int cw = ks < 176 ? ks / 11 : 16 + (ks - 176) / 10;
    pos = ks - (cw < 16 ? 11 * cw : 176 + 10 * (cw - 16));
    return cw;
}

template <bool PV>
__device__ __forceinline__ void chain_loop(const uint32_t (&wa)[36][4], const uint32_t sb, const int w, const int lane0, const int rank,
                                           const int h, const int side) {
    const int rk1 = rank == 2 ? 0 : rank + 1, rk2 = rank == 0 ? 2 : rank - 1;
    const int nq = rank == 0 ? 6 : 5, u0 = rank == 0 ? 0 : 1 + 5 * rank, v0 = rank == 0 ? -6 : 3 * rank - 6;
    const uint32_t pt = CH_PART + (w >> 1) * 4096 + (w & 1) * 256;
    const uint32_t barS = sb + CH_BAR, barM = barS + 8, zero = barS + 24;
    char* const ring0 = ring_base();
    const uint32_t m_rd = ring_off(24 + w, side), o_rd = ring_off(rank * 8 + w, side);
    uint32_t pub;
    if (PV) { int pos, cw = o_chunk(h * 8 + v0 + w, pos); pub = (ring_off(cw, 0) & ~4096u) + pos * 256; }
    else pub = (ring_off(24 + (h >> 2), 0) & ~4096u) + ((2 * h + w) & 7) * 256;
    char* const kvo = (char*)(PV ? g_vm + 128 * (v0 + w) : g_km + 64 * (u0 + w)) + h * 2048;
    const bool mown = !PV && w == rank && rank < 2;
    uint32_t lo16 = lane0 * 16;
    uint32_t sw[12][4];
#pragma unroll
    for (int i = 0; i < 12; i++) ldsm4t(sw[i], sb + lo16 + w * CH_WREG + i * 512);

#pragma unroll 1
    for (int s = 0;; s++) {
        const bool last = s == NSEG - 1;
        const uint32_t slot = (s & 3) << 14;
        lo16 += delay<DLM>(zero);
        const uint32_t lane = lo16 >> 4, l16 = sb + lo16, wl = l16 + w * CH_WREG, pw = l16 + CH_PART + w * 512;
        const uint32_t xs = l16 + CH_XS + nq * 512 + (w - nq) * 1024;
        const uint32_t eye = ((lo16 >> 7) == (lane & 3)) ? ((lo16 & 64) ? 0x3F800000u : 0x3F80u) : 0u;
        uint2 b[8];
        const char* pm = ring0 + (m_rd + slot + (lo16 >> 1));
        poll_issue<8>(b, pm, true);
        poll_check<8>(b, pm);
        if ((OB || (XB & 1)) && !last) bar_arrive(8, 256 + OB);
        if (PV && !last && w == 7) bar_arrive(13, 64);
        {
            float acc[6][4];
#pragma unroll
            for (int kk = 0; kk < 8; kk++) {
                const int j = (2 * kk) % 12;
                if (kk == 0) { mma16z(acc[5], sw[0], b[0].x, b[0].y); mma16z(acc[4], sw[1], b[0].x, b[0].y); }
                else { mma16(acc[5], sw[j], b[kk].x, b[kk].y); mma16(acc[4], sw[j + 1], b[kk].x, b[kk].y); }
#pragma unroll
                for (int i = 0; i < 4; i++) {
                    if (kk == 0) mma16z(acc[i], wa[i * 8], b[0].x, b[0].y);
                    else mma16(acc[i], wa[i * 8 + kk], b[kk].x, b[kk].y);
                    if (i < 2) ldsm4t(sw[j + i], wl + (12 + 2 * kk + i) * 512);
                }
            }
            st_part(pw + 4 * 2048, acc[4], acc[5]);
            st_part(pw, acc[0], acc[1]);
            st_part(pw + 2 * 2048, acc[2], acc[3]);
        }
        uint32_t kv0, kv1;
        const uint32_t lp = l16 + (lane >> 4) * 256, pl = lp + pt;
        if (!PV) {
            bar_sync(1, last ? 256 : 256 + OB);
            red_part<true>(kv1, kv0, pl, eye);
            sts64(l16 + CH_QK + (w >> 1) * 512 + (w & 1) * 8, __uint_as_float(kv1), __uint_as_float(kv0));
            if (!last) bar_arrive(2, nq * 32 + 64 + OB);
        } else {
            bar_sync(1, last ? 256 : 256 + OB);
        }
        {
            float va[4][4];
            const float z = __uint_as_float(delay<1>(zero));
#pragma unroll
            for (int i = 0; i < 4; i++) va[i][0] = va[i][1] = va[i][2] = va[i][3] = z;
#pragma unroll
            for (int kk = 0; kk < 8; kk++) {
                const int c = (PV ? VCH_P : VCH_C) == 4 ? kk & 1 : 0;
                if (kk < 2) { mma16(va[c], wa[32 + 2 * kk], b[kk].x, b[kk].y); mma16(va[2 + c], wa[33 + 2 * kk], b[kk].x, b[kk].y); }
                else { mma16(va[c], sw[(2 * kk) % 12], b[kk].x, b[kk].y); mma16(va[2 + c], sw[(2 * kk + 1) % 12], b[kk].x, b[kk].y); }
            }
            if ((PV ? VCH_P : VCH_C) == 4) {
#pragma unroll
                for (int j = 0; j < 4; j++) { va[0][j] += va[1][j]; va[2][j] += va[3][j]; }
            }
            st_part(pw + 6 * 2048, va[0], va[2]);
        }
        if (PV) {
            uint32_t vt0[4], vt1[4];
            ldsm4t(vt0, xs); ldsm4t(vt1, xs + 512);
            if (w >= 6 && !last) {
                uint32_t kx[3][4];
#pragma unroll
                for (int j = 0; j < 3; j++)
                    ldsm4(kx[j], sb + CH_XS + j * 1024 + (j == 2 && nq == 5 ? 0 : ((lane >> 3) & 1) * 512) + (w - 6) * 256 + (lane >> 4) * 128 + (lane & 7) * 16);
                const uint32_t da = l16 + CH_SX + rank * 1280 + (w - 6) * 512, dc = sb + CH_SX + rank * 1280 + 1024 + lane * 8;
                bar_sync(2, nq * 32 + 64 + OB);
                uint32_t qk[3][4];
#pragma unroll
                for (int j = 0; j < 3; j++) {
                    const float4 v = lds128(l16 + CH_QK + j * 512);
                    qk[j][0] = __float_as_uint(v.x); qk[j][1] = __float_as_uint(v.y); qk[j][2] = __float_as_uint(v.z); qk[j][3] = __float_as_uint(v.w);
                }
                float s0[4], s1[4], s2[4], s3[4];
                mma16z(s0, qk[0], kx[0][0], kx[0][1]); mma16z(s1, qk[0], kx[0][2], kx[0][3]);
                mma16z(s2, qk[1], kx[1][0], kx[1][1]); mma16z(s3, qk[1], kx[1][2], kx[1][3]);
                if (nq == 5) qk[2][2] = qk[2][3] = 0;
                mma16(s0, qk[2], kx[2][0], kx[2][1]); mma16(s1, qk[2], kx[2][2], kx[2][3]);
                float m0[4], m1[4];
                mma16z(m0, qk[0], qk[0][1], qk[0][3]); mma16z(m1, qk[1], qk[1][1], qk[1][3]);
                mma16(m0, qk[2], qk[2][1], qk[2][3]);
                const float4 sv = make_float4(s0[0] + s2[0], s0[1] + s2[1], s1[0] + s3[0], s1[1] + s3[1]);
                st_async4(mapa(da, rk1), sv, mapa(barS, rk1));
                st_async4(mapa(da, rk2), sv, mapa(barS, rk2));
                {
                    const float c0 = m0[0] + m1[0], c1 = m0[1] + m1[1];
                    const int dr = w == 6 ? rk1 : rk2;
                    st_async2(mapa(dc, dr), c0, c1, mapa(barS, dr));
                    sts64(dc, c0, c1);
                }
                const float t4[4] = {sv.x, sv.y, sv.z, sv.w};
                sts128(da, t4);
            }
            bar_sync(3, last ? 256 : 256 + OB);
            if (!last && w == 7) bar_arrive(12, 64);
            red_part<false>(kv0, kv1, pl, eye);
            if (last) {
                uint32_t* d = (uint32_t*)(kvo + (uint32_t)(s * (NH * 2048) + lane * 4));
                d[0] = movm(kv0); d[32] = movm(kv1);
                break;
            }
            {
                const uint32_t sx = l16 + CH_SX, r0 = rank * 1280, r1 = rk1 * 1280, r2 = rk2 * 1280;
                float4 a0 = lds128(sx + r0), b0 = lds128(sx + 512 + r0);
                const float2 c0 = lds64(sx + 1024 + r0 - lane * 8);
                mbar_wait(barS, s & 1);
                const float4 a1 = lds128(sx + r1), a2 = lds128(sx + r2), b1 = lds128(sx + 512 + r1), b2 = lds128(sx + 512 + r2);
                const float2 c1 = lds64(sx + 1024 + r1 - lane * 8), c2 = lds64(sx + 1024 + r2 - lane * 8);
                a0 = add4(add4(a0, a1), a2); b0 = add4(add4(b0, b1), b2);
                float sc[10] = {a0.x, a0.y, a0.z, a0.w, b0.x, b0.y, b0.z, b0.w, c0.x + c1.x + c2.x, c0.y + c1.y + c2.y};
                float mx = fmaxf(fmaxf(fmaxf(sc[0], sc[1]), fmaxf(sc[2], sc[3])), fmaxf(fmaxf(sc[4], sc[5]), fmaxf(sc[6], sc[7])));
                mx = fmaxf(mx, fmaxf(sc[8], sc[9]));
                mx = fmaxf(fmaxf(mx, __shfl_xor_sync(0xffffffffu, mx, 1)),
                           fmaxf(__shfl_xor_sync(0xffffffffu, mx, 2), __shfl_xor_sync(0xffffffffu, mx, 3)));
                const float cs = 0.08838834764831845f * 1.4426950408889634f;
                const float mb = -mx * cs;
#pragma unroll
                for (int j = 0; j < 10; j++) sc[j] = ex2(fmaf(sc[j], cs, mb));
                uint32_t pf[5];
#pragma unroll
                for (int j = 0; j < 5; j++) pf[j] = pack_bf16(sc[2 * j], sc[2 * j + 1]);
                float o0[4], o1[4], o2[4], o3[4], o4[4], o5[4];
                const uint32_t p0[4] = {pf[0], 0, pf[1], 0}, p1[4] = {pf[2], 0, pf[3], 0};
                mma16z(o0, p0, vt0[0], vt0[1]); mma16z(o1, p0, vt1[0], vt1[1]);
                mma16z(o2, p1, vt0[2], vt0[3]); mma16z(o3, p1, vt1[2], vt1[3]);
                mma8z(o4, pf[4], 0, kv0); mma8z(o5, pf[4], 0, kv1);
                float sum = (((sc[0] + sc[1]) + (sc[2] + sc[3])) + ((sc[4] + sc[5]) + (sc[6] + sc[7]))) + (sc[8] + sc[9]);
                sum = (sum + __shfl_xor_sync(0xffffffffu, sum, 1)) + (__shfl_xor_sync(0xffffffffu, sum, 2) + __shfl_xor_sync(0xffffffffu, sum, 3));
                float inv; asm("rcp.approx.ftz.f32 %0, %1;" : "=f"(inv) : "f"(sum));
                const uint32_t ox = pack_bf16((o0[0] + o2[0] + o4[0]) * inv, (o0[1] + o2[1] + o4[1]) * inv);
                const uint32_t oy = pack_bf16((o1[0] + o3[0] + o5[0]) * inv, (o1[1] + o3[1] + o5[1]) * inv);
                char* const pp = ring0 + (pub + slot + (lo16 >> 1));
                st_pub(pp, ox, oy); st_pub(pp + 4096, ox, oy);
                if (OB || (XB & 4)) bar_arrive(10, (8 - nq) * 32 + OB);
                preload<0>(sw, wl + 28 * 512, zero);
            }
            kv0 = movm(kv0); kv1 = movm(kv1);
        } else {
            *(uint32_t*)(kvo + (uint32_t)(s * (NH * 2048) + lane * 4)) = kv0;
            bar_sync(3, last ? 256 : 256 + OB);
            if (last) break;
            preload<1>(sw, wl + 28 * 512, zero);
        }
        uint2 c[11];
        bar_sync(4, 256 + OB);
        const char* po = ring0 + (o_rd + slot + (lo16 >> 1) + delay<DLO>(zero));
        poll_issue<11>(c, po, rank < 2);
        if (PV) { uint32_t* d = (uint32_t*)(kvo + (uint32_t)(s * (NH * 2048) + lane * 4)); d[0] = kv0; d[32] = kv1; }
        poll_check<11>(c, po);
        if (OB || (XB & 2)) bar_arrive(9, 256 + OB);
        {
            float acc[4][4];
#pragma unroll
            for (int f = 0; f < 22; f++) {
                const int kk = f >> 1, a = f & 3;
                if (f < 4) mma16z(acc[a], sw[f % 12], c[kk].x, c[kk].y);
                else mma16(acc[a], sw[f % 12], c[kk].x, c[kk].y);
                if (f + 12 < 22) ldsm4t(sw[f % 12], wl + (28 + f + 12) * 512);
            }
#pragma unroll
            for (int i = 0; i < 2; i++) {
#pragma unroll
                for (int j = 0; j < 4; j++) acc[i][j] += acc[i + 2][j];
                sts128(l16 + CH_PART + i * 4096 + w * 512, acc[i]);
            }
        }
        if (!PV && w < 2) {
            bar_sync(5, 288 + OB);
            float4 v[8];
#pragma unroll
            for (int i = 0; i < 8; i++) v[i] = lds128(l16 + CH_PART + w * 4096 + i * 512);
            float4 r = add4(add4(add4(v[0], v[1]), add4(v[2], v[3])), add4(add4(v[4], v[5]), add4(v[6], v[7])));
            if (!mown) st_async4(mapa(l16 + CH_MX + rank * 512, w), r, mapa(barM, w));
            bar_arrive(7, 256 + OB);
            if (mown) {
                mbar_wait(barM, s & 1);
                float4 x = lds128(l16 + CH_MX + (rank ^ 1) * 512), y = lds128(l16 + CH_MX + 2 * 512);
                r = add4(add4(x, r), y);
                const uint32_t mx = movm(pack_bf16(r.x, r.y)), my = movm(pack_bf16(r.z, r.w));
                const uint32_t ns = (slot + 0x4000) & 0xC000;
                char* const pp = ring0 + (pub + ns + (lo16 >> 1));
                st_pub(pp, mx, my); st_pub(pp + 4096, mx, my);
            }
            preload<0>(sw, wl, zero);
        } else {
            bar_arrive(5, 288 + OB);
            bar_sync(7, 256 + OB);
            preload<2>(sw, wl, zero);
        }
        bar_sync(6, 320 + OB);
    }
    bar_arrive(6, 288);
}

__device__ __forceinline__ void chain_pace(const uint32_t sb, const int lane, const int rank, const int aware) {
    const uint32_t zero = sb + CH_BAR + 24;
    if (lane == 0) {
        char* ring = ring_base();
        uint32_t* p0 = (uint32_t*)(ring + ring_off(blockIdx.x & 15, 0) + 3072 + (blockIdx.x >> 4) * 128);
        uint32_t* p1 = (uint32_t*)(ring + ring_off(blockIdx.x & 15, 1) + 3072 + (blockIdx.x >> 4) * 128);
        *p0 = 0; *p1 = 0;
        int b0 = 1 << 30, b1 = 1 << 30; uint32_t v = 0;
        for (int r = 0; r < 4 || (r < 256 && !mbar_test(sb + CH_BAR + 16, 0)); r++) {
            uint32_t t0 = clk(); v = atomicExch(p0 + (v == 500), r); uint32_t t1 = v == 777 ? clk() + 1 : clk(); b0 = min(b0, (int)(t1 - t0));
            t0 = clk(); v = atomicExch(p1 + (v == 500), r); t1 = v == 777 ? clk() + 1 : clk(); b1 = min(b1, (int)(t1 - t0));
            asm volatile("st.volatile.shared.u32 [%0], %1;" ::"r"(zero + 4), "r"(aware ? (b1 < b0) ^ (aware - 1) : 0) : "memory");
        }
    }
    __syncwarp();
#pragma unroll 1
    for (int s = 1; s < NSEG; s++) {
        bar_sync(5, 288 + OB);
        bar_arrive(6, 320 + OB + (rank == 2 ? delay<18>(zero) : 0));
    }
}
__device__ __forceinline__ char* reset_ptr(const int lane, const int rank, const int h) {
    const int nq = rank == 0 ? 6 : 5, v0 = rank == 0 ? -6 : 3 * rank - 6;
    int pos, cw = o_chunk(h * 8 + v0 + min(max(5 + (lane >> 3), nq), 7), pos);
    if (lane >= 24 && rank < 2) { cw = 24 + (h >> 2); pos = (2 * h + rank) & 7; }
    return ring_base() + ((ring_off(cw, 0) & ~4096u) + pos * 256 + (lane & 7) * 16);
}
__device__ __forceinline__ void chain_chores(const uint32_t sb, const int lane, const int rank, const int h, const bf16* __restrict__ mem0) {
    const int nq = rank == 0 ? 6 : 5, u0 = rank == 0 ? 0 : 1 + 5 * rank, v0 = rank == 0 ? -6 : 3 * rank - 6;
    const uint32_t barS = sb + CH_BAR, barM = barS + 8, barX = barS + 16;
    auto xload = [&](int s) {
        mbar_expect(barX, 8192 - nq * 512);
        bulk_load(sb + CH_XS, g_kx + (size_t)(s * NH + h) * 4096 + u0 * 256, nq * 512, barX);
        bulk_load(sb + CH_XS + nq * 512, g_vx + (size_t)(s * NH + h) * 4096 + (v0 + nq) * 512, (8 - nq) * 1024, barX);
    };
    char* const rb = reset_ptr(lane, rank, h);
    int* const kvf = g_kvf + blockIdx.x * 16;
    if (rank < 2) {
        const uint32_t* p = (const uint32_t*)(mem0 + (lane >> 2) * DM + 32 * h + 16 * rank + 2 * (lane & 3));
        char* d = ring_base() + ((ring_off(24 + (h >> 2), 0) & ~4096u) + ((2 * h + rank) & 7) * 256 + lane * 8);
        const uint32_t x = p[0] == SENT ? 0x7FFF7FFFu : p[0];
        st_pub(d, x, p[4]); st_pub(d + 4096, x, p[4]);
    }
    if (lane == 0) {
        if (!KVN) __nanosleep(18000);
        wait_ctr(kvf, KVN);
        asm volatile("fence.proxy.async;" ::: "memory");
        xload(0);
    }
#pragma unroll 1
    for (int s = 0; s < NSEG - 1; s++) {
        if (lane == 0) {
            mbar_expect(barS, 2 * 1280);
            if (rank < 2) mbar_expect(barM, 2 * 512);
        }
        bar_sync(13, 64);
#pragma unroll
        for (int i = 0; i < 4; i++)
            asm volatile("st.relaxed.gpu.global.v4.u32 [%0], {%1,%1,%1,%1};" ::"l"(rb + ((((s + 2) & 3) << 14) + (i >> 1) * 4096 + (i & 1) * 128)), "r"(SENT) : "memory");
        if (FEN || (s & 3) == 0) __threadfence();
        if (lane == 0 && (s & 3) == 0 && s) atomicAdd(g_ctr + C_CHAIN + (s >> 2) - 1, 1);
        if (lane == 0 && (s & 3) == 3) { wait_ctr(kvf + (s >> 2) + 1, KVN); asm volatile("fence.proxy.async;" ::: "memory"); }
        __syncwarp();
        bar_sync(12, 64);
        if (lane == 0) xload(s + 1);
        mbar_wait(barX, (s + 1) & 1);
        bar_sync(6, 320 + OB);
    }
    bar_sync(6, 288);
    __threadfence();
    if (lane == 0) atomicAdd(g_ctr + C_CHAIN + 15, 1);
}

struct S4Params { const bf16 *Are, *Aim, *Bre, *Bim, *Cre, *Cim, *ldt, *dsk; };
__device__ __forceinline__ float2 cmul(float2 a, float2 b) { return make_float2(a.x * b.x - a.y * b.y, a.x * b.y + a.y * b.x); }
__device__ __forceinline__ float2 csq(float2 a) { return make_float2(a.x * a.x - a.y * a.y, (a.x + a.x) * a.y); }
__device__ __forceinline__ float2 cexp_t(float lr, float turns) {
    float f = (turns - rintf(turns)) * 6.283185307179586f, e = ex2(lr);
    return make_float2(e * __cosf(f), e * __sinf(f));
}
__device__ __forceinline__ float bf_at(uint2 v, int i) {
    const uint32_t w = i < 2 ? v.x : v.y;
    return __uint_as_float((i & 1) ? w & 0xFFFF0000u : w << 16);
}
__device__ __forceinline__ void kg_step(uint32_t (&a)[4][4], uint32_t (&b)[5][2], uint32_t pa, uint32_t pe, float x0) {
#pragma unroll
    for (int i = 0; i < 2; i++) {
        const float4 p = lds128(pa + i * 64);
        const float2 e8 = lds64(pe + i * 32), c = make_float2(p.z, p.w);
        const float mag = ex2(p.x * x0), ph = p.y * x0;
        float2 e0 = make_float2(mag * __cosf(ph), mag * __sinf(ph)), e1 = cmul(e0, e8);
#pragma unroll
        for (int j = 0; j < 4; j++) {
            a[j][2 * i] = pack_bf16(e0.x, e0.y); a[j][2 * i + 1] = pack_bf16(e1.x, e1.y);
            e0 = csq(e0); e1 = csq(e1);
        }
        float2 m = cmul(c, e0);
        b[0][i] = pack_bf16(m.x, -m.y);
#pragma unroll
        for (int j = 0; j < 4; j++) {
            m = cmul(c, e1);
            b[j + 1][i] = pack_bf16(m.x, -m.y);
            if (j < 3) e1 = csq(e1);
        }
    }
}
__device__ __forceinline__ void kg_mma(float (&kd)[5][4], const uint32_t (&a)[4][4], const uint32_t (&b)[5][2]) {
    mma16(kd[0], a[0], b[0][0], b[0][1]);
#pragma unroll
    for (int j = 0; j < 4; j++) mma16(kd[j + 1], a[j], b[j + 1][0], b[j + 1][1]);
}
struct KgRaw { uint2 v[6]; float ldt; };
__device__ __forceinline__ void kg_load(KgRaw& r, const S4Params& P, int d, int lane) {
    const bf16* src[6] = {P.Are, P.Aim, P.Bre, P.Bim, P.Cre, P.Cim};
#pragma unroll
    for (int j = 0; j < 6; j++) r.v[j] = __ldg((const uint2*)(src[j] + d * 128) + lane);
    r.ldt = __bfloat162float(P.ldt[d]);
}
__device__ __forceinline__ float kg_params(const KgRaw& r, uint32_t stg, int lane) {
    const float dt = __bfloat162float(__float2bfloat16(expf(r.ldt)));
    float k2048 = 0.f;
#pragma unroll
    for (int i = 0; i < 4; i++) {
        const float br = dt * bf_at(r.v[2], i), bi = dt * bf_at(r.v[3], i), cr = bf_at(r.v[4], i), ci = bf_at(r.v[5], i);
        const float zr = dt * bf_at(r.v[0], i) * 1.4426950408889634f;
        float zt = dt * bf_at(r.v[1], i) * 0.15915494309189535f;
        zt -= rintf(zt);
        const float v[4] = {zr, zt * 6.283185307179586f, cr * br - ci * bi, cr * bi + ci * br};
        const float2 e8 = cexp_t(8.f * zr, 8.f * zt), el = cexp_t(2048.f * zr, 2048.f * zt);
        k2048 += v[2] * el.x - v[3] * el.y;
        sts128(stg + (i * 32 + lane) * 16, v);
        sts64(stg + 2048 + (i * 32 + lane) * 8, e8.x, e8.y);
    }
#pragma unroll
    for (int o = 16; o; o >>= 1) k2048 += __shfl_xor_sync(0xffffffffu, k2048, o);
    __syncwarp();
    return k2048;
}
__device__ __forceinline__ void kg_store(const float (&kd)[5][4], float k2048, uint32_t stg, int d, int lane) {
    __syncwarp();
    const uint32_t ta = stg + (lane & 7) * 32 + ((lane >> 3) & 1) * 16 + (lane >> 4) * 256;
    stsm4t(ta, pack_bf16(kd[0][0], kd[0][1]), pack_bf16(kd[0][2], kd[0][3]), pack_bf16(kd[1][0], kd[1][1]), pack_bf16(kd[1][2], kd[1][3]));
    stsm4t(ta + 512, pack_bf16(kd[2][0], kd[2][1]), pack_bf16(kd[2][2], kd[2][3]), pack_bf16(kd[3][0], kd[3][1]), pack_bf16(kd[3][2], kd[3][3]));
    stsm4t(ta + 1024, pack_bf16(kd[4][0], kd[4][1]), pack_bf16(kd[4][2], kd[4][3]), pack_bf16(k2048, 0.f), 0);
    __syncwarp();
#pragma unroll
    for (int j = 0; j < 3; j++) ((float4*)(g_kd + d * 768))[j * 32 + lane] = lds128(stg + j * 512 + lane * 16);
    __syncwarp();
}

__global__ void __cluster_dims__(3, 1, 1) __launch_bounds__(CH_THREADS, 1)
chain_kernel(const __grid_constant__ CUtensorMap mq, const __grid_constant__ CUtensorMap mk, const __grid_constant__ CUtensorMap mv,
             const __grid_constant__ CUtensorMap mo, const bf16* __restrict__ Wq, const bf16* __restrict__ Wk, const bf16* __restrict__ Wv,
             const bf16* __restrict__ mem0, const __grid_constant__ S4Params P, int aware) {
    extern __shared__ __align__(1024) unsigned char smem[];
    const uint32_t sb = smem_u32(smem);
    const int tid = threadIdx.x, lane = tid & 31;
    const int w = __shfl_sync(0xffffffffu, tid >> 5, 0);
    int rank; asm("mov.u32 %0, %%cluster_ctarank;" : "=r"(rank));
    const int h = blockIdx.x / 3;
    if (tid == 0) {
        mbar_init(sb + CH_BAR, 1); mbar_init(sb + CH_BAR + 8, 1); mbar_init(sb + CH_BAR + 16, 1);
        for (int i = 0; i < 16; i++) mbar_init(sb + CH_BAR + 64 + i * 8, 1);
        *(int*)(smem + CH_BAR + 24) = 0; *(int*)(smem + CH_BAR + 28) = 0; *(int*)(smem + CH_BAR + 32) = 0;
        asm volatile("fence.mbarrier_init.release.cluster;" ::: "memory");
    }
    if (w == 10 && PFKV) {
        const int e = lane * 96 + blockIdx.x;
        if (e < 2048) asm volatile("cp.async.bulk.prefetch.L2.global [%0], 8192;" ::"l"(((e & 1) ? Wv : Wk) + (size_t)(e >> 1) * HD) : "memory");
        if (PFKV > 1) __nanosleep(PFKV);
    }
    if (w == 9) {
        char* const rb = reset_ptr(lane, rank, h);
#pragma unroll
        for (int i = 0; i < 8; i++)
            asm volatile("st.relaxed.gpu.global.v4.u32 [%0], {%1,%1,%1,%1};" ::"l"(rb + (((i >> 2) << 14) + ((i >> 1) & 1) * 4096 + (i & 1) * 128)), "r"(SENT) : "memory");
        if (lane < 16) g_kvf[blockIdx.x * 16 + lane] = 0;
        if (blockIdx.x == 0)
            for (int k = lane; k < N_CTR; k += 32) g_ctr[k] = 0;
        __threadfence();
        __syncwarp();
        asm volatile("griddepcontrol.launch_dependents;" ::: "memory");
    }
    __syncthreads();
    asm volatile("barrier.cluster.arrive.relaxed.aligned;" ::: "memory");

    if (w >= 8) {
        reg_dec<24>();
        asm volatile("barrier.cluster.wait.aligned;" ::: "memory");
        if (w == 8) chain_pace(sb, lane, rank, aware);
        else if (w == 9) {
            chain_chores(sb, lane, rank, h, mem0);
            asm volatile("st.volatile.shared.u32 [%0], %1;" ::"r"(sb + CH_BAR + 32), "r"(0x3F803F80) : "memory");
        } else if (w == 11 && KEEP) {
#pragma unroll 1
            for (int it = 0; it < (1 << 22); it++) {
                int d0, d1;
                const uint32_t x = delay<1>(sb + CH_BAR + 32);
                asm volatile("mma.sync.aligned.m8n8k16.row.col.s32.s8.s8.s32 {%0,%1}, {%2}, {%2}, {%3,%3};" : "=r"(d0), "=r"(d1) : "r"(x), "r"(0));
                if (d0 | d1) break;
                if ((XB & 8) && lane == 0) asm volatile("st.relaxed.gpu.global.u32 [%0], %1;" ::"l"(g_kd + DM * 768 + blockIdx.x * 64), "r"(it) : "memory");
                if ((XB & 16) && lane == 0) ld_acq((int*)(g_kd + DM * 768 + blockIdx.x * 64));
                __nanosleep(KEEP);
            }
        }
    } else {
        reg_inc<240>();
        const int nq = rank == 0 ? 6 : 5;
        const int u0 = rank == 0 ? 0 : 1 + 5 * rank;
        const int v0 = rank == 0 ? -6 : 3 * rank - 6;
        const int gw = rank * 8 + w;
        const int ks0 = gw < 16 ? 11 * gw : 176 + 10 * (gw - 16);
        const int nko = gw < 16 ? 11 : 10;
        const uint32_t wr = sb + w * CH_WREG, bar0 = sb + CH_BAR + 64 + w * 16, bar1 = bar0 + 8;
        uint32_t wa[36][4];
        const uint32_t vst = sb + CH_PART + w * 2048;
        const int cq = h * DH + 8 * u0, cv = h * DH + 16 * (v0 + 6);
        const int r8 = lane >> 2, p = lane & 3;
        const bf16* src = p >= 2 ? ((p & 1) ? Wk : Wq) + cq + 32 : rank == 0 ? ((p & 1) ? Wk : Wq) + cq + 40 : Wv + cv - 16 + 8 * p;
        src += (size_t)(128 * w + r8) * HD;
        auto cp_rows = [&](int kh) {
            cp16(wr + ((kh >> 1) * 2 + (p >> 1)) * 512 + ((kh & 1) * 2 + (p & 1)) * 128 + r8 * 16, src + (size_t)kh * 8 * HD);
        };
        {
            int d = blockIdx.x * 8 + w, t = 0;
            const int d1 = 768 + blockIdx.x * 3 + w, nt = (w < 3 && d1 < DM) ? 32 : 16;
            const uint32_t stg = wr + 4096;
            KgRaw raw, raw1;
            kg_load(raw, P, d, lane);
            kg_load(raw1, P, min(d1, DM - 1), lane);
            float kd[5][4], k2048;
#pragma unroll 1
            for (int i = -LDW; i < 9 || t < nt; i++) {
                if (i >= 0 && i < 9) {
                    const uint32_t bar = bar0 + (i & 1) * 8;
                    if (i >= 2) mbar_wait(bar, ((i >> 1) - 1) & 1);
                    if (lane == 0) {
                        mbar_expect(bar, 2048);
                        if (i < 8) tma2d(wr + 8192 + (i & 1) * 8192 + (i >> 1) * 2048, (i & 1) ? &mk : &mq, cq, 128 * w + 32 * (i >> 1), bar);
                        else tma2d(vst, &mv, cv, 128 * w, bar);
                    }
                    if (i < 8) cp_rows(i);
                }
#pragma unroll 1
                for (int e = min(t + KGS, nt); t < e; t++) {
                    if ((t & 15) == 0) {
                        k2048 = kg_params(raw, stg, lane);
#pragma unroll
                        for (int j = 0; j < 20; j++) kd[j >> 2][j & 3] = 0.f;
                    }
                    uint32_t ka[4][4], kb[5][2];
                    kg_step(ka, kb, stg + ((t & 15) * 8 + (lane & 3)) * 16, stg + 2048 + ((t & 15) * 8 + (lane & 3)) * 8, (float)(lane >> 2));
                    kg_mma(kd, ka, kb);
                    if ((t & 15) == 15) { kg_store(kd, k2048, stg, d, lane); raw = raw1; d = d1; }
                }
            }
        }
        const uint32_t lrow = ((lane >> 4) * 8 + (lane & 7)) * 64, lsw = (lane >> 1) & 3, lh = (lane >> 3) & 1;
        mbar_wait(bar1, 1); mbar_wait(bar0, 0);
#pragma unroll
        for (int i = 0; i < 32; i++) ldsm4t(wa[i], wr + 8192 + lh * 8192 + (i & 7) * 1024 + lrow + (((i >> 3) ^ lsw) << 4));
#pragma unroll
        for (int i = 0; i < 4; i++) ldsm4t(wa[32 + i], vst + (i >> 1) * 1024 + lrow + ((((i & 1) * 2 + lh) ^ lsw) << 4));
        asm volatile("fence.proxy.async.shared::cta;" ::"r"(wa[31][0]), "r"(wa[35][0]) : "memory");
        __syncwarp();
#pragma unroll 1
        for (int i = 9; i < 18; i++) {
            const uint32_t bar = bar0 + (i & 1) * 8;
            if (i >= 11) mbar_wait(bar, ((i >> 1) - 1) & 1);
            if (lane == 0) {
                const int j = 2 * (i - 12), nb = min(2, nko - j);
                mbar_expect(bar, i < 12 ? 2048 : nb * 1024);
                if (i < 12) tma2d(wr + 8192 + (i - 9) * 2048, &mv, cv, 128 * w + 32 * (i - 8), bar);
                else for (int e = 0; e < nb; e++) tma2d(wr + 14336 + (j + e) * 1024, &mo, 32 * h, 16 * (ks0 + j + e), bar);
            }
            if (i < 17) cp_rows(i - 1);
        }
        mbar_wait(bar0, 0); mbar_wait(bar1, 0);
#pragma unroll 1
        for (int i = 0; i < 17; i++) {
            uint32_t x[4], y[4];
            ldsm4t(x, wr + 8192 + i * 1024 + lrow + ((lh ^ lsw) << 4));
            ldsm4t(y, wr + 8192 + i * 1024 + lrow + (((2 + lh) ^ lsw) << 4));
            if (i == 16 && nko == 10) x[0] = x[1] = x[2] = x[3] = y[0] = y[1] = y[2] = y[3] = 0;
            __syncwarp();
            stsm4t(wr + 8192 + i * 1024 + lane * 16, x[0], x[1], x[2], x[3]);
            stsm4t(wr + 8192 + i * 1024 + 512 + lane * 16, y[0], y[1], y[2], y[3]);
        }
        asm volatile("cp.async.wait_all;" ::: "memory");
        asm volatile("barrier.cluster.wait.aligned;" ::: "memory");
        bar_sync(1, 256);
        mbar_wait_long(sb + CH_BAR + 16, 0);
        const int side = __shfl_sync(0xffffffffu, *(volatile int*)(smem + CH_BAR + 28), 0);
        if (w >= nq) chain_loop<true>(wa, sb, w, lane, rank, h, side);
        else chain_loop<false>(wa, sb, w, lane, rank, h, side);
    }
}

constexpr int G_STAGE = 49152, G_NST = 4;
constexpr int G_STG = G_NST * G_STAGE;
constexpr int G_BAR = G_STG + 32768;
constexpr int G_SMEM = G_BAR + 256 + 1024;

#define ST(id, w, i)
#define WLOG(e)
constexpr int IT_QA = 0, IT_O = 1, IT_S4 = 2, IT_END = 3, IT_KV = 4;
#define Q_A 11
#define Q_W1 9
#define O_WIDE 11
#define KVP 0
#define KVS 8
#define STM 0
__device__ __forceinline__ void st_out(uint32_t* p, uint32_t v) {
    if (STM == 0) *p = v;
    else if (STM == 1) __stcs(p, v);
    else asm volatile("st.global.L1::no_allocate.u32 [%0], %1;" ::"l"(p), "r"(v) : "memory");
}
#define Q_S1 8
__device__ __forceinline__ int queue_item(int q) {
    if (KVP && q >= KVP && q < 512) return (IT_KV << 16) | (((q >> 6) * 2 + (q & 1)) << 8) | ((q >> 1) & 31);
    if (q < 512) return (IT_KV << 16) | ((q >> 5) << 8) | (q & 31);
    q -= 512;
    if (q < Q_A * 16) return (IT_QA << 16) | ((q >> 4) << 8) | (q & 15);
    q -= Q_A * 16;
    if (q < Q_W1 * 4) return (IT_O << 16) | ((q >> 2) << 8) | (q & 3);
    q -= Q_W1 * 4;
    if (q < (16 - Q_A) * 16) return (IT_QA << 16) | ((Q_A + (q >> 4)) << 8) | (q & 15);
    q -= (16 - Q_A) * 16;
    if (q < (O_WIDE - Q_W1) * 4) return (IT_O << 16) | ((Q_W1 + (q >> 2)) << 8) | (q & 3);
    q -= (O_WIDE - Q_W1) * 4;
    if (q < Q_S1) return (IT_S4 << 16) | q;
    q -= Q_S1;
    if (q < (16 - O_WIDE) * 8) return (IT_O << 16) | ((O_WIDE + (q >> 3)) << 8) | (q & 7);
    q -= (16 - O_WIDE) * 8;
    if (q < 128 - Q_S1) return (IT_S4 << 16) | (Q_S1 + q);
    return IT_END << 16;
}
__device__ __forceinline__ void tma2d_store(const CUtensorMap* m, uint32_t src, int c0, int c1) {
    asm volatile("cp.async.bulk.tensor.2d.global.shared::cta.bulk_group [%0, {%2, %3}], [%1];" ::"l"(m), "r"(src), "r"(c0), "r"(c1) : "memory");
}

__device__ __forceinline__ void attn_head(const uint32_t (&q)[32], uint32_t sk, uint32_t sv, uint32_t fullv, uint32_t parv, uint32_t emptyk,
                                          int wi, int lane, uint32_t* dst) {
    const int g = lane >> 2, t = lane & 3, hi = wi & 1;
    float s[5][4];
#pragma unroll
    for (int j = 0; j < 5; j++) s[j][0] = s[j][1] = s[j][2] = s[j][3] = 0.f;
#pragma unroll
    for (int k2 = 0; k2 < 4; k2++) {
        uint32_t km[4];
        ldsm4(km, sk + 8192 + k2 * 512 + lane * 16);
#pragma unroll
        for (int i = 0; i < 2; i++) {
            const int ks = 2 * k2 + i;
            const uint32_t a[4] = {q[4 * ks], q[4 * ks + 1], q[4 * ks + 2], q[4 * ks + 3]};
            uint32_t b[4];
            const uint32_t ad = sk + ks * 1024 + ((lane >> 3) & 1) * 512 + (lane >> 4) * 128 + (lane & 7) * 16;
            ldsm4(b, ad);
            mma16(s[4], a, km[2 * i], km[2 * i + 1]);
            mma16(s[0], a, b[0], b[1]); mma16(s[1], a, b[2], b[3]);
            if (hi) { ldsm4(b, ad + 256); mma16(s[2], a, b[0], b[1]); mma16(s[3], a, b[2], b[3]); }
        }
    }
    __syncwarp();
    if (lane == 0) mbar_arrive(emptyk);
    const int r0 = hi * 16 + g;
    float m0 = fmaxf(s[4][0], s[4][1]), m1 = fmaxf(s[4][2], s[4][3]);
#pragma unroll
    for (int j = 0; j < 4; j++) {
        const int c = 8 * j + 2 * t;
        if (c > r0) s[j][0] = -INFINITY;
        if (c + 1 > r0) s[j][1] = -INFINITY;
        if (c > r0 + 8) s[j][2] = -INFINITY;
        if (c + 1 > r0 + 8) s[j][3] = -INFINITY;
        m0 = fmaxf(m0, fmaxf(s[j][0], s[j][1])); m1 = fmaxf(m1, fmaxf(s[j][2], s[j][3]));
    }
    m0 = fmaxf(m0, __shfl_xor_sync(0xffffffffu, m0, 1)); m1 = fmaxf(m1, __shfl_xor_sync(0xffffffffu, m1, 1));
    m0 = fmaxf(m0, __shfl_xor_sync(0xffffffffu, m0, 2)); m1 = fmaxf(m1, __shfl_xor_sync(0xffffffffu, m1, 2));
    const float cs = 0.08838834764831845f * 1.4426950408889634f;
    m0 *= -cs; m1 *= -cs;
    float l0 = 0, l1 = 0;
#pragma unroll
    for (int j = 0; j < 5; j++) {
        s[j][0] = ex2(fmaf(s[j][0], cs, m0)); s[j][1] = ex2(fmaf(s[j][1], cs, m0));
        s[j][2] = ex2(fmaf(s[j][2], cs, m1)); s[j][3] = ex2(fmaf(s[j][3], cs, m1));
        l0 += s[j][0] + s[j][1]; l1 += s[j][2] + s[j][3];
    }
    l0 += __shfl_xor_sync(0xffffffffu, l0, 1); l1 += __shfl_xor_sync(0xffffffffu, l1, 1);
    l0 += __shfl_xor_sync(0xffffffffu, l0, 2); l1 += __shfl_xor_sync(0xffffffffu, l1, 2);
    l0 = __fdividef(1.f, l0); l1 = __fdividef(1.f, l1);
    uint32_t p[10];
#pragma unroll
    for (int j = 0; j < 5; j++) { p[2 * j] = pack_bf16(s[j][0] * l0, s[j][1] * l0); p[2 * j + 1] = pack_bf16(s[j][2] * l1, s[j][3] * l1); }
    const uint32_t p0[4] = {p[0], p[1], p[2], p[3]}, p1[4] = {p[4], p[5], p[6], p[7]};
    mbar_wait(fullv, parv);
#pragma unroll
    for (int u4 = 0; u4 < 4; u4++) {
        uint32_t vm[4];
        ldsm4t(vm, sv + 8192 + u4 * 512 + lane * 16);
#pragma unroll
        for (int i = 0; i < 4; i++) {
            const int u = 4 * u4 + i;
            uint32_t b[4];
            ldsm4t(b, sv + u * 512 + lane * 16);
            float o[4];
            mma16z(o, p0, b[0], b[1]);
            if (hi) mma16(o, p1, b[2], b[3]);
            mma8(o, p[8], p[9], vm[i]);
            dst[(u >> 3) * 4096 + (u & 7) * 32] = pack_bf16(o[0], o[1]);
            dst[(u >> 3) * 4096 + (u & 7) * 32 + 256] = pack_bf16(o[2], o[3]);
        }
    }
}

template <int BN, int NKB, bool BLOCKED_A>
__device__ __forceinline__ void mainloop(float (&acc)[BN / 2], uint32_t sb, int wgi, uint32_t full, uint32_t empty, int& it, bool elect) {
#pragma unroll
    for (int j = 0; j < BN / 2; j++) acc[j] = 0.f;
#pragma unroll 1
    for (int k4 = 0; k4 < NKB; k4 += 4) {
#pragma unroll
        for (int st = 0; st < 4; st++, it++) {
            mbar_wait(full + 8 * st, (it >> 2) & 1);
            const uint64_t da = BLOCKED_A ? mkdesc(sb + st * G_STAGE + wgi * 8192, 128, 1024, 0) : mkdesc(sb + st * G_STAGE + wgi * 8192, 16, 1024, 1);
            const uint64_t db = mkdesc(sb + st * G_STAGE + 16384, 8192, 1024, 1);
            wg_fence();
#pragma unroll
            for (int k = 0; k < 4; k++) {
                if constexpr (BN == 256) wgmma256(acc, da + k * (BLOCKED_A ? 16 : 2), db + k * 128, 1);
                else wgmma128(acc, da + k * (BLOCKED_A ? 16 : 2), db + k * 128, 1);
            }
            wg_commit();
            if (k4 | st) {
                wg_wait<1>();
                if (elect) mbar_arrive(empty + 8 * ((st + 3) & 3));
            }
        }
    }
    wg_wait<0>();
    if (elect) mbar_arrive(empty + 8 * 3);
}

template <int BN>
__device__ __forceinline__ void o_item(uint32_t sb, int wgi, int wi, int lane, uint32_t full, uint32_t empty, int& it, const CUtensorMap* mout,
                                       int row0, int col0) {
    float acc[BN / 2];
    mainloop<BN, 64, true>(acc, sb, wgi, full, empty, it, lane == 0);
    const uint32_t stg = sb + G_STG + (wgi * 4 + wi) * 4096;
    const int r = lane & 15, cu = lane >> 4;
#pragma unroll
    for (int hf = 0; hf < BN / 128; hf++) {
        if (lane == 0) asm volatile("cp.async.bulk.wait_group.read 0;" ::: "memory");
        __syncwarp();
#pragma unroll
        for (int j = 0; j < 8; j++) {
            const float* a = acc + hf * 64 + j * 8;
            stsm4(stg + (j >> 2) * 2048 + r * 128 + ((((j & 3) * 2 + cu) ^ (r & 7)) << 4),
                  pack_bf16(a[0], a[1]), pack_bf16(a[2], a[3]), pack_bf16(a[4], a[5]), pack_bf16(a[6], a[7]));
        }
        asm volatile("fence.proxy.async.shared::cta;" ::: "memory");
        __syncwarp();
        if (lane == 0) {
            tma2d_store(mout, stg, col0 + hf * 128, row0 + wgi * 64 + wi * 16);
            tma2d_store(mout, stg + 2048, col0 + hf * 128 + 64, row0 + wgi * 64 + wi * 16);
            asm volatile("cp.async.bulk.commit_group;" ::: "memory");
        }
    }
}

constexpr int S4_KD = 32768;
constexpr int S4_CH = 2 * G_STAGE;
constexpr int S4_HALF = 2304;
constexpr int S4_WD = 2 * S4_HALF;
constexpr int S4_STRIDE = S4_WD + 2304 + 16;
__device__ __forceinline__ uint32_t addz(uint32_t x, uint32_t z) { uint32_t r; asm volatile("add.u32 %0, %1, %2;" : "=r"(r) : "r"(x), "r"(z)); return r; }
__device__ __forceinline__ uint32_t lds16(uint32_t a) { uint32_t v; asm volatile("ld.shared.u16 %0, [%1];" : "=r"(v) : "r"(a) : "memory"); return v; }
__device__ __forceinline__ uint32_t ldsu(uint32_t a) { return __float_as_uint(lds32(a)); }

template <int E0, int NE, int KP>
__device__ __forceinline__ void s4_windows(float (&acc)[8][2][4], uint32_t ut, uint32_t kd, int rho, int w, int lane, uint32_t z) {
    const int gt = (lane >> 2) - 2 * (lane & 3), p0 = rho == 16 ? -3 : -2, c = (lane >> 3) + p0;
    uint32_t band[2][4], tw[2 * NE + 1], ta[NE][4];
    {
        uint32_t f[5];
#pragma unroll
        for (int m = 0; m < 5; m++) {
            const int d = 8 * (p0 + m - 1) - gt + rho;
            f[m] = (abs(d) <= w ? 0x3F80u : 0u) | (abs(d + 1) <= w ? 0x3F800000u : 0u);
        }
#pragma unroll
        for (int j = 0; j < 2; j++) { band[j][0] = f[2 * j + 1]; band[j][1] = addz(f[2 * j], z); band[j][2] = f[2 * j + 2]; band[j][3] = addz(f[2 * j + 1], z); }
    }
#pragma unroll
    for (int m = 0; m < 2 * NE + 1; m++) {
        const int q = 8 * (2 * E0 - 1 + m) + gt;
        const uint32_t lo = lds16(kd + q * KP), hi = lds16(kd + (q - 1) * KP);
        tw[m] = ((unsigned)(q - 16 * E0) < 16 * E0 ? lo : 0u) | ((unsigned)(q - 1 - 16 * E0) < 16 * E0 ? hi << 16 : 0u);
    }
#pragma unroll
    for (int e = 0; e < NE; e++) { ta[e][0] = tw[2 * e + 1]; ta[e][1] = tw[2 * e + 2]; ta[e][2] = addz(tw[2 * e], z); ta[e][3] = addz(tw[2 * e + 1], z); }
    const uint32_t ua = ut + (c & 1) * S4_HALF + (16 + (lane & 7) + (c >> 1)) * 16;
#pragma unroll
    for (int J = 0; J < 8 - E0; J++) {
        uint32_t u0[4], u1[4];
        ldsm4(u0, ua + J * 256); ldsm4(u1, ua + J * 256 + 128);
        float s0[4], s1[4];
        mma16z(s0, band[0], u0[0], u0[1]); mma16z(s1, band[0], u1[0], u1[1]);
        mma16(s0, band[1], u0[2], u0[3]); mma16(s1, band[1], u1[2], u1[3]);
        const uint32_t b00 = pack_bf16(s0[0], s0[1]), b01 = pack_bf16(s1[0], s1[1]), b10 = pack_bf16(s0[2], s0[3]), b11 = pack_bf16(s1[2], s1[3]);
#pragma unroll
        for (int e = 0; e < NE; e++)
            if (J + E0 + e < 8) { mma16(acc[J + E0 + e][0], ta[e], b00, b01); mma16(acc[J + E0 + e][1], ta[e], b10, b11); }
    }
}
template <int D0, int D1>
__device__ __forceinline__ void s4_dense(float (&acc)[8][2][4], uint32_t ua, const uint32_t (&b0)[4], const uint32_t (&b1)[4]) {
#pragma unroll
    for (int J = 0; J < 8 - D0; J++) {
        uint32_t a[4];
        ldsm4(a, ua + J * 256);
        mma16(acc[J + D0][0], a, b0[0], b0[1]); mma16(acc[J + D0][1], a, b0[2], b0[3]);
        if (J + D1 < 8) { mma16(acc[J + D1][0], a, b1[0], b1[1]); mma16(acc[J + D1][1], a, b1[2], b1[3]); }
    }
}
__device__ __forceinline__ void s4_words(uint32_t (&b)[4], uint32_t wd) {
    asm volatile("ld.shared.u32 %0, [%4]; ld.shared.u32 %1, [%4+-32]; ld.shared.u32 %2, [%4+32]; ld.volatile.shared.u32 %3, [%4];"
        : "=r"(b[0]), "=r"(b[1]), "=r"(b[2]), "=r"(b[3]) : "r"(wd) : "memory");
}

__device__ __forceinline__ void s4_item(uint32_t sb, int cw, int lane, int item, const bf16* __restrict__ dsk, uint32_t empty, const CUtensorMap* my) {
    const int gt = (lane >> 2) - 2 * (lane & 3);
    const uint32_t ch = sb + S4_CH + cw * S4_STRIDE, kd = sb + S4_KD + cw * 1536;
    const __nv_bfloat162 dk = __bfloat162bfloat162(dsk[item * 8 + cw]);
    ST(item, cw, 0);
    asm volatile("st.shared.v4.u32 [%0], {%1,%1,%1,%1};" ::"r"(ch + (lane >> 4) * S4_HALF + (lane & 15) * 16), "r"(0) : "memory");
    const uint32_t tch = sb + S4_CH + (lane & 7) * S4_STRIDE + ((lane >> 3) & 1) * S4_HALF + (16 + 16 * cw + (lane >> 4)) * 16;
#pragma unroll
    for (int i = 0; i < 8; i++) {
        uint32_t x[4];
        ldsm4t(x, sb + cw * 4096 + i * 512 + lane * 16);
        stsm4(tch + i * 32, x[0], x[1], x[2], x[3]);
    }
#pragma unroll 1
    for (int x0 = lane * 2 - 16; x0 < 560; x0 += 64) {
        uint32_t k[3];
#pragma unroll
        for (int j = 0; j < 3; j++) {
            const int x = x0 + j - 1, idx = x < 256 ? max(x, 0) : min(128 + ((x + ((x >> 1) & 1)) >> 1), 384);
            k[j] = lds16(kd + idx * 2);
            if ((unsigned)x > 514u) k[j] = 0;
        }
        asm volatile("st.shared.v2.u32 [%0], {%1,%2};" ::"r"(ch + S4_WD + 64 + x0 * 4), "r"(k[1] | (k[0] << 16)), "r"(k[2] | (k[1] << 16)) : "memory");
    }
    const uint32_t k1024 = lds16(kd + 1024);
    bar_sync(2, 256);
    ST(item, cw, 1);
    const uint32_t z = ldsu(ch);
    float acc[8][2][4];
#pragma unroll
    for (int j = 0; j < 16; j++) acc[j >> 1][j & 1][0] = acc[j >> 1][j & 1][1] = acc[j >> 1][j & 1][2] = acc[j >> 1][j & 1][3] = 0.f;
#pragma unroll 1
    for (int r = 1; r <= 4; r++) s4_windows<2, 3, 8>(acc, ch, kd + 512 + 2 * r, 4 * r, 2 - (r & 1), lane, z);
    ST(item, cw, 2);
#pragma unroll 1
    for (int r = 1; r <= 2; r++) s4_windows<4, 4, 4>(acc, ch, kd + 768 + 2 * r, 8 * r, 2 + r, lane, z);
    ST(item, cw, 3);
    const uint32_t ua = ch + (lane >> 4) * S4_HALF + (16 + (lane & 15)) * 16, wd = ch + S4_WD + 64 + gt * 4;
#pragma unroll 1
    for (int q = 0; q < 2; q++) {
        uint32_t b0[4], b1[4];
        s4_words(b0, wd + (q + 32) * 64);
#pragma unroll
        for (int j = 0; j < 4; j++) {
            const int x = 16 * q + gt + (j == 1 ? -8 : j == 2 ? 8 : 0) - 3;
            b1[j] = addz(((unsigned)x < 2u ? k1024 : 0u) | ((unsigned)(x - 1) < 2u ? k1024 << 16 : 0u), z);
        }
        s4_dense<2, 4>(acc, ua - q * 16, b0, b1);
    }
    {
        uint32_t b0[4], b1[4], c0[4], c1[4];
        s4_words(b0, wd); s4_words(b1, wd + 1024);
#pragma unroll 1
        for (int q = 0; q < 16; q += 2) {
            s4_words(c0, wd + q * 64 + 64); s4_words(c1, wd + q * 64 + 64 + 1024);
            s4_dense<0, 1>(acc, ua - q * 16, b0, b1);
            s4_words(b0, wd + q * 64 + 128); s4_words(b1, wd + q * 64 + 128 + 1024);
            s4_dense<0, 1>(acc, ua - q * 16 - 16, c0, c1);
            if (q == 8 && lane == 0) { mbar_arrive(empty); mbar_arrive(empty + 8); }
        }
    }
    ST(item, cw, 4);
    if (lane == 0) asm volatile("cp.async.bulk.wait_group.read 0;" ::: "memory");
    __syncwarp();
#pragma unroll
    for (int I = 0; I < 8; I++) {
        uint32_t u[4];
        ldsm4(u, ua + I * 256);
#pragma unroll
        for (int j = 0; j < 4; j++) {
            const uint32_t y = pack_bf16(acc[I][j >> 1][2 * (j & 1)], acc[I][j >> 1][2 * (j & 1) + 1]);
            const __nv_bfloat162 r = __hadd2_rn(*(const __nv_bfloat162*)&y, __hmul2_rn(*(const __nv_bfloat162*)&u[j], dk));
            u[j] = *(const uint32_t*)&r;
        }
        stsm4(ua + I * 256, u[0], u[1], u[2], u[3]);
    }
    bar_sync(2, 256);
#pragma unroll
    for (int i = 0; i < 8; i++) {
        uint32_t y[4];
        ldsm4t(y, tch + i * 32);
        stsm4(sb + G_STG + cw * 4096 + i * 512 + lane * 16, y[0], y[1], y[2], y[3]);
    }
    asm volatile("fence.proxy.async.shared::cta;" ::: "memory");
    __syncwarp();
    if (lane == 0) {
        mbar_arrive(empty + 16); mbar_arrive(empty + 24);
        tma2d_store(my, sb + G_STG + cw * 4096, DM + item * 8, cw * 256);
        asm volatile("cp.async.bulk.commit_group;" ::: "memory");
    }
    ST(item, cw, 5);
}

__global__ void __launch_bounds__(384, 1)
worker_kernel(const __grid_constant__ CUtensorMap mx, const __grid_constant__ CUtensorMap mq, const __grid_constant__ CUtensorMap mk,
              const __grid_constant__ CUtensorMap mv, const __grid_constant__ CUtensorMap mo,
              const __grid_constant__ CUtensorMap mout, const __grid_constant__ CUtensorMap mu, const __grid_constant__ CUtensorMap my,
              const bf16* __restrict__ dsk) {
    extern __shared__ unsigned char smem_raw[];
    const uint32_t sb = (smem_u32(smem_raw) + 1023) & ~1023u;
    const uint32_t full = sb + G_BAR, empty = full + 32, ifull = full + 64, iempty = full + 80, islot = full + 96, sigbar = full + 112, sigslot = full + 120;
    const int tid = threadIdx.x, wg = tid >> 7, lane = tid & 31;
    if (tid == 0) {
        for (int i = 0; i < G_NST; i++) { mbar_init(full + 8 * i, 1); mbar_init(empty + 8 * i, 8); }
        for (int i = 0; i < 2; i++) { mbar_init(ifull + 8 * i, 1); mbar_init(iempty + 8 * i, 8); }
        mbar_init(sigbar, 8);
        asm volatile("fence.proxy.async;" ::: "memory");
    }
    __syncthreads();
    if (wg == 0) {
        reg_dec<40>();
        if (tid >= 32 && tid < 64) {
            for (int n = 0;; n++) {
                mbar_wait_long(sigbar, n & 1);
                int item; asm volatile("ld.shared.u32 %0, [%1];" : "=r"(item) : "r"(sigslot + 4 * (n & 1)) : "memory");
                const int type = item >> 16, b = (item >> 8) & 255, i = item & 255;
                if (type == IT_END) break;
                __threadfence();
                if (type == IT_KV) { if (lane < 6) atomicAdd(g_kvf + ((i & 15) * 6 + lane) * 16 + b, 1); }
                else if (lane == 0) atomicAdd(g_ctr + C_QA_DONE + b, 1);
            }
        } else if (tid < 32) {
            int it = 0;
            if (!KVN) asm volatile("griddepcontrol.wait;" ::: "memory");
            for (int n = 0;; n++) {
                int item = 0;
                if (lane == 0) {
                    const int q = (n == 0 && blockIdx.x < 32) ? blockIdx.x : 32 + atomicAdd(g_ctr + C_NEXT, 1);
                    item = queue_item(q);
                }
                item = __shfl_sync(0xffffffffu, item, 0);
                if (lane == 0) {
                    mbar_wait(iempty + 8 * (n & 1), ((n >> 1) & 1) ^ 1);
                    asm volatile("st.shared.u32 [%0], %1;" ::"r"(islot + 4 * (n & 1)), "r"(item) : "memory");
                    mbar_arrive(ifull + 8 * (n & 1));
                    const int type = item >> 16, b = (item >> 8) & 255, i = item & 255;
                    if (type == IT_QA || type == IT_KV) {
                        const CUtensorMap* mw = type == IT_QA ? &mq : i < 16 ? &mk : &mv;
                        bool ready = false;
                        for (int kb = 0; kb < 16; kb++, it++) {
                            const int st = it & 3;
                            mbar_wait(empty + 8 * st, ((it >> 2) & 1) ^ 1);
                            mbar_expect(full + 8 * st, G_STAGE);
                            const uint32_t a = sb + st * G_STAGE;
                            tma2d(a, &mx, kb * 64, b * 128, full + 8 * st);
                            tma3d(a + 16384, mw, 0, kb * 64, (i & 15) * 4, full + 8 * st);
                            tma3d(a + 32768, mw, 0, kb * 64, (i & 15) * 4 + 2, full + 8 * st);
                            if (type == IT_QA && kb == 3) ready = ld_acq(g_ctr + C_CHAIN + b) >= 96;
                            if (type == IT_QA && kb >= 3 && kb < 11) {
                                const size_t sh = (b * 4 + ((kb - 3) & 3)) * NH + i * 2;
                                asm volatile("cp.async.bulk.prefetch.L2.global [%0], 16384;" ::"l"((kb >= 7 ? g_vx : g_kx) + sh * 4096) : "memory");
                                if (ready) asm volatile("cp.async.bulk.prefetch.L2.global [%0], 4096;" ::"l"((kb >= 7 ? g_vm : g_km) + sh * 1024) : "memory");
                            }
                        }
                    }
                    if (type == IT_QA) {
                        wait_ctr(g_ctr + C_CHAIN + b, 96);
                        asm volatile("fence.proxy.async;" ::: "memory");
                        for (int st = 0; st < 4; st++, it++) {
                            mbar_wait(empty + 8 * st, ((it >> 2) & 1) ^ 1);
                            mbar_expect(full + 8 * st, 4 * 10240);
                            for (int sg = 0; sg < 4; sg++) {
                                const int sh = (b * 4 + sg) * NH + i * 2 + (st >> 1);
                                bulk_load(sb + st * G_STAGE + sg * 10240, ((st & 1) ? g_vx : g_kx) + (size_t)sh * 4096, 8192, full + 8 * st);
                                bulk_load(sb + st * G_STAGE + sg * 10240 + 8192, ((st & 1) ? g_vm : g_km) + (size_t)sh * 1024, 2048, full + 8 * st);
                            }
                        }
                    } else if (type == IT_O) {
                        const bool wide = b < O_WIDE;
                        wait_ctr(g_ctr + C_QA_DONE + b, 16);
                        asm volatile("fence.proxy.async;" ::: "memory");
                        for (int kb = 0; kb < 64; kb++, it++) {
                            const int st = it & 3;
                            mbar_wait(empty + 8 * st, ((it >> 2) & 1) ^ 1);
                            mbar_expect(full + 8 * st, wide ? G_STAGE : 32768);
                            const uint32_t a = sb + st * G_STAGE;
                            bulk_load(a, g_ox + (size_t)(b * 64 + kb) * 8192, 16384, full + 8 * st);
                            tma3d(a + 16384, &mo, 0, kb * 64, wide ? i * 4 : i * 2, full + 8 * st);
                            if (wide) tma3d(a + 32768, &mo, 0, kb * 64, i * 4 + 2, full + 8 * st);
                        }
                    } else if (type == IT_S4) {
                        wait_ctr(g_ctr + C_CHAIN, 96);
                        asm volatile("fence.proxy.async;" ::: "memory");
                        mbar_wait(empty, ((it >> 2) & 1) ^ 1);
                        mbar_expect(full, 32768 + 12288);
                        bulk_load(sb + S4_KD, g_kd + i * 8 * 768, 12288, full);
                        for (int j = 0; j < 8; j++) tma2d(sb + j * 4096, &mu, i * 8, j * 256, full);
                        for (int st = 1; st < 4; st++) { mbar_wait(empty + 8 * st, ((it >> 2) & 1) ^ 1); mbar_arrive(full + 8 * st); }
                        it += 4;
                        mbar_wait_long(empty, ((it >> 2) & 1) ^ 1);
                    }
                }
                __syncwarp();
                if (item >> 16 == IT_END) break;
            }
            asm volatile("griddepcontrol.wait;" ::: "memory");
        }
    } else {
        reg_inc<232>();
        const int wu = __shfl_sync(0xffffffffu, tid >> 5, 0);
        const int wgi = (wu >> 2) - 1, wi = wu & 3;
        int it = 0, nsig = 0, n = 0, item;
        auto next_item = [&]() {
            mbar_wait_long(ifull + 8 * (n & 1), (n >> 1) & 1);
            asm volatile("ld.shared.u32 %0, [%1];" : "=r"(item) : "r"(islot + 4 * (n & 1)) : "memory");
            __syncwarp();
            if (lane == 0) mbar_arrive(iempty + 8 * (n & 1));
        };
        auto signal = [&](int what) {
            if (tid == 128) asm volatile("st.shared.u32 [%0], %1;" ::"r"(sigslot + 4 * (nsig & 1)), "r"(what) : "memory");
            __syncwarp();
            if (lane == 0) mbar_arrive(sigbar);
            nsig++;
        };
        next_item();
        if (item >> 16 == IT_KV) {
            float acc[128];
            uint32_t pk[64];
            uint32_t* dst = nullptr;
            int prev = 0;
            do {
                WLOG(0);
#pragma unroll
                for (int kb = 0; kb < 16; kb++, it++) {
                    const int st = kb & 3;
                    mbar_wait(full + 8 * st, (it >> 2) & 1);
                    const uint64_t da = mkdesc(sb + st * G_STAGE + wgi * 8192, 16, 1024, 1);
                    const uint64_t db = mkdesc(sb + st * G_STAGE + 16384, 8192, 1024, 1);
                    wg_fence();
#pragma unroll
                    for (int k = 0; k < 4; k++) wgmma256(acc, da + k * 2, db + k * 128, kb | k);
                    wg_commit();
                    if (kb < KVS && dst) {
#pragma unroll
                        for (int j = kb * (64 / KVS); j < (kb + 1) * (64 / KVS); j++) st_out(dst + (j >> 1) * 128 + (j & 1) * 32, pk[j]);
                        if (kb == KVS - 1) signal(prev);
                    }
                    if (kb > 0) {
                        wg_wait<1>();
                        if (lane == 0) mbar_arrive(empty + 8 * ((kb - 1) & 3));
                    }
                }
                wg_wait<0>();
                if (lane == 0) mbar_arrive(empty + 8 * 3);
#pragma unroll
                for (int j = 0; j < 64; j++) pk[j] = pack_bf16(acc[2 * j], acc[2 * j + 1]);
                const int row = ((item >> 8) & 255) * 128 + wgi * 64 + wi * 16, nt = item & 255;
                dst = (uint32_t*)(nt < 16 ? g_kx : g_vx) + (size_t)((row >> 5) * 512 + (nt & 15) * 32) * 128 + (row & 31) * 4 + lane;
                prev = item;
                if (n == 0) {
#pragma unroll
                    for (int j = 0; j < 64; j++) dst[(j >> 1) * 128 + (j & 1) * 32] = pk[j];
                    signal(prev);
                    dst = nullptr;
                }
                WLOG(1);
                n++;
                next_item();
            } while (item >> 16 == IT_KV);
            if (dst) {
#pragma unroll
                for (int j = 0; j < 64; j++) dst[(j >> 1) * 128 + (j & 1) * 32] = pk[j];
                signal(prev);
            }
        }
        for (;; n++, next_item()) {
            const int type = item >> 16, b = (item >> 8) & 255, i = item & 255;
            WLOG(0);
            if (type == IT_QA) {
                float acc[128];
                ST(sid, cw, 0);
                ST(sid, cw, 1);
                mainloop<256, 16, false>(acc, sb, wgi, full, empty, it, lane == 0);
                ST(sid, cw, 2);
                uint32_t q0[32], q1[32];
#pragma unroll
                for (int j = 0; j < 32; j++) { q0[j] = pack_bf16(acc[2 * j], acc[2 * j + 1]); q1[j] = pack_bf16(acc[64 + 2 * j], acc[65 + 2 * j]); }
                const uint32_t par = (it >> 2) & 1, so = (wgi * 2 + (wi >> 1)) * 10240;
                uint32_t* dst = (uint32_t*)g_ox + (size_t)(b * 64 + i * 4) * 4096 + (wgi * 8 + wi * 2) * 256 + lane;
                mbar_wait_long(full, par);
                ST(sid, cw, 3);
                attn_head(q0, sb + so, sb + G_STAGE + so, full + 8, par, empty, wi, lane, dst);
                __syncwarp();
                if (lane == 0) mbar_arrive(empty + 8);
                ST(sid, cw, 4);
                mbar_wait(full + 16, par);
                ST(sid, cw, 5);
                attn_head(q1, sb + 2 * G_STAGE + so, sb + 3 * G_STAGE + so, full + 24, par, empty + 16, wi, lane, dst + 2 * 4096);
                __syncwarp();
                if (lane == 0) mbar_arrive(empty + 24);
                ST(sid, cw, 6);
                signal(item);
                it += 4;
            } else if (type == IT_O) {
                mbar_wait_long(full, (it >> 2) & 1);
                if (b < O_WIDE) o_item<256>(sb, wgi, wi, lane, full, empty, it, &mout, b * 128, i * 256);
                else o_item<128>(sb, wgi, wi, lane, full, empty, it, &mout, b * 128, i * 128);
            } else if (type == IT_S4) {
                mbar_wait_long(full, (it >> 2) & 1);
                mbar_wait(full + 24, (it >> 2) & 1);
                s4_item(sb, wgi * 4 + wi, lane, i, dsk, empty, &my);
                it += 4;
            } else break;
            WLOG(1);
        }
        bar_sync(2, 256);
        signal(item);
        if (lane == 0) asm volatile("cp.async.bulk.wait_group 0;" ::: "memory");
    }
}

typedef CUresult (*EncodeFn)(CUtensorMap*, CUtensorMapDataType, cuuint32_t, void*, const cuuint64_t*, const cuuint64_t*, const cuuint32_t*,
                             const cuuint32_t*, CUtensorMapInterleave, CUtensorMapSwizzle, CUtensorMapL2promotion, CUtensorMapFloatOOBfill);
static EncodeFn get_encode() {
    void* fn = nullptr; cudaDriverEntryPointQueryResult st;
    cudaGetDriverEntryPoint("cuTensorMapEncodeTiled", &fn, cudaEnableDefault, &st);
    return (EncodeFn)fn;
}
static void map_act(EncodeFn enc, CUtensorMap* m, const void* p, int rows, int cols, int boxr) {
    cuuint64_t dim[2] = {(cuuint64_t)cols, (cuuint64_t)rows}, str[1] = {(cuuint64_t)cols * 2};
    cuuint32_t box[2] = {64, (cuuint32_t)boxr}, es[2] = {1, 1};
    enc(m, CU_TENSOR_MAP_DATA_TYPE_BFLOAT16, 2, (void*)p, dim, str, box, es, CU_TENSOR_MAP_INTERLEAVE_NONE, CU_TENSOR_MAP_SWIZZLE_128B,
        CU_TENSOR_MAP_L2_PROMOTION_L2_128B, CU_TENSOR_MAP_FLOAT_OOB_FILL_NONE);
}
static void map_w(EncodeFn enc, CUtensorMap* m, const void* p, int k, int n) {
    cuuint64_t dim[3] = {64, (cuuint64_t)k, (cuuint64_t)n / 64}, str[2] = {(cuuint64_t)n * 2, 128};
    cuuint32_t box[3] = {64, 64, 2}, es[3] = {1, 1, 1};
    enc(m, CU_TENSOR_MAP_DATA_TYPE_BFLOAT16, 3, (void*)p, dim, str, box, es, CU_TENSOR_MAP_INTERLEAVE_NONE, CU_TENSOR_MAP_SWIZZLE_128B,
        CU_TENSOR_MAP_L2_PROMOTION_L2_256B, CU_TENSOR_MAP_FLOAT_OOB_FILL_NONE);
}

static void map_box(EncodeFn enc, CUtensorMap* m, const void* p, int rows, int ld, int boxc, int boxr, CUtensorMapSwizzle sw) {
    cuuint64_t dim[2] = {(cuuint64_t)ld, (cuuint64_t)rows}, str[1] = {(cuuint64_t)ld * 2};
    cuuint32_t box[2] = {(cuuint32_t)boxc, (cuuint32_t)boxr}, es[2] = {1, 1};
    enc(m, CU_TENSOR_MAP_DATA_TYPE_BFLOAT16, 2, (void*)p, dim, str, box, es, CU_TENSOR_MAP_INTERLEAVE_NONE, sw,
        CU_TENSOR_MAP_L2_PROMOTION_NONE, CU_TENSOR_MAP_FLOAT_OOB_FILL_NONE);
}

extern "C" void kernel_launch(void* const* d_in, const int* in_sizes, int n_in, void* d_out, int out_size) {
    const bf16* x = (const bf16*)d_in[0];
    const bf16* mem0 = (const bf16*)d_in[1];
    const bf16 *Wq = (const bf16*)d_in[2], *Wk = (const bf16*)d_in[3], *Wv = (const bf16*)d_in[4], *Wo = (const bf16*)d_in[5];
    static EncodeFn enc = nullptr;
    static int nsm = 0;
    if (!enc) {
        enc = get_encode();
        cudaDeviceGetAttribute(&nsm, cudaDevAttrMultiProcessorCount, 0);
        cudaFuncSetAttribute(chain_kernel, cudaFuncAttributeMaxDynamicSharedMemorySize, CH_SMEM);
        cudaFuncSetAttribute(worker_kernel, cudaFuncAttributeMaxDynamicSharedMemorySize, G_SMEM);
    }
    CUtensorMap mx, mq, mk, mv, mo, mout, mu, my;
    map_act(enc, &mx, x, S_LEN, DM, 128);
    map_w(enc, &mq, Wq, DM, HD); map_w(enc, &mk, Wk, DM, HD); map_w(enc, &mv, Wv, DM, HD); map_w(enc, &mo, Wo, HD, DM);
    map_box(enc, &mout, d_out, S_LEN, 2 * DM, 64, 16, CU_TENSOR_MAP_SWIZZLE_128B);
    map_box(enc, &mu, d_in[7], S_LEN, DM, 8, 256, CU_TENSOR_MAP_SWIZZLE_NONE);
    map_box(enc, &my, d_out, S_LEN, 2 * DM, 8, 256, CU_TENSOR_MAP_SWIZZLE_NONE);
    CUtensorMap cq, ck, cv, co;
    map_box(enc, &cq, Wq, DM, HD, 32, 32, CU_TENSOR_MAP_SWIZZLE_64B); map_box(enc, &ck, Wk, DM, HD, 32, 32, CU_TENSOR_MAP_SWIZZLE_64B);
    map_box(enc, &cv, Wv, DM, HD, 32, 32, CU_TENSOR_MAP_SWIZZLE_64B); map_box(enc, &co, Wo, HD, DM, 32, 16, CU_TENSOR_MAP_SWIZZLE_64B);
    S4Params P = {(const bf16*)d_in[8], (const bf16*)d_in[9], (const bf16*)d_in[10], (const bf16*)d_in[11],
                  (const bf16*)d_in[12], (const bf16*)d_in[13], (const bf16*)d_in[14], (const bf16*)d_in[15]};
    int aware = 1;
    cudaLaunchAttribute at[1];
    at[0].id = cudaLaunchAttributeProgrammaticStreamSerialization;
    at[0].val.programmaticStreamSerializationAllowed = 1;
    cudaLaunchConfig_t cfg = {};
    cfg.stream = cudaStreamPerThread;
    cfg.gridDim = dim3(96); cfg.blockDim = dim3(CH_THREADS); cfg.dynamicSmemBytes = CH_SMEM;
    cudaLaunchKernelEx(&cfg, chain_kernel, cq, ck, cv, co, Wq, Wk, Wv, mem0, P, aware);
    cfg.attrs = at; cfg.numAttrs = 1;
    cfg.gridDim = dim3(nsm); cfg.blockDim = dim3(384); cfg.dynamicSmemBytes = G_SMEM;
    cudaLaunchKernelEx(&cfg, worker_kernel, mx, mq, mk, mv, mo, mout, mu, my, P.dsk);
}
```

```cpp
#include <cuda.h>
#include <cuda_runtime.h>
#include <cuda_bf16.h>
#include <stdint.h>
#include <stdio.h>
#include <string.h>

typedef __nv_bfloat16 bf16;

constexpr int S_LEN = 2048, DM = 1024, NH = 32, DH = 128, HD = 4096, NSEG = 64;
constexpr uint32_t SENT = 0xFFFFFFFFu;
constexpr int SPIN_LIMIT = 1 << 18;
#define REALL 0

__device__ __align__(1024) bf16 g_kx[S_LEN * HD];
__device__ __align__(1024) bf16 g_vx[S_LEN * HD];
__device__ __align__(1024) bf16 g_ox[S_LEN * HD];
__device__ __align__(1024) bf16 g_km[NSEG * NH * 8 * DH];
__device__ __align__(1024) bf16 g_vm[NSEG * NH * 8 * DH];
__device__ __align__(1024) bf16 g_kd[DM * 768 + 8192];
__device__ __align__(1024) char g_ring[2 << 20];
__device__ int g_kvf[96 * 16];
constexpr int C_NEXT = 0, C_CHAIN = 32, C_QA_DONE = 64, N_CTR = 96;
__device__ int g_ctr[N_CTR];

__device__ __forceinline__ uint32_t smem_u32(const void* p) { return (uint32_t)__cvta_generic_to_shared(p); }
__device__ __forceinline__ uint32_t clk() { uint32_t c; asm volatile("mov.u32 %0, %%clock;" : "=r"(c)::"memory"); return c; }
__device__ __forceinline__ uint32_t pack_bf16(float lo, float hi) {
    uint32_t r; asm("cvt.rn.bf16x2.f32 %0, %1, %2;" : "=r"(r) : "f"(hi), "f"(lo)); return r;
}
__device__ __forceinline__ uint32_t movm(uint32_t a) {
    uint32_t d; asm volatile("movmatrix.sync.aligned.m8n8.trans.b16 %0, %1;" : "=r"(d) : "r"(a)); return d;
}
__device__ __forceinline__ void mma16(float (&d)[4], const uint32_t (&a)[4], uint32_t b0, uint32_t b1) {
    asm volatile("mma.sync.aligned.m16n8k16.row.col.f32.bf16.bf16.f32 {%0,%1,%2,%3}, {%4,%5,%6,%7}, {%8,%9}, {%0,%1,%2,%3};"
        : "+f"(d[0]), "+f"(d[1]), "+f"(d[2]), "+f"(d[3]) : "r"(a[0]), "r"(a[1]), "r"(a[2]), "r"(a[3]), "r"(b0), "r"(b1));
}
__device__ __forceinline__ void mma16z(float (&d)[4], const uint32_t (&a)[4], uint32_t b0, uint32_t b1) {
    asm volatile("mma.sync.aligned.m16n8k16.row.col.f32.bf16.bf16.f32 {%0,%1,%2,%3}, {%4,%5,%6,%7}, {%8,%9}, {%10,%10,%10,%10};"
        : "=f"(d[0]), "=f"(d[1]), "=f"(d[2]), "=f"(d[3]) : "r"(a[0]), "r"(a[1]), "r"(a[2]), "r"(a[3]), "r"(b0), "r"(b1), "f"(0.f));
}
__device__ __forceinline__ void mma8z(float (&d)[4], uint32_t a0, uint32_t a1, uint32_t b0) {
    asm volatile("mma.sync.aligned.m16n8k8.row.col.f32.bf16.bf16.f32 {%0,%1,%2,%3}, {%4,%5}, {%6}, {%7,%7,%7,%7};"
        : "=f"(d[0]), "=f"(d[1]), "=f"(d[2]), "=f"(d[3]) : "r"(a0), "r"(a1), "r"(b0), "f"(0.f));
}
__device__ __forceinline__ void ldsm4t(uint32_t (&r)[4], uint32_t addr) {
    asm volatile("ldmatrix.sync.aligned.m8n8.x4.trans.shared.b16 {%0,%1,%2,%3}, [%4];"
        : "=r"(r[0]), "=r"(r[1]), "=r"(r[2]), "=r"(r[3]) : "r"(addr) : "memory");
}
__device__ __forceinline__ void ldsm4(uint32_t (&r)[4], uint32_t addr) {
    asm volatile("ldmatrix.sync.aligned.m8n8.x4.shared.b16 {%0,%1,%2,%3}, [%4];"
        : "=r"(r[0]), "=r"(r[1]), "=r"(r[2]), "=r"(r[3]) : "r"(addr) : "memory");
}
__device__ __forceinline__ float lds32(uint32_t a) {
    float v; asm volatile("ld.shared.f32 %0, [%1];" : "=f"(v) : "r"(a) : "memory"); return v;
}
__device__ __forceinline__ void st_async1(uint32_t dst, float v, uint32_t bar) {
    asm volatile("st.async.shared::cluster.mbarrier::complete_tx::bytes.f32 [%0], %1, [%2];" ::"r"(dst), "f"(v), "r"(bar) : "memory");
}
__device__ __forceinline__ void st_async2(uint32_t dst, float x, float y, uint32_t bar) {
    asm volatile("st.async.shared::cluster.mbarrier::complete_tx::bytes.v2.f32 [%0], {%1,%2}, [%3];" ::"r"(dst), "f"(x), "f"(y), "r"(bar) : "memory");
}
__device__ __forceinline__ void mma8(float (&d)[4], uint32_t a0, uint32_t a1, uint32_t b0) {
    asm volatile("mma.sync.aligned.m16n8k8.row.col.f32.bf16.bf16.f32 {%0,%1,%2,%3}, {%4,%5}, {%6}, {%0,%1,%2,%3};"
        : "+f"(d[0]), "+f"(d[1]), "+f"(d[2]), "+f"(d[3]) : "r"(a0), "r"(a1), "r"(b0));
}
__device__ __forceinline__ void cp16(uint32_t dst, const void* src) {
    asm volatile("cp.async.cg.shared.global [%0], [%1], 16;" ::"r"(dst), "l"(src) : "memory");
}
__device__ __forceinline__ void sts128(uint32_t a, const float (&v)[4]) {
    asm volatile("st.shared.v4.f32 [%0], {%1,%2,%3,%4};" ::"r"(a), "f"(v[0]), "f"(v[1]), "f"(v[2]), "f"(v[3]) : "memory");
}
__device__ __forceinline__ float4 lds128(uint32_t a) {
    float4 v; asm volatile("ld.shared.v4.f32 {%0,%1,%2,%3}, [%4];" : "=f"(v.x), "=f"(v.y), "=f"(v.z), "=f"(v.w) : "r"(a) : "memory"); return v;
}
__device__ __forceinline__ void sts64(uint32_t a, float x, float y) {
    asm volatile("st.shared.v2.f32 [%0], {%1,%2};" ::"r"(a), "f"(x), "f"(y) : "memory");
}
__device__ __forceinline__ float2 lds64(uint32_t a) {
    float2 v; asm volatile("ld.shared.v2.f32 {%0,%1}, [%2];" : "=f"(v.x), "=f"(v.y) : "r"(a) : "memory"); return v;
}
__device__ __forceinline__ void bar_sync(int id, int n) { asm volatile("bar.sync %0, %1;" ::"r"(id), "r"(n) : "memory"); }
__device__ __forceinline__ void bar_arrive(int id, int n) { asm volatile("bar.arrive %0, %1;" ::"r"(id), "r"(n) : "memory"); }
__device__ __forceinline__ uint32_t mapa(uint32_t a, uint32_t r) {
    uint32_t o; asm("mapa.shared::cluster.u32 %0, %1, %2;" : "=r"(o) : "r"(a), "r"(r)); return o;
}
__device__ __forceinline__ void st_async4(uint32_t dst, float4 v, uint32_t bar) {
    asm volatile("st.async.shared::cluster.mbarrier::complete_tx::bytes.v4.f32 [%0], {%1,%2,%3,%4}, [%5];"
        ::"r"(dst), "f"(v.x), "f"(v.y), "f"(v.z), "f"(v.w), "r"(bar) : "memory");
}
__device__ __forceinline__ void mbar_init(uint32_t bar, int n) { asm volatile("mbarrier.init.shared.b64 [%0], %1;" ::"r"(bar), "r"(n) : "memory"); }
__device__ __forceinline__ void mbar_expect(uint32_t bar, int bytes) {
    asm volatile("mbarrier.arrive.expect_tx.shared.b64 _, [%0], %1;" ::"r"(bar), "r"(bytes) : "memory");
}
__device__ __forceinline__ void bulk_load(uint32_t dst, const void* src, int bytes, uint32_t bar) {
    asm volatile("cp.async.bulk.shared::cluster.global.mbarrier::complete_tx::bytes [%0], [%1], %2, [%3];"
        ::"r"(dst), "l"(src), "r"(bytes), "r"(bar) : "memory");
}
__device__ __forceinline__ bool mbar_try(uint32_t bar, uint32_t par) {
    uint32_t ok;
    asm volatile("{.reg .pred p; mbarrier.try_wait.parity.shared::cta.b64 p, [%1], %2; selp.u32 %0, 1, 0, p;}"
        : "=r"(ok) : "r"(bar), "r"(par) : "memory");
    return ok;
}
__device__ __forceinline__ bool mbar_test(uint32_t bar, uint32_t par) {
    uint32_t ok;
    asm volatile("{.reg .pred p; mbarrier.test_wait.parity.shared::cta.b64 p, [%1], %2; selp.u32 %0, 1, 0, p;}"
        : "=r"(ok) : "r"(bar), "r"(par) : "memory");
    return ok;
}
__device__ __forceinline__ int ld_acq(const int* p) { int v; asm volatile("ld.acquire.gpu.global.s32 %0, [%1];" : "=r"(v) : "l"(p) : "memory"); return v; }
__device__ __forceinline__ void wait_ctr(const int* p, int n) {
    for (int it = 0; it < (1 << 20) && ld_acq(p) < n; it++) __nanosleep(64);
}
__device__ __forceinline__ void mbar_wait(uint32_t bar, uint32_t par) {
    if (!mbar_try(bar, par))
        for (int it = 0; it < SPIN_LIMIT && !mbar_try(bar, par); it++) {}
}
__device__ __forceinline__ void mbar_wait_long(uint32_t bar, uint32_t par) {
    for (int it = 0; it < (1 << 24) && !mbar_try(bar, par); it++) {}
}
__device__ __forceinline__ float4 add4(float4 a, float4 b) { return make_float4(a.x + b.x, a.y + b.y, a.z + b.z, a.w + b.w); }
__device__ __forceinline__ float ex2(float x) { float y; asm("ex2.approx.ftz.f32 %0, %1;" : "=f"(y) : "f"(x)); return y; }

__device__ __forceinline__ void wgmma256(float (&d)[128], uint64_t da, uint64_t db, int acc) {
    asm volatile("{.reg .pred p; setp.ne.b32 p, %130, 0;\n"
        "wgmma.mma_async.sync.aligned.m64n256k16.f32.bf16.bf16 {"
        "%0,%1,%2,%3,%4,%5,%6,%7,%8,%9,%10,%11,%12,%13,%14,%15,"
        "%16,%17,%18,%19,%20,%21,%22,%23,%24,%25,%26,%27,%28,%29,%30,%31,"
        "%32,%33,%34,%35,%36,%37,%38,%39,%40,%41,%42,%43,%44,%45,%46,%47,"
        "%48,%49,%50,%51,%52,%53,%54,%55,%56,%57,%58,%59,%60,%61,%62,%63,"
        "%64,%65,%66,%67,%68,%69,%70,%71,%72,%73,%74,%75,%76,%77,%78,%79,"
        "%80,%81,%82,%83,%84,%85,%86,%87,%88,%89,%90,%91,%92,%93,%94,%95,"
        "%96,%97,%98,%99,%100,%101,%102,%103,%104,%105,%106,%107,%108,%109,%110,%111,"
        "%112,%113,%114,%115,%116,%117,%118,%119,%120,%121,%122,%123,%124,%125,%126,%127"
        "}, %128, %129, p, 1, 1, 0, 1;}"
        : "+f"(d[0]), "+f"(d[1]), "+f"(d[2]), "+f"(d[3]), "+f"(d[4]), "+f"(d[5]), "+f"(d[6]), "+f"(d[7]), "+f"(d[8]), "+f"(d[9]), "+f"(d[10]), "+f"(d[11]), "+f"(d[12]), "+f"(d[13]), "+f"(d[14]), "+f"(d[15]), "+f"(d[16]), "+f"(d[17]), "+f"(d[18]), "+f"(d[19]), "+f"(d[20]), "+f"(d[21]), "+f"(d[22]), "+f"(d[23]), "+f"(d[24]), "+f"(d[25]), "+f"(d[26]), "+f"(d[27]), "+f"(d[28]), "+f"(d[29]), "+f"(d[30]), "+f"(d[31]), "+f"(d[32]), "+f"(d[33]), "+f"(d[34]), "+f"(d[35]), "+f"(d[36]), "+f"(d[37]), "+f"(d[38]), "+f"(d[39]), "+f"(d[40]), "+f"(d[41]), "+f"(d[42]), "+f"(d[43]), "+f"(d[44]), "+f"(d[45]), "+f"(d[46]), "+f"(d[47]), "+f"(d[48]), "+f"(d[49]), "+f"(d[50]), "+f"(d[51]), "+f"(d[52]), "+f"(d[53]), "+f"(d[54]), "+f"(d[55]), "+f"(d[56]), "+f"(d[57]), "+f"(d[58]), "+f"(d[59]), "+f"(d[60]), "+f"(d[61]), "+f"(d[62]), "+f"(d[63]), "+f"(d[64]), "+f"(d[65]), "+f"(d[66]), "+f"(d[67]), "+f"(d[68]), "+f"(d[69]), "+f"(d[70]), "+f"(d[71]), "+f"(d[72]), "+f"(d[73]), "+f"(d[74]), "+f"(d[75]), "+f"(d[76]), "+f"(d[77]), "+f"(d[78]), "+f"(d[79]), "+f"(d[80]), "+f"(d[81]), "+f"(d[82]), "+f"(d[83]), "+f"(d[84]), "+f"(d[85]), "+f"(d[86]), "+f"(d[87]), "+f"(d[88]), "+f"(d[89]), "+f"(d[90]), "+f"(d[91]), "+f"(d[92]), "+f"(d[93]), "+f"(d[94]), "+f"(d[95]), "+f"(d[96]), "+f"(d[97]), "+f"(d[98]), "+f"(d[99]), "+f"(d[100]), "+f"(d[101]), "+f"(d[102]), "+f"(d[103]), "+f"(d[104]), "+f"(d[105]), "+f"(d[106]), "+f"(d[107]), "+f"(d[108]), "+f"(d[109]), "+f"(d[110]), "+f"(d[111]), "+f"(d[112]), "+f"(d[113]), "+f"(d[114]), "+f"(d[115]), "+f"(d[116]), "+f"(d[117]), "+f"(d[118]), "+f"(d[119]), "+f"(d[120]), "+f"(d[121]), "+f"(d[122]), "+f"(d[123]), "+f"(d[124]), "+f"(d[125]), "+f"(d[126]), "+f"(d[127])
        : "l"(da), "l"(db), "r"(acc));
}
__device__ __forceinline__ void wgmma128(float (&d)[64], uint64_t da, uint64_t db, int acc) {
    asm volatile("{.reg .pred p; setp.ne.b32 p, %66, 0;\n"
        "wgmma.mma_async.sync.aligned.m64n128k16.f32.bf16.bf16 {"
        "%0,%1,%2,%3,%4,%5,%6,%7,%8,%9,%10,%11,%12,%13,%14,%15,"
        "%16,%17,%18,%19,%20,%21,%22,%23,%24,%25,%26,%27,%28,%29,%30,%31,"
        "%32,%33,%34,%35,%36,%37,%38,%39,%40,%41,%42,%43,%44,%45,%46,%47,"
        "%48,%49,%50,%51,%52,%53,%54,%55,%56,%57,%58,%59,%60,%61,%62,%63"
        "}, %64, %65, p, 1, 1, 0, 1;}"
        : "+f"(d[0]), "+f"(d[1]), "+f"(d[2]), "+f"(d[3]), "+f"(d[4]), "+f"(d[5]), "+f"(d[6]), "+f"(d[7]), "+f"(d[8]), "+f"(d[9]), "+f"(d[10]), "+f"(d[11]), "+f"(d[12]), "+f"(d[13]), "+f"(d[14]), "+f"(d[15]), "+f"(d[16]), "+f"(d[17]), "+f"(d[18]), "+f"(d[19]), "+f"(d[20]), "+f"(d[21]), "+f"(d[22]), "+f"(d[23]), "+f"(d[24]), "+f"(d[25]), "+f"(d[26]), "+f"(d[27]), "+f"(d[28]), "+f"(d[29]), "+f"(d[30]), "+f"(d[31]), "+f"(d[32]), "+f"(d[33]), "+f"(d[34]), "+f"(d[35]), "+f"(d[36]), "+f"(d[37]), "+f"(d[38]), "+f"(d[39]), "+f"(d[40]), "+f"(d[41]), "+f"(d[42]), "+f"(d[43]), "+f"(d[44]), "+f"(d[45]), "+f"(d[46]), "+f"(d[47]), "+f"(d[48]), "+f"(d[49]), "+f"(d[50]), "+f"(d[51]), "+f"(d[52]), "+f"(d[53]), "+f"(d[54]), "+f"(d[55]), "+f"(d[56]), "+f"(d[57]), "+f"(d[58]), "+f"(d[59]), "+f"(d[60]), "+f"(d[61]), "+f"(d[62]), "+f"(d[63])
        : "l"(da), "l"(db), "r"(acc));
}
__device__ __forceinline__ void wg_fence() { asm volatile("wgmma.fence.sync.aligned;" ::: "memory"); }
__device__ __forceinline__ void wg_commit() { asm volatile("wgmma.commit_group.sync.aligned;" ::: "memory"); }
template <int N> __device__ __forceinline__ void wg_wait() { asm volatile("wgmma.wait_group.sync.aligned %0;" ::"n"(N) : "memory"); }
__device__ __forceinline__ uint64_t mkdesc(uint32_t addr, uint32_t lbo, uint32_t sbo, uint32_t sw) {
    return (uint64_t)((addr & 0x3FFFF) >> 4) | ((uint64_t)(lbo >> 4) << 16) | ((uint64_t)(sbo >> 4) << 32) | ((uint64_t)sw << 62);
}
__device__ __forceinline__ void tma2d(uint32_t dst, const CUtensorMap* m, int c0, int c1, uint32_t bar) {
    asm volatile("cp.async.bulk.tensor.2d.shared::cluster.global.mbarrier::complete_tx::bytes [%0], [%1, {%2, %3}], [%4];"
        ::"r"(dst), "l"(m), "r"(c0), "r"(c1), "r"(bar) : "memory");
}
__device__ __forceinline__ void tma3d(uint32_t dst, const CUtensorMap* m, int c0, int c1, int c2, uint32_t bar) {
    asm volatile("cp.async.bulk.tensor.3d.shared::cluster.global.mbarrier::complete_tx::bytes [%0], [%1, {%2, %3, %4}], [%5];"
        ::"r"(dst), "l"(m), "r"(c0), "r"(c1), "r"(c2), "r"(bar) : "memory");
}
__device__ __forceinline__ void tma3d_mc(uint32_t dst, const CUtensorMap* m, int c0, int c1, int c2, uint32_t bar, uint16_t mask) {
    asm volatile("cp.async.bulk.tensor.3d.shared::cluster.global.mbarrier::complete_tx::bytes.multicast::cluster [%0], [%1, {%2, %3, %4}], [%5], %6;"
        ::"r"(dst), "l"(m), "r"(c0), "r"(c1), "r"(c2), "r"(bar), "h"(mask) : "memory");
}
__device__ __forceinline__ void mbar_arrive(uint32_t bar) { asm volatile("mbarrier.arrive.shared.b64 _, [%0];" ::"r"(bar) : "memory"); }
__device__ __forceinline__ void mbar_arrive_remote(uint32_t bar) {
    asm volatile("mbarrier.arrive.shared::cluster.b64 _, [%0];" ::"r"(bar) : "memory");
}
template <int R> __device__ __forceinline__ void reg_inc() { asm volatile("setmaxnreg.inc.sync.aligned.u32 %0;" ::"n"(R)); }
template <int R> __device__ __forceinline__ void reg_dec() { asm volatile("setmaxnreg.dec.sync.aligned.u32 %0;" ::"n"(R)); }

constexpr int CH_NRES = 50;
constexpr int CH_WREG = CH_NRES * 512;
constexpr int CH_PART = 8 * CH_WREG;
constexpr int CH_SX = CH_PART + 16384;
constexpr int CH_MX = CH_SX + 3 * 1280;
constexpr int CH_QK = CH_MX;
constexpr int CH_XS = CH_MX + 3 * 512;
constexpr int CH_BAR = CH_XS + 5632;
constexpr int CH_SMEM = CH_BAR + 192;
constexpr int CH_THREADS = 384;

__device__ __forceinline__ char* ring_base() { return (char*)(((uintptr_t)g_ring + (1 << 20) - 1) & ~(uintptr_t)((1 << 20) - 1)); }
__device__ __forceinline__ uint32_t ring_off(int chunk, int side) {
    uint32_t o = ((chunk & 1) << 13) | ((chunk >> 1) << 16);
    uint32_t par = ((o >> 13) ^ (o >> 16) ^ (o >> 17) ^ (o >> 19) ^ side) & 1;
    return o | (par << 12);
}
__device__ __forceinline__ uint2 ld_poll(const char* p) {
    unsigned long long v; asm volatile("ld.relaxed.gpu.global.b64 %0, [%1];" : "=l"(v) : "l"(p) : "memory");
    return make_uint2((uint32_t)v, (uint32_t)(v >> 32));
}
__device__ __forceinline__ void st_pub(char* p, uint32_t x, uint32_t y) {
    unsigned long long v = ((unsigned long long)y << 32) | x;
    asm volatile("st.relaxed.gpu.global.b64 [%0], %1;" ::"l"(p), "l"(v) : "memory");
}
template <int N>
__device__ __forceinline__ void poll_issue(uint2 (&b)[N], const char* p, bool lastvalid) {
#pragma unroll
    for (int i = 0; i < N; i++) {
        if (i < N - 1 || lastvalid) b[i] = ld_poll(p + i * 256);
        else b[i] = make_uint2(0, 0);
    }
}
template <int N>
__device__ __forceinline__ int poll_check(uint2 (&b)[N], const char* p) {
    int it = 0;
    uint32_t mx = b[0].x;
#pragma unroll
    for (int i = 1; i < N; i++) mx = max(mx, b[i].x);
    if (__any_sync(0xffffffffu, mx == SENT)) {
        do {
#pragma unroll
            for (int i = 0; i < N; i++)
                if ((REALL && i < 10) || b[i].x == SENT) b[i] = ld_poll(p + i * 256);
            mx = b[0].x;
#pragma unroll
            for (int i = 1; i < N; i++) mx = max(mx, b[i].x);
            it++;
        } while (__any_sync(0xffffffffu, mx == SENT && it < SPIN_LIMIT));
    }
    return it;
}
template <int N>
__device__ __forceinline__ uint32_t delay(uint32_t a) {
    uint32_t z = 0;
#pragma unroll
    for (int i = 0; i < N; i++) asm volatile("ld.volatile.shared.u32 %0, [%1];" : "=r"(z) : "r"(a + z) : "memory");
    return z;
}

#define PFKV 0
#define LDW 1
constexpr int KVN = 2;
#define FEN 1
#define XB 4
#define KEEP 100
#define VCH_P 4
#define VCH_C 2
#define KGS 3
#define DLM 1
#define DLO 2
constexpr int OB = 0;
template <int PACE>
__device__ __forceinline__ void preload(uint32_t (&sw)[12][4], uint32_t a, uint32_t zero) {
    uint32_t z = 0;
#pragma unroll
    for (int i = 0; i < 12; i++) {
        if (PACE && i % (PACE ? PACE : 1) == 0) z = delay<1>(zero + z);
        ldsm4t(sw[i], a + z + i * 512);
    }
}
__device__ __forceinline__ void stsm4(uint32_t addr, uint32_t a, uint32_t b, uint32_t c, uint32_t d) {
    asm volatile("stmatrix.sync.aligned.m8n8.x4.shared.b16 [%0], {%1,%2,%3,%4};" ::"r"(addr), "r"(a), "r"(b), "r"(c), "r"(d) : "memory");
}
__device__ __forceinline__ void stsm4t(uint32_t addr, uint32_t a, uint32_t b, uint32_t c, uint32_t d) {
    asm volatile("stmatrix.sync.aligned.m8n8.x4.trans.shared.b16 [%0], {%1,%2,%3,%4};" ::"r"(addr), "r"(a), "r"(b), "r"(c), "r"(d) : "memory");
}
__device__ __forceinline__ void st_part(uint32_t addr, const float (&x)[4], const float (&y)[4]) {
    stsm4(addr, pack_bf16(x[0], x[1]), pack_bf16(x[2], x[3]), pack_bf16(y[0], y[1]), pack_bf16(y[2], y[3]));
}
template <bool TR>
__device__ __forceinline__ void red_part(uint32_t& lo, uint32_t& hi, uint32_t addr, uint32_t eye) {
    uint32_t a[4][4];
#pragma unroll
    for (int j = 0; j < 4; j++) { if (TR) ldsm4t(a[j], addr + j * 1024); else ldsm4(a[j], addr + j * 1024); }
    float r0[4], r1[4], r2[4], r3[4];
    mma16z(r0, a[0], eye, eye); mma16z(r1, a[1], eye, eye); mma16z(r2, a[2], eye, eye); mma16z(r3, a[3], eye, eye);
#pragma unroll
    for (int j = 0; j < 4; j++) r0[j] = ((r0[j] + r1[j]) + r2[j]) + r3[j];
    lo = pack_bf16(r0[0], r0[1]); hi = pack_bf16(r0[2], r0[3]);
}
__device__ __forceinline__ int o_chunk(int ks, int& pos) {
    const int cw = ks < 176 ? ks / 11 : 16 + (ks - 176) / 10;
    pos = ks - (cw < 16 ? 11 * cw : 176 + 10 * (cw - 16));
    return cw;
}

template <bool PV>
__device__ __forceinline__ void chain_loop(const uint32_t (&wa)[36][4], const uint32_t sb, const int w, const int lane0, const int rank,
                                           const int h, const int side) {
    const int rk1 = rank == 2 ? 0 : rank + 1, rk2 = rank == 0 ? 2 : rank - 1;
    const int nq = rank == 0 ? 6 : 5, u0 = rank == 0 ? 0 : 1 + 5 * rank, v0 = rank == 0 ? -6 : 3 * rank - 6;
    const uint32_t pt = CH_PART + (w >> 1) * 4096 + (w & 1) * 256;
    const uint32_t barS = sb + CH_BAR, barM = barS + 8, zero = barS + 24;
    char* const ring0 = ring_base();
    const uint32_t m_rd = ring_off(24 + w, side), o_rd = ring_off(rank * 8 + w, side);
    uint32_t pub;
    if (PV) { int pos, cw = o_chunk(h * 8 + v0 + w, pos); pub = (ring_off(cw, 0) & ~4096u) + pos * 256; }
    else pub = (ring_off(24 + (h >> 2), 0) & ~4096u) + ((2 * h + w) & 7) * 256;
    char* const kvo = (char*)(PV ? g_vm + 128 * (v0 + w) : g_km + 64 * (u0 + w)) + h * 2048;
    const bool mown = !PV && w == rank && rank < 2;
    uint32_t lo16 = lane0 * 16;
    uint32_t sw[12][4];
#pragma unroll
    for (int i = 0; i < 12; i++) ldsm4t(sw[i], sb + lo16 + w * CH_WREG + i * 512);

#pragma unroll 1
    for (int s = 0;; s++) {
        const bool last = s == NSEG - 1;
        const uint32_t slot = (s & 3) << 14;
        lo16 += delay<DLM>(zero);
        const uint32_t lane = lo16 >> 4, l16 = sb + lo16, wl = l16 + w * CH_WREG, pw = l16 + CH_PART + w * 512;
        const uint32_t xs = l16 + CH_XS + nq * 512 + (w - nq) * 1024;
        const uint32_t eye = ((lo16 >> 7) == (lane & 3)) ? ((lo16 & 64) ? 0x3F800000u : 0x3F80u) : 0u;
        uint2 b[8];
        const char* pm = ring0 + (m_rd + slot + (lo16 >> 1));
        poll_issue<8>(b, pm, true);
        poll_check<8>(b, pm);
        if ((OB || (XB & 1)) && !last) bar_arrive(8, 256 + OB);
        if (PV && !last && w == 7) bar_arrive(13, 64);
        {
            float acc[6][4];
#pragma unroll
            for (int kk = 0; kk < 8; kk++) {
                const int j = (2 * kk) % 12;
                if (kk == 0) { mma16z(acc[5], sw[0], b[0].x, b[0].y); mma16z(acc[4], sw[1], b[0].x, b[0].y); }
                else { mma16(acc[5], sw[j], b[kk].x, b[kk].y); mma16(acc[4], sw[j + 1], b[kk].x, b[kk].y); }
#pragma unroll
                for (int i = 0; i < 4; i++) {
                    if (kk == 0) mma16z(acc[i], wa[i * 8], b[0].x, b[0].y);
                    else mma16(acc[i], wa[i * 8 + kk], b[kk].x, b[kk].y);
                    if (i < 2) ldsm4t(sw[j + i], wl + (12 + 2 * kk + i) * 512);
                }
            }
            st_part(pw + 4 * 2048, acc[4], acc[5]);
            st_part(pw, acc[0], acc[1]);
            st_part(pw + 2 * 2048, acc[2], acc[3]);
        }
        uint32_t kv0, kv1;
        const uint32_t lp = l16 + (lane >> 4) * 256, pl = lp + pt;
        if (!PV) {
            bar_sync(1, last ? 256 : 256 + OB);
            red_part<true>(kv1, kv0, pl, eye);
            sts64(l16 + CH_QK + (w >> 1) * 512 + (w & 1) * 8, __uint_as_float(kv1), __uint_as_float(kv0));
            if (!last) bar_arrive(2, nq * 32 + 64 + OB);
        } else {
            bar_sync(1, last ? 256 : 256 + OB);
        }
        {
            float va[4][4];
            const float z = __uint_as_float(delay<1>(zero));
#pragma unroll
            for (int i = 0; i < 4; i++) va[i][0] = va[i][1] = va[i][2] = va[i][3] = z;
#pragma unroll
            for (int kk = 0; kk < 8; kk++) {
                const int c = (PV ? VCH_P : VCH_C) == 4 ? kk & 1 : 0;
                if (kk < 2) { mma16(va[c], wa[32 + 2 * kk], b[kk].x, b[kk].y); mma16(va[2 + c], wa[33 + 2 * kk], b[kk].x, b[kk].y); }
                else { mma16(va[c], sw[(2 * kk) % 12], b[kk].x, b[kk].y); mma16(va[2 + c], sw[(2 * kk + 1) % 12], b[kk].x, b[kk].y); }
            }
            if ((PV ? VCH_P : VCH_C) == 4) {
#pragma unroll
                for (int j = 0; j < 4; j++) { va[0][j] += va[1][j]; va[2][j] += va[3][j]; }
            }
            st_part(pw + 6 * 2048, va[0], va[2]);
        }
        if (PV) {
            uint32_t vt0[4], vt1[4];
            ldsm4t(vt0, xs); ldsm4t(vt1, xs + 512);
            if (w >= 6 && !last) {
                uint32_t kx[3][4];
#pragma unroll
                for (int j = 0; j < 3; j++)
                    ldsm4(kx[j], sb + CH_XS + j * 1024 + (j == 2 && nq == 5 ? 0 : ((lane >> 3) & 1) * 512) + (w - 6) * 256 + (lane >> 4) * 128 + (lane & 7) * 16);
                const uint32_t da = l16 + CH_SX + rank * 1280 + (w - 6) * 512, dc = sb + CH_SX + rank * 1280 + 1024 + lane * 8;
                bar_sync(2, nq * 32 + 64 + OB);
                uint32_t qk[3][4];
#pragma unroll
                for (int j = 0; j < 3; j++) {
                    const float4 v = lds128(l16 + CH_QK + j * 512);
                    qk[j][0] = __float_as_uint(v.x); qk[j][1] = __float_as_uint(v.y); qk[j][2] = __float_as_uint(v.z); qk[j][3] = __float_as_uint(v.w);
                }
                float s0[4], s1[4], s2[4], s3[4];
                mma16z(s0, qk[0], kx[0][0], kx[0][1]); mma16z(s1, qk[0], kx[0][2], kx[0][3]);
                mma16z(s2, qk[1], kx[1][0], kx[1][1]); mma16z(s3, qk[1], kx[1][2], kx[1][3]);
                if (nq == 5) qk[2][2] = qk[2][3] = 0;
                mma16(s0, qk[2], kx[2][0], kx[2][1]); mma16(s1, qk[2], kx[2][2], kx[2][3]);
                float m0[4], m1[4];
                mma16z(m0, qk[0], qk[0][1], qk[0][3]); mma16z(m1, qk[1], qk[1][1], qk[1][3]);
                mma16(m0, qk[2], qk[2][1], qk[2][3]);
                const float4 sv = make_float4(s0[0] + s2[0], s0[1] + s2[1], s1[0] + s3[0], s1[1] + s3[1]);
                st_async4(mapa(da, rk1), sv, mapa(barS, rk1));
                st_async4(mapa(da, rk2), sv, mapa(barS, rk2));
                {
                    const float c0 = m0[0] + m1[0], c1 = m0[1] + m1[1];
                    const int dr = w == 6 ? rk1 : rk2;
                    st_async2(mapa(dc, dr), c0, c1, mapa(barS, dr));
                    sts64(dc, c0, c1);
                }
                const float t4[4] = {sv.x, sv.y, sv.z, sv.w};
                sts128(da, t4);
            }
            bar_sync(3, last ? 256 : 256 + OB);
            if (!last && w == 7) bar_arrive(12, 64);
            red_part<false>(kv0, kv1, pl, eye);
            if (last) {
                uint32_t* d = (uint32_t*)(kvo + (uint32_t)(s * (NH * 2048) + lane * 4));
                d[0] = movm(kv0); d[32] = movm(kv1);
                break;
            }
            {
                const uint32_t sx = l16 + CH_SX, r0 = rank * 1280, r1 = rk1 * 1280, r2 = rk2 * 1280;
                float4 a0 = lds128(sx + r0), b0 = lds128(sx + 512 + r0);
                const float2 c0 = lds64(sx + 1024 + r0 - lane * 8);
                mbar_wait(barS, s & 1);
                const float4 a1 = lds128(sx + r1), a2 = lds128(sx + r2), b1 = lds128(sx + 512 + r1), b2 = lds128(sx + 512 + r2);
                const float2 c1 = lds64(sx + 1024 + r1 - lane * 8), c2 = lds64(sx + 1024 + r2 - lane * 8);
                a0 = add4(add4(a0, a1), a2); b0 = add4(add4(b0, b1), b2);
                float sc[10] = {a0.x, a0.y, a0.z, a0.w, b0.x, b0.y, b0.z, b0.w, c0.x + c1.x + c2.x, c0.y + c1.y + c2.y};
                float mx = fmaxf(fmaxf(fmaxf(sc[0], sc[1]), fmaxf(sc[2], sc[3])), fmaxf(fmaxf(sc[4], sc[5]), fmaxf(sc[6], sc[7])));
                mx = fmaxf(mx, fmaxf(sc[8], sc[9]));
                mx = fmaxf(fmaxf(mx, __shfl_xor_sync(0xffffffffu, mx, 1)),
                           fmaxf(__shfl_xor_sync(0xffffffffu, mx, 2), __shfl_xor_sync(0xffffffffu, mx, 3)));
                const float cs = 0.08838834764831845f * 1.4426950408889634f;
                const float mb = -mx * cs;
#pragma unroll
                for (int j = 0; j < 10; j++) sc[j] = ex2(fmaf(sc[j], cs, mb));
                uint32_t pf[5];
#pragma unroll
                for (int j = 0; j < 5; j++) pf[j] = pack_bf16(sc[2 * j], sc[2 * j + 1]);
                float o0[4], o1[4], o2[4], o3[4], o4[4], o5[4];
                const uint32_t p0[4] = {pf[0], 0, pf[1], 0}, p1[4] = {pf[2], 0, pf[3], 0};
                mma16z(o0, p0, vt0[0], vt0[1]); mma16z(o1, p0, vt1[0], vt1[1]);
                mma16z(o2, p1, vt0[2], vt0[3]); mma16z(o3, p1, vt1[2], vt1[3]);
                mma8z(o4, pf[4], 0, kv0); mma8z(o5, pf[4], 0, kv1);
                float sum = (((sc[0] + sc[1]) + (sc[2] + sc[3])) + ((sc[4] + sc[5]) + (sc[6] + sc[7]))) + (sc[8] + sc[9]);
                sum = (sum + __shfl_xor_sync(0xffffffffu, sum, 1)) + (__shfl_xor_sync(0xffffffffu, sum, 2) + __shfl_xor_sync(0xffffffffu, sum, 3));
                float inv; asm("rcp.approx.ftz.f32 %0, %1;" : "=f"(inv) : "f"(sum));
                const uint32_t ox = pack_bf16((o0[0] + o2[0] + o4[0]) * inv, (o0[1] + o2[1] + o4[1]) * inv);
                const uint32_t oy = pack_bf16((o1[0] + o3[0] + o5[0]) * inv, (o1[1] + o3[1] + o5[1]) * inv);
                char* const pp = ring0 + (pub + slot + (lo16 >> 1));
                st_pub(pp, ox, oy); st_pub(pp + 4096, ox, oy);
                if (OB || (XB & 4)) bar_arrive(10, (8 - nq) * 32 + OB);
                preload<0>(sw, wl + 28 * 512, zero);
            }
            kv0 = movm(kv0); kv1 = movm(kv1);
        } else {
            *(uint32_t*)(kvo + (uint32_t)(s * (NH * 2048) + lane * 4)) = kv0;
            bar_sync(3, last ? 256 : 256 + OB);
            if (last) break;
            preload<1>(sw, wl + 28 * 512, zero);
        }
        uint2 c[11];
        bar_sync(4, 256 + OB);
        const char* po = ring0 + (o_rd + slot + (lo16 >> 1) + delay<DLO>(zero));
        poll_issue<11>(c, po, rank < 2);
        if (PV) { uint32_t* d = (uint32_t*)(kvo + (uint32_t)(s * (NH * 2048) + lane * 4)); d[0] = kv0; d[32] = kv1; }
        poll_check<11>(c, po);
        if (OB || (XB & 2)) bar_arrive(9, 256 + OB);
        {
            float acc[4][4];
#pragma unroll
            for (int f = 0; f < 22; f++) {
                const int kk = f >> 1, a = f & 3;
                if (f < 4) mma16z(acc[a], sw[f % 12], c[kk].x, c[kk].y);
                else mma16(acc[a], sw[f % 12], c[kk].x, c[kk].y);
                if (f + 12 < 22) ldsm4t(sw[f % 12], wl + (28 + f + 12) * 512);
            }
#pragma unroll
            for (int i = 0; i < 2; i++) {
#pragma unroll
                for (int j = 0; j < 4; j++) acc[i][j] += acc[i + 2][j];
                sts128(l16 + CH_PART + i * 4096 + w * 512, acc[i]);
            }
        }
        if (!PV && w < 2) {
            bar_sync(5, 288 + OB);
            float4 v[8];
#pragma unroll
            for (int i = 0; i < 8; i++) v[i] = lds128(l16 + CH_PART + w * 4096 + i * 512);
            float4 r = add4(add4(add4(v[0], v[1]), add4(v[2], v[3])), add4(add4(v[4], v[5]), add4(v[6], v[7])));
            if (!mown) st_async4(mapa(l16 + CH_MX + rank * 512, w), r, mapa(barM, w));
            bar_arrive(7, 256 + OB);
            if (mown) {
                mbar_wait(barM, s & 1);
                float4 x = lds128(l16 + CH_MX + (rank ^ 1) * 512), y = lds128(l16 + CH_MX + 2 * 512);
                r = add4(add4(x, r), y);
                const uint32_t mx = movm(pack_bf16(r.x, r.y)), my = movm(pack_bf16(r.z, r.w));
                const uint32_t ns = (slot + 0x4000) & 0xC000;
                char* const pp = ring0 + (pub + ns + (lo16 >> 1));
                st_pub(pp, mx, my); st_pub(pp + 4096, mx, my);
            }
            preload<0>(sw, wl, zero);
        } else {
            bar_arrive(5, 288 + OB);
            bar_sync(7, 256 + OB);
            preload<2>(sw, wl, zero);
        }
        bar_sync(6, 320 + OB);
    }
    bar_arrive(6, 288);
}

__device__ __forceinline__ void chain_pace(const uint32_t sb, const int lane, const int rank, const int aware) {
    const uint32_t zero = sb + CH_BAR + 24;
    if (lane == 0) {
        char* ring = ring_base();
        uint32_t* p0 = (uint32_t*)(ring + ring_off(blockIdx.x & 15, 0) + 3072 + (blockIdx.x >> 4) * 128);
        uint32_t* p1 = (uint32_t*)(ring + ring_off(blockIdx.x & 15, 1) + 3072 + (blockIdx.x >> 4) * 128);
        *p0 = 0; *p1 = 0;
        int b0 = 1 << 30, b1 = 1 << 30; uint32_t v = 0;
        for (int r = 0; r < 4 || (r < 256 && !mbar_test(sb + CH_BAR + 16, 0)); r++) {
            uint32_t t0 = clk(); v = atomicExch(p0 + (v == 500), r); uint32_t t1 = v == 777 ? clk() + 1 : clk(); b0 = min(b0, (int)(t1 - t0));
            t0 = clk(); v = atomicExch(p1 + (v == 500), r); t1 = v == 777 ? clk() + 1 : clk(); b1 = min(b1, (int)(t1 - t0));
            asm volatile("st.volatile.shared.u32 [%0], %1;" ::"r"(zero + 4), "r"(aware ? (b1 < b0) ^ (aware - 1) : 0) : "memory");
        }
    }
    __syncwarp();
#pragma unroll 1
    for (int s = 1; s < NSEG; s++) {
        bar_sync(5, 288 + OB);
        bar_arrive(6, 320 + OB + (rank == 2 ? delay<18>(zero) : 0));
    }
}
__device__ __forceinline__ char* reset_ptr(const int lane, const int rank, const int h) {
    const int nq = rank == 0 ? 6 : 5, v0 = rank == 0 ? -6 : 3 * rank - 6;
    int pos, cw = o_chunk(h * 8 + v0 + min(max(5 + (lane >> 3), nq), 7), pos);
    if (lane >= 24 && rank < 2) { cw = 24 + (h >> 2); pos = (2 * h + rank) & 7; }
    return ring_base() + ((ring_off(cw, 0) & ~4096u) + pos * 256 + (lane & 7) * 16);
}
__device__ __forceinline__ void chain_chores(const uint32_t sb, const int lane, const int rank, const int h, const bf16* __restrict__ mem0) {
    const int nq = rank == 0 ? 6 : 5, u0 = rank == 0 ? 0 : 1 + 5 * rank, v0 = rank == 0 ? -6 : 3 * rank - 6;
    const uint32_t barS = sb + CH_BAR, barM = barS + 8, barX = barS + 16;
    auto xload = [&](int s) {
        mbar_expect(barX, 8192 - nq * 512);
        bulk_load(sb + CH_XS, g_kx + (size_t)(s * NH + h) * 4096 + u0 * 256, nq * 512, barX);
        bulk_load(sb + CH_XS + nq * 512, g_vx + (size_t)(s * NH + h) * 4096 + (v0 + nq) * 512, (8 - nq) * 1024, barX);
    };
    char* const rb = reset_ptr(lane, rank, h);
    int* const kvf = g_kvf + blockIdx.x * 16;
    if (rank < 2) {
        const uint32_t* p = (const uint32_t*)(mem0 + (lane >> 2) * DM + 32 * h + 16 * rank + 2 * (lane & 3));
        char* d = ring_base() + ((ring_off(24 + (h >> 2), 0) & ~4096u) + ((2 * h + rank) & 7) * 256 + lane * 8);
        const uint32_t x = p[0] == SENT ? 0x7FFF7FFFu : p[0];
        st_pub(d, x, p[4]); st_pub(d + 4096, x, p[4]);
    }
    if (lane == 0) {
        if (!KVN) __nanosleep(18000);
        wait_ctr(kvf, KVN);
        asm volatile("fence.proxy.async;" ::: "memory");
        xload(0);
    }
#pragma unroll 1
    for (int s = 0; s < NSEG - 1; s++) {
        if (lane == 0) {
            mbar_expect(barS, 2 * 1280);
            if (rank < 2) mbar_expect(barM, 2 * 512);
        }
        bar_sync(13, 64);
#pragma unroll
        for (int i = 0; i < 4; i++)
            asm volatile("st.relaxed.gpu.global.v4.u32 [%0], {%1,%1,%1,%1};" ::"l"(rb + ((((s + 2) & 3) << 14) + (i >> 1) * 4096 + (i & 1) * 128)), "r"(SENT) : "memory");
        if (FEN || (s & 3) == 0) __threadfence();
        if (lane == 0 && (s & 3) == 0 && s) atomicAdd(g_ctr + C_CHAIN + (s >> 2) - 1, 1);
        if (lane == 0 && (s & 3) == 3) { wait_ctr(kvf + (s >> 2) + 1, KVN); asm volatile("fence.proxy.async;" ::: "memory"); }
        __syncwarp();
        bar_sync(12, 64);
        if (lane == 0) xload(s + 1);
        mbar_wait(barX, (s + 1) & 1);
        bar_sync(6, 320 + OB);
    }
    bar_sync(6, 288);
    __threadfence();
    if (lane == 0) atomicAdd(g_ctr + C_CHAIN + 15, 1);
}

struct S4Params { const bf16 *Are, *Aim, *Bre, *Bim, *Cre, *Cim, *ldt, *dsk; };
__device__ __forceinline__ float2 cmul(float2 a, float2 b) { return make_float2(a.x * b.x - a.y * b.y, a.x * b.y + a.y * b.x); }
__device__ __forceinline__ float2 csq(float2 a) { return make_float2(a.x * a.x - a.y * a.y, (a.x + a.x) * a.y); }
__device__ __forceinline__ float2 cexp_t(float lr, float turns) {
    float f = (turns - rintf(turns)) * 6.283185307179586f, e = ex2(lr);
    return make_float2(e * __cosf(f), e * __sinf(f));
}
__device__ __forceinline__ float bf_at(uint2 v, int i) {
    const uint32_t w = i < 2 ? v.x : v.y;
    return __uint_as_float((i & 1) ? w & 0xFFFF0000u : w << 16);
}
__device__ __forceinline__ void kg_step(uint32_t (&a)[4][4], uint32_t (&b)[5][2], uint32_t pa, uint32_t pe, float x0) {
#pragma unroll
    for (int i = 0; i < 2; i++) {
        const float4 p = lds128(pa + i * 64);
        const float2 e8 = lds64(pe + i * 32), c = make_float2(p.z, p.w);
        const float mag = ex2(p.x * x0), ph = p.y * x0;
        float2 e0 = make_float2(mag * __cosf(ph), mag * __sinf(ph)), e1 = cmul(e0, e8);
#pragma unroll
        for (int j = 0; j < 4; j++) {
            a[j][2 * i] = pack_bf16(e0.x, e0.y); a[j][2 * i + 1] = pack_bf16(e1.x, e1.y);
            e0 = csq(e0); e1 = csq(e1);
        }
        float2 m = cmul(c, e0);
        b[0][i] = pack_bf16(m.x, -m.y);
#pragma unroll
        for (int j = 0; j < 4; j++) {
            m = cmul(c, e1);
            b[j + 1][i] = pack_bf16(m.x, -m.y);
            if (j < 3) e1 = csq(e1);
        }
    }
}
__device__ __forceinline__ void kg_mma(float (&kd)[5][4], const uint32_t (&a)[4][4], const uint32_t (&b)[5][2]) {
    mma16(kd[0], a[0], b[0][0], b[0][1]);
#pragma unroll
    for (int j = 0; j < 4; j++) mma16(kd[j + 1], a[j], b[j + 1][0], b[j + 1][1]);
}
struct KgRaw { uint2 v[6]; float ldt; };
__device__ __forceinline__ void kg_load(KgRaw& r, const S4Params& P, int d, int lane) {
    const bf16* src[6] = {P.Are, P.Aim, P.Bre, P.Bim, P.Cre, P.Cim};
#pragma unroll
    for (int j = 0; j < 6; j++) r.v[j] = __ldg((const uint2*)(src[j] + d * 128) + lane);
    r.ldt = __bfloat162float(P.ldt[d]);
}
__device__ __forceinline__ float kg_params(const KgRaw& r, uint32_t stg, int lane) {
    const float dt = __bfloat162float(__float2bfloat16(expf(r.ldt)));
    float k2048 = 0.f;
#pragma unroll
    for (int i = 0; i < 4; i++) {
        const float br = dt * bf_at(r.v[2], i), bi = dt * bf_at(r.v[3], i), cr = bf_at(r.v[4], i), ci = bf_at(r.v[5], i);
        const float zr = dt * bf_at(r.v[0], i) * 1.4426950408889634f;
        float zt = dt * bf_at(r.v[1], i) * 0.15915494309189535f;
        zt -= rintf(zt);
        const float v[4] = {zr, zt * 6.283185307179586f, cr * br - ci * bi, cr * bi + ci * br};
        const float2 e8 = cexp_t(8.f * zr, 8.f * zt), el = cexp_t(2048.f * zr, 2048.f * zt);
        k2048 += v[2] * el.x - v[3] * el.y;
        sts128(stg + (i * 32 + lane) * 16, v);
        sts64(stg + 2048 + (i * 32 + lane) * 8, e8.x, e8.y);
    }
#pragma unroll
    for (int o = 16; o; o >>= 1) k2048 += __shfl_xor_sync(0xffffffffu, k2048, o);
    __syncwarp();
    return k2048;
}
__device__ __forceinline__ void kg_store(const float (&kd)[5][4], float k2048, uint32_t stg, int d, int lane) {
    __syncwarp();
    const uint32_t ta = stg + (lane & 7) * 32 + ((lane >> 3) & 1) * 16 + (lane >> 4) * 256;
    stsm4t(ta, pack_bf16(kd[0][0], kd[0][1]), pack_bf16(kd[0][2], kd[0][3]), pack_bf16(kd[1][0], kd[1][1]), pack_bf16(kd[1][2], kd[1][3]));
    stsm4t(ta + 512, pack_bf16(kd[2][0], kd[2][1]), pack_bf16(kd[2][2], kd[2][3]), pack_bf16(kd[3][0], kd[3][1]), pack_bf16(kd[3][2], kd[3][3]));
    stsm4t(ta + 1024, pack_bf16(kd[4][0], kd[4][1]), pack_bf16(kd[4][2], kd[4][3]), pack_bf16(k2048, 0.f), 0);
    __syncwarp();
#pragma unroll
    for (int j = 0; j < 3; j++) ((float4*)(g_kd + d * 768))[j * 32 + lane] = lds128(stg + j * 512 + lane * 16);
    __syncwarp();
}

__global__ void __cluster_dims__(3, 1, 1) __launch_bounds__(CH_THREADS, 1)
chain_kernel(const __grid_constant__ CUtensorMap mq, const __grid_constant__ CUtensorMap mk, const __grid_constant__ CUtensorMap mv,
             const __grid_constant__ CUtensorMap mo, const bf16* __restrict__ Wq, const bf16* __restrict__ Wk, const bf16* __restrict__ Wv,
             const bf16* __restrict__ mem0, const __grid_constant__ S4Params P, int aware) {
    extern __shared__ __align__(1024) unsigned char smem[];
    const uint32_t sb = smem_u32(smem);
    const int tid = threadIdx.x, lane = tid & 31;
    const int w = __shfl_sync(0xffffffffu, tid >> 5, 0);
    int rank; asm("mov.u32 %0, %%cluster_ctarank;" : "=r"(rank));
    const int h = blockIdx.x / 3;
    if (tid == 0) {
        mbar_init(sb + CH_BAR, 1); mbar_init(sb + CH_BAR + 8, 1); mbar_init(sb + CH_BAR + 16, 1);
        for (int i = 0; i < 16; i++) mbar_init(sb + CH_BAR + 64 + i * 8, 1);
        *(int*)(smem + CH_BAR + 24) = 0; *(int*)(smem + CH_BAR + 28) = 0; *(int*)(smem + CH_BAR + 32) = 0;
        asm volatile("fence.mbarrier_init.release.cluster;" ::: "memory");
    }
    if (w == 10 && PFKV) {
        const int e = lane * 96 + blockIdx.x;
        if (e < 2048) asm volatile("cp.async.bulk.prefetch.L2.global [%0], 8192;" ::"l"(((e & 1) ? Wv : Wk) + (size_t)(e >> 1) * HD) : "memory");
        if (PFKV > 1) __nanosleep(PFKV);
    }
    if (w == 9) {
        char* const rb = reset_ptr(lane, rank, h);
#pragma unroll
        for (int i = 0; i < 8; i++)
            asm volatile("st.relaxed.gpu.global.v4.u32 [%0], {%1,%1,%1,%1};" ::"l"(rb + (((i >> 2) << 14) + ((i >> 1) & 1) * 4096 + (i & 1) * 128)), "r"(SENT) : "memory");
        if (lane < 16) g_kvf[blockIdx.x * 16 + lane] = 0;
        if (blockIdx.x == 0)
            for (int k = lane; k < N_CTR; k += 32) g_ctr[k] = 0;
        __threadfence();
        __syncwarp();
        asm volatile("griddepcontrol.launch_dependents;" ::: "memory");
    }
    __syncthreads();
    asm volatile("barrier.cluster.arrive.relaxed.aligned;" ::: "memory");

    if (w >= 8) {
        reg_dec<24>();
        asm volatile("barrier.cluster.wait.aligned;" ::: "memory");
        if (w == 8) chain_pace(sb, lane, rank, aware);
        else if (w == 9) {
            chain_chores(sb, lane, rank, h, mem0);
            asm volatile("st.volatile.shared.u32 [%0], %1;" ::"r"(sb + CH_BAR + 32), "r"(0x3F803F80) : "memory");
        } else if (w == 11 && KEEP) {
#pragma unroll 1
            for (int it = 0; it < (1 << 22); it++) {
                int d0, d1;
                const uint32_t x = delay<1>(sb + CH_BAR + 32);
                asm volatile("mma.sync.aligned.m8n8k16.row.col.s32.s8.s8.s32 {%0,%1}, {%2}, {%2}, {%3,%3};" : "=r"(d0), "=r"(d1) : "r"(x), "r"(0));
                if (d0 | d1) break;
                if ((XB & 8) && lane == 0) asm volatile("st.relaxed.gpu.global.u32 [%0], %1;" ::"l"(g_kd + DM * 768 + blockIdx.x * 64), "r"(it) : "memory");
                if ((XB & 16) && lane == 0) ld_acq((int*)(g_kd + DM * 768 + blockIdx.x * 64));
                __nanosleep(KEEP);
            }
        }
    } else {
        reg_inc<240>();
        const int nq = rank == 0 ? 6 : 5;
        const int u0 = rank == 0 ? 0 : 1 + 5 * rank;
        const int v0 = rank == 0 ? -6 : 3 * rank - 6;
        const int gw = rank * 8 + w;
        const int ks0 = gw < 16 ? 11 * gw : 176 + 10 * (gw - 16);
        const int nko = gw < 16 ? 11 : 10;
        const uint32_t wr = sb + w * CH_WREG, bar0 = sb + CH_BAR + 64 + w * 16, bar1 = bar0 + 8;
        uint32_t wa[36][4];
        const uint32_t vst = sb + CH_PART + w * 2048;
        const int cq = h * DH + 8 * u0, cv = h * DH + 16 * (v0 + 6);
        const int r8 = lane >> 2, p = lane & 3;
        const bf16* src = p >= 2 ? ((p & 1) ? Wk : Wq) + cq + 32 : rank == 0 ? ((p & 1) ? Wk : Wq) + cq + 40 : Wv + cv - 16 + 8 * p;
        src += (size_t)(128 * w + r8) * HD;
        auto cp_rows = [&](int kh) {
            cp16(wr + ((kh >> 1) * 2 + (p >> 1)) * 512 + ((kh & 1) * 2 + (p & 1)) * 128 + r8 * 16, src + (size_t)kh * 8 * HD);
        };
        {
            int d = blockIdx.x * 8 + w, t = 0;
            const int d1 = 768 + blockIdx.x * 3 + w, nt = (w < 3 && d1 < DM) ? 32 : 16;
            const uint32_t stg = wr + 4096;
            KgRaw raw, raw1;
            kg_load(raw, P, d, lane);
            kg_load(raw1, P, min(d1, DM - 1), lane);
            float kd[5][4], k2048;
#pragma unroll 1
            for (int i = -LDW; i < 9 || t < nt; i++) {
                if (i >= 0 && i < 9) {
                    const uint32_t bar = bar0 + (i & 1) * 8;
                    if (i >= 2) mbar_wait(bar, ((i >> 1) - 1) & 1);
                    if (lane == 0) {
                        mbar_expect(bar, 2048);
                        if (i < 8) tma2d(wr + 8192 + (i & 1) * 8192 + (i >> 1) * 2048, (i & 1) ? &mk : &mq, cq, 128 * w + 32 * (i >> 1), bar);
                        else tma2d(vst, &mv, cv, 128 * w, bar);
                    }
                    if (i < 8) cp_rows(i);
                }
#pragma unroll 1
                for (int e = min(t + KGS, nt); t < e; t++) {
                    if ((t & 15) == 0) {
                        k2048 = kg_params(raw, stg, lane);
#pragma unroll
                        for (int j = 0; j < 20; j++) kd[j >> 2][j & 3] = 0.f;
                    }
                    uint32_t ka[4][4], kb[5][2];
                    kg_step(ka, kb, stg + ((t & 15) * 8 + (lane & 3)) * 16, stg + 2048 + ((t & 15) * 8 + (lane & 3)) * 8, (float)(lane >> 2));
                    kg_mma(kd, ka, kb);
                    if ((t & 15) == 15) { kg_store(kd, k2048, stg, d, lane); raw = raw1; d = d1; }
                }
            }
        }
        const uint32_t lrow = ((lane >> 4) * 8 + (lane & 7)) * 64, lsw = (lane >> 1) & 3, lh = (lane >> 3) & 1;
        mbar_wait(bar1, 1); mbar_wait(bar0, 0);
#pragma unroll
        for (int i = 0; i < 32; i++) ldsm4t(wa[i], wr + 8192 + lh * 8192 + (i & 7) * 1024 + lrow + (((i >> 3) ^ lsw) << 4));
#pragma unroll
        for (int i = 0; i < 4; i++) ldsm4t(wa[32 + i], vst + (i >> 1) * 1024 + lrow + ((((i & 1) * 2 + lh) ^ lsw) << 4));
        asm volatile("fence.proxy.async.shared::cta;" ::"r"(wa[31][0]), "r"(wa[35][0]) : "memory");
        __syncwarp();
#pragma unroll 1
        for (int i = 9; i < 18; i++) {
            const uint32_t bar = bar0 + (i & 1) * 8;
            if (i >= 11) mbar_wait(bar, ((i >> 1) - 1) & 1);
            if (lane == 0) {
                const int j = 2 * (i - 12), nb = min(2, nko - j);
                mbar_expect(bar, i < 12 ? 2048 : nb * 1024);
                if (i < 12) tma2d(wr + 8192 + (i - 9) * 2048, &mv, cv, 128 * w + 32 * (i - 8), bar);
                else for (int e = 0; e < nb; e++) tma2d(wr + 14336 + (j + e) * 1024, &mo, 32 * h, 16 * (ks0 + j + e), bar);
            }
            if (i < 17) cp_rows(i - 1);
        }
        mbar_wait(bar0, 0); mbar_wait(bar1, 0);
#pragma unroll 1
        for (int i = 0; i < 17; i++) {
            uint32_t x[4], y[4];
            ldsm4t(x, wr + 8192 + i * 1024 + lrow + ((lh ^ lsw) << 4));
            ldsm4t(y, wr + 8192 + i * 1024 + lrow + (((2 + lh) ^ lsw) << 4));
            if (i == 16 && nko == 10) x[0] = x[1] = x[2] = x[3] = y[0] = y[1] = y[2] = y[3] = 0;
            __syncwarp();
            stsm4t(wr + 8192 + i * 1024 + lane * 16, x[0], x[1], x[2], x[3]);
            stsm4t(wr + 8192 + i * 1024 + 512 + lane * 16, y[0], y[1], y[2], y[3]);
        }
        asm volatile("cp.async.wait_all;" ::: "memory");
        asm volatile("barrier.cluster.wait.aligned;" ::: "memory");
        bar_sync(1, 256);
        mbar_wait_long(sb + CH_BAR + 16, 0);
        const int side = __shfl_sync(0xffffffffu, *(volatile int*)(smem + CH_BAR + 28), 0);
        if (w >= nq) chain_loop<true>(wa, sb, w, lane, rank, h, side);
        else chain_loop<false>(wa, sb, w, lane, rank, h, side);
    }
}

constexpr int G_STAGE = 49152, G_NST = 4;
constexpr int G_STG = G_NST * G_STAGE;
constexpr int G_BAR = G_STG + 32768;
constexpr int G_SMEM = G_BAR + 256 + 1024;

#define ST(id, w, i)
#define WLOG(e)
constexpr int IT_QA = 0, IT_O = 1, IT_S4 = 2, IT_END = 3, IT_KV = 4;
#define O_WIDE 8
#define ATT2 0
#define S4REL 4
#define KVP 0
#define KVS 8
#define STM 0
__device__ __forceinline__ void st_out(uint32_t* p, uint32_t v) {
    if (STM == 0) *p = v;
    else if (STM == 1) __stcs(p, v);
    else asm volatile("st.global.L1::no_allocate.u32 [%0], %1;" ::"l"(p), "r"(v) : "memory");
}
#define Q_N1 0
#define Q_S1 0
__device__ __forceinline__ int queue_item(int q) {
    if (KVP && q >= KVP && q < 512) return (IT_KV << 16) | (((q >> 6) * 2 + (q & 1)) << 8) | ((q >> 1) & 31);
    if (q < 512) return (IT_KV << 16) | ((q >> 5) << 8) | (q & 31);
    q -= 512;
    if (q < 256) return (IT_QA << 16) | ((q >> 4) << 8) | (q & 15);
    q -= 256;
    if (q < Q_N1 * 8) return (IT_O << 16) | ((O_WIDE + (q >> 3)) << 8) | (q & 7);
    q -= Q_N1 * 8;
    if (q < Q_S1) return (IT_S4 << 16) | q;
    q -= Q_S1;
    if (q < (16 - O_WIDE - Q_N1) * 8) return (IT_O << 16) | ((O_WIDE + Q_N1 + (q >> 3)) << 8) | (q & 7);
    q -= (16 - O_WIDE - Q_N1) * 8;
    if (q < 128 - Q_S1) return (IT_S4 << 16) | (Q_S1 + q);
    return IT_END << 16;
}
__device__ __forceinline__ void tma2d_store(const CUtensorMap* m, uint32_t src, int c0, int c1) {
    asm volatile("cp.async.bulk.tensor.2d.global.shared::cta.bulk_group [%0, {%2, %3}], [%1];" ::"l"(m), "r"(src), "r"(c0), "r"(c1) : "memory");
}

__device__ __forceinline__ void wgmma_s64(float (&d)[32], uint32_t a0, uint32_t a1, uint32_t a2, uint32_t a3, uint64_t db, int acc) {
    asm volatile("{.reg .pred p; setp.ne.b32 p, %37, 0;\n"
        "wgmma.mma_async.sync.aligned.m64n64k16.f32.bf16.bf16 {"
        "%0,%1,%2,%3,%4,%5,%6,%7,%8,%9,%10,%11,%12,%13,%14,%15,"
        "%16,%17,%18,%19,%20,%21,%22,%23,%24,%25,%26,%27,%28,%29,%30,%31"
        "}, {%32,%33,%34,%35}, %36, p, 1, 1, 0;}"
        : "+f"(d[0]), "+f"(d[1]), "+f"(d[2]), "+f"(d[3]), "+f"(d[4]), "+f"(d[5]), "+f"(d[6]), "+f"(d[7]), "+f"(d[8]), "+f"(d[9]), "+f"(d[10]), "+f"(d[11]), "+f"(d[12]), "+f"(d[13]), "+f"(d[14]), "+f"(d[15]), "+f"(d[16]), "+f"(d[17]), "+f"(d[18]), "+f"(d[19]), "+f"(d[20]), "+f"(d[21]), "+f"(d[22]), "+f"(d[23]), "+f"(d[24]), "+f"(d[25]), "+f"(d[26]), "+f"(d[27]), "+f"(d[28]), "+f"(d[29]), "+f"(d[30]), "+f"(d[31])
        : "r"(a0), "r"(a1), "r"(a2), "r"(a3), "l"(db), "r"(acc));
}
__device__ __forceinline__ void wgmma_s16(float (&d)[8], uint32_t a0, uint32_t a1, uint32_t a2, uint32_t a3, uint64_t db, int acc) {
    asm volatile("{.reg .pred p; setp.ne.b32 p, %13, 0;\n"
        "wgmma.mma_async.sync.aligned.m64n16k16.f32.bf16.bf16 {"
        "%0,%1,%2,%3,%4,%5,%6,%7"
        "}, {%8,%9,%10,%11}, %12, p, 1, 1, 0;}"
        : "+f"(d[0]), "+f"(d[1]), "+f"(d[2]), "+f"(d[3]), "+f"(d[4]), "+f"(d[5]), "+f"(d[6]), "+f"(d[7])
        : "r"(a0), "r"(a1), "r"(a2), "r"(a3), "l"(db), "r"(acc));
}
__device__ __forceinline__ void wgmma_v128(float (&d)[64], uint32_t a0, uint32_t a1, uint32_t a2, uint32_t a3, uint64_t db, int acc) {
    asm volatile("{.reg .pred p; setp.ne.b32 p, %69, 0;\n"
        "wgmma.mma_async.sync.aligned.m64n128k16.f32.bf16.bf16 {"
        "%0,%1,%2,%3,%4,%5,%6,%7,%8,%9,%10,%11,%12,%13,%14,%15,"
        "%16,%17,%18,%19,%20,%21,%22,%23,%24,%25,%26,%27,%28,%29,%30,%31,"
        "%32,%33,%34,%35,%36,%37,%38,%39,%40,%41,%42,%43,%44,%45,%46,%47,"
        "%48,%49,%50,%51,%52,%53,%54,%55,%56,%57,%58,%59,%60,%61,%62,%63"
        "}, {%64,%65,%66,%67}, %68, p, 1, 1, 1;}"
        : "+f"(d[0]), "+f"(d[1]), "+f"(d[2]), "+f"(d[3]), "+f"(d[4]), "+f"(d[5]), "+f"(d[6]), "+f"(d[7]), "+f"(d[8]), "+f"(d[9]), "+f"(d[10]), "+f"(d[11]), "+f"(d[12]), "+f"(d[13]), "+f"(d[14]), "+f"(d[15]), "+f"(d[16]), "+f"(d[17]), "+f"(d[18]), "+f"(d[19]), "+f"(d[20]), "+f"(d[21]), "+f"(d[22]), "+f"(d[23]), "+f"(d[24]), "+f"(d[25]), "+f"(d[26]), "+f"(d[27]), "+f"(d[28]), "+f"(d[29]), "+f"(d[30]), "+f"(d[31]), "+f"(d[32]), "+f"(d[33]), "+f"(d[34]), "+f"(d[35]), "+f"(d[36]), "+f"(d[37]), "+f"(d[38]), "+f"(d[39]), "+f"(d[40]), "+f"(d[41]), "+f"(d[42]), "+f"(d[43]), "+f"(d[44]), "+f"(d[45]), "+f"(d[46]), "+f"(d[47]), "+f"(d[48]), "+f"(d[49]), "+f"(d[50]), "+f"(d[51]), "+f"(d[52]), "+f"(d[53]), "+f"(d[54]), "+f"(d[55]), "+f"(d[56]), "+f"(d[57]), "+f"(d[58]), "+f"(d[59]), "+f"(d[60]), "+f"(d[61]), "+f"(d[62]), "+f"(d[63])
        : "r"(a0), "r"(a1), "r"(a2), "r"(a3), "l"(db), "r"(acc));
}

__device__ __forceinline__ void attn_scores(float (&sx)[32], float (&sm)[8], const uint32_t (&q)[32], uint32_t sk) {
    const uint64_t dx = mkdesc(sk, 1024, 128, 0), dm = mkdesc(sk + 16384, 256, 128, 0);
    wg_fence();
#pragma unroll
    for (int ks = 0; ks < 8; ks++) {
        wgmma_s64(sx, q[4 * ks], q[4 * ks + 1], q[4 * ks + 2], q[4 * ks + 3], dx + ks * 128, ks);
        wgmma_s16(sm, q[4 * ks], q[4 * ks + 1], q[4 * ks + 2], q[4 * ks + 3], dm + ks * 32, ks);
    }
    wg_commit();
}
__device__ __forceinline__ void attn_softmax(uint32_t (&p)[20], const float (&sx)[32], const float (&sm)[8], int wi, int lane) {
    const bool sb = wi >= 2;
    const int r0 = (wi & 1) * 16 + (lane >> 2) - 2 * (lane & 3);
    float s[5][4];
#pragma unroll
    for (int j = 0; j < 4; j++) s[4][j] = sb ? sm[4 + j] : sm[j];
    float m0 = fmaxf(s[4][0], s[4][1]), m1 = fmaxf(s[4][2], s[4][3]);
#pragma unroll
    for (int j = 0; j < 4; j++) {
#pragma unroll
        for (int e = 0; e < 4; e++) s[j][e] = 8 * j + (e & 1) > r0 + 8 * (e >> 1) ? -INFINITY : sb ? sx[16 + 4 * j + e] : sx[4 * j + e];
        m0 = fmaxf(m0, fmaxf(s[j][0], s[j][1])); m1 = fmaxf(m1, fmaxf(s[j][2], s[j][3]));
    }
    m0 = fmaxf(m0, __shfl_xor_sync(0xffffffffu, m0, 1)); m1 = fmaxf(m1, __shfl_xor_sync(0xffffffffu, m1, 1));
    m0 = fmaxf(m0, __shfl_xor_sync(0xffffffffu, m0, 2)); m1 = fmaxf(m1, __shfl_xor_sync(0xffffffffu, m1, 2));
    const float cs = 0.08838834764831845f * 1.4426950408889634f;
    m0 *= -cs; m1 *= -cs;
    float l0 = 0, l1 = 0;
#pragma unroll
    for (int j = 0; j < 5; j++) {
        s[j][0] = ex2(fmaf(s[j][0], cs, m0)); s[j][1] = ex2(fmaf(s[j][1], cs, m0));
        s[j][2] = ex2(fmaf(s[j][2], cs, m1)); s[j][3] = ex2(fmaf(s[j][3], cs, m1));
        l0 += s[j][0] + s[j][1]; l1 += s[j][2] + s[j][3];
    }
    l0 += __shfl_xor_sync(0xffffffffu, l0, 1); l1 += __shfl_xor_sync(0xffffffffu, l1, 1);
    l0 += __shfl_xor_sync(0xffffffffu, l0, 2); l1 += __shfl_xor_sync(0xffffffffu, l1, 2);
    asm("rcp.approx.ftz.f32 %0, %0;" : "+f"(l0)); asm("rcp.approx.ftz.f32 %0, %0;" : "+f"(l1));
    const uint32_t ma = sb ? 0u : ~0u;
#pragma unroll
    for (int j = 0; j < 5; j++) {
        const uint32_t x = pack_bf16(s[j][0] * l0, s[j][1] * l0), y = pack_bf16(s[j][2] * l1, s[j][3] * l1);
        const int ia = j < 4 ? 2 * j : 16, ib = j < 4 ? 8 + 2 * j : 18;
        asm volatile("and.b32 %0, %4, %6; and.b32 %1, %5, %6; and.b32 %2, %4, %7; and.b32 %3, %5, %7;"
            : "=&r"(p[ia]), "=&r"(p[ia + 1]), "=&r"(p[ib]), "=&r"(p[ib + 1]) : "r"(x), "r"(y), "r"(ma), "r"(~ma));
    }
}
__device__ __forceinline__ void attn_pv(float (&o)[64], const uint32_t (&p)[20], uint32_t sv) {
    const uint64_t dx = mkdesc(sv, 128, 1024, 0), dm = mkdesc(sv + 16384, 128, 256, 0);
    wg_fence();
#pragma unroll
    for (int ks = 0; ks < 5; ks++) wgmma_v128(o, p[4 * ks], p[4 * ks + 1], p[4 * ks + 2], p[4 * ks + 3], ks < 4 ? dx + ks * 16 : dm, ks);
    wg_commit();
}
__device__ __forceinline__ void attn_stage(const float (&o)[64], uint32_t dst) {
#pragma unroll
    for (int u = 0; u < 16; u += 2)
        stsm4(dst + (u >> 3) * 8192 + (u & 7) * 128, pack_bf16(o[4 * u], o[4 * u + 1]), pack_bf16(o[4 * u + 2], o[4 * u + 3]),
              pack_bf16(o[4 * u + 4], o[4 * u + 5]), pack_bf16(o[4 * u + 6], o[4 * u + 7]));
}

template <int BN, int NKB, bool BLOCKED_A>
__device__ __forceinline__ void mainloop(float (&acc)[BN / 2], uint32_t sb, int wgi, uint32_t full, uint32_t empty, int& it, bool elect) {
#pragma unroll
    for (int j = 0; j < BN / 2; j++) acc[j] = 0.f;
#pragma unroll 1
    for (int k4 = 0; k4 < NKB; k4 += 4) {
#pragma unroll
        for (int st = 0; st < 4; st++, it++) {
            mbar_wait(full + 8 * st, (it >> 2) & 1);
            const uint64_t da = BLOCKED_A ? mkdesc(sb + st * G_STAGE + wgi * 8192, 128, 1024, 0) : mkdesc(sb + st * G_STAGE + wgi * 8192, 16, 1024, 1);
            const uint64_t db = mkdesc(sb + st * G_STAGE + 16384, 8192, 1024, 1);
            wg_fence();
#pragma unroll
            for (int k = 0; k < 4; k++) {
                if constexpr (BN == 256) wgmma256(acc, da + k * (BLOCKED_A ? 16 : 2), db + k * 128, 1);
                else wgmma128(acc, da + k * (BLOCKED_A ? 16 : 2), db + k * 128, 1);
            }
            wg_commit();
            if (k4 | st) {
                wg_wait<1>();
                if (elect) mbar_arrive(empty + 8 * ((st + 3) & 3));
            }
        }
    }
    wg_wait<0>();
    if (elect) mbar_arrive(empty + 8 * 3);
}

template <int BN>
__device__ __forceinline__ void o_item(uint32_t sb, int wgi, int wi, int lane, uint32_t full, uint32_t empty, int& it, const CUtensorMap* mout,
                                       int row0, int col0, uint32_t stgpar) {
    float acc[BN / 2];
    mainloop<BN, 64, true>(acc, sb, wgi, full, empty, it, lane == 0);
    mbar_wait(full + 104, stgpar);
    const uint32_t stg = sb + G_STG + (wgi * 4 + wi) * 4096;
    const int r = lane & 15, cu = lane >> 4;
#pragma unroll
    for (int hf = 0; hf < BN / 128; hf++) {
        if (lane == 0) asm volatile("cp.async.bulk.wait_group.read 0;" ::: "memory");
        __syncwarp();
#pragma unroll
        for (int j = 0; j < 8; j++) {
            const float* a = acc + hf * 64 + j * 8;
            stsm4(stg + (j >> 2) * 2048 + r * 128 + ((((j & 3) * 2 + cu) ^ (r & 7)) << 4),
                  pack_bf16(a[0], a[1]), pack_bf16(a[2], a[3]), pack_bf16(a[4], a[5]), pack_bf16(a[6], a[7]));
        }
        asm volatile("fence.proxy.async.shared::cta;" ::: "memory");
        __syncwarp();
        if (lane == 0) {
            tma2d_store(mout, stg, col0 + hf * 128, row0 + wgi * 64 + wi * 16);
            tma2d_store(mout, stg + 2048, col0 + hf * 128 + 64, row0 + wgi * 64 + wi * 16);
            asm volatile("cp.async.bulk.commit_group;" ::: "memory");
        }
    }
}

constexpr int S4_KD = 32768;
constexpr int S4_CH = 2 * G_STAGE;
constexpr int S4_HALF = 2304;
constexpr int S4_WD = 2 * S4_HALF;
constexpr int S4_STRIDE = S4_WD + 2304 + 16;
__device__ __forceinline__ uint32_t addz(uint32_t x, uint32_t z) { uint32_t r; asm volatile("add.u32 %0, %1, %2;" : "=r"(r) : "r"(x), "r"(z)); return r; }
__device__ __forceinline__ uint32_t lds16(uint32_t a) { uint32_t v; asm volatile("ld.shared.u16 %0, [%1];" : "=r"(v) : "r"(a) : "memory"); return v; }
__device__ __forceinline__ uint32_t ldsu(uint32_t a) { return __float_as_uint(lds32(a)); }

template <int E0, int NE, int KP>
__device__ __forceinline__ void s4_windows(float (&acc)[8][2][4], uint32_t ut, uint32_t kd, int rho, int w, int lane, uint32_t z) {
    const int gt = (lane >> 2) - 2 * (lane & 3), p0 = rho == 16 ? -3 : -2, c = (lane >> 3) + p0;
    uint32_t band[2][4], tw[2 * NE + 1], ta[NE][4];
    {
        uint32_t f[5];
#pragma unroll
        for (int m = 0; m < 5; m++) {
            const int d = 8 * (p0 + m - 1) - gt + rho;
            f[m] = (abs(d) <= w ? 0x3F80u : 0u) | (abs(d + 1) <= w ? 0x3F800000u : 0u);
        }
#pragma unroll
        for (int j = 0; j < 2; j++) { band[j][0] = f[2 * j + 1]; band[j][1] = addz(f[2 * j], z); band[j][2] = f[2 * j + 2]; band[j][3] = addz(f[2 * j + 1], z); }
    }
#pragma unroll
    for (int m = 0; m < 2 * NE + 1; m++) {
        const int q = 8 * (2 * E0 - 1 + m) + gt;
        const uint32_t lo = lds16(kd + q * KP), hi = lds16(kd + (q - 1) * KP);
        tw[m] = ((unsigned)(q - 16 * E0) < 16 * E0 ? lo : 0u) | ((unsigned)(q - 1 - 16 * E0) < 16 * E0 ? hi << 16 : 0u);
    }
#pragma unroll
    for (int e = 0; e < NE; e++) { ta[e][0] = tw[2 * e + 1]; ta[e][1] = tw[2 * e + 2]; ta[e][2] = addz(tw[2 * e], z); ta[e][3] = addz(tw[2 * e + 1], z); }
    const uint32_t ua = ut + (c & 1) * S4_HALF + (16 + (lane & 7) + (c >> 1)) * 16;
#pragma unroll
    for (int J = 0; J < 8 - E0; J++) {
        uint32_t u0[4], u1[4];
        ldsm4(u0, ua + J * 256); ldsm4(u1, ua + J * 256 + 128);
        float s0[4], s1[4];
        mma16z(s0, band[0], u0[0], u0[1]); mma16z(s1, band[0], u1[0], u1[1]);
        mma16(s0, band[1], u0[2], u0[3]); mma16(s1, band[1], u1[2], u1[3]);
        const uint32_t b00 = pack_bf16(s0[0], s0[1]), b01 = pack_bf16(s1[0], s1[1]), b10 = pack_bf16(s0[2], s0[3]), b11 = pack_bf16(s1[2], s1[3]);
#pragma unroll
        for (int e = 0; e < NE; e++)
            if (J + E0 + e < 8) { mma16(acc[J + E0 + e][0], ta[e], b00, b01); mma16(acc[J + E0 + e][1], ta[e], b10, b11); }
    }
}
template <int D0, int D1>
__device__ __forceinline__ void s4_dense(float (&acc)[8][2][4], uint32_t ua, const uint32_t (&b0)[4], const uint32_t (&b1)[4]) {
#pragma unroll
    for (int J = 0; J < 8 - D0; J++) {
        uint32_t a[4];
        ldsm4(a, ua + J * 256);
        mma16(acc[J + D0][0], a, b0[0], b0[1]); mma16(acc[J + D0][1], a, b0[2], b0[3]);
        if (J + D1 < 8) { mma16(acc[J + D1][0], a, b1[0], b1[1]); mma16(acc[J + D1][1], a, b1[2], b1[3]); }
    }
}
__device__ __forceinline__ void s4_words(uint32_t (&b)[4], uint32_t wd) {
    asm volatile("ld.shared.u32 %0, [%4]; ld.shared.u32 %1, [%4+-32]; ld.shared.u32 %2, [%4+32]; ld.volatile.shared.u32 %3, [%4];"
        : "=r"(b[0]), "=r"(b[1]), "=r"(b[2]), "=r"(b[3]) : "r"(wd) : "memory");
}

__device__ __forceinline__ void s4_item(uint32_t sb, int cw, int lane, int item, const bf16* __restrict__ dsk, uint32_t empty, const CUtensorMap* my, uint32_t stgpar) {
    const int gt = (lane >> 2) - 2 * (lane & 3);
    const uint32_t ch = sb + S4_CH + cw * S4_STRIDE, kd = sb + S4_KD + cw * 1536;
    const __nv_bfloat162 dk = __bfloat162bfloat162(dsk[item * 8 + cw]);
    ST(item, cw, 0);
    asm volatile("st.shared.v4.u32 [%0], {%1,%1,%1,%1};" ::"r"(ch + (lane >> 4) * S4_HALF + (lane & 15) * 16), "r"(0) : "memory");
    const uint32_t tch = sb + S4_CH + (lane & 7) * S4_STRIDE + ((lane >> 3) & 1) * S4_HALF + (16 + 16 * cw + (lane >> 4)) * 16;
#pragma unroll
    for (int i = 0; i < 8; i++) {
        uint32_t x[4];
        ldsm4t(x, sb + cw * 4096 + i * 512 + lane * 16);
        stsm4(tch + i * 32, x[0], x[1], x[2], x[3]);
    }
#pragma unroll 3
    for (int x0 = lane * 2 - 16; x0 < 560; x0 += 64) {
        uint32_t k[3];
#pragma unroll
        for (int j = 0; j < 3; j++) {
            const int x = x0 + j - 1, idx = x < 256 ? max(x, 0) : min(128 + ((x + ((x >> 1) & 1)) >> 1), 384);
            k[j] = lds16(kd + idx * 2);
            if ((unsigned)x > 514u) k[j] = 0;
        }
        asm volatile("st.shared.v2.u32 [%0], {%1,%2};" ::"r"(ch + S4_WD + 64 + x0 * 4), "r"(k[1] | (k[0] << 16)), "r"(k[2] | (k[1] << 16)) : "memory");
    }
    const uint32_t k1024 = lds16(kd + 1024);
    bar_sync(2, 256);
    ST(item, cw, 1);
    const uint32_t z = ldsu(ch);
    float acc[8][2][4];
#pragma unroll
    for (int j = 0; j < 16; j++) acc[j >> 1][j & 1][0] = acc[j >> 1][j & 1][1] = acc[j >> 1][j & 1][2] = acc[j >> 1][j & 1][3] = 0.f;
#pragma unroll 1
    for (int r = 1; r <= 4; r++) s4_windows<2, 3, 8>(acc, ch, kd + 512 + 2 * r, 4 * r, 2 - (r & 1), lane, z);
    ST(item, cw, 2);
#pragma unroll 1
    for (int r = 1; r <= 2; r++) s4_windows<4, 4, 4>(acc, ch, kd + 768 + 2 * r, 8 * r, 2 + r, lane, z);
    ST(item, cw, 3);
    const uint32_t ua = ch + (lane >> 4) * S4_HALF + (16 + (lane & 15)) * 16, wd = ch + S4_WD + 64 + gt * 4;
#pragma unroll 1
    for (int q = 0; q < 2; q++) {
        uint32_t b0[4], b1[4];
        s4_words(b0, wd + (q + 32) * 64);
#pragma unroll
        for (int j = 0; j < 4; j++) {
            const int x = 16 * q + gt + (j == 1 ? -8 : j == 2 ? 8 : 0) - 3;
            b1[j] = addz(((unsigned)x < 2u ? k1024 : 0u) | ((unsigned)(x - 1) < 2u ? k1024 << 16 : 0u), z);
        }
        s4_dense<2, 4>(acc, ua - q * 16, b0, b1);
    }
    {
        uint32_t b0[4], b1[4], c0[4], c1[4];
        s4_words(b0, wd); s4_words(b1, wd + 1024);
#pragma unroll 1
        for (int q = 0; q < 16; q += 2) {
            s4_words(c0, wd + q * 64 + 64); s4_words(c1, wd + q * 64 + 64 + 1024);
            s4_dense<0, 1>(acc, ua - q * 16, b0, b1);
            s4_words(b0, wd + q * 64 + 128); s4_words(b1, wd + q * 64 + 128 + 1024);
            s4_dense<0, 1>(acc, ua - q * 16 - 16, c0, c1);
            if (q == S4REL && lane == 0) { mbar_arrive(empty); mbar_arrive(empty + 8); }
        }
    }
    ST(item, cw, 4);
    mbar_wait(empty + 72, stgpar);
    if (lane == 0) asm volatile("cp.async.bulk.wait_group.read 0;" ::: "memory");
    __syncwarp();
#pragma unroll
    for (int I = 0; I < 8; I++) {
        uint32_t u[4];
        ldsm4(u, ua + I * 256);
#pragma unroll
        for (int j = 0; j < 4; j++) {
            const uint32_t y = pack_bf16(acc[I][j >> 1][2 * (j & 1)], acc[I][j >> 1][2 * (j & 1) + 1]);
            const __nv_bfloat162 r = __hadd2_rn(*(const __nv_bfloat162*)&y, __hmul2_rn(*(const __nv_bfloat162*)&u[j], dk));
            u[j] = *(const uint32_t*)&r;
        }
        stsm4(ua + I * 256, u[0], u[1], u[2], u[3]);
    }
    bar_sync(2, 256);
#pragma unroll
    for (int i = 0; i < 8; i++) {
        uint32_t y[4];
        ldsm4t(y, tch + i * 32);
        stsm4(sb + G_STG + cw * 4096 + i * 512 + lane * 16, y[0], y[1], y[2], y[3]);
    }
    asm volatile("fence.proxy.async.shared::cta;" ::: "memory");
    __syncwarp();
    if (lane == 0) {
        mbar_arrive(empty + 16); mbar_arrive(empty + 24);
        tma2d_store(my, sb + G_STG + cw * 4096, DM + item * 8, cw * 256);
        asm volatile("cp.async.bulk.commit_group;" ::: "memory");
    }
    ST(item, cw, 5);
}

__global__ void __launch_bounds__(384, 1)
worker_kernel(const __grid_constant__ CUtensorMap mx, const __grid_constant__ CUtensorMap mq, const __grid_constant__ CUtensorMap mk,
              const __grid_constant__ CUtensorMap mv, const __grid_constant__ CUtensorMap mo,
              const __grid_constant__ CUtensorMap mout, const __grid_constant__ CUtensorMap mu, const __grid_constant__ CUtensorMap my,
              const __grid_constant__ CUtensorMap mkx, const __grid_constant__ CUtensorMap mvx, const __grid_constant__ CUtensorMap mkm,
              const __grid_constant__ CUtensorMap mvm, const bf16* __restrict__ dsk) {
    extern __shared__ unsigned char smem_raw[];
    const uint32_t sb = (smem_u32(smem_raw) + 1023) & ~1023u;
    const uint32_t full = sb + G_BAR, empty = full + 32, ifull = full + 64, iempty = full + 80, islot = full + 96, stgbar = full + 104, sigbar = full + 112, sigslot = full + 120;
    const int tid = threadIdx.x, wg = tid >> 7, lane = tid & 31;
    int q0 = blockIdx.x;
    const int wide0 = q0 - ((int)gridDim.x - O_WIDE * 4);
    if (tid == 0) {
        if (q0 >= 32 && wide0 < 0) q0 = 32 + atomicAdd(g_ctr + C_NEXT, 1);
        for (int i = 0; i < G_NST; i++) { mbar_init(full + 8 * i, 1); mbar_init(empty + 8 * i, 8); }
        for (int i = 0; i < 2; i++) { mbar_init(ifull + 8 * i, 1); mbar_init(iempty + 8 * i, 8); }
        mbar_init(sigbar, 8); mbar_init(stgbar, 1);
        asm volatile("fence.proxy.async;" ::: "memory");
    }
    __syncthreads();
    if (wg == 0) {
        reg_dec<40>();
        if (tid >= 32 && tid < 64) {
            for (int n = 0;; n++) {
                mbar_wait_long(sigbar, n & 1);
                int item; asm volatile("ld.shared.u32 %0, [%1];" : "=r"(item) : "r"(sigslot + 4 * (n & 1)) : "memory");
                const int type = item >> 16, b = (item >> 8) & 255, i = item & 255;
                if (type == IT_END) break;
                if (type == IT_QA) {
                    if (lane == 0) {
                        for (int j = 0; j < 8; j++) {
                            const uint32_t src = sb + (j >= 4 ? G_STG + (j & 1) * 16384 : 3 * G_STAGE + (j & 1) * 20480) + ((j >> 1) & 1) * 8192;
                            asm volatile("cp.async.bulk.global.shared::cta.bulk_group [%0], [%1], 8192;"
                                ::"l"(g_ox + (size_t)(b * 64 + i * 4 + ((j >> 1) ^ 2)) * 8192 + (j & 1) * 4096), "r"(src) : "memory");
                            if ((j & 3) == 3) asm volatile("cp.async.bulk.commit_group;" ::: "memory");
                        }
                        asm volatile("cp.async.bulk.wait_group.read 1;" ::: "memory");
                        asm volatile("mbarrier.arrive.shared.b64 _, [%0], 8;" ::"r"(empty + 24) : "memory");
                        asm volatile("cp.async.bulk.wait_group 0;" ::: "memory");
                        mbar_arrive(stgbar);
                        asm volatile("fence.proxy.async;" ::: "memory");
                    }
                    __syncwarp();
                }
                __threadfence();
                if (type == IT_KV) { if (lane < 6) atomicAdd(g_kvf + ((i & 15) * 6 + lane) * 16 + b, 1); }
                else if (lane == 0) atomicAdd(g_ctr + C_QA_DONE + b, 1);
            }
        } else if (tid < 32) {
            int it = 0;
            if (!KVN) asm volatile("griddepcontrol.wait;" ::: "memory");
            for (int n = 0;; n++) {
                int item = 0;
                if (lane == 0) {
                    const int q = n == 0 ? q0 : 32 + atomicAdd(g_ctr + C_NEXT, 1);
                    item = n == 0 && wide0 >= 0 ? (IT_O << 16) | ((wide0 >> 2) << 8) | (wide0 & 3) : queue_item(q);
                }
                item = __shfl_sync(0xffffffffu, item, 0);
                if (lane == 0) {
                    mbar_wait(iempty + 8 * (n & 1), ((n >> 1) & 1) ^ 1);
                    asm volatile("st.shared.u32 [%0], %1;" ::"r"(islot + 4 * (n & 1)), "r"(item) : "memory");
                    mbar_arrive(ifull + 8 * (n & 1));
                    const int type = item >> 16, b = (item >> 8) & 255, i = item & 255;
                    if (type == IT_QA || type == IT_KV) {
                        const CUtensorMap* mw = type == IT_QA ? &mq : i < 16 ? &mk : &mv;
                        bool ready = false;
                        for (int kb = 0; kb < 16; kb++, it++) {
                            const int st = it & 3;
                            mbar_wait(empty + 8 * st, ((it >> 2) & 1) ^ 1);
                            mbar_expect(full + 8 * st, G_STAGE);
                            const uint32_t a = sb + st * G_STAGE;
                            tma2d(a, &mx, kb * 64, b * 128, full + 8 * st);
                            tma3d(a + 16384, mw, 0, kb * 64, (i & 15) * 4, full + 8 * st);
                            tma3d(a + 32768, mw, 0, kb * 64, (i & 15) * 4 + 2, full + 8 * st);
                            if (type == IT_QA && kb == 3) ready = ld_acq(g_ctr + C_CHAIN + b) >= 96;
                            if (type == IT_QA && kb >= 3 && kb < 11) {
                                const size_t sh = (b * 4 + ((kb - 3) & 3)) * NH + i * 2;
                                asm volatile("cp.async.bulk.prefetch.L2.global [%0], 16384;" ::"l"((kb >= 7 ? g_vx : g_kx) + sh * 4096) : "memory");
                                if (ready) asm volatile("cp.async.bulk.prefetch.L2.global [%0], 4096;" ::"l"((kb >= 7 ? g_vm : g_km) + sh * 1024) : "memory");
                            }
                        }
                    }
                    if (type == IT_QA) {
                        wait_ctr(g_ctr + C_CHAIN + b, 96);
                        asm volatile("fence.proxy.async;" ::: "memory");
                        for (int st = 0; st < 4; st++, it++) {
                            mbar_wait(empty + 8 * st, ((it >> 2) & 1) ^ 1);
                            mbar_expect(full + 8 * st, 4 * 10240);
                            for (int g2 = 0; g2 < 2; g2++) {
                                tma3d(sb + st * G_STAGE + g2 * 20480, st < 2 ? &mkx : &mvx, 0, b * 4 + g2 * 2, (i * 2 + (st & 1)) * 16, full + 8 * st);
                                tma3d(sb + st * G_STAGE + g2 * 20480 + 16384, st < 2 ? &mkm : &mvm, 0, b * 4 + g2 * 2, (i * 2 + (st & 1)) * 16, full + 8 * st);
                            }
                        }
                    } else if (type == IT_O) {
                        const bool wide = b < O_WIDE;
                        wait_ctr(g_ctr + C_QA_DONE + b, 16);
                        asm volatile("fence.proxy.async;" ::: "memory");
                        for (int kb = 0; kb < 64; kb++, it++) {
                            const int st = it & 3;
                            mbar_wait(empty + 8 * st, ((it >> 2) & 1) ^ 1);
                            mbar_expect(full + 8 * st, wide ? G_STAGE : 32768);
                            const uint32_t a = sb + st * G_STAGE;
                            bulk_load(a, g_ox + (size_t)(b * 64 + kb) * 8192, 16384, full + 8 * st);
                            tma3d(a + 16384, &mo, 0, kb * 64, wide ? i * 4 : i * 2, full + 8 * st);
                            if (wide) tma3d(a + 32768, &mo, 0, kb * 64, i * 4 + 2, full + 8 * st);
                        }
                    } else if (type == IT_S4) {
                        wait_ctr(g_ctr + C_CHAIN, 96);
                        asm volatile("fence.proxy.async;" ::: "memory");
                        mbar_wait(empty, ((it >> 2) & 1) ^ 1);
                        mbar_expect(full, 32768 + 12288);
                        bulk_load(sb + S4_KD, g_kd + i * 8 * 768, 12288, full);
                        for (int j = 0; j < 8; j++) tma2d(sb + j * 4096, &mu, i * 8, j * 256, full);
                        for (int st = 1; st < 4; st++) { mbar_wait(empty + 8 * st, ((it >> 2) & 1) ^ 1); mbar_arrive(full + 8 * st); }
                        it += 4;
                        mbar_wait_long(empty, ((it >> 2) & 1) ^ 1);
                    }
                }
                __syncwarp();
                if (item >> 16 == IT_END) break;
            }
            asm volatile("griddepcontrol.wait;" ::: "memory");
        }
    } else {
        reg_inc<232>();
        const int wu = __shfl_sync(0xffffffffu, tid >> 5, 0);
        const int wgi = (wu >> 2) - 1, wi = wu & 3;
        int it = 0, nqa = 0, nsig = 0, n = 0, item;
        auto next_item = [&]() {
            mbar_wait_long(ifull + 8 * (n & 1), (n >> 1) & 1);
            asm volatile("ld.shared.u32 %0, [%1];" : "=r"(item) : "r"(islot + 4 * (n & 1)) : "memory");
            __syncwarp();
            if (lane == 0) mbar_arrive(iempty + 8 * (n & 1));
        };
        auto signal = [&](int what) {
            if (tid == 128) asm volatile("st.shared.u32 [%0], %1;" ::"r"(sigslot + 4 * (nsig & 1)), "r"(what) : "memory");
            __syncwarp();
            if (lane == 0) mbar_arrive(sigbar);
            nsig++;
        };
        next_item();
        if (item >> 16 == IT_KV) {
            float acc[128];
            uint32_t pk[64];
            uint32_t* dst = nullptr;
            int prev = 0;
            do {
                WLOG(0);
#pragma unroll
                for (int kb = 0; kb < 16; kb++, it++) {
                    const int st = kb & 3;
                    mbar_wait(full + 8 * st, (it >> 2) & 1);
                    const uint64_t da = mkdesc(sb + st * G_STAGE + wgi * 8192, 16, 1024, 1);
                    const uint64_t db = mkdesc(sb + st * G_STAGE + 16384, 8192, 1024, 1);
                    wg_fence();
#pragma unroll
                    for (int k = 0; k < 4; k++) wgmma256(acc, da + k * 2, db + k * 128, kb | k);
                    wg_commit();
                    if (kb < KVS && dst) {
#pragma unroll
                        for (int j = kb * (64 / KVS); j < (kb + 1) * (64 / KVS); j++) st_out(dst + (j >> 1) * 128 + (j & 1) * 32, pk[j]);
                        if (kb == KVS - 1) signal(prev);
                    }
                    if (kb > 0) {
                        wg_wait<1>();
                        if (lane == 0) mbar_arrive(empty + 8 * ((kb - 1) & 3));
                    }
                }
                wg_wait<0>();
                if (lane == 0) mbar_arrive(empty + 8 * 3);
#pragma unroll
                for (int j = 0; j < 64; j++) pk[j] = pack_bf16(acc[2 * j], acc[2 * j + 1]);
                const int row = ((item >> 8) & 255) * 128 + wgi * 64 + wi * 16, nt = item & 255;
                dst = (uint32_t*)(nt < 16 ? g_kx : g_vx) + (size_t)((row >> 5) * 512 + (nt & 15) * 32) * 128 + (row & 31) * 4 + lane;
                prev = item;
                if (n == 0) {
#pragma unroll
                    for (int j = 0; j < 64; j++) dst[(j >> 1) * 128 + (j & 1) * 32] = pk[j];
                    signal(prev);
                    dst = nullptr;
                }
                WLOG(1);
                n++;
                next_item();
            } while (item >> 16 == IT_KV);
            if (dst) {
#pragma unroll
                for (int j = 0; j < 64; j++) dst[(j >> 1) * 128 + (j & 1) * 32] = pk[j];
                signal(prev);
            }
        }
        for (;; n++, next_item()) {
            const int type = item >> 16, b = (item >> 8) & 255, i = item & 255;
            const int lane = (tid & 31) + (item >> 24);
            WLOG(0);
            if (type == IT_QA) {
                float acc[128];
                ST(sid, cw, 0);
                ST(sid, cw, 1);
                mainloop<256, 16, false>(acc, sb, wgi, full, empty, it, lane == 0);
                ST(sid, cw, 2);
                uint32_t q0[32], q1[32];
#pragma unroll
                for (int j = 0; j < 32; j++) { q0[j] = pack_bf16(acc[2 * j], acc[2 * j + 1]); q1[j] = pack_bf16(acc[64 + 2 * j], acc[65 + 2 * j]); }
                const uint32_t par = (it >> 2) & 1, so = sb + wgi * 20480;
                float sx0[32] = {}, sm0[8] = {}, sx1[32] = {}, sm1[8] = {};
                uint32_t p0[20], p1[20];
                if (lane == 0) asm volatile("cp.async.bulk.wait_group.read 0;" ::: "memory");
                mbar_wait(stgbar, (nqa++ & 1) ^ 1);
                bar_sync(3 + wgi, 128);
                mbar_wait_long(full, par);
                ST(sid, cw, 3);
                attn_scores(sx0, sm0, q0, so);
                ST(sid, cw, 7);
                mbar_wait(full + 8, par);
                attn_scores(sx1, sm1, q1, so + G_STAGE);
                float o0[64] = {}, o1[64] = {};
                if (ATT2) {
                    ST(sid, cw, 8);
                    wg_wait<0>();
                    ST(sid, cw, 9);
                    if (lane == 0) { mbar_arrive(empty); mbar_arrive(empty + 8); }
                    attn_softmax(p0, sx0, sm0, wi, lane);
                    attn_softmax(p1, sx1, sm1, wi, lane);
                    ST(sid, cw, 10);
                    mbar_wait(full + 16, par);
                    ST(sid, cw, 11);
                    attn_pv(o0, p0, so + 2 * G_STAGE);
                    ST(sid, cw, 4);
                } else {
                    wg_wait<1>();
                    if (lane == 0) mbar_arrive(empty);
                    attn_softmax(p0, sx0, sm0, wi, lane);
                    mbar_wait(full + 16, par);
                    attn_pv(o0, p0, so + 2 * G_STAGE);
                    wg_wait<1>();
                    if (lane == 0) mbar_arrive(empty + 8);
                    ST(sid, cw, 4);
                    attn_softmax(p1, sx1, sm1, wi, lane);
                }
                mbar_wait(full + 24, par);
                attn_pv(o1, p1, so + 3 * G_STAGE);
                wg_wait<1>();
                if (lane == 0) mbar_arrive(empty + 16);
                ST(sid, cw, 5);
                const uint32_t da = (wi * 2 + ((lane >> 3) & 1)) * 1024 + (lane >> 4) * 128 + (lane & 7) * 16;
                attn_stage(o0, sb + G_STG + wgi * 16384 + da);
                wg_wait<0>();
                bar_sync(3 + wgi, 128);
                attn_stage(o1, so + 3 * G_STAGE + da);
                asm volatile("fence.proxy.async.shared::cta;" ::: "memory");
                ST(sid, cw, 6);
                signal(item);
                it += 4;
            } else if (type == IT_O) {
                mbar_wait_long(full, (it >> 2) & 1);
                if (b < O_WIDE) o_item<256>(sb, wgi, wi, lane, full, empty, it, &mout, b * 128, i * 256, (nqa & 1) ^ 1);
                else o_item<128>(sb, wgi, wi, lane, full, empty, it, &mout, b * 128, i * 128, (nqa & 1) ^ 1);
            } else if (type == IT_S4) {
                mbar_wait_long(full, (it >> 2) & 1);
                mbar_wait(full + 24, (it >> 2) & 1);
                s4_item(sb, wgi * 4 + wi, lane, i, dsk, empty, &my, (nqa & 1) ^ 1);
                it += 4;
            } else break;
            WLOG(1);
        }
        bar_sync(2, 256);
        signal(item);
        if (lane == 0) asm volatile("cp.async.bulk.wait_group 0;" ::: "memory");
    }
}

typedef CUresult (*EncodeFn)(CUtensorMap*, CUtensorMapDataType, cuuint32_t, void*, const cuuint64_t*, const cuuint64_t*, const cuuint32_t*,
                             const cuuint32_t*, CUtensorMapInterleave, CUtensorMapSwizzle, CUtensorMapL2promotion, CUtensorMapFloatOOBfill);
static EncodeFn get_encode() {
    void* fn = nullptr; cudaDriverEntryPointQueryResult st;
    cudaGetDriverEntryPoint("cuTensorMapEncodeTiled", &fn, cudaEnableDefault, &st);
    return (EncodeFn)fn;
}
static void map_act(EncodeFn enc, CUtensorMap* m, const void* p, int rows, int cols, int boxr) {
    cuuint64_t dim[2] = {(cuuint64_t)cols, (cuuint64_t)rows}, str[1] = {(cuuint64_t)cols * 2};
    cuuint32_t box[2] = {64, (cuuint32_t)boxr}, es[2] = {1, 1};
    enc(m, CU_TENSOR_MAP_DATA_TYPE_BFLOAT16, 2, (void*)p, dim, str, box, es, CU_TENSOR_MAP_INTERLEAVE_NONE, CU_TENSOR_MAP_SWIZZLE_128B,
        CU_TENSOR_MAP_L2_PROMOTION_L2_128B, CU_TENSOR_MAP_FLOAT_OOB_FILL_NONE);
}
static void map_w(EncodeFn enc, CUtensorMap* m, const void* p, int k, int n) {
    cuuint64_t dim[3] = {64, (cuuint64_t)k, (cuuint64_t)n / 64}, str[2] = {(cuuint64_t)n * 2, 128};
    cuuint32_t box[3] = {64, 64, 2}, es[3] = {1, 1, 1};
    enc(m, CU_TENSOR_MAP_DATA_TYPE_BFLOAT16, 3, (void*)p, dim, str, box, es, CU_TENSOR_MAP_INTERLEAVE_NONE, CU_TENSOR_MAP_SWIZZLE_128B,
        CU_TENSOR_MAP_L2_PROMOTION_L2_256B, CU_TENSOR_MAP_FLOAT_OOB_FILL_NONE);
}

static void map_kv(EncodeFn enc, CUtensorMap* m, void* p, int n) {
    cuuint64_t dim[3] = {(cuuint64_t)n, NSEG, 512}, str[2] = {(cuuint64_t)n * 1024, (cuuint64_t)n * 2};
    cuuint32_t box[3] = {(cuuint32_t)n, 2, 16}, es[3] = {1, 1, 1};
    enc(m, CU_TENSOR_MAP_DATA_TYPE_BFLOAT16, 3, p, dim, str, box, es, CU_TENSOR_MAP_INTERLEAVE_NONE, CU_TENSOR_MAP_SWIZZLE_NONE,
        CU_TENSOR_MAP_L2_PROMOTION_NONE, CU_TENSOR_MAP_FLOAT_OOB_FILL_NONE);
}
static void map_box(EncodeFn enc, CUtensorMap* m, const void* p, int rows, int ld, int boxc, int boxr, CUtensorMapSwizzle sw) {
    cuuint64_t dim[2] = {(cuuint64_t)ld, (cuuint64_t)rows}, str[1] = {(cuuint64_t)ld * 2};
    cuuint32_t box[2] = {(cuuint32_t)boxc, (cuuint32_t)boxr}, es[2] = {1, 1};
    enc(m, CU_TENSOR_MAP_DATA_TYPE_BFLOAT16, 2, (void*)p, dim, str, box, es, CU_TENSOR_MAP_INTERLEAVE_NONE, sw,
        CU_TENSOR_MAP_L2_PROMOTION_NONE, CU_TENSOR_MAP_FLOAT_OOB_FILL_NONE);
}

extern "C" void kernel_launch(void* const* d_in, const int* in_sizes, int n_in, void* d_out, int out_size) {
    const bf16* x = (const bf16*)d_in[0];
    const bf16* mem0 = (const bf16*)d_in[1];
    const bf16 *Wq = (const bf16*)d_in[2], *Wk = (const bf16*)d_in[3], *Wv = (const bf16*)d_in[4], *Wo = (const bf16*)d_in[5];
    static EncodeFn enc = nullptr;
    static int nsm = 0;
    static void* kv[4];
    if (!enc) {
        enc = get_encode();
        cudaGetSymbolAddress(&kv[0], g_kx); cudaGetSymbolAddress(&kv[1], g_vx); cudaGetSymbolAddress(&kv[2], g_km); cudaGetSymbolAddress(&kv[3], g_vm);
        cudaDeviceGetAttribute(&nsm, cudaDevAttrMultiProcessorCount, 0);
        cudaFuncSetAttribute(chain_kernel, cudaFuncAttributeMaxDynamicSharedMemorySize, CH_SMEM);
        cudaFuncSetAttribute(worker_kernel, cudaFuncAttributeMaxDynamicSharedMemorySize, G_SMEM);
    }
    CUtensorMap mx, mq, mk, mv, mo, mout, mu, my;
    map_act(enc, &mx, x, S_LEN, DM, 128);
    map_w(enc, &mq, Wq, DM, HD); map_w(enc, &mk, Wk, DM, HD); map_w(enc, &mv, Wv, DM, HD); map_w(enc, &mo, Wo, HD, DM);
    map_box(enc, &mout, d_out, S_LEN, 2 * DM, 64, 16, CU_TENSOR_MAP_SWIZZLE_128B);
    map_box(enc, &mu, d_in[7], S_LEN, DM, 8, 256, CU_TENSOR_MAP_SWIZZLE_NONE);
    map_box(enc, &my, d_out, S_LEN, 2 * DM, 8, 256, CU_TENSOR_MAP_SWIZZLE_NONE);
    CUtensorMap mkx, mvx, mkm, mvm;
    map_kv(enc, &mkx, kv[0], 256); map_kv(enc, &mvx, kv[1], 256); map_kv(enc, &mkm, kv[2], 64); map_kv(enc, &mvm, kv[3], 64);
    CUtensorMap cq, ck, cv, co;
    map_box(enc, &cq, Wq, DM, HD, 32, 32, CU_TENSOR_MAP_SWIZZLE_64B); map_box(enc, &ck, Wk, DM, HD, 32, 32, CU_TENSOR_MAP_SWIZZLE_64B);
    map_box(enc, &cv, Wv, DM, HD, 32, 32, CU_TENSOR_MAP_SWIZZLE_64B); map_box(enc, &co, Wo, HD, DM, 32, 16, CU_TENSOR_MAP_SWIZZLE_64B);
    S4Params P = {(const bf16*)d_in[8], (const bf16*)d_in[9], (const bf16*)d_in[10], (const bf16*)d_in[11],
                  (const bf16*)d_in[12], (const bf16*)d_in[13], (const bf16*)d_in[14], (const bf16*)d_in[15]};
    int aware = 1;
    cudaLaunchAttribute at[1];
    at[0].id = cudaLaunchAttributeProgrammaticStreamSerialization;
    at[0].val.programmaticStreamSerializationAllowed = 1;
    cudaLaunchConfig_t cfg = {};
    cfg.stream = cudaStreamPerThread;
    cfg.gridDim = dim3(96); cfg.blockDim = dim3(CH_THREADS); cfg.dynamicSmemBytes = CH_SMEM;
    cudaLaunchKernelEx(&cfg, chain_kernel, cq, ck, cv, co, Wq, Wk, Wv, mem0, P, aware);
    cfg.attrs = at; cfg.numAttrs = 1;
    cfg.gridDim = dim3(nsm); cfg.blockDim = dim3(384); cfg.dynamicSmemBytes = G_SMEM;
    cudaLaunchKernelEx(&cfg, worker_kernel, mx, mq, mk, mv, mo, mout, mu, my, mkx, mvx, mkm, mvm, P.dsk);
}
```

```cpp
#include <cuda.h>
#include <cuda_runtime.h>
#include <cuda_bf16.h>
#include <stdint.h>
#include <stdio.h>
#include <string.h>

typedef __nv_bfloat16 bf16;

constexpr int S_LEN = 2048, DM = 1024, NH = 32, DH = 128, HD = 4096, NSEG = 64;
constexpr uint32_t SENT = 0xFFFFFFFFu;
constexpr int SPIN_LIMIT = 1 << 18;
#define REALL 0

__device__ __align__(1024) bf16 g_kx[S_LEN * HD];
__device__ __align__(1024) bf16 g_vx[S_LEN * HD];
__device__ __align__(1024) bf16 g_ox[S_LEN * HD];
__device__ __align__(1024) bf16 g_km[NSEG * NH * 8 * DH];
__device__ __align__(1024) bf16 g_vm[NSEG * NH * 8 * DH];
__device__ __align__(1024) bf16 g_kd[DM * 768 + 8192];
__device__ __align__(1024) char g_ring[2 << 20];
__device__ int g_kvf[96 * 16];
constexpr int C_NEXT = 0, C_CHAIN = 32, C_QA_DONE = 64, N_CTR = 96;
__device__ int g_ctr[N_CTR];

__device__ __forceinline__ uint32_t smem_u32(const void* p) { return (uint32_t)__cvta_generic_to_shared(p); }
__device__ __forceinline__ uint32_t clk() { uint32_t c; asm volatile("mov.u32 %0, %%clock;" : "=r"(c)::"memory"); return c; }
__device__ __forceinline__ uint32_t pack_bf16(float lo, float hi) {
    uint32_t r; asm("cvt.rn.bf16x2.f32 %0, %1, %2;" : "=r"(r) : "f"(hi), "f"(lo)); return r;
}
__device__ __forceinline__ uint32_t movm(uint32_t a) {
    uint32_t d; asm volatile("movmatrix.sync.aligned.m8n8.trans.b16 %0, %1;" : "=r"(d) : "r"(a)); return d;
}
__device__ __forceinline__ void mma16(float (&d)[4], const uint32_t (&a)[4], uint32_t b0, uint32_t b1) {
    asm volatile("mma.sync.aligned.m16n8k16.row.col.f32.bf16.bf16.f32 {%0,%1,%2,%3}, {%4,%5,%6,%7}, {%8,%9}, {%0,%1,%2,%3};"
        : "+f"(d[0]), "+f"(d[1]), "+f"(d[2]), "+f"(d[3]) : "r"(a[0]), "r"(a[1]), "r"(a[2]), "r"(a[3]), "r"(b0), "r"(b1));
}
__device__ __forceinline__ void mma16z(float (&d)[4], const uint32_t (&a)[4], uint32_t b0, uint32_t b1) {
    asm volatile("mma.sync.aligned.m16n8k16.row.col.f32.bf16.bf16.f32 {%0,%1,%2,%3}, {%4,%5,%6,%7}, {%8,%9}, {%10,%10,%10,%10};"
        : "=f"(d[0]), "=f"(d[1]), "=f"(d[2]), "=f"(d[3]) : "r"(a[0]), "r"(a[1]), "r"(a[2]), "r"(a[3]), "r"(b0), "r"(b1), "f"(0.f));
}
__device__ __forceinline__ void mma8z(float (&d)[4], uint32_t a0, uint32_t a1, uint32_t b0) {
    asm volatile("mma.sync.aligned.m16n8k8.row.col.f32.bf16.bf16.f32 {%0,%1,%2,%3}, {%4,%5}, {%6}, {%7,%7,%7,%7};"
        : "=f"(d[0]), "=f"(d[1]), "=f"(d[2]), "=f"(d[3]) : "r"(a0), "r"(a1), "r"(b0), "f"(0.f));
}
__device__ __forceinline__ void ldsm4t(uint32_t (&r)[4], uint32_t addr) {
    asm volatile("ldmatrix.sync.aligned.m8n8.x4.trans.shared.b16 {%0,%1,%2,%3}, [%4];"
        : "=r"(r[0]), "=r"(r[1]), "=r"(r[2]), "=r"(r[3]) : "r"(addr) : "memory");
}
__device__ __forceinline__ void ldsm4(uint32_t (&r)[4], uint32_t addr) {
    asm volatile("ldmatrix.sync.aligned.m8n8.x4.shared.b16 {%0,%1,%2,%3}, [%4];"
        : "=r"(r[0]), "=r"(r[1]), "=r"(r[2]), "=r"(r[3]) : "r"(addr) : "memory");
}
__device__ __forceinline__ float lds32(uint32_t a) {
    float v; asm volatile("ld.shared.f32 %0, [%1];" : "=f"(v) : "r"(a) : "memory"); return v;
}
__device__ __forceinline__ void st_async1(uint32_t dst, float v, uint32_t bar) {
    asm volatile("st.async.shared::cluster.mbarrier::complete_tx::bytes.f32 [%0], %1, [%2];" ::"r"(dst), "f"(v), "r"(bar) : "memory");
}
__device__ __forceinline__ void st_async2(uint32_t dst, float x, float y, uint32_t bar) {
    asm volatile("st.async.shared::cluster.mbarrier::complete_tx::bytes.v2.f32 [%0], {%1,%2}, [%3];" ::"r"(dst), "f"(x), "f"(y), "r"(bar) : "memory");
}
__device__ __forceinline__ void mma8(float (&d)[4], uint32_t a0, uint32_t a1, uint32_t b0) {
    asm volatile("mma.sync.aligned.m16n8k8.row.col.f32.bf16.bf16.f32 {%0,%1,%2,%3}, {%4,%5}, {%6}, {%0,%1,%2,%3};"
        : "+f"(d[0]), "+f"(d[1]), "+f"(d[2]), "+f"(d[3]) : "r"(a0), "r"(a1), "r"(b0));
}
__device__ __forceinline__ void cp16(uint32_t dst, const void* src) {
    asm volatile("cp.async.cg.shared.global [%0], [%1], 16;" ::"r"(dst), "l"(src) : "memory");
}
__device__ __forceinline__ void sts128(uint32_t a, const float (&v)[4]) {
    asm volatile("st.shared.v4.f32 [%0], {%1,%2,%3,%4};" ::"r"(a), "f"(v[0]), "f"(v[1]), "f"(v[2]), "f"(v[3]) : "memory");
}
__device__ __forceinline__ float4 lds128(uint32_t a) {
    float4 v; asm volatile("ld.shared.v4.f32 {%0,%1,%2,%3}, [%4];" : "=f"(v.x), "=f"(v.y), "=f"(v.z), "=f"(v.w) : "r"(a) : "memory"); return v;
}
__device__ __forceinline__ void sts64(uint32_t a, float x, float y) {
    asm volatile("st.shared.v2.f32 [%0], {%1,%2};" ::"r"(a), "f"(x), "f"(y) : "memory");
}
__device__ __forceinline__ float2 lds64(uint32_t a) {
    float2 v; asm volatile("ld.shared.v2.f32 {%0,%1}, [%2];" : "=f"(v.x), "=f"(v.y) : "r"(a) : "memory"); return v;
}
__device__ __forceinline__ void bar_sync(int id, int n) { asm volatile("bar.sync %0, %1;" ::"r"(id), "r"(n) : "memory"); }
__device__ __forceinline__ void bar_arrive(int id, int n) { asm volatile("bar.arrive %0, %1;" ::"r"(id), "r"(n) : "memory"); }
__device__ __forceinline__ uint32_t mapa(uint32_t a, uint32_t r) {
    uint32_t o; asm("mapa.shared::cluster.u32 %0, %1, %2;" : "=r"(o) : "r"(a), "r"(r)); return o;
}
__device__ __forceinline__ void st_async4(uint32_t dst, float4 v, uint32_t bar) {
    asm volatile("st.async.shared::cluster.mbarrier::complete_tx::bytes.v4.f32 [%0], {%1,%2,%3,%4}, [%5];"
        ::"r"(dst), "f"(v.x), "f"(v.y), "f"(v.z), "f"(v.w), "r"(bar) : "memory");
}
__device__ __forceinline__ void mbar_init(uint32_t bar, int n) { asm volatile("mbarrier.init.shared.b64 [%0], %1;" ::"r"(bar), "r"(n) : "memory"); }
__device__ __forceinline__ void mbar_expect(uint32_t bar, int bytes) {
    asm volatile("mbarrier.arrive.expect_tx.shared.b64 _, [%0], %1;" ::"r"(bar), "r"(bytes) : "memory");
}
__device__ __forceinline__ void bulk_load(uint32_t dst, const void* src, int bytes, uint32_t bar) {
    asm volatile("cp.async.bulk.shared::cluster.global.mbarrier::complete_tx::bytes [%0], [%1], %2, [%3];"
        ::"r"(dst), "l"(src), "r"(bytes), "r"(bar) : "memory");
}
__device__ __forceinline__ bool mbar_try(uint32_t bar, uint32_t par) {
    uint32_t ok;
    asm volatile("{.reg .pred p; mbarrier.try_wait.parity.shared::cta.b64 p, [%1], %2; selp.u32 %0, 1, 0, p;}"
        : "=r"(ok) : "r"(bar), "r"(par) : "memory");
    return ok;
}
__device__ __forceinline__ bool mbar_test(uint32_t bar, uint32_t par) {
    uint32_t ok;
    asm volatile("{.reg .pred p; mbarrier.test_wait.parity.shared::cta.b64 p, [%1], %2; selp.u32 %0, 1, 0, p;}"
        : "=r"(ok) : "r"(bar), "r"(par) : "memory");
    return ok;
}
__device__ __forceinline__ int ld_acq(const int* p) { int v; asm volatile("ld.acquire.gpu.global.s32 %0, [%1];" : "=r"(v) : "l"(p) : "memory"); return v; }
__device__ __forceinline__ void wait_ctr(const int* p, int n) {
    for (int it = 0; it < (1 << 20) && ld_acq(p) < n; it++) __nanosleep(64);
}
__device__ __forceinline__ void mbar_wait(uint32_t bar, uint32_t par) {
    if (!mbar_try(bar, par))
        for (int it = 0; it < SPIN_LIMIT && !mbar_try(bar, par); it++) {}
}
__device__ __forceinline__ void mbar_wait_long(uint32_t bar, uint32_t par) {
    for (int it = 0; it < (1 << 24) && !mbar_try(bar, par); it++) {}
}
__device__ __forceinline__ float4 add4(float4 a, float4 b) { return make_float4(a.x + b.x, a.y + b.y, a.z + b.z, a.w + b.w); }
__device__ __forceinline__ float ex2(float x) { float y; asm("ex2.approx.ftz.f32 %0, %1;" : "=f"(y) : "f"(x)); return y; }

__device__ __forceinline__ void wgmma256(float (&d)[128], uint64_t da, uint64_t db, int acc) {
    asm volatile("{.reg .pred p; setp.ne.b32 p, %130, 0;\n"
        "wgmma.mma_async.sync.aligned.m64n256k16.f32.bf16.bf16 {"
        "%0,%1,%2,%3,%4,%5,%6,%7,%8,%9,%10,%11,%12,%13,%14,%15,"
        "%16,%17,%18,%19,%20,%21,%22,%23,%24,%25,%26,%27,%28,%29,%30,%31,"
        "%32,%33,%34,%35,%36,%37,%38,%39,%40,%41,%42,%43,%44,%45,%46,%47,"
        "%48,%49,%50,%51,%52,%53,%54,%55,%56,%57,%58,%59,%60,%61,%62,%63,"
        "%64,%65,%66,%67,%68,%69,%70,%71,%72,%73,%74,%75,%76,%77,%78,%79,"
        "%80,%81,%82,%83,%84,%85,%86,%87,%88,%89,%90,%91,%92,%93,%94,%95,"
        "%96,%97,%98,%99,%100,%101,%102,%103,%104,%105,%106,%107,%108,%109,%110,%111,"
        "%112,%113,%114,%115,%116,%117,%118,%119,%120,%121,%122,%123,%124,%125,%126,%127"
        "}, %128, %129, p, 1, 1, 0, 1;}"
        : "+f"(d[0]), "+f"(d[1]), "+f"(d[2]), "+f"(d[3]), "+f"(d[4]), "+f"(d[5]), "+f"(d[6]), "+f"(d[7]), "+f"(d[8]), "+f"(d[9]), "+f"(d[10]), "+f"(d[11]), "+f"(d[12]), "+f"(d[13]), "+f"(d[14]), "+f"(d[15]), "+f"(d[16]), "+f"(d[17]), "+f"(d[18]), "+f"(d[19]), "+f"(d[20]), "+f"(d[21]), "+f"(d[22]), "+f"(d[23]), "+f"(d[24]), "+f"(d[25]), "+f"(d[26]), "+f"(d[27]), "+f"(d[28]), "+f"(d[29]), "+f"(d[30]), "+f"(d[31]), "+f"(d[32]), "+f"(d[33]), "+f"(d[34]), "+f"(d[35]), "+f"(d[36]), "+f"(d[37]), "+f"(d[38]), "+f"(d[39]), "+f"(d[40]), "+f"(d[41]), "+f"(d[42]), "+f"(d[43]), "+f"(d[44]), "+f"(d[45]), "+f"(d[46]), "+f"(d[47]), "+f"(d[48]), "+f"(d[49]), "+f"(d[50]), "+f"(d[51]), "+f"(d[52]), "+f"(d[53]), "+f"(d[54]), "+f"(d[55]), "+f"(d[56]), "+f"(d[57]), "+f"(d[58]), "+f"(d[59]), "+f"(d[60]), "+f"(d[61]), "+f"(d[62]), "+f"(d[63]), "+f"(d[64]), "+f"(d[65]), "+f"(d[66]), "+f"(d[67]), "+f"(d[68]), "+f"(d[69]), "+f"(d[70]), "+f"(d[71]), "+f"(d[72]), "+f"(d[73]), "+f"(d[74]), "+f"(d[75]), "+f"(d[76]), "+f"(d[77]), "+f"(d[78]), "+f"(d[79]), "+f"(d[80]), "+f"(d[81]), "+f"(d[82]), "+f"(d[83]), "+f"(d[84]), "+f"(d[85]), "+f"(d[86]), "+f"(d[87]), "+f"(d[88]), "+f"(d[89]), "+f"(d[90]), "+f"(d[91]), "+f"(d[92]), "+f"(d[93]), "+f"(d[94]), "+f"(d[95]), "+f"(d[96]), "+f"(d[97]), "+f"(d[98]), "+f"(d[99]), "+f"(d[100]), "+f"(d[101]), "+f"(d[102]), "+f"(d[103]), "+f"(d[104]), "+f"(d[105]), "+f"(d[106]), "+f"(d[107]), "+f"(d[108]), "+f"(d[109]), "+f"(d[110]), "+f"(d[111]), "+f"(d[112]), "+f"(d[113]), "+f"(d[114]), "+f"(d[115]), "+f"(d[116]), "+f"(d[117]), "+f"(d[118]), "+f"(d[119]), "+f"(d[120]), "+f"(d[121]), "+f"(d[122]), "+f"(d[123]), "+f"(d[124]), "+f"(d[125]), "+f"(d[126]), "+f"(d[127])
        : "l"(da), "l"(db), "r"(acc));
}
__device__ __forceinline__ void wgmma128(float (&d)[64], uint64_t da, uint64_t db, int acc) {
    asm volatile("{.reg .pred p; setp.ne.b32 p, %66, 0;\n"
        "wgmma.mma_async.sync.aligned.m64n128k16.f32.bf16.bf16 {"
        "%0,%1,%2,%3,%4,%5,%6,%7,%8,%9,%10,%11,%12,%13,%14,%15,"
        "%16,%17,%18,%19,%20,%21,%22,%23,%24,%25,%26,%27,%28,%29,%30,%31,"
        "%32,%33,%34,%35,%36,%37,%38,%39,%40,%41,%42,%43,%44,%45,%46,%47,"
        "%48,%49,%50,%51,%52,%53,%54,%55,%56,%57,%58,%59,%60,%61,%62,%63"
        "}, %64, %65, p, 1, 1, 0, 1;}"
        : "+f"(d[0]), "+f"(d[1]), "+f"(d[2]), "+f"(d[3]), "+f"(d[4]), "+f"(d[5]), "+f"(d[6]), "+f"(d[7]), "+f"(d[8]), "+f"(d[9]), "+f"(d[10]), "+f"(d[11]), "+f"(d[12]), "+f"(d[13]), "+f"(d[14]), "+f"(d[15]), "+f"(d[16]), "+f"(d[17]), "+f"(d[18]), "+f"(d[19]), "+f"(d[20]), "+f"(d[21]), "+f"(d[22]), "+f"(d[23]), "+f"(d[24]), "+f"(d[25]), "+f"(d[26]), "+f"(d[27]), "+f"(d[28]), "+f"(d[29]), "+f"(d[30]), "+f"(d[31]), "+f"(d[32]), "+f"(d[33]), "+f"(d[34]), "+f"(d[35]), "+f"(d[36]), "+f"(d[37]), "+f"(d[38]), "+f"(d[39]), "+f"(d[40]), "+f"(d[41]), "+f"(d[42]), "+f"(d[43]), "+f"(d[44]), "+f"(d[45]), "+f"(d[46]), "+f"(d[47]), "+f"(d[48]), "+f"(d[49]), "+f"(d[50]), "+f"(d[51]), "+f"(d[52]), "+f"(d[53]), "+f"(d[54]), "+f"(d[55]), "+f"(d[56]), "+f"(d[57]), "+f"(d[58]), "+f"(d[59]), "+f"(d[60]), "+f"(d[61]), "+f"(d[62]), "+f"(d[63])
        : "l"(da), "l"(db), "r"(acc));
}
__device__ __forceinline__ void wg_fence() { asm volatile("wgmma.fence.sync.aligned;" ::: "memory"); }
__device__ __forceinline__ void wg_commit() { asm volatile("wgmma.commit_group.sync.aligned;" ::: "memory"); }
template <int N> __device__ __forceinline__ void wg_wait() { asm volatile("wgmma.wait_group.sync.aligned %0;" ::"n"(N) : "memory"); }
__device__ __forceinline__ uint64_t mkdesc(uint32_t addr, uint32_t lbo, uint32_t sbo, uint32_t sw) {
    return (uint64_t)((addr & 0x3FFFF) >> 4) | ((uint64_t)(lbo >> 4) << 16) | ((uint64_t)(sbo >> 4) << 32) | ((uint64_t)sw << 62);
}
__device__ __forceinline__ void tma2d(uint32_t dst, const CUtensorMap* m, int c0, int c1, uint32_t bar) {
    asm volatile("cp.async.bulk.tensor.2d.shared::cluster.global.mbarrier::complete_tx::bytes [%0], [%1, {%2, %3}], [%4];"
        ::"r"(dst), "l"(m), "r"(c0), "r"(c1), "r"(bar) : "memory");
}
__device__ __forceinline__ void tma3d(uint32_t dst, const CUtensorMap* m, int c0, int c1, int c2, uint32_t bar) {
    asm volatile("cp.async.bulk.tensor.3d.shared::cluster.global.mbarrier::complete_tx::bytes [%0], [%1, {%2, %3, %4}], [%5];"
        ::"r"(dst), "l"(m), "r"(c0), "r"(c1), "r"(c2), "r"(bar) : "memory");
}
__device__ __forceinline__ void tma3d_mc(uint32_t dst, const CUtensorMap* m, int c0, int c1, int c2, uint32_t bar, uint16_t mask) {
    asm volatile("cp.async.bulk.tensor.3d.shared::cluster.global.mbarrier::complete_tx::bytes.multicast::cluster [%0], [%1, {%2, %3, %4}], [%5], %6;"
        ::"r"(dst), "l"(m), "r"(c0), "r"(c1), "r"(c2), "r"(bar), "h"(mask) : "memory");
}
__device__ __forceinline__ void mbar_arrive(uint32_t bar) { asm volatile("mbarrier.arrive.shared.b64 _, [%0];" ::"r"(bar) : "memory"); }
__device__ __forceinline__ void mbar_arrive_remote(uint32_t bar) {
    asm volatile("mbarrier.arrive.shared::cluster.b64 _, [%0];" ::"r"(bar) : "memory");
}
template <int R> __device__ __forceinline__ void reg_inc() { asm volatile("setmaxnreg.inc.sync.aligned.u32 %0;" ::"n"(R)); }
template <int R> __device__ __forceinline__ void reg_dec() { asm volatile("setmaxnreg.dec.sync.aligned.u32 %0;" ::"n"(R)); }

constexpr int CH_NRES = 50;
constexpr int CH_WREG = CH_NRES * 512;
constexpr int CH_PART = 8 * CH_WREG;
constexpr int CH_SX = CH_PART + 16384;
constexpr int CH_MX = CH_SX + 3 * 1280;
constexpr int CH_QK = CH_MX;
constexpr int CH_XS = CH_MX + 3 * 512;
constexpr int CH_BAR = CH_XS + 5632;
constexpr int CH_SMEM = CH_BAR + 192;
constexpr int CH_THREADS = 384;

__device__ __forceinline__ char* ring_base() { return (char*)(((uintptr_t)g_ring + (1 << 20) - 1) & ~(uintptr_t)((1 << 20) - 1)); }
__device__ __forceinline__ uint32_t ring_off(int chunk, int side) {
    uint32_t o = ((chunk & 1) << 13) | ((chunk >> 1) << 16);
    uint32_t par = ((o >> 13) ^ (o >> 16) ^ (o >> 17) ^ (o >> 19) ^ side) & 1;
    return o | (par << 12);
}
__device__ __forceinline__ uint2 ld_poll(const char* p) {
    unsigned long long v; asm volatile("ld.relaxed.gpu.global.b64 %0, [%1];" : "=l"(v) : "l"(p) : "memory");
    return make_uint2((uint32_t)v, (uint32_t)(v >> 32));
}
__device__ __forceinline__ void st_pub(char* p, uint32_t x, uint32_t y) {
    unsigned long long v = ((unsigned long long)y << 32) | x;
    asm volatile("st.relaxed.gpu.global.b64 [%0], %1;" ::"l"(p), "l"(v) : "memory");
}
template <int N>
__device__ __forceinline__ void poll_issue(uint2 (&b)[N], const char* p, bool lastvalid) {
#pragma unroll
    for (int i = 0; i < N; i++) {
        if (i < N - 1 || lastvalid) b[i] = ld_poll(p + i * 256);
        else b[i] = make_uint2(0, 0);
    }
}
template <int N>
__device__ __forceinline__ int poll_check(uint2 (&b)[N], const char* p) {
    int it = 0;
    uint32_t mx = b[0].x;
#pragma unroll
    for (int i = 1; i < N; i++) mx = max(mx, b[i].x);
    if (__any_sync(0xffffffffu, mx == SENT)) {
        do {
#pragma unroll
            for (int i = 0; i < N; i++)
                if ((REALL && i < 10) || b[i].x == SENT) b[i] = ld_poll(p + i * 256);
            mx = b[0].x;
#pragma unroll
            for (int i = 1; i < N; i++) mx = max(mx, b[i].x);
            it++;
        } while (__any_sync(0xffffffffu, mx == SENT && it < SPIN_LIMIT));
    }
    return it;
}
template <int N>
__device__ __forceinline__ uint32_t delay(uint32_t a) {
    uint32_t z = 0;
#pragma unroll
    for (int i = 0; i < N; i++) asm volatile("ld.volatile.shared.u32 %0, [%1];" : "=r"(z) : "r"(a + z) : "memory");
    return z;
}

#define PFKV 0
#define LDW 1
constexpr int KVN = 2;
#define FEN 1
#define XB 4
#define KEEP 100
#define VCH_P 4
#define VCH_C 2
#define KGS 3
#define DLM 1
#define DLO 2
constexpr int OB = 0;
template <int PACE>
__device__ __forceinline__ void preload(uint32_t (&sw)[12][4], uint32_t a, uint32_t zero) {
    uint32_t z = 0;
#pragma unroll
    for (int i = 0; i < 12; i++) {
        if (PACE && i % (PACE ? PACE : 1) == 0) z = delay<1>(zero + z);
        ldsm4t(sw[i], a + z + i * 512);
    }
}
__device__ __forceinline__ void stsm4(uint32_t addr, uint32_t a, uint32_t b, uint32_t c, uint32_t d) {
    asm volatile("stmatrix.sync.aligned.m8n8.x4.shared.b16 [%0], {%1,%2,%3,%4};" ::"r"(addr), "r"(a), "r"(b), "r"(c), "r"(d) : "memory");
}
__device__ __forceinline__ void stsm4t(uint32_t addr, uint32_t a, uint32_t b, uint32_t c, uint32_t d) {
    asm volatile("stmatrix.sync.aligned.m8n8.x4.trans.shared.b16 [%0], {%1,%2,%3,%4};" ::"r"(addr), "r"(a), "r"(b), "r"(c), "r"(d) : "memory");
}
__device__ __forceinline__ void st_part(uint32_t addr, const float (&x)[4], const float (&y)[4]) {
    stsm4(addr, pack_bf16(x[0], x[1]), pack_bf16(x[2], x[3]), pack_bf16(y[0], y[1]), pack_bf16(y[2], y[3]));
}
template <bool TR>
__device__ __forceinline__ void red_part(uint32_t& lo, uint32_t& hi, uint32_t addr, uint32_t eye) {
    uint32_t a[4][4];
#pragma unroll
    for (int j = 0; j < 4; j++) { if (TR) ldsm4t(a[j], addr + j * 1024); else ldsm4(a[j], addr + j * 1024); }
    float r0[4], r1[4], r2[4], r3[4];
    mma16z(r0, a[0], eye, eye); mma16z(r1, a[1], eye, eye); mma16z(r2, a[2], eye, eye); mma16z(r3, a[3], eye, eye);
#pragma unroll
    for (int j = 0; j < 4; j++) r0[j] = ((r0[j] + r1[j]) + r2[j]) + r3[j];
    lo = pack_bf16(r0[0], r0[1]); hi = pack_bf16(r0[2], r0[3]);
}
__device__ __forceinline__ int o_chunk(int ks, int& pos) {
    const int cw = ks < 176 ? ks / 11 : 16 + (ks - 176) / 10;
    pos = ks - (cw < 16 ? 11 * cw : 176 + 10 * (cw - 16));
    return cw;
}

template <bool PV>
__device__ __forceinline__ void chain_loop(const uint32_t (&wa)[36][4], const uint32_t sb, const int w, const int lane0, const int rank,
                                           const int h, const int side) {
    const int rk1 = rank == 2 ? 0 : rank + 1, rk2 = rank == 0 ? 2 : rank - 1;
    const int nq = rank == 0 ? 6 : 5, u0 = rank == 0 ? 0 : 1 + 5 * rank, v0 = rank == 0 ? -6 : 3 * rank - 6;
    const uint32_t pt = CH_PART + (w >> 1) * 4096 + (w & 1) * 256;
    const uint32_t barS = sb + CH_BAR, barM = barS + 8, zero = barS + 24;
    char* const ring0 = ring_base();
    const uint32_t m_rd = ring_off(24 + w, side), o_rd = ring_off(rank * 8 + w, side);
    uint32_t pub;
    if (PV) { int pos, cw = o_chunk(h * 8 + v0 + w, pos); pub = (ring_off(cw, 0) & ~4096u) + pos * 256; }
    else pub = (ring_off(24 + (h >> 2), 0) & ~4096u) + ((2 * h + w) & 7) * 256;
    char* const kvo = (char*)(PV ? g_vm + 128 * (v0 + w) : g_km + 64 * (u0 + w)) + h * 2048;
    const bool mown = !PV && w == rank && rank < 2;
    uint32_t lo16 = lane0 * 16;
    uint32_t sw[12][4];
#pragma unroll
    for (int i = 0; i < 12; i++) ldsm4t(sw[i], sb + lo16 + w * CH_WREG + i * 512);

#pragma unroll 1
    for (int s = 0;; s++) {
        const bool last = s == NSEG - 1;
        const uint32_t slot = (s & 3) << 14;
        lo16 += delay<DLM>(zero);
        const uint32_t lane = lo16 >> 4, l16 = sb + lo16, wl = l16 + w * CH_WREG, pw = l16 + CH_PART + w * 512;
        const uint32_t xs = l16 + CH_XS + nq * 512 + (w - nq) * 1024;
        const uint32_t eye = ((lo16 >> 7) == (lane & 3)) ? ((lo16 & 64) ? 0x3F800000u : 0x3F80u) : 0u;
        uint2 b[8];
        const char* pm = ring0 + (m_rd + slot + (lo16 >> 1));
        poll_issue<8>(b, pm, true);
        poll_check<8>(b, pm);
        if ((OB || (XB & 1)) && !last) bar_arrive(8, 256 + OB);
        if (PV && !last && w == 7) bar_arrive(13, 64);
        {
            float acc[6][4];
#pragma unroll
            for (int kk = 0; kk < 8; kk++) {
                const int j = (2 * kk) % 12;
                if (kk == 0) { mma16z(acc[5], sw[0], b[0].x, b[0].y); mma16z(acc[4], sw[1], b[0].x, b[0].y); }
                else { mma16(acc[5], sw[j], b[kk].x, b[kk].y); mma16(acc[4], sw[j + 1], b[kk].x, b[kk].y); }
#pragma unroll
                for (int i = 0; i < 4; i++) {
                    if (kk == 0) mma16z(acc[i], wa[i * 8], b[0].x, b[0].y);
                    else mma16(acc[i], wa[i * 8 + kk], b[kk].x, b[kk].y);
                    if (i < 2) ldsm4t(sw[j + i], wl + (12 + 2 * kk + i) * 512);
                }
            }
            st_part(pw + 4 * 2048, acc[4], acc[5]);
            st_part(pw, acc[0], acc[1]);
            st_part(pw + 2 * 2048, acc[2], acc[3]);
        }
        uint32_t kv0, kv1;
        const uint32_t lp = l16 + (lane >> 4) * 256, pl = lp + pt;
        if (!PV) {
            bar_sync(1, last ? 256 : 256 + OB);
            red_part<true>(kv1, kv0, pl, eye);
            sts64(l16 + CH_QK + (w >> 1) * 512 + (w & 1) * 8, __uint_as_float(kv1), __uint_as_float(kv0));
            if (!last) bar_arrive(2, nq * 32 + 64 + OB);
        } else {
            bar_sync(1, last ? 256 : 256 + OB);
        }
        {
            float va[4][4];
            const float z = __uint_as_float(delay<1>(zero));
#pragma unroll
            for (int i = 0; i < 4; i++) va[i][0] = va[i][1] = va[i][2] = va[i][3] = z;
#pragma unroll
            for (int kk = 0; kk < 8; kk++) {
                const int c = (PV ? VCH_P : VCH_C) == 4 ? kk & 1 : 0;
                if (kk < 2) { mma16(va[c], wa[32 + 2 * kk], b[kk].x, b[kk].y); mma16(va[2 + c], wa[33 + 2 * kk], b[kk].x, b[kk].y); }
                else { mma16(va[c], sw[(2 * kk) % 12], b[kk].x, b[kk].y); mma16(va[2 + c], sw[(2 * kk + 1) % 12], b[kk].x, b[kk].y); }
            }
            if ((PV ? VCH_P : VCH_C) == 4) {
#pragma unroll
                for (int j = 0; j < 4; j++) { va[0][j] += va[1][j]; va[2][j] += va[3][j]; }
            }
            st_part(pw + 6 * 2048, va[0], va[2]);
        }
        if (PV) {
            uint32_t vt0[4], vt1[4];
            ldsm4t(vt0, xs); ldsm4t(vt1, xs + 512);
            if (w >= 6 && !last) {
                uint32_t kx[3][4];
#pragma unroll
                for (int j = 0; j < 3; j++)
                    ldsm4(kx[j], sb + CH_XS + j * 1024 + (j == 2 && nq == 5 ? 0 : ((lane >> 3) & 1) * 512) + (w - 6) * 256 + (lane >> 4) * 128 + (lane & 7) * 16);
                const uint32_t da = l16 + CH_SX + rank * 1280 + (w - 6) * 512, dc = sb + CH_SX + rank * 1280 + 1024 + lane * 8;
                bar_sync(2, nq * 32 + 64 + OB);
                uint32_t qk[3][4];
#pragma unroll
                for (int j = 0; j < 3; j++) {
                    const float4 v = lds128(l16 + CH_QK + j * 512);
                    qk[j][0] = __float_as_uint(v.x); qk[j][1] = __float_as_uint(v.y); qk[j][2] = __float_as_uint(v.z); qk[j][3] = __float_as_uint(v.w);
                }
                float s0[4], s1[4], s2[4], s3[4];
                mma16z(s0, qk[0], kx[0][0], kx[0][1]); mma16z(s1, qk[0], kx[0][2], kx[0][3]);
                mma16z(s2, qk[1], kx[1][0], kx[1][1]); mma16z(s3, qk[1], kx[1][2], kx[1][3]);
                if (nq == 5) qk[2][2] = qk[2][3] = 0;
                mma16(s0, qk[2], kx[2][0], kx[2][1]); mma16(s1, qk[2], kx[2][2], kx[2][3]);
                float m0[4], m1[4];
                mma16z(m0, qk[0], qk[0][1], qk[0][3]); mma16z(m1, qk[1], qk[1][1], qk[1][3]);
                mma16(m0, qk[2], qk[2][1], qk[2][3]);
                const float4 sv = make_float4(s0[0] + s2[0], s0[1] + s2[1], s1[0] + s3[0], s1[1] + s3[1]);
                st_async4(mapa(da, rk1), sv, mapa(barS, rk1));
                st_async4(mapa(da, rk2), sv, mapa(barS, rk2));
                {
                    const float c0 = m0[0] + m1[0], c1 = m0[1] + m1[1];
                    const int dr = w == 6 ? rk1 : rk2;
                    st_async2(mapa(dc, dr), c0, c1, mapa(barS, dr));
                    sts64(dc, c0, c1);
                }
                const float t4[4] = {sv.x, sv.y, sv.z, sv.w};
                sts128(da, t4);
            }
            bar_sync(3, last ? 256 : 256 + OB);
            if (!last && w == 7) bar_arrive(12, 64);
            red_part<false>(kv0, kv1, pl, eye);
            if (last) {
                uint32_t* d = (uint32_t*)(kvo + (uint32_t)(s * (NH * 2048) + lane * 4));
                d[0] = movm(kv0); d[32] = movm(kv1);
                break;
            }
            {
                const uint32_t sx = l16 + CH_SX, r0 = rank * 1280, r1 = rk1 * 1280, r2 = rk2 * 1280;
                float4 a0 = lds128(sx + r0), b0 = lds128(sx + 512 + r0);
                const float2 c0 = lds64(sx + 1024 + r0 - lane * 8);
                mbar_wait(barS, s & 1);
                const float4 a1 = lds128(sx + r1), a2 = lds128(sx + r2), b1 = lds128(sx + 512 + r1), b2 = lds128(sx + 512 + r2);
                const float2 c1 = lds64(sx + 1024 + r1 - lane * 8), c2 = lds64(sx + 1024 + r2 - lane * 8);
                a0 = add4(add4(a0, a1), a2); b0 = add4(add4(b0, b1), b2);
                float sc[10] = {a0.x, a0.y, a0.z, a0.w, b0.x, b0.y, b0.z, b0.w, c0.x + c1.x + c2.x, c0.y + c1.y + c2.y};
                float mx = fmaxf(fmaxf(fmaxf(sc[0], sc[1]), fmaxf(sc[2], sc[3])), fmaxf(fmaxf(sc[4], sc[5]), fmaxf(sc[6], sc[7])));
                mx = fmaxf(mx, fmaxf(sc[8], sc[9]));
                mx = fmaxf(fmaxf(mx, __shfl_xor_sync(0xffffffffu, mx, 1)),
                           fmaxf(__shfl_xor_sync(0xffffffffu, mx, 2), __shfl_xor_sync(0xffffffffu, mx, 3)));
                const float cs = 0.08838834764831845f * 1.4426950408889634f;
                const float mb = -mx * cs;
#pragma unroll
                for (int j = 0; j < 10; j++) sc[j] = ex2(fmaf(sc[j], cs, mb));
                uint32_t pf[5];
#pragma unroll
                for (int j = 0; j < 5; j++) pf[j] = pack_bf16(sc[2 * j], sc[2 * j + 1]);
                float o0[4], o1[4], o2[4], o3[4], o4[4], o5[4];
                const uint32_t p0[4] = {pf[0], 0, pf[1], 0}, p1[4] = {pf[2], 0, pf[3], 0};
                mma16z(o0, p0, vt0[0], vt0[1]); mma16z(o1, p0, vt1[0], vt1[1]);
                mma16z(o2, p1, vt0[2], vt0[3]); mma16z(o3, p1, vt1[2], vt1[3]);
                mma8z(o4, pf[4], 0, kv0); mma8z(o5, pf[4], 0, kv1);
                float sum = (((sc[0] + sc[1]) + (sc[2] + sc[3])) + ((sc[4] + sc[5]) + (sc[6] + sc[7]))) + (sc[8] + sc[9]);
                sum = (sum + __shfl_xor_sync(0xffffffffu, sum, 1)) + (__shfl_xor_sync(0xffffffffu, sum, 2) + __shfl_xor_sync(0xffffffffu, sum, 3));
                float inv; asm("rcp.approx.ftz.f32 %0, %1;" : "=f"(inv) : "f"(sum));
                const uint32_t ox = pack_bf16((o0[0] + o2[0] + o4[0]) * inv, (o0[1] + o2[1] + o4[1]) * inv);
                const uint32_t oy = pack_bf16((o1[0] + o3[0] + o5[0]) * inv, (o1[1] + o3[1] + o5[1]) * inv);
                char* const pp = ring0 + (pub + slot + (lo16 >> 1));
                st_pub(pp, ox, oy); st_pub(pp + 4096, ox, oy);
                if (OB || (XB & 4)) bar_arrive(10, (8 - nq) * 32 + OB);
                preload<0>(sw, wl + 28 * 512, zero);
            }
            kv0 = movm(kv0); kv1 = movm(kv1);
        } else {
            *(uint32_t*)(kvo + (uint32_t)(s * (NH * 2048) + lane * 4)) = kv0;
            bar_sync(3, last ? 256 : 256 + OB);
            if (last) break;
            preload<1>(sw, wl + 28 * 512, zero);
        }
        uint2 c[11];
        bar_sync(4, 256 + OB);
        const char* po = ring0 + (o_rd + slot + (lo16 >> 1) + delay<DLO>(zero));
        poll_issue<11>(c, po, rank < 2);
        if (PV) { uint32_t* d = (uint32_t*)(kvo + (uint32_t)(s * (NH * 2048) + lane * 4)); d[0] = kv0; d[32] = kv1; }
        poll_check<11>(c, po);
        if (OB || (XB & 2)) bar_arrive(9, 256 + OB);
        {
            float acc[4][4];
#pragma unroll
            for (int f = 0; f < 22; f++) {
                const int kk = f >> 1, a = f & 3;
                if (f < 4) mma16z(acc[a], sw[f % 12], c[kk].x, c[kk].y);
                else mma16(acc[a], sw[f % 12], c[kk].x, c[kk].y);
                if (f + 12 < 22) ldsm4t(sw[f % 12], wl + (28 + f + 12) * 512);
            }
#pragma unroll
            for (int i = 0; i < 2; i++) {
#pragma unroll
                for (int j = 0; j < 4; j++) acc[i][j] += acc[i + 2][j];
                sts128(l16 + CH_PART + i * 4096 + w * 512, acc[i]);
            }
        }
        if (!PV && w < 2) {
            bar_sync(5, 288 + OB);
            float4 v[8];
#pragma unroll
            for (int i = 0; i < 8; i++) v[i] = lds128(l16 + CH_PART + w * 4096 + i * 512);
            float4 r = add4(add4(add4(v[0], v[1]), add4(v[2], v[3])), add4(add4(v[4], v[5]), add4(v[6], v[7])));
            if (!mown) st_async4(mapa(l16 + CH_MX + rank * 512, w), r, mapa(barM, w));
            bar_arrive(7, 256 + OB);
            if (mown) {
                mbar_wait(barM, s & 1);
                float4 x = lds128(l16 + CH_MX + (rank ^ 1) * 512), y = lds128(l16 + CH_MX + 2 * 512);
                r = add4(add4(x, r), y);
                const uint32_t mx = movm(pack_bf16(r.x, r.y)), my = movm(pack_bf16(r.z, r.w));
                const uint32_t ns = (slot + 0x4000) & 0xC000;
                char* const pp = ring0 + (pub + ns + (lo16 >> 1));
                st_pub(pp, mx, my); st_pub(pp + 4096, mx, my);
            }
            preload<0>(sw, wl, zero);
        } else {
            bar_arrive(5, 288 + OB);
            bar_sync(7, 256 + OB);
            preload<2>(sw, wl, zero);
        }
        bar_sync(6, 320 + OB);
    }
    bar_arrive(6, 288);
}

__device__ __forceinline__ void chain_pace(const uint32_t sb, const int lane, const int rank, const int aware) {
    const uint32_t zero = sb + CH_BAR + 24;
    if (lane == 0) {
        char* ring = ring_base();
        uint32_t* p0 = (uint32_t*)(ring + ring_off(blockIdx.x & 15, 0) + 3072 + (blockIdx.x >> 4) * 128);
        uint32_t* p1 = (uint32_t*)(ring + ring_off(blockIdx.x & 15, 1) + 3072 + (blockIdx.x >> 4) * 128);
        *p0 = 0; *p1 = 0;
        int b0 = 1 << 30, b1 = 1 << 30; uint32_t v = 0;
        for (int r = 0; r < 4 || (r < 256 && !mbar_test(sb + CH_BAR + 16, 0)); r++) {
            uint32_t t0 = clk(); v = atomicExch(p0 + (v == 500), r); uint32_t t1 = v == 777 ? clk() + 1 : clk(); b0 = min(b0, (int)(t1 - t0));
            t0 = clk(); v = atomicExch(p1 + (v == 500), r); t1 = v == 777 ? clk() + 1 : clk(); b1 = min(b1, (int)(t1 - t0));
            asm volatile("st.volatile.shared.u32 [%0], %1;" ::"r"(zero + 4), "r"(aware ? (b1 < b0) ^ (aware - 1) : 0) : "memory");
        }
    }
    __syncwarp();
#pragma unroll 1
    for (int s = 1; s < NSEG; s++) {
        bar_sync(5, 288 + OB);
        bar_arrive(6, 320 + OB + (rank == 2 ? delay<18>(zero) : 0));
    }
}
__device__ __forceinline__ char* reset_ptr(const int lane, const int rank, const int h) {
    const int nq = rank == 0 ? 6 : 5, v0 = rank == 0 ? -6 : 3 * rank - 6;
    int pos, cw = o_chunk(h * 8 + v0 + min(max(5 + (lane >> 3), nq), 7), pos);
    if (lane >= 24 && rank < 2) { cw = 24 + (h >> 2); pos = (2 * h + rank) & 7; }
    return ring_base() + ((ring_off(cw, 0) & ~4096u) + pos * 256 + (lane & 7) * 16);
}
__device__ __forceinline__ void chain_chores(const uint32_t sb, const int lane, const int rank, const int h, const bf16* __restrict__ mem0) {
    const int nq = rank == 0 ? 6 : 5, u0 = rank == 0 ? 0 : 1 + 5 * rank, v0 = rank == 0 ? -6 : 3 * rank - 6;
    const uint32_t barS = sb + CH_BAR, barM = barS + 8, barX = barS + 16;
    auto xload = [&](int s) {
        mbar_expect(barX, 8192 - nq * 512);
        bulk_load(sb + CH_XS, g_kx + (size_t)(s * NH + h) * 4096 + u0 * 256, nq * 512, barX);
        bulk_load(sb + CH_XS + nq * 512, g_vx + (size_t)(s * NH + h) * 4096 + (v0 + nq) * 512, (8 - nq) * 1024, barX);
    };
    char* const rb = reset_ptr(lane, rank, h);
    int* const kvf = g_kvf + blockIdx.x * 16;
    if (rank < 2) {
        const uint32_t* p = (const uint32_t*)(mem0 + (lane >> 2) * DM + 32 * h + 16 * rank + 2 * (lane & 3));
        char* d = ring_base() + ((ring_off(24 + (h >> 2), 0) & ~4096u) + ((2 * h + rank) & 7) * 256 + lane * 8);
        const uint32_t x = p[0] == SENT ? 0x7FFF7FFFu : p[0];
        st_pub(d, x, p[4]); st_pub(d + 4096, x, p[4]);
    }
    if (lane == 0) {
        if (!KVN) __nanosleep(18000);
        wait_ctr(kvf, KVN);
        asm volatile("fence.proxy.async;" ::: "memory");
        xload(0);
    }
#pragma unroll 1
    for (int s = 0; s < NSEG - 1; s++) {
        if (lane == 0) {
            mbar_expect(barS, 2 * 1280);
            if (rank < 2) mbar_expect(barM, 2 * 512);
        }
        bar_sync(13, 64);
#pragma unroll
        for (int i = 0; i < 4; i++)
            asm volatile("st.relaxed.gpu.global.v4.u32 [%0], {%1,%1,%1,%1};" ::"l"(rb + ((((s + 2) & 3) << 14) + (i >> 1) * 4096 + (i & 1) * 128)), "r"(SENT) : "memory");
        if (FEN || (s & 3) == 0) __threadfence();
        if (lane == 0 && (s & 3) == 0 && s) atomicAdd(g_ctr + C_CHAIN + (s >> 2) - 1, 1);
        if (lane == 0 && (s & 3) == 3) { wait_ctr(kvf + (s >> 2) + 1, KVN); asm volatile("fence.proxy.async;" ::: "memory"); }
        __syncwarp();
        bar_sync(12, 64);
        if (lane == 0) xload(s + 1);
        mbar_wait(barX, (s + 1) & 1);
        bar_sync(6, 320 + OB);
    }
    bar_sync(6, 288);
    __threadfence();
    if (lane == 0) atomicAdd(g_ctr + C_CHAIN + 15, 1);
}

struct S4Params { const bf16 *Are, *Aim, *Bre, *Bim, *Cre, *Cim, *ldt, *dsk; };
__device__ __forceinline__ float2 cmul(float2 a, float2 b) { return make_float2(a.x * b.x - a.y * b.y, a.x * b.y + a.y * b.x); }
__device__ __forceinline__ float2 csq(float2 a) { return make_float2(a.x * a.x - a.y * a.y, (a.x + a.x) * a.y); }
__device__ __forceinline__ float2 cexp_t(float lr, float turns) {
    float f = (turns - rintf(turns)) * 6.283185307179586f, e = ex2(lr);
    return make_float2(e * __cosf(f), e * __sinf(f));
}
__device__ __forceinline__ float bf_at(uint2 v, int i) {
    const uint32_t w = i < 2 ? v.x : v.y;
    return __uint_as_float((i & 1) ? w & 0xFFFF0000u : w << 16);
}
__device__ __forceinline__ void kg_step(uint32_t (&a)[4][4], uint32_t (&b)[5][2], uint32_t pa, uint32_t pe, float x0) {
#pragma unroll
    for (int i = 0; i < 2; i++) {
        const float4 p = lds128(pa + i * 64);
        const float2 e8 = lds64(pe + i * 32), c = make_float2(p.z, p.w);
        const float mag = ex2(p.x * x0), ph = p.y * x0;
        float2 e0 = make_float2(mag * __cosf(ph), mag * __sinf(ph)), e1 = cmul(e0, e8);
#pragma unroll
        for (int j = 0; j < 4; j++) {
            a[j][2 * i] = pack_bf16(e0.x, e0.y); a[j][2 * i + 1] = pack_bf16(e1.x, e1.y);
            e0 = csq(e0); e1 = csq(e1);
        }
        float2 m = cmul(c, e0);
        b[0][i] = pack_bf16(m.x, -m.y);
#pragma unroll
        for (int j = 0; j < 4; j++) {
            m = cmul(c, e1);
            b[j + 1][i] = pack_bf16(m.x, -m.y);
            if (j < 3) e1 = csq(e1);
        }
    }
}
__device__ __forceinline__ void kg_mma(float (&kd)[5][4], const uint32_t (&a)[4][4], const uint32_t (&b)[5][2]) {
    mma16(kd[0], a[0], b[0][0], b[0][1]);
#pragma unroll
    for (int j = 0; j < 4; j++) mma16(kd[j + 1], a[j], b[j + 1][0], b[j + 1][1]);
}
struct KgRaw { uint2 v[6]; float ldt; };
__device__ __forceinline__ void kg_load(KgRaw& r, const S4Params& P, int d, int lane) {
    const bf16* src[6] = {P.Are, P.Aim, P.Bre, P.Bim, P.Cre, P.Cim};
#pragma unroll
    for (int j = 0; j < 6; j++) r.v[j] = __ldg((const uint2*)(src[j] + d * 128) + lane);
    r.ldt = __bfloat162float(P.ldt[d]);
}
__device__ __forceinline__ float kg_params(const KgRaw& r, uint32_t stg, int lane) {
    const float dt = __bfloat162float(__float2bfloat16(expf(r.ldt)));
    float k2048 = 0.f;
#pragma unroll
    for (int i = 0; i < 4; i++) {
        const float br = dt * bf_at(r.v[2], i), bi = dt * bf_at(r.v[3], i), cr = bf_at(r.v[4], i), ci = bf_at(r.v[5], i);
        const float zr = dt * bf_at(r.v[0], i) * 1.4426950408889634f;
        float zt = dt * bf_at(r.v[1], i) * 0.15915494309189535f;
        zt -= rintf(zt);
        const float v[4] = {zr, zt * 6.283185307179586f, cr * br - ci * bi, cr * bi + ci * br};
        const float2 e8 = cexp_t(8.f * zr, 8.f * zt), el = cexp_t(2048.f * zr, 2048.f * zt);
        k2048 += v[2] * el.x - v[3] * el.y;
        sts128(stg + (i * 32 + lane) * 16, v);
        sts64(stg + 2048 + (i * 32 + lane) * 8, e8.x, e8.y);
    }
#pragma unroll
    for (int o = 16; o; o >>= 1) k2048 += __shfl_xor_sync(0xffffffffu, k2048, o);
    __syncwarp();
    return k2048;
}
__device__ __forceinline__ void kg_store(const float (&kd)[5][4], float k2048, uint32_t stg, int d, int lane) {
    __syncwarp();
    const uint32_t ta = stg + (lane & 7) * 32 + ((lane >> 3) & 1) * 16 + (lane >> 4) * 256;
    stsm4t(ta, pack_bf16(kd[0][0], kd[0][1]), pack_bf16(kd[0][2], kd[0][3]), pack_bf16(kd[1][0], kd[1][1]), pack_bf16(kd[1][2], kd[1][3]));
    stsm4t(ta + 512, pack_bf16(kd[2][0], kd[2][1]), pack_bf16(kd[2][2], kd[2][3]), pack_bf16(kd[3][0], kd[3][1]), pack_bf16(kd[3][2], kd[3][3]));
    stsm4t(ta + 1024, pack_bf16(kd[4][0], kd[4][1]), pack_bf16(kd[4][2], kd[4][3]), pack_bf16(k2048, 0.f), 0);
    __syncwarp();
#pragma unroll
    for (int j = 0; j < 3; j++) ((float4*)(g_kd + d * 768))[j * 32 + lane] = lds128(stg + j * 512 + lane * 16);
    __syncwarp();
}

__global__ void __cluster_dims__(3, 1, 1) __launch_bounds__(CH_THREADS, 1)
chain_kernel(const __grid_constant__ CUtensorMap mq, const __grid_constant__ CUtensorMap mk, const __grid_constant__ CUtensorMap mv,
             const __grid_constant__ CUtensorMap mo, const bf16* __restrict__ Wq, const bf16* __restrict__ Wk, const bf16* __restrict__ Wv,
             const bf16* __restrict__ mem0, const __grid_constant__ S4Params P, int aware) {
    extern __shared__ __align__(1024) unsigned char smem[];
    const uint32_t sb = smem_u32(smem);
    const int tid = threadIdx.x, lane = tid & 31;
    const int w = __shfl_sync(0xffffffffu, tid >> 5, 0);
    int rank; asm("mov.u32 %0, %%cluster_ctarank;" : "=r"(rank));
    const int h = blockIdx.x / 3;
    if (tid == 0) {
        mbar_init(sb + CH_BAR, 1); mbar_init(sb + CH_BAR + 8, 1); mbar_init(sb + CH_BAR + 16, 1);
        for (int i = 0; i < 16; i++) mbar_init(sb + CH_BAR + 64 + i * 8, 1);
        *(int*)(smem + CH_BAR + 24) = 0; *(int*)(smem + CH_BAR + 28) = 0; *(int*)(smem + CH_BAR + 32) = 0;
        asm volatile("fence.mbarrier_init.release.cluster;" ::: "memory");
    }
    if (w == 10 && PFKV) {
        const int e = lane * 96 + blockIdx.x;
        if (e < 2048) asm volatile("cp.async.bulk.prefetch.L2.global [%0], 8192;" ::"l"(((e & 1) ? Wv : Wk) + (size_t)(e >> 1) * HD) : "memory");
        if (PFKV > 1) __nanosleep(PFKV);
    }
    if (w == 9) {
        char* const rb = reset_ptr(lane, rank, h);
#pragma unroll
        for (int i = 0; i < 8; i++)
            asm volatile("st.relaxed.gpu.global.v4.u32 [%0], {%1,%1,%1,%1};" ::"l"(rb + (((i >> 2) << 14) + ((i >> 1) & 1) * 4096 + (i & 1) * 128)), "r"(SENT) : "memory");
        if (lane < 16) g_kvf[blockIdx.x * 16 + lane] = 0;
        if (blockIdx.x == 0)
            for (int k = lane; k < N_CTR; k += 32) g_ctr[k] = 0;
        __threadfence();
        __syncwarp();
        asm volatile("griddepcontrol.launch_dependents;" ::: "memory");
    }
    __syncthreads();
    asm volatile("barrier.cluster.arrive.relaxed.aligned;" ::: "memory");

    if (w >= 8) {
        reg_dec<24>();
        asm volatile("barrier.cluster.wait.aligned;" ::: "memory");
        if (w == 8) chain_pace(sb, lane, rank, aware);
        else if (w == 9) {
            chain_chores(sb, lane, rank, h, mem0);
            asm volatile("st.volatile.shared.u32 [%0], %1;" ::"r"(sb + CH_BAR + 32), "r"(0x3F803F80) : "memory");
        } else if (w == 11 && KEEP) {
#pragma unroll 1
            for (int it = 0; it < (1 << 22); it++) {
                int d0, d1;
                const uint32_t x = delay<1>(sb + CH_BAR + 32);
                asm volatile("mma.sync.aligned.m8n8k16.row.col.s32.s8.s8.s32 {%0,%1}, {%2}, {%2}, {%3,%3};" : "=r"(d0), "=r"(d1) : "r"(x), "r"(0));
                if (d0 | d1) break;
                if ((XB & 8) && lane == 0) asm volatile("st.relaxed.gpu.global.u32 [%0], %1;" ::"l"(g_kd + DM * 768 + blockIdx.x * 64), "r"(it) : "memory");
                if ((XB & 16) && lane == 0) ld_acq((int*)(g_kd + DM * 768 + blockIdx.x * 64));
                __nanosleep(KEEP);
            }
        }
    } else {
        reg_inc<240>();
        const int nq = rank == 0 ? 6 : 5;
        const int u0 = rank == 0 ? 0 : 1 + 5 * rank;
        const int v0 = rank == 0 ? -6 : 3 * rank - 6;
        const int gw = rank * 8 + w;
        const int ks0 = gw < 16 ? 11 * gw : 176 + 10 * (gw - 16);
        const int nko = gw < 16 ? 11 : 10;
        const uint32_t wr = sb + w * CH_WREG, bar0 = sb + CH_BAR + 64 + w * 16, bar1 = bar0 + 8;
        uint32_t wa[36][4];
        const uint32_t vst = sb + CH_PART + w * 2048;
        const int cq = h * DH + 8 * u0, cv = h * DH + 16 * (v0 + 6);
        const int r8 = lane >> 2, p = lane & 3;
        const bf16* src = p >= 2 ? ((p & 1) ? Wk : Wq) + cq + 32 : rank == 0 ? ((p & 1) ? Wk : Wq) + cq + 40 : Wv + cv - 16 + 8 * p;
        src += (size_t)(128 * w + r8) * HD;
        auto cp_rows = [&](int kh) {
            cp16(wr + ((kh >> 1) * 2 + (p >> 1)) * 512 + ((kh & 1) * 2 + (p & 1)) * 128 + r8 * 16, src + (size_t)kh * 8 * HD);
        };
        {
            int d = blockIdx.x * 8 + w, t = 0;
            const int d1 = 768 + blockIdx.x * 3 + w, nt = (w < 3 && d1 < DM) ? 32 : 16;
            const uint32_t stg = wr + 4096;
            KgRaw raw, raw1;
            kg_load(raw, P, d, lane);
            kg_load(raw1, P, min(d1, DM - 1), lane);
            float kd[5][4], k2048;
#pragma unroll 1
            for (int i = -LDW; i < 9 || t < nt; i++) {
                if (i >= 0 && i < 9) {
                    const uint32_t bar = bar0 + (i & 1) * 8;
                    if (i >= 2) mbar_wait(bar, ((i >> 1) - 1) & 1);
                    if (lane == 0) {
                        mbar_expect(bar, 2048);
                        if (i < 8) tma2d(wr + 8192 + (i & 1) * 8192 + (i >> 1) * 2048, (i & 1) ? &mk : &mq, cq, 128 * w + 32 * (i >> 1), bar);
                        else tma2d(vst, &mv, cv, 128 * w, bar);
                    }
                    if (i < 8) cp_rows(i);
                }
#pragma unroll 1
                for (int e = min(t + KGS, nt); t < e; t++) {
                    if ((t & 15) == 0) {
                        k2048 = kg_params(raw, stg, lane);
#pragma unroll
                        for (int j = 0; j < 20; j++) kd[j >> 2][j & 3] = 0.f;
                    }
                    uint32_t ka[4][4], kb[5][2];
                    kg_step(ka, kb, stg + ((t & 15) * 8 + (lane & 3)) * 16, stg + 2048 + ((t & 15) * 8 + (lane & 3)) * 8, (float)(lane >> 2));
                    kg_mma(kd, ka, kb);
                    if ((t & 15) == 15) { kg_store(kd, k2048, stg, d, lane); raw = raw1; d = d1; }
                }
            }
        }
        const uint32_t lrow = ((lane >> 4) * 8 + (lane & 7)) * 64, lsw = (lane >> 1) & 3, lh = (lane >> 3) & 1;
        mbar_wait(bar1, 1); mbar_wait(bar0, 0);
#pragma unroll
        for (int i = 0; i < 32; i++) ldsm4t(wa[i], wr + 8192 + lh * 8192 + (i & 7) * 1024 + lrow + (((i >> 3) ^ lsw) << 4));
#pragma unroll
        for (int i = 0; i < 4; i++) ldsm4t(wa[32 + i], vst + (i >> 1) * 1024 + lrow + ((((i & 1) * 2 + lh) ^ lsw) << 4));
        asm volatile("fence.proxy.async.shared::cta;" ::"r"(wa[31][0]), "r"(wa[35][0]) : "memory");
        __syncwarp();
#pragma unroll 1
        for (int i = 9; i < 18; i++) {
            const uint32_t bar = bar0 + (i & 1) * 8;
            if (i >= 11) mbar_wait(bar, ((i >> 1) - 1) & 1);
            if (lane == 0) {
                const int j = 2 * (i - 12), nb = min(2, nko - j);
                mbar_expect(bar, i < 12 ? 2048 : nb * 1024);
                if (i < 12) tma2d(wr + 8192 + (i - 9) * 2048, &mv, cv, 128 * w + 32 * (i - 8), bar);
                else for (int e = 0; e < nb; e++) tma2d(wr + 14336 + (j + e) * 1024, &mo, 32 * h, 16 * (ks0 + j + e), bar);
            }
            if (i < 17) cp_rows(i - 1);
        }
        mbar_wait(bar0, 0); mbar_wait(bar1, 0);
#pragma unroll 1
        for (int i = 0; i < 17; i++) {
            uint32_t x[4], y[4];
            ldsm4t(x, wr + 8192 + i * 1024 + lrow + ((lh ^ lsw) << 4));
            ldsm4t(y, wr + 8192 + i * 1024 + lrow + (((2 + lh) ^ lsw) << 4));
            if (i == 16 && nko == 10) x[0] = x[1] = x[2] = x[3] = y[0] = y[1] = y[2] = y[3] = 0;
            __syncwarp();
            stsm4t(wr + 8192 + i * 1024 + lane * 16, x[0], x[1], x[2], x[3]);
            stsm4t(wr + 8192 + i * 1024 + 512 + lane * 16, y[0], y[1], y[2], y[3]);
        }
        asm volatile("cp.async.wait_all;" ::: "memory");
        asm volatile("barrier.cluster.wait.aligned;" ::: "memory");
        bar_sync(1, 256);
        mbar_wait_long(sb + CH_BAR + 16, 0);
        const int side = __shfl_sync(0xffffffffu, *(volatile int*)(smem + CH_BAR + 28), 0);
        if (w >= nq) chain_loop<true>(wa, sb, w, lane, rank, h, side);
        else chain_loop<false>(wa, sb, w, lane, rank, h, side);
    }
}

constexpr int G_STAGE = 49152, G_NST = 4;
constexpr int G_STG = G_NST * G_STAGE;
constexpr int G_BAR = G_STG + 32768;
constexpr int G_SMEM = G_BAR + 256 + 1024;

#define ST(id, w, i)
#define WLOG(e)
constexpr int IT_QA = 0, IT_O = 1, IT_S4 = 2, IT_END = 3, IT_KV = 4;
#define O_WIDE 10
#define OPF 0
#define ATT2 0
#define S4REL 4
#define KVP 0
#define KVS 8
#define STM 0
__device__ __forceinline__ void st_out(uint32_t* p, uint32_t v) {
    if (STM == 0) *p = v;
    else if (STM == 1) __stcs(p, v);
    else asm volatile("st.global.L1::no_allocate.u32 [%0], %1;" ::"l"(p), "r"(v) : "memory");
}
#define Q_N1 1
#define Q_S1 16
__device__ __forceinline__ int queue_item(int q) {
    if (KVP && q >= KVP && q < 512) return (IT_KV << 16) | (((q >> 6) * 2 + (q & 1)) << 8) | ((q >> 1) & 31);
    if (q < 512) return (IT_KV << 16) | ((q >> 5) << 8) | (q & 31);
    q -= 512;
    if (q < 256) return (IT_QA << 16) | ((q >> 4) << 8) | (q & 15);
    q -= 256;
    if (q < Q_N1 * 8) return (IT_O << 16) | ((O_WIDE + (q >> 3)) << 8) | (q & 7);
    q -= Q_N1 * 8;
    if (q < Q_S1) return (IT_S4 << 16) | q;
    q -= Q_S1;
    if (q < (16 - O_WIDE - Q_N1) * 8) return (IT_O << 16) | ((O_WIDE + Q_N1 + (q >> 3)) << 8) | (q & 7);
    q -= (16 - O_WIDE - Q_N1) * 8;
    if (q < 128 - Q_S1) return (IT_S4 << 16) | (Q_S1 + q);
    return IT_END << 16;
}
__device__ __forceinline__ void tma2d_store(const CUtensorMap* m, uint32_t src, int c0, int c1) {
    asm volatile("cp.async.bulk.tensor.2d.global.shared::cta.bulk_group [%0, {%2, %3}], [%1];" ::"l"(m), "r"(src), "r"(c0), "r"(c1) : "memory");
}

__device__ __forceinline__ void wgmma_s64(float (&d)[32], uint32_t a0, uint32_t a1, uint32_t a2, uint32_t a3, uint64_t db, int acc) {
    asm volatile("{.reg .pred p; setp.ne.b32 p, %37, 0;\n"
        "wgmma.mma_async.sync.aligned.m64n64k16.f32.bf16.bf16 {"
        "%0,%1,%2,%3,%4,%5,%6,%7,%8,%9,%10,%11,%12,%13,%14,%15,"
        "%16,%17,%18,%19,%20,%21,%22,%23,%24,%25,%26,%27,%28,%29,%30,%31"
        "}, {%32,%33,%34,%35}, %36, p, 1, 1, 0;}"
        : "+f"(d[0]), "+f"(d[1]), "+f"(d[2]), "+f"(d[3]), "+f"(d[4]), "+f"(d[5]), "+f"(d[6]), "+f"(d[7]), "+f"(d[8]), "+f"(d[9]), "+f"(d[10]), "+f"(d[11]), "+f"(d[12]), "+f"(d[13]), "+f"(d[14]), "+f"(d[15]), "+f"(d[16]), "+f"(d[17]), "+f"(d[18]), "+f"(d[19]), "+f"(d[20]), "+f"(d[21]), "+f"(d[22]), "+f"(d[23]), "+f"(d[24]), "+f"(d[25]), "+f"(d[26]), "+f"(d[27]), "+f"(d[28]), "+f"(d[29]), "+f"(d[30]), "+f"(d[31])
        : "r"(a0), "r"(a1), "r"(a2), "r"(a3), "l"(db), "r"(acc));
}
__device__ __forceinline__ void wgmma_s16(float (&d)[8], uint32_t a0, uint32_t a1, uint32_t a2, uint32_t a3, uint64_t db, int acc) {
    asm volatile("{.reg .pred p; setp.ne.b32 p, %13, 0;\n"
        "wgmma.mma_async.sync.aligned.m64n16k16.f32.bf16.bf16 {"
        "%0,%1,%2,%3,%4,%5,%6,%7"
        "}, {%8,%9,%10,%11}, %12, p, 1, 1, 0;}"
        : "+f"(d[0]), "+f"(d[1]), "+f"(d[2]), "+f"(d[3]), "+f"(d[4]), "+f"(d[5]), "+f"(d[6]), "+f"(d[7])
        : "r"(a0), "r"(a1), "r"(a2), "r"(a3), "l"(db), "r"(acc));
}
__device__ __forceinline__ void wgmma_v128(float (&d)[64], uint32_t a0, uint32_t a1, uint32_t a2, uint32_t a3, uint64_t db, int acc) {
    asm volatile("{.reg .pred p; setp.ne.b32 p, %69, 0;\n"
        "wgmma.mma_async.sync.aligned.m64n128k16.f32.bf16.bf16 {"
        "%0,%1,%2,%3,%4,%5,%6,%7,%8,%9,%10,%11,%12,%13,%14,%15,"
        "%16,%17,%18,%19,%20,%21,%22,%23,%24,%25,%26,%27,%28,%29,%30,%31,"
        "%32,%33,%34,%35,%36,%37,%38,%39,%40,%41,%42,%43,%44,%45,%46,%47,"
        "%48,%49,%50,%51,%52,%53,%54,%55,%56,%57,%58,%59,%60,%61,%62,%63"
        "}, {%64,%65,%66,%67}, %68, p, 1, 1, 1;}"
        : "+f"(d[0]), "+f"(d[1]), "+f"(d[2]), "+f"(d[3]), "+f"(d[4]), "+f"(d[5]), "+f"(d[6]), "+f"(d[7]), "+f"(d[8]), "+f"(d[9]), "+f"(d[10]), "+f"(d[11]), "+f"(d[12]), "+f"(d[13]), "+f"(d[14]), "+f"(d[15]), "+f"(d[16]), "+f"(d[17]), "+f"(d[18]), "+f"(d[19]), "+f"(d[20]), "+f"(d[21]), "+f"(d[22]), "+f"(d[23]), "+f"(d[24]), "+f"(d[25]), "+f"(d[26]), "+f"(d[27]), "+f"(d[28]), "+f"(d[29]), "+f"(d[30]), "+f"(d[31]), "+f"(d[32]), "+f"(d[33]), "+f"(d[34]), "+f"(d[35]), "+f"(d[36]), "+f"(d[37]), "+f"(d[38]), "+f"(d[39]), "+f"(d[40]), "+f"(d[41]), "+f"(d[42]), "+f"(d[43]), "+f"(d[44]), "+f"(d[45]), "+f"(d[46]), "+f"(d[47]), "+f"(d[48]), "+f"(d[49]), "+f"(d[50]), "+f"(d[51]), "+f"(d[52]), "+f"(d[53]), "+f"(d[54]), "+f"(d[55]), "+f"(d[56]), "+f"(d[57]), "+f"(d[58]), "+f"(d[59]), "+f"(d[60]), "+f"(d[61]), "+f"(d[62]), "+f"(d[63])
        : "r"(a0), "r"(a1), "r"(a2), "r"(a3), "l"(db), "r"(acc));
}

__device__ __forceinline__ void attn_scores(float (&sx)[32], float (&sm)[8], const uint32_t (&q)[32], uint32_t sk) {
    const uint64_t dx = mkdesc(sk, 1024, 128, 0), dm = mkdesc(sk + 16384, 256, 128, 0);
    wg_fence();
#pragma unroll
    for (int ks = 0; ks < 8; ks++) {
        wgmma_s64(sx, q[4 * ks], q[4 * ks + 1], q[4 * ks + 2], q[4 * ks + 3], dx + ks * 128, ks);
        wgmma_s16(sm, q[4 * ks], q[4 * ks + 1], q[4 * ks + 2], q[4 * ks + 3], dm + ks * 32, ks);
    }
    wg_commit();
}
__device__ __forceinline__ void attn_softmax(uint32_t (&p)[20], const float (&sx)[32], const float (&sm)[8], int wi, int lane) {
    const bool sb = wi >= 2;
    const int r0 = (wi & 1) * 16 + (lane >> 2) - 2 * (lane & 3);
    float s[5][4];
#pragma unroll
    for (int j = 0; j < 4; j++) s[4][j] = sb ? sm[4 + j] : sm[j];
    float m0 = fmaxf(s[4][0], s[4][1]), m1 = fmaxf(s[4][2], s[4][3]);
#pragma unroll
    for (int j = 0; j < 4; j++) {
#pragma unroll
        for (int e = 0; e < 4; e++) s[j][e] = 8 * j + (e & 1) > r0 + 8 * (e >> 1) ? -INFINITY : sb ? sx[16 + 4 * j + e] : sx[4 * j + e];
        m0 = fmaxf(m0, fmaxf(s[j][0], s[j][1])); m1 = fmaxf(m1, fmaxf(s[j][2], s[j][3]));
    }
    m0 = fmaxf(m0, __shfl_xor_sync(0xffffffffu, m0, 1)); m1 = fmaxf(m1, __shfl_xor_sync(0xffffffffu, m1, 1));
    m0 = fmaxf(m0, __shfl_xor_sync(0xffffffffu, m0, 2)); m1 = fmaxf(m1, __shfl_xor_sync(0xffffffffu, m1, 2));
    const float cs = 0.08838834764831845f * 1.4426950408889634f;
    m0 *= -cs; m1 *= -cs;
    float l0 = 0, l1 = 0;
#pragma unroll
    for (int j = 0; j < 5; j++) {
        s[j][0] = ex2(fmaf(s[j][0], cs, m0)); s[j][1] = ex2(fmaf(s[j][1], cs, m0));
        s[j][2] = ex2(fmaf(s[j][2], cs, m1)); s[j][3] = ex2(fmaf(s[j][3], cs, m1));
        l0 += s[j][0] + s[j][1]; l1 += s[j][2] + s[j][3];
    }
    l0 += __shfl_xor_sync(0xffffffffu, l0, 1); l1 += __shfl_xor_sync(0xffffffffu, l1, 1);
    l0 += __shfl_xor_sync(0xffffffffu, l0, 2); l1 += __shfl_xor_sync(0xffffffffu, l1, 2);
    asm("rcp.approx.ftz.f32 %0, %0;" : "+f"(l0)); asm("rcp.approx.ftz.f32 %0, %0;" : "+f"(l1));
    const uint32_t ma = sb ? 0u : ~0u;
#pragma unroll
    for (int j = 0; j < 5; j++) {
        const uint32_t x = pack_bf16(s[j][0] * l0, s[j][1] * l0), y = pack_bf16(s[j][2] * l1, s[j][3] * l1);
        const int ia = j < 4 ? 2 * j : 16, ib = j < 4 ? 8 + 2 * j : 18;
        asm volatile("and.b32 %0, %4, %6; and.b32 %1, %5, %6; and.b32 %2, %4, %7; and.b32 %3, %5, %7;"
            : "=&r"(p[ia]), "=&r"(p[ia + 1]), "=&r"(p[ib]), "=&r"(p[ib + 1]) : "r"(x), "r"(y), "r"(ma), "r"(~ma));
    }
}
__device__ __forceinline__ void attn_pv(float (&o)[64], const uint32_t (&p)[20], uint32_t sv) {
    const uint64_t dx = mkdesc(sv, 128, 1024, 0), dm = mkdesc(sv + 16384, 128, 256, 0);
    wg_fence();
#pragma unroll
    for (int ks = 0; ks < 5; ks++) wgmma_v128(o, p[4 * ks], p[4 * ks + 1], p[4 * ks + 2], p[4 * ks + 3], ks < 4 ? dx + ks * 16 : dm, ks);
    wg_commit();
}
__device__ __forceinline__ void attn_stage(const float (&o)[64], uint32_t dst) {
#pragma unroll
    for (int u = 0; u < 16; u += 2)
        stsm4(dst + (u >> 3) * 8192 + (u & 7) * 128, pack_bf16(o[4 * u], o[4 * u + 1]), pack_bf16(o[4 * u + 2], o[4 * u + 3]),
              pack_bf16(o[4 * u + 4], o[4 * u + 5]), pack_bf16(o[4 * u + 6], o[4 * u + 7]));
}

template <int BN, int NKB, bool BLOCKED_A>
__device__ __forceinline__ void mainloop(float (&acc)[BN / 2], uint32_t sb, int wgi, uint32_t full, uint32_t empty, int& it, bool elect) {
#pragma unroll
    for (int j = 0; j < BN / 2; j++) acc[j] = 0.f;
#pragma unroll 1
    for (int k4 = 0; k4 < NKB; k4 += 4) {
#pragma unroll
        for (int st = 0; st < 4; st++, it++) {
            mbar_wait(full + 8 * st, (it >> 2) & 1);
            const uint64_t da = BLOCKED_A ? mkdesc(sb + st * G_STAGE + wgi * 8192, 128, 1024, 0) : mkdesc(sb + st * G_STAGE + wgi * 8192, 16, 1024, 1);
            const uint64_t db = mkdesc(sb + st * G_STAGE + 16384, 8192, 1024, 1);
            wg_fence();
#pragma unroll
            for (int k = 0; k < 4; k++) {
                if constexpr (BN == 256) wgmma256(acc, da + k * (BLOCKED_A ? 16 : 2), db + k * 128, 1);
                else wgmma128(acc, da + k * (BLOCKED_A ? 16 : 2), db + k * 128, 1);
            }
            wg_commit();
            if (k4 | st) {
                wg_wait<1>();
                if (elect) mbar_arrive(empty + 8 * ((st + 3) & 3));
            }
        }
    }
    wg_wait<0>();
    if (elect) mbar_arrive(empty + 8 * 3);
}

__device__ __forceinline__ uint32_t n6_a(int st) { return st < 4 ? st * G_STAGE : (2 * st - 8) * G_STAGE + 32768; }
__device__ __forceinline__ uint32_t n6_b(int st) { return st < 4 ? st * G_STAGE + 16384 : (2 * st - 7) * G_STAGE + 32768; }
__device__ __forceinline__ uint32_t n6_bar(int st) { return st < 4 ? 8 * st : 96 + 8 * st; }
__device__ __forceinline__ void mainloop6(float (&acc)[64], uint32_t sb, int wgi, uint32_t full, uint32_t empty, int& it, bool elect) {
#pragma unroll
    for (int j = 0; j < 64; j++) acc[j] = 0.f;
    int st = 0, prev = 0, r = 0;
#pragma unroll 1
    for (int kb = 0; kb < 64; kb++) {
        mbar_wait(full + n6_bar(st), ((st < 4 ? it >> 2 : 0) + r) & 1);
        const uint64_t da = mkdesc(sb + n6_a(st) + wgi * 8192, 128, 1024, 0), db = mkdesc(sb + n6_b(st), 8192, 1024, 1);
        wg_fence();
#pragma unroll
        for (int k = 0; k < 4; k++) wgmma128(acc, da + k * 16, db + k * 128, 1);
        wg_commit();
        if (kb) {
            wg_wait<1>();
            if (elect) mbar_arrive(empty + n6_bar(prev));
        }
        prev = st;
        if (++st == 6) { st = 0; r++; }
    }
    wg_wait<0>();
    if (elect) mbar_arrive(empty + 8 * 3);
    it += 44;
}

template <int BN>
__device__ __forceinline__ void o_item(uint32_t sb, int wgi, int wi, int lane, uint32_t full, uint32_t empty, int& it, const CUtensorMap* mout,
                                       int row0, int col0, uint32_t stgpar) {
    float acc[BN / 2];
    if constexpr (BN == 256) mainloop<BN, 64, true>(acc, sb, wgi, full, empty, it, lane == 0);
    else mainloop6(acc, sb, wgi, full, empty, it, lane == 0);
    mbar_wait(full + 104, stgpar);
    const uint32_t stg = sb + G_STG + (wgi * 4 + wi) * 4096;
    const int r = lane & 15, cu = lane >> 4;
#pragma unroll
    for (int hf = 0; hf < BN / 128; hf++) {
        if (lane == 0) asm volatile("cp.async.bulk.wait_group.read 0;" ::: "memory");
        __syncwarp();
#pragma unroll
        for (int j = 0; j < 8; j++) {
            const float* a = acc + hf * 64 + j * 8;
            stsm4(stg + (j >> 2) * 2048 + r * 128 + ((((j & 3) * 2 + cu) ^ (r & 7)) << 4),
                  pack_bf16(a[0], a[1]), pack_bf16(a[2], a[3]), pack_bf16(a[4], a[5]), pack_bf16(a[6], a[7]));
        }
        asm volatile("fence.proxy.async.shared::cta;" ::: "memory");
        __syncwarp();
        if (lane == 0) {
            tma2d_store(mout, stg, col0 + hf * 128, row0 + wgi * 64 + wi * 16);
            tma2d_store(mout, stg + 2048, col0 + hf * 128 + 64, row0 + wgi * 64 + wi * 16);
            asm volatile("cp.async.bulk.commit_group;" ::: "memory");
        }
    }
}

constexpr int S4_KD = 32768;
constexpr int S4_CH = 2 * G_STAGE;
constexpr int S4_HALF = 2304;
constexpr int S4_WD = 2 * S4_HALF;
constexpr int S4_STRIDE = S4_WD + 2304 + 16;
__device__ __forceinline__ uint32_t addz(uint32_t x, uint32_t z) { uint32_t r; asm volatile("add.u32 %0, %1, %2;" : "=r"(r) : "r"(x), "r"(z)); return r; }
__device__ __forceinline__ uint32_t lds16(uint32_t a) { uint32_t v; asm volatile("ld.shared.u16 %0, [%1];" : "=r"(v) : "r"(a) : "memory"); return v; }
__device__ __forceinline__ uint32_t ldsu(uint32_t a) { return __float_as_uint(lds32(a)); }

template <int E0, int NE, int KP>
__device__ __forceinline__ void s4_windows(float (&acc)[8][2][4], uint32_t ut, uint32_t kd, int rho, int w, int lane, uint32_t z) {
    const int gt = (lane >> 2) - 2 * (lane & 3), p0 = rho == 16 ? -3 : -2, c = (lane >> 3) + p0;
    uint32_t band[2][4], tw[2 * NE + 1], ta[NE][4];
    {
        uint32_t f[5];
#pragma unroll
        for (int m = 0; m < 5; m++) {
            const int d = 8 * (p0 + m - 1) - gt + rho;
            f[m] = (abs(d) <= w ? 0x3F80u : 0u) | (abs(d + 1) <= w ? 0x3F800000u : 0u);
        }
#pragma unroll
        for (int j = 0; j < 2; j++) { band[j][0] = f[2 * j + 1]; band[j][1] = addz(f[2 * j], z); band[j][2] = f[2 * j + 2]; band[j][3] = addz(f[2 * j + 1], z); }
    }
#pragma unroll
    for (int m = 0; m < 2 * NE + 1; m++) {
        const int q = 8 * (2 * E0 - 1 + m) + gt;
        const uint32_t lo = lds16(kd + q * KP), hi = lds16(kd + (q - 1) * KP);
        tw[m] = ((unsigned)(q - 16 * E0) < 16 * E0 ? lo : 0u) | ((unsigned)(q - 1 - 16 * E0) < 16 * E0 ? hi << 16 : 0u);
    }
#pragma unroll
    for (int e = 0; e < NE; e++) { ta[e][0] = tw[2 * e + 1]; ta[e][1] = tw[2 * e + 2]; ta[e][2] = addz(tw[2 * e], z); ta[e][3] = addz(tw[2 * e + 1], z); }
    const uint32_t ua = ut + (c & 1) * S4_HALF + (16 + (lane & 7) + (c >> 1)) * 16;
#pragma unroll
    for (int J = 0; J < 8 - E0; J++) {
        uint32_t u0[4], u1[4];
        ldsm4(u0, ua + J * 256); ldsm4(u1, ua + J * 256 + 128);
        float s0[4], s1[4];
        mma16z(s0, band[0], u0[0], u0[1]); mma16z(s1, band[0], u1[0], u1[1]);
        mma16(s0, band[1], u0[2], u0[3]); mma16(s1, band[1], u1[2], u1[3]);
        const uint32_t b00 = pack_bf16(s0[0], s0[1]), b01 = pack_bf16(s1[0], s1[1]), b10 = pack_bf16(s0[2], s0[3]), b11 = pack_bf16(s1[2], s1[3]);
#pragma unroll
        for (int e = 0; e < NE; e++)
            if (J + E0 + e < 8) { mma16(acc[J + E0 + e][0], ta[e], b00, b01); mma16(acc[J + E0 + e][1], ta[e], b10, b11); }
    }
}
template <int D0, int D1>
__device__ __forceinline__ void s4_dense(float (&acc)[8][2][4], uint32_t ua, const uint32_t (&b0)[4], const uint32_t (&b1)[4]) {
#pragma unroll
    for (int J = 0; J < 8 - D0; J++) {
        uint32_t a[4];
        ldsm4(a, ua + J * 256);
        mma16(acc[J + D0][0], a, b0[0], b0[1]); mma16(acc[J + D0][1], a, b0[2], b0[3]);
        if (J + D1 < 8) { mma16(acc[J + D1][0], a, b1[0], b1[1]); mma16(acc[J + D1][1], a, b1[2], b1[3]); }
    }
}
__device__ __forceinline__ void s4_words(uint32_t (&b)[4], uint32_t wd) {
    asm volatile("ld.shared.u32 %0, [%4]; ld.shared.u32 %1, [%4+-32]; ld.shared.u32 %2, [%4+32]; ld.volatile.shared.u32 %3, [%4];"
        : "=r"(b[0]), "=r"(b[1]), "=r"(b[2]), "=r"(b[3]) : "r"(wd) : "memory");
}

__device__ __forceinline__ void s4_item(uint32_t sb, int cw, int lane, int item, const bf16* __restrict__ dsk, uint32_t empty, const CUtensorMap* my, uint32_t stgpar) {
    const int gt = (lane >> 2) - 2 * (lane & 3);
    const uint32_t ch = sb + S4_CH + cw * S4_STRIDE, kd = sb + S4_KD + cw * 1536;
    const __nv_bfloat162 dk = __bfloat162bfloat162(dsk[item * 8 + cw]);
    ST(item, cw, 0);
    asm volatile("st.shared.v4.u32 [%0], {%1,%1,%1,%1};" ::"r"(ch + (lane >> 4) * S4_HALF + (lane & 15) * 16), "r"(0) : "memory");
    const uint32_t tch = sb + S4_CH + (lane & 7) * S4_STRIDE + ((lane >> 3) & 1) * S4_HALF + (16 + 16 * cw + (lane >> 4)) * 16;
#pragma unroll
    for (int i = 0; i < 8; i++) {
        uint32_t x[4];
        ldsm4t(x, sb + cw * 4096 + i * 512 + lane * 16);
        stsm4(tch + i * 32, x[0], x[1], x[2], x[3]);
    }
#pragma unroll 3
    for (int x0 = lane * 2 - 16; x0 < 560; x0 += 64) {
        uint32_t k[3];
#pragma unroll
        for (int j = 0; j < 3; j++) {
            const int x = x0 + j - 1, idx = x < 256 ? max(x, 0) : min(128 + ((x + ((x >> 1) & 1)) >> 1), 384);
            k[j] = lds16(kd + idx * 2);
            if ((unsigned)x > 514u) k[j] = 0;
        }
        asm volatile("st.shared.v2.u32 [%0], {%1,%2};" ::"r"(ch + S4_WD + 64 + x0 * 4), "r"(k[1] | (k[0] << 16)), "r"(k[2] | (k[1] << 16)) : "memory");
    }
    const uint32_t k1024 = lds16(kd + 1024);
    bar_sync(2, 256);
    ST(item, cw, 1);
    const uint32_t z = ldsu(ch);
    float acc[8][2][4];
#pragma unroll
    for (int j = 0; j < 16; j++) acc[j >> 1][j & 1][0] = acc[j >> 1][j & 1][1] = acc[j >> 1][j & 1][2] = acc[j >> 1][j & 1][3] = 0.f;
#pragma unroll 1
    for (int r = 1; r <= 4; r++) s4_windows<2, 3, 8>(acc, ch, kd + 512 + 2 * r, 4 * r, 2 - (r & 1), lane, z);
    ST(item, cw, 2);
#pragma unroll 1
    for (int r = 1; r <= 2; r++) s4_windows<4, 4, 4>(acc, ch, kd + 768 + 2 * r, 8 * r, 2 + r, lane, z);
    ST(item, cw, 3);
    const uint32_t ua = ch + (lane >> 4) * S4_HALF + (16 + (lane & 15)) * 16, wd = ch + S4_WD + 64 + gt * 4;
#pragma unroll 1
    for (int q = 0; q < 2; q++) {
        uint32_t b0[4], b1[4];
        s4_words(b0, wd + (q + 32) * 64);
#pragma unroll
        for (int j = 0; j < 4; j++) {
            const int x = 16 * q + gt + (j == 1 ? -8 : j == 2 ? 8 : 0) - 3;
            b1[j] = addz(((unsigned)x < 2u ? k1024 : 0u) | ((unsigned)(x - 1) < 2u ? k1024 << 16 : 0u), z);
        }
        s4_dense<2, 4>(acc, ua - q * 16, b0, b1);
    }
    {
        uint32_t b0[4], b1[4], c0[4], c1[4];
        s4_words(b0, wd); s4_words(b1, wd + 1024);
#pragma unroll 1
        for (int q = 0; q < 16; q += 2) {
            s4_words(c0, wd + q * 64 + 64); s4_words(c1, wd + q * 64 + 64 + 1024);
            s4_dense<0, 1>(acc, ua - q * 16, b0, b1);
            s4_words(b0, wd + q * 64 + 128); s4_words(b1, wd + q * 64 + 128 + 1024);
            s4_dense<0, 1>(acc, ua - q * 16 - 16, c0, c1);
            if (q == S4REL && lane == 0) { mbar_arrive(empty); mbar_arrive(empty + 8); }
        }
    }
    ST(item, cw, 4);
    mbar_wait(empty + 72, stgpar);
    if (lane == 0) asm volatile("cp.async.bulk.wait_group.read 0;" ::: "memory");
    __syncwarp();
#pragma unroll
    for (int I = 0; I < 8; I++) {
        uint32_t u[4];
        ldsm4(u, ua + I * 256);
#pragma unroll
        for (int j = 0; j < 4; j++) {
            const uint32_t y = pack_bf16(acc[I][j >> 1][2 * (j & 1)], acc[I][j >> 1][2 * (j & 1) + 1]);
            const __nv_bfloat162 r = __hadd2_rn(*(const __nv_bfloat162*)&y, __hmul2_rn(*(const __nv_bfloat162*)&u[j], dk));
            u[j] = *(const uint32_t*)&r;
        }
        stsm4(ua + I * 256, u[0], u[1], u[2], u[3]);
    }
    bar_sync(2, 256);
#pragma unroll
    for (int i = 0; i < 8; i++) {
        uint32_t y[4];
        ldsm4t(y, tch + i * 32);
        stsm4(sb + G_STG + cw * 4096 + i * 512 + lane * 16, y[0], y[1], y[2], y[3]);
    }
    asm volatile("fence.proxy.async.shared::cta;" ::: "memory");
    __syncwarp();
    if (lane == 0) {
        mbar_arrive(empty + 16); mbar_arrive(empty + 24);
        tma2d_store(my, sb + G_STG + cw * 4096, DM + item * 8, cw * 256);
        asm volatile("cp.async.bulk.commit_group;" ::: "memory");
    }
    ST(item, cw, 5);
}

__global__ void __launch_bounds__(384, 1)
worker_kernel(const __grid_constant__ CUtensorMap mx, const __grid_constant__ CUtensorMap mq, const __grid_constant__ CUtensorMap mk,
              const __grid_constant__ CUtensorMap mv, const __grid_constant__ CUtensorMap mo,
              const __grid_constant__ CUtensorMap mout, const __grid_constant__ CUtensorMap mu, const __grid_constant__ CUtensorMap my,
              const __grid_constant__ CUtensorMap mkx, const __grid_constant__ CUtensorMap mvx, const __grid_constant__ CUtensorMap mkm,
              const __grid_constant__ CUtensorMap mvm, const bf16* __restrict__ dsk) {
    extern __shared__ unsigned char smem_raw[];
    const uint32_t sb = (smem_u32(smem_raw) + 1023) & ~1023u;
    const uint32_t full = sb + G_BAR, empty = full + 32, ifull = full + 64, iempty = full + 80, islot = full + 96, stgbar = full + 104, sigbar = full + 112, sigslot = full + 120;
    const int tid = threadIdx.x, wg = tid >> 7, lane = tid & 31;
    int q0 = blockIdx.x;
    const int wide0 = q0 - ((int)gridDim.x - O_WIDE * 4);
    if (tid == 0) {
        if (q0 >= 32 && wide0 < 0) q0 = 32 + atomicAdd(g_ctr + C_NEXT, 1);
        for (int i = 0; i < 6; i++) { mbar_init(full + n6_bar(i), 1); mbar_init(empty + n6_bar(i), 8); }
        for (int i = 0; i < 2; i++) { mbar_init(ifull + 8 * i, 1); mbar_init(iempty + 8 * i, 8); }
        mbar_init(sigbar, 8); mbar_init(stgbar, 1);
        asm volatile("fence.proxy.async;" ::: "memory");
    }
    __syncthreads();
    if (wg == 0) {
        reg_dec<40>();
        if (tid >= 32 && tid < 64) {
            for (int n = 0;; n++) {
                mbar_wait_long(sigbar, n & 1);
                int item; asm volatile("ld.shared.u32 %0, [%1];" : "=r"(item) : "r"(sigslot + 4 * (n & 1)) : "memory");
                const int type = item >> 16, b = (item >> 8) & 255, i = item & 255;
                if (type == IT_END) break;
                if (type == IT_QA) {
                    if (lane == 0) {
                        for (int j = 0; j < 8; j++) {
                            const uint32_t src = sb + (j >= 4 ? G_STG + (j & 1) * 16384 : 3 * G_STAGE + (j & 1) * 20480) + ((j >> 1) & 1) * 8192;
                            asm volatile("cp.async.bulk.global.shared::cta.bulk_group [%0], [%1], 8192;"
                                ::"l"(g_ox + (size_t)(b * 64 + i * 4 + ((j >> 1) ^ 2)) * 8192 + (j & 1) * 4096), "r"(src) : "memory");
                            if ((j & 3) == 3) asm volatile("cp.async.bulk.commit_group;" ::: "memory");
                        }
                        asm volatile("cp.async.bulk.wait_group.read 1;" ::: "memory");
                        asm volatile("mbarrier.arrive.shared.b64 _, [%0], 8;" ::"r"(empty + 24) : "memory");
                        asm volatile("cp.async.bulk.wait_group 0;" ::: "memory");
                        mbar_arrive(stgbar);
                        asm volatile("fence.proxy.async;" ::: "memory");
                    }
                    __syncwarp();
                }
                __threadfence();
                if (type == IT_KV) { if (lane < 6) atomicAdd(g_kvf + ((i & 15) * 6 + lane) * 16 + b, 1); }
                else if (lane == 0) atomicAdd(g_ctr + C_QA_DONE + b, 1);
            }
        } else if (tid < 32) {
            int it = 0;
            if (!KVN) asm volatile("griddepcontrol.wait;" ::: "memory");
            for (int n = 0;; n++) {
                int item = 0;
                if (lane == 0) {
                    const int q = n == 0 ? q0 : 32 + atomicAdd(g_ctr + C_NEXT, 1);
                    item = n == 0 && wide0 >= 0 ? (IT_O << 16) | ((wide0 >> 2) << 8) | (wide0 & 3) : queue_item(q);
                }
                item = __shfl_sync(0xffffffffu, item, 0);
                if (lane == 0) {
                    mbar_wait(iempty + 8 * (n & 1), ((n >> 1) & 1) ^ 1);
                    asm volatile("st.shared.u32 [%0], %1;" ::"r"(islot + 4 * (n & 1)), "r"(item) : "memory");
                    mbar_arrive(ifull + 8 * (n & 1));
                    const int type = item >> 16, b = (item >> 8) & 255, i = item & 255;
                    if (type == IT_QA || type == IT_KV) {
                        const CUtensorMap* mw = type == IT_QA ? &mq : i < 16 ? &mk : &mv;
                        bool ready = false;
                        for (int kb = 0; kb < 16; kb++, it++) {
                            const int st = it & 3;
                            mbar_wait(empty + 8 * st, ((it >> 2) & 1) ^ 1);
                            mbar_expect(full + 8 * st, G_STAGE);
                            const uint32_t a = sb + st * G_STAGE;
                            tma2d(a, &mx, kb * 64, b * 128, full + 8 * st);
                            tma3d(a + 16384, mw, 0, kb * 64, (i & 15) * 4, full + 8 * st);
                            tma3d(a + 32768, mw, 0, kb * 64, (i & 15) * 4 + 2, full + 8 * st);
                            if (type == IT_QA && kb == 3) ready = ld_acq(g_ctr + C_CHAIN + b) >= 96;
                            if (type == IT_QA && kb >= 3 && kb < 11) {
                                const size_t sh = (b * 4 + ((kb - 3) & 3)) * NH + i * 2;
                                asm volatile("cp.async.bulk.prefetch.L2.global [%0], 16384;" ::"l"((kb >= 7 ? g_vx : g_kx) + sh * 4096) : "memory");
                                if (ready) asm volatile("cp.async.bulk.prefetch.L2.global [%0], 4096;" ::"l"((kb >= 7 ? g_vm : g_km) + sh * 1024) : "memory");
                            }
                        }
                    }
                    if (type == IT_QA) {
                        wait_ctr(g_ctr + C_CHAIN + b, 96);
                        asm volatile("fence.proxy.async;" ::: "memory");
                        for (int st = 0; st < 4; st++, it++) {
                            mbar_wait(empty + 8 * st, ((it >> 2) & 1) ^ 1);
                            mbar_expect(full + 8 * st, 4 * 10240);
                            for (int g2 = 0; g2 < 2; g2++) {
                                tma3d(sb + st * G_STAGE + g2 * 20480, st < 2 ? &mkx : &mvx, 0, b * 4 + g2 * 2, (i * 2 + (st & 1)) * 16, full + 8 * st);
                                tma3d(sb + st * G_STAGE + g2 * 20480 + 16384, st < 2 ? &mkm : &mvm, 0, b * 4 + g2 * 2, (i * 2 + (st & 1)) * 16, full + 8 * st);
                            }
                        }
                    } else if (type == IT_O) {
                        const bool wide = b < O_WIDE;
                        wait_ctr(g_ctr + C_QA_DONE + b, 16);
                        asm volatile("fence.proxy.async;" ::: "memory");
                        if (OPF)
                            for (int j = i; j < 64; j += wide ? 4 : 8)
                                if (j >= 6) asm volatile("cp.async.bulk.prefetch.L2.global [%0], 16384;" ::"l"(g_ox + (size_t)(b * 64 + j) * 8192) : "memory");
                        const int ns = wide ? 4 : 6;
                        for (int kb = 0, st = 0, r = 0; kb < 64; kb++) {
                            const uint32_t bo = n6_bar(st);
                            mbar_wait(empty + bo, (((st < 4 ? it >> 2 : 0) + r) & 1) ^ 1);
                            mbar_expect(full + bo, wide ? G_STAGE : 32768);
                            bulk_load(sb + n6_a(st), g_ox + (size_t)(b * 64 + kb) * 8192, 16384, full + bo);
                            tma3d(sb + n6_b(st), &mo, 0, kb * 64, wide ? i * 4 : i * 2, full + bo);
                            if (wide) tma3d(sb + n6_b(st) + 16384, &mo, 0, kb * 64, i * 4 + 2, full + bo);
                            if (++st == ns) { st = 0; r++; }
                        }
                        it += wide ? 64 : 44;
                    } else if (type == IT_S4) {
                        wait_ctr(g_ctr + C_CHAIN, 96);
                        asm volatile("fence.proxy.async;" ::: "memory");
                        mbar_wait(empty, ((it >> 2) & 1) ^ 1);
                        mbar_expect(full, 32768 + 12288);
                        bulk_load(sb + S4_KD, g_kd + i * 8 * 768, 12288, full);
                        for (int j = 0; j < 8; j++) tma2d(sb + j * 4096, &mu, i * 8, j * 256, full);
                        for (int st = 1; st < 4; st++) { mbar_wait(empty + 8 * st, ((it >> 2) & 1) ^ 1); mbar_arrive(full + 8 * st); }
                        it += 4;
                        mbar_wait_long(empty, ((it >> 2) & 1) ^ 1);
                    }
                }
                __syncwarp();
                if (item >> 16 == IT_END) break;
            }
            asm volatile("griddepcontrol.wait;" ::: "memory");
        }
    } else {
        reg_inc<232>();
        const int wu = __shfl_sync(0xffffffffu, tid >> 5, 0);
        const int wgi = (wu >> 2) - 1, wi = wu & 3;
        int it = 0, nqa = 0, nsig = 0, n = 0, item;
        auto next_item = [&]() {
            mbar_wait_long(ifull + 8 * (n & 1), (n >> 1) & 1);
            asm volatile("ld.shared.u32 %0, [%1];" : "=r"(item) : "r"(islot + 4 * (n & 1)) : "memory");
            __syncwarp();
            if (lane == 0) mbar_arrive(iempty + 8 * (n & 1));
        };
        auto signal = [&](int what) {
            if (tid == 128) asm volatile("st.shared.u32 [%0], %1;" ::"r"(sigslot + 4 * (nsig & 1)), "r"(what) : "memory");
            __syncwarp();
            if (lane == 0) mbar_arrive(sigbar);
            nsig++;
        };
        next_item();
        if (item >> 16 == IT_KV) {
            float acc[128];
            uint32_t pk[64];
            uint32_t* dst = nullptr;
            int prev = 0;
            do {
                WLOG(0);
#pragma unroll
                for (int kb = 0; kb < 16; kb++, it++) {
                    const int st = kb & 3;
                    mbar_wait(full + 8 * st, (it >> 2) & 1);
                    const uint64_t da = mkdesc(sb + st * G_STAGE + wgi * 8192, 16, 1024, 1);
                    const uint64_t db = mkdesc(sb + st * G_STAGE + 16384, 8192, 1024, 1);
                    wg_fence();
#pragma unroll
                    for (int k = 0; k < 4; k++) wgmma256(acc, da + k * 2, db + k * 128, kb | k);
                    wg_commit();
                    if (kb < KVS && dst) {
#pragma unroll
                        for (int j = kb * (64 / KVS); j < (kb + 1) * (64 / KVS); j++) st_out(dst + (j >> 1) * 128 + (j & 1) * 32, pk[j]);
                        if (kb == KVS - 1) signal(prev);
                    }
                    if (kb > 0) {
                        wg_wait<1>();
                        if (lane == 0) mbar_arrive(empty + 8 * ((kb - 1) & 3));
                    }
                }
                wg_wait<0>();
                if (lane == 0) mbar_arrive(empty + 8 * 3);
#pragma unroll
                for (int j = 0; j < 64; j++) pk[j] = pack_bf16(acc[2 * j], acc[2 * j + 1]);
                const int row = ((item >> 8) & 255) * 128 + wgi * 64 + wi * 16, nt = item & 255;
                dst = (uint32_t*)(nt < 16 ? g_kx : g_vx) + (size_t)((row >> 5) * 512 + (nt & 15) * 32) * 128 + (row & 31) * 4 + lane;
                prev = item;
                if (n == 0) {
#pragma unroll
                    for (int j = 0; j < 64; j++) dst[(j >> 1) * 128 + (j & 1) * 32] = pk[j];
                    signal(prev);
                    dst = nullptr;
                }
                WLOG(1);
                n++;
                next_item();
            } while (item >> 16 == IT_KV);
            if (dst) {
#pragma unroll
                for (int j = 0; j < 64; j++) dst[(j >> 1) * 128 + (j & 1) * 32] = pk[j];
                signal(prev);
            }
        }
        for (;; n++, next_item()) {
            const int type = item >> 16, b = (item >> 8) & 255, i = item & 255;
            const int lane = (tid & 31) + (item >> 24), wgi = (wu >> 2) - 1 + __shfl_sync(0xffffffffu, item >> 24, 0), wi = wu & 3;
            WLOG(0);
            if (type == IT_QA) {
                float acc[128];
                ST(sid, cw, 0);
                ST(sid, cw, 1);
                mainloop<256, 16, false>(acc, sb, wgi, full, empty, it, lane == 0);
                ST(sid, cw, 2);
                uint32_t q0[32], q1[32];
#pragma unroll
                for (int j = 0; j < 32; j++) { q0[j] = pack_bf16(acc[2 * j], acc[2 * j + 1]); q1[j] = pack_bf16(acc[64 + 2 * j], acc[65 + 2 * j]); }
                const uint32_t par = (it >> 2) & 1, so = sb + wgi * 20480;
                float sx0[32] = {}, sm0[8] = {}, sx1[32] = {}, sm1[8] = {};
                uint32_t p0[20], p1[20];
                if (lane == 0) asm volatile("cp.async.bulk.wait_group.read 0;" ::: "memory");
                mbar_wait(stgbar, (nqa++ & 1) ^ 1);
                bar_sync(3 + wgi, 128);
                mbar_wait_long(full, par);
                ST(sid, cw, 3);
                attn_scores(sx0, sm0, q0, so);
                ST(sid, cw, 7);
                mbar_wait(full + 8, par);
                attn_scores(sx1, sm1, q1, so + G_STAGE);
                float o0[64] = {}, o1[64] = {};
                if (ATT2) {
                    ST(sid, cw, 8);
                    wg_wait<0>();
                    ST(sid, cw, 9);
                    if (lane == 0) { mbar_arrive(empty); mbar_arrive(empty + 8); }
                    attn_softmax(p0, sx0, sm0, wi, lane);
                    attn_softmax(p1, sx1, sm1, wi, lane);
                    ST(sid, cw, 10);
                    mbar_wait(full + 16, par);
                    ST(sid, cw, 11);
                    attn_pv(o0, p0, so + 2 * G_STAGE);
                    ST(sid, cw, 4);
                } else {
                    wg_wait<1>();
                    if (lane == 0) mbar_arrive(empty);
                    attn_softmax(p0, sx0, sm0, wi, lane);
                    mbar_wait(full + 16, par);
                    attn_pv(o0, p0, so + 2 * G_STAGE);
                    wg_wait<1>();
                    if (lane == 0) mbar_arrive(empty + 8);
                    ST(sid, cw, 4);
                    attn_softmax(p1, sx1, sm1, wi, lane);
                }
                mbar_wait(full + 24, par);
                attn_pv(o1, p1, so + 3 * G_STAGE);
                wg_wait<1>();
                if (lane == 0) mbar_arrive(empty + 16);
                ST(sid, cw, 5);
                const uint32_t da = (wi * 2 + ((lane >> 3) & 1)) * 1024 + (lane >> 4) * 128 + (lane & 7) * 16;
                attn_stage(o0, sb + G_STG + wgi * 16384 + da);
                wg_wait<0>();
                bar_sync(3 + wgi, 128);
                attn_stage(o1, so + 3 * G_STAGE + da);
                asm volatile("fence.proxy.async.shared::cta;" ::: "memory");
                ST(sid, cw, 6);
                signal(item);
                it += 4;
            } else if (type == IT_O) {
                mbar_wait_long(full, (it >> 2) & 1);
                if (b < O_WIDE) o_item<256>(sb, wgi, wi, lane, full, empty, it, &mout, b * 128, i * 256, (nqa & 1) ^ 1);
                else o_item<128>(sb, wgi, wi, lane, full, empty, it, &mout, b * 128, i * 128, (nqa & 1) ^ 1);
            } else if (type == IT_S4) {
                mbar_wait_long(full, (it >> 2) & 1);
                mbar_wait(full + 24, (it >> 2) & 1);
                s4_item(sb, wgi * 4 + wi, lane, i, dsk, empty, &my, (nqa & 1) ^ 1);
                it += 4;
            } else break;
            WLOG(1);
        }
        bar_sync(2, 256);
        signal(item);
        if (lane == 0) asm volatile("cp.async.bulk.wait_group 0;" ::: "memory");
    }
}

typedef CUresult (*EncodeFn)(CUtensorMap*, CUtensorMapDataType, cuuint32_t, void*, const cuuint64_t*, const cuuint64_t*, const cuuint32_t*,
                             const cuuint32_t*, CUtensorMapInterleave, CUtensorMapSwizzle, CUtensorMapL2promotion, CUtensorMapFloatOOBfill);
static EncodeFn get_encode() {
    void* fn = nullptr; cudaDriverEntryPointQueryResult st;
    cudaGetDriverEntryPoint("cuTensorMapEncodeTiled", &fn, cudaEnableDefault, &st);
    return (EncodeFn)fn;
}
static void map_act(EncodeFn enc, CUtensorMap* m, const void* p, int rows, int cols, int boxr) {
    cuuint64_t dim[2] = {(cuuint64_t)cols, (cuuint64_t)rows}, str[1] = {(cuuint64_t)cols * 2};
    cuuint32_t box[2] = {64, (cuuint32_t)boxr}, es[2] = {1, 1};
    enc(m, CU_TENSOR_MAP_DATA_TYPE_BFLOAT16, 2, (void*)p, dim, str, box, es, CU_TENSOR_MAP_INTERLEAVE_NONE, CU_TENSOR_MAP_SWIZZLE_128B,
        CU_TENSOR_MAP_L2_PROMOTION_L2_128B, CU_TENSOR_MAP_FLOAT_OOB_FILL_NONE);
}
static void map_w(EncodeFn enc, CUtensorMap* m, const void* p, int k, int n) {
    cuuint64_t dim[3] = {64, (cuuint64_t)k, (cuuint64_t)n / 64}, str[2] = {(cuuint64_t)n * 2, 128};
    cuuint32_t box[3] = {64, 64, 2}, es[3] = {1, 1, 1};
    enc(m, CU_TENSOR_MAP_DATA_TYPE_BFLOAT16, 3, (void*)p, dim, str, box, es, CU_TENSOR_MAP_INTERLEAVE_NONE, CU_TENSOR_MAP_SWIZZLE_128B,
        CU_TENSOR_MAP_L2_PROMOTION_L2_256B, CU_TENSOR_MAP_FLOAT_OOB_FILL_NONE);
}

static void map_kv(EncodeFn enc, CUtensorMap* m, void* p, int n) {
    cuuint64_t dim[3] = {(cuuint64_t)n, NSEG, 512}, str[2] = {(cuuint64_t)n * 1024, (cuuint64_t)n * 2};
    cuuint32_t box[3] = {(cuuint32_t)n, 2, 16}, es[3] = {1, 1, 1};
    enc(m, CU_TENSOR_MAP_DATA_TYPE_BFLOAT16, 3, p, dim, str, box, es, CU_TENSOR_MAP_INTERLEAVE_NONE, CU_TENSOR_MAP_SWIZZLE_NONE,
        CU_TENSOR_MAP_L2_PROMOTION_NONE, CU_TENSOR_MAP_FLOAT_OOB_FILL_NONE);
}
static void map_box(EncodeFn enc, CUtensorMap* m, const void* p, int rows, int ld, int boxc, int boxr, CUtensorMapSwizzle sw) {
    cuuint64_t dim[2] = {(cuuint64_t)ld, (cuuint64_t)rows}, str[1] = {(cuuint64_t)ld * 2};
    cuuint32_t box[2] = {(cuuint32_t)boxc, (cuuint32_t)boxr}, es[2] = {1, 1};
    enc(m, CU_TENSOR_MAP_DATA_TYPE_BFLOAT16, 2, (void*)p, dim, str, box, es, CU_TENSOR_MAP_INTERLEAVE_NONE, sw,
        CU_TENSOR_MAP_L2_PROMOTION_NONE, CU_TENSOR_MAP_FLOAT_OOB_FILL_NONE);
}

extern "C" void kernel_launch(void* const* d_in, const int* in_sizes, int n_in, void* d_out, int out_size) {
    const bf16* x = (const bf16*)d_in[0];
    const bf16* mem0 = (const bf16*)d_in[1];
    const bf16 *Wq = (const bf16*)d_in[2], *Wk = (const bf16*)d_in[3], *Wv = (const bf16*)d_in[4], *Wo = (const bf16*)d_in[5];
    static EncodeFn enc = nullptr;
    static int nsm = 0;
    static void* kv[4];
    if (!enc) {
        enc = get_encode();
        cudaGetSymbolAddress(&kv[0], g_kx); cudaGetSymbolAddress(&kv[1], g_vx); cudaGetSymbolAddress(&kv[2], g_km); cudaGetSymbolAddress(&kv[3], g_vm);
        cudaDeviceGetAttribute(&nsm, cudaDevAttrMultiProcessorCount, 0);
        cudaFuncSetAttribute(chain_kernel, cudaFuncAttributeMaxDynamicSharedMemorySize, CH_SMEM);
        cudaFuncSetAttribute(worker_kernel, cudaFuncAttributeMaxDynamicSharedMemorySize, G_SMEM);
    }
    CUtensorMap mx, mq, mk, mv, mo, mout, mu, my;
    map_act(enc, &mx, x, S_LEN, DM, 128);
    map_w(enc, &mq, Wq, DM, HD); map_w(enc, &mk, Wk, DM, HD); map_w(enc, &mv, Wv, DM, HD); map_w(enc, &mo, Wo, HD, DM);
    map_box(enc, &mout, d_out, S_LEN, 2 * DM, 64, 16, CU_TENSOR_MAP_SWIZZLE_128B);
    map_box(enc, &mu, d_in[7], S_LEN, DM, 8, 256, CU_TENSOR_MAP_SWIZZLE_NONE);
    map_box(enc, &my, d_out, S_LEN, 2 * DM, 8, 256, CU_TENSOR_MAP_SWIZZLE_NONE);
    CUtensorMap mkx, mvx, mkm, mvm;
    map_kv(enc, &mkx, kv[0], 256); map_kv(enc, &mvx, kv[1], 256); map_kv(enc, &mkm, kv[2], 64); map_kv(enc, &mvm, kv[3], 64);
    CUtensorMap cq, ck, cv, co;
    map_box(enc, &cq, Wq, DM, HD, 32, 32, CU_TENSOR_MAP_SWIZZLE_64B); map_box(enc, &ck, Wk, DM, HD, 32, 32, CU_TENSOR_MAP_SWIZZLE_64B);
    map_box(enc, &cv, Wv, DM, HD, 32, 32, CU_TENSOR_MAP_SWIZZLE_64B); map_box(enc, &co, Wo, HD, DM, 32, 16, CU_TENSOR_MAP_SWIZZLE_64B);
    S4Params P = {(const bf16*)d_in[8], (const bf16*)d_in[9], (const bf16*)d_in[10], (const bf16*)d_in[11],
                  (const bf16*)d_in[12], (const bf16*)d_in[13], (const bf16*)d_in[14], (const bf16*)d_in[15]};
    int aware = 1;
    cudaLaunchAttribute at[1];
    at[0].id = cudaLaunchAttributeProgrammaticStreamSerialization;
    at[0].val.programmaticStreamSerializationAllowed = 1;
    cudaLaunchConfig_t cfg = {};
    cfg.stream = cudaStreamPerThread;
    cfg.gridDim = dim3(96); cfg.blockDim = dim3(CH_THREADS); cfg.dynamicSmemBytes = CH_SMEM;
    cudaLaunchKernelEx(&cfg, chain_kernel, cq, ck, cv, co, Wq, Wk, Wv, mem0, P, aware);
    cfg.attrs = at; cfg.numAttrs = 1;
    cfg.gridDim = dim3(nsm); cfg.blockDim = dim3(384); cfg.dynamicSmemBytes = G_SMEM;
    cudaLaunchKernelEx(&cfg, worker_kernel, mx, mq, mk, mv, mo, mout, mu, my, mkx, mvx, mkm, mvm, P.dsk);
}
```

```cpp
#include <cuda.h>
#include <cuda_runtime.h>
#include <cuda_bf16.h>
#include <stdint.h>
#include <stdio.h>
#include <string.h>

typedef __nv_bfloat16 bf16;

constexpr int S_LEN = 2048, DM = 1024, NH = 32, DH = 128, HD = 4096, NSEG = 64;
constexpr uint32_t SENT = 0xFFFFFFFFu;
constexpr int SPIN_LIMIT = 1 << 18;
#define REALL 0

__device__ __align__(1024) bf16 g_kx[S_LEN * HD];
__device__ __align__(1024) bf16 g_vx[S_LEN * HD];
__device__ __align__(1024) bf16 g_ox[S_LEN * HD];
__device__ __align__(1024) bf16 g_km[NSEG * NH * 8 * DH];
__device__ __align__(1024) bf16 g_vm[NSEG * NH * 8 * DH];
__device__ __align__(1024) bf16 g_kd[DM * 768 + 8192];
__device__ __align__(1024) char g_ring[2 << 20];
__device__ int g_kvf[96 * 16];
constexpr int C_NEXT = 0, C_CHAIN = 32, C_QA_DONE = 64, N_CTR = 96;
__device__ int g_ctr[N_CTR];

__device__ __forceinline__ uint32_t smem_u32(const void* p) { return (uint32_t)__cvta_generic_to_shared(p); }
__device__ __forceinline__ uint32_t clk() { uint32_t c; asm volatile("mov.u32 %0, %%clock;" : "=r"(c)::"memory"); return c; }
__device__ __forceinline__ uint32_t pack_bf16(float lo, float hi) {
    uint32_t r; asm("cvt.rn.bf16x2.f32 %0, %1, %2;" : "=r"(r) : "f"(hi), "f"(lo)); return r;
}
__device__ __forceinline__ uint32_t movm(uint32_t a) {
    uint32_t d; asm volatile("movmatrix.sync.aligned.m8n8.trans.b16 %0, %1;" : "=r"(d) : "r"(a)); return d;
}
__device__ __forceinline__ void mma16(float (&d)[4], const uint32_t (&a)[4], uint32_t b0, uint32_t b1) {
    asm volatile("mma.sync.aligned.m16n8k16.row.col.f32.bf16.bf16.f32 {%0,%1,%2,%3}, {%4,%5,%6,%7}, {%8,%9}, {%0,%1,%2,%3};"
        : "+f"(d[0]), "+f"(d[1]), "+f"(d[2]), "+f"(d[3]) : "r"(a[0]), "r"(a[1]), "r"(a[2]), "r"(a[3]), "r"(b0), "r"(b1));
}
__device__ __forceinline__ void mma16z(float (&d)[4], const uint32_t (&a)[4], uint32_t b0, uint32_t b1) {
    asm volatile("mma.sync.aligned.m16n8k16.row.col.f32.bf16.bf16.f32 {%0,%1,%2,%3}, {%4,%5,%6,%7}, {%8,%9}, {%10,%10,%10,%10};"
        : "=f"(d[0]), "=f"(d[1]), "=f"(d[2]), "=f"(d[3]) : "r"(a[0]), "r"(a[1]), "r"(a[2]), "r"(a[3]), "r"(b0), "r"(b1), "f"(0.f));
}
__device__ __forceinline__ void mma8z(float (&d)[4], uint32_t a0, uint32_t a1, uint32_t b0) {
    asm volatile("mma.sync.aligned.m16n8k8.row.col.f32.bf16.bf16.f32 {%0,%1,%2,%3}, {%4,%5}, {%6}, {%7,%7,%7,%7};"
        : "=f"(d[0]), "=f"(d[1]), "=f"(d[2]), "=f"(d[3]) : "r"(a0), "r"(a1), "r"(b0), "f"(0.f));
}
__device__ __forceinline__ void ldsm4t(uint32_t (&r)[4], uint32_t addr) {
    asm volatile("ldmatrix.sync.aligned.m8n8.x4.trans.shared.b16 {%0,%1,%2,%3}, [%4];"
        : "=r"(r[0]), "=r"(r[1]), "=r"(r[2]), "=r"(r[3]) : "r"(addr) : "memory");
}
__device__ __forceinline__ void ldsm4(uint32_t (&r)[4], uint32_t addr) {
    asm volatile("ldmatrix.sync.aligned.m8n8.x4.shared.b16 {%0,%1,%2,%3}, [%4];"
        : "=r"(r[0]), "=r"(r[1]), "=r"(r[2]), "=r"(r[3]) : "r"(addr) : "memory");
}
__device__ __forceinline__ float lds32(uint32_t a) {
    float v; asm volatile("ld.shared.f32 %0, [%1];" : "=f"(v) : "r"(a) : "memory"); return v;
}
__device__ __forceinline__ void st_async1(uint32_t dst, float v, uint32_t bar) {
    asm volatile("st.async.shared::cluster.mbarrier::complete_tx::bytes.f32 [%0], %1, [%2];" ::"r"(dst), "f"(v), "r"(bar) : "memory");
}
__device__ __forceinline__ void st_async2(uint32_t dst, float x, float y, uint32_t bar) {
    asm volatile("st.async.shared::cluster.mbarrier::complete_tx::bytes.v2.f32 [%0], {%1,%2}, [%3];" ::"r"(dst), "f"(x), "f"(y), "r"(bar) : "memory");
}
__device__ __forceinline__ void mma8(float (&d)[4], uint32_t a0, uint32_t a1, uint32_t b0) {
    asm volatile("mma.sync.aligned.m16n8k8.row.col.f32.bf16.bf16.f32 {%0,%1,%2,%3}, {%4,%5}, {%6}, {%0,%1,%2,%3};"
        : "+f"(d[0]), "+f"(d[1]), "+f"(d[2]), "+f"(d[3]) : "r"(a0), "r"(a1), "r"(b0));
}
__device__ __forceinline__ void cp16(uint32_t dst, const void* src) {
    asm volatile("cp.async.cg.shared.global [%0], [%1], 16;" ::"r"(dst), "l"(src) : "memory");
}
__device__ __forceinline__ void sts128(uint32_t a, const float (&v)[4]) {
    asm volatile("st.shared.v4.f32 [%0], {%1,%2,%3,%4};" ::"r"(a), "f"(v[0]), "f"(v[1]), "f"(v[2]), "f"(v[3]) : "memory");
}
__device__ __forceinline__ float4 lds128(uint32_t a) {
    float4 v; asm volatile("ld.shared.v4.f32 {%0,%1,%2,%3}, [%4];" : "=f"(v.x), "=f"(v.y), "=f"(v.z), "=f"(v.w) : "r"(a) : "memory"); return v;
}
__device__ __forceinline__ void sts64(uint32_t a, float x, float y) {
    asm volatile("st.shared.v2.f32 [%0], {%1,%2};" ::"r"(a), "f"(x), "f"(y) : "memory");
}
__device__ __forceinline__ float2 lds64(uint32_t a) {
    float2 v; asm volatile("ld.shared.v2.f32 {%0,%1}, [%2];" : "=f"(v.x), "=f"(v.y) : "r"(a) : "memory"); return v;
}
__device__ __forceinline__ void bar_sync(int id, int n) { asm volatile("bar.sync %0, %1;" ::"r"(id), "r"(n) : "memory"); }
__device__ __forceinline__ void bar_arrive(int id, int n) { asm volatile("bar.arrive %0, %1;" ::"r"(id), "r"(n) : "memory"); }
__device__ __forceinline__ uint32_t mapa(uint32_t a, uint32_t r) {
    uint32_t o; asm("mapa.shared::cluster.u32 %0, %1, %2;" : "=r"(o) : "r"(a), "r"(r)); return o;
}
__device__ __forceinline__ void st_async4(uint32_t dst, float4 v, uint32_t bar) {
    asm volatile("st.async.shared::cluster.mbarrier::complete_tx::bytes.v4.f32 [%0], {%1,%2,%3,%4}, [%5];"
        ::"r"(dst), "f"(v.x), "f"(v.y), "f"(v.z), "f"(v.w), "r"(bar) : "memory");
}
__device__ __forceinline__ void mbar_init(uint32_t bar, int n) { asm volatile("mbarrier.init.shared.b64 [%0], %1;" ::"r"(bar), "r"(n) : "memory"); }
__device__ __forceinline__ void mbar_expect(uint32_t bar, int bytes) {
    asm volatile("mbarrier.arrive.expect_tx.shared.b64 _, [%0], %1;" ::"r"(bar), "r"(bytes) : "memory");
}
__device__ __forceinline__ void bulk_load(uint32_t dst, const void* src, int bytes, uint32_t bar) {
    asm volatile("cp.async.bulk.shared::cluster.global.mbarrier::complete_tx::bytes [%0], [%1], %2, [%3];"
        ::"r"(dst), "l"(src), "r"(bytes), "r"(bar) : "memory");
}
__device__ __forceinline__ bool mbar_try(uint32_t bar, uint32_t par) {
    uint32_t ok;
    asm volatile("{.reg .pred p; mbarrier.try_wait.parity.shared::cta.b64 p, [%1], %2; selp.u32 %0, 1, 0, p;}"
        : "=r"(ok) : "r"(bar), "r"(par) : "memory");
    return ok;
}
__device__ __forceinline__ bool mbar_test(uint32_t bar, uint32_t par) {
    uint32_t ok;
    asm volatile("{.reg .pred p; mbarrier.test_wait.parity.shared::cta.b64 p, [%1], %2; selp.u32 %0, 1, 0, p;}"
        : "=r"(ok) : "r"(bar), "r"(par) : "memory");
    return ok;
}
__device__ __forceinline__ int ld_acq(const int* p) { int v; asm volatile("ld.acquire.gpu.global.s32 %0, [%1];" : "=r"(v) : "l"(p) : "memory"); return v; }
__device__ __forceinline__ void wait_ctr(const int* p, int n) {
    for (int it = 0; it < (1 << 20) && ld_acq(p) < n; it++) __nanosleep(64);
}
__device__ __forceinline__ void mbar_wait(uint32_t bar, uint32_t par) {
    if (!mbar_try(bar, par))
        for (int it = 0; it < SPIN_LIMIT && !mbar_try(bar, par); it++) {}
}
__device__ __forceinline__ void mbar_wait_long(uint32_t bar, uint32_t par) {
    for (int it = 0; it < (1 << 24) && !mbar_try(bar, par); it++) {}
}
__device__ __forceinline__ float4 add4(float4 a, float4 b) { return make_float4(a.x + b.x, a.y + b.y, a.z + b.z, a.w + b.w); }
__device__ __forceinline__ float ex2(float x) { float y; asm("ex2.approx.ftz.f32 %0, %1;" : "=f"(y) : "f"(x)); return y; }

__device__ __forceinline__ void wgmma256(float (&d)[128], uint64_t da, uint64_t db, int acc) {
    asm volatile("{.reg .pred p; setp.ne.b32 p, %130, 0;\n"
        "wgmma.mma_async.sync.aligned.m64n256k16.f32.bf16.bf16 {"
        "%0,%1,%2,%3,%4,%5,%6,%7,%8,%9,%10,%11,%12,%13,%14,%15,"
        "%16,%17,%18,%19,%20,%21,%22,%23,%24,%25,%26,%27,%28,%29,%30,%31,"
        "%32,%33,%34,%35,%36,%37,%38,%39,%40,%41,%42,%43,%44,%45,%46,%47,"
        "%48,%49,%50,%51,%52,%53,%54,%55,%56,%57,%58,%59,%60,%61,%62,%63,"
        "%64,%65,%66,%67,%68,%69,%70,%71,%72,%73,%74,%75,%76,%77,%78,%79,"
        "%80,%81,%82,%83,%84,%85,%86,%87,%88,%89,%90,%91,%92,%93,%94,%95,"
        "%96,%97,%98,%99,%100,%101,%102,%103,%104,%105,%106,%107,%108,%109,%110,%111,"
        "%112,%113,%114,%115,%116,%117,%118,%119,%120,%121,%122,%123,%124,%125,%126,%127"
        "}, %128, %129, p, 1, 1, 0, 1;}"
        : "+f"(d[0]), "+f"(d[1]), "+f"(d[2]), "+f"(d[3]), "+f"(d[4]), "+f"(d[5]), "+f"(d[6]), "+f"(d[7]), "+f"(d[8]), "+f"(d[9]), "+f"(d[10]), "+f"(d[11]), "+f"(d[12]), "+f"(d[13]), "+f"(d[14]), "+f"(d[15]), "+f"(d[16]), "+f"(d[17]), "+f"(d[18]), "+f"(d[19]), "+f"(d[20]), "+f"(d[21]), "+f"(d[22]), "+f"(d[23]), "+f"(d[24]), "+f"(d[25]), "+f"(d[26]), "+f"(d[27]), "+f"(d[28]), "+f"(d[29]), "+f"(d[30]), "+f"(d[31]), "+f"(d[32]), "+f"(d[33]), "+f"(d[34]), "+f"(d[35]), "+f"(d[36]), "+f"(d[37]), "+f"(d[38]), "+f"(d[39]), "+f"(d[40]), "+f"(d[41]), "+f"(d[42]), "+f"(d[43]), "+f"(d[44]), "+f"(d[45]), "+f"(d[46]), "+f"(d[47]), "+f"(d[48]), "+f"(d[49]), "+f"(d[50]), "+f"(d[51]), "+f"(d[52]), "+f"(d[53]), "+f"(d[54]), "+f"(d[55]), "+f"(d[56]), "+f"(d[57]), "+f"(d[58]), "+f"(d[59]), "+f"(d[60]), "+f"(d[61]), "+f"(d[62]), "+f"(d[63]), "+f"(d[64]), "+f"(d[65]), "+f"(d[66]), "+f"(d[67]), "+f"(d[68]), "+f"(d[69]), "+f"(d[70]), "+f"(d[71]), "+f"(d[72]), "+f"(d[73]), "+f"(d[74]), "+f"(d[75]), "+f"(d[76]), "+f"(d[77]), "+f"(d[78]), "+f"(d[79]), "+f"(d[80]), "+f"(d[81]), "+f"(d[82]), "+f"(d[83]), "+f"(d[84]), "+f"(d[85]), "+f"(d[86]), "+f"(d[87]), "+f"(d[88]), "+f"(d[89]), "+f"(d[90]), "+f"(d[91]), "+f"(d[92]), "+f"(d[93]), "+f"(d[94]), "+f"(d[95]), "+f"(d[96]), "+f"(d[97]), "+f"(d[98]), "+f"(d[99]), "+f"(d[100]), "+f"(d[101]), "+f"(d[102]), "+f"(d[103]), "+f"(d[104]), "+f"(d[105]), "+f"(d[106]), "+f"(d[107]), "+f"(d[108]), "+f"(d[109]), "+f"(d[110]), "+f"(d[111]), "+f"(d[112]), "+f"(d[113]), "+f"(d[114]), "+f"(d[115]), "+f"(d[116]), "+f"(d[117]), "+f"(d[118]), "+f"(d[119]), "+f"(d[120]), "+f"(d[121]), "+f"(d[122]), "+f"(d[123]), "+f"(d[124]), "+f"(d[125]), "+f"(d[126]), "+f"(d[127])
        : "l"(da), "l"(db), "r"(acc));
}
__device__ __forceinline__ void wgmma128(float (&d)[64], uint64_t da, uint64_t db, int acc) {
    asm volatile("{.reg .pred p; setp.ne.b32 p, %66, 0;\n"
        "wgmma.mma_async.sync.aligned.m64n128k16.f32.bf16.bf16 {"
        "%0,%1,%2,%3,%4,%5,%6,%7,%8,%9,%10,%11,%12,%13,%14,%15,"
        "%16,%17,%18,%19,%20,%21,%22,%23,%24,%25,%26,%27,%28,%29,%30,%31,"
        "%32,%33,%34,%35,%36,%37,%38,%39,%40,%41,%42,%43,%44,%45,%46,%47,"
        "%48,%49,%50,%51,%52,%53,%54,%55,%56,%57,%58,%59,%60,%61,%62,%63"
        "}, %64, %65, p, 1, 1, 0, 1;}"
        : "+f"(d[0]), "+f"(d[1]), "+f"(d[2]), "+f"(d[3]), "+f"(d[4]), "+f"(d[5]), "+f"(d[6]), "+f"(d[7]), "+f"(d[8]), "+f"(d[9]), "+f"(d[10]), "+f"(d[11]), "+f"(d[12]), "+f"(d[13]), "+f"(d[14]), "+f"(d[15]), "+f"(d[16]), "+f"(d[17]), "+f"(d[18]), "+f"(d[19]), "+f"(d[20]), "+f"(d[21]), "+f"(d[22]), "+f"(d[23]), "+f"(d[24]), "+f"(d[25]), "+f"(d[26]), "+f"(d[27]), "+f"(d[28]), "+f"(d[29]), "+f"(d[30]), "+f"(d[31]), "+f"(d[32]), "+f"(d[33]), "+f"(d[34]), "+f"(d[35]), "+f"(d[36]), "+f"(d[37]), "+f"(d[38]), "+f"(d[39]), "+f"(d[40]), "+f"(d[41]), "+f"(d[42]), "+f"(d[43]), "+f"(d[44]), "+f"(d[45]), "+f"(d[46]), "+f"(d[47]), "+f"(d[48]), "+f"(d[49]), "+f"(d[50]), "+f"(d[51]), "+f"(d[52]), "+f"(d[53]), "+f"(d[54]), "+f"(d[55]), "+f"(d[56]), "+f"(d[57]), "+f"(d[58]), "+f"(d[59]), "+f"(d[60]), "+f"(d[61]), "+f"(d[62]), "+f"(d[63])
        : "l"(da), "l"(db), "r"(acc));
}
__device__ __forceinline__ void wg_fence() { asm volatile("wgmma.fence.sync.aligned;" ::: "memory"); }
__device__ __forceinline__ void wg_commit() { asm volatile("wgmma.commit_group.sync.aligned;" ::: "memory"); }
template <int N> __device__ __forceinline__ void wg_wait() { asm volatile("wgmma.wait_group.sync.aligned %0;" ::"n"(N) : "memory"); }
__device__ __forceinline__ uint64_t mkdesc(uint32_t addr, uint32_t lbo, uint32_t sbo, uint32_t sw) {
    return (uint64_t)((addr & 0x3FFFF) >> 4) | ((uint64_t)(lbo >> 4) << 16) | ((uint64_t)(sbo >> 4) << 32) | ((uint64_t)sw << 62);
}
__device__ __forceinline__ void tma2d(uint32_t dst, const CUtensorMap* m, int c0, int c1, uint32_t bar) {
    asm volatile("cp.async.bulk.tensor.2d.shared::cluster.global.mbarrier::complete_tx::bytes [%0], [%1, {%2, %3}], [%4];"
        ::"r"(dst), "l"(m), "r"(c0), "r"(c1), "r"(bar) : "memory");
}
__device__ __forceinline__ void tma3d(uint32_t dst, const CUtensorMap* m, int c0, int c1, int c2, uint32_t bar) {
    asm volatile("cp.async.bulk.tensor.3d.shared::cluster.global.mbarrier::complete_tx::bytes [%0], [%1, {%2, %3, %4}], [%5];"
        ::"r"(dst), "l"(m), "r"(c0), "r"(c1), "r"(c2), "r"(bar) : "memory");
}
__device__ __forceinline__ void tma3d_mc(uint32_t dst, const CUtensorMap* m, int c0, int c1, int c2, uint32_t bar, uint16_t mask) {
    asm volatile("cp.async.bulk.tensor.3d.shared::cluster.global.mbarrier::complete_tx::bytes.multicast::cluster [%0], [%1, {%2, %3, %4}], [%5], %6;"
        ::"r"(dst), "l"(m), "r"(c0), "r"(c1), "r"(c2), "r"(bar), "h"(mask) : "memory");
}
__device__ __forceinline__ void mbar_arrive(uint32_t bar) { asm volatile("mbarrier.arrive.shared.b64 _, [%0];" ::"r"(bar) : "memory"); }
__device__ __forceinline__ void mbar_arrive_remote(uint32_t bar) {
    asm volatile("mbarrier.arrive.shared::cluster.b64 _, [%0];" ::"r"(bar) : "memory");
}
template <int R> __device__ __forceinline__ void reg_inc() { asm volatile("setmaxnreg.inc.sync.aligned.u32 %0;" ::"n"(R)); }
template <int R> __device__ __forceinline__ void reg_dec() { asm volatile("setmaxnreg.dec.sync.aligned.u32 %0;" ::"n"(R)); }

#define ST(id, w, i)
constexpr int CH_NRES = 50;
constexpr int CH_WREG = CH_NRES * 512;
constexpr int CH_PART = 8 * CH_WREG;
constexpr int CH_SX = CH_PART + 16384;
constexpr int CH_MX = CH_SX + 3 * 1280;
constexpr int CH_QK = CH_MX;
constexpr int CH_XS = CH_MX + 3 * 512;
constexpr int CH_BAR = CH_XS + 5632;
constexpr int CH_SMEM = CH_BAR + 192;
constexpr int CH_THREADS = 384;

__device__ __forceinline__ char* ring_base() { return (char*)(((uintptr_t)g_ring + (1 << 20) - 1) & ~(uintptr_t)((1 << 20) - 1)); }
__device__ __forceinline__ uint32_t ring_off(int chunk, int side) {
    uint32_t o = ((chunk & 1) << 13) | ((chunk >> 1) << 16);
    uint32_t par = ((o >> 13) ^ (o >> 16) ^ (o >> 17) ^ (o >> 19) ^ side) & 1;
    return o | (par << 12);
}
__device__ __forceinline__ uint2 ld_poll(const char* p) {
    unsigned long long v; asm volatile("ld.relaxed.gpu.global.b64 %0, [%1];" : "=l"(v) : "l"(p) : "memory");
    return make_uint2((uint32_t)v, (uint32_t)(v >> 32));
}
__device__ __forceinline__ void st_pub(char* p, uint32_t x, uint32_t y) {
    unsigned long long v = ((unsigned long long)y << 32) | x;
    asm volatile("st.relaxed.gpu.global.b64 [%0], %1;" ::"l"(p), "l"(v) : "memory");
}
template <int N>
__device__ __forceinline__ void poll_issue(uint2 (&b)[N], const char* p, bool lastvalid) {
#pragma unroll
    for (int i = 0; i < N; i++) {
        if (i < N - 1 || lastvalid) b[i] = ld_poll(p + i * 256);
        else b[i] = make_uint2(0, 0);
    }
}
template <int N>
__device__ __forceinline__ int poll_check(uint2 (&b)[N], const char* p) {
    int it = 0;
    uint32_t mx = b[0].x;
#pragma unroll
    for (int i = 1; i < N; i++) mx = max(mx, b[i].x);
    if (__any_sync(0xffffffffu, mx == SENT)) {
        do {
#pragma unroll
            for (int i = 0; i < N; i++)
                if ((REALL && i < 10) || b[i].x == SENT) b[i] = ld_poll(p + i * 256);
            mx = b[0].x;
#pragma unroll
            for (int i = 1; i < N; i++) mx = max(mx, b[i].x);
            it++;
        } while (__any_sync(0xffffffffu, mx == SENT && it < SPIN_LIMIT));
    }
    return it;
}
template <int N>
__device__ __forceinline__ uint32_t delay(uint32_t a) {
    uint32_t z = 0;
#pragma unroll
    for (int i = 0; i < N; i++) asm volatile("ld.volatile.shared.u32 %0, [%1];" : "=r"(z) : "r"(a + z) : "memory");
    return z;
}

#define PFKV 0
#define LDW 0
#define KGS 3
constexpr int KVN = 2;
#define FEN 1
#define XB 4
#define KEEP 100
#define PE 0
#define PROMO 2
#define PROMU 0
#define CL 8
#define PL 0
#define ML 4
#define MP 2
#define VCH_P 4
#define VCH_C 2
#define DLM 3
#define DLO 5
constexpr int OB = 0;
template <int PACE, int I0 = 0, int I1 = 12>
__device__ __forceinline__ void preload(uint32_t (&sw)[12][4], uint32_t a, uint32_t zero) {
    uint32_t z = 0;
#pragma unroll
    for (int i = I0; i < I1; i++) {
        if (PACE && i % (PACE ? PACE : 1) == 0) z = delay<1>(zero + z);
        ldsm4t(sw[i], a + z + i * 512);
    }
}
__device__ __forceinline__ void stsm4(uint32_t addr, uint32_t a, uint32_t b, uint32_t c, uint32_t d) {
    asm volatile("stmatrix.sync.aligned.m8n8.x4.shared.b16 [%0], {%1,%2,%3,%4};" ::"r"(addr), "r"(a), "r"(b), "r"(c), "r"(d) : "memory");
}
__device__ __forceinline__ void stsm4t(uint32_t addr, uint32_t a, uint32_t b, uint32_t c, uint32_t d) {
    asm volatile("stmatrix.sync.aligned.m8n8.x4.trans.shared.b16 [%0], {%1,%2,%3,%4};" ::"r"(addr), "r"(a), "r"(b), "r"(c), "r"(d) : "memory");
}
__device__ __forceinline__ void st_part(uint32_t addr, const float (&x)[4], const float (&y)[4]) {
    stsm4(addr, pack_bf16(x[0], x[1]), pack_bf16(x[2], x[3]), pack_bf16(y[0], y[1]), pack_bf16(y[2], y[3]));
}
template <bool TR>
__device__ __forceinline__ void red_part(uint32_t& lo, uint32_t& hi, uint32_t addr, uint32_t eye) {
    uint32_t a[4][4];
#pragma unroll
    for (int j = 0; j < 4; j++) { if (TR) ldsm4t(a[j], addr + j * 1024); else ldsm4(a[j], addr + j * 1024); }
    float r0[4], r1[4], r2[4], r3[4];
    mma16z(r0, a[0], eye, eye); mma16z(r1, a[1], eye, eye); mma16z(r2, a[2], eye, eye); mma16z(r3, a[3], eye, eye);
#pragma unroll
    for (int j = 0; j < 4; j++) r0[j] = ((r0[j] + r1[j]) + r2[j]) + r3[j];
    lo = pack_bf16(r0[0], r0[1]); hi = pack_bf16(r0[2], r0[3]);
}
__device__ __forceinline__ int o_chunk(int ks, int& pos) {
    const int cw = ks < 176 ? ks / 11 : 16 + (ks - 176) / 10;
    pos = ks - (cw < 16 ? 11 * cw : 176 + 10 * (cw - 16));
    return cw;
}

template <bool PV>
__device__ __forceinline__ void chain_loop(const uint32_t (&wa)[36][4], const uint32_t sb, const int w, const int lane0, const int rank,
                                           const int h, const int side) {
    const int rk1 = rank == 2 ? 0 : rank + 1, rk2 = rank == 0 ? 2 : rank - 1;
    const int nq = rank == 0 ? 6 : 5, u0 = rank == 0 ? 0 : 1 + 5 * rank, v0 = rank == 0 ? -6 : 3 * rank - 6;
    const uint32_t pt = CH_PART + (w >> 1) * 4096 + (w & 1) * 256;
    const uint32_t barS = sb + CH_BAR, barM = barS + 8, zero = barS + 24;
    char* const ring0 = ring_base();
    const uint32_t m_rd = ring_off(24 + w, side), o_rd = ring_off(rank * 8 + w, side);
    uint32_t pub;
    if (PV) { int pos, cw = o_chunk(h * 8 + v0 + w, pos); pub = (ring_off(cw, 0) & ~4096u) + pos * 256; }
    else pub = (ring_off(24 + (h >> 2), 0) & ~4096u) + ((2 * h + w) & 7) * 256;
    char* const kvo = (char*)(PV ? g_vm + 128 * (v0 + w) : g_km + 64 * (u0 + w)) + h * 2048;
    const bool mown = !PV && w == rank && rank < 2;
    uint32_t lo16 = lane0 * 16;
    uint32_t sw[12][4];
#pragma unroll
    for (int i = 0; i < 12; i++) ldsm4t(sw[i], sb + lo16 + w * CH_WREG + i * 512);

#pragma unroll 1
    for (int s = 0;; s++) {
        const bool last = s == NSEG - 1;
        const uint32_t slot = (s & 3) << 14;
        lo16 += delay<DLM>(zero);
        const uint32_t lane = lo16 >> 4, l16 = sb + lo16, wl = l16 + w * CH_WREG, pw = l16 + CH_PART + w * 512;
        const uint32_t xs = l16 + CH_XS + nq * 512 + (w - nq) * 1024;
        const uint32_t eye = ((lo16 >> 7) == (lane & 3)) ? ((lo16 & 64) ? 0x3F800000u : 0x3F80u) : 0u;
        uint2 b[8];
        const char* pm = ring0 + (m_rd + slot + (lo16 >> 1));
        poll_issue<8>(b, pm, true);
        preload<0, ML, 12>(sw, wl, zero);
        poll_check<8>(b, pm);
        if ((OB || (XB & 1)) && !last) bar_arrive(8, 256 + OB);
        if (PV && !last && w == 7) bar_arrive(13, 64);
        {
            float acc[6][4];
#pragma unroll
            for (int kk = 0; kk < 8; kk++) {
                const int j = (2 * kk) % 12;
                if (kk == 0) { mma16z(acc[5], sw[0], b[0].x, b[0].y); mma16z(acc[4], sw[1], b[0].x, b[0].y); }
                else { mma16(acc[5], sw[j], b[kk].x, b[kk].y); mma16(acc[4], sw[j + 1], b[kk].x, b[kk].y); }
#pragma unroll
                for (int i = 0; i < 4; i++) {
                    if (kk == 0) mma16z(acc[i], wa[i * 8], b[0].x, b[0].y);
                    else mma16(acc[i], wa[i * 8 + kk], b[kk].x, b[kk].y);
                    if (i < 2) ldsm4t(sw[j + i], wl + (12 + 2 * kk + i) * 512);
                }
            }
            st_part(pw + 4 * 2048, acc[4], acc[5]);
            st_part(pw, acc[0], acc[1]);
            st_part(pw + 2 * 2048, acc[2], acc[3]);
        }
        uint32_t kv0, kv1;
        const uint32_t lp = l16 + (lane >> 4) * 256, pl = lp + pt;
        if (!PV) {
            bar_sync(1, last ? 256 : 256 + OB);
            red_part<true>(kv1, kv0, pl, eye);
            sts64(l16 + CH_QK + (w >> 1) * 512 + (w & 1) * 8, __uint_as_float(kv1), __uint_as_float(kv0));
            if (!last) bar_arrive(2, nq * 32 + 64 + OB);
        } else {
            bar_sync(1, last ? 256 : 256 + OB);
        }
        {
            float va[4][4];
            const float z = __uint_as_float(delay<1>(zero));
#pragma unroll
            for (int i = 0; i < 4; i++) va[i][0] = va[i][1] = va[i][2] = va[i][3] = z;
#pragma unroll
            for (int kk = 0; kk < 8; kk++) {
                const int c = (PV ? VCH_P : VCH_C) == 4 ? kk & 1 : 0;
                if (kk < 2) { mma16(va[c], wa[32 + 2 * kk], b[kk].x, b[kk].y); mma16(va[2 + c], wa[33 + 2 * kk], b[kk].x, b[kk].y); }
                else { mma16(va[c], sw[(2 * kk) % 12], b[kk].x, b[kk].y); mma16(va[2 + c], sw[(2 * kk + 1) % 12], b[kk].x, b[kk].y); }
            }
            if ((PV ? VCH_P : VCH_C) == 4) {
#pragma unroll
                for (int j = 0; j < 4; j++) { va[0][j] += va[1][j]; va[2][j] += va[3][j]; }
            }
            st_part(pw + 6 * 2048, va[0], va[2]);
        }
        if (PV) {
            uint32_t vt0[4], vt1[4];
            ldsm4t(vt0, xs); ldsm4t(vt1, xs + 512);
            if (w >= 6 && !last) {
                uint32_t kx[3][4];
#pragma unroll
                for (int j = 0; j < 3; j++)
                    ldsm4(kx[j], sb + CH_XS + j * 1024 + (j == 2 && nq == 5 ? 0 : ((lane >> 3) & 1) * 512) + (w - 6) * 256 + (lane >> 4) * 128 + (lane & 7) * 16);
                const uint32_t da = l16 + CH_SX + rank * 1280 + (w - 6) * 512, dc = sb + CH_SX + rank * 1280 + 1024 + lane * 8;
                bar_sync(2, nq * 32 + 64 + OB);
                uint32_t qk[3][4];
#pragma unroll
                for (int j = 0; j < 3; j++) {
                    const float4 v = lds128(l16 + CH_QK + j * 512);
                    qk[j][0] = __float_as_uint(v.x); qk[j][1] = __float_as_uint(v.y); qk[j][2] = __float_as_uint(v.z); qk[j][3] = __float_as_uint(v.w);
                }
                float s0[4], s1[4], s2[4], s3[4];
                mma16z(s0, qk[0], kx[0][0], kx[0][1]); mma16z(s1, qk[0], kx[0][2], kx[0][3]);
                mma16z(s2, qk[1], kx[1][0], kx[1][1]); mma16z(s3, qk[1], kx[1][2], kx[1][3]);
                if (nq == 5) qk[2][2] = qk[2][3] = 0;
                mma16(s0, qk[2], kx[2][0], kx[2][1]); mma16(s1, qk[2], kx[2][2], kx[2][3]);
                float m0[4], m1[4];
                mma16z(m0, qk[0], qk[0][1], qk[0][3]); mma16z(m1, qk[1], qk[1][1], qk[1][3]);
                mma16(m0, qk[2], qk[2][1], qk[2][3]);
                const float4 sv = make_float4(s0[0] + s2[0], s0[1] + s2[1], s1[0] + s3[0], s1[1] + s3[1]);
                st_async4(mapa(da, rk1), sv, mapa(barS, rk1));
                st_async4(mapa(da, rk2), sv, mapa(barS, rk2));
                {
                    const float c0 = m0[0] + m1[0], c1 = m0[1] + m1[1];
                    const int dr = w == 6 ? rk1 : rk2;
                    st_async2(mapa(dc, dr), c0, c1, mapa(barS, dr));
                    sts64(dc, c0, c1);
                }
                const float t4[4] = {sv.x, sv.y, sv.z, sv.w};
                sts128(da, t4);
            }
            bar_sync(3, last ? 256 : 256 + OB);
            if (!last && w == 7) bar_arrive(12, 64);
            red_part<false>(kv0, kv1, pl, eye);
            if (last) {
                uint32_t* d = (uint32_t*)(kvo + (uint32_t)(s * (NH * 2048) + lane * 4));
                d[0] = movm(kv0); d[32] = movm(kv1);
                break;
            }
            {
                const uint32_t sx = l16 + CH_SX, r0 = rank * 1280, r1 = rk1 * 1280, r2 = rk2 * 1280;
                float4 a0 = lds128(sx + r0), b0 = lds128(sx + 512 + r0);
                const float2 c0 = lds64(sx + 1024 + r0 - lane * 8);
                preload<0, 0, PE>(sw, wl + 28 * 512, zero);
                mbar_wait(barS, s & 1);
                const float4 a1 = lds128(sx + r1), a2 = lds128(sx + r2), b1 = lds128(sx + 512 + r1), b2 = lds128(sx + 512 + r2);
                const float2 c1 = lds64(sx + 1024 + r1 - lane * 8), c2 = lds64(sx + 1024 + r2 - lane * 8);
                a0 = add4(add4(a0, a1), a2); b0 = add4(add4(b0, b1), b2);
                float sc[10] = {a0.x, a0.y, a0.z, a0.w, b0.x, b0.y, b0.z, b0.w, c0.x + c1.x + c2.x, c0.y + c1.y + c2.y};
                float mx = fmaxf(fmaxf(fmaxf(sc[0], sc[1]), fmaxf(sc[2], sc[3])), fmaxf(fmaxf(sc[4], sc[5]), fmaxf(sc[6], sc[7])));
                mx = fmaxf(mx, fmaxf(sc[8], sc[9]));
                mx = fmaxf(fmaxf(mx, __shfl_xor_sync(0xffffffffu, mx, 1)),
                           fmaxf(__shfl_xor_sync(0xffffffffu, mx, 2), __shfl_xor_sync(0xffffffffu, mx, 3)));
                const float cs = 0.08838834764831845f * 1.4426950408889634f;
                const float mb = -mx * cs;
#pragma unroll
                for (int j = 0; j < 10; j++) sc[j] = ex2(fmaf(sc[j], cs, mb));
                uint32_t pf[5];
#pragma unroll
                for (int j = 0; j < 5; j++) pf[j] = pack_bf16(sc[2 * j], sc[2 * j + 1]);
                float o0[4], o1[4], o2[4], o3[4], o4[4], o5[4];
                const uint32_t p0[4] = {pf[0], 0, pf[1], 0}, p1[4] = {pf[2], 0, pf[3], 0};
                mma16z(o0, p0, vt0[0], vt0[1]); mma16z(o1, p0, vt1[0], vt1[1]);
                mma16z(o2, p1, vt0[2], vt0[3]); mma16z(o3, p1, vt1[2], vt1[3]);
                mma8z(o4, pf[4], 0, kv0); mma8z(o5, pf[4], 0, kv1);
                float sum = (((sc[0] + sc[1]) + (sc[2] + sc[3])) + ((sc[4] + sc[5]) + (sc[6] + sc[7]))) + (sc[8] + sc[9]);
                sum = (sum + __shfl_xor_sync(0xffffffffu, sum, 1)) + (__shfl_xor_sync(0xffffffffu, sum, 2) + __shfl_xor_sync(0xffffffffu, sum, 3));
                float inv; asm("rcp.approx.ftz.f32 %0, %1;" : "=f"(inv) : "f"(sum));
                const uint32_t ox = pack_bf16((o0[0] + o2[0] + o4[0]) * inv, (o0[1] + o2[1] + o4[1]) * inv);
                const uint32_t oy = pack_bf16((o1[0] + o3[0] + o5[0]) * inv, (o1[1] + o3[1] + o5[1]) * inv);
                char* const pp = ring0 + (pub + slot + (lo16 >> 1));
                st_pub(pp, ox, oy); st_pub(pp + 4096, ox, oy);
                if (OB || (XB & 4)) bar_arrive(10, (8 - nq) * 32 + OB);
                preload<0, PE, PL>(sw, wl + 28 * 512, zero);
            }
            kv0 = movm(kv0); kv1 = movm(kv1);
        } else {
            *(uint32_t*)(kvo + (uint32_t)(s * (NH * 2048) + lane * 4)) = kv0;
            bar_sync(3, last ? 256 : 256 + OB);
            if (last) break;
            preload<1, 0, CL>(sw, wl + 28 * 512, zero);
        }
        uint2 c[11];
        bar_sync(4, 256 + OB);
        const char* po = ring0 + (o_rd + slot + (lo16 >> 1) + delay<DLO>(zero));
        poll_issue<11>(c, po, rank < 2);
        preload<0, PV ? PL : CL, 12>(sw, wl + 28 * 512, zero);
        if (PV) { uint32_t* d = (uint32_t*)(kvo + (uint32_t)(s * (NH * 2048) + lane * 4)); d[0] = kv0; d[32] = kv1; }
        poll_check<11>(c, po);
        if (OB || (XB & 2)) bar_arrive(9, 256 + OB);
        {
            float acc[4][4];
#pragma unroll
            for (int f = 0; f < 22; f++) {
                const int kk = f >> 1, a = f & 3;
                if (f < 4) mma16z(acc[a], sw[f % 12], c[kk].x, c[kk].y);
                else mma16(acc[a], sw[f % 12], c[kk].x, c[kk].y);
                if (f + 12 < 22) ldsm4t(sw[f % 12], wl + (28 + f + 12) * 512);
            }
#pragma unroll
            for (int i = 0; i < 2; i++) {
#pragma unroll
                for (int j = 0; j < 4; j++) acc[i][j] += acc[i + 2][j];
                sts128(l16 + CH_PART + i * 4096 + w * 512, acc[i]);
            }
        }
        if (!PV && w < 2) {
            bar_sync(5, 288 + OB);
            float4 v[8];
#pragma unroll
            for (int i = 0; i < 8; i++) v[i] = lds128(l16 + CH_PART + w * 4096 + i * 512);
            float4 r = add4(add4(add4(v[0], v[1]), add4(v[2], v[3])), add4(add4(v[4], v[5]), add4(v[6], v[7])));
            if (!mown) st_async4(mapa(l16 + CH_MX + rank * 512, w), r, mapa(barM, w));
            bar_arrive(7, 256 + OB);
            if (mown) {
                mbar_wait(barM, s & 1);
                float4 x = lds128(l16 + CH_MX + (rank ^ 1) * 512), y = lds128(l16 + CH_MX + 2 * 512);
                r = add4(add4(x, r), y);
                const uint32_t mx = movm(pack_bf16(r.x, r.y)), my = movm(pack_bf16(r.z, r.w));
                const uint32_t ns = (slot + 0x4000) & 0xC000;
                char* const pp = ring0 + (pub + ns + (lo16 >> 1));
                st_pub(pp, mx, my); st_pub(pp + 4096, mx, my);
            }
            preload<0, 0, ML>(sw, wl, zero);
        } else {
            bar_arrive(5, 288 + OB);
            bar_sync(7, 256 + OB);
            preload<MP, 0, ML>(sw, wl, zero);
        }
        bar_sync(6, 320 + OB);
    }
    bar_arrive(6, 288);
}

__device__ __forceinline__ void chain_pace(const uint32_t sb, const int lane, const int rank, const int aware) {
    const uint32_t zero = sb + CH_BAR + 24;
    if (lane == 0) {
        char* ring = ring_base();
        uint32_t* p0 = (uint32_t*)(ring + ring_off(blockIdx.x & 15, 0) + 3072 + (blockIdx.x >> 4) * 128);
        uint32_t* p1 = (uint32_t*)(ring + ring_off(blockIdx.x & 15, 1) + 3072 + (blockIdx.x >> 4) * 128);
        *p0 = 0; *p1 = 0;
        int b0 = 1 << 30, b1 = 1 << 30; uint32_t v = 0;
        for (int r = 0; r < 4 || (r < 256 && !mbar_test(sb + CH_BAR + 16, 0)); r++) {
            uint32_t t0 = clk(); v = atomicExch(p0 + (v == 500), r); uint32_t t1 = v == 777 ? clk() + 1 : clk(); b0 = min(b0, (int)(t1 - t0));
            t0 = clk(); v = atomicExch(p1 + (v == 500), r); t1 = v == 777 ? clk() + 1 : clk(); b1 = min(b1, (int)(t1 - t0));
            asm volatile("st.volatile.shared.u32 [%0], %1;" ::"r"(zero + 4), "r"(aware ? (b1 < b0) ^ (aware - 1) : 0) : "memory");
        }
    }
    __syncwarp();
#pragma unroll 1
    for (int s = 1; s < NSEG; s++) {
        bar_sync(5, 288 + OB);
        bar_arrive(6, 320 + OB + (rank == 2 ? delay<18>(zero) : 0));
    }
}
__device__ __forceinline__ char* reset_ptr(const int lane, const int rank, const int h) {
    const int nq = rank == 0 ? 6 : 5, v0 = rank == 0 ? -6 : 3 * rank - 6;
    int pos, cw = o_chunk(h * 8 + v0 + min(max(5 + (lane >> 3), nq), 7), pos);
    if (lane >= 24 && rank < 2) { cw = 24 + (h >> 2); pos = (2 * h + rank) & 7; }
    return ring_base() + ((ring_off(cw, 0) & ~4096u) + pos * 256 + (lane & 7) * 16);
}
__device__ __forceinline__ void chain_chores(const uint32_t sb, const int lane, const int rank, const int h, const bf16* __restrict__ mem0) {
    const int nq = rank == 0 ? 6 : 5, u0 = rank == 0 ? 0 : 1 + 5 * rank, v0 = rank == 0 ? -6 : 3 * rank - 6;
    const uint32_t barS = sb + CH_BAR, barM = barS + 8, barX = barS + 16;
    auto xload = [&](int s) {
        mbar_expect(barX, 8192 - nq * 512);
        bulk_load(sb + CH_XS, g_kx + (size_t)(s * NH + h) * 4096 + u0 * 256, nq * 512, barX);
        bulk_load(sb + CH_XS + nq * 512, g_vx + (size_t)(s * NH + h) * 4096 + (v0 + nq) * 512, (8 - nq) * 1024, barX);
    };
    char* const rb = reset_ptr(lane, rank, h);
    int* const kvf = g_kvf + blockIdx.x * 16;
    if (rank < 2) {
        const uint32_t* p = (const uint32_t*)(mem0 + (lane >> 2) * DM + 32 * h + 16 * rank + 2 * (lane & 3));
        char* d = ring_base() + ((ring_off(24 + (h >> 2), 0) & ~4096u) + ((2 * h + rank) & 7) * 256 + lane * 8);
        const uint32_t x = p[0] == SENT ? 0x7FFF7FFFu : p[0];
        st_pub(d, x, p[4]); st_pub(d + 4096, x, p[4]);
    }
    if (lane == 0) {
        if (!KVN) __nanosleep(18000);
        wait_ctr(kvf, KVN);
        asm volatile("fence.proxy.async;" ::: "memory");
        xload(0);
    }
#pragma unroll 1
    for (int s = 0; s < NSEG - 1; s++) {
        if (lane == 0) {
            mbar_expect(barS, 2 * 1280);
            if (rank < 2) mbar_expect(barM, 2 * 512);
        }
        bar_sync(13, 64);
#pragma unroll
        for (int i = 0; i < 4; i++)
            asm volatile("st.relaxed.gpu.global.v4.u32 [%0], {%1,%1,%1,%1};" ::"l"(rb + ((((s + 2) & 3) << 14) + (i >> 1) * 4096 + (i & 1) * 128)), "r"(SENT) : "memory");
        if (FEN || (s & 3) == 0) __threadfence();
        if (lane == 0 && (s & 3) == 0 && s) atomicAdd(g_ctr + C_CHAIN + (s >> 2) - 1, 1);
        if (lane == 0 && (s & 3) == 3) { wait_ctr(kvf + (s >> 2) + 1, KVN); asm volatile("fence.proxy.async;" ::: "memory"); }
        __syncwarp();
        bar_sync(12, 64);
        if (lane == 0) xload(s + 1);
        mbar_wait(barX, (s + 1) & 1);
        bar_sync(6, 320 + OB);
    }
    bar_sync(6, 288);
    __threadfence();
    if (lane == 0) atomicAdd(g_ctr + C_CHAIN + 15, 1);
}

struct S4Params { const bf16 *Are, *Aim, *Bre, *Bim, *Cre, *Cim, *ldt, *dsk; };
__device__ __forceinline__ float2 cmul(float2 a, float2 b) { return make_float2(a.x * b.x - a.y * b.y, a.x * b.y + a.y * b.x); }
__device__ __forceinline__ float2 csq(float2 a) { return make_float2(a.x * a.x - a.y * a.y, (a.x + a.x) * a.y); }
__device__ __forceinline__ float2 cexp_t(float lr, float turns) {
    float f = (turns - rintf(turns)) * 6.283185307179586f, e = ex2(lr);
    return make_float2(e * __cosf(f), e * __sinf(f));
}
__device__ __forceinline__ float bf_at(uint2 v, int i) {
    const uint32_t w = i < 2 ? v.x : v.y;
    return __uint_as_float((i & 1) ? w & 0xFFFF0000u : w << 16);
}
__device__ __forceinline__ void kg_step(uint32_t (&a)[4][4], uint32_t (&b)[5][2], uint32_t pa, uint32_t pe, float x0) {
#pragma unroll
    for (int i = 0; i < 2; i++) {
        const float4 p = lds128(pa + i * 64);
        const float2 e8 = lds64(pe + i * 32), c = make_float2(p.z, p.w);
        const float mag = ex2(p.x * x0), ph = p.y * x0;
        float2 e0 = make_float2(mag * __cosf(ph), mag * __sinf(ph)), e1 = cmul(e0, e8);
#pragma unroll
        for (int j = 0; j < 4; j++) {
            a[j][2 * i] = pack_bf16(e0.x, e0.y); a[j][2 * i + 1] = pack_bf16(e1.x, e1.y);
            e0 = csq(e0); e1 = csq(e1);
        }
        float2 m = cmul(c, e0);
        b[0][i] = pack_bf16(m.x, -m.y);
#pragma unroll
        for (int j = 0; j < 4; j++) {
            m = cmul(c, e1);
            b[j + 1][i] = pack_bf16(m.x, -m.y);
            if (j < 3) e1 = csq(e1);
        }
    }
}
__device__ __forceinline__ void kg_mma(float (&kd)[5][4], const uint32_t (&a)[4][4], const uint32_t (&b)[5][2]) {
    mma16(kd[0], a[0], b[0][0], b[0][1]);
#pragma unroll
    for (int j = 0; j < 4; j++) mma16(kd[j + 1], a[j], b[j + 1][0], b[j + 1][1]);
}
struct KgRaw { uint2 v[6]; float ldt; };
__device__ __forceinline__ void kg_load(KgRaw& r, const S4Params& P, int d, int lane) {
    const bf16* src[6] = {P.Are, P.Aim, P.Bre, P.Bim, P.Cre, P.Cim};
#pragma unroll
    for (int j = 0; j < 6; j++) r.v[j] = __ldg((const uint2*)(src[j] + d * 128) + lane);
    r.ldt = __bfloat162float(P.ldt[d]);
}
__device__ __forceinline__ float kg_params(const KgRaw& r, uint32_t stg, int lane) {
    const float dt = __bfloat162float(__float2bfloat16(expf(r.ldt)));
    float k2048 = 0.f;
#pragma unroll
    for (int i = 0; i < 4; i++) {
        const float br = dt * bf_at(r.v[2], i), bi = dt * bf_at(r.v[3], i), cr = bf_at(r.v[4], i), ci = bf_at(r.v[5], i);
        const float zr = dt * bf_at(r.v[0], i) * 1.4426950408889634f;
        float zt = dt * bf_at(r.v[1], i) * 0.15915494309189535f;
        zt -= rintf(zt);
        const float v[4] = {zr, zt * 6.283185307179586f, cr * br - ci * bi, cr * bi + ci * br};
        const float2 e8 = cexp_t(8.f * zr, 8.f * zt), el = cexp_t(2048.f * zr, 2048.f * zt);
        k2048 += v[2] * el.x - v[3] * el.y;
        sts128(stg + (i * 32 + lane) * 16, v);
        sts64(stg + 2048 + (i * 32 + lane) * 8, e8.x, e8.y);
    }
#pragma unroll
    for (int o = 16; o; o >>= 1) k2048 += __shfl_xor_sync(0xffffffffu, k2048, o);
    __syncwarp();
    return k2048;
}
__device__ __forceinline__ void kg_store(const float (&kd)[5][4], float k2048, uint32_t stg, int d, int lane) {
    __syncwarp();
    const uint32_t ta = stg + (lane & 7) * 32 + ((lane >> 3) & 1) * 16 + (lane >> 4) * 256;
    stsm4t(ta, pack_bf16(kd[0][0], kd[0][1]), pack_bf16(kd[0][2], kd[0][3]), pack_bf16(kd[1][0], kd[1][1]), pack_bf16(kd[1][2], kd[1][3]));
    stsm4t(ta + 512, pack_bf16(kd[2][0], kd[2][1]), pack_bf16(kd[2][2], kd[2][3]), pack_bf16(kd[3][0], kd[3][1]), pack_bf16(kd[3][2], kd[3][3]));
    stsm4t(ta + 1024, pack_bf16(kd[4][0], kd[4][1]), pack_bf16(kd[4][2], kd[4][3]), pack_bf16(k2048, 0.f), 0);
    __syncwarp();
#pragma unroll
    for (int j = 0; j < 3; j++) ((float4*)(g_kd + d * 768))[j * 32 + lane] = lds128(stg + j * 512 + lane * 16);
    __syncwarp();
}

__global__ void __cluster_dims__(3, 1, 1) __launch_bounds__(CH_THREADS, 1)
chain_kernel(const __grid_constant__ CUtensorMap mq, const __grid_constant__ CUtensorMap mk, const __grid_constant__ CUtensorMap mv,
             const __grid_constant__ CUtensorMap mo, const bf16* __restrict__ Wq, const bf16* __restrict__ Wk, const bf16* __restrict__ Wv,
             const bf16* __restrict__ mem0, const __grid_constant__ S4Params P, int aware) {
    extern __shared__ __align__(1024) unsigned char smem[];
    const uint32_t sb = smem_u32(smem);
    const int tid = threadIdx.x, lane = tid & 31;
    const int w = __shfl_sync(0xffffffffu, tid >> 5, 0);
    int rank; asm("mov.u32 %0, %%cluster_ctarank;" : "=r"(rank));
    const int h = blockIdx.x / 3;
    if (tid == 0) {
        mbar_init(sb + CH_BAR, 1); mbar_init(sb + CH_BAR + 8, 1); mbar_init(sb + CH_BAR + 16, 1);
        for (int i = 0; i < 16; i++) mbar_init(sb + CH_BAR + 64 + i * 8, 1);
        *(int*)(smem + CH_BAR + 24) = 0; *(int*)(smem + CH_BAR + 28) = 0; *(int*)(smem + CH_BAR + 32) = 0;
        asm volatile("fence.mbarrier_init.release.cluster;" ::: "memory");
    }
    if (w == 10 && PFKV) {
        const int e = lane * 96 + blockIdx.x;
        if (e < 2048) asm volatile("cp.async.bulk.prefetch.L2.global [%0], 8192;" ::"l"(((e & 1) ? Wv : Wk) + (size_t)(e >> 1) * HD) : "memory");
        if (PFKV > 1) __nanosleep(PFKV);
    }
    if (w == 9) {
        char* const rb = reset_ptr(lane, rank, h);
#pragma unroll
        for (int i = 0; i < 8; i++)
            asm volatile("st.relaxed.gpu.global.v4.u32 [%0], {%1,%1,%1,%1};" ::"l"(rb + (((i >> 2) << 14) + ((i >> 1) & 1) * 4096 + (i & 1) * 128)), "r"(SENT) : "memory");
        if (lane < 16) g_kvf[blockIdx.x * 16 + lane] = 0;
        if (blockIdx.x == 0)
            for (int k = lane; k < N_CTR; k += 32) g_ctr[k] = 0;
        __threadfence();
        __syncwarp();
        asm volatile("griddepcontrol.launch_dependents;" ::: "memory");
    }
    __syncthreads();
    asm volatile("barrier.cluster.arrive.relaxed.aligned;" ::: "memory");

    if (w >= 8) {
        reg_dec<24>();
        asm volatile("barrier.cluster.wait.aligned;" ::: "memory");
        if (w == 8) chain_pace(sb, lane, rank, aware);
        else if (w == 9) {
            chain_chores(sb, lane, rank, h, mem0);
            asm volatile("st.volatile.shared.u32 [%0], %1;" ::"r"(sb + CH_BAR + 32), "r"(0x3F803F80) : "memory");
        } else if (w == 11 && KEEP) {
#pragma unroll 1
            for (int it = 0; it < (1 << 22); it++) {
                int d0, d1;
                const uint32_t x = delay<1>(sb + CH_BAR + 32);
                asm volatile("mma.sync.aligned.m8n8k16.row.col.s32.s8.s8.s32 {%0,%1}, {%2}, {%2}, {%3,%3};" : "=r"(d0), "=r"(d1) : "r"(x), "r"(0));
                if (d0 | d1) break;
                if ((XB & 8) && lane == 0) asm volatile("st.relaxed.gpu.global.u32 [%0], %1;" ::"l"(g_kd + DM * 768 + blockIdx.x * 64), "r"(it) : "memory");
                if ((XB & 16) && lane == 0) ld_acq((int*)(g_kd + DM * 768 + blockIdx.x * 64));
                __nanosleep(KEEP);
            }
        }
    } else {
        reg_inc<240>();
        const int nq = rank == 0 ? 6 : 5;
        const int u0 = rank == 0 ? 0 : 1 + 5 * rank;
        const int v0 = rank == 0 ? -6 : 3 * rank - 6;
        const int gw = rank * 8 + w;
        const int ks0 = gw < 16 ? 11 * gw : 176 + 10 * (gw - 16);
        const int nko = gw < 16 ? 11 : 10;
        const uint32_t wr = sb + w * CH_WREG, bar0 = sb + CH_BAR + 64 + w * 16, bar1 = bar0 + 8;
        uint32_t wa[36][4];
        const uint32_t vst = sb + CH_PART + w * 2048;
        const int cq = h * DH + 8 * u0, cv = h * DH + 16 * (v0 + 6);
        const int r8 = lane >> 2, p = lane & 3;
        const bf16* src = p >= 2 ? ((p & 1) ? Wk : Wq) + cq + 32 : rank == 0 ? ((p & 1) ? Wk : Wq) + cq + 40 : Wv + cv - 16 + 8 * p;
        src += (size_t)(128 * w + r8) * HD;
        auto cp_rows = [&](int kh) {
            cp16(wr + ((kh >> 1) * 2 + (p >> 1)) * 512 + ((kh & 1) * 2 + (p & 1)) * 128 + r8 * 16, src + (size_t)kh * 8 * HD);
        };
        {
            int d = blockIdx.x * 8 + w, t = 0;
            const int d1 = 768 + blockIdx.x * 3 + w, nt = (w < 3 && d1 < DM) ? 32 : 16;
            const uint32_t stg = wr + 4096;
            KgRaw raw, raw1;
            kg_load(raw, P, d, lane);
            kg_load(raw1, P, min(d1, DM - 1), lane);
            float kd[5][4], k2048;
#pragma unroll 1
            for (int i = -LDW; i < 9 || t < nt; i++) {
                if (i >= 0 && i < 9) {
                    const uint32_t bar = bar0 + (i & 1) * 8;
                    if (i >= 2) mbar_wait(bar, ((i >> 1) - 1) & 1);
                    if (lane == 0) {
                        mbar_expect(bar, 2048);
                        if (i < 8) tma2d(wr + 8192 + (i & 1) * 8192 + (i >> 1) * 2048, (i & 1) ? &mk : &mq, cq, 128 * w + 32 * (i >> 1), bar);
                        else tma2d(vst, &mv, cv, 128 * w, bar);
                    }
                    if (i < 8) cp_rows(i);
                }
#pragma unroll 1
                for (int e = min(t + KGS, nt); t < e; t++) {
                    if ((t & 15) == 0) {
                        k2048 = kg_params(raw, stg, lane);
#pragma unroll
                        for (int j = 0; j < 20; j++) kd[j >> 2][j & 3] = 0.f;
                    }
                    uint32_t ka[4][4], kb[5][2];
                    kg_step(ka, kb, stg + ((t & 15) * 8 + (lane & 3)) * 16, stg + 2048 + ((t & 15) * 8 + (lane & 3)) * 8, (float)(lane >> 2));
                    kg_mma(kd, ka, kb);
                    if ((t & 15) == 15) { kg_store(kd, k2048, stg, d, lane); raw = raw1; d = d1; }
                }
            }
        }
        const uint32_t lrow = ((lane >> 4) * 8 + (lane & 7)) * 64, lsw = (lane >> 1) & 3, lh = (lane >> 3) & 1;
        mbar_wait(bar1, 1); mbar_wait(bar0, 0);
#pragma unroll
        for (int i = 0; i < 32; i++) ldsm4t(wa[i], wr + 8192 + lh * 8192 + (i & 7) * 1024 + lrow + (((i >> 3) ^ lsw) << 4));
#pragma unroll
        for (int i = 0; i < 4; i++) ldsm4t(wa[32 + i], vst + (i >> 1) * 1024 + lrow + ((((i & 1) * 2 + lh) ^ lsw) << 4));
        asm volatile("fence.proxy.async.shared::cta;" ::"r"(wa[31][0]), "r"(wa[35][0]) : "memory");
        __syncwarp();
#pragma unroll 1
        for (int i = 9; i < 18; i++) {
            const uint32_t bar = bar0 + (i & 1) * 8;
            if (i >= 11) mbar_wait(bar, ((i >> 1) - 1) & 1);
            if (lane == 0) {
                const int j = 2 * (i - 12), nb = min(2, nko - j);
                mbar_expect(bar, i < 12 ? 2048 : nb * 1024);
                if (i < 12) tma2d(wr + 8192 + (i - 9) * 2048, &mv, cv, 128 * w + 32 * (i - 8), bar);
                else for (int e = 0; e < nb; e++) tma2d(wr + 14336 + (j + e) * 1024, &mo, 32 * h, 16 * (ks0 + j + e), bar);
            }
            if (i < 17) cp_rows(i - 1);
        }
        mbar_wait(bar0, 0); mbar_wait(bar1, 0);
#pragma unroll 1
        for (int i = 0; i < 17; i++) {
            uint32_t x[4], y[4];
            ldsm4t(x, wr + 8192 + i * 1024 + lrow + ((lh ^ lsw) << 4));
            ldsm4t(y, wr + 8192 + i * 1024 + lrow + (((2 + lh) ^ lsw) << 4));
            if (i == 16 && nko == 10) x[0] = x[1] = x[2] = x[3] = y[0] = y[1] = y[2] = y[3] = 0;
            __syncwarp();
            stsm4t(wr + 8192 + i * 1024 + lane * 16, x[0], x[1], x[2], x[3]);
            stsm4t(wr + 8192 + i * 1024 + 512 + lane * 16, y[0], y[1], y[2], y[3]);
        }
        asm volatile("cp.async.wait_all;" ::: "memory");
        asm volatile("barrier.cluster.wait.aligned;" ::: "memory");
        bar_sync(1, 256);
        mbar_wait_long(sb + CH_BAR + 16, 0);
        const int side = __shfl_sync(0xffffffffu, *(volatile int*)(smem + CH_BAR + 28), 0);
        if (w >= nq) chain_loop<true>(wa, sb, w, lane, rank, h, side);
        else chain_loop<false>(wa, sb, w, lane, rank, h, side);
    }
}

constexpr int G_STAGE = 49152, G_NST = 4;
constexpr int G_STG = G_NST * G_STAGE;
constexpr int G_BAR = G_STG + 32768;
constexpr int G_SMEM = G_BAR + 256 + 1024;

#define WLOG(e)
constexpr int IT_QA = 0, IT_O = 1, IT_S4 = 2, IT_END = 3, IT_KV = 4;
#define O_WIDE 10
#define OPF 0
#define ATT2 0
#define S4REL 4
#define KVP 0
#define KVS 8
#define STM 0
__device__ __forceinline__ void st_out(uint32_t* p, uint32_t v) {
    if (STM == 0) *p = v;
    else if (STM == 1) __stcs(p, v);
    else asm volatile("st.global.L1::no_allocate.u32 [%0], %1;" ::"l"(p), "r"(v) : "memory");
}
#define Q_N1 1
#define Q_S1 16
__device__ __forceinline__ int queue_item(int q) {
    if (KVP && q >= KVP && q < 512) return (IT_KV << 16) | (((q >> 6) * 2 + (q & 1)) << 8) | ((q >> 1) & 31);
    if (q < 512) return (IT_KV << 16) | ((q >> 5) << 8) | (q & 31);
    q -= 512;
    if (q < 256) return (IT_QA << 16) | ((q >> 4) << 8) | (q & 15);
    q -= 256;
    if (q < Q_N1 * 8) return (IT_O << 16) | ((O_WIDE + (q >> 3)) << 8) | (q & 7);
    q -= Q_N1 * 8;
    if (q < Q_S1) return (IT_S4 << 16) | q;
    q -= Q_S1;
    if (q < (16 - O_WIDE - Q_N1) * 8) return (IT_O << 16) | ((O_WIDE + Q_N1 + (q >> 3)) << 8) | (q & 7);
    q -= (16 - O_WIDE - Q_N1) * 8;
    if (q < 128 - Q_S1) return (IT_S4 << 16) | (Q_S1 + q);
    return IT_END << 16;
}
__device__ __forceinline__ void tma2d_store(const CUtensorMap* m, uint32_t src, int c0, int c1) {
    asm volatile("cp.async.bulk.tensor.2d.global.shared::cta.bulk_group [%0, {%2, %3}], [%1];" ::"l"(m), "r"(src), "r"(c0), "r"(c1) : "memory");
}

__device__ __forceinline__ void wgmma_s64(float (&d)[32], uint32_t a0, uint32_t a1, uint32_t a2, uint32_t a3, uint64_t db, int acc) {
    asm volatile("{.reg .pred p; setp.ne.b32 p, %37, 0;\n"
        "wgmma.mma_async.sync.aligned.m64n64k16.f32.bf16.bf16 {"
        "%0,%1,%2,%3,%4,%5,%6,%7,%8,%9,%10,%11,%12,%13,%14,%15,"
        "%16,%17,%18,%19,%20,%21,%22,%23,%24,%25,%26,%27,%28,%29,%30,%31"
        "}, {%32,%33,%34,%35}, %36, p, 1, 1, 0;}"
        : "+f"(d[0]), "+f"(d[1]), "+f"(d[2]), "+f"(d[3]), "+f"(d[4]), "+f"(d[5]), "+f"(d[6]), "+f"(d[7]), "+f"(d[8]), "+f"(d[9]), "+f"(d[10]), "+f"(d[11]), "+f"(d[12]), "+f"(d[13]), "+f"(d[14]), "+f"(d[15]), "+f"(d[16]), "+f"(d[17]), "+f"(d[18]), "+f"(d[19]), "+f"(d[20]), "+f"(d[21]), "+f"(d[22]), "+f"(d[23]), "+f"(d[24]), "+f"(d[25]), "+f"(d[26]), "+f"(d[27]), "+f"(d[28]), "+f"(d[29]), "+f"(d[30]), "+f"(d[31])
        : "r"(a0), "r"(a1), "r"(a2), "r"(a3), "l"(db), "r"(acc));
}
__device__ __forceinline__ void wgmma_s16(float (&d)[8], uint32_t a0, uint32_t a1, uint32_t a2, uint32_t a3, uint64_t db, int acc) {
    asm volatile("{.reg .pred p; setp.ne.b32 p, %13, 0;\n"
        "wgmma.mma_async.sync.aligned.m64n16k16.f32.bf16.bf16 {"
        "%0,%1,%2,%3,%4,%5,%6,%7"
        "}, {%8,%9,%10,%11}, %12, p, 1, 1, 0;}"
        : "+f"(d[0]), "+f"(d[1]), "+f"(d[2]), "+f"(d[3]), "+f"(d[4]), "+f"(d[5]), "+f"(d[6]), "+f"(d[7])
        : "r"(a0), "r"(a1), "r"(a2), "r"(a3), "l"(db), "r"(acc));
}
__device__ __forceinline__ void wgmma_v128(float (&d)[64], uint32_t a0, uint32_t a1, uint32_t a2, uint32_t a3, uint64_t db, int acc) {
    asm volatile("{.reg .pred p; setp.ne.b32 p, %69, 0;\n"
        "wgmma.mma_async.sync.aligned.m64n128k16.f32.bf16.bf16 {"
        "%0,%1,%2,%3,%4,%5,%6,%7,%8,%9,%10,%11,%12,%13,%14,%15,"
        "%16,%17,%18,%19,%20,%21,%22,%23,%24,%25,%26,%27,%28,%29,%30,%31,"
        "%32,%33,%34,%35,%36,%37,%38,%39,%40,%41,%42,%43,%44,%45,%46,%47,"
        "%48,%49,%50,%51,%52,%53,%54,%55,%56,%57,%58,%59,%60,%61,%62,%63"
        "}, {%64,%65,%66,%67}, %68, p, 1, 1, 1;}"
        : "+f"(d[0]), "+f"(d[1]), "+f"(d[2]), "+f"(d[3]), "+f"(d[4]), "+f"(d[5]), "+f"(d[6]), "+f"(d[7]), "+f"(d[8]), "+f"(d[9]), "+f"(d[10]), "+f"(d[11]), "+f"(d[12]), "+f"(d[13]), "+f"(d[14]), "+f"(d[15]), "+f"(d[16]), "+f"(d[17]), "+f"(d[18]), "+f"(d[19]), "+f"(d[20]), "+f"(d[21]), "+f"(d[22]), "+f"(d[23]), "+f"(d[24]), "+f"(d[25]), "+f"(d[26]), "+f"(d[27]), "+f"(d[28]), "+f"(d[29]), "+f"(d[30]), "+f"(d[31]), "+f"(d[32]), "+f"(d[33]), "+f"(d[34]), "+f"(d[35]), "+f"(d[36]), "+f"(d[37]), "+f"(d[38]), "+f"(d[39]), "+f"(d[40]), "+f"(d[41]), "+f"(d[42]), "+f"(d[43]), "+f"(d[44]), "+f"(d[45]), "+f"(d[46]), "+f"(d[47]), "+f"(d[48]), "+f"(d[49]), "+f"(d[50]), "+f"(d[51]), "+f"(d[52]), "+f"(d[53]), "+f"(d[54]), "+f"(d[55]), "+f"(d[56]), "+f"(d[57]), "+f"(d[58]), "+f"(d[59]), "+f"(d[60]), "+f"(d[61]), "+f"(d[62]), "+f"(d[63])
        : "r"(a0), "r"(a1), "r"(a2), "r"(a3), "l"(db), "r"(acc));
}

__device__ __forceinline__ void attn_scores(float (&sx)[32], float (&sm)[8], const uint32_t (&q)[32], uint32_t sk) {
    const uint64_t dx = mkdesc(sk, 1024, 128, 0), dm = mkdesc(sk + 16384, 256, 128, 0);
    wg_fence();
#pragma unroll
    for (int ks = 0; ks < 8; ks++) {
        wgmma_s64(sx, q[4 * ks], q[4 * ks + 1], q[4 * ks + 2], q[4 * ks + 3], dx + ks * 128, ks);
        wgmma_s16(sm, q[4 * ks], q[4 * ks + 1], q[4 * ks + 2], q[4 * ks + 3], dm + ks * 32, ks);
    }
    wg_commit();
}
__device__ __forceinline__ void attn_softmax(uint32_t (&p)[20], const float (&sx)[32], const float (&sm)[8], int wi, int lane) {
    const bool sb = wi >= 2;
    const int r0 = (wi & 1) * 16 + (lane >> 2) - 2 * (lane & 3);
    float s[5][4];
#pragma unroll
    for (int j = 0; j < 4; j++) s[4][j] = sb ? sm[4 + j] : sm[j];
    float m0 = fmaxf(s[4][0], s[4][1]), m1 = fmaxf(s[4][2], s[4][3]);
#pragma unroll
    for (int j = 0; j < 4; j++) {
#pragma unroll
        for (int e = 0; e < 4; e++) s[j][e] = 8 * j + (e & 1) > r0 + 8 * (e >> 1) ? -INFINITY : sb ? sx[16 + 4 * j + e] : sx[4 * j + e];
        m0 = fmaxf(m0, fmaxf(s[j][0], s[j][1])); m1 = fmaxf(m1, fmaxf(s[j][2], s[j][3]));
    }
    m0 = fmaxf(m0, __shfl_xor_sync(0xffffffffu, m0, 1)); m1 = fmaxf(m1, __shfl_xor_sync(0xffffffffu, m1, 1));
    m0 = fmaxf(m0, __shfl_xor_sync(0xffffffffu, m0, 2)); m1 = fmaxf(m1, __shfl_xor_sync(0xffffffffu, m1, 2));
    const float cs = 0.08838834764831845f * 1.4426950408889634f;
    m0 *= -cs; m1 *= -cs;
    float l0 = 0, l1 = 0;
#pragma unroll
    for (int j = 0; j < 5; j++) {
        s[j][0] = ex2(fmaf(s[j][0], cs, m0)); s[j][1] = ex2(fmaf(s[j][1], cs, m0));
        s[j][2] = ex2(fmaf(s[j][2], cs, m1)); s[j][3] = ex2(fmaf(s[j][3], cs, m1));
        l0 += s[j][0] + s[j][1]; l1 += s[j][2] + s[j][3];
    }
    l0 += __shfl_xor_sync(0xffffffffu, l0, 1); l1 += __shfl_xor_sync(0xffffffffu, l1, 1);
    l0 += __shfl_xor_sync(0xffffffffu, l0, 2); l1 += __shfl_xor_sync(0xffffffffu, l1, 2);
    asm("rcp.approx.ftz.f32 %0, %0;" : "+f"(l0)); asm("rcp.approx.ftz.f32 %0, %0;" : "+f"(l1));
    const uint32_t ma = sb ? 0u : ~0u;
#pragma unroll
    for (int j = 0; j < 5; j++) {
        const uint32_t x = pack_bf16(s[j][0] * l0, s[j][1] * l0), y = pack_bf16(s[j][2] * l1, s[j][3] * l1);
        const int ia = j < 4 ? 2 * j : 16, ib = j < 4 ? 8 + 2 * j : 18;
        asm volatile("and.b32 %0, %4, %6; and.b32 %1, %5, %6; and.b32 %2, %4, %7; and.b32 %3, %5, %7;"
            : "=&r"(p[ia]), "=&r"(p[ia + 1]), "=&r"(p[ib]), "=&r"(p[ib + 1]) : "r"(x), "r"(y), "r"(ma), "r"(~ma));
    }
}
__device__ __forceinline__ void attn_pv(float (&o)[64], const uint32_t (&p)[20], uint32_t sv) {
    const uint64_t dx = mkdesc(sv, 128, 1024, 0), dm = mkdesc(sv + 16384, 128, 256, 0);
    wg_fence();
#pragma unroll
    for (int ks = 0; ks < 5; ks++) wgmma_v128(o, p[4 * ks], p[4 * ks + 1], p[4 * ks + 2], p[4 * ks + 3], ks < 4 ? dx + ks * 16 : dm, ks);
    wg_commit();
}
__device__ __forceinline__ void attn_stage(const float (&o)[64], uint32_t dst) {
#pragma unroll
    for (int u = 0; u < 16; u += 2)
        stsm4(dst + (u >> 3) * 8192 + (u & 7) * 128, pack_bf16(o[4 * u], o[4 * u + 1]), pack_bf16(o[4 * u + 2], o[4 * u + 3]),
              pack_bf16(o[4 * u + 4], o[4 * u + 5]), pack_bf16(o[4 * u + 6], o[4 * u + 7]));
}

template <int BN, int NKB, bool BLOCKED_A>
__device__ __forceinline__ void mainloop(float (&acc)[BN / 2], uint32_t sb, int wgi, uint32_t full, uint32_t empty, int& it, bool elect) {
#pragma unroll
    for (int j = 0; j < BN / 2; j++) acc[j] = 0.f;
#pragma unroll 1
    for (int k4 = 0; k4 < NKB; k4 += 4) {
#pragma unroll
        for (int st = 0; st < 4; st++, it++) {
            mbar_wait(full + 8 * st, (it >> 2) & 1);
            const uint64_t da = BLOCKED_A ? mkdesc(sb + st * G_STAGE + wgi * 8192, 128, 1024, 0) : mkdesc(sb + st * G_STAGE + wgi * 8192, 16, 1024, 1);
            const uint64_t db = mkdesc(sb + st * G_STAGE + 16384, 8192, 1024, 1);
            wg_fence();
#pragma unroll
            for (int k = 0; k < 4; k++) {
                if constexpr (BN == 256) wgmma256(acc, da + k * (BLOCKED_A ? 16 : 2), db + k * 128, 1);
                else wgmma128(acc, da + k * (BLOCKED_A ? 16 : 2), db + k * 128, 1);
            }
            wg_commit();
            if (k4 | st) {
                wg_wait<1>();
                if (elect) mbar_arrive(empty + 8 * ((st + 3) & 3));
            }
        }
    }
    wg_wait<0>();
    if (elect) mbar_arrive(empty + 8 * 3);
}

__device__ __forceinline__ uint32_t n6_a(int st) { return st < 4 ? st * G_STAGE : (2 * st - 8) * G_STAGE + 32768; }
__device__ __forceinline__ uint32_t n6_b(int st) { return st < 4 ? st * G_STAGE + 16384 : (2 * st - 7) * G_STAGE + 32768; }
__device__ __forceinline__ uint32_t n6_bar(int st) { return st < 4 ? 8 * st : 96 + 8 * st; }
__device__ __forceinline__ void mainloop6(float (&acc)[64], uint32_t sb, int wgi, uint32_t full, uint32_t empty, int& it, bool elect) {
#pragma unroll
    for (int j = 0; j < 64; j++) acc[j] = 0.f;
    int st = 0, prev = 0, r = 0;
#pragma unroll 1
    for (int kb = 0; kb < 64; kb++) {
        mbar_wait(full + n6_bar(st), ((st < 4 ? it >> 2 : 0) + r) & 1);
        const uint64_t da = mkdesc(sb + n6_a(st) + wgi * 8192, 128, 1024, 0), db = mkdesc(sb + n6_b(st), 8192, 1024, 1);
        wg_fence();
#pragma unroll
        for (int k = 0; k < 4; k++) wgmma128(acc, da + k * 16, db + k * 128, 1);
        wg_commit();
        if (kb) {
            wg_wait<1>();
            if (elect) mbar_arrive(empty + n6_bar(prev));
        }
        prev = st;
        if (++st == 6) { st = 0; r++; }
    }
    wg_wait<0>();
    if (elect) mbar_arrive(empty + 8 * 3);
    it += 44;
}

template <int BN>
__device__ __forceinline__ void o_item(uint32_t sb, int wgi, int wi, int lane, uint32_t full, uint32_t empty, int& it, const CUtensorMap* mout,
                                       int row0, int col0, uint32_t stgpar) {
    float acc[BN / 2];
    if constexpr (BN == 256) mainloop<BN, 64, true>(acc, sb, wgi, full, empty, it, lane == 0);
    else mainloop6(acc, sb, wgi, full, empty, it, lane == 0);
    mbar_wait(full + 104, stgpar);
    const uint32_t stg = sb + G_STG + (wgi * 4 + wi) * 4096;
    const int r = lane & 15, cu = lane >> 4;
#pragma unroll
    for (int hf = 0; hf < BN / 128; hf++) {
        if (lane == 0) asm volatile("cp.async.bulk.wait_group.read 0;" ::: "memory");
        __syncwarp();
#pragma unroll
        for (int j = 0; j < 8; j++) {
            const float* a = acc + hf * 64 + j * 8;
            stsm4(stg + (j >> 2) * 2048 + r * 128 + ((((j & 3) * 2 + cu) ^ (r & 7)) << 4),
                  pack_bf16(a[0], a[1]), pack_bf16(a[2], a[3]), pack_bf16(a[4], a[5]), pack_bf16(a[6], a[7]));
        }
        asm volatile("fence.proxy.async.shared::cta;" ::: "memory");
        __syncwarp();
        if (lane == 0) {
            tma2d_store(mout, stg, col0 + hf * 128, row0 + wgi * 64 + wi * 16);
            tma2d_store(mout, stg + 2048, col0 + hf * 128 + 64, row0 + wgi * 64 + wi * 16);
            asm volatile("cp.async.bulk.commit_group;" ::: "memory");
        }
    }
}

constexpr int S4_KD = 32768;
constexpr int S4_CH = 2 * G_STAGE;
constexpr int S4_HALF = 2304;
constexpr int S4_WD = 2 * S4_HALF;
constexpr int S4_STRIDE = S4_WD + 2304 + 16;
__device__ __forceinline__ uint32_t addz(uint32_t x, uint32_t z) { uint32_t r; asm volatile("add.u32 %0, %1, %2;" : "=r"(r) : "r"(x), "r"(z)); return r; }
__device__ __forceinline__ uint32_t lds16(uint32_t a) { uint32_t v; asm volatile("ld.shared.u16 %0, [%1];" : "=r"(v) : "r"(a) : "memory"); return v; }
__device__ __forceinline__ uint32_t ldsu(uint32_t a) { return __float_as_uint(lds32(a)); }

template <int E0, int NE, int KP>
__device__ __forceinline__ void s4_windows(float (&acc)[8][2][4], uint32_t ut, uint32_t kd, int rho, int w, int lane, uint32_t z) {
    const int gt = (lane >> 2) - 2 * (lane & 3), p0 = rho == 16 ? -3 : -2, c = (lane >> 3) + p0;
    uint32_t band[2][4], tw[2 * NE + 1], ta[NE][4];
    {
        uint32_t f[5];
#pragma unroll
        for (int m = 0; m < 5; m++) {
            const int d = 8 * (p0 + m - 1) - gt + rho;
            f[m] = (abs(d) <= w ? 0x3F80u : 0u) | (abs(d + 1) <= w ? 0x3F800000u : 0u);
        }
#pragma unroll
        for (int j = 0; j < 2; j++) { band[j][0] = f[2 * j + 1]; band[j][1] = addz(f[2 * j], z); band[j][2] = f[2 * j + 2]; band[j][3] = addz(f[2 * j + 1], z); }
    }
#pragma unroll
    for (int m = 0; m < 2 * NE + 1; m++) {
        const int q = 8 * (2 * E0 - 1 + m) + gt;
        const uint32_t lo = lds16(kd + q * KP), hi = lds16(kd + (q - 1) * KP);
        tw[m] = ((unsigned)(q - 16 * E0) < 16 * E0 ? lo : 0u) | ((unsigned)(q - 1 - 16 * E0) < 16 * E0 ? hi << 16 : 0u);
    }
#pragma unroll
    for (int e = 0; e < NE; e++) { ta[e][0] = tw[2 * e + 1]; ta[e][1] = tw[2 * e + 2]; ta[e][2] = addz(tw[2 * e], z); ta[e][3] = addz(tw[2 * e + 1], z); }
    const uint32_t ua = ut + (c & 1) * S4_HALF + (16 + (lane & 7) + (c >> 1)) * 16;
#pragma unroll
    for (int J = 0; J < 8 - E0; J++) {
        uint32_t u0[4], u1[4];
        ldsm4(u0, ua + J * 256); ldsm4(u1, ua + J * 256 + 128);
        float s0[4], s1[4];
        mma16z(s0, band[0], u0[0], u0[1]); mma16z(s1, band[0], u1[0], u1[1]);
        mma16(s0, band[1], u0[2], u0[3]); mma16(s1, band[1], u1[2], u1[3]);
        const uint32_t b00 = pack_bf16(s0[0], s0[1]), b01 = pack_bf16(s1[0], s1[1]), b10 = pack_bf16(s0[2], s0[3]), b11 = pack_bf16(s1[2], s1[3]);
#pragma unroll
        for (int e = 0; e < NE; e++)
            if (J + E0 + e < 8) { mma16(acc[J + E0 + e][0], ta[e], b00, b01); mma16(acc[J + E0 + e][1], ta[e], b10, b11); }
    }
}
template <int D0, int D1>
__device__ __forceinline__ void s4_dense(float (&acc)[8][2][4], uint32_t ua, const uint32_t (&b0)[4], const uint32_t (&b1)[4]) {
#pragma unroll
    for (int J = 0; J < 8 - D0; J++) {
        uint32_t a[4];
        ldsm4(a, ua + J * 256);
        mma16(acc[J + D0][0], a, b0[0], b0[1]); mma16(acc[J + D0][1], a, b0[2], b0[3]);
        if (J + D1 < 8) { mma16(acc[J + D1][0], a, b1[0], b1[1]); mma16(acc[J + D1][1], a, b1[2], b1[3]); }
    }
}
__device__ __forceinline__ void s4_words(uint32_t (&b)[4], uint32_t wd) {
    asm volatile("ld.shared.u32 %0, [%4]; ld.shared.u32 %1, [%4+-32]; ld.shared.u32 %2, [%4+32]; ld.volatile.shared.u32 %3, [%4];"
        : "=r"(b[0]), "=r"(b[1]), "=r"(b[2]), "=r"(b[3]) : "r"(wd) : "memory");
}

__device__ __forceinline__ void s4_item(uint32_t sb, int cw, int lane, int item, const bf16* __restrict__ dsk, uint32_t empty, const CUtensorMap* my, uint32_t stgpar) {
    const int gt = (lane >> 2) - 2 * (lane & 3);
    const uint32_t ch = sb + S4_CH + cw * S4_STRIDE, kd = sb + S4_KD + cw * 1536;
    const __nv_bfloat162 dk = __bfloat162bfloat162(dsk[item * 8 + cw]);
    ST(item, cw, 0);
    asm volatile("st.shared.v4.u32 [%0], {%1,%1,%1,%1};" ::"r"(ch + (lane >> 4) * S4_HALF + (lane & 15) * 16), "r"(0) : "memory");
    const uint32_t tch = sb + S4_CH + (lane & 7) * S4_STRIDE + ((lane >> 3) & 1) * S4_HALF + (16 + 16 * cw + (lane >> 4)) * 16;
#pragma unroll
    for (int i = 0; i < 8; i++) {
        uint32_t x[4];
        ldsm4t(x, sb + cw * 4096 + i * 512 + lane * 16);
        stsm4(tch + i * 32, x[0], x[1], x[2], x[3]);
    }
#pragma unroll 3
    for (int x0 = lane * 2 - 16; x0 < 560; x0 += 64) {
        uint32_t k[3];
#pragma unroll
        for (int j = 0; j < 3; j++) {
            const int x = x0 + j - 1, idx = x < 256 ? max(x, 0) : min(128 + ((x + ((x >> 1) & 1)) >> 1), 384);
            k[j] = lds16(kd + idx * 2);
            if ((unsigned)x > 514u) k[j] = 0;
        }
        asm volatile("st.shared.v2.u32 [%0], {%1,%2};" ::"r"(ch + S4_WD + 64 + x0 * 4), "r"(k[1] | (k[0] << 16)), "r"(k[2] | (k[1] << 16)) : "memory");
    }
    const uint32_t k1024 = lds16(kd + 1024);
    bar_sync(2, 256);
    ST(item, cw, 1);
    const uint32_t z = ldsu(ch);
    float acc[8][2][4];
#pragma unroll
    for (int j = 0; j < 16; j++) acc[j >> 1][j & 1][0] = acc[j >> 1][j & 1][1] = acc[j >> 1][j & 1][2] = acc[j >> 1][j & 1][3] = 0.f;
#pragma unroll 1
    for (int r = 1; r <= 4; r++) s4_windows<2, 3, 8>(acc, ch, kd + 512 + 2 * r, 4 * r, 2 - (r & 1), lane, z);
    ST(item, cw, 2);
#pragma unroll 1
    for (int r = 1; r <= 2; r++) s4_windows<4, 4, 4>(acc, ch, kd + 768 + 2 * r, 8 * r, 2 + r, lane, z);
    ST(item, cw, 3);
    const uint32_t ua = ch + (lane >> 4) * S4_HALF + (16 + (lane & 15)) * 16, wd = ch + S4_WD + 64 + gt * 4;
#pragma unroll 1
    for (int q = 0; q < 2; q++) {
        uint32_t b0[4], b1[4];
        s4_words(b0, wd + (q + 32) * 64);
#pragma unroll
        for (int j = 0; j < 4; j++) {
            const int x = 16 * q + gt + (j == 1 ? -8 : j == 2 ? 8 : 0) - 3;
            b1[j] = addz(((unsigned)x < 2u ? k1024 : 0u) | ((unsigned)(x - 1) < 2u ? k1024 << 16 : 0u), z);
        }
        s4_dense<2, 4>(acc, ua - q * 16, b0, b1);
    }
    {
        uint32_t b0[4], b1[4], c0[4], c1[4];
        s4_words(b0, wd); s4_words(b1, wd + 1024);
#pragma unroll 1
        for (int q = 0; q < 16; q += 2) {
            s4_words(c0, wd + q * 64 + 64); s4_words(c1, wd + q * 64 + 64 + 1024);
            s4_dense<0, 1>(acc, ua - q * 16, b0, b1);
            s4_words(b0, wd + q * 64 + 128); s4_words(b1, wd + q * 64 + 128 + 1024);
            s4_dense<0, 1>(acc, ua - q * 16 - 16, c0, c1);
            if (q == S4REL && lane == 0) { mbar_arrive(empty); mbar_arrive(empty + 8); }
        }
    }
    ST(item, cw, 4);
    mbar_wait(empty + 72, stgpar);
    if (lane == 0) asm volatile("cp.async.bulk.wait_group.read 0;" ::: "memory");
    __syncwarp();
#pragma unroll
    for (int I = 0; I < 8; I++) {
        uint32_t u[4];
        ldsm4(u, ua + I * 256);
#pragma unroll
        for (int j = 0; j < 4; j++) {
            const uint32_t y = pack_bf16(acc[I][j >> 1][2 * (j & 1)], acc[I][j >> 1][2 * (j & 1) + 1]);
            const __nv_bfloat162 r = __hadd2_rn(*(const __nv_bfloat162*)&y, __hmul2_rn(*(const __nv_bfloat162*)&u[j], dk));
            u[j] = *(const uint32_t*)&r;
        }
        stsm4(ua + I * 256, u[0], u[1], u[2], u[3]);
    }
    bar_sync(2, 256);
#pragma unroll
    for (int i = 0; i < 8; i++) {
        uint32_t y[4];
        ldsm4t(y, tch + i * 32);
        stsm4(sb + G_STG + cw * 4096 + i * 512 + lane * 16, y[0], y[1], y[2], y[3]);
    }
    asm volatile("fence.proxy.async.shared::cta;" ::: "memory");
    __syncwarp();
    if (lane == 0) {
        mbar_arrive(empty + 16); mbar_arrive(empty + 24);
        tma2d_store(my, sb + G_STG + cw * 4096, DM + item * 8, cw * 256);
        asm volatile("cp.async.bulk.commit_group;" ::: "memory");
    }
    ST(item, cw, 5);
}

__global__ void __launch_bounds__(384, 1)
worker_kernel(const __grid_constant__ CUtensorMap mx, const __grid_constant__ CUtensorMap mq, const __grid_constant__ CUtensorMap mk,
              const __grid_constant__ CUtensorMap mv, const __grid_constant__ CUtensorMap mo,
              const __grid_constant__ CUtensorMap mout, const __grid_constant__ CUtensorMap mu, const __grid_constant__ CUtensorMap my,
              const __grid_constant__ CUtensorMap mkx, const __grid_constant__ CUtensorMap mvx, const __grid_constant__ CUtensorMap mkm,
              const __grid_constant__ CUtensorMap mvm, const bf16* __restrict__ dsk) {
    extern __shared__ unsigned char smem_raw[];
    const uint32_t sb = (smem_u32(smem_raw) + 1023) & ~1023u;
    const uint32_t full = sb + G_BAR, empty = full + 32, ifull = full + 64, iempty = full + 80, islot = full + 96, stgbar = full + 104, sigbar = full + 112, sigslot = full + 120;
    const int tid = threadIdx.x, wg = tid >> 7, lane = tid & 31;
    int q0 = blockIdx.x;
    const int wide0 = q0 - ((int)gridDim.x - O_WIDE * 4);
    if (tid == 0) {
        if (q0 >= 32 && wide0 < 0) q0 = 32 + atomicAdd(g_ctr + C_NEXT, 1);
        for (int i = 0; i < 6; i++) { mbar_init(full + n6_bar(i), 1); mbar_init(empty + n6_bar(i), 8); }
        for (int i = 0; i < 2; i++) { mbar_init(ifull + 8 * i, 1); mbar_init(iempty + 8 * i, 8); }
        mbar_init(sigbar, 8); mbar_init(stgbar, 1);
        asm volatile("fence.proxy.async;" ::: "memory");
    }
    __syncthreads();
    if (wg == 0) {
        reg_dec<40>();
        if (tid >= 32 && tid < 64) {
            for (int n = 0;; n++) {
                mbar_wait_long(sigbar, n & 1);
                int item; asm volatile("ld.shared.u32 %0, [%1];" : "=r"(item) : "r"(sigslot + 4 * (n & 1)) : "memory");
                const int type = item >> 16, b = (item >> 8) & 255, i = item & 255;
                if (type == IT_END) break;
                if (type == IT_QA) {
                    if (lane == 0) {
                        for (int j = 0; j < 8; j++) {
                            const uint32_t src = sb + (j >= 4 ? G_STG + (j & 1) * 16384 : 3 * G_STAGE + (j & 1) * 20480) + ((j >> 1) & 1) * 8192;
                            asm volatile("cp.async.bulk.global.shared::cta.bulk_group [%0], [%1], 8192;"
                                ::"l"(g_ox + (size_t)(b * 64 + i * 4 + ((j >> 1) ^ 2)) * 8192 + (j & 1) * 4096), "r"(src) : "memory");
                            if ((j & 3) == 3) asm volatile("cp.async.bulk.commit_group;" ::: "memory");
                        }
                        asm volatile("cp.async.bulk.wait_group.read 1;" ::: "memory");
                        asm volatile("mbarrier.arrive.shared.b64 _, [%0], 8;" ::"r"(empty + 24) : "memory");
                        asm volatile("cp.async.bulk.wait_group 0;" ::: "memory");
                        mbar_arrive(stgbar);
                        asm volatile("fence.proxy.async;" ::: "memory");
                    }
                    __syncwarp();
                }
                __threadfence();
                if (type == IT_KV) { if (lane < 6) atomicAdd(g_kvf + ((i & 15) * 6 + lane) * 16 + b, 1); }
                else if (lane == 0) atomicAdd(g_ctr + C_QA_DONE + b, 1);
            }
        } else if (tid < 32) {
            int it = 0;
            if (!KVN) asm volatile("griddepcontrol.wait;" ::: "memory");
            for (int n = 0;; n++) {
                int item = 0;
                if (lane == 0) {
                    const int q = n == 0 ? q0 : 32 + atomicAdd(g_ctr + C_NEXT, 1);
                    item = n == 0 && wide0 >= 0 ? (IT_O << 16) | ((wide0 >> 2) << 8) | (wide0 & 3) : queue_item(q);
                }
                item = __shfl_sync(0xffffffffu, item, 0);
                if (lane == 0) {
                    mbar_wait(iempty + 8 * (n & 1), ((n >> 1) & 1) ^ 1);
                    asm volatile("st.shared.u32 [%0], %1;" ::"r"(islot + 4 * (n & 1)), "r"(item) : "memory");
                    mbar_arrive(ifull + 8 * (n & 1));
                    const int type = item >> 16, b = (item >> 8) & 255, i = item & 255;
                    if (type == IT_QA || type == IT_KV) {
                        const CUtensorMap* mw = type == IT_QA ? &mq : i < 16 ? &mk : &mv;
                        bool ready = false;
                        for (int kb = 0; kb < 16; kb++, it++) {
                            const int st = it & 3;
                            mbar_wait(empty + 8 * st, ((it >> 2) & 1) ^ 1);
                            mbar_expect(full + 8 * st, G_STAGE);
                            const uint32_t a = sb + st * G_STAGE;
                            tma2d(a, &mx, kb * 64, b * 128, full + 8 * st);
                            tma3d(a + 16384, mw, 0, kb * 64, (i & 15) * 4, full + 8 * st);
                            tma3d(a + 32768, mw, 0, kb * 64, (i & 15) * 4 + 2, full + 8 * st);
                            if (type == IT_QA && kb == 3) ready = ld_acq(g_ctr + C_CHAIN + b) >= 96;
                            if (type == IT_QA && kb >= 3 && kb < 11) {
                                const size_t sh = (b * 4 + ((kb - 3) & 3)) * NH + i * 2;
                                asm volatile("cp.async.bulk.prefetch.L2.global [%0], 16384;" ::"l"((kb >= 7 ? g_vx : g_kx) + sh * 4096) : "memory");
                                if (ready) asm volatile("cp.async.bulk.prefetch.L2.global [%0], 4096;" ::"l"((kb >= 7 ? g_vm : g_km) + sh * 1024) : "memory");
                            }
                        }
                    }
                    if (type == IT_QA) {
                        wait_ctr(g_ctr + C_CHAIN + b, 96);
                        asm volatile("fence.proxy.async;" ::: "memory");
                        for (int st = 0; st < 4; st++, it++) {
                            mbar_wait(empty + 8 * st, ((it >> 2) & 1) ^ 1);
                            mbar_expect(full + 8 * st, 4 * 10240);
                            for (int g2 = 0; g2 < 2; g2++) {
                                tma3d(sb + st * G_STAGE + g2 * 20480, st < 2 ? &mkx : &mvx, 0, b * 4 + g2 * 2, (i * 2 + (st & 1)) * 16, full + 8 * st);
                                tma3d(sb + st * G_STAGE + g2 * 20480 + 16384, st < 2 ? &mkm : &mvm, 0, b * 4 + g2 * 2, (i * 2 + (st & 1)) * 16, full + 8 * st);
                            }
                        }
                    } else if (type == IT_O) {
                        const bool wide = b < O_WIDE;
                        wait_ctr(g_ctr + C_QA_DONE + b, 16);
                        asm volatile("fence.proxy.async;" ::: "memory");
                        if (OPF)
                            for (int j = i; j < 64; j += wide ? 4 : 8)
                                if (j >= 6) asm volatile("cp.async.bulk.prefetch.L2.global [%0], 16384;" ::"l"(g_ox + (size_t)(b * 64 + j) * 8192) : "memory");
                        const int ns = wide ? 4 : 6;
                        for (int kb = 0, st = 0, r = 0; kb < 64; kb++) {
                            const uint32_t bo = n6_bar(st);
                            mbar_wait(empty + bo, (((st < 4 ? it >> 2 : 0) + r) & 1) ^ 1);
                            mbar_expect(full + bo, wide ? G_STAGE : 32768);
                            bulk_load(sb + n6_a(st), g_ox + (size_t)(b * 64 + kb) * 8192, 16384, full + bo);
                            tma3d(sb + n6_b(st), &mo, 0, kb * 64, wide ? i * 4 : i * 2, full + bo);
                            if (wide) tma3d(sb + n6_b(st) + 16384, &mo, 0, kb * 64, i * 4 + 2, full + bo);
                            if (++st == ns) { st = 0; r++; }
                        }
                        it += wide ? 64 : 44;
                    } else if (type == IT_S4) {
                        wait_ctr(g_ctr + C_CHAIN, 96);
                        asm volatile("fence.proxy.async;" ::: "memory");
                        mbar_wait(empty, ((it >> 2) & 1) ^ 1);
                        mbar_expect(full, 32768 + 12288);
                        bulk_load(sb + S4_KD, g_kd + i * 8 * 768, 12288, full);
                        for (int j = 0; j < 8; j++) tma2d(sb + j * 4096, &mu, i * 8, j * 256, full);
                        for (int st = 1; st < 4; st++) { mbar_wait(empty + 8 * st, ((it >> 2) & 1) ^ 1); mbar_arrive(full + 8 * st); }
                        it += 4;
                        mbar_wait_long(empty, ((it >> 2) & 1) ^ 1);
                    }
                }
                __syncwarp();
                if (item >> 16 == IT_END) break;
            }
            asm volatile("griddepcontrol.wait;" ::: "memory");
        }
    } else {
        reg_inc<232>();
        const int wu = __shfl_sync(0xffffffffu, tid >> 5, 0);
        const int wgi = (wu >> 2) - 1, wi = wu & 3;
        int it = 0, nqa = 0, nsig = 0, n = 0, item;
        auto next_item = [&]() {
            mbar_wait_long(ifull + 8 * (n & 1), (n >> 1) & 1);
            asm volatile("ld.shared.u32 %0, [%1];" : "=r"(item) : "r"(islot + 4 * (n & 1)) : "memory");
            __syncwarp();
            if (lane == 0) mbar_arrive(iempty + 8 * (n & 1));
        };
        auto signal = [&](int what) {
            if (tid == 128) asm volatile("st.shared.u32 [%0], %1;" ::"r"(sigslot + 4 * (nsig & 1)), "r"(what) : "memory");
            __syncwarp();
            if (lane == 0) mbar_arrive(sigbar);
            nsig++;
        };
        next_item();
        if (item >> 16 == IT_KV) {
            float acc[128];
            uint32_t pk[64];
            uint32_t* dst = nullptr;
            int prev = 0;
            do {
                WLOG(0);
#pragma unroll
                for (int kb = 0; kb < 16; kb++, it++) {
                    const int st = kb & 3;
                    mbar_wait(full + 8 * st, (it >> 2) & 1);
                    const uint64_t da = mkdesc(sb + st * G_STAGE + wgi * 8192, 16, 1024, 1);
                    const uint64_t db = mkdesc(sb + st * G_STAGE + 16384, 8192, 1024, 1);
                    wg_fence();
#pragma unroll
                    for (int k = 0; k < 4; k++) wgmma256(acc, da + k * 2, db + k * 128, kb | k);
                    wg_commit();
                    if (kb < KVS && dst) {
#pragma unroll
                        for (int j = kb * (64 / KVS); j < (kb + 1) * (64 / KVS); j++) st_out(dst + (j >> 1) * 128 + (j & 1) * 32, pk[j]);
                        if (kb == KVS - 1) signal(prev);
                    }
                    if (kb > 0) {
                        wg_wait<1>();
                        if (lane == 0) mbar_arrive(empty + 8 * ((kb - 1) & 3));
                    }
                }
                wg_wait<0>();
                if (lane == 0) mbar_arrive(empty + 8 * 3);
#pragma unroll
                for (int j = 0; j < 64; j++) pk[j] = pack_bf16(acc[2 * j], acc[2 * j + 1]);
                const int row = ((item >> 8) & 255) * 128 + wgi * 64 + wi * 16, nt = item & 255;
                dst = (uint32_t*)(nt < 16 ? g_kx : g_vx) + (size_t)((row >> 5) * 512 + (nt & 15) * 32) * 128 + (row & 31) * 4 + lane;
                prev = item;
                if (n == 0) {
#pragma unroll
                    for (int j = 0; j < 64; j++) dst[(j >> 1) * 128 + (j & 1) * 32] = pk[j];
                    signal(prev);
                    dst = nullptr;
                }
                WLOG(1);
                n++;
                next_item();
            } while (item >> 16 == IT_KV);
            if (dst) {
#pragma unroll
                for (int j = 0; j < 64; j++) dst[(j >> 1) * 128 + (j & 1) * 32] = pk[j];
                signal(prev);
            }
        }
        for (;; n++, next_item()) {
            const int type = item >> 16, b = (item >> 8) & 255, i = item & 255;
            const int lane = (tid & 31) + (item >> 24), wgi = (wu >> 2) - 1 + __shfl_sync(0xffffffffu, item >> 24, 0), wi = wu & 3;
            WLOG(0);
            if (type == IT_QA) {
                float acc[128];
                ST(sid, cw, 0);
                ST(sid, cw, 1);
                mainloop<256, 16, false>(acc, sb, wgi, full, empty, it, lane == 0);
                ST(sid, cw, 2);
                uint32_t q0[32], q1[32];
#pragma unroll
                for (int j = 0; j < 32; j++) { q0[j] = pack_bf16(acc[2 * j], acc[2 * j + 1]); q1[j] = pack_bf16(acc[64 + 2 * j], acc[65 + 2 * j]); }
                const uint32_t par = (it >> 2) & 1, so = sb + wgi * 20480;
                float sx0[32] = {}, sm0[8] = {}, sx1[32] = {}, sm1[8] = {};
                uint32_t p0[20], p1[20];
                if (lane == 0) asm volatile("cp.async.bulk.wait_group.read 0;" ::: "memory");
                mbar_wait(stgbar, (nqa++ & 1) ^ 1);
                bar_sync(3 + wgi, 128);
                mbar_wait_long(full, par);
                ST(sid, cw, 3);
                attn_scores(sx0, sm0, q0, so);
                ST(sid, cw, 7);
                mbar_wait(full + 8, par);
                attn_scores(sx1, sm1, q1, so + G_STAGE);
                float o0[64] = {}, o1[64] = {};
                if (ATT2) {
                    ST(sid, cw, 8);
                    wg_wait<0>();
                    ST(sid, cw, 9);
                    if (lane == 0) { mbar_arrive(empty); mbar_arrive(empty + 8); }
                    attn_softmax(p0, sx0, sm0, wi, lane);
                    attn_softmax(p1, sx1, sm1, wi, lane);
                    ST(sid, cw, 10);
                    mbar_wait(full + 16, par);
                    ST(sid, cw, 11);
                    attn_pv(o0, p0, so + 2 * G_STAGE);
                    ST(sid, cw, 4);
                } else {
                    wg_wait<1>();
                    if (lane == 0) mbar_arrive(empty);
                    attn_softmax(p0, sx0, sm0, wi, lane);
                    mbar_wait(full + 16, par);
                    attn_pv(o0, p0, so + 2 * G_STAGE);
                    wg_wait<1>();
                    if (lane == 0) mbar_arrive(empty + 8);
                    ST(sid, cw, 4);
                    attn_softmax(p1, sx1, sm1, wi, lane);
                }
                mbar_wait(full + 24, par);
                attn_pv(o1, p1, so + 3 * G_STAGE);
                wg_wait<1>();
                if (lane == 0) mbar_arrive(empty + 16);
                ST(sid, cw, 5);
                const uint32_t da = (wi * 2 + ((lane >> 3) & 1)) * 1024 + (lane >> 4) * 128 + (lane & 7) * 16;
                attn_stage(o0, sb + G_STG + wgi * 16384 + da);
                wg_wait<0>();
                bar_sync(3 + wgi, 128);
                attn_stage(o1, so + 3 * G_STAGE + da);
                asm volatile("fence.proxy.async.shared::cta;" ::: "memory");
                ST(sid, cw, 6);
                signal(item);
                it += 4;
            } else if (type == IT_O) {
                mbar_wait_long(full, (it >> 2) & 1);
                if (b < O_WIDE) o_item<256>(sb, wgi, wi, lane, full, empty, it, &mout, b * 128, i * 256, (nqa & 1) ^ 1);
                else o_item<128>(sb, wgi, wi, lane, full, empty, it, &mout, b * 128, i * 128, (nqa & 1) ^ 1);
            } else if (type == IT_S4) {
                mbar_wait_long(full, (it >> 2) & 1);
                mbar_wait(full + 24, (it >> 2) & 1);
                s4_item(sb, wgi * 4 + wi, lane, i, dsk, empty, &my, (nqa & 1) ^ 1);
                it += 4;
            } else break;
            WLOG(1);
        }
        bar_sync(2, 256);
        signal(item);
        if (lane == 0) asm volatile("cp.async.bulk.wait_group 0;" ::: "memory");
    }
}

typedef CUresult (*EncodeFn)(CUtensorMap*, CUtensorMapDataType, cuuint32_t, void*, const cuuint64_t*, const cuuint64_t*, const cuuint32_t*,
                             const cuuint32_t*, CUtensorMapInterleave, CUtensorMapSwizzle, CUtensorMapL2promotion, CUtensorMapFloatOOBfill);
static EncodeFn get_encode() {
    void* fn = nullptr; cudaDriverEntryPointQueryResult st;
    cudaGetDriverEntryPoint("cuTensorMapEncodeTiled", &fn, cudaEnableDefault, &st);
    return (EncodeFn)fn;
}
static void map_act(EncodeFn enc, CUtensorMap* m, const void* p, int rows, int cols, int boxr) {
    cuuint64_t dim[2] = {(cuuint64_t)cols, (cuuint64_t)rows}, str[1] = {(cuuint64_t)cols * 2};
    cuuint32_t box[2] = {64, (cuuint32_t)boxr}, es[2] = {1, 1};
    enc(m, CU_TENSOR_MAP_DATA_TYPE_BFLOAT16, 2, (void*)p, dim, str, box, es, CU_TENSOR_MAP_INTERLEAVE_NONE, CU_TENSOR_MAP_SWIZZLE_128B,
        CU_TENSOR_MAP_L2_PROMOTION_L2_128B, CU_TENSOR_MAP_FLOAT_OOB_FILL_NONE);
}
static void map_w(EncodeFn enc, CUtensorMap* m, const void* p, int k, int n) {
    cuuint64_t dim[3] = {64, (cuuint64_t)k, (cuuint64_t)n / 64}, str[2] = {(cuuint64_t)n * 2, 128};
    cuuint32_t box[3] = {64, 64, 2}, es[3] = {1, 1, 1};
    enc(m, CU_TENSOR_MAP_DATA_TYPE_BFLOAT16, 3, (void*)p, dim, str, box, es, CU_TENSOR_MAP_INTERLEAVE_NONE, CU_TENSOR_MAP_SWIZZLE_128B,
        CU_TENSOR_MAP_L2_PROMOTION_L2_256B, CU_TENSOR_MAP_FLOAT_OOB_FILL_NONE);
}

static void map_kv(EncodeFn enc, CUtensorMap* m, void* p, int n) {
    cuuint64_t dim[3] = {(cuuint64_t)n, NSEG, 512}, str[2] = {(cuuint64_t)n * 1024, (cuuint64_t)n * 2};
    cuuint32_t box[3] = {(cuuint32_t)n, 2, 16}, es[3] = {1, 1, 1};
    enc(m, CU_TENSOR_MAP_DATA_TYPE_BFLOAT16, 3, p, dim, str, box, es, CU_TENSOR_MAP_INTERLEAVE_NONE, CU_TENSOR_MAP_SWIZZLE_NONE,
        CU_TENSOR_MAP_L2_PROMOTION_NONE, CU_TENSOR_MAP_FLOAT_OOB_FILL_NONE);
}
static void map_box(EncodeFn enc, CUtensorMap* m, const void* p, int rows, int ld, int boxc, int boxr, CUtensorMapSwizzle sw,
                    CUtensorMapL2promotion promo = CU_TENSOR_MAP_L2_PROMOTION_NONE) {
    cuuint64_t dim[2] = {(cuuint64_t)ld, (cuuint64_t)rows}, str[1] = {(cuuint64_t)ld * 2};
    cuuint32_t box[2] = {(cuuint32_t)boxc, (cuuint32_t)boxr}, es[2] = {1, 1};
    enc(m, CU_TENSOR_MAP_DATA_TYPE_BFLOAT16, 2, (void*)p, dim, str, box, es, CU_TENSOR_MAP_INTERLEAVE_NONE, sw,
        promo, CU_TENSOR_MAP_FLOAT_OOB_FILL_NONE);
}

extern "C" void kernel_launch(void* const* d_in, const int* in_sizes, int n_in, void* d_out, int out_size) {
    const bf16* x = (const bf16*)d_in[0];
    const bf16* mem0 = (const bf16*)d_in[1];
    const bf16 *Wq = (const bf16*)d_in[2], *Wk = (const bf16*)d_in[3], *Wv = (const bf16*)d_in[4], *Wo = (const bf16*)d_in[5];
    static EncodeFn enc = nullptr;
    static int nsm = 0;
    static void* kv[4];
    if (!enc) {
        enc = get_encode();
        cudaGetSymbolAddress(&kv[0], g_kx); cudaGetSymbolAddress(&kv[1], g_vx); cudaGetSymbolAddress(&kv[2], g_km); cudaGetSymbolAddress(&kv[3], g_vm);
        cudaDeviceGetAttribute(&nsm, cudaDevAttrMultiProcessorCount, 0);
        cudaFuncSetAttribute(chain_kernel, cudaFuncAttributeMaxDynamicSharedMemorySize, CH_SMEM);
        cudaFuncSetAttribute(worker_kernel, cudaFuncAttributeMaxDynamicSharedMemorySize, G_SMEM);
    }
    CUtensorMap mx, mq, mk, mv, mo, mout, mu, my;
    map_act(enc, &mx, x, S_LEN, DM, 128);
    map_w(enc, &mq, Wq, DM, HD); map_w(enc, &mk, Wk, DM, HD); map_w(enc, &mv, Wv, DM, HD); map_w(enc, &mo, Wo, HD, DM);
    map_box(enc, &mout, d_out, S_LEN, 2 * DM, 64, 16, CU_TENSOR_MAP_SWIZZLE_128B);
    map_box(enc, &mu, d_in[7], S_LEN, DM, 8, 256, CU_TENSOR_MAP_SWIZZLE_NONE, (CUtensorMapL2promotion)PROMU);
    map_box(enc, &my, d_out, S_LEN, 2 * DM, 8, 256, CU_TENSOR_MAP_SWIZZLE_NONE);
    CUtensorMap mkx, mvx, mkm, mvm;
    map_kv(enc, &mkx, kv[0], 256); map_kv(enc, &mvx, kv[1], 256); map_kv(enc, &mkm, kv[2], 64); map_kv(enc, &mvm, kv[3], 64);
    CUtensorMap cq, ck, cv, co;
    map_box(enc, &cq, Wq, DM, HD, 32, 32, CU_TENSOR_MAP_SWIZZLE_64B, (CUtensorMapL2promotion)PROMO); map_box(enc, &ck, Wk, DM, HD, 32, 32, CU_TENSOR_MAP_SWIZZLE_64B, (CUtensorMapL2promotion)PROMO);
    map_box(enc, &cv, Wv, DM, HD, 32, 32, CU_TENSOR_MAP_SWIZZLE_64B, (CUtensorMapL2promotion)PROMO); map_box(enc, &co, Wo, HD, DM, 32, 16, CU_TENSOR_MAP_SWIZZLE_64B, (CUtensorMapL2promotion)PROMO);
    S4Params P = {(const bf16*)d_in[8], (const bf16*)d_in[9], (const bf16*)d_in[10], (const bf16*)d_in[11],
                  (const bf16*)d_in[12], (const bf16*)d_in[13], (const bf16*)d_in[14], (const bf16*)d_in[15]};
    int aware = 1;
    cudaLaunchAttribute at[1];
    at[0].id = cudaLaunchAttributeProgrammaticStreamSerialization;
    at[0].val.programmaticStreamSerializationAllowed = 1;
    cudaLaunchConfig_t cfg = {};
    cfg.stream = cudaStreamPerThread;
    cfg.gridDim = dim3(96); cfg.blockDim = dim3(CH_THREADS); cfg.dynamicSmemBytes = CH_SMEM;
    cudaLaunchKernelEx(&cfg, chain_kernel, cq, ck, cv, co, Wq, Wk, Wv, mem0, P, aware);
    cfg.attrs = at; cfg.numAttrs = 1;
    cfg.gridDim = dim3(nsm); cfg.blockDim = dim3(384); cfg.dynamicSmemBytes = G_SMEM;
    cudaLaunchKernelEx(&cfg, worker_kernel, mx, mq, mk, mv, mo, mout, mu, my, mkx, mvx, mkm, mvm, P.dsk);
}
```

```cpp
#include <cuda.h>
#include <cuda_runtime.h>
#include <cuda_bf16.h>
#include <stdint.h>
#include <stdio.h>
#include <string.h>

typedef __nv_bfloat16 bf16;

constexpr int S_LEN = 2048, DM = 1024, NH = 32, DH = 128, HD = 4096, NSEG = 64;
constexpr uint32_t SENT = 0xFFFFFFFFu;
constexpr int SPIN_LIMIT = 1 << 18;
#define REALL 0

__device__ __align__(1024) bf16 g_kx[S_LEN * HD];
__device__ __align__(1024) bf16 g_vx[S_LEN * HD];
__device__ __align__(1024) bf16 g_ox[S_LEN * HD];
__device__ __align__(1024) bf16 g_km[NSEG * NH * 8 * DH];
__device__ __align__(1024) bf16 g_vm[NSEG * NH * 8 * DH];
__device__ __align__(1024) bf16 g_kd[DM * 768 + 8192];
__device__ __align__(1024) char g_ring[2 << 20];
__device__ int g_kvf[96 * 16];
constexpr int C_NEXT = 0, C_CHAIN = 32, C_QA_DONE = 64, N_CTR = 96;
__device__ int g_ctr[N_CTR];

__device__ __forceinline__ uint32_t smem_u32(const void* p) { return (uint32_t)__cvta_generic_to_shared(p); }
__device__ __forceinline__ uint32_t clk() { uint32_t c; asm volatile("mov.u32 %0, %%clock;" : "=r"(c)::"memory"); return c; }
__device__ __forceinline__ uint32_t pack_bf16(float lo, float hi) {
    uint32_t r; asm("cvt.rn.bf16x2.f32 %0, %1, %2;" : "=r"(r) : "f"(hi), "f"(lo)); return r;
}
__device__ __forceinline__ uint32_t movm(uint32_t a) {
    uint32_t d; asm volatile("movmatrix.sync.aligned.m8n8.trans.b16 %0, %1;" : "=r"(d) : "r"(a)); return d;
}
__device__ __forceinline__ void mma16(float (&d)[4], const uint32_t (&a)[4], uint32_t b0, uint32_t b1) {
    asm volatile("mma.sync.aligned.m16n8k16.row.col.f32.bf16.bf16.f32 {%0,%1,%2,%3}, {%4,%5,%6,%7}, {%8,%9}, {%0,%1,%2,%3};"
        : "+f"(d[0]), "+f"(d[1]), "+f"(d[2]), "+f"(d[3]) : "r"(a[0]), "r"(a[1]), "r"(a[2]), "r"(a[3]), "r"(b0), "r"(b1));
}
__device__ __forceinline__ void mma16z(float (&d)[4], const uint32_t (&a)[4], uint32_t b0, uint32_t b1) {
    asm volatile("mma.sync.aligned.m16n8k16.row.col.f32.bf16.bf16.f32 {%0,%1,%2,%3}, {%4,%5,%6,%7}, {%8,%9}, {%10,%10,%10,%10};"
        : "=f"(d[0]), "=f"(d[1]), "=f"(d[2]), "=f"(d[3]) : "r"(a[0]), "r"(a[1]), "r"(a[2]), "r"(a[3]), "r"(b0), "r"(b1), "f"(0.f));
}
__device__ __forceinline__ void mma8z(float (&d)[4], uint32_t a0, uint32_t a1, uint32_t b0) {
    asm volatile("mma.sync.aligned.m16n8k8.row.col.f32.bf16.bf16.f32 {%0,%1,%2,%3}, {%4,%5}, {%6}, {%7,%7,%7,%7};"
        : "=f"(d[0]), "=f"(d[1]), "=f"(d[2]), "=f"(d[3]) : "r"(a0), "r"(a1), "r"(b0), "f"(0.f));
}
__device__ __forceinline__ void ldsm4t(uint32_t (&r)[4], uint32_t addr) {
    asm volatile("ldmatrix.sync.aligned.m8n8.x4.trans.shared.b16 {%0,%1,%2,%3}, [%4];"
        : "=r"(r[0]), "=r"(r[1]), "=r"(r[2]), "=r"(r[3]) : "r"(addr) : "memory");
}
__device__ __forceinline__ void ldsm4(uint32_t (&r)[4], uint32_t addr) {
    asm volatile("ldmatrix.sync.aligned.m8n8.x4.shared.b16 {%0,%1,%2,%3}, [%4];"
        : "=r"(r[0]), "=r"(r[1]), "=r"(r[2]), "=r"(r[3]) : "r"(addr) : "memory");
}
__device__ __forceinline__ float lds32(uint32_t a) {
    float v; asm volatile("ld.shared.f32 %0, [%1];" : "=f"(v) : "r"(a) : "memory"); return v;
}
__device__ __forceinline__ void st_async1(uint32_t dst, float v, uint32_t bar) {
    asm volatile("st.async.shared::cluster.mbarrier::complete_tx::bytes.f32 [%0], %1, [%2];" ::"r"(dst), "f"(v), "r"(bar) : "memory");
}
__device__ __forceinline__ void st_async2(uint32_t dst, float x, float y, uint32_t bar) {
    asm volatile("st.async.shared::cluster.mbarrier::complete_tx::bytes.v2.f32 [%0], {%1,%2}, [%3];" ::"r"(dst), "f"(x), "f"(y), "r"(bar) : "memory");
}
__device__ __forceinline__ void mma8(float (&d)[4], uint32_t a0, uint32_t a1, uint32_t b0) {
    asm volatile("mma.sync.aligned.m16n8k8.row.col.f32.bf16.bf16.f32 {%0,%1,%2,%3}, {%4,%5}, {%6}, {%0,%1,%2,%3};"
        : "+f"(d[0]), "+f"(d[1]), "+f"(d[2]), "+f"(d[3]) : "r"(a0), "r"(a1), "r"(b0));
}
__device__ __forceinline__ void cp16(uint32_t dst, const void* src) {
    asm volatile("cp.async.cg.shared.global [%0], [%1], 16;" ::"r"(dst), "l"(src) : "memory");
}
__device__ __forceinline__ void sts128(uint32_t a, const float (&v)[4]) {
    asm volatile("st.shared.v4.f32 [%0], {%1,%2,%3,%4};" ::"r"(a), "f"(v[0]), "f"(v[1]), "f"(v[2]), "f"(v[3]) : "memory");
}
__device__ __forceinline__ float4 lds128(uint32_t a) {
    float4 v; asm volatile("ld.shared.v4.f32 {%0,%1,%2,%3}, [%4];" : "=f"(v.x), "=f"(v.y), "=f"(v.z), "=f"(v.w) : "r"(a) : "memory"); return v;
}
__device__ __forceinline__ void sts64(uint32_t a, float x, float y) {
    asm volatile("st.shared.v2.f32 [%0], {%1,%2};" ::"r"(a), "f"(x), "f"(y) : "memory");
}
__device__ __forceinline__ float2 lds64(uint32_t a) {
    float2 v; asm volatile("ld.shared.v2.f32 {%0,%1}, [%2];" : "=f"(v.x), "=f"(v.y) : "r"(a) : "memory"); return v;
}
__device__ __forceinline__ void bar_sync(int id, int n) { asm volatile("bar.sync %0, %1;" ::"r"(id), "r"(n) : "memory"); }
__device__ __forceinline__ void bar_arrive(int id, int n) { asm volatile("bar.arrive %0, %1;" ::"r"(id), "r"(n) : "memory"); }
__device__ __forceinline__ uint32_t mapa(uint32_t a, uint32_t r) {
    uint32_t o; asm("mapa.shared::cluster.u32 %0, %1, %2;" : "=r"(o) : "r"(a), "r"(r)); return o;
}
__device__ __forceinline__ void st_async4(uint32_t dst, float4 v, uint32_t bar) {
    asm volatile("st.async.shared::cluster.mbarrier::complete_tx::bytes.v4.f32 [%0], {%1,%2,%3,%4}, [%5];"
        ::"r"(dst), "f"(v.x), "f"(v.y), "f"(v.z), "f"(v.w), "r"(bar) : "memory");
}
__device__ __forceinline__ void mbar_init(uint32_t bar, int n) { asm volatile("mbarrier.init.shared.b64 [%0], %1;" ::"r"(bar), "r"(n) : "memory"); }
__device__ __forceinline__ void mbar_expect(uint32_t bar, int bytes) {
    asm volatile("mbarrier.arrive.expect_tx.shared.b64 _, [%0], %1;" ::"r"(bar), "r"(bytes) : "memory");
}
__device__ __forceinline__ void bulk_load(uint32_t dst, const void* src, int bytes, uint32_t bar) {
    asm volatile("cp.async.bulk.shared::cluster.global.mbarrier::complete_tx::bytes [%0], [%1], %2, [%3];"
        ::"r"(dst), "l"(src), "r"(bytes), "r"(bar) : "memory");
}
__device__ __forceinline__ bool mbar_try(uint32_t bar, uint32_t par) {
    uint32_t ok;
    asm volatile("{.reg .pred p; mbarrier.try_wait.parity.shared::cta.b64 p, [%1], %2; selp.u32 %0, 1, 0, p;}"
        : "=r"(ok) : "r"(bar), "r"(par) : "memory");
    return ok;
}
__device__ __forceinline__ bool mbar_test(uint32_t bar, uint32_t par) {
    uint32_t ok;
    asm volatile("{.reg .pred p; mbarrier.test_wait.parity.shared::cta.b64 p, [%1], %2; selp.u32 %0, 1, 0, p;}"
        : "=r"(ok) : "r"(bar), "r"(par) : "memory");
    return ok;
}
__device__ __forceinline__ int ld_acq(const int* p) { int v; asm volatile("ld.acquire.gpu.global.s32 %0, [%1];" : "=r"(v) : "l"(p) : "memory"); return v; }
__device__ __forceinline__ void wait_ctr(const int* p, int n) {
    for (int it = 0; it < (1 << 20) && ld_acq(p) < n; it++) __nanosleep(64);
}
__device__ __forceinline__ void mbar_wait(uint32_t bar, uint32_t par) {
    if (!mbar_try(bar, par))
        for (int it = 0; it < SPIN_LIMIT && !mbar_try(bar, par); it++) {}
}
__device__ __forceinline__ void mbar_wait_long(uint32_t bar, uint32_t par) {
    for (int it = 0; it < (1 << 24) && !mbar_try(bar, par); it++) {}
}
__device__ __forceinline__ float4 add4(float4 a, float4 b) { return make_float4(a.x + b.x, a.y + b.y, a.z + b.z, a.w + b.w); }
__device__ __forceinline__ float ex2(float x) { float y; asm("ex2.approx.ftz.f32 %0, %1;" : "=f"(y) : "f"(x)); return y; }

__device__ __forceinline__ void wgmma256(float (&d)[128], uint64_t da, uint64_t db, int acc) {
    asm volatile("{.reg .pred p; setp.ne.b32 p, %130, 0;\n"
        "wgmma.mma_async.sync.aligned.m64n256k16.f32.bf16.bf16 {"
        "%0,%1,%2,%3,%4,%5,%6,%7,%8,%9,%10,%11,%12,%13,%14,%15,"
        "%16,%17,%18,%19,%20,%21,%22,%23,%24,%25,%26,%27,%28,%29,%30,%31,"
        "%32,%33,%34,%35,%36,%37,%38,%39,%40,%41,%42,%43,%44,%45,%46,%47,"
        "%48,%49,%50,%51,%52,%53,%54,%55,%56,%57,%58,%59,%60,%61,%62,%63,"
        "%64,%65,%66,%67,%68,%69,%70,%71,%72,%73,%74,%75,%76,%77,%78,%79,"
        "%80,%81,%82,%83,%84,%85,%86,%87,%88,%89,%90,%91,%92,%93,%94,%95,"
        "%96,%97,%98,%99,%100,%101,%102,%103,%104,%105,%106,%107,%108,%109,%110,%111,"
        "%112,%113,%114,%115,%116,%117,%118,%119,%120,%121,%122,%123,%124,%125,%126,%127"
        "}, %128, %129, p, 1, 1, 0, 1;}"
        : "+f"(d[0]), "+f"(d[1]), "+f"(d[2]), "+f"(d[3]), "+f"(d[4]), "+f"(d[5]), "+f"(d[6]), "+f"(d[7]), "+f"(d[8]), "+f"(d[9]), "+f"(d[10]), "+f"(d[11]), "+f"(d[12]), "+f"(d[13]), "+f"(d[14]), "+f"(d[15]), "+f"(d[16]), "+f"(d[17]), "+f"(d[18]), "+f"(d[19]), "+f"(d[20]), "+f"(d[21]), "+f"(d[22]), "+f"(d[23]), "+f"(d[24]), "+f"(d[25]), "+f"(d[26]), "+f"(d[27]), "+f"(d[28]), "+f"(d[29]), "+f"(d[30]), "+f"(d[31]), "+f"(d[32]), "+f"(d[33]), "+f"(d[34]), "+f"(d[35]), "+f"(d[36]), "+f"(d[37]), "+f"(d[38]), "+f"(d[39]), "+f"(d[40]), "+f"(d[41]), "+f"(d[42]), "+f"(d[43]), "+f"(d[44]), "+f"(d[45]), "+f"(d[46]), "+f"(d[47]), "+f"(d[48]), "+f"(d[49]), "+f"(d[50]), "+f"(d[51]), "+f"(d[52]), "+f"(d[53]), "+f"(d[54]), "+f"(d[55]), "+f"(d[56]), "+f"(d[57]), "+f"(d[58]), "+f"(d[59]), "+f"(d[60]), "+f"(d[61]), "+f"(d[62]), "+f"(d[63]), "+f"(d[64]), "+f"(d[65]), "+f"(d[66]), "+f"(d[67]), "+f"(d[68]), "+f"(d[69]), "+f"(d[70]), "+f"(d[71]), "+f"(d[72]), "+f"(d[73]), "+f"(d[74]), "+f"(d[75]), "+f"(d[76]), "+f"(d[77]), "+f"(d[78]), "+f"(d[79]), "+f"(d[80]), "+f"(d[81]), "+f"(d[82]), "+f"(d[83]), "+f"(d[84]), "+f"(d[85]), "+f"(d[86]), "+f"(d[87]), "+f"(d[88]), "+f"(d[89]), "+f"(d[90]), "+f"(d[91]), "+f"(d[92]), "+f"(d[93]), "+f"(d[94]), "+f"(d[95]), "+f"(d[96]), "+f"(d[97]), "+f"(d[98]), "+f"(d[99]), "+f"(d[100]), "+f"(d[101]), "+f"(d[102]), "+f"(d[103]), "+f"(d[104]), "+f"(d[105]), "+f"(d[106]), "+f"(d[107]), "+f"(d[108]), "+f"(d[109]), "+f"(d[110]), "+f"(d[111]), "+f"(d[112]), "+f"(d[113]), "+f"(d[114]), "+f"(d[115]), "+f"(d[116]), "+f"(d[117]), "+f"(d[118]), "+f"(d[119]), "+f"(d[120]), "+f"(d[121]), "+f"(d[122]), "+f"(d[123]), "+f"(d[124]), "+f"(d[125]), "+f"(d[126]), "+f"(d[127])
        : "l"(da), "l"(db), "r"(acc));
}
__device__ __forceinline__ void wgmma128(float (&d)[64], uint64_t da, uint64_t db, int acc) {
    asm volatile("{.reg .pred p; setp.ne.b32 p, %66, 0;\n"
        "wgmma.mma_async.sync.aligned.m64n128k16.f32.bf16.bf16 {"
        "%0,%1,%2,%3,%4,%5,%6,%7,%8,%9,%10,%11,%12,%13,%14,%15,"
        "%16,%17,%18,%19,%20,%21,%22,%23,%24,%25,%26,%27,%28,%29,%30,%31,"
        "%32,%33,%34,%35,%36,%37,%38,%39,%40,%41,%42,%43,%44,%45,%46,%47,"
        "%48,%49,%50,%51,%52,%53,%54,%55,%56,%57,%58,%59,%60,%61,%62,%63"
        "}, %64, %65, p, 1, 1, 0, 1;}"
        : "+f"(d[0]), "+f"(d[1]), "+f"(d[2]), "+f"(d[3]), "+f"(d[4]), "+f"(d[5]), "+f"(d[6]), "+f"(d[7]), "+f"(d[8]), "+f"(d[9]), "+f"(d[10]), "+f"(d[11]), "+f"(d[12]), "+f"(d[13]), "+f"(d[14]), "+f"(d[15]), "+f"(d[16]), "+f"(d[17]), "+f"(d[18]), "+f"(d[19]), "+f"(d[20]), "+f"(d[21]), "+f"(d[22]), "+f"(d[23]), "+f"(d[24]), "+f"(d[25]), "+f"(d[26]), "+f"(d[27]), "+f"(d[28]), "+f"(d[29]), "+f"(d[30]), "+f"(d[31]), "+f"(d[32]), "+f"(d[33]), "+f"(d[34]), "+f"(d[35]), "+f"(d[36]), "+f"(d[37]), "+f"(d[38]), "+f"(d[39]), "+f"(d[40]), "+f"(d[41]), "+f"(d[42]), "+f"(d[43]), "+f"(d[44]), "+f"(d[45]), "+f"(d[46]), "+f"(d[47]), "+f"(d[48]), "+f"(d[49]), "+f"(d[50]), "+f"(d[51]), "+f"(d[52]), "+f"(d[53]), "+f"(d[54]), "+f"(d[55]), "+f"(d[56]), "+f"(d[57]), "+f"(d[58]), "+f"(d[59]), "+f"(d[60]), "+f"(d[61]), "+f"(d[62]), "+f"(d[63])
        : "l"(da), "l"(db), "r"(acc));
}
__device__ __forceinline__ void wg_fence() { asm volatile("wgmma.fence.sync.aligned;" ::: "memory"); }
__device__ __forceinline__ void wg_commit() { asm volatile("wgmma.commit_group.sync.aligned;" ::: "memory"); }
template <int N> __device__ __forceinline__ void wg_wait() { asm volatile("wgmma.wait_group.sync.aligned %0;" ::"n"(N) : "memory"); }
__device__ __forceinline__ uint64_t mkdesc(uint32_t addr, uint32_t lbo, uint32_t sbo, uint32_t sw) {
    return (uint64_t)((addr & 0x3FFFF) >> 4) | ((uint64_t)(lbo >> 4) << 16) | ((uint64_t)(sbo >> 4) << 32) | ((uint64_t)sw << 62);
}
__device__ __forceinline__ void tma2d(uint32_t dst, const CUtensorMap* m, int c0, int c1, uint32_t bar) {
    asm volatile("cp.async.bulk.tensor.2d.shared::cluster.global.mbarrier::complete_tx::bytes [%0], [%1, {%2, %3}], [%4];"
        ::"r"(dst), "l"(m), "r"(c0), "r"(c1), "r"(bar) : "memory");
}
__device__ __forceinline__ void tma3d(uint32_t dst, const CUtensorMap* m, int c0, int c1, int c2, uint32_t bar) {
    asm volatile("cp.async.bulk.tensor.3d.shared::cluster.global.mbarrier::complete_tx::bytes [%0], [%1, {%2, %3, %4}], [%5];"
        ::"r"(dst), "l"(m), "r"(c0), "r"(c1), "r"(c2), "r"(bar) : "memory");
}
__device__ __forceinline__ void tma3d_mc(uint32_t dst, const CUtensorMap* m, int c0, int c1, int c2, uint32_t bar, uint16_t mask) {
    asm volatile("cp.async.bulk.tensor.3d.shared::cluster.global.mbarrier::complete_tx::bytes.multicast::cluster [%0], [%1, {%2, %3, %4}], [%5], %6;"
        ::"r"(dst), "l"(m), "r"(c0), "r"(c1), "r"(c2), "r"(bar), "h"(mask) : "memory");
}
__device__ __forceinline__ void mbar_arrive(uint32_t bar) { asm volatile("mbarrier.arrive.shared.b64 _, [%0];" ::"r"(bar) : "memory"); }
__device__ __forceinline__ void mbar_arrive_remote(uint32_t bar) {
    asm volatile("mbarrier.arrive.shared::cluster.b64 _, [%0];" ::"r"(bar) : "memory");
}
template <int R> __device__ __forceinline__ void reg_inc() { asm volatile("setmaxnreg.inc.sync.aligned.u32 %0;" ::"n"(R)); }
template <int R> __device__ __forceinline__ void reg_dec() { asm volatile("setmaxnreg.dec.sync.aligned.u32 %0;" ::"n"(R)); }

#define ST(id, w, i)
constexpr int CH_NRES = 50;
constexpr int CH_WREG = CH_NRES * 512;
constexpr int CH_PART = 8 * CH_WREG;
constexpr int CH_SX = CH_PART + 16384;
constexpr int CH_MX = CH_SX + 3 * 1280;
constexpr int CH_QK = CH_MX;
constexpr int CH_XS = CH_MX + 3 * 512;
constexpr int CH_BAR = CH_XS + 5632;
constexpr int CH_SMEM = CH_BAR + 192;
constexpr int CH_THREADS = 384;

__device__ __forceinline__ char* ring_base() { return (char*)(((uintptr_t)g_ring + (1 << 20) - 1) & ~(uintptr_t)((1 << 20) - 1)); }
__device__ __forceinline__ uint32_t ring_off(int chunk, int side) {
    uint32_t o = ((chunk & 1) << 13) | ((chunk >> 1) << 16);
    uint32_t par = ((o >> 13) ^ (o >> 16) ^ (o >> 17) ^ (o >> 19) ^ side) & 1;
    return o | (par << 12);
}
__device__ __forceinline__ uint2 ld_poll(const char* p) {
    unsigned long long v; asm volatile("ld.relaxed.gpu.global.b64 %0, [%1];" : "=l"(v) : "l"(p) : "memory");
    return make_uint2((uint32_t)v, (uint32_t)(v >> 32));
}
__device__ __forceinline__ void st_pub(char* p, uint32_t x, uint32_t y) {
    unsigned long long v = ((unsigned long long)y << 32) | x;
    asm volatile("st.relaxed.gpu.global.b64 [%0], %1;" ::"l"(p), "l"(v) : "memory");
}
template <int N>
__device__ __forceinline__ void poll_issue(uint2 (&b)[N], const char* p, bool lastvalid) {
#pragma unroll
    for (int i = 0; i < N; i++) {
        if (i < N - 1 || lastvalid) b[i] = ld_poll(p + i * 256);
        else b[i] = make_uint2(0, 0);
    }
}
template <int N>
__device__ __forceinline__ int poll_check(uint2 (&b)[N], const char* p, uint32_t z) {
    int it = 0;
    uint32_t mx = z;
#pragma unroll
    for (int i = 0; i < N; i++) mx = max(mx, b[i].x);
    if (__any_sync(0xffffffffu, mx == SENT)) {
        do {
#pragma unroll
            for (int i = 0; i < N; i++)
                if ((REALL && i < 10) || b[i].x == SENT) b[i] = ld_poll(p + i * 256);
            mx = b[0].x;
#pragma unroll
            for (int i = 1; i < N; i++) mx = max(mx, b[i].x);
            it++;
        } while (__any_sync(0xffffffffu, mx == SENT && it < SPIN_LIMIT));
    }
    return it;
}
template <int N>
__device__ __forceinline__ uint32_t delay(uint32_t a) {
    uint32_t z = 0;
#pragma unroll
    for (int i = 0; i < N; i++) asm volatile("ld.volatile.shared.u32 %0, [%1];" : "=r"(z) : "r"(a + z) : "memory");
    return z;
}

#define PFKV 0
#define LDW 0
#define KGS 3
constexpr int KVN = 2;
#define FEN 1
#define XB 4
#define KEEP 100
#define PE 0
#define PROMO 2
#define PROMU 0
#define FNC 1
#define CL 8
#define PL 0
#define ML 4
#define MP 2
#define VCH_P 4
#define VCH_C 2
#define DLM 3
#define DLO 5
constexpr int OB = 0;
template <int PACE, int I0 = 0, int I1 = 12>
__device__ __forceinline__ void preload(uint32_t (&sw)[12][4], uint32_t a, uint32_t zero) {
    uint32_t z = 0;
#pragma unroll
    for (int i = I0; i < I1; i++) {
        if (PACE && i % (PACE ? PACE : 1) == 0) z = delay<1>(zero + z);
        ldsm4t(sw[i], a + z + i * 512);
    }
}
__device__ __forceinline__ void stsm4(uint32_t addr, uint32_t a, uint32_t b, uint32_t c, uint32_t d) {
    asm volatile("stmatrix.sync.aligned.m8n8.x4.shared.b16 [%0], {%1,%2,%3,%4};" ::"r"(addr), "r"(a), "r"(b), "r"(c), "r"(d) : "memory");
}
__device__ __forceinline__ void stsm4t(uint32_t addr, uint32_t a, uint32_t b, uint32_t c, uint32_t d) {
    asm volatile("stmatrix.sync.aligned.m8n8.x4.trans.shared.b16 [%0], {%1,%2,%3,%4};" ::"r"(addr), "r"(a), "r"(b), "r"(c), "r"(d) : "memory");
}
__device__ __forceinline__ void st_part(uint32_t addr, const float (&x)[4], const float (&y)[4]) {
    stsm4(addr, pack_bf16(x[0], x[1]), pack_bf16(x[2], x[3]), pack_bf16(y[0], y[1]), pack_bf16(y[2], y[3]));
}
template <bool TR>
__device__ __forceinline__ void red_part(uint32_t& lo, uint32_t& hi, uint32_t addr, uint32_t eye) {
    uint32_t a[4][4];
#pragma unroll
    for (int j = 0; j < 4; j++) { if (TR) ldsm4t(a[j], addr + j * 1024); else ldsm4(a[j], addr + j * 1024); }
    float r0[4], r1[4], r2[4], r3[4];
    mma16z(r0, a[0], eye, eye); mma16z(r1, a[1], eye, eye); mma16z(r2, a[2], eye, eye); mma16z(r3, a[3], eye, eye);
#pragma unroll
    for (int j = 0; j < 4; j++) r0[j] = ((r0[j] + r1[j]) + r2[j]) + r3[j];
    lo = pack_bf16(r0[0], r0[1]); hi = pack_bf16(r0[2], r0[3]);
}
__device__ __forceinline__ int o_chunk(int ks, int& pos) {
    const int cw = ks < 176 ? ks / 11 : 16 + (ks - 176) / 10;
    pos = ks - (cw < 16 ? 11 * cw : 176 + 10 * (cw - 16));
    return cw;
}

template <bool PV>
__device__ __forceinline__ void chain_loop(const uint32_t (&wa)[36][4], const uint32_t sb, const int w, const int lane0, const int rank,
                                           const int h, const int side) {
    const int rk1 = rank == 2 ? 0 : rank + 1, rk2 = rank == 0 ? 2 : rank - 1;
    const int nq = rank == 0 ? 6 : 5, u0 = rank == 0 ? 0 : 1 + 5 * rank, v0 = rank == 0 ? -6 : 3 * rank - 6;
    const uint32_t pt = CH_PART + (w >> 1) * 4096 + (w & 1) * 256;
    const uint32_t barS = sb + CH_BAR, barM = barS + 8, zero = barS + 24;
    char* const ring0 = ring_base();
    const uint32_t m_rd = ring_off(24 + w, side), o_rd = ring_off(rank * 8 + w, side);
    uint32_t pub;
    if (PV) { int pos, cw = o_chunk(h * 8 + v0 + w, pos); pub = (ring_off(cw, 0) & ~4096u) + pos * 256; }
    else pub = (ring_off(24 + (h >> 2), 0) & ~4096u) + ((2 * h + w) & 7) * 256;
    char* const kvo = (char*)(PV ? g_vm + 128 * (v0 + w) : g_km + 64 * (u0 + w)) + h * 2048;
    const bool mown = !PV && w == rank && rank < 2;
    uint32_t lo16 = lane0 * 16;
    uint32_t sw[12][4];
#pragma unroll
    for (int i = 0; i < 12; i++) ldsm4t(sw[i], sb + lo16 + w * CH_WREG + i * 512);

#pragma unroll 1
    for (int s = 0;; s++) {
        const bool last = s == NSEG - 1;
        const uint32_t slot = (s & 3) << 14;
        lo16 += delay<DLM>(zero);
        const uint32_t lane = lo16 >> 4, l16 = sb + lo16, wl = l16 + w * CH_WREG, pw = l16 + CH_PART + w * 512;
        const uint32_t xs = l16 + CH_XS + nq * 512 + (w - nq) * 1024;
        const uint32_t eye = ((lo16 >> 7) == (lane & 3)) ? ((lo16 & 64) ? 0x3F800000u : 0x3F80u) : 0u;
        uint2 b[8];
        const char* pm = ring0 + (m_rd + slot + (lo16 >> 1));
        poll_issue<8>(b, pm, true);
        preload<0, ML, 12>(sw, wl, zero);
        if (FNC & 1) bar_arrive(14, 256);
        poll_check<8>(b, pm, delay<FNC & 1>(zero));
        if ((OB || (XB & 1)) && !last) bar_arrive(8, 256 + OB);
        if (PV && !last && w == 7) bar_arrive(13, 64);
        {
            float acc[6][4];
#pragma unroll
            for (int kk = 0; kk < 8; kk++) {
                const int j = (2 * kk) % 12;
                if (kk == 0) { mma16z(acc[5], sw[0], b[0].x, b[0].y); mma16z(acc[4], sw[1], b[0].x, b[0].y); }
                else { mma16(acc[5], sw[j], b[kk].x, b[kk].y); mma16(acc[4], sw[j + 1], b[kk].x, b[kk].y); }
#pragma unroll
                for (int i = 0; i < 4; i++) {
                    if (kk == 0) mma16z(acc[i], wa[i * 8], b[0].x, b[0].y);
                    else mma16(acc[i], wa[i * 8 + kk], b[kk].x, b[kk].y);
                    if (i < 2) ldsm4t(sw[j + i], wl + (12 + 2 * kk + i) * 512);
                }
            }
            st_part(pw + 4 * 2048, acc[4], acc[5]);
            st_part(pw, acc[0], acc[1]);
            st_part(pw + 2 * 2048, acc[2], acc[3]);
        }
        uint32_t kv0, kv1;
        const uint32_t lp = l16 + (lane >> 4) * 256, pl = lp + pt;
        if (!PV) {
            bar_sync(1, last ? 256 : 256 + OB);
            red_part<true>(kv1, kv0, pl, eye);
            sts64(l16 + CH_QK + (w >> 1) * 512 + (w & 1) * 8, __uint_as_float(kv1), __uint_as_float(kv0));
            if (!last) bar_arrive(2, nq * 32 + 64 + OB);
        } else {
            bar_sync(1, last ? 256 : 256 + OB);
        }
        {
            float va[4][4];
            const float z = __uint_as_float(delay<1>(zero));
#pragma unroll
            for (int i = 0; i < 4; i++) va[i][0] = va[i][1] = va[i][2] = va[i][3] = z;
#pragma unroll
            for (int kk = 0; kk < 8; kk++) {
                const int c = (PV ? VCH_P : VCH_C) == 4 ? kk & 1 : 0;
                if (kk < 2) { mma16(va[c], wa[32 + 2 * kk], b[kk].x, b[kk].y); mma16(va[2 + c], wa[33 + 2 * kk], b[kk].x, b[kk].y); }
                else { mma16(va[c], sw[(2 * kk) % 12], b[kk].x, b[kk].y); mma16(va[2 + c], sw[(2 * kk + 1) % 12], b[kk].x, b[kk].y); }
            }
            if ((PV ? VCH_P : VCH_C) == 4) {
#pragma unroll
                for (int j = 0; j < 4; j++) { va[0][j] += va[1][j]; va[2][j] += va[3][j]; }
            }
            st_part(pw + 6 * 2048, va[0], va[2]);
        }
        if (PV) {
            uint32_t vt0[4], vt1[4];
            ldsm4t(vt0, xs); ldsm4t(vt1, xs + 512);
            if (w >= 6 && !last) {
                uint32_t kx[3][4];
#pragma unroll
                for (int j = 0; j < 3; j++)
                    ldsm4(kx[j], sb + CH_XS + j * 1024 + (j == 2 && nq == 5 ? 0 : ((lane >> 3) & 1) * 512) + (w - 6) * 256 + (lane >> 4) * 128 + (lane & 7) * 16);
                const uint32_t da = l16 + CH_SX + rank * 1280 + (w - 6) * 512, dc = sb + CH_SX + rank * 1280 + 1024 + lane * 8;
                bar_sync(2, nq * 32 + 64 + OB);
                uint32_t qk[3][4];
#pragma unroll
                for (int j = 0; j < 3; j++) {
                    const float4 v = lds128(l16 + CH_QK + j * 512);
                    qk[j][0] = __float_as_uint(v.x); qk[j][1] = __float_as_uint(v.y); qk[j][2] = __float_as_uint(v.z); qk[j][3] = __float_as_uint(v.w);
                }
                float s0[4], s1[4], s2[4], s3[4];
                mma16z(s0, qk[0], kx[0][0], kx[0][1]); mma16z(s1, qk[0], kx[0][2], kx[0][3]);
                mma16z(s2, qk[1], kx[1][0], kx[1][1]); mma16z(s3, qk[1], kx[1][2], kx[1][3]);
                if (nq == 5) qk[2][2] = qk[2][3] = 0;
                mma16(s0, qk[2], kx[2][0], kx[2][1]); mma16(s1, qk[2], kx[2][2], kx[2][3]);
                float m0[4], m1[4];
                mma16z(m0, qk[0], qk[0][1], qk[0][3]); mma16z(m1, qk[1], qk[1][1], qk[1][3]);
                mma16(m0, qk[2], qk[2][1], qk[2][3]);
                const float4 sv = make_float4(s0[0] + s2[0], s0[1] + s2[1], s1[0] + s3[0], s1[1] + s3[1]);
                st_async4(mapa(da, rk1), sv, mapa(barS, rk1));
                st_async4(mapa(da, rk2), sv, mapa(barS, rk2));
                {
                    const float c0 = m0[0] + m1[0], c1 = m0[1] + m1[1];
                    const int dr = w == 6 ? rk1 : rk2;
                    st_async2(mapa(dc, dr), c0, c1, mapa(barS, dr));
                    sts64(dc, c0, c1);
                }
                const float t4[4] = {sv.x, sv.y, sv.z, sv.w};
                sts128(da, t4);
            }
            bar_sync(3, last ? 256 : 256 + OB);
            if (!last && w == 7) bar_arrive(12, 64);
            red_part<false>(kv0, kv1, pl, eye);
            if (last) {
                uint32_t* d = (uint32_t*)(kvo + (uint32_t)(s * (NH * 2048) + lane * 4));
                d[0] = movm(kv0); d[32] = movm(kv1);
                break;
            }
            {
                const uint32_t sx = l16 + CH_SX, r0 = rank * 1280, r1 = rk1 * 1280, r2 = rk2 * 1280;
                float4 a0 = lds128(sx + r0), b0 = lds128(sx + 512 + r0);
                const float2 c0 = lds64(sx + 1024 + r0 - lane * 8);
                preload<0, 0, PE>(sw, wl + 28 * 512, zero);
                mbar_wait(barS, s & 1);
                const float4 a1 = lds128(sx + r1), a2 = lds128(sx + r2), b1 = lds128(sx + 512 + r1), b2 = lds128(sx + 512 + r2);
                const float2 c1 = lds64(sx + 1024 + r1 - lane * 8), c2 = lds64(sx + 1024 + r2 - lane * 8);
                a0 = add4(add4(a0, a1), a2); b0 = add4(add4(b0, b1), b2);
                float sc[10] = {a0.x, a0.y, a0.z, a0.w, b0.x, b0.y, b0.z, b0.w, c0.x + c1.x + c2.x, c0.y + c1.y + c2.y};
                float mx = fmaxf(fmaxf(fmaxf(sc[0], sc[1]), fmaxf(sc[2], sc[3])), fmaxf(fmaxf(sc[4], sc[5]), fmaxf(sc[6], sc[7])));
                mx = fmaxf(mx, fmaxf(sc[8], sc[9]));
                mx = fmaxf(fmaxf(mx, __shfl_xor_sync(0xffffffffu, mx, 1)),
                           fmaxf(__shfl_xor_sync(0xffffffffu, mx, 2), __shfl_xor_sync(0xffffffffu, mx, 3)));
                const float cs = 0.08838834764831845f * 1.4426950408889634f;
                const float mb = -mx * cs;
#pragma unroll
                for (int j = 0; j < 10; j++) sc[j] = ex2(fmaf(sc[j], cs, mb));
                uint32_t pf[5];
#pragma unroll
                for (int j = 0; j < 5; j++) pf[j] = pack_bf16(sc[2 * j], sc[2 * j + 1]);
                float o0[4], o1[4], o2[4], o3[4], o4[4], o5[4];
                const uint32_t p0[4] = {pf[0], 0, pf[1], 0}, p1[4] = {pf[2], 0, pf[3], 0};
                mma16z(o0, p0, vt0[0], vt0[1]); mma16z(o1, p0, vt1[0], vt1[1]);
                mma16z(o2, p1, vt0[2], vt0[3]); mma16z(o3, p1, vt1[2], vt1[3]);
                mma8z(o4, pf[4], 0, kv0); mma8z(o5, pf[4], 0, kv1);
                float sum = (((sc[0] + sc[1]) + (sc[2] + sc[3])) + ((sc[4] + sc[5]) + (sc[6] + sc[7]))) + (sc[8] + sc[9]);
                sum = (sum + __shfl_xor_sync(0xffffffffu, sum, 1)) + (__shfl_xor_sync(0xffffffffu, sum, 2) + __shfl_xor_sync(0xffffffffu, sum, 3));
                float inv; asm("rcp.approx.ftz.f32 %0, %1;" : "=f"(inv) : "f"(sum));
                const uint32_t ox = pack_bf16((o0[0] + o2[0] + o4[0]) * inv, (o0[1] + o2[1] + o4[1]) * inv);
                const uint32_t oy = pack_bf16((o1[0] + o3[0] + o5[0]) * inv, (o1[1] + o3[1] + o5[1]) * inv);
                char* const pp = ring0 + (pub + slot + (lo16 >> 1));
                st_pub(pp, ox, oy); st_pub(pp + 4096, ox, oy);
                if (OB || (XB & 4)) bar_arrive(10, (8 - nq) * 32 + OB);
                preload<0, PE, PL>(sw, wl + 28 * 512, zero);
            }
            kv0 = movm(kv0); kv1 = movm(kv1);
        } else {
            *(uint32_t*)(kvo + (uint32_t)(s * (NH * 2048) + lane * 4)) = kv0;
            bar_sync(3, last ? 256 : 256 + OB);
            if (last) break;
            preload<1, 0, CL>(sw, wl + 28 * 512, zero);
        }
        uint2 c[11];
        bar_sync(4, 256 + OB);
        const char* po = ring0 + (o_rd + slot + (lo16 >> 1) + delay<DLO>(zero));
        poll_issue<11>(c, po, rank < 2);
        preload<0, PV ? PL : CL, 12>(sw, wl + 28 * 512, zero);
        if (PV) { uint32_t* d = (uint32_t*)(kvo + (uint32_t)(s * (NH * 2048) + lane * 4)); d[0] = kv0; d[32] = kv1; }
        if (FNC & 2) bar_arrive(15, 256);
        poll_check<11>(c, po, delay<(FNC >> 1)>(zero));
        if (OB || (XB & 2)) bar_arrive(9, 256 + OB);
        {
            float acc[4][4];
#pragma unroll
            for (int f = 0; f < 22; f++) {
                const int kk = f >> 1, a = f & 3;
                if (f < 4) mma16z(acc[a], sw[f % 12], c[kk].x, c[kk].y);
                else mma16(acc[a], sw[f % 12], c[kk].x, c[kk].y);
                if (f + 12 < 22) ldsm4t(sw[f % 12], wl + (28 + f + 12) * 512);
            }
#pragma unroll
            for (int i = 0; i < 2; i++) {
#pragma unroll
                for (int j = 0; j < 4; j++) acc[i][j] += acc[i + 2][j];
                sts128(l16 + CH_PART + i * 4096 + w * 512, acc[i]);
            }
        }
        if (!PV && w < 2) {
            bar_sync(5, 288 + OB);
            float4 v[8];
#pragma unroll
            for (int i = 0; i < 8; i++) v[i] = lds128(l16 + CH_PART + w * 4096 + i * 512);
            float4 r = add4(add4(add4(v[0], v[1]), add4(v[2], v[3])), add4(add4(v[4], v[5]), add4(v[6], v[7])));
            if (!mown) st_async4(mapa(l16 + CH_MX + rank * 512, w), r, mapa(barM, w));
            bar_arrive(7, 256 + OB);
            if (mown) {
                mbar_wait(barM, s & 1);
                float4 x = lds128(l16 + CH_MX + (rank ^ 1) * 512), y = lds128(l16 + CH_MX + 2 * 512);
                r = add4(add4(x, r), y);
                const uint32_t mx = movm(pack_bf16(r.x, r.y)), my = movm(pack_bf16(r.z, r.w));
                const uint32_t ns = (slot + 0x4000) & 0xC000;
                char* const pp = ring0 + (pub + ns + (lo16 >> 1));
                st_pub(pp, mx, my); st_pub(pp + 4096, mx, my);
            }
            preload<0, 0, ML>(sw, wl, zero);
        } else {
            bar_arrive(5, 288 + OB);
            bar_sync(7, 256 + OB);
            preload<MP, 0, ML>(sw, wl, zero);
        }
        bar_sync(6, 320 + OB);
    }
    bar_arrive(6, 288);
}

__device__ __forceinline__ void chain_pace(const uint32_t sb, const int lane, const int rank, const int aware) {
    const uint32_t zero = sb + CH_BAR + 24;
    if (lane == 0) {
        char* ring = ring_base();
        uint32_t* p0 = (uint32_t*)(ring + ring_off(blockIdx.x & 15, 0) + 3072 + (blockIdx.x >> 4) * 128);
        uint32_t* p1 = (uint32_t*)(ring + ring_off(blockIdx.x & 15, 1) + 3072 + (blockIdx.x >> 4) * 128);
        *p0 = 0; *p1 = 0;
        int b0 = 1 << 30, b1 = 1 << 30; uint32_t v = 0;
        for (int r = 0; r < 4 || (r < 256 && !mbar_test(sb + CH_BAR + 16, 0)); r++) {
            uint32_t t0 = clk(); v = atomicExch(p0 + (v == 500), r); uint32_t t1 = v == 777 ? clk() + 1 : clk(); b0 = min(b0, (int)(t1 - t0));
            t0 = clk(); v = atomicExch(p1 + (v == 500), r); t1 = v == 777 ? clk() + 1 : clk(); b1 = min(b1, (int)(t1 - t0));
            asm volatile("st.volatile.shared.u32 [%0], %1;" ::"r"(zero + 4), "r"(aware ? (b1 < b0) ^ (aware - 1) : 0) : "memory");
        }
    }
    __syncwarp();
#pragma unroll 1
    for (int s = 1; s < NSEG; s++) {
        bar_sync(5, 288 + OB);
        bar_arrive(6, 320 + OB + (rank == 2 ? delay<18>(zero) : 0));
    }
}
__device__ __forceinline__ char* reset_ptr(const int lane, const int rank, const int h) {
    const int nq = rank == 0 ? 6 : 5, v0 = rank == 0 ? -6 : 3 * rank - 6;
    int pos, cw = o_chunk(h * 8 + v0 + min(max(5 + (lane >> 3), nq), 7), pos);
    if (lane >= 24 && rank < 2) { cw = 24 + (h >> 2); pos = (2 * h + rank) & 7; }
    return ring_base() + ((ring_off(cw, 0) & ~4096u) + pos * 256 + (lane & 7) * 16);
}
__device__ __forceinline__ void chain_chores(const uint32_t sb, const int lane, const int rank, const int h, const bf16* __restrict__ mem0) {
    const int nq = rank == 0 ? 6 : 5, u0 = rank == 0 ? 0 : 1 + 5 * rank, v0 = rank == 0 ? -6 : 3 * rank - 6;
    const uint32_t barS = sb + CH_BAR, barM = barS + 8, barX = barS + 16;
    auto xload = [&](int s) {
        mbar_expect(barX, 8192 - nq * 512);
        bulk_load(sb + CH_XS, g_kx + (size_t)(s * NH + h) * 4096 + u0 * 256, nq * 512, barX);
        bulk_load(sb + CH_XS + nq * 512, g_vx + (size_t)(s * NH + h) * 4096 + (v0 + nq) * 512, (8 - nq) * 1024, barX);
    };
    char* const rb = reset_ptr(lane, rank, h);
    int* const kvf = g_kvf + blockIdx.x * 16;
    if (rank < 2) {
        const uint32_t* p = (const uint32_t*)(mem0 + (lane >> 2) * DM + 32 * h + 16 * rank + 2 * (lane & 3));
        char* d = ring_base() + ((ring_off(24 + (h >> 2), 0) & ~4096u) + ((2 * h + rank) & 7) * 256 + lane * 8);
        const uint32_t x = p[0] == SENT ? 0x7FFF7FFFu : p[0];
        st_pub(d, x, p[4]); st_pub(d + 4096, x, p[4]);
    }
    if (lane == 0) {
        if (!KVN) __nanosleep(18000);
        wait_ctr(kvf, KVN);
        asm volatile("fence.proxy.async;" ::: "memory");
        xload(0);
    }
#pragma unroll 1
    for (int s = 0; s < NSEG - 1; s++) {
        if (lane == 0) {
            mbar_expect(barS, 2 * 1280);
            if (rank < 2) mbar_expect(barM, 2 * 512);
        }
        bar_sync(13, 64);
#pragma unroll
        for (int i = 0; i < 4; i++)
            asm volatile("st.relaxed.gpu.global.v4.u32 [%0], {%1,%1,%1,%1};" ::"l"(rb + ((((s + 2) & 3) << 14) + (i >> 1) * 4096 + (i & 1) * 128)), "r"(SENT) : "memory");
        if (FEN || (s & 3) == 0) __threadfence();
        if (lane == 0 && (s & 3) == 0 && s) atomicAdd(g_ctr + C_CHAIN + (s >> 2) - 1, 1);
        if (lane == 0 && (s & 3) == 3) { wait_ctr(kvf + (s >> 2) + 1, KVN); asm volatile("fence.proxy.async;" ::: "memory"); }
        __syncwarp();
        bar_sync(12, 64);
        if (lane == 0) xload(s + 1);
        mbar_wait(barX, (s + 1) & 1);
        bar_sync(6, 320 + OB);
    }
    bar_sync(6, 288);
    __threadfence();
    if (lane == 0) atomicAdd(g_ctr + C_CHAIN + 15, 1);
}

struct S4Params { const bf16 *Are, *Aim, *Bre, *Bim, *Cre, *Cim, *ldt, *dsk; };
__device__ __forceinline__ float2 cmul(float2 a, float2 b) { return make_float2(a.x * b.x - a.y * b.y, a.x * b.y + a.y * b.x); }
__device__ __forceinline__ float2 csq(float2 a) { return make_float2(a.x * a.x - a.y * a.y, (a.x + a.x) * a.y); }
__device__ __forceinline__ float2 cexp_t(float lr, float turns) {
    float f = (turns - rintf(turns)) * 6.283185307179586f, e = ex2(lr);
    return make_float2(e * __cosf(f), e * __sinf(f));
}
__device__ __forceinline__ float bf_at(uint2 v, int i) {
    const uint32_t w = i < 2 ? v.x : v.y;
    return __uint_as_float((i & 1) ? w & 0xFFFF0000u : w << 16);
}
__device__ __forceinline__ void kg_step(uint32_t (&a)[4][4], uint32_t (&b)[5][2], uint32_t pa, uint32_t pe, float x0) {
#pragma unroll
    for (int i = 0; i < 2; i++) {
        const float4 p = lds128(pa + i * 64);
        const float2 e8 = lds64(pe + i * 32), c = make_float2(p.z, p.w);
        const float mag = ex2(p.x * x0), ph = p.y * x0;
        float2 e0 = make_float2(mag * __cosf(ph), mag * __sinf(ph)), e1 = cmul(e0, e8);
#pragma unroll
        for (int j = 0; j < 4; j++) {
            a[j][2 * i] = pack_bf16(e0.x, e0.y); a[j][2 * i + 1] = pack_bf16(e1.x, e1.y);
            e0 = csq(e0); e1 = csq(e1);
        }
        float2 m = cmul(c, e0);
        b[0][i] = pack_bf16(m.x, -m.y);
#pragma unroll
        for (int j = 0; j < 4; j++) {
            m = cmul(c, e1);
            b[j + 1][i] = pack_bf16(m.x, -m.y);
            if (j < 3) e1 = csq(e1);
        }
    }
}
__device__ __forceinline__ void kg_mma(float (&kd)[5][4], const uint32_t (&a)[4][4], const uint32_t (&b)[5][2]) {
    mma16(kd[0], a[0], b[0][0], b[0][1]);
#pragma unroll
    for (int j = 0; j < 4; j++) mma16(kd[j + 1], a[j], b[j + 1][0], b[j + 1][1]);
}
struct KgRaw { uint2 v[6]; float ldt; };
__device__ __forceinline__ void kg_load(KgRaw& r, const S4Params& P, int d, int lane) {
    const bf16* src[6] = {P.Are, P.Aim, P.Bre, P.Bim, P.Cre, P.Cim};
#pragma unroll
    for (int j = 0; j < 6; j++) r.v[j] = __ldg((const uint2*)(src[j] + d * 128) + lane);
    r.ldt = __bfloat162float(P.ldt[d]);
}
__device__ __forceinline__ float kg_params(const KgRaw& r, uint32_t stg, int lane) {
    const float dt = __bfloat162float(__float2bfloat16(expf(r.ldt)));
    float k2048 = 0.f;
#pragma unroll
    for (int i = 0; i < 4; i++) {
        const float br = dt * bf_at(r.v[2], i), bi = dt * bf_at(r.v[3], i), cr = bf_at(r.v[4], i), ci = bf_at(r.v[5], i);
        const float zr = dt * bf_at(r.v[0], i) * 1.4426950408889634f;
        float zt = dt * bf_at(r.v[1], i) * 0.15915494309189535f;
        zt -= rintf(zt);
        const float v[4] = {zr, zt * 6.283185307179586f, cr * br - ci * bi, cr * bi + ci * br};
        const float2 e8 = cexp_t(8.f * zr, 8.f * zt), el = cexp_t(2048.f * zr, 2048.f * zt);
        k2048 += v[2] * el.x - v[3] * el.y;
        sts128(stg + (i * 32 + lane) * 16, v);
        sts64(stg + 2048 + (i * 32 + lane) * 8, e8.x, e8.y);
    }
#pragma unroll
    for (int o = 16; o; o >>= 1) k2048 += __shfl_xor_sync(0xffffffffu, k2048, o);
    __syncwarp();
    return k2048;
}
__device__ __forceinline__ void kg_store(const float (&kd)[5][4], float k2048, uint32_t stg, int d, int lane) {
    __syncwarp();
    const uint32_t ta = stg + (lane & 7) * 32 + ((lane >> 3) & 1) * 16 + (lane >> 4) * 256;
    stsm4t(ta, pack_bf16(kd[0][0], kd[0][1]), pack_bf16(kd[0][2], kd[0][3]), pack_bf16(kd[1][0], kd[1][1]), pack_bf16(kd[1][2], kd[1][3]));
    stsm4t(ta + 512, pack_bf16(kd[2][0], kd[2][1]), pack_bf16(kd[2][2], kd[2][3]), pack_bf16(kd[3][0], kd[3][1]), pack_bf16(kd[3][2], kd[3][3]));
    stsm4t(ta + 1024, pack_bf16(kd[4][0], kd[4][1]), pack_bf16(kd[4][2], kd[4][3]), pack_bf16(k2048, 0.f), 0);
    __syncwarp();
#pragma unroll
    for (int j = 0; j < 3; j++) ((float4*)(g_kd + d * 768))[j * 32 + lane] = lds128(stg + j * 512 + lane * 16);
    __syncwarp();
}

__global__ void __cluster_dims__(3, 1, 1) __launch_bounds__(CH_THREADS, 1)
chain_kernel(const __grid_constant__ CUtensorMap mq, const __grid_constant__ CUtensorMap mk, const __grid_constant__ CUtensorMap mv,
             const __grid_constant__ CUtensorMap mo, const bf16* __restrict__ Wq, const bf16* __restrict__ Wk, const bf16* __restrict__ Wv,
             const bf16* __restrict__ mem0, const __grid_constant__ S4Params P, int aware) {
    extern __shared__ __align__(1024) unsigned char smem[];
    const uint32_t sb = smem_u32(smem);
    const int tid = threadIdx.x, lane = tid & 31;
    const int w = __shfl_sync(0xffffffffu, tid >> 5, 0);
    int rank; asm("mov.u32 %0, %%cluster_ctarank;" : "=r"(rank));
    const int h = blockIdx.x / 3;
    if (tid == 0) {
        mbar_init(sb + CH_BAR, 1); mbar_init(sb + CH_BAR + 8, 1); mbar_init(sb + CH_BAR + 16, 1);
        for (int i = 0; i < 16; i++) mbar_init(sb + CH_BAR + 64 + i * 8, 1);
        *(int*)(smem + CH_BAR + 24) = 0; *(int*)(smem + CH_BAR + 28) = 0; *(int*)(smem + CH_BAR + 32) = 0;
        asm volatile("fence.mbarrier_init.release.cluster;" ::: "memory");
    }
    if (w == 10 && PFKV) {
        const int e = lane * 96 + blockIdx.x;
        if (e < 2048) asm volatile("cp.async.bulk.prefetch.L2.global [%0], 8192;" ::"l"(((e & 1) ? Wv : Wk) + (size_t)(e >> 1) * HD) : "memory");
        if (PFKV > 1) __nanosleep(PFKV);
    }
    if (w == 9) {
        char* const rb = reset_ptr(lane, rank, h);
#pragma unroll
        for (int i = 0; i < 8; i++)
            asm volatile("st.relaxed.gpu.global.v4.u32 [%0], {%1,%1,%1,%1};" ::"l"(rb + (((i >> 2) << 14) + ((i >> 1) & 1) * 4096 + (i & 1) * 128)), "r"(SENT) : "memory");
        if (lane < 16) g_kvf[blockIdx.x * 16 + lane] = 0;
        if (blockIdx.x == 0)
            for (int k = lane; k < N_CTR; k += 32) g_ctr[k] = 0;
        __threadfence();
        __syncwarp();
        asm volatile("griddepcontrol.launch_dependents;" ::: "memory");
    }
    __syncthreads();
    asm volatile("barrier.cluster.arrive.relaxed.aligned;" ::: "memory");

    if (w >= 8) {
        reg_dec<24>();
        asm volatile("barrier.cluster.wait.aligned;" ::: "memory");
        if (w == 8) chain_pace(sb, lane, rank, aware);
        else if (w == 9) {
            chain_chores(sb, lane, rank, h, mem0);
            asm volatile("st.volatile.shared.u32 [%0], %1;" ::"r"(sb + CH_BAR + 32), "r"(0x3F803F80) : "memory");
        } else if (w == 11 && KEEP) {
#pragma unroll 1
            for (int it = 0; it < (1 << 22); it++) {
                int d0, d1;
                const uint32_t x = delay<1>(sb + CH_BAR + 32);
                asm volatile("mma.sync.aligned.m8n8k16.row.col.s32.s8.s8.s32 {%0,%1}, {%2}, {%2}, {%3,%3};" : "=r"(d0), "=r"(d1) : "r"(x), "r"(0));
                if (d0 | d1) break;
                if ((XB & 8) && lane == 0) asm volatile("st.relaxed.gpu.global.u32 [%0], %1;" ::"l"(g_kd + DM * 768 + blockIdx.x * 64), "r"(it) : "memory");
                if ((XB & 16) && lane == 0) ld_acq((int*)(g_kd + DM * 768 + blockIdx.x * 64));
                __nanosleep(KEEP);
            }
        }
    } else {
        reg_inc<240>();
        const int nq = rank == 0 ? 6 : 5;
        const int u0 = rank == 0 ? 0 : 1 + 5 * rank;
        const int v0 = rank == 0 ? -6 : 3 * rank - 6;
        const int gw = rank * 8 + w;
        const int ks0 = gw < 16 ? 11 * gw : 176 + 10 * (gw - 16);
        const int nko = gw < 16 ? 11 : 10;
        const uint32_t wr = sb + w * CH_WREG, bar0 = sb + CH_BAR + 64 + w * 16, bar1 = bar0 + 8;
        uint32_t wa[36][4];
        const uint32_t vst = sb + CH_PART + w * 2048;
        const int cq = h * DH + 8 * u0, cv = h * DH + 16 * (v0 + 6);
        const int r8 = lane >> 2, p = lane & 3;
        const bf16* src = p >= 2 ? ((p & 1) ? Wk : Wq) + cq + 32 : rank == 0 ? ((p & 1) ? Wk : Wq) + cq + 40 : Wv + cv - 16 + 8 * p;
        src += (size_t)(128 * w + r8) * HD;
        auto cp_rows = [&](int kh) {
            cp16(wr + ((kh >> 1) * 2 + (p >> 1)) * 512 + ((kh & 1) * 2 + (p & 1)) * 128 + r8 * 16, src + (size_t)kh * 8 * HD);
        };
        {
            int d = blockIdx.x * 8 + w, t = 0;
            const int d1 = 768 + blockIdx.x * 3 + w, nt = (w < 3 && d1 < DM) ? 32 : 16;
            const uint32_t stg = wr + 4096;
            KgRaw raw, raw1;
            kg_load(raw, P, d, lane);
            kg_load(raw1, P, min(d1, DM - 1), lane);
            float kd[5][4], k2048;
#pragma unroll 1
            for (int i = -LDW; i < 9 || t < nt; i++) {
                if (i >= 0 && i < 9) {
                    const uint32_t bar = bar0 + (i & 1) * 8;
                    if (i >= 2) mbar_wait(bar, ((i >> 1) - 1) & 1);
                    if (lane == 0) {
                        mbar_expect(bar, 2048);
                        if (i < 8) tma2d(wr + 8192 + (i & 1) * 8192 + (i >> 1) * 2048, (i & 1) ? &mk : &mq, cq, 128 * w + 32 * (i >> 1), bar);
                        else tma2d(vst, &mv, cv, 128 * w, bar);
                    }
                    if (i < 8) cp_rows(i);
                }
#pragma unroll 1
                for (int e = min(t + KGS, nt); t < e; t++) {
                    if ((t & 15) == 0) {
                        k2048 = kg_params(raw, stg, lane);
#pragma unroll
                        for (int j = 0; j < 20; j++) kd[j >> 2][j & 3] = 0.f;
                    }
                    uint32_t ka[4][4], kb[5][2];
                    kg_step(ka, kb, stg + ((t & 15) * 8 + (lane & 3)) * 16, stg + 2048 + ((t & 15) * 8 + (lane & 3)) * 8, (float)(lane >> 2));
                    kg_mma(kd, ka, kb);
                    if ((t & 15) == 15) { kg_store(kd, k2048, stg, d, lane); raw = raw1; d = d1; }
                }
            }
        }
        const uint32_t lrow = ((lane >> 4) * 8 + (lane & 7)) * 64, lsw = (lane >> 1) & 3, lh = (lane >> 3) & 1;
        mbar_wait(bar1, 1); mbar_wait(bar0, 0);
#pragma unroll
        for (int i = 0; i < 32; i++) ldsm4t(wa[i], wr + 8192 + lh * 8192 + (i & 7) * 1024 + lrow + (((i >> 3) ^ lsw) << 4));
#pragma unroll
        for (int i = 0; i < 4; i++) ldsm4t(wa[32 + i], vst + (i >> 1) * 1024 + lrow + ((((i & 1) * 2 + lh) ^ lsw) << 4));
        asm volatile("fence.proxy.async.shared::cta;" ::"r"(wa[31][0]), "r"(wa[35][0]) : "memory");
        __syncwarp();
#pragma unroll 1
        for (int i = 9; i < 18; i++) {
            const uint32_t bar = bar0 + (i & 1) * 8;
            if (i >= 11) mbar_wait(bar, ((i >> 1) - 1) & 1);
            if (lane == 0) {
                const int j = 2 * (i - 12), nb = min(2, nko - j);
                mbar_expect(bar, i < 12 ? 2048 : nb * 1024);
                if (i < 12) tma2d(wr + 8192 + (i - 9) * 2048, &mv, cv, 128 * w + 32 * (i - 8), bar);
                else for (int e = 0; e < nb; e++) tma2d(wr + 14336 + (j + e) * 1024, &mo, 32 * h, 16 * (ks0 + j + e), bar);
            }
            if (i < 17) cp_rows(i - 1);
        }
        mbar_wait(bar0, 0); mbar_wait(bar1, 0);
#pragma unroll 1
        for (int i = 0; i < 17; i++) {
            uint32_t x[4], y[4];
            ldsm4t(x, wr + 8192 + i * 1024 + lrow + ((lh ^ lsw) << 4));
            ldsm4t(y, wr + 8192 + i * 1024 + lrow + (((2 + lh) ^ lsw) << 4));
            if (i == 16 && nko == 10) x[0] = x[1] = x[2] = x[3] = y[0] = y[1] = y[2] = y[3] = 0;
            __syncwarp();
            stsm4t(wr + 8192 + i * 1024 + lane * 16, x[0], x[1], x[2], x[3]);
            stsm4t(wr + 8192 + i * 1024 + 512 + lane * 16, y[0], y[1], y[2], y[3]);
        }
        asm volatile("cp.async.wait_all;" ::: "memory");
        asm volatile("barrier.cluster.wait.aligned;" ::: "memory");
        bar_sync(1, 256);
        mbar_wait_long(sb + CH_BAR + 16, 0);
        const int side = __shfl_sync(0xffffffffu, *(volatile int*)(smem + CH_BAR + 28), 0);
        if (w >= nq) chain_loop<true>(wa, sb, w, lane, rank, h, side);
        else chain_loop<false>(wa, sb, w, lane, rank, h, side);
    }
}

constexpr int G_STAGE = 49152, G_NST = 4;
constexpr int G_STG = G_NST * G_STAGE;
constexpr int G_BAR = G_STG + 32768;
constexpr int G_SMEM = G_BAR + 256 + 1024;

#define WLOG(e)
constexpr int IT_QA = 0, IT_O = 1, IT_S4 = 2, IT_END = 3, IT_KV = 4;
#define O_WIDE 10
#define OPF 0
#define ATT2 0
#define S4REL 4
#define KVP 0
#define KVS 8
#define STM 0
__device__ __forceinline__ void st_out(uint32_t* p, uint32_t v) {
    if (STM == 0) *p = v;
    else if (STM == 1) __stcs(p, v);
    else asm volatile("st.global.L1::no_allocate.u32 [%0], %1;" ::"l"(p), "r"(v) : "memory");
}
#define Q_N1 1
#define Q_S1 16
__device__ __forceinline__ int queue_item(int q) {
    if (KVP && q >= KVP && q < 512) return (IT_KV << 16) | (((q >> 6) * 2 + (q & 1)) << 8) | ((q >> 1) & 31);
    if (q < 512) return (IT_KV << 16) | ((q >> 5) << 8) | (q & 31);
    q -= 512;
    if (q < 256) return (IT_QA << 16) | ((q >> 4) << 8) | (q & 15);
    q -= 256;
    if (q < Q_N1 * 8) return (IT_O << 16) | ((O_WIDE + (q >> 3)) << 8) | (q & 7);
    q -= Q_N1 * 8;
    if (q < Q_S1) return (IT_S4 << 16) | q;
    q -= Q_S1;
    if (q < (16 - O_WIDE - Q_N1) * 8) return (IT_O << 16) | ((O_WIDE + Q_N1 + (q >> 3)) << 8) | (q & 7);
    q -= (16 - O_WIDE - Q_N1) * 8;
    if (q < 128 - Q_S1) return (IT_S4 << 16) | (Q_S1 + q);
    return IT_END << 16;
}
__device__ __forceinline__ void tma2d_store(const CUtensorMap* m, uint32_t src, int c0, int c1) {
    asm volatile("cp.async.bulk.tensor.2d.global.shared::cta.bulk_group [%0, {%2, %3}], [%1];" ::"l"(m), "r"(src), "r"(c0), "r"(c1) : "memory");
}

__device__ __forceinline__ void wgmma_s64(float (&d)[32], uint32_t a0, uint32_t a1, uint32_t a2, uint32_t a3, uint64_t db, int acc) {
    asm volatile("{.reg .pred p; setp.ne.b32 p, %37, 0;\n"
        "wgmma.mma_async.sync.aligned.m64n64k16.f32.bf16.bf16 {"
        "%0,%1,%2,%3,%4,%5,%6,%7,%8,%9,%10,%11,%12,%13,%14,%15,"
        "%16,%17,%18,%19,%20,%21,%22,%23,%24,%25,%26,%27,%28,%29,%30,%31"
        "}, {%32,%33,%34,%35}, %36, p, 1, 1, 0;}"
        : "+f"(d[0]), "+f"(d[1]), "+f"(d[2]), "+f"(d[3]), "+f"(d[4]), "+f"(d[5]), "+f"(d[6]), "+f"(d[7]), "+f"(d[8]), "+f"(d[9]), "+f"(d[10]), "+f"(d[11]), "+f"(d[12]), "+f"(d[13]), "+f"(d[14]), "+f"(d[15]), "+f"(d[16]), "+f"(d[17]), "+f"(d[18]), "+f"(d[19]), "+f"(d[20]), "+f"(d[21]), "+f"(d[22]), "+f"(d[23]), "+f"(d[24]), "+f"(d[25]), "+f"(d[26]), "+f"(d[27]), "+f"(d[28]), "+f"(d[29]), "+f"(d[30]), "+f"(d[31])
        : "r"(a0), "r"(a1), "r"(a2), "r"(a3), "l"(db), "r"(acc));
}
__device__ __forceinline__ void wgmma_s16(float (&d)[8], uint32_t a0, uint32_t a1, uint32_t a2, uint32_t a3, uint64_t db, int acc) {
    asm volatile("{.reg .pred p; setp.ne.b32 p, %13, 0;\n"
        "wgmma.mma_async.sync.aligned.m64n16k16.f32.bf16.bf16 {"
        "%0,%1,%2,%3,%4,%5,%6,%7"
        "}, {%8,%9,%10,%11}, %12, p, 1, 1, 0;}"
        : "+f"(d[0]), "+f"(d[1]), "+f"(d[2]), "+f"(d[3]), "+f"(d[4]), "+f"(d[5]), "+f"(d[6]), "+f"(d[7])
        : "r"(a0), "r"(a1), "r"(a2), "r"(a3), "l"(db), "r"(acc));
}
__device__ __forceinline__ void wgmma_v128(float (&d)[64], uint32_t a0, uint32_t a1, uint32_t a2, uint32_t a3, uint64_t db, int acc) {
    asm volatile("{.reg .pred p; setp.ne.b32 p, %69, 0;\n"
        "wgmma.mma_async.sync.aligned.m64n128k16.f32.bf16.bf16 {"
        "%0,%1,%2,%3,%4,%5,%6,%7,%8,%9,%10,%11,%12,%13,%14,%15,"
        "%16,%17,%18,%19,%20,%21,%22,%23,%24,%25,%26,%27,%28,%29,%30,%31,"
        "%32,%33,%34,%35,%36,%37,%38,%39,%40,%41,%42,%43,%44,%45,%46,%47,"
        "%48,%49,%50,%51,%52,%53,%54,%55,%56,%57,%58,%59,%60,%61,%62,%63"
        "}, {%64,%65,%66,%67}, %68, p, 1, 1, 1;}"
        : "+f"(d[0]), "+f"(d[1]), "+f"(d[2]), "+f"(d[3]), "+f"(d[4]), "+f"(d[5]), "+f"(d[6]), "+f"(d[7]), "+f"(d[8]), "+f"(d[9]), "+f"(d[10]), "+f"(d[11]), "+f"(d[12]), "+f"(d[13]), "+f"(d[14]), "+f"(d[15]), "+f"(d[16]), "+f"(d[17]), "+f"(d[18]), "+f"(d[19]), "+f"(d[20]), "+f"(d[21]), "+f"(d[22]), "+f"(d[23]), "+f"(d[24]), "+f"(d[25]), "+f"(d[26]), "+f"(d[27]), "+f"(d[28]), "+f"(d[29]), "+f"(d[30]), "+f"(d[31]), "+f"(d[32]), "+f"(d[33]), "+f"(d[34]), "+f"(d[35]), "+f"(d[36]), "+f"(d[37]), "+f"(d[38]), "+f"(d[39]), "+f"(d[40]), "+f"(d[41]), "+f"(d[42]), "+f"(d[43]), "+f"(d[44]), "+f"(d[45]), "+f"(d[46]), "+f"(d[47]), "+f"(d[48]), "+f"(d[49]), "+f"(d[50]), "+f"(d[51]), "+f"(d[52]), "+f"(d[53]), "+f"(d[54]), "+f"(d[55]), "+f"(d[56]), "+f"(d[57]), "+f"(d[58]), "+f"(d[59]), "+f"(d[60]), "+f"(d[61]), "+f"(d[62]), "+f"(d[63])
        : "r"(a0), "r"(a1), "r"(a2), "r"(a3), "l"(db), "r"(acc));
}

__device__ __forceinline__ void attn_scores(float (&sx)[32], float (&sm)[8], const uint32_t (&q)[32], uint32_t sk) {
    const uint64_t dx = mkdesc(sk, 1024, 128, 0), dm = mkdesc(sk + 16384, 256, 128, 0);
    wg_fence();
#pragma unroll
    for (int ks = 0; ks < 8; ks++) {
        wgmma_s64(sx, q[4 * ks], q[4 * ks + 1], q[4 * ks + 2], q[4 * ks + 3], dx + ks * 128, ks);
        wgmma_s16(sm, q[4 * ks], q[4 * ks + 1], q[4 * ks + 2], q[4 * ks + 3], dm + ks * 32, ks);
    }
    wg_commit();
}
__device__ __forceinline__ void attn_softmax(uint32_t (&p)[20], const float (&sx)[32], const float (&sm)[8], int wi, int lane) {
    const bool sb = wi >= 2;
    const int r0 = (wi & 1) * 16 + (lane >> 2) - 2 * (lane & 3);
    float s[5][4];
#pragma unroll
    for (int j = 0; j < 4; j++) s[4][j] = sb ? sm[4 + j] : sm[j];
    float m0 = fmaxf(s[4][0], s[4][1]), m1 = fmaxf(s[4][2], s[4][3]);
#pragma unroll
    for (int j = 0; j < 4; j++) {
#pragma unroll
        for (int e = 0; e < 4; e++) s[j][e] = 8 * j + (e & 1) > r0 + 8 * (e >> 1) ? -INFINITY : sb ? sx[16 + 4 * j + e] : sx[4 * j + e];
        m0 = fmaxf(m0, fmaxf(s[j][0], s[j][1])); m1 = fmaxf(m1, fmaxf(s[j][2], s[j][3]));
    }
    m0 = fmaxf(m0, __shfl_xor_sync(0xffffffffu, m0, 1)); m1 = fmaxf(m1, __shfl_xor_sync(0xffffffffu, m1, 1));
    m0 = fmaxf(m0, __shfl_xor_sync(0xffffffffu, m0, 2)); m1 = fmaxf(m1, __shfl_xor_sync(0xffffffffu, m1, 2));
    const float cs = 0.08838834764831845f * 1.4426950408889634f;
    m0 *= -cs; m1 *= -cs;
    float l0 = 0, l1 = 0;
#pragma unroll
    for (int j = 0; j < 5; j++) {
        s[j][0] = ex2(fmaf(s[j][0], cs, m0)); s[j][1] = ex2(fmaf(s[j][1], cs, m0));
        s[j][2] = ex2(fmaf(s[j][2], cs, m1)); s[j][3] = ex2(fmaf(s[j][3], cs, m1));
        l0 += s[j][0] + s[j][1]; l1 += s[j][2] + s[j][3];
    }
    l0 += __shfl_xor_sync(0xffffffffu, l0, 1); l1 += __shfl_xor_sync(0xffffffffu, l1, 1);
    l0 += __shfl_xor_sync(0xffffffffu, l0, 2); l1 += __shfl_xor_sync(0xffffffffu, l1, 2);
    asm("rcp.approx.ftz.f32 %0, %0;" : "+f"(l0)); asm("rcp.approx.ftz.f32 %0, %0;" : "+f"(l1));
    const uint32_t ma = sb ? 0u : ~0u;
#pragma unroll
    for (int j = 0; j < 5; j++) {
        const uint32_t x = pack_bf16(s[j][0] * l0, s[j][1] * l0), y = pack_bf16(s[j][2] * l1, s[j][3] * l1);
        const int ia = j < 4 ? 2 * j : 16, ib = j < 4 ? 8 + 2 * j : 18;
        asm volatile("and.b32 %0, %4, %6; and.b32 %1, %5, %6; and.b32 %2, %4, %7; and.b32 %3, %5, %7;"
            : "=&r"(p[ia]), "=&r"(p[ia + 1]), "=&r"(p[ib]), "=&r"(p[ib + 1]) : "r"(x), "r"(y), "r"(ma), "r"(~ma));
    }
}
__device__ __forceinline__ void attn_pv(float (&o)[64], const uint32_t (&p)[20], uint32_t sv) {
    const uint64_t dx = mkdesc(sv, 128, 1024, 0), dm = mkdesc(sv + 16384, 128, 256, 0);
    wg_fence();
#pragma unroll
    for (int ks = 0; ks < 5; ks++) wgmma_v128(o, p[4 * ks], p[4 * ks + 1], p[4 * ks + 2], p[4 * ks + 3], ks < 4 ? dx + ks * 16 : dm, ks);
    wg_commit();
}
__device__ __forceinline__ void attn_stage(const float (&o)[64], uint32_t dst) {
#pragma unroll
    for (int u = 0; u < 16; u += 2)
        stsm4(dst + (u >> 3) * 8192 + (u & 7) * 128, pack_bf16(o[4 * u], o[4 * u + 1]), pack_bf16(o[4 * u + 2], o[4 * u + 3]),
              pack_bf16(o[4 * u + 4], o[4 * u + 5]), pack_bf16(o[4 * u + 6], o[4 * u + 7]));
}

template <int BN, int NKB, bool BLOCKED_A>
__device__ __forceinline__ void mainloop(float (&acc)[BN / 2], uint32_t sb, int wgi, uint32_t full, uint32_t empty, int& it, bool elect) {
#pragma unroll
    for (int j = 0; j < BN / 2; j++) acc[j] = 0.f;
#pragma unroll 1
    for (int k4 = 0; k4 < NKB; k4 += 4) {
#pragma unroll
        for (int st = 0; st < 4; st++, it++) {
            mbar_wait(full + 8 * st, (it >> 2) & 1);
            const uint64_t da = BLOCKED_A ? mkdesc(sb + st * G_STAGE + wgi * 8192, 128, 1024, 0) : mkdesc(sb + st * G_STAGE + wgi * 8192, 16, 1024, 1);
            const uint64_t db = mkdesc(sb + st * G_STAGE + 16384, 8192, 1024, 1);
            wg_fence();
#pragma unroll
            for (int k = 0; k < 4; k++) {
                if constexpr (BN == 256) wgmma256(acc, da + k * (BLOCKED_A ? 16 : 2), db + k * 128, 1);
                else wgmma128(acc, da + k * (BLOCKED_A ? 16 : 2), db + k * 128, 1);
            }
            wg_commit();
            if (k4 | st) {
                wg_wait<1>();
                if (elect) mbar_arrive(empty + 8 * ((st + 3) & 3));
            }
        }
    }
    wg_wait<0>();
    if (elect) mbar_arrive(empty + 8 * 3);
}

__device__ __forceinline__ uint32_t n6_a(int st) { return st < 4 ? st * G_STAGE : (2 * st - 8) * G_STAGE + 32768; }
__device__ __forceinline__ uint32_t n6_b(int st) { return st < 4 ? st * G_STAGE + 16384 : (2 * st - 7) * G_STAGE + 32768; }
__device__ __forceinline__ uint32_t n6_bar(int st) { return st < 4 ? 8 * st : 96 + 8 * st; }
__device__ __forceinline__ void mainloop6(float (&acc)[64], uint32_t sb, int wgi, uint32_t full, uint32_t empty, int& it, bool elect) {
#pragma unroll
    for (int j = 0; j < 64; j++) acc[j] = 0.f;
    int st = 0, prev = 0, r = 0;
#pragma unroll 1
    for (int kb = 0; kb < 64; kb++) {
        mbar_wait(full + n6_bar(st), ((st < 4 ? it >> 2 : 0) + r) & 1);
        const uint64_t da = mkdesc(sb + n6_a(st) + wgi * 8192, 128, 1024, 0), db = mkdesc(sb + n6_b(st), 8192, 1024, 1);
        wg_fence();
#pragma unroll
        for (int k = 0; k < 4; k++) wgmma128(acc, da + k * 16, db + k * 128, 1);
        wg_commit();
        if (kb) {
            wg_wait<1>();
            if (elect) mbar_arrive(empty + n6_bar(prev));
        }
        prev = st;
        if (++st == 6) { st = 0; r++; }
    }
    wg_wait<0>();
    if (elect) mbar_arrive(empty + 8 * 3);
    it += 44;
}

template <int BN>
__device__ __forceinline__ void o_item(uint32_t sb, int wgi, int wi, int lane, uint32_t full, uint32_t empty, int& it, const CUtensorMap* mout,
                                       int row0, int col0, uint32_t stgpar) {
    float acc[BN / 2];
    if constexpr (BN == 256) mainloop<BN, 64, true>(acc, sb, wgi, full, empty, it, lane == 0);
    else mainloop6(acc, sb, wgi, full, empty, it, lane == 0);
    mbar_wait(full + 104, stgpar);
    const uint32_t stg = sb + G_STG + (wgi * 4 + wi) * 4096;
    const int r = lane & 15, cu = lane >> 4;
#pragma unroll
    for (int hf = 0; hf < BN / 128; hf++) {
        if (lane == 0) asm volatile("cp.async.bulk.wait_group.read 0;" ::: "memory");
        __syncwarp();
#pragma unroll
        for (int j = 0; j < 8; j++) {
            const float* a = acc + hf * 64 + j * 8;
            stsm4(stg + (j >> 2) * 2048 + r * 128 + ((((j & 3) * 2 + cu) ^ (r & 7)) << 4),
                  pack_bf16(a[0], a[1]), pack_bf16(a[2], a[3]), pack_bf16(a[4], a[5]), pack_bf16(a[6], a[7]));
        }
        asm volatile("fence.proxy.async.shared::cta;" ::: "memory");
        __syncwarp();
        if (lane == 0) {
            tma2d_store(mout, stg, col0 + hf * 128, row0 + wgi * 64 + wi * 16);
            tma2d_store(mout, stg + 2048, col0 + hf * 128 + 64, row0 + wgi * 64 + wi * 16);
            asm volatile("cp.async.bulk.commit_group;" ::: "memory");
        }
    }
}

constexpr int S4_KD = 32768;
constexpr int S4_CH = 2 * G_STAGE;
constexpr int S4_HALF = 2304;
constexpr int S4_WD = 2 * S4_HALF;
constexpr int S4_STRIDE = S4_WD + 2304 + 16;
__device__ __forceinline__ uint32_t addz(uint32_t x, uint32_t z) { uint32_t r; asm volatile("add.u32 %0, %1, %2;" : "=r"(r) : "r"(x), "r"(z)); return r; }
__device__ __forceinline__ uint32_t lds16(uint32_t a) { uint32_t v; asm volatile("ld.shared.u16 %0, [%1];" : "=r"(v) : "r"(a) : "memory"); return v; }
__device__ __forceinline__ uint32_t ldsu(uint32_t a) { return __float_as_uint(lds32(a)); }

template <int E0, int NE, int KP>
__device__ __forceinline__ void s4_windows(float (&acc)[8][2][4], uint32_t ut, uint32_t kd, int rho, int w, int lane, uint32_t z) {
    const int gt = (lane >> 2) - 2 * (lane & 3), p0 = rho == 16 ? -3 : -2, c = (lane >> 3) + p0;
    uint32_t band[2][4], tw[2 * NE + 1], ta[NE][4];
    {
        uint32_t f[5];
#pragma unroll
        for (int m = 0; m < 5; m++) {
            const int d = 8 * (p0 + m - 1) - gt + rho;
            f[m] = (abs(d) <= w ? 0x3F80u : 0u) | (abs(d + 1) <= w ? 0x3F800000u : 0u);
        }
#pragma unroll
        for (int j = 0; j < 2; j++) { band[j][0] = f[2 * j + 1]; band[j][1] = addz(f[2 * j], z); band[j][2] = f[2 * j + 2]; band[j][3] = addz(f[2 * j + 1], z); }
    }
#pragma unroll
    for (int m = 0; m < 2 * NE + 1; m++) {
        const int q = 8 * (2 * E0 - 1 + m) + gt;
        const uint32_t lo = lds16(kd + q * KP), hi = lds16(kd + (q - 1) * KP);
        tw[m] = ((unsigned)(q - 16 * E0) < 16 * E0 ? lo : 0u) | ((unsigned)(q - 1 - 16 * E0) < 16 * E0 ? hi << 16 : 0u);
    }
#pragma unroll
    for (int e = 0; e < NE; e++) { ta[e][0] = tw[2 * e + 1]; ta[e][1] = tw[2 * e + 2]; ta[e][2] = addz(tw[2 * e], z); ta[e][3] = addz(tw[2 * e + 1], z); }
    const uint32_t ua = ut + (c & 1) * S4_HALF + (16 + (lane & 7) + (c >> 1)) * 16;
#pragma unroll
    for (int J = 0; J < 8 - E0; J++) {
        uint32_t u0[4], u1[4];
        ldsm4(u0, ua + J * 256); ldsm4(u1, ua + J * 256 + 128);
        float s0[4], s1[4];
        mma16z(s0, band[0], u0[0], u0[1]); mma16z(s1, band[0], u1[0], u1[1]);
        mma16(s0, band[1], u0[2], u0[3]); mma16(s1, band[1], u1[2], u1[3]);
        const uint32_t b00 = pack_bf16(s0[0], s0[1]), b01 = pack_bf16(s1[0], s1[1]), b10 = pack_bf16(s0[2], s0[3]), b11 = pack_bf16(s1[2], s1[3]);
#pragma unroll
        for (int e = 0; e < NE; e++)
            if (J + E0 + e < 8) { mma16(acc[J + E0 + e][0], ta[e], b00, b01); mma16(acc[J + E0 + e][1], ta[e], b10, b11); }
    }
}
template <int D0, int D1>
__device__ __forceinline__ void s4_dense(float (&acc)[8][2][4], uint32_t ua, const uint32_t (&b0)[4], const uint32_t (&b1)[4]) {
#pragma unroll
    for (int J = 0; J < 8 - D0; J++) {
        uint32_t a[4];
        ldsm4(a, ua + J * 256);
        mma16(acc[J + D0][0], a, b0[0], b0[1]); mma16(acc[J + D0][1], a, b0[2], b0[3]);
        if (J + D1 < 8) { mma16(acc[J + D1][0], a, b1[0], b1[1]); mma16(acc[J + D1][1], a, b1[2], b1[3]); }
    }
}
__device__ __forceinline__ void s4_words(uint32_t (&b)[4], uint32_t wd) {
    asm volatile("ld.shared.u32 %0, [%4]; ld.shared.u32 %1, [%4+-32]; ld.shared.u32 %2, [%4+32]; ld.volatile.shared.u32 %3, [%4];"
        : "=r"(b[0]), "=r"(b[1]), "=r"(b[2]), "=r"(b[3]) : "r"(wd) : "memory");
}

__device__ __forceinline__ void s4_item(uint32_t sb, int cw, int lane, int item, const bf16* __restrict__ dsk, uint32_t empty, const CUtensorMap* my, uint32_t stgpar) {
    const int gt = (lane >> 2) - 2 * (lane & 3);
    const uint32_t ch = sb + S4_CH + cw * S4_STRIDE, kd = sb + S4_KD + cw * 1536;
    const __nv_bfloat162 dk = __bfloat162bfloat162(dsk[item * 8 + cw]);
    ST(item, cw, 0);
    asm volatile("st.shared.v4.u32 [%0], {%1,%1,%1,%1};" ::"r"(ch + (lane >> 4) * S4_HALF + (lane & 15) * 16), "r"(0) : "memory");
    const uint32_t tch = sb + S4_CH + (lane & 7) * S4_STRIDE + ((lane >> 3) & 1) * S4_HALF + (16 + 16 * cw + (lane >> 4)) * 16;
#pragma unroll
    for (int i = 0; i < 8; i++) {
        uint32_t x[4];
        ldsm4t(x, sb + cw * 4096 + i * 512 + lane * 16);
        stsm4(tch + i * 32, x[0], x[1], x[2], x[3]);
    }
#pragma unroll 3
    for (int x0 = lane * 2 - 16; x0 < 560; x0 += 64) {
        uint32_t k[3];
#pragma unroll
        for (int j = 0; j < 3; j++) {
            const int x = x0 + j - 1, idx = x < 256 ? max(x, 0) : min(128 + ((x + ((x >> 1) & 1)) >> 1), 384);
            k[j] = lds16(kd + idx * 2);
            if ((unsigned)x > 514u) k[j] = 0;
        }
        asm volatile("st.shared.v2.u32 [%0], {%1,%2};" ::"r"(ch + S4_WD + 64 + x0 * 4), "r"(k[1] | (k[0] << 16)), "r"(k[2] | (k[1] << 16)) : "memory");
    }
    const uint32_t k1024 = lds16(kd + 1024);
    bar_sync(2, 256);
    ST(item, cw, 1);
    const uint32_t z = ldsu(ch);
    float acc[8][2][4];
#pragma unroll
    for (int j = 0; j < 16; j++) acc[j >> 1][j & 1][0] = acc[j >> 1][j & 1][1] = acc[j >> 1][j & 1][2] = acc[j >> 1][j & 1][3] = 0.f;
#pragma unroll 1
    for (int r = 1; r <= 4; r++) s4_windows<2, 3, 8>(acc, ch, kd + 512 + 2 * r, 4 * r, 2 - (r & 1), lane, z);
    ST(item, cw, 2);
#pragma unroll 1
    for (int r = 1; r <= 2; r++) s4_windows<4, 4, 4>(acc, ch, kd + 768 + 2 * r, 8 * r, 2 + r, lane, z);
    ST(item, cw, 3);
    const uint32_t ua = ch + (lane >> 4) * S4_HALF + (16 + (lane & 15)) * 16, wd = ch + S4_WD + 64 + gt * 4;
#pragma unroll 1
    for (int q = 0; q < 2; q++) {
        uint32_t b0[4], b1[4];
        s4_words(b0, wd + (q + 32) * 64);
#pragma unroll
        for (int j = 0; j < 4; j++) {
            const int x = 16 * q + gt + (j == 1 ? -8 : j == 2 ? 8 : 0) - 3;
            b1[j] = addz(((unsigned)x < 2u ? k1024 : 0u) | ((unsigned)(x - 1) < 2u ? k1024 << 16 : 0u), z);
        }
        s4_dense<2, 4>(acc, ua - q * 16, b0, b1);
    }
    {
        uint32_t b0[4], b1[4], c0[4], c1[4];
        s4_words(b0, wd); s4_words(b1, wd + 1024);
#pragma unroll 1
        for (int q = 0; q < 16; q += 2) {
            s4_words(c0, wd + q * 64 + 64); s4_words(c1, wd + q * 64 + 64 + 1024);
            s4_dense<0, 1>(acc, ua - q * 16, b0, b1);
            s4_words(b0, wd + q * 64 + 128); s4_words(b1, wd + q * 64 + 128 + 1024);
            s4_dense<0, 1>(acc, ua - q * 16 - 16, c0, c1);
            if (q == S4REL && lane == 0) { mbar_arrive(empty); mbar_arrive(empty + 8); }
        }
    }
    ST(item, cw, 4);
    mbar_wait(empty + 72, stgpar);
    if (lane == 0) asm volatile("cp.async.bulk.wait_group.read 0;" ::: "memory");
    __syncwarp();
#pragma unroll
    for (int I = 0; I < 8; I++) {
        uint32_t u[4];
        ldsm4(u, ua + I * 256);
#pragma unroll
        for (int j = 0; j < 4; j++) {
            const uint32_t y = pack_bf16(acc[I][j >> 1][2 * (j & 1)], acc[I][j >> 1][2 * (j & 1) + 1]);
            const __nv_bfloat162 r = __hadd2_rn(*(const __nv_bfloat162*)&y, __hmul2_rn(*(const __nv_bfloat162*)&u[j], dk));
            u[j] = *(const uint32_t*)&r;
        }
        stsm4(ua + I * 256, u[0], u[1], u[2], u[3]);
    }
    bar_sync(2, 256);
#pragma unroll
    for (int i = 0; i < 8; i++) {
        uint32_t y[4];
        ldsm4t(y, tch + i * 32);
        stsm4(sb + G_STG + cw * 4096 + i * 512 + lane * 16, y[0], y[1], y[2], y[3]);
    }
    asm volatile("fence.proxy.async.shared::cta;" ::: "memory");
    __syncwarp();
    if (lane == 0) {
        mbar_arrive(empty + 16); mbar_arrive(empty + 24);
        tma2d_store(my, sb + G_STG + cw * 4096, DM + item * 8, cw * 256);
        asm volatile("cp.async.bulk.commit_group;" ::: "memory");
    }
    ST(item, cw, 5);
}

__global__ void __launch_bounds__(384, 1)
worker_kernel(const __grid_constant__ CUtensorMap mx, const __grid_constant__ CUtensorMap mq, const __grid_constant__ CUtensorMap mk,
              const __grid_constant__ CUtensorMap mv, const __grid_constant__ CUtensorMap mo,
              const __grid_constant__ CUtensorMap mout, const __grid_constant__ CUtensorMap mu, const __grid_constant__ CUtensorMap my,
              const __grid_constant__ CUtensorMap mkx, const __grid_constant__ CUtensorMap mvx, const __grid_constant__ CUtensorMap mkm,
              const __grid_constant__ CUtensorMap mvm, const bf16* __restrict__ dsk) {
    extern __shared__ unsigned char smem_raw[];
    const uint32_t sb = (smem_u32(smem_raw) + 1023) & ~1023u;
    const uint32_t full = sb + G_BAR, empty = full + 32, ifull = full + 64, iempty = full + 80, islot = full + 96, stgbar = full + 104, sigbar = full + 112, sigslot = full + 120;
    const int tid = threadIdx.x, wg = tid >> 7, lane = tid & 31;
    int q0 = blockIdx.x;
    const int wide0 = q0 - ((int)gridDim.x - O_WIDE * 4);
    if (tid == 0) {
        if (q0 >= 32 && wide0 < 0) q0 = 32 + atomicAdd(g_ctr + C_NEXT, 1);
        for (int i = 0; i < 6; i++) { mbar_init(full + n6_bar(i), 1); mbar_init(empty + n6_bar(i), 8); }
        for (int i = 0; i < 2; i++) { mbar_init(ifull + 8 * i, 1); mbar_init(iempty + 8 * i, 8); }
        mbar_init(sigbar, 8); mbar_init(stgbar, 1);
        asm volatile("fence.proxy.async;" ::: "memory");
    }
    __syncthreads();
    if (wg == 0) {
        reg_dec<40>();
        if (tid >= 32 && tid < 64) {
            for (int n = 0;; n++) {
                mbar_wait_long(sigbar, n & 1);
                int item; asm volatile("ld.shared.u32 %0, [%1];" : "=r"(item) : "r"(sigslot + 4 * (n & 1)) : "memory");
                const int type = item >> 16, b = (item >> 8) & 255, i = item & 255;
                if (type == IT_END) break;
                if (type == IT_QA) {
                    if (lane == 0) {
                        for (int j = 0; j < 8; j++) {
                            const uint32_t src = sb + (j >= 4 ? G_STG + (j & 1) * 16384 : 3 * G_STAGE + (j & 1) * 20480) + ((j >> 1) & 1) * 8192;
                            asm volatile("cp.async.bulk.global.shared::cta.bulk_group [%0], [%1], 8192;"
                                ::"l"(g_ox + (size_t)(b * 64 + i * 4 + ((j >> 1) ^ 2)) * 8192 + (j & 1) * 4096), "r"(src) : "memory");
                            if ((j & 3) == 3) asm volatile("cp.async.bulk.commit_group;" ::: "memory");
                        }
                        asm volatile("cp.async.bulk.wait_group.read 1;" ::: "memory");
                        asm volatile("mbarrier.arrive.shared.b64 _, [%0], 8;" ::"r"(empty + 24) : "memory");
                        asm volatile("cp.async.bulk.wait_group 0;" ::: "memory");
                        mbar_arrive(stgbar);
                        asm volatile("fence.proxy.async;" ::: "memory");
                    }
                    __syncwarp();
                }
                __threadfence();
                if (type == IT_KV) { if (lane < 6) atomicAdd(g_kvf + ((i & 15) * 6 + lane) * 16 + b, 1); }
                else if (lane == 0) atomicAdd(g_ctr + C_QA_DONE + b, 1);
            }
        } else if (tid < 32) {
            int it = 0;
            if (!KVN) asm volatile("griddepcontrol.wait;" ::: "memory");
            for (int n = 0;; n++) {
                int item = 0;
                if (lane == 0) {
                    const int q = n == 0 ? q0 : 32 + atomicAdd(g_ctr + C_NEXT, 1);
                    item = n == 0 && wide0 >= 0 ? (IT_O << 16) | ((wide0 >> 2) << 8) | (wide0 & 3) : queue_item(q);
                }
                item = __shfl_sync(0xffffffffu, item, 0);
                if (lane == 0) {
                    mbar_wait(iempty + 8 * (n & 1), ((n >> 1) & 1) ^ 1);
                    asm volatile("st.shared.u32 [%0], %1;" ::"r"(islot + 4 * (n & 1)), "r"(item) : "memory");
                    mbar_arrive(ifull + 8 * (n & 1));
                    const int type = item >> 16, b = (item >> 8) & 255, i = item & 255;
                    if (type == IT_QA || type == IT_KV) {
                        const CUtensorMap* mw = type == IT_QA ? &mq : i < 16 ? &mk : &mv;
                        bool ready = false;
                        for (int kb = 0; kb < 16; kb++, it++) {
                            const int st = it & 3;
                            mbar_wait(empty + 8 * st, ((it >> 2) & 1) ^ 1);
                            mbar_expect(full + 8 * st, G_STAGE);
                            const uint32_t a = sb + st * G_STAGE;
                            tma2d(a, &mx, kb * 64, b * 128, full + 8 * st);
                            tma3d(a + 16384, mw, 0, kb * 64, (i & 15) * 4, full + 8 * st);
                            tma3d(a + 32768, mw, 0, kb * 64, (i & 15) * 4 + 2, full + 8 * st);
                            if (type == IT_QA && kb == 3) ready = ld_acq(g_ctr + C_CHAIN + b) >= 96;
                            if (type == IT_QA && kb >= 3 && kb < 11) {
                                const size_t sh = (b * 4 + ((kb - 3) & 3)) * NH + i * 2;
                                asm volatile("cp.async.bulk.prefetch.L2.global [%0], 16384;" ::"l"((kb >= 7 ? g_vx : g_kx) + sh * 4096) : "memory");
                                if (ready) asm volatile("cp.async.bulk.prefetch.L2.global [%0], 4096;" ::"l"((kb >= 7 ? g_vm : g_km) + sh * 1024) : "memory");
                            }
                        }
                    }
                    if (type == IT_QA) {
                        wait_ctr(g_ctr + C_CHAIN + b, 96);
                        asm volatile("fence.proxy.async;" ::: "memory");
                        for (int st = 0; st < 4; st++, it++) {
                            mbar_wait(empty + 8 * st, ((it >> 2) & 1) ^ 1);
                            mbar_expect(full + 8 * st, 4 * 10240);
                            for (int g2 = 0; g2 < 2; g2++) {
                                tma3d(sb + st * G_STAGE + g2 * 20480, st < 2 ? &mkx : &mvx, 0, b * 4 + g2 * 2, (i * 2 + (st & 1)) * 16, full + 8 * st);
                                tma3d(sb + st * G_STAGE + g2 * 20480 + 16384, st < 2 ? &mkm : &mvm, 0, b * 4 + g2 * 2, (i * 2 + (st & 1)) * 16, full + 8 * st);
                            }
                        }
                    } else if (type == IT_O) {
                        const bool wide = b < O_WIDE;
                        wait_ctr(g_ctr + C_QA_DONE + b, 16);
                        asm volatile("fence.proxy.async;" ::: "memory");
                        if (OPF)
                            for (int j = i; j < 64; j += wide ? 4 : 8)
                                if (j >= 6) asm volatile("cp.async.bulk.prefetch.L2.global [%0], 16384;" ::"l"(g_ox + (size_t)(b * 64 + j) * 8192) : "memory");
                        const int ns = wide ? 4 : 6;
                        for (int kb = 0, st = 0, r = 0; kb < 64; kb++) {
                            const uint32_t bo = n6_bar(st);
                            mbar_wait(empty + bo, (((st < 4 ? it >> 2 : 0) + r) & 1) ^ 1);
                            mbar_expect(full + bo, wide ? G_STAGE : 32768);
                            bulk_load(sb + n6_a(st), g_ox + (size_t)(b * 64 + kb) * 8192, 16384, full + bo);
                            tma3d(sb + n6_b(st), &mo, 0, kb * 64, wide ? i * 4 : i * 2, full + bo);
                            if (wide) tma3d(sb + n6_b(st) + 16384, &mo, 0, kb * 64, i * 4 + 2, full + bo);
                            if (++st == ns) { st = 0; r++; }
                        }
                        it += wide ? 64 : 44;
                    } else if (type == IT_S4) {
                        wait_ctr(g_ctr + C_CHAIN, 96);
                        asm volatile("fence.proxy.async;" ::: "memory");
                        mbar_wait(empty, ((it >> 2) & 1) ^ 1);
                        mbar_expect(full, 32768 + 12288);
                        bulk_load(sb + S4_KD, g_kd + i * 8 * 768, 12288, full);
                        for (int j = 0; j < 8; j++) tma2d(sb + j * 4096, &mu, i * 8, j * 256, full);
                        for (int st = 1; st < 4; st++) { mbar_wait(empty + 8 * st, ((it >> 2) & 1) ^ 1); mbar_arrive(full + 8 * st); }
                        it += 4;
                        mbar_wait_long(empty, ((it >> 2) & 1) ^ 1);
                    }
                }
                __syncwarp();
                if (item >> 16 == IT_END) break;
            }
            asm volatile("griddepcontrol.wait;" ::: "memory");
        }
    } else {
        reg_inc<232>();
        const int wu = __shfl_sync(0xffffffffu, tid >> 5, 0);
        const int wgi = (wu >> 2) - 1, wi = wu & 3;
        int it = 0, nqa = 0, nsig = 0, n = 0, item;
        auto next_item = [&]() {
            mbar_wait_long(ifull + 8 * (n & 1), (n >> 1) & 1);
            asm volatile("ld.shared.u32 %0, [%1];" : "=r"(item) : "r"(islot + 4 * (n & 1)) : "memory");
            __syncwarp();
            if (lane == 0) mbar_arrive(iempty + 8 * (n & 1));
        };
        auto signal = [&](int what) {
            if (tid == 128) asm volatile("st.shared.u32 [%0], %1;" ::"r"(sigslot + 4 * (nsig & 1)), "r"(what) : "memory");
            __syncwarp();
            if (lane == 0) mbar_arrive(sigbar);
            nsig++;
        };
        next_item();
        if (item >> 16 == IT_KV) {
            float acc[128];
            uint32_t pk[64];
            uint32_t* dst = nullptr;
            int prev = 0;
            do {
                WLOG(0);
#pragma unroll
                for (int kb = 0; kb < 16; kb++, it++) {
                    const int st = kb & 3;
                    mbar_wait(full + 8 * st, (it >> 2) & 1);
                    const uint64_t da = mkdesc(sb + st * G_STAGE + wgi * 8192, 16, 1024, 1);
                    const uint64_t db = mkdesc(sb + st * G_STAGE + 16384, 8192, 1024, 1);
                    wg_fence();
#pragma unroll
                    for (int k = 0; k < 4; k++) wgmma256(acc, da + k * 2, db + k * 128, kb | k);
                    wg_commit();
                    if (kb < KVS && dst) {
#pragma unroll
                        for (int j = kb * (64 / KVS); j < (kb + 1) * (64 / KVS); j++) st_out(dst + (j >> 1) * 128 + (j & 1) * 32, pk[j]);
                        if (kb == KVS - 1) signal(prev);
                    }
                    if (kb > 0) {
                        wg_wait<1>();
                        if (lane == 0) mbar_arrive(empty + 8 * ((kb - 1) & 3));
                    }
                }
                wg_wait<0>();
                if (lane == 0) mbar_arrive(empty + 8 * 3);
#pragma unroll
                for (int j = 0; j < 64; j++) pk[j] = pack_bf16(acc[2 * j], acc[2 * j + 1]);
                const int row = ((item >> 8) & 255) * 128 + wgi * 64 + wi * 16, nt = item & 255;
                dst = (uint32_t*)(nt < 16 ? g_kx : g_vx) + (size_t)((row >> 5) * 512 + (nt & 15) * 32) * 128 + (row & 31) * 4 + lane;
                prev = item;
                if (n == 0) {
#pragma unroll
                    for (int j = 0; j < 64; j++) dst[(j >> 1) * 128 + (j & 1) * 32] = pk[j];
                    signal(prev);
                    dst = nullptr;
                }
                WLOG(1);
                n++;
                next_item();
            } while (item >> 16 == IT_KV);
            if (dst) {
#pragma unroll
                for (int j = 0; j < 64; j++) dst[(j >> 1) * 128 + (j & 1) * 32] = pk[j];
                signal(prev);
            }
        }
        for (;; n++, next_item()) {
            const int type = item >> 16, b = (item >> 8) & 255, i = item & 255;
            const int lane = (tid & 31) + (item >> 24), wgi = (wu >> 2) - 1 + __shfl_sync(0xffffffffu, item >> 24, 0), wi = wu & 3;
            WLOG(0);
            if (type == IT_QA) {
                float acc[128];
                ST(sid, cw, 0);
                ST(sid, cw, 1);
                mainloop<256, 16, false>(acc, sb, wgi, full, empty, it, lane == 0);
                ST(sid, cw, 2);
                uint32_t q0[32], q1[32];
#pragma unroll
                for (int j = 0; j < 32; j++) { q0[j] = pack_bf16(acc[2 * j], acc[2 * j + 1]); q1[j] = pack_bf16(acc[64 + 2 * j], acc[65 + 2 * j]); }
                const uint32_t par = (it >> 2) & 1, so = sb + wgi * 20480;
                float sx0[32] = {}, sm0[8] = {}, sx1[32] = {}, sm1[8] = {};
                uint32_t p0[20], p1[20];
                if (lane == 0) asm volatile("cp.async.bulk.wait_group.read 0;" ::: "memory");
                mbar_wait(stgbar, (nqa++ & 1) ^ 1);
                bar_sync(3 + wgi, 128);
                mbar_wait_long(full, par);
                ST(sid, cw, 3);
                attn_scores(sx0, sm0, q0, so);
                ST(sid, cw, 7);
                mbar_wait(full + 8, par);
                attn_scores(sx1, sm1, q1, so + G_STAGE);
                float o0[64] = {}, o1[64] = {};
                if (ATT2) {
                    ST(sid, cw, 8);
                    wg_wait<0>();
                    ST(sid, cw, 9);
                    if (lane == 0) { mbar_arrive(empty); mbar_arrive(empty + 8); }
                    attn_softmax(p0, sx0, sm0, wi, lane);
                    attn_softmax(p1, sx1, sm1, wi, lane);
                    ST(sid, cw, 10);
                    mbar_wait(full + 16, par);
                    ST(sid, cw, 11);
                    attn_pv(o0, p0, so + 2 * G_STAGE);
                    ST(sid, cw, 4);
                } else {
                    wg_wait<1>();
                    if (lane == 0) mbar_arrive(empty);
                    attn_softmax(p0, sx0, sm0, wi, lane);
                    mbar_wait(full + 16, par);
                    attn_pv(o0, p0, so + 2 * G_STAGE);
                    wg_wait<1>();
                    if (lane == 0) mbar_arrive(empty + 8);
                    ST(sid, cw, 4);
                    attn_softmax(p1, sx1, sm1, wi, lane);
                }
                mbar_wait(full + 24, par);
                attn_pv(o1, p1, so + 3 * G_STAGE);
                wg_wait<1>();
                if (lane == 0) mbar_arrive(empty + 16);
                ST(sid, cw, 5);
                const uint32_t da = (wi * 2 + ((lane >> 3) & 1)) * 1024 + (lane >> 4) * 128 + (lane & 7) * 16;
                attn_stage(o0, sb + G_STG + wgi * 16384 + da);
                wg_wait<0>();
                bar_sync(3 + wgi, 128);
                attn_stage(o1, so + 3 * G_STAGE + da);
                asm volatile("fence.proxy.async.shared::cta;" ::: "memory");
                ST(sid, cw, 6);
                signal(item);
                it += 4;
            } else if (type == IT_O) {
                mbar_wait_long(full, (it >> 2) & 1);
                if (b < O_WIDE) o_item<256>(sb, wgi, wi, lane, full, empty, it, &mout, b * 128, i * 256, (nqa & 1) ^ 1);
                else o_item<128>(sb, wgi, wi, lane, full, empty, it, &mout, b * 128, i * 128, (nqa & 1) ^ 1);
            } else if (type == IT_S4) {
                mbar_wait_long(full, (it >> 2) & 1);
                mbar_wait(full + 24, (it >> 2) & 1);
                s4_item(sb, wgi * 4 + wi, lane, i, dsk, empty, &my, (nqa & 1) ^ 1);
                it += 4;
            } else break;
            WLOG(1);
        }
        bar_sync(2, 256);
        signal(item);
        if (lane == 0) asm volatile("cp.async.bulk.wait_group 0;" ::: "memory");
    }
}

typedef CUresult (*EncodeFn)(CUtensorMap*, CUtensorMapDataType, cuuint32_t, void*, const cuuint64_t*, const cuuint64_t*, const cuuint32_t*,
                             const cuuint32_t*, CUtensorMapInterleave, CUtensorMapSwizzle, CUtensorMapL2promotion, CUtensorMapFloatOOBfill);
static EncodeFn get_encode() {
    void* fn = nullptr; cudaDriverEntryPointQueryResult st;
    cudaGetDriverEntryPoint("cuTensorMapEncodeTiled", &fn, cudaEnableDefault, &st);
    return (EncodeFn)fn;
}
static void map_act(EncodeFn enc, CUtensorMap* m, const void* p, int rows, int cols, int boxr) {
    cuuint64_t dim[2] = {(cuuint64_t)cols, (cuuint64_t)rows}, str[1] = {(cuuint64_t)cols * 2};
    cuuint32_t box[2] = {64, (cuuint32_t)boxr}, es[2] = {1, 1};
    enc(m, CU_TENSOR_MAP_DATA_TYPE_BFLOAT16, 2, (void*)p, dim, str, box, es, CU_TENSOR_MAP_INTERLEAVE_NONE, CU_TENSOR_MAP_SWIZZLE_128B,
        CU_TENSOR_MAP_L2_PROMOTION_L2_128B, CU_TENSOR_MAP_FLOAT_OOB_FILL_NONE);
}
static void map_w(EncodeFn enc, CUtensorMap* m, const void* p, int k, int n) {
    cuuint64_t dim[3] = {64, (cuuint64_t)k, (cuuint64_t)n / 64}, str[2] = {(cuuint64_t)n * 2, 128};
    cuuint32_t box[3] = {64, 64, 2}, es[3] = {1, 1, 1};
    enc(m, CU_TENSOR_MAP_DATA_TYPE_BFLOAT16, 3, (void*)p, dim, str, box, es, CU_TENSOR_MAP_INTERLEAVE_NONE, CU_TENSOR_MAP_SWIZZLE_128B,
        CU_TENSOR_MAP_L2_PROMOTION_L2_256B, CU_TENSOR_MAP_FLOAT_OOB_FILL_NONE);
}

static void map_kv(EncodeFn enc, CUtensorMap* m, void* p, int n) {
    cuuint64_t dim[3] = {(cuuint64_t)n, NSEG, 512}, str[2] = {(cuuint64_t)n * 1024, (cuuint64_t)n * 2};
    cuuint32_t box[3] = {(cuuint32_t)n, 2, 16}, es[3] = {1, 1, 1};
    enc(m, CU_TENSOR_MAP_DATA_TYPE_BFLOAT16, 3, p, dim, str, box, es, CU_TENSOR_MAP_INTERLEAVE_NONE, CU_TENSOR_MAP_SWIZZLE_NONE,
        CU_TENSOR_MAP_L2_PROMOTION_NONE, CU_TENSOR_MAP_FLOAT_OOB_FILL_NONE);
}
static void map_box(EncodeFn enc, CUtensorMap* m, const void* p, int rows, int ld, int boxc, int boxr, CUtensorMapSwizzle sw,
                    CUtensorMapL2promotion promo = CU_TENSOR_MAP_L2_PROMOTION_NONE) {
    cuuint64_t dim[2] = {(cuuint64_t)ld, (cuuint64_t)rows}, str[1] = {(cuuint64_t)ld * 2};
    cuuint32_t box[2] = {(cuuint32_t)boxc, (cuuint32_t)boxr}, es[2] = {1, 1};
    enc(m, CU_TENSOR_MAP_DATA_TYPE_BFLOAT16, 2, (void*)p, dim, str, box, es, CU_TENSOR_MAP_INTERLEAVE_NONE, sw,
        promo, CU_TENSOR_MAP_FLOAT_OOB_FILL_NONE);
}

extern "C" void kernel_launch(void* const* d_in, const int* in_sizes, int n_in, void* d_out, int out_size) {
    const bf16* x = (const bf16*)d_in[0];
    const bf16* mem0 = (const bf16*)d_in[1];
    const bf16 *Wq = (const bf16*)d_in[2], *Wk = (const bf16*)d_in[3], *Wv = (const bf16*)d_in[4], *Wo = (const bf16*)d_in[5];
    static EncodeFn enc = nullptr;
    static int nsm = 0;
    static void* kv[4];
    if (!enc) {
        enc = get_encode();
        cudaGetSymbolAddress(&kv[0], g_kx); cudaGetSymbolAddress(&kv[1], g_vx); cudaGetSymbolAddress(&kv[2], g_km); cudaGetSymbolAddress(&kv[3], g_vm);
        cudaDeviceGetAttribute(&nsm, cudaDevAttrMultiProcessorCount, 0);
        cudaFuncSetAttribute(chain_kernel, cudaFuncAttributeMaxDynamicSharedMemorySize, CH_SMEM);
        cudaFuncSetAttribute(worker_kernel, cudaFuncAttributeMaxDynamicSharedMemorySize, G_SMEM);
    }
    CUtensorMap mx, mq, mk, mv, mo, mout, mu, my;
    map_act(enc, &mx, x, S_LEN, DM, 128);
    map_w(enc, &mq, Wq, DM, HD); map_w(enc, &mk, Wk, DM, HD); map_w(enc, &mv, Wv, DM, HD); map_w(enc, &mo, Wo, HD, DM);
    map_box(enc, &mout, d_out, S_LEN, 2 * DM, 64, 16, CU_TENSOR_MAP_SWIZZLE_128B);
    map_box(enc, &mu, d_in[7], S_LEN, DM, 8, 256, CU_TENSOR_MAP_SWIZZLE_NONE, (CUtensorMapL2promotion)PROMU);
    map_box(enc, &my, d_out, S_LEN, 2 * DM, 8, 256, CU_TENSOR_MAP_SWIZZLE_NONE);
    CUtensorMap mkx, mvx, mkm, mvm;
    map_kv(enc, &mkx, kv[0], 256); map_kv(enc, &mvx, kv[1], 256); map_kv(enc, &mkm, kv[2], 64); map_kv(enc, &mvm, kv[3], 64);
    CUtensorMap cq, ck, cv, co;
    map_box(enc, &cq, Wq, DM, HD, 32, 32, CU_TENSOR_MAP_SWIZZLE_64B, (CUtensorMapL2promotion)PROMO); map_box(enc, &ck, Wk, DM, HD, 32, 32, CU_TENSOR_MAP_SWIZZLE_64B, (CUtensorMapL2promotion)PROMO);
    map_box(enc, &cv, Wv, DM, HD, 32, 32, CU_TENSOR_MAP_SWIZZLE_64B, (CUtensorMapL2promotion)PROMO); map_box(enc, &co, Wo, HD, DM, 32, 16, CU_TENSOR_MAP_SWIZZLE_64B, (CUtensorMapL2promotion)PROMO);
    S4Params P = {(const bf16*)d_in[8], (const bf16*)d_in[9], (const bf16*)d_in[10], (const bf16*)d_in[11],
                  (const bf16*)d_in[12], (const bf16*)d_in[13], (const bf16*)d_in[14], (const bf16*)d_in[15]};
    int aware = 1;
    cudaLaunchAttribute at[1];
    at[0].id = cudaLaunchAttributeProgrammaticStreamSerialization;
    at[0].val.programmaticStreamSerializationAllowed = 1;
    cudaLaunchConfig_t cfg = {};
    cfg.stream = cudaStreamPerThread;
    cfg.gridDim = dim3(96); cfg.blockDim = dim3(CH_THREADS); cfg.dynamicSmemBytes = CH_SMEM;
    cudaLaunchKernelEx(&cfg, chain_kernel, cq, ck, cv, co, Wq, Wk, Wv, mem0, P, aware);
    cfg.attrs = at; cfg.numAttrs = 1;
    cfg.gridDim = dim3(nsm); cfg.blockDim = dim3(384); cfg.dynamicSmemBytes = G_SMEM;
    cudaLaunchKernelEx(&cfg, worker_kernel, mx, mq, mk, mv, mo, mout, mu, my, mkx, mvx, mkm, mvm, P.dsk);
}
```

```cpp
#include <cuda.h>
#include <cuda_runtime.h>
#include <cuda_bf16.h>
#include <stdint.h>
#include <stdio.h>
#include <string.h>

typedef __nv_bfloat16 bf16;

constexpr int S_LEN = 2048, DM = 1024, NH = 32, DH = 128, HD = 4096, NSEG = 64;
constexpr uint32_t SENT = 0xFFFFFFFFu;
constexpr int SPIN_LIMIT = 1 << 18;
#define REALL 0

__device__ __align__(1024) bf16 g_kx[S_LEN * HD];
__device__ __align__(1024) bf16 g_vx[S_LEN * HD];
__device__ __align__(1024) bf16 g_ox[S_LEN * HD];
__device__ __align__(1024) bf16 g_km[NSEG * NH * 8 * DH];
__device__ __align__(1024) bf16 g_vm[NSEG * NH * 8 * DH];
__device__ __align__(1024) bf16 g_kd[DM * 768 + 8192];
__device__ __align__(1024) char g_ring[2 << 20];
__device__ int g_kvf[96 * 16];
constexpr int C_NEXT = 0, C_CHAIN = 32, C_QA_DONE = 64, N_CTR = 96;
__device__ int g_ctr[N_CTR];

__device__ __forceinline__ uint32_t smem_u32(const void* p) { return (uint32_t)__cvta_generic_to_shared(p); }
__device__ __forceinline__ uint32_t clk() { uint32_t c; asm volatile("mov.u32 %0, %%clock;" : "=r"(c)::"memory"); return c; }
__device__ __forceinline__ uint32_t pack_bf16(float lo, float hi) {
    uint32_t r; asm("cvt.rn.bf16x2.f32 %0, %1, %2;" : "=r"(r) : "f"(hi), "f"(lo)); return r;
}
__device__ __forceinline__ uint32_t movm(uint32_t a) {
    uint32_t d; asm volatile("movmatrix.sync.aligned.m8n8.trans.b16 %0, %1;" : "=r"(d) : "r"(a)); return d;
}
__device__ __forceinline__ void mma16(float (&d)[4], const uint32_t (&a)[4], uint32_t b0, uint32_t b1) {
    asm volatile("mma.sync.aligned.m16n8k16.row.col.f32.bf16.bf16.f32 {%0,%1,%2,%3}, {%4,%5,%6,%7}, {%8,%9}, {%0,%1,%2,%3};"
        : "+f"(d[0]), "+f"(d[1]), "+f"(d[2]), "+f"(d[3]) : "r"(a[0]), "r"(a[1]), "r"(a[2]), "r"(a[3]), "r"(b0), "r"(b1));
}
__device__ __forceinline__ void mma16z(float (&d)[4], const uint32_t (&a)[4], uint32_t b0, uint32_t b1) {
    asm volatile("mma.sync.aligned.m16n8k16.row.col.f32.bf16.bf16.f32 {%0,%1,%2,%3}, {%4,%5,%6,%7}, {%8,%9}, {%10,%10,%10,%10};"
        : "=f"(d[0]), "=f"(d[1]), "=f"(d[2]), "=f"(d[3]) : "r"(a[0]), "r"(a[1]), "r"(a[2]), "r"(a[3]), "r"(b0), "r"(b1), "f"(0.f));
}
__device__ __forceinline__ void mma8z(float (&d)[4], uint32_t a0, uint32_t a1, uint32_t b0) {
    asm volatile("mma.sync.aligned.m16n8k8.row.col.f32.bf16.bf16.f32 {%0,%1,%2,%3}, {%4,%5}, {%6}, {%7,%7,%7,%7};"
        : "=f"(d[0]), "=f"(d[1]), "=f"(d[2]), "=f"(d[3]) : "r"(a0), "r"(a1), "r"(b0), "f"(0.f));
}
__device__ __forceinline__ void ldsm4t(uint32_t (&r)[4], uint32_t addr) {
    asm volatile("ldmatrix.sync.aligned.m8n8.x4.trans.shared.b16 {%0,%1,%2,%3}, [%4];"
        : "=r"(r[0]), "=r"(r[1]), "=r"(r[2]), "=r"(r[3]) : "r"(addr) : "memory");
}
__device__ __forceinline__ void ldsm4(uint32_t (&r)[4], uint32_t addr) {
    asm volatile("ldmatrix.sync.aligned.m8n8.x4.shared.b16 {%0,%1,%2,%3}, [%4];"
        : "=r"(r[0]), "=r"(r[1]), "=r"(r[2]), "=r"(r[3]) : "r"(addr) : "memory");
}
__device__ __forceinline__ float lds32(uint32_t a) {
    float v; asm volatile("ld.shared.f32 %0, [%1];" : "=f"(v) : "r"(a) : "memory"); return v;
}
__device__ __forceinline__ void st_async1(uint32_t dst, float v, uint32_t bar) {
    asm volatile("st.async.shared::cluster.mbarrier::complete_tx::bytes.f32 [%0], %1, [%2];" ::"r"(dst), "f"(v), "r"(bar) : "memory");
}
__device__ __forceinline__ void st_async2(uint32_t dst, float x, float y, uint32_t bar) {
    asm volatile("st.async.shared::cluster.mbarrier::complete_tx::bytes.v2.f32 [%0], {%1,%2}, [%3];" ::"r"(dst), "f"(x), "f"(y), "r"(bar) : "memory");
}
__device__ __forceinline__ void mma8(float (&d)[4], uint32_t a0, uint32_t a1, uint32_t b0) {
    asm volatile("mma.sync.aligned.m16n8k8.row.col.f32.bf16.bf16.f32 {%0,%1,%2,%3}, {%4,%5}, {%6}, {%0,%1,%2,%3};"
        : "+f"(d[0]), "+f"(d[1]), "+f"(d[2]), "+f"(d[3]) : "r"(a0), "r"(a1), "r"(b0));
}
__device__ __forceinline__ void cp16(uint32_t dst, const void* src) {
    asm volatile("cp.async.cg.shared.global [%0], [%1], 16;" ::"r"(dst), "l"(src) : "memory");
}
__device__ __forceinline__ void sts128(uint32_t a, const float (&v)[4]) {
    asm volatile("st.shared.v4.f32 [%0], {%1,%2,%3,%4};" ::"r"(a), "f"(v[0]), "f"(v[1]), "f"(v[2]), "f"(v[3]) : "memory");
}
__device__ __forceinline__ float4 lds128(uint32_t a) {
    float4 v; asm volatile("ld.shared.v4.f32 {%0,%1,%2,%3}, [%4];" : "=f"(v.x), "=f"(v.y), "=f"(v.z), "=f"(v.w) : "r"(a) : "memory"); return v;
}
__device__ __forceinline__ void sts64(uint32_t a, float x, float y) {
    asm volatile("st.shared.v2.f32 [%0], {%1,%2};" ::"r"(a), "f"(x), "f"(y) : "memory");
}
__device__ __forceinline__ float2 lds64(uint32_t a) {
    float2 v; asm volatile("ld.shared.v2.f32 {%0,%1}, [%2];" : "=f"(v.x), "=f"(v.y) : "r"(a) : "memory"); return v;
}
__device__ __forceinline__ void bar_sync(int id, int n) { asm volatile("bar.sync %0, %1;" ::"r"(id), "r"(n) : "memory"); }
__device__ __forceinline__ void bar_arrive(int id, int n) { asm volatile("bar.arrive %0, %1;" ::"r"(id), "r"(n) : "memory"); }
__device__ __forceinline__ uint32_t mapa(uint32_t a, uint32_t r) {
    uint32_t o; asm("mapa.shared::cluster.u32 %0, %1, %2;" : "=r"(o) : "r"(a), "r"(r)); return o;
}
__device__ __forceinline__ void st_async4(uint32_t dst, float4 v, uint32_t bar) {
    asm volatile("st.async.shared::cluster.mbarrier::complete_tx::bytes.v4.f32 [%0], {%1,%2,%3,%4}, [%5];"
        ::"r"(dst), "f"(v.x), "f"(v.y), "f"(v.z), "f"(v.w), "r"(bar) : "memory");
}
__device__ __forceinline__ void mbar_init(uint32_t bar, int n) { asm volatile("mbarrier.init.shared.b64 [%0], %1;" ::"r"(bar), "r"(n) : "memory"); }
__device__ __forceinline__ void mbar_expect(uint32_t bar, int bytes) {
    asm volatile("mbarrier.arrive.expect_tx.shared.b64 _, [%0], %1;" ::"r"(bar), "r"(bytes) : "memory");
}
__device__ __forceinline__ void bulk_load(uint32_t dst, const void* src, int bytes, uint32_t bar) {
    asm volatile("cp.async.bulk.shared::cluster.global.mbarrier::complete_tx::bytes [%0], [%1], %2, [%3];"
        ::"r"(dst), "l"(src), "r"(bytes), "r"(bar) : "memory");
}
__device__ __forceinline__ bool mbar_try(uint32_t bar, uint32_t par) {
    uint32_t ok;
    asm volatile("{.reg .pred p; mbarrier.try_wait.parity.shared::cta.b64 p, [%1], %2; selp.u32 %0, 1, 0, p;}"
        : "=r"(ok) : "r"(bar), "r"(par) : "memory");
    return ok;
}
__device__ __forceinline__ bool mbar_test(uint32_t bar, uint32_t par) {
    uint32_t ok;
    asm volatile("{.reg .pred p; mbarrier.test_wait.parity.shared::cta.b64 p, [%1], %2; selp.u32 %0, 1, 0, p;}"
        : "=r"(ok) : "r"(bar), "r"(par) : "memory");
    return ok;
}
__device__ __forceinline__ int ld_acq(const int* p) { int v; asm volatile("ld.acquire.gpu.global.s32 %0, [%1];" : "=r"(v) : "l"(p) : "memory"); return v; }
__device__ __forceinline__ void red_release(int* p, int v) { asm volatile("red.release.gpu.global.add.s32 [%0], %1;" ::"l"(p), "r"(v) : "memory"); }
__device__ __forceinline__ void fence_gpu() { asm volatile("fence.acq_rel.gpu;" ::: "memory"); }
__device__ __forceinline__ void wait_ctr(const int* p, int n) {
    for (int it = 0; it < (1 << 20) && ld_acq(p) < n; it++) __nanosleep(64);
}
__device__ __forceinline__ void mbar_wait(uint32_t bar, uint32_t par) {
    if (!mbar_try(bar, par))
        for (int it = 0; it < SPIN_LIMIT && !mbar_try(bar, par); it++) {}
}
__device__ __forceinline__ void mbar_wait_long(uint32_t bar, uint32_t par) {
    for (int it = 0; it < (1 << 24) && !mbar_try(bar, par); it++) {}
}
__device__ __forceinline__ float4 add4(float4 a, float4 b) { return make_float4(a.x + b.x, a.y + b.y, a.z + b.z, a.w + b.w); }
__device__ __forceinline__ float ex2(float x) { float y; asm("ex2.approx.ftz.f32 %0, %1;" : "=f"(y) : "f"(x)); return y; }

__device__ __forceinline__ void wgmma256(float (&d)[128], uint64_t da, uint64_t db, int acc) {
    asm volatile("{.reg .pred p; setp.ne.b32 p, %130, 0;\n"
        "wgmma.mma_async.sync.aligned.m64n256k16.f32.bf16.bf16 {"
        "%0,%1,%2,%3,%4,%5,%6,%7,%8,%9,%10,%11,%12,%13,%14,%15,"
        "%16,%17,%18,%19,%20,%21,%22,%23,%24,%25,%26,%27,%28,%29,%30,%31,"
        "%32,%33,%34,%35,%36,%37,%38,%39,%40,%41,%42,%43,%44,%45,%46,%47,"
        "%48,%49,%50,%51,%52,%53,%54,%55,%56,%57,%58,%59,%60,%61,%62,%63,"
        "%64,%65,%66,%67,%68,%69,%70,%71,%72,%73,%74,%75,%76,%77,%78,%79,"
        "%80,%81,%82,%83,%84,%85,%86,%87,%88,%89,%90,%91,%92,%93,%94,%95,"
        "%96,%97,%98,%99,%100,%101,%102,%103,%104,%105,%106,%107,%108,%109,%110,%111,"
        "%112,%113,%114,%115,%116,%117,%118,%119,%120,%121,%122,%123,%124,%125,%126,%127"
        "}, %128, %129, p, 1, 1, 0, 1;}"
        : "+f"(d[0]), "+f"(d[1]), "+f"(d[2]), "+f"(d[3]), "+f"(d[4]), "+f"(d[5]), "+f"(d[6]), "+f"(d[7]), "+f"(d[8]), "+f"(d[9]), "+f"(d[10]), "+f"(d[11]), "+f"(d[12]), "+f"(d[13]), "+f"(d[14]), "+f"(d[15]), "+f"(d[16]), "+f"(d[17]), "+f"(d[18]), "+f"(d[19]), "+f"(d[20]), "+f"(d[21]), "+f"(d[22]), "+f"(d[23]), "+f"(d[24]), "+f"(d[25]), "+f"(d[26]), "+f"(d[27]), "+f"(d[28]), "+f"(d[29]), "+f"(d[30]), "+f"(d[31]), "+f"(d[32]), "+f"(d[33]), "+f"(d[34]), "+f"(d[35]), "+f"(d[36]), "+f"(d[37]), "+f"(d[38]), "+f"(d[39]), "+f"(d[40]), "+f"(d[41]), "+f"(d[42]), "+f"(d[43]), "+f"(d[44]), "+f"(d[45]), "+f"(d[46]), "+f"(d[47]), "+f"(d[48]), "+f"(d[49]), "+f"(d[50]), "+f"(d[51]), "+f"(d[52]), "+f"(d[53]), "+f"(d[54]), "+f"(d[55]), "+f"(d[56]), "+f"(d[57]), "+f"(d[58]), "+f"(d[59]), "+f"(d[60]), "+f"(d[61]), "+f"(d[62]), "+f"(d[63]), "+f"(d[64]), "+f"(d[65]), "+f"(d[66]), "+f"(d[67]), "+f"(d[68]), "+f"(d[69]), "+f"(d[70]), "+f"(d[71]), "+f"(d[72]), "+f"(d[73]), "+f"(d[74]), "+f"(d[75]), "+f"(d[76]), "+f"(d[77]), "+f"(d[78]), "+f"(d[79]), "+f"(d[80]), "+f"(d[81]), "+f"(d[82]), "+f"(d[83]), "+f"(d[84]), "+f"(d[85]), "+f"(d[86]), "+f"(d[87]), "+f"(d[88]), "+f"(d[89]), "+f"(d[90]), "+f"(d[91]), "+f"(d[92]), "+f"(d[93]), "+f"(d[94]), "+f"(d[95]), "+f"(d[96]), "+f"(d[97]), "+f"(d[98]), "+f"(d[99]), "+f"(d[100]), "+f"(d[101]), "+f"(d[102]), "+f"(d[103]), "+f"(d[104]), "+f"(d[105]), "+f"(d[106]), "+f"(d[107]), "+f"(d[108]), "+f"(d[109]), "+f"(d[110]), "+f"(d[111]), "+f"(d[112]), "+f"(d[113]), "+f"(d[114]), "+f"(d[115]), "+f"(d[116]), "+f"(d[117]), "+f"(d[118]), "+f"(d[119]), "+f"(d[120]), "+f"(d[121]), "+f"(d[122]), "+f"(d[123]), "+f"(d[124]), "+f"(d[125]), "+f"(d[126]), "+f"(d[127])
        : "l"(da), "l"(db), "r"(acc));
}
__device__ __forceinline__ void wgmma128(float (&d)[64], uint64_t da, uint64_t db, int acc) {
    asm volatile("{.reg .pred p; setp.ne.b32 p, %66, 0;\n"
        "wgmma.mma_async.sync.aligned.m64n128k16.f32.bf16.bf16 {"
        "%0,%1,%2,%3,%4,%5,%6,%7,%8,%9,%10,%11,%12,%13,%14,%15,"
        "%16,%17,%18,%19,%20,%21,%22,%23,%24,%25,%26,%27,%28,%29,%30,%31,"
        "%32,%33,%34,%35,%36,%37,%38,%39,%40,%41,%42,%43,%44,%45,%46,%47,"
        "%48,%49,%50,%51,%52,%53,%54,%55,%56,%57,%58,%59,%60,%61,%62,%63"
        "}, %64, %65, p, 1, 1, 0, 1;}"
        : "+f"(d[0]), "+f"(d[1]), "+f"(d[2]), "+f"(d[3]), "+f"(d[4]), "+f"(d[5]), "+f"(d[6]), "+f"(d[7]), "+f"(d[8]), "+f"(d[9]), "+f"(d[10]), "+f"(d[11]), "+f"(d[12]), "+f"(d[13]), "+f"(d[14]), "+f"(d[15]), "+f"(d[16]), "+f"(d[17]), "+f"(d[18]), "+f"(d[19]), "+f"(d[20]), "+f"(d[21]), "+f"(d[22]), "+f"(d[23]), "+f"(d[24]), "+f"(d[25]), "+f"(d[26]), "+f"(d[27]), "+f"(d[28]), "+f"(d[29]), "+f"(d[30]), "+f"(d[31]), "+f"(d[32]), "+f"(d[33]), "+f"(d[34]), "+f"(d[35]), "+f"(d[36]), "+f"(d[37]), "+f"(d[38]), "+f"(d[39]), "+f"(d[40]), "+f"(d[41]), "+f"(d[42]), "+f"(d[43]), "+f"(d[44]), "+f"(d[45]), "+f"(d[46]), "+f"(d[47]), "+f"(d[48]), "+f"(d[49]), "+f"(d[50]), "+f"(d[51]), "+f"(d[52]), "+f"(d[53]), "+f"(d[54]), "+f"(d[55]), "+f"(d[56]), "+f"(d[57]), "+f"(d[58]), "+f"(d[59]), "+f"(d[60]), "+f"(d[61]), "+f"(d[62]), "+f"(d[63])
        : "l"(da), "l"(db), "r"(acc));
}
__device__ __forceinline__ void wg_fence() { asm volatile("wgmma.fence.sync.aligned;" ::: "memory"); }
__device__ __forceinline__ void wg_commit() { asm volatile("wgmma.commit_group.sync.aligned;" ::: "memory"); }
template <int N> __device__ __forceinline__ void wg_wait() { asm volatile("wgmma.wait_group.sync.aligned %0;" ::"n"(N) : "memory"); }
__device__ __forceinline__ uint64_t mkdesc(uint32_t addr, uint32_t lbo, uint32_t sbo, uint32_t sw) {
    return (uint64_t)((addr & 0x3FFFF) >> 4) | ((uint64_t)(lbo >> 4) << 16) | ((uint64_t)(sbo >> 4) << 32) | ((uint64_t)sw << 62);
}
__device__ __forceinline__ void tma2d(uint32_t dst, const CUtensorMap* m, int c0, int c1, uint32_t bar) {
    asm volatile("cp.async.bulk.tensor.2d.shared::cluster.global.mbarrier::complete_tx::bytes [%0], [%1, {%2, %3}], [%4];"
        ::"r"(dst), "l"(m), "r"(c0), "r"(c1), "r"(bar) : "memory");
}
__device__ __forceinline__ void tma3d(uint32_t dst, const CUtensorMap* m, int c0, int c1, int c2, uint32_t bar) {
    asm volatile("cp.async.bulk.tensor.3d.shared::cluster.global.mbarrier::complete_tx::bytes [%0], [%1, {%2, %3, %4}], [%5];"
        ::"r"(dst), "l"(m), "r"(c0), "r"(c1), "r"(c2), "r"(bar) : "memory");
}
__device__ __forceinline__ void tma3d_mc(uint32_t dst, const CUtensorMap* m, int c0, int c1, int c2, uint32_t bar, uint16_t mask) {
    asm volatile("cp.async.bulk.tensor.3d.shared::cluster.global.mbarrier::complete_tx::bytes.multicast::cluster [%0], [%1, {%2, %3, %4}], [%5], %6;"
        ::"r"(dst), "l"(m), "r"(c0), "r"(c1), "r"(c2), "r"(bar), "h"(mask) : "memory");
}
__device__ __forceinline__ void mbar_arrive(uint32_t bar) { asm volatile("mbarrier.arrive.shared.b64 _, [%0];" ::"r"(bar) : "memory"); }
__device__ __forceinline__ void mbar_arrive_remote(uint32_t bar) {
    asm volatile("mbarrier.arrive.shared::cluster.b64 _, [%0];" ::"r"(bar) : "memory");
}
template <int R> __device__ __forceinline__ void reg_inc() { asm volatile("setmaxnreg.inc.sync.aligned.u32 %0;" ::"n"(R)); }
template <int R> __device__ __forceinline__ void reg_dec() { asm volatile("setmaxnreg.dec.sync.aligned.u32 %0;" ::"n"(R)); }

#define ST(id, w, i)
constexpr int CH_NRES = 50;
constexpr int CH_WREG = CH_NRES * 512;
constexpr int CH_PART = 8 * CH_WREG;
constexpr int CH_SX = CH_PART + 16384;
constexpr int CH_MX = CH_SX + 3 * 1280;
constexpr int CH_QK = CH_MX;
constexpr int CH_XS = CH_MX + 3 * 512;
constexpr int CH_BAR = CH_XS + 5632;
constexpr int CH_SMEM = CH_BAR + 192;
constexpr int CH_THREADS = 384;

__device__ __forceinline__ char* ring_base() { return (char*)(((uintptr_t)g_ring + (1 << 20) - 1) & ~(uintptr_t)((1 << 20) - 1)); }
__device__ __forceinline__ uint32_t ring_off(int chunk, int side) {
    uint32_t o = ((chunk & 1) << 13) | ((chunk >> 1) << 16);
    uint32_t par = ((o >> 13) ^ (o >> 16) ^ (o >> 17) ^ (o >> 19) ^ side) & 1;
    return o | (par << 12);
}
__device__ __forceinline__ uint2 ld_poll(const char* p) {
    unsigned long long v; asm volatile("ld.relaxed.gpu.global.b64 %0, [%1];" : "=l"(v) : "l"(p) : "memory");
    return make_uint2((uint32_t)v, (uint32_t)(v >> 32));
}
__device__ __forceinline__ void st_pub(char* p, uint32_t x, uint32_t y) {
    unsigned long long v = ((unsigned long long)y << 32) | x;
    asm volatile("st.relaxed.gpu.global.b64 [%0], %1;" ::"l"(p), "l"(v) : "memory");
}
template <int N>
__device__ __forceinline__ void poll_issue(uint2 (&b)[N], const char* p, bool lastvalid) {
#pragma unroll
    for (int i = 0; i < N; i++) {
        if (i < N - 1 || lastvalid) b[i] = ld_poll(p + i * 256);
        else b[i] = make_uint2(0, 0);
    }
}
template <int N>
__device__ __forceinline__ int poll_check(uint2 (&b)[N], const char* p, uint32_t z) {
    int it = 0;
    uint32_t mx = z;
#pragma unroll
    for (int i = 0; i < N; i++) mx = max(mx, b[i].x);
    if (__any_sync(0xffffffffu, mx == SENT)) {
        do {
#pragma unroll
            for (int i = 0; i < N; i++)
                if ((REALL && i < 10) || b[i].x == SENT) b[i] = ld_poll(p + i * 256);
            mx = b[0].x;
#pragma unroll
            for (int i = 1; i < N; i++) mx = max(mx, b[i].x);
            it++;
        } while (__any_sync(0xffffffffu, mx == SENT && it < SPIN_LIMIT));
    }
    return it;
}
template <int N>
__device__ __forceinline__ uint32_t delay(uint32_t a) {
    uint32_t z = 0;
#pragma unroll
    for (int i = 0; i < N; i++) asm volatile("ld.volatile.shared.u32 %0, [%1];" : "=r"(z) : "r"(a + z) : "memory");
    return z;
}

#define PFKV 0
#define LDW 0
#define KGS 3
constexpr int KVN = 2;
#define FEN 1
#define XB 4
#define KEEP 100
#define PE 0
#define PROMO 2
#define PROMU 0
#define FNC 1
#define CL 8
#define PL 0
#define ML 4
#define MP 2
#define VCH_P 4
#define VCH_C 2
#define DLM 3
#define DLO 5
constexpr int OB = 0;
template <int PACE, int I0 = 0, int I1 = 12>
__device__ __forceinline__ void preload(uint32_t (&sw)[12][4], uint32_t a, uint32_t zero) {
    uint32_t z = 0;
#pragma unroll
    for (int i = I0; i < I1; i++) {
        if (PACE && i % (PACE ? PACE : 1) == 0) z = delay<1>(zero + z);
        ldsm4t(sw[i], a + z + i * 512);
    }
}
__device__ __forceinline__ void stsm4(uint32_t addr, uint32_t a, uint32_t b, uint32_t c, uint32_t d) {
    asm volatile("stmatrix.sync.aligned.m8n8.x4.shared.b16 [%0], {%1,%2,%3,%4};" ::"r"(addr), "r"(a), "r"(b), "r"(c), "r"(d) : "memory");
}
__device__ __forceinline__ void stsm4t(uint32_t addr, uint32_t a, uint32_t b, uint32_t c, uint32_t d) {
    asm volatile("stmatrix.sync.aligned.m8n8.x4.trans.shared.b16 [%0], {%1,%2,%3,%4};" ::"r"(addr), "r"(a), "r"(b), "r"(c), "r"(d) : "memory");
}
__device__ __forceinline__ void st_part(uint32_t addr, const float (&x)[4], const float (&y)[4]) {
    stsm4(addr, pack_bf16(x[0], x[1]), pack_bf16(x[2], x[3]), pack_bf16(y[0], y[1]), pack_bf16(y[2], y[3]));
}
template <bool TR>
__device__ __forceinline__ void red_part(uint32_t& lo, uint32_t& hi, uint32_t addr, uint32_t eye) {
    uint32_t a[4][4];
#pragma unroll
    for (int j = 0; j < 4; j++) { if (TR) ldsm4t(a[j], addr + j * 1024); else ldsm4(a[j], addr + j * 1024); }
    float r0[4], r1[4], r2[4], r3[4];
    mma16z(r0, a[0], eye, eye); mma16z(r1, a[1], eye, eye); mma16z(r2, a[2], eye, eye); mma16z(r3, a[3], eye, eye);
#pragma unroll
    for (int j = 0; j < 4; j++) r0[j] = ((r0[j] + r1[j]) + r2[j]) + r3[j];
    lo = pack_bf16(r0[0], r0[1]); hi = pack_bf16(r0[2], r0[3]);
}
__device__ __forceinline__ int o_chunk(int ks, int& pos) {
    const int cw = ks < 176 ? ks / 11 : 16 + (ks - 176) / 10;
    pos = ks - (cw < 16 ? 11 * cw : 176 + 10 * (cw - 16));
    return cw;
}

template <bool PV>
__device__ __forceinline__ void chain_loop(const uint32_t (&wa)[36][4], const uint32_t sb, const int w, const int lane0, const int rank,
                                           const int h, const int side) {
    const int rk1 = rank == 2 ? 0 : rank + 1, rk2 = rank == 0 ? 2 : rank - 1;
    const int nq = rank == 0 ? 6 : 5, u0 = rank == 0 ? 0 : 1 + 5 * rank, v0 = rank == 0 ? -6 : 3 * rank - 6;
    const uint32_t pt = CH_PART + (w >> 1) * 4096 + (w & 1) * 256;
    const uint32_t barS = sb + CH_BAR, barM = barS + 8, zero = barS + 24;
    char* const ring0 = ring_base();
    const uint32_t m_rd = ring_off(24 + w, side), o_rd = ring_off(rank * 8 + w, side);
    uint32_t pub;
    if (PV) { int pos, cw = o_chunk(h * 8 + v0 + w, pos); pub = (ring_off(cw, 0) & ~4096u) + pos * 256; }
    else pub = (ring_off(24 + (h >> 2), 0) & ~4096u) + ((2 * h + w) & 7) * 256;
    char* const kvo = (char*)(PV ? g_vm + 128 * (v0 + w) : g_km + 64 * (u0 + w)) + h * 2048;
    const bool mown = !PV && w == rank && rank < 2;
    uint32_t lo16 = lane0 * 16;
    uint32_t sw[12][4];
#pragma unroll
    for (int i = 0; i < 12; i++) ldsm4t(sw[i], sb + lo16 + w * CH_WREG + i * 512);

#pragma unroll 1
    for (int s = 0;; s++) {
        const bool last = s == NSEG - 1;
        const uint32_t slot = (s & 3) << 14;
        lo16 += delay<DLM>(zero);
        const uint32_t lane = lo16 >> 4, l16 = sb + lo16, wl = l16 + w * CH_WREG, pw = l16 + CH_PART + w * 512;
        const uint32_t xs = l16 + CH_XS + nq * 512 + (w - nq) * 1024;
        const uint32_t eye = ((lo16 >> 7) == (lane & 3)) ? ((lo16 & 64) ? 0x3F800000u : 0x3F80u) : 0u;
        uint2 b[8];
        const char* pm = ring0 + (m_rd + slot + (lo16 >> 1));
        poll_issue<8>(b, pm, true);
        preload<0, ML, 12>(sw, wl, zero);
        if (FNC & 1) bar_arrive(14, 256);
        poll_check<8>(b, pm, delay<FNC & 1>(zero));
        if ((OB || (XB & 1)) && !last) bar_arrive(8, 256 + OB);
        if (PV && !last && w == 7) bar_arrive(13, 64);
        {
            float acc[6][4];
#pragma unroll
            for (int kk = 0; kk < 8; kk++) {
                const int j = (2 * kk) % 12;
                if (kk == 0) { mma16z(acc[5], sw[0], b[0].x, b[0].y); mma16z(acc[4], sw[1], b[0].x, b[0].y); }
                else { mma16(acc[5], sw[j], b[kk].x, b[kk].y); mma16(acc[4], sw[j + 1], b[kk].x, b[kk].y); }
#pragma unroll
                for (int i = 0; i < 4; i++) {
                    if (kk == 0) mma16z(acc[i], wa[i * 8], b[0].x, b[0].y);
                    else mma16(acc[i], wa[i * 8 + kk], b[kk].x, b[kk].y);
                    if (i < 2) ldsm4t(sw[j + i], wl + (12 + 2 * kk + i) * 512);
                }
            }
            st_part(pw + 4 * 2048, acc[4], acc[5]);
            st_part(pw, acc[0], acc[1]);
            st_part(pw + 2 * 2048, acc[2], acc[3]);
        }
        uint32_t kv0, kv1;
        const uint32_t lp = l16 + (lane >> 4) * 256, pl = lp + pt;
        if (!PV) {
            bar_sync(1, last ? 256 : 256 + OB);
            red_part<true>(kv1, kv0, pl, eye);
            sts64(l16 + CH_QK + (w >> 1) * 512 + (w & 1) * 8, __uint_as_float(kv1), __uint_as_float(kv0));
            if (!last) bar_arrive(2, nq * 32 + 64 + OB);
        } else {
            bar_sync(1, last ? 256 : 256 + OB);
        }
        {
            float va[4][4];
            const float z = __uint_as_float(delay<1>(zero));
#pragma unroll
            for (int i = 0; i < 4; i++) va[i][0] = va[i][1] = va[i][2] = va[i][3] = z;
#pragma unroll
            for (int kk = 0; kk < 8; kk++) {
                const int c = (PV ? VCH_P : VCH_C) == 4 ? kk & 1 : 0;
                if (kk < 2) { mma16(va[c], wa[32 + 2 * kk], b[kk].x, b[kk].y); mma16(va[2 + c], wa[33 + 2 * kk], b[kk].x, b[kk].y); }
                else { mma16(va[c], sw[(2 * kk) % 12], b[kk].x, b[kk].y); mma16(va[2 + c], sw[(2 * kk + 1) % 12], b[kk].x, b[kk].y); }
            }
            if ((PV ? VCH_P : VCH_C) == 4) {
#pragma unroll
                for (int j = 0; j < 4; j++) { va[0][j] += va[1][j]; va[2][j] += va[3][j]; }
            }
            st_part(pw + 6 * 2048, va[0], va[2]);
        }
        if (PV) {
            uint32_t vt0[4], vt1[4];
            ldsm4t(vt0, xs); ldsm4t(vt1, xs + 512);
            if (w >= 6 && !last) {
                uint32_t kx[3][4];
#pragma unroll
                for (int j = 0; j < 3; j++)
                    ldsm4(kx[j], sb + CH_XS + j * 1024 + (j == 2 && nq == 5 ? 0 : ((lane >> 3) & 1) * 512) + (w - 6) * 256 + (lane >> 4) * 128 + (lane & 7) * 16);
                const uint32_t da = l16 + CH_SX + rank * 1280 + (w - 6) * 512, dc = sb + CH_SX + rank * 1280 + 1024 + lane * 8;
                bar_sync(2, nq * 32 + 64 + OB);
                uint32_t qk[3][4];
#pragma unroll
                for (int j = 0; j < 3; j++) {
                    const float4 v = lds128(l16 + CH_QK + j * 512);
                    qk[j][0] = __float_as_uint(v.x); qk[j][1] = __float_as_uint(v.y); qk[j][2] = __float_as_uint(v.z); qk[j][3] = __float_as_uint(v.w);
                }
                float s0[4], s1[4], s2[4], s3[4];
                mma16z(s0, qk[0], kx[0][0], kx[0][1]); mma16z(s1, qk[0], kx[0][2], kx[0][3]);
                mma16z(s2, qk[1], kx[1][0], kx[1][1]); mma16z(s3, qk[1], kx[1][2], kx[1][3]);
                if (nq == 5) qk[2][2] = qk[2][3] = 0;
                mma16(s0, qk[2], kx[2][0], kx[2][1]); mma16(s1, qk[2], kx[2][2], kx[2][3]);
                float m0[4], m1[4];
                mma16z(m0, qk[0], qk[0][1], qk[0][3]); mma16z(m1, qk[1], qk[1][1], qk[1][3]);
                mma16(m0, qk[2], qk[2][1], qk[2][3]);
                const float4 sv = make_float4(s0[0] + s2[0], s0[1] + s2[1], s1[0] + s3[0], s1[1] + s3[1]);
                st_async4(mapa(da, rk1), sv, mapa(barS, rk1));
                st_async4(mapa(da, rk2), sv, mapa(barS, rk2));
                {
                    const float c0 = m0[0] + m1[0], c1 = m0[1] + m1[1];
                    const int dr = w == 6 ? rk1 : rk2;
                    st_async2(mapa(dc, dr), c0, c1, mapa(barS, dr));
                    sts64(dc, c0, c1);
                }
                const float t4[4] = {sv.x, sv.y, sv.z, sv.w};
                sts128(da, t4);
            }
            bar_sync(3, last ? 256 : 256 + OB);
            if (!last && w == 7) bar_arrive(12, 64);
            red_part<false>(kv0, kv1, pl, eye);
            if (last) {
                uint32_t* d = (uint32_t*)(kvo + (uint32_t)(s * (NH * 2048) + lane * 4));
                d[0] = movm(kv0); d[32] = movm(kv1);
                break;
            }
            {
                const uint32_t sx = l16 + CH_SX, r0 = rank * 1280, r1 = rk1 * 1280, r2 = rk2 * 1280;
                float4 a0 = lds128(sx + r0), b0 = lds128(sx + 512 + r0);
                const float2 c0 = lds64(sx + 1024 + r0 - lane * 8);
                preload<0, 0, PE>(sw, wl + 28 * 512, zero);
                mbar_wait(barS, s & 1);
                const float4 a1 = lds128(sx + r1), a2 = lds128(sx + r2), b1 = lds128(sx + 512 + r1), b2 = lds128(sx + 512 + r2);
                const float2 c1 = lds64(sx + 1024 + r1 - lane * 8), c2 = lds64(sx + 1024 + r2 - lane * 8);
                a0 = add4(add4(a0, a1), a2); b0 = add4(add4(b0, b1), b2);
                float sc[10] = {a0.x, a0.y, a0.z, a0.w, b0.x, b0.y, b0.z, b0.w, c0.x + c1.x + c2.x, c0.y + c1.y + c2.y};
                float mx = fmaxf(fmaxf(fmaxf(sc[0], sc[1]), fmaxf(sc[2], sc[3])), fmaxf(fmaxf(sc[4], sc[5]), fmaxf(sc[6], sc[7])));
                mx = fmaxf(mx, fmaxf(sc[8], sc[9]));
                mx = fmaxf(fmaxf(mx, __shfl_xor_sync(0xffffffffu, mx, 1)),
                           fmaxf(__shfl_xor_sync(0xffffffffu, mx, 2), __shfl_xor_sync(0xffffffffu, mx, 3)));
                const float cs = 0.08838834764831845f * 1.4426950408889634f;
                const float mb = -mx * cs;
#pragma unroll
                for (int j = 0; j < 10; j++) sc[j] = ex2(fmaf(sc[j], cs, mb));
                uint32_t pf[5];
#pragma unroll
                for (int j = 0; j < 5; j++) pf[j] = pack_bf16(sc[2 * j], sc[2 * j + 1]);
                float o0[4], o1[4], o2[4], o3[4], o4[4], o5[4];
                const uint32_t p0[4] = {pf[0], 0, pf[1], 0}, p1[4] = {pf[2], 0, pf[3], 0};
                mma16z(o0, p0, vt0[0], vt0[1]); mma16z(o1, p0, vt1[0], vt1[1]);
                mma16z(o2, p1, vt0[2], vt0[3]); mma16z(o3, p1, vt1[2], vt1[3]);
                mma8z(o4, pf[4], 0, kv0); mma8z(o5, pf[4], 0, kv1);
                float sum = (((sc[0] + sc[1]) + (sc[2] + sc[3])) + ((sc[4] + sc[5]) + (sc[6] + sc[7]))) + (sc[8] + sc[9]);
                sum = (sum + __shfl_xor_sync(0xffffffffu, sum, 1)) + (__shfl_xor_sync(0xffffffffu, sum, 2) + __shfl_xor_sync(0xffffffffu, sum, 3));
                float inv; asm("rcp.approx.ftz.f32 %0, %1;" : "=f"(inv) : "f"(sum));
                const uint32_t ox = pack_bf16((o0[0] + o2[0] + o4[0]) * inv, (o0[1] + o2[1] + o4[1]) * inv);
                const uint32_t oy = pack_bf16((o1[0] + o3[0] + o5[0]) * inv, (o1[1] + o3[1] + o5[1]) * inv);
                char* const pp = ring0 + (pub + slot + (lo16 >> 1));
                st_pub(pp, ox, oy); st_pub(pp + 4096, ox, oy);
                if (OB || (XB & 4)) bar_arrive(10, (8 - nq) * 32 + OB);
                preload<0, PE, PL>(sw, wl + 28 * 512, zero);
            }
            kv0 = movm(kv0); kv1 = movm(kv1);
        } else {
            *(uint32_t*)(kvo + (uint32_t)(s * (NH * 2048) + lane * 4)) = kv0;
            bar_sync(3, last ? 256 : 256 + OB);
            if (last) break;
            preload<1, 0, CL>(sw, wl + 28 * 512, zero);
        }
        uint2 c[11];
        bar_sync(4, 256 + OB);
        const char* po = ring0 + (o_rd + slot + (lo16 >> 1) + delay<DLO>(zero));
        poll_issue<11>(c, po, rank < 2);
        preload<0, PV ? PL : CL, 12>(sw, wl + 28 * 512, zero);
        if (PV) { uint32_t* d = (uint32_t*)(kvo + (uint32_t)(s * (NH * 2048) + lane * 4)); d[0] = kv0; d[32] = kv1; }
        if (FNC & 2) bar_arrive(15, 256);
        poll_check<11>(c, po, delay<(FNC >> 1)>(zero));
        if (OB || (XB & 2)) bar_arrive(9, 256 + OB);
        {
            float acc[4][4];
#pragma unroll
            for (int f = 0; f < 22; f++) {
                const int kk = f >> 1, a = f & 3;
                if (f < 4) mma16z(acc[a], sw[f % 12], c[kk].x, c[kk].y);
                else mma16(acc[a], sw[f % 12], c[kk].x, c[kk].y);
                if (f + 12 < 22) ldsm4t(sw[f % 12], wl + (28 + f + 12) * 512);
            }
#pragma unroll
            for (int i = 0; i < 2; i++) {
#pragma unroll
                for (int j = 0; j < 4; j++) acc[i][j] += acc[i + 2][j];
                sts128(l16 + CH_PART + i * 4096 + w * 512, acc[i]);
            }
        }
        if (!PV && w < 2) {
            bar_sync(5, 288 + OB);
            float4 v[8];
#pragma unroll
            for (int i = 0; i < 8; i++) v[i] = lds128(l16 + CH_PART + w * 4096 + i * 512);
            float4 r = add4(add4(add4(v[0], v[1]), add4(v[2], v[3])), add4(add4(v[4], v[5]), add4(v[6], v[7])));
            if (!mown) st_async4(mapa(l16 + CH_MX + rank * 512, w), r, mapa(barM, w));
            bar_arrive(7, 256 + OB);
            if (mown) {
                mbar_wait(barM, s & 1);
                float4 x = lds128(l16 + CH_MX + (rank ^ 1) * 512), y = lds128(l16 + CH_MX + 2 * 512);
                r = add4(add4(x, r), y);
                const uint32_t mx = movm(pack_bf16(r.x, r.y)), my = movm(pack_bf16(r.z, r.w));
                const uint32_t ns = (slot + 0x4000) & 0xC000;
                char* const pp = ring0 + (pub + ns + (lo16 >> 1));
                st_pub(pp, mx, my); st_pub(pp + 4096, mx, my);
            }
            preload<0, 0, ML>(sw, wl, zero);
        } else {
            bar_arrive(5, 288 + OB);
            bar_sync(7, 256 + OB);
            preload<MP, 0, ML>(sw, wl, zero);
        }
        bar_sync(6, 320 + OB);
    }
    bar_arrive(6, 288);
}

__device__ __forceinline__ void chain_pace(const uint32_t sb, const int lane, const int rank, const int aware) {
    const uint32_t zero = sb + CH_BAR + 24;
    if (lane == 0) {
        char* ring = ring_base();
        uint32_t* p0 = (uint32_t*)(ring + ring_off(blockIdx.x & 15, 0) + 3072 + (blockIdx.x >> 4) * 128);
        uint32_t* p1 = (uint32_t*)(ring + ring_off(blockIdx.x & 15, 1) + 3072 + (blockIdx.x >> 4) * 128);
        *p0 = 0; *p1 = 0;
        int b0 = 1 << 30, b1 = 1 << 30; uint32_t v = 0;
        for (int r = 0; r < 4 || (r < 256 && !mbar_test(sb + CH_BAR + 16, 0)); r++) {
            uint32_t t0 = clk(); v = atomicExch(p0 + (v == 500), r); uint32_t t1 = v == 777 ? clk() + 1 : clk(); b0 = min(b0, (int)(t1 - t0));
            t0 = clk(); v = atomicExch(p1 + (v == 500), r); t1 = v == 777 ? clk() + 1 : clk(); b1 = min(b1, (int)(t1 - t0));
            asm volatile("st.volatile.shared.u32 [%0], %1;" ::"r"(zero + 4), "r"(aware ? (b1 < b0) ^ (aware - 1) : 0) : "memory");
        }
    }
    __syncwarp();
#pragma unroll 1
    for (int s = 1; s < NSEG; s++) {
        bar_sync(5, 288 + OB);
        bar_arrive(6, 320 + OB + (rank == 2 ? delay<18>(zero) : 0));
    }
}
__device__ __forceinline__ char* reset_ptr(const int lane, const int rank, const int h) {
    const int nq = rank == 0 ? 6 : 5, v0 = rank == 0 ? -6 : 3 * rank - 6;
    int pos, cw = o_chunk(h * 8 + v0 + min(max(5 + (lane >> 3), nq), 7), pos);
    if (lane >= 24 && rank < 2) { cw = 24 + (h >> 2); pos = (2 * h + rank) & 7; }
    return ring_base() + ((ring_off(cw, 0) & ~4096u) + pos * 256 + (lane & 7) * 16);
}
__device__ __forceinline__ void chain_chores(const uint32_t sb, const int lane, const int rank, const int h, const bf16* __restrict__ mem0) {
    const int nq = rank == 0 ? 6 : 5, u0 = rank == 0 ? 0 : 1 + 5 * rank, v0 = rank == 0 ? -6 : 3 * rank - 6;
    const uint32_t barS = sb + CH_BAR, barM = barS + 8, barX = barS + 16;
    auto xload = [&](int s) {
        mbar_expect(barX, 8192 - nq * 512);
        bulk_load(sb + CH_XS, g_kx + (size_t)(s * NH + h) * 4096 + u0 * 256, nq * 512, barX);
        bulk_load(sb + CH_XS + nq * 512, g_vx + (size_t)(s * NH + h) * 4096 + (v0 + nq) * 512, (8 - nq) * 1024, barX);
    };
    char* const rb = reset_ptr(lane, rank, h);
    int* const kvf = g_kvf + blockIdx.x * 16;
    if (rank < 2) {
        const uint32_t* p = (const uint32_t*)(mem0 + (lane >> 2) * DM + 32 * h + 16 * rank + 2 * (lane & 3));
        char* d = ring_base() + ((ring_off(24 + (h >> 2), 0) & ~4096u) + ((2 * h + rank) & 7) * 256 + lane * 8);
        const uint32_t x = p[0] == SENT ? 0x7FFF7FFFu : p[0];
        st_pub(d, x, p[4]); st_pub(d + 4096, x, p[4]);
    }
    if (lane == 0) {
        if (!KVN) __nanosleep(18000);
        wait_ctr(kvf, KVN);
        asm volatile("fence.proxy.async.global;" ::: "memory");
        xload(0);
    }
#pragma unroll 1
    for (int s = 0; s < NSEG - 1; s++) {
        if (lane == 0) {
            mbar_expect(barS, 2 * 1280);
            if (rank < 2) mbar_expect(barM, 2 * 512);
        }
        bar_sync(13, 64);
#pragma unroll
        for (int i = 0; i < 4; i++)
            asm volatile("st.relaxed.gpu.global.v4.u32 [%0], {%1,%1,%1,%1};" ::"l"(rb + ((((s + 2) & 3) << 14) + (i >> 1) * 4096 + (i & 1) * 128)), "r"(SENT) : "memory");
        if (FEN || (s & 3) == 0) fence_gpu();
        if (lane == 0 && (s & 3) == 0 && s) atomicAdd(g_ctr + C_CHAIN + (s >> 2) - 1, 1);
        if (lane == 0 && (s & 3) == 3) { wait_ctr(kvf + (s >> 2) + 1, KVN); asm volatile("fence.proxy.async.global;" ::: "memory"); }
        __syncwarp();
        bar_sync(12, 64);
        if (lane == 0) xload(s + 1);
        mbar_wait(barX, (s + 1) & 1);
        bar_sync(6, 320 + OB);
    }
    bar_sync(6, 288);
    fence_gpu();
    if (lane == 0) atomicAdd(g_ctr + C_CHAIN + 15, 1);
}

struct S4Params { const bf16 *Are, *Aim, *Bre, *Bim, *Cre, *Cim, *ldt, *dsk; };
__device__ __forceinline__ float2 cmul(float2 a, float2 b) { return make_float2(a.x * b.x - a.y * b.y, a.x * b.y + a.y * b.x); }
__device__ __forceinline__ float2 csq(float2 a) { return make_float2(a.x * a.x - a.y * a.y, (a.x + a.x) * a.y); }
__device__ __forceinline__ float2 cexp_t(float lr, float turns) {
    float f = (turns - rintf(turns)) * 6.283185307179586f, e = ex2(lr);
    return make_float2(e * __cosf(f), e * __sinf(f));
}
__device__ __forceinline__ float bf_at(uint2 v, int i) {
    const uint32_t w = i < 2 ? v.x : v.y;
    return __uint_as_float((i & 1) ? w & 0xFFFF0000u : w << 16);
}
__device__ __forceinline__ void kg_step(uint32_t (&a)[4][4], uint32_t (&b)[5][2], uint32_t pa, uint32_t pe, float x0) {
#pragma unroll
    for (int i = 0; i < 2; i++) {
        const float4 p = lds128(pa + i * 64);
        const float2 e8 = lds64(pe + i * 32), c = make_float2(p.z, p.w);
        const float mag = ex2(p.x * x0), ph = p.y * x0;
        float2 e0 = make_float2(mag * __cosf(ph), mag * __sinf(ph)), e1 = cmul(e0, e8);
#pragma unroll
        for (int j = 0; j < 4; j++) {
            a[j][2 * i] = pack_bf16(e0.x, e0.y); a[j][2 * i + 1] = pack_bf16(e1.x, e1.y);
            e0 = csq(e0); e1 = csq(e1);
        }
        float2 m = cmul(c, e0);
        b[0][i] = pack_bf16(m.x, -m.y);
#pragma unroll
        for (int j = 0; j < 4; j++) {
            m = cmul(c, e1);
            b[j + 1][i] = pack_bf16(m.x, -m.y);
            if (j < 3) e1 = csq(e1);
        }
    }
}
__device__ __forceinline__ void kg_mma(float (&kd)[5][4], const uint32_t (&a)[4][4], const uint32_t (&b)[5][2]) {
    mma16(kd[0], a[0], b[0][0], b[0][1]);
#pragma unroll
    for (int j = 0; j < 4; j++) mma16(kd[j + 1], a[j], b[j + 1][0], b[j + 1][1]);
}
struct KgRaw { uint2 v[6]; float ldt; };
__device__ __forceinline__ void kg_load(KgRaw& r, const S4Params& P, int d, int lane) {
    const bf16* src[6] = {P.Are, P.Aim, P.Bre, P.Bim, P.Cre, P.Cim};
#pragma unroll
    for (int j = 0; j < 6; j++) r.v[j] = __ldg((const uint2*)(src[j] + d * 128) + lane);
    r.ldt = __bfloat162float(P.ldt[d]);
}
__device__ __forceinline__ float kg_params(const KgRaw& r, uint32_t stg, int lane) {
    const float dt = __bfloat162float(__float2bfloat16(expf(r.ldt)));
    float k2048 = 0.f;
#pragma unroll
    for (int i = 0; i < 4; i++) {
        const float br = dt * bf_at(r.v[2], i), bi = dt * bf_at(r.v[3], i), cr = bf_at(r.v[4], i), ci = bf_at(r.v[5], i);
        const float zr = dt * bf_at(r.v[0], i) * 1.4426950408889634f;
        float zt = dt * bf_at(r.v[1], i) * 0.15915494309189535f;
        zt -= rintf(zt);
        const float v[4] = {zr, zt * 6.283185307179586f, cr * br - ci * bi, cr * bi + ci * br};
        const float2 e8 = cexp_t(8.f * zr, 8.f * zt), el = cexp_t(2048.f * zr, 2048.f * zt);
        k2048 += v[2] * el.x - v[3] * el.y;
        sts128(stg + (i * 32 + lane) * 16, v);
        sts64(stg + 2048 + (i * 32 + lane) * 8, e8.x, e8.y);
    }
#pragma unroll
    for (int o = 16; o; o >>= 1) k2048 += __shfl_xor_sync(0xffffffffu, k2048, o);
    __syncwarp();
    return k2048;
}
__device__ __forceinline__ void kg_store(const float (&kd)[5][4], float k2048, uint32_t stg, int d, int lane) {
    __syncwarp();
    const uint32_t ta = stg + (lane & 7) * 32 + ((lane >> 3) & 1) * 16 + (lane >> 4) * 256;
    stsm4t(ta, pack_bf16(kd[0][0], kd[0][1]), pack_bf16(kd[0][2], kd[0][3]), pack_bf16(kd[1][0], kd[1][1]), pack_bf16(kd[1][2], kd[1][3]));
    stsm4t(ta + 512, pack_bf16(kd[2][0], kd[2][1]), pack_bf16(kd[2][2], kd[2][3]), pack_bf16(kd[3][0], kd[3][1]), pack_bf16(kd[3][2], kd[3][3]));
    stsm4t(ta + 1024, pack_bf16(kd[4][0], kd[4][1]), pack_bf16(kd[4][2], kd[4][3]), pack_bf16(k2048, 0.f), 0);
    __syncwarp();
#pragma unroll
    for (int j = 0; j < 3; j++) ((float4*)(g_kd + d * 768))[j * 32 + lane] = lds128(stg + j * 512 + lane * 16);
    __syncwarp();
}

__global__ void __cluster_dims__(3, 1, 1) __launch_bounds__(CH_THREADS, 1)
chain_kernel(const __grid_constant__ CUtensorMap mq, const __grid_constant__ CUtensorMap mk, const __grid_constant__ CUtensorMap mv,
             const __grid_constant__ CUtensorMap mo, const bf16* __restrict__ Wq, const bf16* __restrict__ Wk, const bf16* __restrict__ Wv,
             const bf16* __restrict__ mem0, const __grid_constant__ S4Params P, int aware) {
    extern __shared__ __align__(1024) unsigned char smem[];
    const uint32_t sb = smem_u32(smem);
    const int tid = threadIdx.x, lane = tid & 31;
    const int w = __shfl_sync(0xffffffffu, tid >> 5, 0);
    int rank; asm("mov.u32 %0, %%cluster_ctarank;" : "=r"(rank));
    const int h = blockIdx.x / 3;
    if (tid == 0) {
        mbar_init(sb + CH_BAR, 1); mbar_init(sb + CH_BAR + 8, 1); mbar_init(sb + CH_BAR + 16, 1);
        for (int i = 0; i < 16; i++) mbar_init(sb + CH_BAR + 64 + i * 8, 1);
        *(int*)(smem + CH_BAR + 24) = 0; *(int*)(smem + CH_BAR + 28) = 0; *(int*)(smem + CH_BAR + 32) = 0;
        asm volatile("fence.mbarrier_init.release.cluster;" ::: "memory");
    }
    if (w == 10 && PFKV) {
        const int e = lane * 96 + blockIdx.x;
        if (e < 2048) asm volatile("cp.async.bulk.prefetch.L2.global [%0], 8192;" ::"l"(((e & 1) ? Wv : Wk) + (size_t)(e >> 1) * HD) : "memory");
        if (PFKV > 1) __nanosleep(PFKV);
    }
    if (w == 9) {
        char* const rb = reset_ptr(lane, rank, h);
#pragma unroll
        for (int i = 0; i < 8; i++)
            asm volatile("st.relaxed.gpu.global.v4.u32 [%0], {%1,%1,%1,%1};" ::"l"(rb + (((i >> 2) << 14) + ((i >> 1) & 1) * 4096 + (i & 1) * 128)), "r"(SENT) : "memory");
        if (lane < 16) g_kvf[blockIdx.x * 16 + lane] = 0;
        if (blockIdx.x == 0)
            for (int k = lane; k < N_CTR; k += 32) g_ctr[k] = 0;
        fence_gpu();
        __syncwarp();
        asm volatile("griddepcontrol.launch_dependents;" ::: "memory");
    }
    __syncthreads();
    asm volatile("barrier.cluster.arrive.relaxed.aligned;" ::: "memory");

    if (w >= 8) {
        reg_dec<24>();
        asm volatile("barrier.cluster.wait.aligned;" ::: "memory");
        if (w == 8) chain_pace(sb, lane, rank, aware);
        else if (w == 9) {
            chain_chores(sb, lane, rank, h, mem0);
            asm volatile("st.volatile.shared.u32 [%0], %1;" ::"r"(sb + CH_BAR + 32), "r"(0x3F803F80) : "memory");
        } else if (w == 11 && KEEP) {
#pragma unroll 1
            for (int it = 0; it < (1 << 22); it++) {
                int d0, d1;
                const uint32_t x = delay<1>(sb + CH_BAR + 32);
                asm volatile("mma.sync.aligned.m8n8k16.row.col.s32.s8.s8.s32 {%0,%1}, {%2}, {%2}, {%3,%3};" : "=r"(d0), "=r"(d1) : "r"(x), "r"(0));
                if (d0 | d1) break;
                if ((XB & 8) && lane == 0) asm volatile("st.relaxed.gpu.global.u32 [%0], %1;" ::"l"(g_kd + DM * 768 + blockIdx.x * 64), "r"(it) : "memory");
                if ((XB & 16) && lane == 0) ld_acq((int*)(g_kd + DM * 768 + blockIdx.x * 64));
                __nanosleep(KEEP);
            }
        }
    } else {
        reg_inc<240>();
        const int nq = rank == 0 ? 6 : 5;
        const int u0 = rank == 0 ? 0 : 1 + 5 * rank;
        const int v0 = rank == 0 ? -6 : 3 * rank - 6;
        const int gw = rank * 8 + w;
        const int ks0 = gw < 16 ? 11 * gw : 176 + 10 * (gw - 16);
        const int nko = gw < 16 ? 11 : 10;
        const uint32_t wr = sb + w * CH_WREG, bar0 = sb + CH_BAR + 64 + w * 16, bar1 = bar0 + 8;
        uint32_t wa[36][4];
        const uint32_t vst = sb + CH_PART + w * 2048;
        const int cq = h * DH + 8 * u0, cv = h * DH + 16 * (v0 + 6);
        const int r8 = lane >> 2, p = lane & 3;
        const bf16* src = p >= 2 ? ((p & 1) ? Wk : Wq) + cq + 32 : rank == 0 ? ((p & 1) ? Wk : Wq) + cq + 40 : Wv + cv - 16 + 8 * p;
        src += (size_t)(128 * w + r8) * HD;
        auto cp_rows = [&](int kh) {
            cp16(wr + ((kh >> 1) * 2 + (p >> 1)) * 512 + ((kh & 1) * 2 + (p & 1)) * 128 + r8 * 16, src + (size_t)kh * 8 * HD);
        };
        {
            int d = blockIdx.x * 8 + w, t = 0;
            const int d1 = 768 + blockIdx.x * 3 + w, nt = (w < 3 && d1 < DM) ? 32 : 16;
            const uint32_t stg = wr + 4096;
            KgRaw raw, raw1;
            kg_load(raw, P, d, lane);
            kg_load(raw1, P, min(d1, DM - 1), lane);
            float kd[5][4], k2048;
#pragma unroll 1
            for (int i = -LDW; i < 9 || t < nt; i++) {
                if (i >= 0 && i < 9) {
                    const uint32_t bar = bar0 + (i & 1) * 8;
                    if (i >= 2) mbar_wait(bar, ((i >> 1) - 1) & 1);
                    if (lane == 0) {
                        mbar_expect(bar, 2048);
                        if (i < 8) tma2d(wr + 8192 + (i & 1) * 8192 + (i >> 1) * 2048, (i & 1) ? &mk : &mq, cq, 128 * w + 32 * (i >> 1), bar);
                        else tma2d(vst, &mv, cv, 128 * w, bar);
                    }
                    if (i < 8) cp_rows(i);
                }
#pragma unroll 1
                for (int e = min(t + KGS, nt); t < e; t++) {
                    if ((t & 15) == 0) {
                        k2048 = kg_params(raw, stg, lane);
#pragma unroll
                        for (int j = 0; j < 20; j++) kd[j >> 2][j & 3] = 0.f;
                    }
                    uint32_t ka[4][4], kb[5][2];
                    kg_step(ka, kb, stg + ((t & 15) * 8 + (lane & 3)) * 16, stg + 2048 + ((t & 15) * 8 + (lane & 3)) * 8, (float)(lane >> 2));
                    kg_mma(kd, ka, kb);
                    if ((t & 15) == 15) { kg_store(kd, k2048, stg, d, lane); raw = raw1; d = d1; }
                }
            }
        }
        const uint32_t lrow = ((lane >> 4) * 8 + (lane & 7)) * 64, lsw = (lane >> 1) & 3, lh = (lane >> 3) & 1;
        mbar_wait(bar1, 1); mbar_wait(bar0, 0);
#pragma unroll
        for (int i = 0; i < 32; i++) ldsm4t(wa[i], wr + 8192 + lh * 8192 + (i & 7) * 1024 + lrow + (((i >> 3) ^ lsw) << 4));
#pragma unroll
        for (int i = 0; i < 4; i++) ldsm4t(wa[32 + i], vst + (i >> 1) * 1024 + lrow + ((((i & 1) * 2 + lh) ^ lsw) << 4));
        asm volatile("fence.proxy.async.shared::cta;" ::"r"(wa[31][0]), "r"(wa[35][0]) : "memory");
        __syncwarp();
#pragma unroll 1
        for (int i = 9; i < 18; i++) {
            const uint32_t bar = bar0 + (i & 1) * 8;
            if (i >= 11) mbar_wait(bar, ((i >> 1) - 1) & 1);
            if (lane == 0) {
                const int j = 2 * (i - 12), nb = min(2, nko - j);
                mbar_expect(bar, i < 12 ? 2048 : nb * 1024);
                if (i < 12) tma2d(wr + 8192 + (i - 9) * 2048, &mv, cv, 128 * w + 32 * (i - 8), bar);
                else for (int e = 0; e < nb; e++) tma2d(wr + 14336 + (j + e) * 1024, &mo, 32 * h, 16 * (ks0 + j + e), bar);
            }
            if (i < 17) cp_rows(i - 1);
        }
        mbar_wait(bar0, 0); mbar_wait(bar1, 0);
#pragma unroll 1
        for (int i = 0; i < 17; i++) {
            uint32_t x[4], y[4];
            ldsm4t(x, wr + 8192 + i * 1024 + lrow + ((lh ^ lsw) << 4));
            ldsm4t(y, wr + 8192 + i * 1024 + lrow + (((2 + lh) ^ lsw) << 4));
            if (i == 16 && nko == 10) x[0] = x[1] = x[2] = x[3] = y[0] = y[1] = y[2] = y[3] = 0;
            __syncwarp();
            stsm4t(wr + 8192 + i * 1024 + lane * 16, x[0], x[1], x[2], x[3]);
            stsm4t(wr + 8192 + i * 1024 + 512 + lane * 16, y[0], y[1], y[2], y[3]);
        }
        asm volatile("cp.async.wait_all;" ::: "memory");
        asm volatile("barrier.cluster.wait.aligned;" ::: "memory");
        bar_sync(1, 256);
        mbar_wait_long(sb + CH_BAR + 16, 0);
        const int side = __shfl_sync(0xffffffffu, *(volatile int*)(smem + CH_BAR + 28), 0);
        if (w >= nq) chain_loop<true>(wa, sb, w, lane, rank, h, side);
        else chain_loop<false>(wa, sb, w, lane, rank, h, side);
    }
}

constexpr int G_STAGE = 49152, G_NST = 4;
constexpr int G_STG = G_NST * G_STAGE;
constexpr int G_BAR = G_STG + 32768;
constexpr int G_SMEM = G_BAR + 256 + 1024;

#define WLOG(e)
constexpr int IT_QA = 0, IT_O = 1, IT_S4 = 2, IT_END = 3, IT_KV = 4;
#define O_WIDE 11
#define TMP 1
#define ATT2 0
#define S4REL 4
#define KVS 8
#define STM 0
__device__ __forceinline__ void st_out(uint32_t* p, uint32_t v) {
    if (STM == 0) *p = v;
    else if (STM == 1) __stcs(p, v);
    else asm volatile("st.global.L1::no_allocate.u32 [%0], %1;" ::"l"(p), "r"(v) : "memory");
}
#define Q_N1 0
#define Q_S1 12
__device__ __forceinline__ int queue_item(int q) {
    if (q < 512) return (IT_KV << 16) | ((q >> 5) << 8) | (q & 31);
    q -= 512;
    if (q < 256) return (IT_QA << 16) | ((q >> 4) << 8) | (q & 15);
    q -= 256;
    if (q < Q_N1 * 8) return (IT_O << 16) | ((O_WIDE + (q >> 3)) << 8) | (q & 7);
    q -= Q_N1 * 8;
    if (q < Q_S1) return (IT_S4 << 16) | q;
    q -= Q_S1;
    if (q < (16 - O_WIDE - Q_N1) * 8) return (IT_O << 16) | ((O_WIDE + Q_N1 + (q >> 3)) << 8) | (q & 7);
    q -= (16 - O_WIDE - Q_N1) * 8;
    if (q < 128 - Q_S1) return (IT_S4 << 16) | (Q_S1 + q);
    return IT_END << 16;
}
__device__ __forceinline__ void tma2d_store(const CUtensorMap* m, uint32_t src, int c0, int c1) {
    asm volatile("cp.async.bulk.tensor.2d.global.shared::cta.bulk_group [%0, {%2, %3}], [%1];" ::"l"(m), "r"(src), "r"(c0), "r"(c1) : "memory");
}

__device__ __forceinline__ void wgmma_s64(float (&d)[32], uint32_t a0, uint32_t a1, uint32_t a2, uint32_t a3, uint64_t db, int acc) {
    asm volatile("{.reg .pred p; setp.ne.b32 p, %37, 0;\n"
        "wgmma.mma_async.sync.aligned.m64n64k16.f32.bf16.bf16 {"
        "%0,%1,%2,%3,%4,%5,%6,%7,%8,%9,%10,%11,%12,%13,%14,%15,"
        "%16,%17,%18,%19,%20,%21,%22,%23,%24,%25,%26,%27,%28,%29,%30,%31"
        "}, {%32,%33,%34,%35}, %36, p, 1, 1, 0;}"
        : "+f"(d[0]), "+f"(d[1]), "+f"(d[2]), "+f"(d[3]), "+f"(d[4]), "+f"(d[5]), "+f"(d[6]), "+f"(d[7]), "+f"(d[8]), "+f"(d[9]), "+f"(d[10]), "+f"(d[11]), "+f"(d[12]), "+f"(d[13]), "+f"(d[14]), "+f"(d[15]), "+f"(d[16]), "+f"(d[17]), "+f"(d[18]), "+f"(d[19]), "+f"(d[20]), "+f"(d[21]), "+f"(d[22]), "+f"(d[23]), "+f"(d[24]), "+f"(d[25]), "+f"(d[26]), "+f"(d[27]), "+f"(d[28]), "+f"(d[29]), "+f"(d[30]), "+f"(d[31])
        : "r"(a0), "r"(a1), "r"(a2), "r"(a3), "l"(db), "r"(acc));
}
__device__ __forceinline__ void wgmma_s16(float (&d)[8], uint32_t a0, uint32_t a1, uint32_t a2, uint32_t a3, uint64_t db, int acc) {
    asm volatile("{.reg .pred p; setp.ne.b32 p, %13, 0;\n"
        "wgmma.mma_async.sync.aligned.m64n16k16.f32.bf16.bf16 {"
        "%0,%1,%2,%3,%4,%5,%6,%7"
        "}, {%8,%9,%10,%11}, %12, p, 1, 1, 0;}"
        : "+f"(d[0]), "+f"(d[1]), "+f"(d[2]), "+f"(d[3]), "+f"(d[4]), "+f"(d[5]), "+f"(d[6]), "+f"(d[7])
        : "r"(a0), "r"(a1), "r"(a2), "r"(a3), "l"(db), "r"(acc));
}
__device__ __forceinline__ void wgmma_v128(float (&d)[64], uint32_t a0, uint32_t a1, uint32_t a2, uint32_t a3, uint64_t db, int acc) {
    asm volatile("{.reg .pred p; setp.ne.b32 p, %69, 0;\n"
        "wgmma.mma_async.sync.aligned.m64n128k16.f32.bf16.bf16 {"
        "%0,%1,%2,%3,%4,%5,%6,%7,%8,%9,%10,%11,%12,%13,%14,%15,"
        "%16,%17,%18,%19,%20,%21,%22,%23,%24,%25,%26,%27,%28,%29,%30,%31,"
        "%32,%33,%34,%35,%36,%37,%38,%39,%40,%41,%42,%43,%44,%45,%46,%47,"
        "%48,%49,%50,%51,%52,%53,%54,%55,%56,%57,%58,%59,%60,%61,%62,%63"
        "}, {%64,%65,%66,%67}, %68, p, 1, 1, 1;}"
        : "+f"(d[0]), "+f"(d[1]), "+f"(d[2]), "+f"(d[3]), "+f"(d[4]), "+f"(d[5]), "+f"(d[6]), "+f"(d[7]), "+f"(d[8]), "+f"(d[9]), "+f"(d[10]), "+f"(d[11]), "+f"(d[12]), "+f"(d[13]), "+f"(d[14]), "+f"(d[15]), "+f"(d[16]), "+f"(d[17]), "+f"(d[18]), "+f"(d[19]), "+f"(d[20]), "+f"(d[21]), "+f"(d[22]), "+f"(d[23]), "+f"(d[24]), "+f"(d[25]), "+f"(d[26]), "+f"(d[27]), "+f"(d[28]), "+f"(d[29]), "+f"(d[30]), "+f"(d[31]), "+f"(d[32]), "+f"(d[33]), "+f"(d[34]), "+f"(d[35]), "+f"(d[36]), "+f"(d[37]), "+f"(d[38]), "+f"(d[39]), "+f"(d[40]), "+f"(d[41]), "+f"(d[42]), "+f"(d[43]), "+f"(d[44]), "+f"(d[45]), "+f"(d[46]), "+f"(d[47]), "+f"(d[48]), "+f"(d[49]), "+f"(d[50]), "+f"(d[51]), "+f"(d[52]), "+f"(d[53]), "+f"(d[54]), "+f"(d[55]), "+f"(d[56]), "+f"(d[57]), "+f"(d[58]), "+f"(d[59]), "+f"(d[60]), "+f"(d[61]), "+f"(d[62]), "+f"(d[63])
        : "r"(a0), "r"(a1), "r"(a2), "r"(a3), "l"(db), "r"(acc));
}

__device__ __forceinline__ void attn_scores(float (&sx)[32], float (&sm)[8], const uint32_t (&q)[32], uint32_t sk) {
    const uint64_t dx = mkdesc(sk, 1024, 128, 0), dm = mkdesc(sk + 16384, 256, 128, 0);
    wg_fence();
#pragma unroll
    for (int ks = 0; ks < 8; ks++) {
        wgmma_s64(sx, q[4 * ks], q[4 * ks + 1], q[4 * ks + 2], q[4 * ks + 3], dx + ks * 128, ks);
        wgmma_s16(sm, q[4 * ks], q[4 * ks + 1], q[4 * ks + 2], q[4 * ks + 3], dm + ks * 32, ks);
    }
    wg_commit();
}
__device__ __forceinline__ void attn_softmax(uint32_t (&p)[20], const float (&sx)[32], const float (&sm)[8], int wi, int lane) {
    const bool sb = wi >= 2;
    const int r0 = (wi & 1) * 16 + (lane >> 2) - 2 * (lane & 3);
    float s[5][4];
#pragma unroll
    for (int j = 0; j < 4; j++) s[4][j] = sb ? sm[4 + j] : sm[j];
    float m0 = fmaxf(s[4][0], s[4][1]), m1 = fmaxf(s[4][2], s[4][3]);
#pragma unroll
    for (int j = 0; j < 4; j++) {
#pragma unroll
        for (int e = 0; e < 4; e++) s[j][e] = 8 * j + (e & 1) > r0 + 8 * (e >> 1) ? -INFINITY : sb ? sx[16 + 4 * j + e] : sx[4 * j + e];
        m0 = fmaxf(m0, fmaxf(s[j][0], s[j][1])); m1 = fmaxf(m1, fmaxf(s[j][2], s[j][3]));
    }
    m0 = fmaxf(m0, __shfl_xor_sync(0xffffffffu, m0, 1)); m1 = fmaxf(m1, __shfl_xor_sync(0xffffffffu, m1, 1));
    m0 = fmaxf(m0, __shfl_xor_sync(0xffffffffu, m0, 2)); m1 = fmaxf(m1, __shfl_xor_sync(0xffffffffu, m1, 2));
    const float cs = 0.08838834764831845f * 1.4426950408889634f;
    m0 *= -cs; m1 *= -cs;
    float l0 = 0, l1 = 0;
#pragma unroll
    for (int j = 0; j < 5; j++) {
        s[j][0] = ex2(fmaf(s[j][0], cs, m0)); s[j][1] = ex2(fmaf(s[j][1], cs, m0));
        s[j][2] = ex2(fmaf(s[j][2], cs, m1)); s[j][3] = ex2(fmaf(s[j][3], cs, m1));
        l0 += s[j][0] + s[j][1]; l1 += s[j][2] + s[j][3];
    }
    l0 += __shfl_xor_sync(0xffffffffu, l0, 1); l1 += __shfl_xor_sync(0xffffffffu, l1, 1);
    l0 += __shfl_xor_sync(0xffffffffu, l0, 2); l1 += __shfl_xor_sync(0xffffffffu, l1, 2);
    asm("rcp.approx.ftz.f32 %0, %0;" : "+f"(l0)); asm("rcp.approx.ftz.f32 %0, %0;" : "+f"(l1));
    const uint32_t ma = sb ? 0u : ~0u;
#pragma unroll
    for (int j = 0; j < 5; j++) {
        const uint32_t x = pack_bf16(s[j][0] * l0, s[j][1] * l0), y = pack_bf16(s[j][2] * l1, s[j][3] * l1);
        const int ia = j < 4 ? 2 * j : 16, ib = j < 4 ? 8 + 2 * j : 18;
        asm volatile("and.b32 %0, %4, %6; and.b32 %1, %5, %6; and.b32 %2, %4, %7; and.b32 %3, %5, %7;"
            : "=&r"(p[ia]), "=&r"(p[ia + 1]), "=&r"(p[ib]), "=&r"(p[ib + 1]) : "r"(x), "r"(y), "r"(ma), "r"(~ma));
    }
}
__device__ __forceinline__ void attn_pv(float (&o)[64], const uint32_t (&p)[20], uint32_t sv) {
    const uint64_t dx = mkdesc(sv, 128, 1024, 0), dm = mkdesc(sv + 16384, 128, 256, 0);
    wg_fence();
#pragma unroll
    for (int ks = 0; ks < 5; ks++) wgmma_v128(o, p[4 * ks], p[4 * ks + 1], p[4 * ks + 2], p[4 * ks + 3], ks < 4 ? dx + ks * 16 : dm, ks);
    wg_commit();
}
__device__ __forceinline__ void attn_stage(const float (&o)[64], uint32_t dst) {
#pragma unroll
    for (int u = 0; u < 16; u += 2)
        stsm4(dst + (u >> 3) * 8192 + (u & 7) * 128, pack_bf16(o[4 * u], o[4 * u + 1]), pack_bf16(o[4 * u + 2], o[4 * u + 3]),
              pack_bf16(o[4 * u + 4], o[4 * u + 5]), pack_bf16(o[4 * u + 6], o[4 * u + 7]));
}

template <int BN, int NKB, bool BLOCKED_A>
__device__ __forceinline__ void mainloop(float (&acc)[BN / 2], uint32_t sb, int wgi, uint32_t full, uint32_t empty, int& it, bool elect) {
#pragma unroll
    for (int j = 0; j < BN / 2; j++) acc[j] = 0.f;
#pragma unroll 1
    for (int k4 = 0; k4 < NKB; k4 += 4) {
#pragma unroll
        for (int st = 0; st < 4; st++, it++) {
            mbar_wait_long(full + 8 * st, (it >> 2) & 1);
            const uint64_t da = BLOCKED_A ? mkdesc(sb + st * G_STAGE + wgi * 8192, 128, 1024, 0) : mkdesc(sb + st * G_STAGE + wgi * 8192, 16, 1024, 1);
            const uint64_t db = mkdesc(sb + st * G_STAGE + 16384, 8192, 1024, 1);
            wg_fence();
#pragma unroll
            for (int k = 0; k < 4; k++) {
                if constexpr (BN == 256) wgmma256(acc, da + k * (BLOCKED_A ? 16 : 2), db + k * 128, 1);
                else wgmma128(acc, da + k * (BLOCKED_A ? 16 : 2), db + k * 128, 1);
            }
            wg_commit();
            if (k4 | st) {
                wg_wait<1>();
                if (elect) mbar_arrive(empty + 8 * ((st + 3) & 3));
            }
        }
    }
    wg_wait<0>();
    if (elect) mbar_arrive(empty + 8 * 3);
}

__device__ __forceinline__ uint32_t n6_a(int st) { return st < 4 ? st * G_STAGE : (2 * st - 8) * G_STAGE + 32768; }
__device__ __forceinline__ uint32_t n6_b(int st) { return st < 4 ? st * G_STAGE + 16384 : (2 * st - 7) * G_STAGE + 32768; }
__device__ __forceinline__ uint32_t n6_bar(int st) { return st < 4 ? 8 * st : 96 + 8 * st; }
__device__ __forceinline__ void mainloop6(float (&acc)[64], uint32_t sb, int wgi, uint32_t full, uint32_t empty, int& it, bool elect) {
#pragma unroll
    for (int j = 0; j < 64; j++) acc[j] = 0.f;
    int st = 0, prev = 0, r = 0;
#pragma unroll 1
    for (int kb = 0; kb < 64; kb++) {
        mbar_wait_long(full + n6_bar(st), ((st < 4 ? it >> 2 : 0) + r) & 1);
        const uint64_t da = mkdesc(sb + n6_a(st) + wgi * 8192, 128, 1024, 0), db = mkdesc(sb + n6_b(st), 8192, 1024, 1);
        wg_fence();
#pragma unroll
        for (int k = 0; k < 4; k++) wgmma128(acc, da + k * 16, db + k * 128, 1);
        wg_commit();
        if (kb) {
            wg_wait<1>();
            if (elect) mbar_arrive(empty + n6_bar(prev));
        }
        prev = st;
        if (++st == 6) { st = 0; r++; }
    }
    wg_wait<0>();
    if (elect) mbar_arrive(empty + 8 * 3);
    it += 44;
}

template <int BN>
__device__ __forceinline__ void o_item(uint32_t sb, int wgi, int wi, int lane, uint32_t full, uint32_t empty, int& it, const CUtensorMap* mout,
                                       int row0, int col0, uint32_t stgpar) {
    float acc[BN / 2];
    if constexpr (BN == 256) mainloop<BN, 64, true>(acc, sb, wgi, full, empty, it, lane == 0);
    else mainloop6(acc, sb, wgi, full, empty, it, lane == 0);
    ST((row0 >> 4) + (col0 / BN), wgi * 4 + wi, 10);
    mbar_wait(full + 104, stgpar);
    const uint32_t stg = sb + G_STG + (wgi * 4 + wi) * 4096;
    const int r = lane & 15, cu = lane >> 4;
#pragma unroll
    for (int hf = 0; hf < BN / 128; hf++) {
        if (lane == 0) asm volatile("cp.async.bulk.wait_group.read 0;" ::: "memory");
        __syncwarp();
#pragma unroll
        for (int j = 0; j < 8; j++) {
            const float* a = acc + hf * 64 + j * 8;
            stsm4(stg + (j >> 2) * 2048 + r * 128 + ((((j & 3) * 2 + cu) ^ (r & 7)) << 4),
                  pack_bf16(a[0], a[1]), pack_bf16(a[2], a[3]), pack_bf16(a[4], a[5]), pack_bf16(a[6], a[7]));
        }
        asm volatile("fence.proxy.async.shared::cta;" ::: "memory");
        __syncwarp();
        if (lane == 0) {
            tma2d_store(mout, stg, col0 + hf * 128, row0 + wgi * 64 + wi * 16);
            tma2d_store(mout, stg + 2048, col0 + hf * 128 + 64, row0 + wgi * 64 + wi * 16);
            asm volatile("cp.async.bulk.commit_group;" ::: "memory");
        }
    }
}

constexpr int S4_KD = 32768;
constexpr int S4_CH = 2 * G_STAGE;
constexpr int S4_HALF = 2304;
constexpr int S4_WD = 2 * S4_HALF;
constexpr int S4_STRIDE = S4_WD + 2304 + 16;
__device__ __forceinline__ uint32_t addz(uint32_t x, uint32_t z) { uint32_t r; asm volatile("add.u32 %0, %1, %2;" : "=r"(r) : "r"(x), "r"(z)); return r; }
__device__ __forceinline__ uint32_t lds16(uint32_t a) { uint32_t v; asm volatile("ld.shared.u16 %0, [%1];" : "=r"(v) : "r"(a) : "memory"); return v; }
__device__ __forceinline__ uint32_t ldsu(uint32_t a) { return __float_as_uint(lds32(a)); }

template <int E0, int NE, int KP>
__device__ __forceinline__ void s4_windows(float (&acc)[8][2][4], uint32_t ut, uint32_t kd, int rho, int w, int lane, uint32_t z) {
    const int gt = (lane >> 2) - 2 * (lane & 3), p0 = rho == 16 ? -3 : -2, c = (lane >> 3) + p0;
    uint32_t band[2][4], tw[2 * NE + 1], ta[NE][4];
    {
        uint32_t f[5];
#pragma unroll
        for (int m = 0; m < 5; m++) {
            const int d = 8 * (p0 + m - 1) - gt + rho;
            f[m] = (abs(d) <= w ? 0x3F80u : 0u) | (abs(d + 1) <= w ? 0x3F800000u : 0u);
        }
#pragma unroll
        for (int j = 0; j < 2; j++) { band[j][0] = f[2 * j + 1]; band[j][1] = addz(f[2 * j], z); band[j][2] = f[2 * j + 2]; band[j][3] = addz(f[2 * j + 1], z); }
    }
#pragma unroll
    for (int m = 0; m < 2 * NE + 1; m++) {
        const int q = 8 * (2 * E0 - 1 + m) + gt;
        const uint32_t lo = lds16(kd + q * KP), hi = lds16(kd + (q - 1) * KP);
        tw[m] = ((unsigned)(q - 16 * E0) < 16 * E0 ? lo : 0u) | ((unsigned)(q - 1 - 16 * E0) < 16 * E0 ? hi << 16 : 0u);
    }
#pragma unroll
    for (int e = 0; e < NE; e++) { ta[e][0] = tw[2 * e + 1]; ta[e][1] = tw[2 * e + 2]; ta[e][2] = addz(tw[2 * e], z); ta[e][3] = addz(tw[2 * e + 1], z); }
    const uint32_t ua = ut + (c & 1) * S4_HALF + (16 + (lane & 7) + (c >> 1)) * 16;
#pragma unroll
    for (int J = 0; J < 8 - E0; J++) {
        uint32_t u0[4], u1[4];
        ldsm4(u0, ua + J * 256); ldsm4(u1, ua + J * 256 + 128);
        float s0[4], s1[4];
        mma16z(s0, band[0], u0[0], u0[1]); mma16z(s1, band[0], u1[0], u1[1]);
        mma16(s0, band[1], u0[2], u0[3]); mma16(s1, band[1], u1[2], u1[3]);
        const uint32_t b00 = pack_bf16(s0[0], s0[1]), b01 = pack_bf16(s1[0], s1[1]), b10 = pack_bf16(s0[2], s0[3]), b11 = pack_bf16(s1[2], s1[3]);
#pragma unroll
        for (int e = 0; e < NE; e++)
            if (J + E0 + e < 8) { mma16(acc[J + E0 + e][0], ta[e], b00, b01); mma16(acc[J + E0 + e][1], ta[e], b10, b11); }
    }
}
template <int D0, int D1>
__device__ __forceinline__ void s4_dense(float (&acc)[8][2][4], uint32_t ua, const uint32_t (&b0)[4], const uint32_t (&b1)[4]) {
#pragma unroll
    for (int J = 0; J < 8 - D0; J++) {
        uint32_t a[4];
        ldsm4(a, ua + J * 256);
        mma16(acc[J + D0][0], a, b0[0], b0[1]); mma16(acc[J + D0][1], a, b0[2], b0[3]);
        if (J + D1 < 8) { mma16(acc[J + D1][0], a, b1[0], b1[1]); mma16(acc[J + D1][1], a, b1[2], b1[3]); }
    }
}
__device__ __forceinline__ void s4_words(uint32_t (&b)[4], uint32_t wd) {
    asm volatile("ld.shared.u32 %0, [%4]; ld.shared.u32 %1, [%4+-32]; ld.shared.u32 %2, [%4+32]; ld.volatile.shared.u32 %3, [%4];"
        : "=r"(b[0]), "=r"(b[1]), "=r"(b[2]), "=r"(b[3]) : "r"(wd) : "memory");
}

__device__ __forceinline__ void s4_item(uint32_t sb, int cw, int lane, int item, const bf16* __restrict__ dsk, uint32_t empty, const CUtensorMap* my, uint32_t stgpar) {
    const int gt = (lane >> 2) - 2 * (lane & 3);
    const uint32_t ch = sb + S4_CH + cw * S4_STRIDE, kd = sb + S4_KD + cw * 1536;
    const __nv_bfloat162 dk = __bfloat162bfloat162(dsk[item * 8 + cw]);
    ST(item, cw, 0);
    asm volatile("st.shared.v4.u32 [%0], {%1,%1,%1,%1};" ::"r"(ch + (lane >> 4) * S4_HALF + (lane & 15) * 16), "r"(0) : "memory");
    const uint32_t tch = sb + S4_CH + (lane & 7) * S4_STRIDE + ((lane >> 3) & 1) * S4_HALF + (16 + 16 * cw + (lane >> 4)) * 16;
#pragma unroll
    for (int i = 0; i < 8; i++) {
        uint32_t x[4];
        ldsm4t(x, sb + cw * 4096 + i * 512 + lane * 16);
        stsm4(tch + i * 32, x[0], x[1], x[2], x[3]);
    }
#pragma unroll 3
    for (int x0 = lane * 2 - 16; x0 < 560; x0 += 64) {
        uint32_t k[3];
#pragma unroll
        for (int j = 0; j < 3; j++) {
            const int x = x0 + j - 1, idx = x < 256 ? max(x, 0) : min(128 + ((x + ((x >> 1) & 1)) >> 1), 384);
            k[j] = lds16(kd + idx * 2);
            if ((unsigned)x > 514u) k[j] = 0;
        }
        asm volatile("st.shared.v2.u32 [%0], {%1,%2};" ::"r"(ch + S4_WD + 64 + x0 * 4), "r"(k[1] | (k[0] << 16)), "r"(k[2] | (k[1] << 16)) : "memory");
    }
    const uint32_t k1024 = lds16(kd + 1024);
    bar_sync(2, 256);
    ST(item, cw, 1);
    const uint32_t z = ldsu(ch);
    float acc[8][2][4];
#pragma unroll
    for (int j = 0; j < 16; j++) acc[j >> 1][j & 1][0] = acc[j >> 1][j & 1][1] = acc[j >> 1][j & 1][2] = acc[j >> 1][j & 1][3] = 0.f;
#pragma unroll 1
    for (int r = 1; r <= 4; r++) s4_windows<2, 3, 8>(acc, ch, kd + 512 + 2 * r, 4 * r, 2 - (r & 1), lane, z);
    ST(item, cw, 2);
#pragma unroll 1
    for (int r = 1; r <= 2; r++) s4_windows<4, 4, 4>(acc, ch, kd + 768 + 2 * r, 8 * r, 2 + r, lane, z);
    ST(item, cw, 3);
    const uint32_t ua = ch + (lane >> 4) * S4_HALF + (16 + (lane & 15)) * 16, wd = ch + S4_WD + 64 + gt * 4;
#pragma unroll 1
    for (int q = 0; q < 2; q++) {
        uint32_t b0[4], b1[4];
        s4_words(b0, wd + (q + 32) * 64);
#pragma unroll
        for (int j = 0; j < 4; j++) {
            const int x = 16 * q + gt + (j == 1 ? -8 : j == 2 ? 8 : 0) - 3;
            b1[j] = addz(((unsigned)x < 2u ? k1024 : 0u) | ((unsigned)(x - 1) < 2u ? k1024 << 16 : 0u), z);
        }
        s4_dense<2, 4>(acc, ua - q * 16, b0, b1);
    }
    {
        uint32_t b0[4], b1[4], c0[4], c1[4];
        s4_words(b0, wd); s4_words(b1, wd + 1024);
#pragma unroll 1
        for (int q = 0; q < 16; q += 2) {
            s4_words(c0, wd + q * 64 + 64); s4_words(c1, wd + q * 64 + 64 + 1024);
            s4_dense<0, 1>(acc, ua - q * 16, b0, b1);
            s4_words(b0, wd + q * 64 + 128); s4_words(b1, wd + q * 64 + 128 + 1024);
            s4_dense<0, 1>(acc, ua - q * 16 - 16, c0, c1);
            if (q == S4REL && lane == 0) { mbar_arrive(empty); mbar_arrive(empty + 8); }
        }
    }
    ST(item, cw, 4);
    mbar_wait(empty + 72, stgpar);
    if (lane == 0) asm volatile("cp.async.bulk.wait_group.read 0;" ::: "memory");
    __syncwarp();
#pragma unroll
    for (int I = 0; I < 8; I++) {
        uint32_t u[4];
        ldsm4(u, ua + I * 256);
#pragma unroll
        for (int j = 0; j < 4; j++) {
            const uint32_t y = pack_bf16(acc[I][j >> 1][2 * (j & 1)], acc[I][j >> 1][2 * (j & 1) + 1]);
            const __nv_bfloat162 r = __hadd2_rn(*(const __nv_bfloat162*)&y, __hmul2_rn(*(const __nv_bfloat162*)&u[j], dk));
            u[j] = *(const uint32_t*)&r;
        }
        stsm4(ua + I * 256, u[0], u[1], u[2], u[3]);
    }
    bar_sync(2, 256);
#pragma unroll
    for (int i = 0; i < 8; i++) {
        uint32_t y[4];
        ldsm4t(y, tch + i * 32);
        stsm4(sb + G_STG + cw * 4096 + i * 512 + lane * 16, y[0], y[1], y[2], y[3]);
    }
    asm volatile("fence.proxy.async.shared::cta;" ::: "memory");
    __syncwarp();
    if (lane == 0) {
        mbar_arrive(empty + 16); mbar_arrive(empty + 24);
        tma2d_store(my, sb + G_STG + cw * 4096, DM + item * 8, cw * 256);
        asm volatile("cp.async.bulk.commit_group;" ::: "memory");
    }
    ST(item, cw, 5);
}

__global__ void __launch_bounds__(384, 1)
worker_kernel(const __grid_constant__ CUtensorMap mx, const __grid_constant__ CUtensorMap mq, const __grid_constant__ CUtensorMap mk,
              const __grid_constant__ CUtensorMap mv, const __grid_constant__ CUtensorMap mo,
              const __grid_constant__ CUtensorMap mout, const __grid_constant__ CUtensorMap mu, const __grid_constant__ CUtensorMap my,
              const __grid_constant__ CUtensorMap mkx, const __grid_constant__ CUtensorMap mvx, const __grid_constant__ CUtensorMap mkm,
              const __grid_constant__ CUtensorMap mvm, const bf16* __restrict__ dsk) {
    extern __shared__ unsigned char smem_raw[];
    const uint32_t sb = (smem_u32(smem_raw) + 1023) & ~1023u;
    const uint32_t full = sb + G_BAR, empty = full + 32, ifull = full + 64, iempty = full + 80, islot = full + 96, stgbar = full + 104, sigbar = full + 112, sigslot = full + 120;
    const int tid = threadIdx.x, wg = tid >> 7, lane = tid & 31;
    if (TMP && tid >= 64 && tid < 76) {
        const CUtensorMap* maps[12] = {&mx, &mq, &mk, &mv, &mo, &mout, &mu, &my, &mkx, &mvx, &mkm, &mvm};
        const CUtensorMap* m = maps[0];
#pragma unroll
        for (int j = 1; j < 12; j++) if (tid - 64 == j) m = maps[j];
        asm volatile("prefetch.tensormap [%0];" ::"l"(m) : "memory");
    }
    int q0 = blockIdx.x;
    const int wide0 = q0 - ((int)gridDim.x - O_WIDE * 4);
    if (tid == 0) {
        if (q0 >= 32 && wide0 < 0) q0 = 32 + atomicAdd(g_ctr + C_NEXT, 1);
        for (int i = 0; i < 6; i++) { mbar_init(full + n6_bar(i), 1); mbar_init(empty + n6_bar(i), 8); }
        for (int i = 0; i < 2; i++) { mbar_init(ifull + 8 * i, 1); mbar_init(iempty + 8 * i, 8); }
        mbar_init(sigbar, 8); mbar_init(stgbar, 1);
        asm volatile("fence.proxy.async.shared::cta;" ::: "memory");
    }
    __syncthreads();
    if (wg == 0) {
        reg_dec<40>();
        if (tid >= 32 && tid < 64) {
            for (int n = 0;; n++) {
                mbar_wait_long(sigbar, n & 1);
                int item; asm volatile("ld.shared.u32 %0, [%1];" : "=r"(item) : "r"(sigslot + 4 * (n & 1)) : "memory");
                const int type = item >> 16, b = (item >> 8) & 255, i = item & 255;
                if (type == IT_END) break;
                if (type == IT_QA) {
                    if (lane == 0) {
                        for (int j = 0; j < 8; j++) {
                            const uint32_t src = sb + (j >= 4 ? G_STG + (j & 1) * 16384 : 3 * G_STAGE + (j & 1) * 20480) + ((j >> 1) & 1) * 8192;
                            asm volatile("cp.async.bulk.global.shared::cta.bulk_group [%0], [%1], 8192;"
                                ::"l"(g_ox + (size_t)(b * 64 + i * 4 + ((j >> 1) ^ 2)) * 8192 + (j & 1) * 4096), "r"(src) : "memory");
                            if ((j & 3) == 3) asm volatile("cp.async.bulk.commit_group;" ::: "memory");
                        }
                        asm volatile("cp.async.bulk.wait_group.read 1;" ::: "memory");
                        asm volatile("mbarrier.arrive.shared.b64 _, [%0], 8;" ::"r"(empty + 24) : "memory");
                        asm volatile("cp.async.bulk.wait_group 0;" ::: "memory");
                        mbar_arrive(stgbar);
                        asm volatile("fence.proxy.async.global;" ::: "memory");
                    }
                    __syncwarp();
                }
                if (type == IT_KV) { if (lane < 6) red_release(g_kvf + ((i & 15) * 6 + lane) * 16 + b, 1); }
                else if (lane == 0) red_release(g_ctr + C_QA_DONE + b, 1 << i);
            }
        } else if (tid < 32) {
            int it = 0;
            if (!KVN) asm volatile("griddepcontrol.wait;" ::: "memory");
            for (int n = 0;; n++) {
                int item = 0;
                if (lane == 0) {
                    if (n) q0 = 32 + atomicAdd(g_ctr + C_NEXT, 1);
                    item = n == 0 && wide0 >= 0 ? (IT_O << 16) | ((wide0 >> 2) << 8) | (wide0 & 3) : queue_item(q0);
                }
                item = __shfl_sync(0xffffffffu, item, 0);
                if (lane == 0) {
                    mbar_wait(iempty + 8 * (n & 1), ((n >> 1) & 1) ^ 1);
                    asm volatile("st.shared.u32 [%0], %1;" ::"r"(islot + 4 * (n & 1)), "r"(item) : "memory");
                    mbar_arrive(ifull + 8 * (n & 1));
                    const int type = item >> 16, b = (item >> 8) & 255, i = item & 255;
                    if (type == IT_QA || type == IT_KV) {
                        const CUtensorMap* mw = type == IT_QA ? &mq : i < 16 ? &mk : &mv;
                        bool ready = false;
                        for (int kb = 0; kb < 16; kb++, it++) {
                            const int st = it & 3;
                            mbar_wait(empty + 8 * st, ((it >> 2) & 1) ^ 1);
                            mbar_expect(full + 8 * st, G_STAGE);
                            const uint32_t a = sb + st * G_STAGE;
                            tma2d(a, &mx, kb * 64, b * 128, full + 8 * st);
                            tma3d(a + 16384, mw, 0, kb * 64, (i & 15) * 4, full + 8 * st);
                            tma3d(a + 32768, mw, 0, kb * 64, (i & 15) * 4 + 2, full + 8 * st);
                            if (type == IT_QA && kb == 3) ready = ld_acq(g_ctr + C_CHAIN + b) >= 96;
                            if (type == IT_QA && kb >= 3 && kb < 11) {
                                const size_t sh = (b * 4 + ((kb - 3) & 3)) * NH + i * 2;
                                asm volatile("cp.async.bulk.prefetch.L2.global [%0], 16384;" ::"l"((kb >= 7 ? g_vx : g_kx) + sh * 4096) : "memory");
                                if (ready) asm volatile("cp.async.bulk.prefetch.L2.global [%0], 4096;" ::"l"((kb >= 7 ? g_vm : g_km) + sh * 1024) : "memory");
                            }
                        }
                    }
                    if (type == IT_QA) {
                        wait_ctr(g_ctr + C_CHAIN + b, 96);
                        asm volatile("fence.proxy.async.global;" ::: "memory");
                        for (int st = 0; st < 4; st++, it++) {
                            mbar_wait(empty + 8 * st, ((it >> 2) & 1) ^ 1);
                            mbar_expect(full + 8 * st, 4 * 10240);
                            for (int g2 = 0; g2 < 2; g2++) {
                                tma3d(sb + st * G_STAGE + g2 * 20480, st < 2 ? &mkx : &mvx, 0, b * 4 + g2 * 2, (i * 2 + (st & 1)) * 16, full + 8 * st);
                                tma3d(sb + st * G_STAGE + g2 * 20480 + 16384, st < 2 ? &mkm : &mvm, 0, b * 4 + g2 * 2, (i * 2 + (st & 1)) * 16, full + 8 * st);
                            }
                        }
                    } else if (type == IT_O) {
                        const bool wide = b < O_WIDE;
                        int done = 0;
                        const int ns = wide ? 4 : 6;
                        for (int kb = 0, st = 0, r = 0; kb < 64; kb++) {
                            const uint32_t bo = n6_bar(st);
                            mbar_wait(empty + bo, (((st < 4 ? it >> 2 : 0) + r) & 1) ^ 1);
                            mbar_expect(full + bo, wide ? G_STAGE : 32768);
                            tma3d(sb + n6_b(st), &mo, 0, kb * 64, wide ? i * 4 : i * 2, full + bo);
                            if (wide) tma3d(sb + n6_b(st) + 16384, &mo, 0, kb * 64, i * 4 + 2, full + bo);
                            if (!(done >> (kb >> 2) & 1)) {
                                for (int sp = 0; sp < (1 << 20) && !((done = ld_acq(g_ctr + C_QA_DONE + b)) >> (kb >> 2) & 1); sp++) __nanosleep(64);
                                asm volatile("fence.proxy.async.global;" ::: "memory");
                            }
                            bulk_load(sb + n6_a(st), g_ox + (size_t)(b * 64 + kb) * 8192, 16384, full + bo);
                            if (++st == ns) { st = 0; r++; }
                        }
                        it += wide ? 64 : 44;
                    } else if (type == IT_S4) {
                        wait_ctr(g_ctr + C_CHAIN, 96);
                        asm volatile("fence.proxy.async.global;" ::: "memory");
                        mbar_wait(empty, ((it >> 2) & 1) ^ 1);
                        mbar_expect(full, 32768 + 12288);
                        bulk_load(sb + S4_KD, g_kd + i * 8 * 768, 12288, full);
                        for (int j = 0; j < 8; j++) tma2d(sb + j * 4096, &mu, i * 8, j * 256, full);
                        for (int st = 1; st < 4; st++) { mbar_wait(empty + 8 * st, ((it >> 2) & 1) ^ 1); mbar_arrive(full + 8 * st); }
                        it += 4;
                        mbar_wait_long(empty, ((it >> 2) & 1) ^ 1);
                    }
                }
                __syncwarp();
                if (item >> 16 == IT_END) break;
            }
            asm volatile("griddepcontrol.wait;" ::: "memory");
        }
    } else {
        reg_inc<232>();
        const int wu = __shfl_sync(0xffffffffu, tid >> 5, 0);
        const int wgi = (wu >> 2) - 1, wi = wu & 3;
        int it = 0, nqa = 0, nsig = 0, n = 0, item;
        auto next_item = [&]() {
            mbar_wait_long(ifull + 8 * (n & 1), (n >> 1) & 1);
            asm volatile("ld.shared.u32 %0, [%1];" : "=r"(item) : "r"(islot + 4 * (n & 1)) : "memory");
            __syncwarp();
            if (lane == 0) mbar_arrive(iempty + 8 * (n & 1));
        };
        auto signal = [&](int what) {
            if (tid == 128) asm volatile("st.shared.u32 [%0], %1;" ::"r"(sigslot + 4 * (nsig & 1)), "r"(what) : "memory");
            __syncwarp();
            if (lane == 0) mbar_arrive(sigbar);
            nsig++;
        };
        next_item();
        if (item >> 16 == IT_KV) {
            float acc[128];
            uint32_t pk[64];
            uint32_t* dst = nullptr;
            int prev = 0;
            do {
                WLOG(0);
#pragma unroll
                for (int kb = 0; kb < 16; kb++, it++) {
                    const int st = kb & 3;
                    mbar_wait(full + 8 * st, (it >> 2) & 1);
                    const uint64_t da = mkdesc(sb + st * G_STAGE + wgi * 8192, 16, 1024, 1);
                    const uint64_t db = mkdesc(sb + st * G_STAGE + 16384, 8192, 1024, 1);
                    wg_fence();
#pragma unroll
                    for (int k = 0; k < 4; k++) wgmma256(acc, da + k * 2, db + k * 128, kb | k);
                    wg_commit();
                    if (kb < KVS && dst) {
#pragma unroll
                        for (int j = kb * (64 / KVS); j < (kb + 1) * (64 / KVS); j++) st_out(dst + (j >> 1) * 128 + (j & 1) * 32, pk[j]);
                        if (kb == KVS - 1) signal(prev);
                    }
                    if (kb > 0) {
                        wg_wait<1>();
                        if (lane == 0) mbar_arrive(empty + 8 * ((kb - 1) & 3));
                    }
                }
                wg_wait<0>();
                if (lane == 0) mbar_arrive(empty + 8 * 3);
#pragma unroll
                for (int j = 0; j < 64; j++) pk[j] = pack_bf16(acc[2 * j], acc[2 * j + 1]);
                const int row = ((item >> 8) & 255) * 128 + wgi * 64 + wi * 16, nt = item & 255;
                dst = (uint32_t*)(nt < 16 ? g_kx : g_vx) + (size_t)((row >> 5) * 512 + (nt & 15) * 32) * 128 + (row & 31) * 4 + lane;
                prev = item;
                if (n == 0) {
#pragma unroll
                    for (int j = 0; j < 64; j++) dst[(j >> 1) * 128 + (j & 1) * 32] = pk[j];
                    signal(prev);
                    dst = nullptr;
                }
                WLOG(1);
                n++;
                next_item();
            } while (item >> 16 == IT_KV);
            if (dst) {
#pragma unroll
                for (int j = 0; j < 64; j++) dst[(j >> 1) * 128 + (j & 1) * 32] = pk[j];
                signal(prev);
            }
        }
        for (;; n++, next_item()) {
            const int type = item >> 16, b = (item >> 8) & 255, i = item & 255;
            const int lane = (tid & 31) + (item >> 24), wgi = (wu >> 2) - 1 + __shfl_sync(0xffffffffu, item >> 24, 0), wi = wu & 3;
            WLOG(0);
            if (type == IT_QA) {
                float acc[128];
                ST(sid, cw, 0);
                ST(sid, cw, 1);
                mainloop<256, 16, false>(acc, sb, wgi, full, empty, it, lane == 0);
                ST(sid, cw, 2);
                uint32_t q0[32], q1[32];
#pragma unroll
                for (int j = 0; j < 32; j++) { q0[j] = pack_bf16(acc[2 * j], acc[2 * j + 1]); q1[j] = pack_bf16(acc[64 + 2 * j], acc[65 + 2 * j]); }
                const uint32_t par = (it >> 2) & 1, so = sb + wgi * 20480;
                float sx0[32] = {}, sm0[8] = {}, sx1[32] = {}, sm1[8] = {};
                uint32_t p0[20], p1[20];
                if (lane == 0) asm volatile("cp.async.bulk.wait_group.read 0;" ::: "memory");
                mbar_wait(stgbar, (nqa++ & 1) ^ 1);
                bar_sync(3 + wgi, 128);
                mbar_wait_long(full, par);
                ST(sid, cw, 3);
                attn_scores(sx0, sm0, q0, so);
                ST(sid, cw, 7);
                mbar_wait(full + 8, par);
                attn_scores(sx1, sm1, q1, so + G_STAGE);
                float o0[64] = {}, o1[64] = {};
                if (ATT2) {
                    ST(sid, cw, 8);
                    wg_wait<0>();
                    ST(sid, cw, 9);
                    if (lane == 0) { mbar_arrive(empty); mbar_arrive(empty + 8); }
                    attn_softmax(p0, sx0, sm0, wi, lane);
                    attn_softmax(p1, sx1, sm1, wi, lane);
                    ST(sid, cw, 10);
                    mbar_wait(full + 16, par);
                    ST(sid, cw, 11);
                    attn_pv(o0, p0, so + 2 * G_STAGE);
                    ST(sid, cw, 4);
                } else {
                    wg_wait<1>();
                    if (lane == 0) mbar_arrive(empty);
                    attn_softmax(p0, sx0, sm0, wi, lane);
                    mbar_wait(full + 16, par);
                    attn_pv(o0, p0, so + 2 * G_STAGE);
                    wg_wait<1>();
                    if (lane == 0) mbar_arrive(empty + 8);
                    ST(sid, cw, 4);
                    attn_softmax(p1, sx1, sm1, wi, lane);
                }
                mbar_wait(full + 24, par);
                attn_pv(o1, p1, so + 3 * G_STAGE);
                wg_wait<1>();
                if (lane == 0) mbar_arrive(empty + 16);
                ST(sid, cw, 5);
                const uint32_t da = (wi * 2 + ((lane >> 3) & 1)) * 1024 + (lane >> 4) * 128 + (lane & 7) * 16;
                attn_stage(o0, sb + G_STG + wgi * 16384 + da);
                wg_wait<0>();
                bar_sync(3 + wgi, 128);
                attn_stage(o1, so + 3 * G_STAGE + da);
                asm volatile("fence.proxy.async.shared::cta;" ::: "memory");
                ST(sid, cw, 6);
                signal(item);
                it += 4;
            } else if (type == IT_O) {
                ST(b * 8 + i, wgi * 4 + wi, 8);
                mbar_wait_long(full, (it >> 2) & 1);
                ST(b * 8 + i, wgi * 4 + wi, 9);
                if (b < O_WIDE) o_item<256>(sb, wgi, wi, lane, full, empty, it, &mout, b * 128, i * 256, (nqa & 1) ^ 1);
                else o_item<128>(sb, wgi, wi, lane, full, empty, it, &mout, b * 128, i * 128, (nqa & 1) ^ 1);
            } else if (type == IT_S4) {
                mbar_wait_long(full, (it >> 2) & 1);
                mbar_wait(full + 24, (it >> 2) & 1);
                s4_item(sb, wgi * 4 + wi, lane, i, dsk, empty, &my, (nqa & 1) ^ 1);
                it += 4;
            } else break;
            WLOG(1);
        }
        bar_sync(2, 256);
        signal(item);
        if (lane == 0) asm volatile("cp.async.bulk.wait_group 0;" ::: "memory");
    }
}

typedef CUresult (*EncodeFn)(CUtensorMap*, CUtensorMapDataType, cuuint32_t, void*, const cuuint64_t*, const cuuint64_t*, const cuuint32_t*,
                             const cuuint32_t*, CUtensorMapInterleave, CUtensorMapSwizzle, CUtensorMapL2promotion, CUtensorMapFloatOOBfill);
static EncodeFn get_encode() {
    void* fn = nullptr; cudaDriverEntryPointQueryResult st;
    cudaGetDriverEntryPoint("cuTensorMapEncodeTiled", &fn, cudaEnableDefault, &st);
    return (EncodeFn)fn;
}
static void map_act(EncodeFn enc, CUtensorMap* m, const void* p, int rows, int cols, int boxr) {
    cuuint64_t dim[2] = {(cuuint64_t)cols, (cuuint64_t)rows}, str[1] = {(cuuint64_t)cols * 2};
    cuuint32_t box[2] = {64, (cuuint32_t)boxr}, es[2] = {1, 1};
    enc(m, CU_TENSOR_MAP_DATA_TYPE_BFLOAT16, 2, (void*)p, dim, str, box, es, CU_TENSOR_MAP_INTERLEAVE_NONE, CU_TENSOR_MAP_SWIZZLE_128B,
        CU_TENSOR_MAP_L2_PROMOTION_L2_128B, CU_TENSOR_MAP_FLOAT_OOB_FILL_NONE);
}
static void map_w(EncodeFn enc, CUtensorMap* m, const void* p, int k, int n) {
    cuuint64_t dim[3] = {64, (cuuint64_t)k, (cuuint64_t)n / 64}, str[2] = {(cuuint64_t)n * 2, 128};
    cuuint32_t box[3] = {64, 64, 2}, es[3] = {1, 1, 1};
    enc(m, CU_TENSOR_MAP_DATA_TYPE_BFLOAT16, 3, (void*)p, dim, str, box, es, CU_TENSOR_MAP_INTERLEAVE_NONE, CU_TENSOR_MAP_SWIZZLE_128B,
        CU_TENSOR_MAP_L2_PROMOTION_L2_256B, CU_TENSOR_MAP_FLOAT_OOB_FILL_NONE);
}

static void map_kv(EncodeFn enc, CUtensorMap* m, void* p, int n) {
    cuuint64_t dim[3] = {(cuuint64_t)n, NSEG, 512}, str[2] = {(cuuint64_t)n * 1024, (cuuint64_t)n * 2};
    cuuint32_t box[3] = {(cuuint32_t)n, 2, 16}, es[3] = {1, 1, 1};
    enc(m, CU_TENSOR_MAP_DATA_TYPE_BFLOAT16, 3, p, dim, str, box, es, CU_TENSOR_MAP_INTERLEAVE_NONE, CU_TENSOR_MAP_SWIZZLE_NONE,
        CU_TENSOR_MAP_L2_PROMOTION_NONE, CU_TENSOR_MAP_FLOAT_OOB_FILL_NONE);
}
static void map_box(EncodeFn enc, CUtensorMap* m, const void* p, int rows, int ld, int boxc, int boxr, CUtensorMapSwizzle sw,
                    CUtensorMapL2promotion promo = CU_TENSOR_MAP_L2_PROMOTION_NONE) {
    cuuint64_t dim[2] = {(cuuint64_t)ld, (cuuint64_t)rows}, str[1] = {(cuuint64_t)ld * 2};
    cuuint32_t box[2] = {(cuuint32_t)boxc, (cuuint32_t)boxr}, es[2] = {1, 1};
    enc(m, CU_TENSOR_MAP_DATA_TYPE_BFLOAT16, 2, (void*)p, dim, str, box, es, CU_TENSOR_MAP_INTERLEAVE_NONE, sw,
        promo, CU_TENSOR_MAP_FLOAT_OOB_FILL_NONE);
}

extern "C" void kernel_launch(void* const* d_in, const int* in_sizes, int n_in, void* d_out, int out_size) {
    const bf16* x = (const bf16*)d_in[0];
    const bf16* mem0 = (const bf16*)d_in[1];
    const bf16 *Wq = (const bf16*)d_in[2], *Wk = (const bf16*)d_in[3], *Wv = (const bf16*)d_in[4], *Wo = (const bf16*)d_in[5];
    static EncodeFn enc = nullptr;
    static int nsm = 0;
    static void* kv[4];
    if (!enc) {
        enc = get_encode();
        cudaGetSymbolAddress(&kv[0], g_kx); cudaGetSymbolAddress(&kv[1], g_vx); cudaGetSymbolAddress(&kv[2], g_km); cudaGetSymbolAddress(&kv[3], g_vm);
        cudaDeviceGetAttribute(&nsm, cudaDevAttrMultiProcessorCount, 0);
        cudaFuncSetAttribute(chain_kernel, cudaFuncAttributeMaxDynamicSharedMemorySize, CH_SMEM);
        cudaFuncSetAttribute(worker_kernel, cudaFuncAttributeMaxDynamicSharedMemorySize, G_SMEM);
    }
    CUtensorMap mx, mq, mk, mv, mo, mout, mu, my;
    map_act(enc, &mx, x, S_LEN, DM, 128);
    map_w(enc, &mq, Wq, DM, HD); map_w(enc, &mk, Wk, DM, HD); map_w(enc, &mv, Wv, DM, HD); map_w(enc, &mo, Wo, HD, DM);
    map_box(enc, &mout, d_out, S_LEN, 2 * DM, 64, 16, CU_TENSOR_MAP_SWIZZLE_128B);
    map_box(enc, &mu, d_in[7], S_LEN, DM, 8, 256, CU_TENSOR_MAP_SWIZZLE_NONE, (CUtensorMapL2promotion)PROMU);
    map_box(enc, &my, d_out, S_LEN, 2 * DM, 8, 256, CU_TENSOR_MAP_SWIZZLE_NONE);
    CUtensorMap mkx, mvx, mkm, mvm;
    map_kv(enc, &mkx, kv[0], 256); map_kv(enc, &mvx, kv[1], 256); map_kv(enc, &mkm, kv[2], 64); map_kv(enc, &mvm, kv[3], 64);
    CUtensorMap cq, ck, cv, co;
    map_box(enc, &cq, Wq, DM, HD, 32, 32, CU_TENSOR_MAP_SWIZZLE_64B, (CUtensorMapL2promotion)PROMO); map_box(enc, &ck, Wk, DM, HD, 32, 32, CU_TENSOR_MAP_SWIZZLE_64B, (CUtensorMapL2promotion)PROMO);
    map_box(enc, &cv, Wv, DM, HD, 32, 32, CU_TENSOR_MAP_SWIZZLE_64B, (CUtensorMapL2promotion)PROMO); map_box(enc, &co, Wo, HD, DM, 32, 16, CU_TENSOR_MAP_SWIZZLE_64B, (CUtensorMapL2promotion)PROMO);
    S4Params P = {(const bf16*)d_in[8], (const bf16*)d_in[9], (const bf16*)d_in[10], (const bf16*)d_in[11],
                  (const bf16*)d_in[12], (const bf16*)d_in[13], (const bf16*)d_in[14], (const bf16*)d_in[15]};
    int aware = 1;
    cudaLaunchAttribute at[1];
    at[0].id = cudaLaunchAttributeProgrammaticStreamSerialization;
    at[0].val.programmaticStreamSerializationAllowed = 1;
    cudaLaunchConfig_t cfg = {};
    cfg.stream = cudaStreamPerThread;
    cfg.gridDim = dim3(96); cfg.blockDim = dim3(CH_THREADS); cfg.dynamicSmemBytes = CH_SMEM;
    cudaLaunchKernelEx(&cfg, chain_kernel, cq, ck, cv, co, Wq, Wk, Wv, mem0, P, aware);
    cfg.attrs = at; cfg.numAttrs = 1;
    cfg.gridDim = dim3(nsm); cfg.blockDim = dim3(384); cfg.dynamicSmemBytes = G_SMEM;
    cudaLaunchKernelEx(&cfg, worker_kernel, mx, mq, mk, mv, mo, mout, mu, my, mkx, mvx, mkm, mvm, P.dsk);
}
```

```cpp
#include <cuda.h>
#include <cuda_runtime.h>
#include <cuda_bf16.h>
#include <stdint.h>
#include <stdio.h>
#include <string.h>

typedef __nv_bfloat16 bf16;

constexpr int S_LEN = 2048, DM = 1024, NH = 32, DH = 128, HD = 4096, NSEG = 64;
constexpr uint32_t SENT = 0xFFFFFFFFu;
constexpr int SPIN_LIMIT = 1 << 18;
#define REALL 0

__device__ __align__(1024) bf16 g_kx[S_LEN * HD];
__device__ __align__(1024) bf16 g_vx[S_LEN * HD];
__device__ __align__(1024) bf16 g_ox[S_LEN * HD];
__device__ __align__(1024) bf16 g_km[NSEG * NH * 8 * DH];
__device__ __align__(1024) bf16 g_vm[NSEG * NH * 8 * DH];
__device__ __align__(1024) bf16 g_kd[DM * 768 + 8192];
__device__ __align__(1024) char g_ring[2 << 20];
__device__ int g_kvf[96 * 16];
constexpr int C_NEXT = 0, C_CHAIN = 32, C_QA_DONE = 64, N_CTR = 96;
__device__ int g_ctr[N_CTR];

__device__ __forceinline__ uint32_t smem_u32(const void* p) { return (uint32_t)__cvta_generic_to_shared(p); }
__device__ __forceinline__ uint32_t clk() { uint32_t c; asm volatile("mov.u32 %0, %%clock;" : "=r"(c)::"memory"); return c; }
__device__ __forceinline__ uint32_t pack_bf16(float lo, float hi) {
    uint32_t r; asm("cvt.rn.bf16x2.f32 %0, %1, %2;" : "=r"(r) : "f"(hi), "f"(lo)); return r;
}
__device__ __forceinline__ uint32_t movm(uint32_t a) {
    uint32_t d; asm volatile("movmatrix.sync.aligned.m8n8.trans.b16 %0, %1;" : "=r"(d) : "r"(a)); return d;
}
__device__ __forceinline__ void mma16(float (&d)[4], const uint32_t (&a)[4], uint32_t b0, uint32_t b1) {
    asm volatile("mma.sync.aligned.m16n8k16.row.col.f32.bf16.bf16.f32 {%0,%1,%2,%3}, {%4,%5,%6,%7}, {%8,%9}, {%0,%1,%2,%3};"
        : "+f"(d[0]), "+f"(d[1]), "+f"(d[2]), "+f"(d[3]) : "r"(a[0]), "r"(a[1]), "r"(a[2]), "r"(a[3]), "r"(b0), "r"(b1));
}
__device__ __forceinline__ void mma16z(float (&d)[4], const uint32_t (&a)[4], uint32_t b0, uint32_t b1) {
    asm volatile("mma.sync.aligned.m16n8k16.row.col.f32.bf16.bf16.f32 {%0,%1,%2,%3}, {%4,%5,%6,%7}, {%8,%9}, {%10,%10,%10,%10};"
        : "=f"(d[0]), "=f"(d[1]), "=f"(d[2]), "=f"(d[3]) : "r"(a[0]), "r"(a[1]), "r"(a[2]), "r"(a[3]), "r"(b0), "r"(b1), "f"(0.f));
}
__device__ __forceinline__ void mma8z(float (&d)[4], uint32_t a0, uint32_t a1, uint32_t b0) {
    asm volatile("mma.sync.aligned.m16n8k8.row.col.f32.bf16.bf16.f32 {%0,%1,%2,%3}, {%4,%5}, {%6}, {%7,%7,%7,%7};"
        : "=f"(d[0]), "=f"(d[1]), "=f"(d[2]), "=f"(d[3]) : "r"(a0), "r"(a1), "r"(b0), "f"(0.f));
}
__device__ __forceinline__ void ldsm4t(uint32_t (&r)[4], uint32_t addr) {
    asm volatile("ldmatrix.sync.aligned.m8n8.x4.trans.shared.b16 {%0,%1,%2,%3}, [%4];"
        : "=r"(r[0]), "=r"(r[1]), "=r"(r[2]), "=r"(r[3]) : "r"(addr) : "memory");
}
__device__ __forceinline__ void ldsm4(uint32_t (&r)[4], uint32_t addr) {
    asm volatile("ldmatrix.sync.aligned.m8n8.x4.shared.b16 {%0,%1,%2,%3}, [%4];"
        : "=r"(r[0]), "=r"(r[1]), "=r"(r[2]), "=r"(r[3]) : "r"(addr) : "memory");
}
__device__ __forceinline__ float lds32(uint32_t a) {
    float v; asm volatile("ld.shared.f32 %0, [%1];" : "=f"(v) : "r"(a) : "memory"); return v;
}
__device__ __forceinline__ void st_async1(uint32_t dst, float v, uint32_t bar) {
    asm volatile("st.async.shared::cluster.mbarrier::complete_tx::bytes.f32 [%0], %1, [%2];" ::"r"(dst), "f"(v), "r"(bar) : "memory");
}
__device__ __forceinline__ void st_async2(uint32_t dst, float x, float y, uint32_t bar) {
    asm volatile("st.async.shared::cluster.mbarrier::complete_tx::bytes.v2.f32 [%0], {%1,%2}, [%3];" ::"r"(dst), "f"(x), "f"(y), "r"(bar) : "memory");
}
__device__ __forceinline__ void mma8(float (&d)[4], uint32_t a0, uint32_t a1, uint32_t b0) {
    asm volatile("mma.sync.aligned.m16n8k8.row.col.f32.bf16.bf16.f32 {%0,%1,%2,%3}, {%4,%5}, {%6}, {%0,%1,%2,%3};"
        : "+f"(d[0]), "+f"(d[1]), "+f"(d[2]), "+f"(d[3]) : "r"(a0), "r"(a1), "r"(b0));
}
__device__ __forceinline__ void cp16(uint32_t dst, const void* src) {
    asm volatile("cp.async.cg.shared.global [%0], [%1], 16;" ::"r"(dst), "l"(src) : "memory");
}
__device__ __forceinline__ void sts128(uint32_t a, const float (&v)[4]) {
    asm volatile("st.shared.v4.f32 [%0], {%1,%2,%3,%4};" ::"r"(a), "f"(v[0]), "f"(v[1]), "f"(v[2]), "f"(v[3]) : "memory");
}
__device__ __forceinline__ float4 lds128(uint32_t a) {
    float4 v; asm volatile("ld.shared.v4.f32 {%0,%1,%2,%3}, [%4];" : "=f"(v.x), "=f"(v.y), "=f"(v.z), "=f"(v.w) : "r"(a) : "memory"); return v;
}
__device__ __forceinline__ void sts64(uint32_t a, float x, float y) {
    asm volatile("st.shared.v2.f32 [%0], {%1,%2};" ::"r"(a), "f"(x), "f"(y) : "memory");
}
__device__ __forceinline__ float2 lds64(uint32_t a) {
    float2 v; asm volatile("ld.shared.v2.f32 {%0,%1}, [%2];" : "=f"(v.x), "=f"(v.y) : "r"(a) : "memory"); return v;
}
__device__ __forceinline__ void bar_sync(int id, int n) { asm volatile("bar.sync %0, %1;" ::"r"(id), "r"(n) : "memory"); }
__device__ __forceinline__ void bar_arrive(int id, int n) { asm volatile("bar.arrive %0, %1;" ::"r"(id), "r"(n) : "memory"); }
__device__ __forceinline__ uint32_t mapa(uint32_t a, uint32_t r) {
    uint32_t o; asm("mapa.shared::cluster.u32 %0, %1, %2;" : "=r"(o) : "r"(a), "r"(r)); return o;
}
__device__ __forceinline__ void st_async4(uint32_t dst, float4 v, uint32_t bar) {
    asm volatile("st.async.shared::cluster.mbarrier::complete_tx::bytes.v4.f32 [%0], {%1,%2,%3,%4}, [%5];"
        ::"r"(dst), "f"(v.x), "f"(v.y), "f"(v.z), "f"(v.w), "r"(bar) : "memory");
}
__device__ __forceinline__ void mbar_init(uint32_t bar, int n) { asm volatile("mbarrier.init.shared.b64 [%0], %1;" ::"r"(bar), "r"(n) : "memory"); }
__device__ __forceinline__ void mbar_expect(uint32_t bar, int bytes) {
    asm volatile("mbarrier.arrive.expect_tx.shared.b64 _, [%0], %1;" ::"r"(bar), "r"(bytes) : "memory");
}
__device__ __forceinline__ void bulk_load(uint32_t dst, const void* src, int bytes, uint32_t bar) {
    asm volatile("cp.async.bulk.shared::cluster.global.mbarrier::complete_tx::bytes [%0], [%1], %2, [%3];"
        ::"r"(dst), "l"(src), "r"(bytes), "r"(bar) : "memory");
}
__device__ __forceinline__ bool mbar_try(uint32_t bar, uint32_t par) {
    uint32_t ok;
    asm volatile("{.reg .pred p; mbarrier.try_wait.parity.shared::cta.b64 p, [%1], %2; selp.u32 %0, 1, 0, p;}"
        : "=r"(ok) : "r"(bar), "r"(par) : "memory");
    return ok;
}
__device__ __forceinline__ bool mbar_test(uint32_t bar, uint32_t par) {
    uint32_t ok;
    asm volatile("{.reg .pred p; mbarrier.test_wait.parity.shared::cta.b64 p, [%1], %2; selp.u32 %0, 1, 0, p;}"
        : "=r"(ok) : "r"(bar), "r"(par) : "memory");
    return ok;
}
__device__ __forceinline__ int ld_acq(const int* p) { int v; asm volatile("ld.acquire.gpu.global.s32 %0, [%1];" : "=r"(v) : "l"(p) : "memory"); return v; }
__device__ __forceinline__ void red_release(int* p, int v) { asm volatile("red.release.gpu.global.add.s32 [%0], %1;" ::"l"(p), "r"(v) : "memory"); }
__device__ __forceinline__ void fence_gpu() { asm volatile("fence.acq_rel.gpu;" ::: "memory"); }
__device__ __forceinline__ void wait_ctr(const int* p, int n) {
    for (int it = 0; it < (1 << 20) && ld_acq(p) < n; it++) __nanosleep(64);
}
__device__ __forceinline__ void mbar_wait(uint32_t bar, uint32_t par) {
    if (!mbar_try(bar, par))
        for (int it = 0; it < SPIN_LIMIT && !mbar_try(bar, par); it++) {}
}
__device__ __forceinline__ void mbar_wait_long(uint32_t bar, uint32_t par) {
    for (int it = 0; it < (1 << 24) && !mbar_try(bar, par); it++) {}
}
__device__ __forceinline__ float4 add4(float4 a, float4 b) { return make_float4(a.x + b.x, a.y + b.y, a.z + b.z, a.w + b.w); }
__device__ __forceinline__ float ex2(float x) { float y; asm("ex2.approx.ftz.f32 %0, %1;" : "=f"(y) : "f"(x)); return y; }

__device__ __forceinline__ void wgmma256(float (&d)[128], uint64_t da, uint64_t db, int acc) {
    asm volatile("{.reg .pred p; setp.ne.b32 p, %130, 0;\n"
        "wgmma.mma_async.sync.aligned.m64n256k16.f32.bf16.bf16 {"
        "%0,%1,%2,%3,%4,%5,%6,%7,%8,%9,%10,%11,%12,%13,%14,%15,"
        "%16,%17,%18,%19,%20,%21,%22,%23,%24,%25,%26,%27,%28,%29,%30,%31,"
        "%32,%33,%34,%35,%36,%37,%38,%39,%40,%41,%42,%43,%44,%45,%46,%47,"
        "%48,%49,%50,%51,%52,%53,%54,%55,%56,%57,%58,%59,%60,%61,%62,%63,"
        "%64,%65,%66,%67,%68,%69,%70,%71,%72,%73,%74,%75,%76,%77,%78,%79,"
        "%80,%81,%82,%83,%84,%85,%86,%87,%88,%89,%90,%91,%92,%93,%94,%95,"
        "%96,%97,%98,%99,%100,%101,%102,%103,%104,%105,%106,%107,%108,%109,%110,%111,"
        "%112,%113,%114,%115,%116,%117,%118,%119,%120,%121,%122,%123,%124,%125,%126,%127"
        "}, %128, %129, p, 1, 1, 0, 1;}"
        : "+f"(d[0]), "+f"(d[1]), "+f"(d[2]), "+f"(d[3]), "+f"(d[4]), "+f"(d[5]), "+f"(d[6]), "+f"(d[7]), "+f"(d[8]), "+f"(d[9]), "+f"(d[10]), "+f"(d[11]), "+f"(d[12]), "+f"(d[13]), "+f"(d[14]), "+f"(d[15]), "+f"(d[16]), "+f"(d[17]), "+f"(d[18]), "+f"(d[19]), "+f"(d[20]), "+f"(d[21]), "+f"(d[22]), "+f"(d[23]), "+f"(d[24]), "+f"(d[25]), "+f"(d[26]), "+f"(d[27]), "+f"(d[28]), "+f"(d[29]), "+f"(d[30]), "+f"(d[31]), "+f"(d[32]), "+f"(d[33]), "+f"(d[34]), "+f"(d[35]), "+f"(d[36]), "+f"(d[37]), "+f"(d[38]), "+f"(d[39]), "+f"(d[40]), "+f"(d[41]), "+f"(d[42]), "+f"(d[43]), "+f"(d[44]), "+f"(d[45]), "+f"(d[46]), "+f"(d[47]), "+f"(d[48]), "+f"(d[49]), "+f"(d[50]), "+f"(d[51]), "+f"(d[52]), "+f"(d[53]), "+f"(d[54]), "+f"(d[55]), "+f"(d[56]), "+f"(d[57]), "+f"(d[58]), "+f"(d[59]), "+f"(d[60]), "+f"(d[61]), "+f"(d[62]), "+f"(d[63]), "+f"(d[64]), "+f"(d[65]), "+f"(d[66]), "+f"(d[67]), "+f"(d[68]), "+f"(d[69]), "+f"(d[70]), "+f"(d[71]), "+f"(d[72]), "+f"(d[73]), "+f"(d[74]), "+f"(d[75]), "+f"(d[76]), "+f"(d[77]), "+f"(d[78]), "+f"(d[79]), "+f"(d[80]), "+f"(d[81]), "+f"(d[82]), "+f"(d[83]), "+f"(d[84]), "+f"(d[85]), "+f"(d[86]), "+f"(d[87]), "+f"(d[88]), "+f"(d[89]), "+f"(d[90]), "+f"(d[91]), "+f"(d[92]), "+f"(d[93]), "+f"(d[94]), "+f"(d[95]), "+f"(d[96]), "+f"(d[97]), "+f"(d[98]), "+f"(d[99]), "+f"(d[100]), "+f"(d[101]), "+f"(d[102]), "+f"(d[103]), "+f"(d[104]), "+f"(d[105]), "+f"(d[106]), "+f"(d[107]), "+f"(d[108]), "+f"(d[109]), "+f"(d[110]), "+f"(d[111]), "+f"(d[112]), "+f"(d[113]), "+f"(d[114]), "+f"(d[115]), "+f"(d[116]), "+f"(d[117]), "+f"(d[118]), "+f"(d[119]), "+f"(d[120]), "+f"(d[121]), "+f"(d[122]), "+f"(d[123]), "+f"(d[124]), "+f"(d[125]), "+f"(d[126]), "+f"(d[127])
        : "l"(da), "l"(db), "r"(acc));
}
__device__ __forceinline__ void wgmma128(float (&d)[64], uint64_t da, uint64_t db, int acc) {
    asm volatile("{.reg .pred p; setp.ne.b32 p, %66, 0;\n"
        "wgmma.mma_async.sync.aligned.m64n128k16.f32.bf16.bf16 {"
        "%0,%1,%2,%3,%4,%5,%6,%7,%8,%9,%10,%11,%12,%13,%14,%15,"
        "%16,%17,%18,%19,%20,%21,%22,%23,%24,%25,%26,%27,%28,%29,%30,%31,"
        "%32,%33,%34,%35,%36,%37,%38,%39,%40,%41,%42,%43,%44,%45,%46,%47,"
        "%48,%49,%50,%51,%52,%53,%54,%55,%56,%57,%58,%59,%60,%61,%62,%63"
        "}, %64, %65, p, 1, 1, 0, 1;}"
        : "+f"(d[0]), "+f"(d[1]), "+f"(d[2]), "+f"(d[3]), "+f"(d[4]), "+f"(d[5]), "+f"(d[6]), "+f"(d[7]), "+f"(d[8]), "+f"(d[9]), "+f"(d[10]), "+f"(d[11]), "+f"(d[12]), "+f"(d[13]), "+f"(d[14]), "+f"(d[15]), "+f"(d[16]), "+f"(d[17]), "+f"(d[18]), "+f"(d[19]), "+f"(d[20]), "+f"(d[21]), "+f"(d[22]), "+f"(d[23]), "+f"(d[24]), "+f"(d[25]), "+f"(d[26]), "+f"(d[27]), "+f"(d[28]), "+f"(d[29]), "+f"(d[30]), "+f"(d[31]), "+f"(d[32]), "+f"(d[33]), "+f"(d[34]), "+f"(d[35]), "+f"(d[36]), "+f"(d[37]), "+f"(d[38]), "+f"(d[39]), "+f"(d[40]), "+f"(d[41]), "+f"(d[42]), "+f"(d[43]), "+f"(d[44]), "+f"(d[45]), "+f"(d[46]), "+f"(d[47]), "+f"(d[48]), "+f"(d[49]), "+f"(d[50]), "+f"(d[51]), "+f"(d[52]), "+f"(d[53]), "+f"(d[54]), "+f"(d[55]), "+f"(d[56]), "+f"(d[57]), "+f"(d[58]), "+f"(d[59]), "+f"(d[60]), "+f"(d[61]), "+f"(d[62]), "+f"(d[63])
        : "l"(da), "l"(db), "r"(acc));
}
__device__ __forceinline__ void wg_fence() { asm volatile("wgmma.fence.sync.aligned;" ::: "memory"); }
__device__ __forceinline__ void wg_commit() { asm volatile("wgmma.commit_group.sync.aligned;" ::: "memory"); }
template <int N> __device__ __forceinline__ void wg_wait() { asm volatile("wgmma.wait_group.sync.aligned %0;" ::"n"(N) : "memory"); }
__device__ __forceinline__ uint64_t mkdesc(uint32_t addr, uint32_t lbo, uint32_t sbo, uint32_t sw) {
    return (uint64_t)((addr & 0x3FFFF) >> 4) | ((uint64_t)(lbo >> 4) << 16) | ((uint64_t)(sbo >> 4) << 32) | ((uint64_t)sw << 62);
}
__device__ __forceinline__ void tma2d(uint32_t dst, const CUtensorMap* m, int c0, int c1, uint32_t bar) {
    asm volatile("cp.async.bulk.tensor.2d.shared::cluster.global.mbarrier::complete_tx::bytes [%0], [%1, {%2, %3}], [%4];"
        ::"r"(dst), "l"(m), "r"(c0), "r"(c1), "r"(bar) : "memory");
}
__device__ __forceinline__ void tma3d(uint32_t dst, const CUtensorMap* m, int c0, int c1, int c2, uint32_t bar) {
    asm volatile("cp.async.bulk.tensor.3d.shared::cluster.global.mbarrier::complete_tx::bytes [%0], [%1, {%2, %3, %4}], [%5];"
        ::"r"(dst), "l"(m), "r"(c0), "r"(c1), "r"(c2), "r"(bar) : "memory");
}
__device__ __forceinline__ void tma3d_mc(uint32_t dst, const CUtensorMap* m, int c0, int c1, int c2, uint32_t bar, uint16_t mask) {
    asm volatile("cp.async.bulk.tensor.3d.shared::cluster.global.mbarrier::complete_tx::bytes.multicast::cluster [%0], [%1, {%2, %3, %4}], [%5], %6;"
        ::"r"(dst), "l"(m), "r"(c0), "r"(c1), "r"(c2), "r"(bar), "h"(mask) : "memory");
}
__device__ __forceinline__ void mbar_arrive(uint32_t bar) { asm volatile("mbarrier.arrive.shared.b64 _, [%0];" ::"r"(bar) : "memory"); }
__device__ __forceinline__ void mbar_arrive_remote(uint32_t bar) {
    asm volatile("mbarrier.arrive.shared::cluster.b64 _, [%0];" ::"r"(bar) : "memory");
}
template <int R> __device__ __forceinline__ void reg_inc() { asm volatile("setmaxnreg.inc.sync.aligned.u32 %0;" ::"n"(R)); }
template <int R> __device__ __forceinline__ void reg_dec() { asm volatile("setmaxnreg.dec.sync.aligned.u32 %0;" ::"n"(R)); }

#define ST(id, w, i)
constexpr int CH_NRES = 50;
constexpr int CH_WREG = CH_NRES * 512;
constexpr int CH_PART = 8 * CH_WREG;
constexpr int CH_SX = CH_PART + 16384;
constexpr int CH_MX = CH_SX + 3 * 1280;
constexpr int CH_QK = CH_MX;
constexpr int CH_XS = CH_MX + 3 * 512;
constexpr int CH_BAR = CH_XS + 5632;
constexpr int CH_SMEM = CH_BAR + 192;
constexpr int CH_THREADS = 384;

__device__ __forceinline__ char* ring_base() { return (char*)(((uintptr_t)g_ring + (1 << 20) - 1) & ~(uintptr_t)((1 << 20) - 1)); }
__device__ __forceinline__ uint32_t ring_off(int chunk, int side) {
    uint32_t o = ((chunk & 1) << 13) | ((chunk >> 1) << 16);
    uint32_t par = ((o >> 13) ^ (o >> 16) ^ (o >> 17) ^ (o >> 19) ^ side) & 1;
    return o | (par << 12);
}
__device__ __forceinline__ uint2 ld_poll(const char* p) {
    unsigned long long v; asm volatile("ld.relaxed.gpu.global.b64 %0, [%1];" : "=l"(v) : "l"(p) : "memory");
    return make_uint2((uint32_t)v, (uint32_t)(v >> 32));
}
__device__ __forceinline__ void st_pub(char* p, uint32_t x, uint32_t y) {
    unsigned long long v = ((unsigned long long)y << 32) | x;
    asm volatile("st.relaxed.gpu.global.b64 [%0], %1;" ::"l"(p), "l"(v) : "memory");
}
template <int N>
__device__ __forceinline__ void poll_issue(uint2 (&b)[N], const char* p, bool lastvalid) {
#pragma unroll
    for (int i = 0; i < N; i++) {
        if (i < N - 1 || lastvalid) b[i] = ld_poll(p + i * 256);
        else b[i] = make_uint2(0, 0);
    }
}
template <int N>
__device__ __forceinline__ int poll_check(uint2 (&b)[N], const char* p, uint32_t z) {
    int it = 0;
    uint32_t mx = z;
#pragma unroll
    for (int i = 0; i < N; i++) mx = max(mx, b[i].x);
    if (__any_sync(0xffffffffu, mx == SENT)) {
        do {
#pragma unroll
            for (int i = 0; i < N; i++)
                if ((REALL && i < 10) || b[i].x == SENT) b[i] = ld_poll(p + i * 256);
            mx = b[0].x;
#pragma unroll
            for (int i = 1; i < N; i++) mx = max(mx, b[i].x);
            it++;
        } while (__any_sync(0xffffffffu, mx == SENT && it < SPIN_LIMIT));
    }
    return it;
}
template <int N>
__device__ __forceinline__ uint32_t delay(uint32_t a) {
    uint32_t z = 0;
#pragma unroll
    for (int i = 0; i < N; i++) asm volatile("ld.volatile.shared.u32 %0, [%1];" : "=r"(z) : "r"(a + z) : "memory");
    return z;
}

#define PFKV 0
#define LDW 0
#define KGS 3
constexpr int KVN = 2;
#define FEN 1
#define XB 4
#define KEEP 100
#define PE 0
#define PROMO 2
#define PROMU 0
#define FNC 1
#define CL 8
#define PL 0
#define ML 4
#define MP 2
#define VCH_P 4
#define VCH_C 2
#define DLM 3
#define DLO 5
constexpr int OB = 0;
template <int PACE, int I0 = 0, int I1 = 12>
__device__ __forceinline__ void preload(uint32_t (&sw)[12][4], uint32_t a, uint32_t zero) {
    uint32_t z = 0;
#pragma unroll
    for (int i = I0; i < I1; i++) {
        if (PACE && i % (PACE ? PACE : 1) == 0) z = delay<1>(zero + z);
        ldsm4t(sw[i], a + z + i * 512);
    }
}
__device__ __forceinline__ void stsm4(uint32_t addr, uint32_t a, uint32_t b, uint32_t c, uint32_t d) {
    asm volatile("stmatrix.sync.aligned.m8n8.x4.shared.b16 [%0], {%1,%2,%3,%4};" ::"r"(addr), "r"(a), "r"(b), "r"(c), "r"(d) : "memory");
}
__device__ __forceinline__ void stsm4t(uint32_t addr, uint32_t a, uint32_t b, uint32_t c, uint32_t d) {
    asm volatile("stmatrix.sync.aligned.m8n8.x4.trans.shared.b16 [%0], {%1,%2,%3,%4};" ::"r"(addr), "r"(a), "r"(b), "r"(c), "r"(d) : "memory");
}
__device__ __forceinline__ void st_part(uint32_t addr, const float (&x)[4], const float (&y)[4]) {
    stsm4(addr, pack_bf16(x[0], x[1]), pack_bf16(x[2], x[3]), pack_bf16(y[0], y[1]), pack_bf16(y[2], y[3]));
}
template <bool TR>
__device__ __forceinline__ void red_part(uint32_t& lo, uint32_t& hi, uint32_t addr, uint32_t eye) {
    uint32_t a[4][4];
#pragma unroll
    for (int j = 0; j < 4; j++) { if (TR) ldsm4t(a[j], addr + j * 1024); else ldsm4(a[j], addr + j * 1024); }
    float r0[4], r1[4], r2[4], r3[4];
    mma16z(r0, a[0], eye, eye); mma16z(r1, a[1], eye, eye); mma16z(r2, a[2], eye, eye); mma16z(r3, a[3], eye, eye);
#pragma unroll
    for (int j = 0; j < 4; j++) r0[j] = ((r0[j] + r1[j]) + r2[j]) + r3[j];
    lo = pack_bf16(r0[0], r0[1]); hi = pack_bf16(r0[2], r0[3]);
}
__device__ __forceinline__ int o_chunk(int ks, int& pos) {
    const int cw = ks < 176 ? ks / 11 : 16 + (ks - 176) / 10;
    pos = ks - (cw < 16 ? 11 * cw : 176 + 10 * (cw - 16));
    return cw;
}

template <bool PV>
__device__ __forceinline__ void chain_loop(const uint32_t (&wa)[36][4], const uint32_t sb, const int w, const int lane0, const int rank,
                                           const int h, const int side) {
    const int rk1 = rank == 2 ? 0 : rank + 1, rk2 = rank == 0 ? 2 : rank - 1;
    const int nq = rank == 0 ? 6 : 5, u0 = rank == 0 ? 0 : 1 + 5 * rank, v0 = rank == 0 ? -6 : 3 * rank - 6;
    const uint32_t pt = CH_PART + (w >> 1) * 4096 + (w & 1) * 256;
    const uint32_t barS = sb + CH_BAR, barM = barS + 8, zero = barS + 24;
    char* const ring0 = ring_base();
    const uint32_t m_rd = ring_off(24 + w, side), o_rd = ring_off(rank * 8 + w, side);
    uint32_t pub;
    if (PV) { int pos, cw = o_chunk(h * 8 + v0 + w, pos); pub = (ring_off(cw, 0) & ~4096u) + pos * 256; }
    else pub = (ring_off(24 + (h >> 2), 0) & ~4096u) + ((2 * h + w) & 7) * 256;
    char* const kvo = (char*)(PV ? g_vm + 128 * (v0 + w) : g_km + 64 * (u0 + w)) + h * 2048;
    const bool mown = !PV && w == rank && rank < 2;
    uint32_t lo16 = lane0 * 16;
    uint32_t sw[12][4];
#pragma unroll
    for (int i = 0; i < 12; i++) ldsm4t(sw[i], sb + lo16 + w * CH_WREG + i * 512);

#pragma unroll 1
    for (int s = 0;; s++) {
        const bool last = s == NSEG - 1;
        const uint32_t slot = (s & 3) << 14;
        lo16 += delay<DLM>(zero);
        const uint32_t lane = lo16 >> 4, l16 = sb + lo16, wl = l16 + w * CH_WREG, pw = l16 + CH_PART + w * 512;
        const uint32_t xs = l16 + CH_XS + nq * 512 + (w - nq) * 1024;
        const uint32_t eye = ((lo16 >> 7) == (lane & 3)) ? ((lo16 & 64) ? 0x3F800000u : 0x3F80u) : 0u;
        uint2 b[8];
        const char* pm = ring0 + (m_rd + slot + (lo16 >> 1));
        poll_issue<8>(b, pm, true);
        preload<0, ML, 12>(sw, wl, zero);
        if (FNC & 1) bar_arrive(14, 256);
        poll_check<8>(b, pm, delay<FNC & 1>(zero));
        if ((OB || (XB & 1)) && !last) bar_arrive(8, 256 + OB);
        if (PV && !last && w == 7) bar_arrive(13, 64);
        {
            float acc[6][4];
#pragma unroll
            for (int kk = 0; kk < 8; kk++) {
                const int j = (2 * kk) % 12;
                if (kk == 0) { mma16z(acc[5], sw[0], b[0].x, b[0].y); mma16z(acc[4], sw[1], b[0].x, b[0].y); }
                else { mma16(acc[5], sw[j], b[kk].x, b[kk].y); mma16(acc[4], sw[j + 1], b[kk].x, b[kk].y); }
#pragma unroll
                for (int i = 0; i < 4; i++) {
                    if (kk == 0) mma16z(acc[i], wa[i * 8], b[0].x, b[0].y);
                    else mma16(acc[i], wa[i * 8 + kk], b[kk].x, b[kk].y);
                    if (i < 2) ldsm4t(sw[j + i], wl + (12 + 2 * kk + i) * 512);
                }
            }
            st_part(pw + 4 * 2048, acc[4], acc[5]);
            st_part(pw, acc[0], acc[1]);
            st_part(pw + 2 * 2048, acc[2], acc[3]);
        }
        uint32_t kv0, kv1;
        const uint32_t lp = l16 + (lane >> 4) * 256, pl = lp + pt;
        if (!PV) {
            bar_sync(1, last ? 256 : 256 + OB);
            red_part<true>(kv1, kv0, pl, eye);
            sts64(l16 + CH_QK + (w >> 1) * 512 + (w & 1) * 8, __uint_as_float(kv1), __uint_as_float(kv0));
            if (!last) bar_arrive(2, nq * 32 + 64 + OB);
        } else {
            bar_sync(1, last ? 256 : 256 + OB);
        }
        {
            float va[4][4];
            const float z = __uint_as_float(delay<1>(zero));
#pragma unroll
            for (int i = 0; i < 4; i++) va[i][0] = va[i][1] = va[i][2] = va[i][3] = z;
#pragma unroll
            for (int kk = 0; kk < 8; kk++) {
                const int c = (PV ? VCH_P : VCH_C) == 4 ? kk & 1 : 0;
                if (kk < 2) { mma16(va[c], wa[32 + 2 * kk], b[kk].x, b[kk].y); mma16(va[2 + c], wa[33 + 2 * kk], b[kk].x, b[kk].y); }
                else { mma16(va[c], sw[(2 * kk) % 12], b[kk].x, b[kk].y); mma16(va[2 + c], sw[(2 * kk + 1) % 12], b[kk].x, b[kk].y); }
            }
            if ((PV ? VCH_P : VCH_C) == 4) {
#pragma unroll
                for (int j = 0; j < 4; j++) { va[0][j] += va[1][j]; va[2][j] += va[3][j]; }
            }
            st_part(pw + 6 * 2048, va[0], va[2]);
        }
        if (PV) {
            uint32_t vt0[4], vt1[4];
            ldsm4t(vt0, xs); ldsm4t(vt1, xs + 512);
            if (w >= 6 && !last) {
                uint32_t kx[3][4];
#pragma unroll
                for (int j = 0; j < 3; j++)
                    ldsm4(kx[j], sb + CH_XS + j * 1024 + (j == 2 && nq == 5 ? 0 : ((lane >> 3) & 1) * 512) + (w - 6) * 256 + (lane >> 4) * 128 + (lane & 7) * 16);
                const uint32_t da = l16 + CH_SX + rank * 1280 + (w - 6) * 512, dc = sb + CH_SX + rank * 1280 + 1024 + lane * 8;
                bar_sync(2, nq * 32 + 64 + OB);
                uint32_t qk[3][4];
#pragma unroll
                for (int j = 0; j < 3; j++) {
                    const float4 v = lds128(l16 + CH_QK + j * 512);
                    qk[j][0] = __float_as_uint(v.x); qk[j][1] = __float_as_uint(v.y); qk[j][2] = __float_as_uint(v.z); qk[j][3] = __float_as_uint(v.w);
                }
                float s0[4], s1[4], s2[4], s3[4];
                mma16z(s0, qk[0], kx[0][0], kx[0][1]); mma16z(s1, qk[0], kx[0][2], kx[0][3]);
                mma16z(s2, qk[1], kx[1][0], kx[1][1]); mma16z(s3, qk[1], kx[1][2], kx[1][3]);
                if (nq == 5) qk[2][2] = qk[2][3] = 0;
                mma16(s0, qk[2], kx[2][0], kx[2][1]); mma16(s1, qk[2], kx[2][2], kx[2][3]);
                float m0[4], m1[4];
                mma16z(m0, qk[0], qk[0][1], qk[0][3]); mma16z(m1, qk[1], qk[1][1], qk[1][3]);
                mma16(m0, qk[2], qk[2][1], qk[2][3]);
                const float4 sv = make_float4(s0[0] + s2[0], s0[1] + s2[1], s1[0] + s3[0], s1[1] + s3[1]);
                st_async4(mapa(da, rk1), sv, mapa(barS, rk1));
                st_async4(mapa(da, rk2), sv, mapa(barS, rk2));
                {
                    const float c0 = m0[0] + m1[0], c1 = m0[1] + m1[1];
                    const int dr = w == 6 ? rk1 : rk2;
                    st_async2(mapa(dc, dr), c0, c1, mapa(barS, dr));
                    sts64(dc, c0, c1);
                }
                const float t4[4] = {sv.x, sv.y, sv.z, sv.w};
                sts128(da, t4);
            }
            bar_sync(3, last ? 256 : 256 + OB);
            if (!last && w == 7) bar_arrive(12, 64);
            red_part<false>(kv0, kv1, pl, eye);
            if (last) {
                uint32_t* d = (uint32_t*)(kvo + (uint32_t)(s * (NH * 2048) + lane * 4));
                d[0] = movm(kv0); d[32] = movm(kv1);
                break;
            }
            {
                const uint32_t sx = l16 + CH_SX, r0 = rank * 1280, r1 = rk1 * 1280, r2 = rk2 * 1280;
                float4 a0 = lds128(sx + r0), b0 = lds128(sx + 512 + r0);
                const float2 c0 = lds64(sx + 1024 + r0 - lane * 8);
                preload<0, 0, PE>(sw, wl + 28 * 512, zero);
                mbar_wait(barS, s & 1);
                const float4 a1 = lds128(sx + r1), a2 = lds128(sx + r2), b1 = lds128(sx + 512 + r1), b2 = lds128(sx + 512 + r2);
                const float2 c1 = lds64(sx + 1024 + r1 - lane * 8), c2 = lds64(sx + 1024 + r2 - lane * 8);
                a0 = add4(add4(a0, a1), a2); b0 = add4(add4(b0, b1), b2);
                float sc[10] = {a0.x, a0.y, a0.z, a0.w, b0.x, b0.y, b0.z, b0.w, c0.x + c1.x + c2.x, c0.y + c1.y + c2.y};
                float mx = fmaxf(fmaxf(fmaxf(sc[0], sc[1]), fmaxf(sc[2], sc[3])), fmaxf(fmaxf(sc[4], sc[5]), fmaxf(sc[6], sc[7])));
                mx = fmaxf(mx, fmaxf(sc[8], sc[9]));
                mx = fmaxf(fmaxf(mx, __shfl_xor_sync(0xffffffffu, mx, 1)),
                           fmaxf(__shfl_xor_sync(0xffffffffu, mx, 2), __shfl_xor_sync(0xffffffffu, mx, 3)));
                const float cs = 0.08838834764831845f * 1.4426950408889634f;
                const float mb = -mx * cs;
#pragma unroll
                for (int j = 0; j < 10; j++) sc[j] = ex2(fmaf(sc[j], cs, mb));
                uint32_t pf[5];
#pragma unroll
                for (int j = 0; j < 5; j++) pf[j] = pack_bf16(sc[2 * j], sc[2 * j + 1]);
                float o0[4], o1[4], o2[4], o3[4], o4[4], o5[4];
                const uint32_t p0[4] = {pf[0], 0, pf[1], 0}, p1[4] = {pf[2], 0, pf[3], 0};
                mma16z(o0, p0, vt0[0], vt0[1]); mma16z(o1, p0, vt1[0], vt1[1]);
                mma16z(o2, p1, vt0[2], vt0[3]); mma16z(o3, p1, vt1[2], vt1[3]);
                mma8z(o4, pf[4], 0, kv0); mma8z(o5, pf[4], 0, kv1);
                float sum = (((sc[0] + sc[1]) + (sc[2] + sc[3])) + ((sc[4] + sc[5]) + (sc[6] + sc[7]))) + (sc[8] + sc[9]);
                sum = (sum + __shfl_xor_sync(0xffffffffu, sum, 1)) + (__shfl_xor_sync(0xffffffffu, sum, 2) + __shfl_xor_sync(0xffffffffu, sum, 3));
                float inv; asm("rcp.approx.ftz.f32 %0, %1;" : "=f"(inv) : "f"(sum));
                const uint32_t ox = pack_bf16((o0[0] + o2[0] + o4[0]) * inv, (o0[1] + o2[1] + o4[1]) * inv);
                const uint32_t oy = pack_bf16((o1[0] + o3[0] + o5[0]) * inv, (o1[1] + o3[1] + o5[1]) * inv);
                char* const pp = ring0 + (pub + slot + (lo16 >> 1));
                st_pub(pp, ox, oy); st_pub(pp + 4096, ox, oy);
                if (OB || (XB & 4)) bar_arrive(10, (8 - nq) * 32 + OB);
                preload<0, PE, PL>(sw, wl + 28 * 512, zero);
            }
            kv0 = movm(kv0); kv1 = movm(kv1);
        } else {
            *(uint32_t*)(kvo + (uint32_t)(s * (NH * 2048) + lane * 4)) = kv0;
            bar_sync(3, last ? 256 : 256 + OB);
            if (last) break;
            preload<1, 0, CL>(sw, wl + 28 * 512, zero);
        }
        uint2 c[11];
        bar_sync(4, 256 + OB);
        const char* po = ring0 + (o_rd + slot + (lo16 >> 1) + delay<DLO>(zero));
        poll_issue<11>(c, po, rank < 2);
        preload<0, PV ? PL : CL, 12>(sw, wl + 28 * 512, zero);
        if (PV) { uint32_t* d = (uint32_t*)(kvo + (uint32_t)(s * (NH * 2048) + lane * 4)); d[0] = kv0; d[32] = kv1; }
        if (FNC & 2) bar_arrive(15, 256);
        poll_check<11>(c, po, delay<(FNC >> 1)>(zero));
        if (OB || (XB & 2)) bar_arrive(9, 256 + OB);
        {
            float acc[4][4];
#pragma unroll
            for (int f = 0; f < 22; f++) {
                const int kk = f >> 1, a = f & 3;
                if (f < 4) mma16z(acc[a], sw[f % 12], c[kk].x, c[kk].y);
                else mma16(acc[a], sw[f % 12], c[kk].x, c[kk].y);
                if (f + 12 < 22) ldsm4t(sw[f % 12], wl + (28 + f + 12) * 512);
            }
#pragma unroll
            for (int i = 0; i < 2; i++) {
#pragma unroll
                for (int j = 0; j < 4; j++) acc[i][j] += acc[i + 2][j];
                sts128(l16 + CH_PART + i * 4096 + w * 512, acc[i]);
            }
        }
        if (!PV && w < 2) {
            bar_sync(5, 288 + OB);
            float4 v[8];
#pragma unroll
            for (int i = 0; i < 8; i++) v[i] = lds128(l16 + CH_PART + w * 4096 + i * 512);
            float4 r = add4(add4(add4(v[0], v[1]), add4(v[2], v[3])), add4(add4(v[4], v[5]), add4(v[6], v[7])));
            if (!mown) st_async4(mapa(l16 + CH_MX + rank * 512, w), r, mapa(barM, w));
            bar_arrive(7, 256 + OB);
            if (mown) {
                mbar_wait(barM, s & 1);
                float4 x = lds128(l16 + CH_MX + (rank ^ 1) * 512), y = lds128(l16 + CH_MX + 2 * 512);
                r = add4(add4(x, r), y);
                const uint32_t mx = movm(pack_bf16(r.x, r.y)), my = movm(pack_bf16(r.z, r.w));
                const uint32_t ns = (slot + 0x4000) & 0xC000;
                char* const pp = ring0 + (pub + ns + (lo16 >> 1));
                st_pub(pp, mx, my); st_pub(pp + 4096, mx, my);
            }
            preload<0, 0, ML>(sw, wl, zero);
        } else {
            bar_arrive(5, 288 + OB);
            bar_sync(7, 256 + OB);
            preload<MP, 0, ML>(sw, wl, zero);
        }
        bar_sync(6, 320 + OB);
    }
    bar_arrive(6, 288);
}

__device__ __forceinline__ void chain_pace(const uint32_t sb, const int lane, const int rank, const int aware) {
    const uint32_t zero = sb + CH_BAR + 24;
    if (lane == 0) {
        char* ring = ring_base();
        uint32_t* p0 = (uint32_t*)(ring + ring_off(blockIdx.x & 15, 0) + 3072 + (blockIdx.x >> 4) * 128);
        uint32_t* p1 = (uint32_t*)(ring + ring_off(blockIdx.x & 15, 1) + 3072 + (blockIdx.x >> 4) * 128);
        *p0 = 0; *p1 = 0;
        int b0 = 1 << 30, b1 = 1 << 30; uint32_t v = 0;
        for (int r = 0; r < 4 || (r < 256 && !mbar_test(sb + CH_BAR + 16, 0)); r++) {
            uint32_t t0 = clk(); v = atomicExch(p0 + (v == 500), r); uint32_t t1 = v == 777 ? clk() + 1 : clk(); b0 = min(b0, (int)(t1 - t0));
            t0 = clk(); v = atomicExch(p1 + (v == 500), r); t1 = v == 777 ? clk() + 1 : clk(); b1 = min(b1, (int)(t1 - t0));
            asm volatile("st.volatile.shared.u32 [%0], %1;" ::"r"(zero + 4), "r"(aware ? (b1 < b0) ^ (aware - 1) : 0) : "memory");
        }
    }
    __syncwarp();
#pragma unroll 1
    for (int s = 1; s < NSEG; s++) {
        bar_sync(5, 288 + OB);
        bar_arrive(6, 320 + OB + (rank == 2 ? delay<18>(zero) : 0));
    }
}
__device__ __forceinline__ char* reset_ptr(const int lane, const int rank, const int h) {
    const int nq = rank == 0 ? 6 : 5, v0 = rank == 0 ? -6 : 3 * rank - 6;
    int pos, cw = o_chunk(h * 8 + v0 + min(max(5 + (lane >> 3), nq), 7), pos);
    if (lane >= 24 && rank < 2) { cw = 24 + (h >> 2); pos = (2 * h + rank) & 7; }
    return ring_base() + ((ring_off(cw, 0) & ~4096u) + pos * 256 + (lane & 7) * 16);
}
__device__ __forceinline__ void chain_chores(const uint32_t sb, const int lane, const int rank, const int h, const bf16* __restrict__ mem0) {
    const int nq = rank == 0 ? 6 : 5, u0 = rank == 0 ? 0 : 1 + 5 * rank, v0 = rank == 0 ? -6 : 3 * rank - 6;
    const uint32_t barS = sb + CH_BAR, barM = barS + 8, barX = barS + 16;
    auto xload = [&](int s) {
        mbar_expect(barX, 8192 - nq * 512);
        bulk_load(sb + CH_XS, g_kx + (size_t)(s * NH + h) * 4096 + u0 * 256, nq * 512, barX);
        bulk_load(sb + CH_XS + nq * 512, g_vx + (size_t)(s * NH + h) * 4096 + (v0 + nq) * 512, (8 - nq) * 1024, barX);
    };
    char* const rb = reset_ptr(lane, rank, h);
    int* const kvf = g_kvf + blockIdx.x * 16;
    if (rank < 2) {
        const uint32_t* p = (const uint32_t*)(mem0 + (lane >> 2) * DM + 32 * h + 16 * rank + 2 * (lane & 3));
        char* d = ring_base() + ((ring_off(24 + (h >> 2), 0) & ~4096u) + ((2 * h + rank) & 7) * 256 + lane * 8);
        const uint32_t x = p[0] == SENT ? 0x7FFF7FFFu : p[0];
        st_pub(d, x, p[4]); st_pub(d + 4096, x, p[4]);
    }
    if (lane == 0) {
        if (!KVN) __nanosleep(18000);
        wait_ctr(kvf, KVN);
        asm volatile("fence.proxy.async.global;" ::: "memory");
        xload(0);
    }
#pragma unroll 1
    for (int s = 0; s < NSEG - 1; s++) {
        if (lane == 0) {
            mbar_expect(barS, 2 * 1280);
            if (rank < 2) mbar_expect(barM, 2 * 512);
        }
        bar_sync(13, 64);
#pragma unroll
        for (int i = 0; i < 4; i++)
            asm volatile("st.relaxed.gpu.global.v4.u32 [%0], {%1,%1,%1,%1};" ::"l"(rb + ((((s + 2) & 3) << 14) + (i >> 1) * 4096 + (i & 1) * 128)), "r"(SENT) : "memory");
        if (FEN || (s & 3) == 0) fence_gpu();
        if (lane == 0 && (s & 3) == 0 && s) atomicAdd(g_ctr + C_CHAIN + (s >> 2) - 1, 1);
        if (lane == 0 && (s & 3) == 3) { wait_ctr(kvf + (s >> 2) + 1, KVN); asm volatile("fence.proxy.async.global;" ::: "memory"); }
        __syncwarp();
        bar_sync(12, 64);
        if (lane == 0) xload(s + 1);
        mbar_wait(barX, (s + 1) & 1);
        bar_sync(6, 320 + OB);
    }
    bar_sync(6, 288);
    fence_gpu();
    if (lane == 0) atomicAdd(g_ctr + C_CHAIN + 15, 1);
}

struct S4Params { const bf16 *Are, *Aim, *Bre, *Bim, *Cre, *Cim, *ldt, *dsk; };
__device__ __forceinline__ float2 cmul(float2 a, float2 b) { return make_float2(a.x * b.x - a.y * b.y, a.x * b.y + a.y * b.x); }
__device__ __forceinline__ float2 csq(float2 a) { return make_float2(a.x * a.x - a.y * a.y, (a.x + a.x) * a.y); }
__device__ __forceinline__ float2 cexp_t(float lr, float turns) {
    float f = (turns - rintf(turns)) * 6.283185307179586f, e = ex2(lr);
    return make_float2(e * __cosf(f), e * __sinf(f));
}
__device__ __forceinline__ float bf_at(uint2 v, int i) {
    const uint32_t w = i < 2 ? v.x : v.y;
    return __uint_as_float((i & 1) ? w & 0xFFFF0000u : w << 16);
}
__device__ __forceinline__ void kg_step(uint32_t (&a)[4][4], uint32_t (&b)[5][2], uint32_t pa, uint32_t pe, float x0) {
#pragma unroll
    for (int i = 0; i < 2; i++) {
        const float4 p = lds128(pa + i * 64);
        const float2 e8 = lds64(pe + i * 32), c = make_float2(p.z, p.w);
        const float mag = ex2(p.x * x0), ph = p.y * x0;
        float2 e0 = make_float2(mag * __cosf(ph), mag * __sinf(ph)), e1 = cmul(e0, e8);
#pragma unroll
        for (int j = 0; j < 4; j++) {
            a[j][2 * i] = pack_bf16(e0.x, e0.y); a[j][2 * i + 1] = pack_bf16(e1.x, e1.y);
            e0 = csq(e0); e1 = csq(e1);
        }
        float2 m = cmul(c, e0);
        b[0][i] = pack_bf16(m.x, -m.y);
#pragma unroll
        for (int j = 0; j < 4; j++) {
            m = cmul(c, e1);
            b[j + 1][i] = pack_bf16(m.x, -m.y);
            if (j < 3) e1 = csq(e1);
        }
    }
}
__device__ __forceinline__ void kg_mma(float (&kd)[5][4], const uint32_t (&a)[4][4], const uint32_t (&b)[5][2]) {
    mma16(kd[0], a[0], b[0][0], b[0][1]);
#pragma unroll
    for (int j = 0; j < 4; j++) mma16(kd[j + 1], a[j], b[j + 1][0], b[j + 1][1]);
}
struct KgRaw { uint2 v[6]; float ldt; };
__device__ __forceinline__ void kg_load(KgRaw& r, const S4Params& P, int d, int lane) {
    const bf16* src[6] = {P.Are, P.Aim, P.Bre, P.Bim, P.Cre, P.Cim};
#pragma unroll
    for (int j = 0; j < 6; j++) r.v[j] = __ldg((const uint2*)(src[j] + d * 128) + lane);
    r.ldt = __bfloat162float(P.ldt[d]);
}
__device__ __forceinline__ float kg_params(const KgRaw& r, uint32_t stg, int lane) {
    const float dt = __bfloat162float(__float2bfloat16(expf(r.ldt)));
    float k2048 = 0.f;
#pragma unroll
    for (int i = 0; i < 4; i++) {
        const float br = dt * bf_at(r.v[2], i), bi = dt * bf_at(r.v[3], i), cr = bf_at(r.v[4], i), ci = bf_at(r.v[5], i);
        const float zr = dt * bf_at(r.v[0], i) * 1.4426950408889634f;
        float zt = dt * bf_at(r.v[1], i) * 0.15915494309189535f;
        zt -= rintf(zt);
        const float v[4] = {zr, zt * 6.283185307179586f, cr * br - ci * bi, cr * bi + ci * br};
        const float2 e8 = cexp_t(8.f * zr, 8.f * zt), el = cexp_t(2048.f * zr, 2048.f * zt);
        k2048 += v[2] * el.x - v[3] * el.y;
        sts128(stg + (i * 32 + lane) * 16, v);
        sts64(stg + 2048 + (i * 32 + lane) * 8, e8.x, e8.y);
    }
#pragma unroll
    for (int o = 16; o; o >>= 1) k2048 += __shfl_xor_sync(0xffffffffu, k2048, o);
    __syncwarp();
    return k2048;
}
__device__ __forceinline__ void kg_store(const float (&kd)[5][4], float k2048, uint32_t stg, int d, int lane) {
    __syncwarp();
    const uint32_t ta = stg + (lane & 7) * 32 + ((lane >> 3) & 1) * 16 + (lane >> 4) * 256;
    stsm4t(ta, pack_bf16(kd[0][0], kd[0][1]), pack_bf16(kd[0][2], kd[0][3]), pack_bf16(kd[1][0], kd[1][1]), pack_bf16(kd[1][2], kd[1][3]));
    stsm4t(ta + 512, pack_bf16(kd[2][0], kd[2][1]), pack_bf16(kd[2][2], kd[2][3]), pack_bf16(kd[3][0], kd[3][1]), pack_bf16(kd[3][2], kd[3][3]));
    stsm4t(ta + 1024, pack_bf16(kd[4][0], kd[4][1]), pack_bf16(kd[4][2], kd[4][3]), pack_bf16(k2048, 0.f), 0);
    __syncwarp();
#pragma unroll
    for (int j = 0; j < 3; j++) ((float4*)(g_kd + d * 768))[j * 32 + lane] = lds128(stg + j * 512 + lane * 16);
    __syncwarp();
}

__global__ void __cluster_dims__(3, 1, 1) __launch_bounds__(CH_THREADS, 1)
chain_kernel(const __grid_constant__ CUtensorMap mq, const __grid_constant__ CUtensorMap mk, const __grid_constant__ CUtensorMap mv,
             const __grid_constant__ CUtensorMap mo, const bf16* __restrict__ Wq, const bf16* __restrict__ Wk, const bf16* __restrict__ Wv,
             const bf16* __restrict__ mem0, const __grid_constant__ S4Params P, int aware) {
    extern __shared__ __align__(1024) unsigned char smem[];
    const uint32_t sb = smem_u32(smem);
    const int tid = threadIdx.x, lane = tid & 31;
    const int w = __shfl_sync(0xffffffffu, tid >> 5, 0);
    int rank; asm("mov.u32 %0, %%cluster_ctarank;" : "=r"(rank));
    const int h = blockIdx.x / 3;
    if (tid == 0) {
        mbar_init(sb + CH_BAR, 1); mbar_init(sb + CH_BAR + 8, 1); mbar_init(sb + CH_BAR + 16, 1);
        for (int i = 0; i < 16; i++) mbar_init(sb + CH_BAR + 64 + i * 8, 1);
        *(int*)(smem + CH_BAR + 24) = 0; *(int*)(smem + CH_BAR + 28) = 0; *(int*)(smem + CH_BAR + 32) = 0;
        asm volatile("fence.mbarrier_init.release.cluster;" ::: "memory");
    }
    if (w == 10 && PFKV) {
        const int e = lane * 96 + blockIdx.x;
        if (e < 2048) asm volatile("cp.async.bulk.prefetch.L2.global [%0], 8192;" ::"l"(((e & 1) ? Wv : Wk) + (size_t)(e >> 1) * HD) : "memory");
        if (PFKV > 1) __nanosleep(PFKV);
    }
    if (w == 9) {
        char* const rb = reset_ptr(lane, rank, h);
#pragma unroll
        for (int i = 0; i < 8; i++)
            asm volatile("st.relaxed.gpu.global.v4.u32 [%0], {%1,%1,%1,%1};" ::"l"(rb + (((i >> 2) << 14) + ((i >> 1) & 1) * 4096 + (i & 1) * 128)), "r"(SENT) : "memory");
        if (lane < 16) g_kvf[blockIdx.x * 16 + lane] = 0;
        if (blockIdx.x == 0)
            for (int k = lane; k < N_CTR; k += 32) g_ctr[k] = 0;
        fence_gpu();
        __syncwarp();
        asm volatile("griddepcontrol.launch_dependents;" ::: "memory");
    }
    __syncthreads();
    asm volatile("barrier.cluster.arrive.relaxed.aligned;" ::: "memory");

    if (w >= 8) {
        reg_dec<24>();
        asm volatile("barrier.cluster.wait.aligned;" ::: "memory");
        if (w == 8) chain_pace(sb, lane, rank, aware);
        else if (w == 9) {
            chain_chores(sb, lane, rank, h, mem0);
            asm volatile("st.volatile.shared.u32 [%0], %1;" ::"r"(sb + CH_BAR + 32), "r"(0x3F803F80) : "memory");
        } else if (w == 11 && KEEP) {
#pragma unroll 1
            for (int it = 0; it < (1 << 22); it++) {
                int d0, d1;
                const uint32_t x = delay<1>(sb + CH_BAR + 32);
                asm volatile("mma.sync.aligned.m8n8k16.row.col.s32.s8.s8.s32 {%0,%1}, {%2}, {%2}, {%3,%3};" : "=r"(d0), "=r"(d1) : "r"(x), "r"(0));
                if (d0 | d1) break;
                if ((XB & 8) && lane == 0) asm volatile("st.relaxed.gpu.global.u32 [%0], %1;" ::"l"(g_kd + DM * 768 + blockIdx.x * 64), "r"(it) : "memory");
                if ((XB & 16) && lane == 0) ld_acq((int*)(g_kd + DM * 768 + blockIdx.x * 64));
                __nanosleep(KEEP);
            }
        }
    } else {
        reg_inc<240>();
        const int nq = rank == 0 ? 6 : 5;
        const int u0 = rank == 0 ? 0 : 1 + 5 * rank;
        const int v0 = rank == 0 ? -6 : 3 * rank - 6;
        const int gw = rank * 8 + w;
        const int ks0 = gw < 16 ? 11 * gw : 176 + 10 * (gw - 16);
        const int nko = gw < 16 ? 11 : 10;
        const uint32_t wr = sb + w * CH_WREG, bar0 = sb + CH_BAR + 64 + w * 16, bar1 = bar0 + 8;
        uint32_t wa[36][4];
        const uint32_t vst = sb + CH_PART + w * 2048;
        const int cq = h * DH + 8 * u0, cv = h * DH + 16 * (v0 + 6);
        const int r8 = lane >> 2, p = lane & 3;
        const bf16* src = p >= 2 ? ((p & 1) ? Wk : Wq) + cq + 32 : rank == 0 ? ((p & 1) ? Wk : Wq) + cq + 40 : Wv + cv - 16 + 8 * p;
        src += (size_t)(128 * w + r8) * HD;
        auto cp_rows = [&](int kh) {
            cp16(wr + ((kh >> 1) * 2 + (p >> 1)) * 512 + ((kh & 1) * 2 + (p & 1)) * 128 + r8 * 16, src + (size_t)kh * 8 * HD);
        };
        {
            int d = blockIdx.x * 8 + w, t = 0;
            const int d1 = 768 + blockIdx.x * 3 + w, nt = (w < 3 && d1 < DM) ? 32 : 16;
            const uint32_t stg = wr + 4096;
            KgRaw raw, raw1;
            kg_load(raw, P, d, lane);
            kg_load(raw1, P, min(d1, DM - 1), lane);
            float kd[5][4], k2048;
#pragma unroll 1
            for (int i = -LDW; i < 9 || t < nt; i++) {
                if (i >= 0 && i < 9) {
                    const uint32_t bar = bar0 + (i & 1) * 8;
                    if (i >= 2) mbar_wait(bar, ((i >> 1) - 1) & 1);
                    if (lane == 0) {
                        mbar_expect(bar, 2048);
                        if (i < 8) tma2d(wr + 8192 + (i & 1) * 8192 + (i >> 1) * 2048, (i & 1) ? &mk : &mq, cq, 128 * w + 32 * (i >> 1), bar);
                        else tma2d(vst, &mv, cv, 128 * w, bar);
                    }
                    if (i < 8) cp_rows(i);
                }
#pragma unroll 1
                for (int e = min(t + KGS, nt); t < e; t++) {
                    if ((t & 15) == 0) {
                        k2048 = kg_params(raw, stg, lane);
#pragma unroll
                        for (int j = 0; j < 20; j++) kd[j >> 2][j & 3] = 0.f;
                    }
                    uint32_t ka[4][4], kb[5][2];
                    kg_step(ka, kb, stg + ((t & 15) * 8 + (lane & 3)) * 16, stg + 2048 + ((t & 15) * 8 + (lane & 3)) * 8, (float)(lane >> 2));
                    kg_mma(kd, ka, kb);
                    if ((t & 15) == 15) { kg_store(kd, k2048, stg, d, lane); raw = raw1; d = d1; }
                }
            }
        }
        const uint32_t lrow = ((lane >> 4) * 8 + (lane & 7)) * 64, lsw = (lane >> 1) & 3, lh = (lane >> 3) & 1;
        mbar_wait(bar1, 1); mbar_wait(bar0, 0);
#pragma unroll
        for (int i = 0; i < 32; i++) ldsm4t(wa[i], wr + 8192 + lh * 8192 + (i & 7) * 1024 + lrow + (((i >> 3) ^ lsw) << 4));
#pragma unroll
        for (int i = 0; i < 4; i++) ldsm4t(wa[32 + i], vst + (i >> 1) * 1024 + lrow + ((((i & 1) * 2 + lh) ^ lsw) << 4));
        asm volatile("fence.proxy.async.shared::cta;" ::"r"(wa[31][0]), "r"(wa[35][0]) : "memory");
        __syncwarp();
#pragma unroll 1
        for (int i = 9; i < 18; i++) {
            const uint32_t bar = bar0 + (i & 1) * 8;
            if (i >= 11) mbar_wait(bar, ((i >> 1) - 1) & 1);
            if (lane == 0) {
                const int j = 2 * (i - 12), nb = min(2, nko - j);
                mbar_expect(bar, i < 12 ? 2048 : nb * 1024);
                if (i < 12) tma2d(wr + 8192 + (i - 9) * 2048, &mv, cv, 128 * w + 32 * (i - 8), bar);
                else for (int e = 0; e < nb; e++) tma2d(wr + 14336 + (j + e) * 1024, &mo, 32 * h, 16 * (ks0 + j + e), bar);
            }
            if (i < 17) cp_rows(i - 1);
        }
        mbar_wait(bar0, 0); mbar_wait(bar1, 0);
#pragma unroll 1
        for (int i = 0; i < 17; i++) {
            uint32_t x[4], y[4];
            ldsm4t(x, wr + 8192 + i * 1024 + lrow + ((lh ^ lsw) << 4));
            ldsm4t(y, wr + 8192 + i * 1024 + lrow + (((2 + lh) ^ lsw) << 4));
            if (i == 16 && nko == 10) x[0] = x[1] = x[2] = x[3] = y[0] = y[1] = y[2] = y[3] = 0;
            __syncwarp();
            stsm4t(wr + 8192 + i * 1024 + lane * 16, x[0], x[1], x[2], x[3]);
            stsm4t(wr + 8192 + i * 1024 + 512 + lane * 16, y[0], y[1], y[2], y[3]);
        }
        asm volatile("cp.async.wait_all;" ::: "memory");
        asm volatile("barrier.cluster.wait.aligned;" ::: "memory");
        bar_sync(1, 256);
        mbar_wait_long(sb + CH_BAR + 16, 0);
        const int side = __shfl_sync(0xffffffffu, *(volatile int*)(smem + CH_BAR + 28), 0);
        if (w >= nq) chain_loop<true>(wa, sb, w, lane, rank, h, side);
        else chain_loop<false>(wa, sb, w, lane, rank, h, side);
    }
}

constexpr int G_STAGE = 49152, G_NST = 4;
constexpr int G_STG = G_NST * G_STAGE;
constexpr int G_BAR = G_STG + 32768;
constexpr int G_SMEM = G_BAR + 256 + 1024;

#define WLOG(e)
constexpr int IT_QA = 0, IT_O = 1, IT_S4 = 2, IT_END = 3, IT_KV = 4;
#define O_WIDE 10
#define TMP 1
#define ATT2 0
#define S4REL 4
#define KVS 8
#define STM 0
__device__ __forceinline__ void st_out(uint32_t* p, uint32_t v) {
    if (STM == 0) *p = v;
    else if (STM == 1) __stcs(p, v);
    else asm volatile("st.global.L1::no_allocate.u32 [%0], %1;" ::"l"(p), "r"(v) : "memory");
}
#define Q_N1 1
#define Q_S1 12
__device__ __forceinline__ int queue_item(int q) {
    if (q < 512) return (IT_KV << 16) | ((q >> 5) << 8) | (q & 31);
    q -= 512;
    if (q < 256) return (IT_QA << 16) | ((q >> 4) << 8) | (q & 15);
    q -= 256;
    if (q < Q_N1 * 8) return (IT_O << 16) | ((O_WIDE + (q >> 3)) << 8) | (q & 7);
    q -= Q_N1 * 8;
    if (q < Q_S1) return (IT_S4 << 16) | q;
    q -= Q_S1;
    if (q < (16 - O_WIDE - Q_N1) * 8) return (IT_O << 16) | ((O_WIDE + Q_N1 + (q >> 3)) << 8) | (q & 7);
    q -= (16 - O_WIDE - Q_N1) * 8;
    if (q < 128 - Q_S1) return (IT_S4 << 16) | (Q_S1 + q);
    return IT_END << 16;
}
__device__ __forceinline__ void tma2d_store(const CUtensorMap* m, uint32_t src, int c0, int c1) {
    asm volatile("cp.async.bulk.tensor.2d.global.shared::cta.bulk_group [%0, {%2, %3}], [%1];" ::"l"(m), "r"(src), "r"(c0), "r"(c1) : "memory");
}

__device__ __forceinline__ void wgmma_s64(float (&d)[32], uint32_t a0, uint32_t a1, uint32_t a2, uint32_t a3, uint64_t db, int acc) {
    asm volatile("{.reg .pred p; setp.ne.b32 p, %37, 0;\n"
        "wgmma.mma_async.sync.aligned.m64n64k16.f32.bf16.bf16 {"
        "%0,%1,%2,%3,%4,%5,%6,%7,%8,%9,%10,%11,%12,%13,%14,%15,"
        "%16,%17,%18,%19,%20,%21,%22,%23,%24,%25,%26,%27,%28,%29,%30,%31"
        "}, {%32,%33,%34,%35}, %36, p, 1, 1, 0;}"
        : "+f"(d[0]), "+f"(d[1]), "+f"(d[2]), "+f"(d[3]), "+f"(d[4]), "+f"(d[5]), "+f"(d[6]), "+f"(d[7]), "+f"(d[8]), "+f"(d[9]), "+f"(d[10]), "+f"(d[11]), "+f"(d[12]), "+f"(d[13]), "+f"(d[14]), "+f"(d[15]), "+f"(d[16]), "+f"(d[17]), "+f"(d[18]), "+f"(d[19]), "+f"(d[20]), "+f"(d[21]), "+f"(d[22]), "+f"(d[23]), "+f"(d[24]), "+f"(d[25]), "+f"(d[26]), "+f"(d[27]), "+f"(d[28]), "+f"(d[29]), "+f"(d[30]), "+f"(d[31])
        : "r"(a0), "r"(a1), "r"(a2), "r"(a3), "l"(db), "r"(acc));
}
__device__ __forceinline__ void wgmma_s16(float (&d)[8], uint32_t a0, uint32_t a1, uint32_t a2, uint32_t a3, uint64_t db, int acc) {
    asm volatile("{.reg .pred p; setp.ne.b32 p, %13, 0;\n"
        "wgmma.mma_async.sync.aligned.m64n16k16.f32.bf16.bf16 {"
        "%0,%1,%2,%3,%4,%5,%6,%7"
        "}, {%8,%9,%10,%11}, %12, p, 1, 1, 0;}"
        : "+f"(d[0]), "+f"(d[1]), "+f"(d[2]), "+f"(d[3]), "+f"(d[4]), "+f"(d[5]), "+f"(d[6]), "+f"(d[7])
        : "r"(a0), "r"(a1), "r"(a2), "r"(a3), "l"(db), "r"(acc));
}
__device__ __forceinline__ void wgmma_v128(float (&d)[64], uint32_t a0, uint32_t a1, uint32_t a2, uint32_t a3, uint64_t db, int acc) {
    asm volatile("{.reg .pred p; setp.ne.b32 p, %69, 0;\n"
        "wgmma.mma_async.sync.aligned.m64n128k16.f32.bf16.bf16 {"
        "%0,%1,%2,%3,%4,%5,%6,%7,%8,%9,%10,%11,%12,%13,%14,%15,"
        "%16,%17,%18,%19,%20,%21,%22,%23,%24,%25,%26,%27,%28,%29,%30,%31,"
        "%32,%33,%34,%35,%36,%37,%38,%39,%40,%41,%42,%43,%44,%45,%46,%47,"
        "%48,%49,%50,%51,%52,%53,%54,%55,%56,%57,%58,%59,%60,%61,%62,%63"
        "}, {%64,%65,%66,%67}, %68, p, 1, 1, 1;}"
        : "+f"(d[0]), "+f"(d[1]), "+f"(d[2]), "+f"(d[3]), "+f"(d[4]), "+f"(d[5]), "+f"(d[6]), "+f"(d[7]), "+f"(d[8]), "+f"(d[9]), "+f"(d[10]), "+f"(d[11]), "+f"(d[12]), "+f"(d[13]), "+f"(d[14]), "+f"(d[15]), "+f"(d[16]), "+f"(d[17]), "+f"(d[18]), "+f"(d[19]), "+f"(d[20]), "+f"(d[21]), "+f"(d[22]), "+f"(d[23]), "+f"(d[24]), "+f"(d[25]), "+f"(d[26]), "+f"(d[27]), "+f"(d[28]), "+f"(d[29]), "+f"(d[30]), "+f"(d[31]), "+f"(d[32]), "+f"(d[33]), "+f"(d[34]), "+f"(d[35]), "+f"(d[36]), "+f"(d[37]), "+f"(d[38]), "+f"(d[39]), "+f"(d[40]), "+f"(d[41]), "+f"(d[42]), "+f"(d[43]), "+f"(d[44]), "+f"(d[45]), "+f"(d[46]), "+f"(d[47]), "+f"(d[48]), "+f"(d[49]), "+f"(d[50]), "+f"(d[51]), "+f"(d[52]), "+f"(d[53]), "+f"(d[54]), "+f"(d[55]), "+f"(d[56]), "+f"(d[57]), "+f"(d[58]), "+f"(d[59]), "+f"(d[60]), "+f"(d[61]), "+f"(d[62]), "+f"(d[63])
        : "r"(a0), "r"(a1), "r"(a2), "r"(a3), "l"(db), "r"(acc));
}

__device__ __forceinline__ void attn_scores(float (&sx)[32], float (&sm)[8], const uint32_t (&q)[32], uint32_t sk) {
    const uint64_t dx = mkdesc(sk, 1024, 128, 0), dm = mkdesc(sk + 16384, 256, 128, 0);
    wg_fence();
#pragma unroll
    for (int ks = 0; ks < 8; ks++) {
        wgmma_s64(sx, q[4 * ks], q[4 * ks + 1], q[4 * ks + 2], q[4 * ks + 3], dx + ks * 128, ks);
        wgmma_s16(sm, q[4 * ks], q[4 * ks + 1], q[4 * ks + 2], q[4 * ks + 3], dm + ks * 32, ks);
    }
    wg_commit();
}
__device__ __forceinline__ void attn_softmax(uint32_t (&p)[20], const float (&sx)[32], const float (&sm)[8], int wi, int lane) {
    const bool sb = wi >= 2;
    const int r0 = (wi & 1) * 16 + (lane >> 2) - 2 * (lane & 3);
    float s[5][4];
#pragma unroll
    for (int j = 0; j < 4; j++) s[4][j] = sb ? sm[4 + j] : sm[j];
    float m0 = fmaxf(s[4][0], s[4][1]), m1 = fmaxf(s[4][2], s[4][3]);
#pragma unroll
    for (int j = 0; j < 4; j++) {
#pragma unroll
        for (int e = 0; e < 4; e++) s[j][e] = 8 * j + (e & 1) > r0 + 8 * (e >> 1) ? -INFINITY : sb ? sx[16 + 4 * j + e] : sx[4 * j + e];
        m0 = fmaxf(m0, fmaxf(s[j][0], s[j][1])); m1 = fmaxf(m1, fmaxf(s[j][2], s[j][3]));
    }
    m0 = fmaxf(m0, __shfl_xor_sync(0xffffffffu, m0, 1)); m1 = fmaxf(m1, __shfl_xor_sync(0xffffffffu, m1, 1));
    m0 = fmaxf(m0, __shfl_xor_sync(0xffffffffu, m0, 2)); m1 = fmaxf(m1, __shfl_xor_sync(0xffffffffu, m1, 2));
    const float cs = 0.08838834764831845f * 1.4426950408889634f;
    m0 *= -cs; m1 *= -cs;
    float l0 = 0, l1 = 0;
#pragma unroll
    for (int j = 0; j < 5; j++) {
        s[j][0] = ex2(fmaf(s[j][0], cs, m0)); s[j][1] = ex2(fmaf(s[j][1], cs, m0));
        s[j][2] = ex2(fmaf(s[j][2], cs, m1)); s[j][3] = ex2(fmaf(s[j][3], cs, m1));
        l0 += s[j][0] + s[j][1]; l1 += s[j][2] + s[j][3];
    }
    l0 += __shfl_xor_sync(0xffffffffu, l0, 1); l1 += __shfl_xor_sync(0xffffffffu, l1, 1);
    l0 += __shfl_xor_sync(0xffffffffu, l0, 2); l1 += __shfl_xor_sync(0xffffffffu, l1, 2);
    asm("rcp.approx.ftz.f32 %0, %0;" : "+f"(l0)); asm("rcp.approx.ftz.f32 %0, %0;" : "+f"(l1));
    const uint32_t ma = sb ? 0u : ~0u;
#pragma unroll
    for (int j = 0; j < 5; j++) {
        const uint32_t x = pack_bf16(s[j][0] * l0, s[j][1] * l0), y = pack_bf16(s[j][2] * l1, s[j][3] * l1);
        const int ia = j < 4 ? 2 * j : 16, ib = j < 4 ? 8 + 2 * j : 18;
        asm volatile("and.b32 %0, %4, %6; and.b32 %1, %5, %6; and.b32 %2, %4, %7; and.b32 %3, %5, %7;"
            : "=&r"(p[ia]), "=&r"(p[ia + 1]), "=&r"(p[ib]), "=&r"(p[ib + 1]) : "r"(x), "r"(y), "r"(ma), "r"(~ma));
    }
}
__device__ __forceinline__ void attn_pv(float (&o)[64], const uint32_t (&p)[20], uint32_t sv) {
    const uint64_t dx = mkdesc(sv, 128, 1024, 0), dm = mkdesc(sv + 16384, 128, 256, 0);
    wg_fence();
#pragma unroll
    for (int ks = 0; ks < 5; ks++) wgmma_v128(o, p[4 * ks], p[4 * ks + 1], p[4 * ks + 2], p[4 * ks + 3], ks < 4 ? dx + ks * 16 : dm, ks);
    wg_commit();
}
__device__ __forceinline__ void attn_stage(const float (&o)[64], uint32_t dst) {
#pragma unroll
    for (int u = 0; u < 16; u += 2)
        stsm4(dst + (u >> 3) * 8192 + (u & 7) * 128, pack_bf16(o[4 * u], o[4 * u + 1]), pack_bf16(o[4 * u + 2], o[4 * u + 3]),
              pack_bf16(o[4 * u + 4], o[4 * u + 5]), pack_bf16(o[4 * u + 6], o[4 * u + 7]));
}

template <int BN, int NKB, bool BLOCKED_A>
__device__ __forceinline__ void mainloop(float (&acc)[BN / 2], uint32_t sb, int wgi, uint32_t full, uint32_t empty, int& it, bool elect) {
#pragma unroll
    for (int j = 0; j < BN / 2; j++) acc[j] = 0.f;
#pragma unroll 1
    for (int k4 = 0; k4 < NKB; k4 += 4) {
#pragma unroll
        for (int st = 0; st < 4; st++, it++) {
            mbar_wait_long(full + 8 * st, (it >> 2) & 1);
            const uint64_t da = BLOCKED_A ? mkdesc(sb + st * G_STAGE + wgi * 8192, 128, 1024, 0) : mkdesc(sb + st * G_STAGE + wgi * 8192, 16, 1024, 1);
            const uint64_t db = mkdesc(sb + st * G_STAGE + 16384, 8192, 1024, 1);
            wg_fence();
#pragma unroll
            for (int k = 0; k < 4; k++) {
                if constexpr (BN == 256) wgmma256(acc, da + k * (BLOCKED_A ? 16 : 2), db + k * 128, 1);
                else wgmma128(acc, da + k * (BLOCKED_A ? 16 : 2), db + k * 128, 1);
            }
            wg_commit();
            if (k4 | st) {
                wg_wait<1>();
                if (elect) mbar_arrive(empty + 8 * ((st + 3) & 3));
            }
        }
    }
    wg_wait<0>();
    if (elect) mbar_arrive(empty + 8 * 3);
}

__device__ __forceinline__ uint32_t n6_a(int st) { return st < 4 ? st * G_STAGE : (2 * st - 8) * G_STAGE + 32768; }
__device__ __forceinline__ uint32_t n6_b(int st) { return st < 4 ? st * G_STAGE + 16384 : (2 * st - 7) * G_STAGE + 32768; }
__device__ __forceinline__ uint32_t n6_bar(int st) { return st < 4 ? 8 * st : 96 + 8 * st; }
__device__ __forceinline__ void mainloop6(float (&acc)[64], uint32_t sb, int wgi, uint32_t full, uint32_t empty, int& it, bool elect) {
#pragma unroll
    for (int j = 0; j < 64; j++) acc[j] = 0.f;
    int st = 0, prev = 0, r = 0;
#pragma unroll 1
    for (int kb = 0; kb < 64; kb++) {
        mbar_wait_long(full + n6_bar(st), ((st < 4 ? it >> 2 : 0) + r) & 1);
        const uint64_t da = mkdesc(sb + n6_a(st) + wgi * 8192, 128, 1024, 0), db = mkdesc(sb + n6_b(st), 8192, 1024, 1);
        wg_fence();
#pragma unroll
        for (int k = 0; k < 4; k++) wgmma128(acc, da + k * 16, db + k * 128, 1);
        wg_commit();
        if (kb) {
            wg_wait<1>();
            if (elect) mbar_arrive(empty + n6_bar(prev));
        }
        prev = st;
        if (++st == 6) { st = 0; r++; }
    }
    wg_wait<0>();
    if (elect) mbar_arrive(empty + 8 * 3);
    it += 44;
}

template <int BN>
__device__ __forceinline__ void o_item(uint32_t sb, int wgi, int wi, int lane, uint32_t full, uint32_t empty, int& it, const CUtensorMap* mout,
                                       int row0, int col0, uint32_t stgpar) {
    float acc[BN / 2];
    if constexpr (BN == 256) mainloop<BN, 64, true>(acc, sb, wgi, full, empty, it, lane == 0);
    else mainloop6(acc, sb, wgi, full, empty, it, lane == 0);
    ST((row0 >> 4) + (col0 / BN), wgi * 4 + wi, 10);
    mbar_wait(full + 104, stgpar);
    const uint32_t stg = sb + G_STG + (wgi * 4 + wi) * 4096;
    const int r = lane & 15, cu = lane >> 4;
#pragma unroll
    for (int hf = 0; hf < BN / 128; hf++) {
        if (lane == 0) asm volatile("cp.async.bulk.wait_group.read 0;" ::: "memory");
        __syncwarp();
#pragma unroll
        for (int j = 0; j < 8; j++) {
            const float* a = acc + hf * 64 + j * 8;
            stsm4(stg + (j >> 2) * 2048 + r * 128 + ((((j & 3) * 2 + cu) ^ (r & 7)) << 4),
                  pack_bf16(a[0], a[1]), pack_bf16(a[2], a[3]), pack_bf16(a[4], a[5]), pack_bf16(a[6], a[7]));
        }
        asm volatile("fence.proxy.async.shared::cta;" ::: "memory");
        __syncwarp();
        if (lane == 0) {
            tma2d_store(mout, stg, col0 + hf * 128, row0 + wgi * 64 + wi * 16);
            tma2d_store(mout, stg + 2048, col0 + hf * 128 + 64, row0 + wgi * 64 + wi * 16);
            asm volatile("cp.async.bulk.commit_group;" ::: "memory");
        }
    }
}

constexpr int S4_KD = 32768;
constexpr int S4_CH = 2 * G_STAGE;
constexpr int S4_HALF = 2304;
constexpr int S4_WD = 2 * S4_HALF;
constexpr int S4_T2 = S4_WD + 2304;
constexpr int S4_T3 = S4_T2 + 1024;
constexpr int S4_STRIDE = S4_T3 + 640 + 16;
__device__ __forceinline__ uint32_t addz(uint32_t x, uint32_t z) { uint32_t r; asm volatile("add.u32 %0, %1, %2;" : "=r"(r) : "r"(x), "r"(z)); return r; }
__device__ __forceinline__ uint32_t lds16(uint32_t a) { uint32_t v; asm volatile("ld.shared.u16 %0, [%1];" : "=r"(v) : "r"(a) : "memory"); return v; }
__device__ __forceinline__ uint32_t ldsu(uint32_t a) { return __float_as_uint(lds32(a)); }

template <int E0, int NE, int KP>
__device__ __forceinline__ void s4_windows(float (&acc)[8][2][4], uint32_t ut, uint32_t tw, int rho, int w, int lane, uint32_t z) {
    const int gt = (lane >> 2) - 2 * (lane & 3), p0 = rho == 16 ? -3 : -2, c = (lane >> 3) + p0;
    uint32_t band[2][4], ta[NE][4];
    {
        const uint64_t ones = ((uint64_t)((2u << 2 * w) - 1) << 32) >> (8 * p0 + 24 - gt + rho + w);
        uint32_t f[5];
#pragma unroll
        for (int m = 0; m < 5; m++) f[m] = ((((uint32_t)(ones >> (8 * m)) & 3) * 0x8001u) & 0x10001u) * 0x3F80u;
#pragma unroll
        for (int j = 0; j < 2; j++) { band[j][0] = f[2 * j + 1]; band[j][1] = addz(f[2 * j], z); band[j][2] = f[2 * j + 2]; band[j][3] = addz(f[2 * j + 1], z); }
    }
#pragma unroll
    for (int e = 0; e < NE; e++)
        asm volatile("ld.shared.u32 %0, [%4]; ld.shared.u32 %1, [%4+%5]; ld.volatile.shared.u32 %2, [%4+%6]; ld.volatile.shared.u32 %3, [%4];"
            : "=r"(ta[e][0]), "=r"(ta[e][1]), "=r"(ta[e][2]), "=r"(ta[e][3]) : "r"(tw + 16 * (E0 + e) * KP), "n"(8 * KP), "n"(-8 * KP) : "memory");
    const uint32_t ua = ut + (c & 1) * S4_HALF + (16 + (lane & 7) + (c >> 1)) * 16;
#pragma unroll
    for (int J = 0; J < 8 - E0; J++) {
        uint32_t u0[4], u1[4];
        ldsm4(u0, ua + J * 256); ldsm4(u1, ua + J * 256 + 128);
        float s0[4], s1[4];
        mma16z(s0, band[0], u0[0], u0[1]); mma16z(s1, band[0], u1[0], u1[1]);
        mma16(s0, band[1], u0[2], u0[3]); mma16(s1, band[1], u1[2], u1[3]);
        const uint32_t b00 = pack_bf16(s0[0], s0[1]), b01 = pack_bf16(s1[0], s1[1]), b10 = pack_bf16(s0[2], s0[3]), b11 = pack_bf16(s1[2], s1[3]);
#pragma unroll
        for (int e = 0; e < NE; e++)
            if (J + E0 + e < 8) { mma16(acc[J + E0 + e][0], ta[e], b00, b01); mma16(acc[J + E0 + e][1], ta[e], b10, b11); }
    }
}
template <int D0, int D1>
__device__ __forceinline__ void s4_dense(float (&acc)[8][2][4], uint32_t ua, const uint32_t (&b0)[4], const uint32_t (&b1)[4]) {
#pragma unroll
    for (int J = 0; J < 8 - D0; J++) {
        uint32_t a[4];
        ldsm4(a, ua + J * 256);
        mma16(acc[J + D0][0], a, b0[0], b0[1]); mma16(acc[J + D0][1], a, b0[2], b0[3]);
        if (J + D1 < 8) { mma16(acc[J + D1][0], a, b1[0], b1[1]); mma16(acc[J + D1][1], a, b1[2], b1[3]); }
    }
}
__device__ __forceinline__ void s4_words(uint32_t (&b)[4], uint32_t wd) {
    asm volatile("ld.shared.u32 %0, [%4]; ld.shared.u32 %1, [%4+-32]; ld.shared.u32 %2, [%4+32]; ld.volatile.shared.u32 %3, [%4];"
        : "=r"(b[0]), "=r"(b[1]), "=r"(b[2]), "=r"(b[3]) : "r"(wd) : "memory");
}

__device__ __forceinline__ void s4_item(uint32_t sb, int cw, int lane, int item, const bf16* __restrict__ dsk, uint32_t empty, const CUtensorMap* my, uint32_t stgpar) {
    const int gt = (lane >> 2) - 2 * (lane & 3);
    const uint32_t ch = sb + S4_CH + cw * S4_STRIDE, kd = sb + S4_KD + cw * 1536;
    const __nv_bfloat162 dk = __bfloat162bfloat162(dsk[item * 8 + cw]);
    ST(item, cw, 0);
    asm volatile("st.shared.v4.u32 [%0], {%1,%1,%1,%1};" ::"r"(ch + (lane >> 4) * S4_HALF + (lane & 15) * 16), "r"(0) : "memory");
    const uint32_t tch = sb + S4_CH + (lane & 7) * S4_STRIDE + ((lane >> 3) & 1) * S4_HALF + (16 + 16 * cw + (lane >> 4)) * 16;
#pragma unroll
    for (int i = 0; i < 8; i++) {
        uint32_t x[4];
        ldsm4t(x, sb + cw * 4096 + i * 512 + lane * 16);
        stsm4(tch + i * 32, x[0], x[1], x[2], x[3]);
    }
    const uint32_t k1024 = lds16(kd + 1024);
    {
        auto st4 = [](uint32_t a, uint32_t x, uint32_t y, uint32_t u, uint32_t v) {
            asm volatile("st.shared.v4.u32 [%0], {%1,%2,%3,%4};" ::"r"(a), "r"(x), "r"(y), "r"(u), "r"(v) : "memory");
        };
        const float4 p = lds128(kd + lane * 16);
        const uint32_t p0 = __float_as_uint(p.x), p1 = __float_as_uint(p.y), p2 = __float_as_uint(p.z), p3 = __float_as_uint(p.w);
        const uint32_t pm = lane ? ldsu(kd + lane * 16 - 4) : 0;
        const uint32_t wa = ch + S4_WD + 64 + lane * 32;
        st4(wa, __byte_perm(p0, pm, 0x7610), __byte_perm(p0, 0, 0x1032), __byte_perm(p1, p0, 0x7610), __byte_perm(p1, 0, 0x1032));
        st4(wa + 16, __byte_perm(p2, p1, 0x7610), __byte_perm(p2, 0, 0x1032), __byte_perm(p3, p2, 0x7610), __byte_perm(p3, 0, 0x1032));
        const float2 q = lds64(kd + 512 + lane * 8);
        const uint32_t q0 = __float_as_uint(q.x), q1 = __float_as_uint(q.y), q2 = ldsu(kd + 520 + lane * 8), k255 = ldsu(kd + 508);
        st4(wa + 1024, lane ? __byte_perm(q0, 0, 0x1010) : __byte_perm(q0, k255, 0x7610), __byte_perm(q0, 0, 0x1010), __byte_perm(q0, 0, 0x1032), __byte_perm(q1, q0, 0x7610));
        st4(wa + 1040, __byte_perm(q1, 0, 0x1010), __byte_perm(q1, 0, 0x1010), __byte_perm(q1, 0, 0x1032), __byte_perm(q2, q1, 0x7610));
        const uint32_t k512 = lane == 4 ? lds16(kd + 768) : 0;
        if (lane < 16) st4(ch + S4_WD + (lane < 4 ? 0 : 2048) + lane * 16, k512 * 0x10001u, k512 * 0x10001u, k512 * 0x10001u, k512 << 16);
        const float2 c = lds64(kd + 768 + lane * 8), d = lds64(kd + 760 + lane * 8);
        const uint32_t c0 = __float_as_uint(c.x), c1 = __float_as_uint(c.y), c2 = ldsu(kd + 776 + lane * 8);
        const uint32_t d0 = lane ? __float_as_uint(d.x) : 0, d1 = lane ? __float_as_uint(d.y) : 0, d2 = lane ? c0 : 0;
        st4(ch + S4_T2 + 256 + lane * 16, __byte_perm(c0, d0, 0x7632), __byte_perm(c1, d1, 0x5410), __byte_perm(c1, d1, 0x7632), __byte_perm(c2, d2, 0x5410));
        const uint32_t m = lane == 31 ? 0xFFFF0000u : 0;
        st4(ch + S4_T2 + (lane < 16 ? lane : lane == 31 ? 48 : lane + 33) * 16, c0 & m, (c1 << 16) & m, c1 & m, (c2 << 16) & m);
        const float2 e = lds64(kd + 1024 + lane * 8);
        const uint32_t e0 = __float_as_uint(e.x), e1 = __float_as_uint(e.y), e2 = ldsu(kd + 1032 + lane * 8), em = ldsu(kd + 1020 + lane * 8);
        st4(ch + S4_T3 + 128 + lane * 16, __byte_perm(e0, lane ? em : 0, 0x7632), __byte_perm(e1, lane ? e0 : 0, 0x5410), __byte_perm(e1, e0, 0x7632), __byte_perm(e2, e1, 0x5410));
        if (lane < 8) st4(ch + S4_T3 + lane * 16, 0, 0, 0, 0);
    }
    bar_sync(2, 256);
    ST(item, cw, 1);
    const uint32_t z = ldsu(ch);
    float acc[8][2][4];
#pragma unroll
    for (int j = 0; j < 16; j++) acc[j >> 1][j & 1][0] = acc[j >> 1][j & 1][1] = acc[j >> 1][j & 1][2] = acc[j >> 1][j & 1][3] = 0.f;
#pragma unroll 1
    for (int r = 1; r <= 4; r++) s4_windows<2, 3, 16>(acc, ch, ch + S4_T2 + (gt - 16) * 16 + 4 * r - 4, 4 * r, 2 - (r & 1), lane, z);
    ST(item, cw, 2);
#pragma unroll 1
    for (int r = 1; r <= 2; r++) s4_windows<4, 4, 8>(acc, ch, ch + S4_T3 + (gt - 48) * 8 + 4 * r - 4, 8 * r, 2 + r, lane, z);
    ST(item, cw, 3);
    const uint32_t ua = ch + (lane >> 4) * S4_HALF + (16 + (lane & 15)) * 16, wd = ch + S4_WD + 64 + gt * 4;
#pragma unroll 1
    for (int q = 0; q < 2; q++) {
        uint32_t b0[4], b1[4];
        s4_words(b0, wd + (q + 32) * 64);
#pragma unroll
        for (int j = 0; j < 4; j++) {
            const int x = 16 * q + gt + (j == 1 ? -8 : j == 2 ? 8 : 0) - 3;
            b1[j] = addz(((unsigned)x < 2u ? k1024 : 0u) | ((unsigned)(x - 1) < 2u ? k1024 << 16 : 0u), z);
        }
        s4_dense<2, 4>(acc, ua - q * 16, b0, b1);
    }
    {
        uint32_t b0[4], b1[4], c0[4], c1[4];
        s4_words(b0, wd); s4_words(b1, wd + 1024);
#pragma unroll 1
        for (int q = 0; q < 16; q += 2) {
            s4_words(c0, wd + q * 64 + 64); s4_words(c1, wd + q * 64 + 64 + 1024);
            s4_dense<0, 1>(acc, ua - q * 16, b0, b1);
            s4_words(b0, wd + q * 64 + 128); s4_words(b1, wd + q * 64 + 128 + 1024);
            s4_dense<0, 1>(acc, ua - q * 16 - 16, c0, c1);
            if (q == S4REL && lane == 0) { mbar_arrive(empty); mbar_arrive(empty + 8); }
        }
    }
    ST(item, cw, 4);
    mbar_wait(empty + 72, stgpar);
    if (lane == 0) asm volatile("cp.async.bulk.wait_group.read 0;" ::: "memory");
    __syncwarp();
#pragma unroll
    for (int I = 0; I < 8; I++) {
        uint32_t u[4];
        ldsm4(u, ua + I * 256);
#pragma unroll
        for (int j = 0; j < 4; j++) {
            const uint32_t y = pack_bf16(acc[I][j >> 1][2 * (j & 1)], acc[I][j >> 1][2 * (j & 1) + 1]);
            const __nv_bfloat162 r = __hadd2_rn(*(const __nv_bfloat162*)&y, __hmul2_rn(*(const __nv_bfloat162*)&u[j], dk));
            u[j] = *(const uint32_t*)&r;
        }
        stsm4(ua + I * 256, u[0], u[1], u[2], u[3]);
    }
    bar_sync(2, 256);
#pragma unroll
    for (int i = 0; i < 8; i++) {
        uint32_t y[4];
        ldsm4t(y, tch + i * 32);
        stsm4(sb + G_STG + cw * 4096 + i * 512 + lane * 16, y[0], y[1], y[2], y[3]);
    }
    asm volatile("fence.proxy.async.shared::cta;" ::: "memory");
    __syncwarp();
    if (lane == 0) {
        mbar_arrive(empty + 16); mbar_arrive(empty + 24);
        tma2d_store(my, sb + G_STG + cw * 4096, DM + item * 8, cw * 256);
        asm volatile("cp.async.bulk.commit_group;" ::: "memory");
    }
    ST(item, cw, 5);
}

__global__ void __launch_bounds__(384, 1)
worker_kernel(const __grid_constant__ CUtensorMap mx, const __grid_constant__ CUtensorMap mq, const __grid_constant__ CUtensorMap mk,
              const __grid_constant__ CUtensorMap mv, const __grid_constant__ CUtensorMap mo,
              const __grid_constant__ CUtensorMap mout, const __grid_constant__ CUtensorMap mu, const __grid_constant__ CUtensorMap my,
              const __grid_constant__ CUtensorMap mkx, const __grid_constant__ CUtensorMap mvx, const __grid_constant__ CUtensorMap mkm,
              const __grid_constant__ CUtensorMap mvm, const bf16* __restrict__ dsk) {
    extern __shared__ unsigned char smem_raw[];
    const uint32_t sb = (smem_u32(smem_raw) + 1023) & ~1023u;
    const uint32_t full = sb + G_BAR, empty = full + 32, ifull = full + 64, iempty = full + 80, islot = full + 96, stgbar = full + 104, sigbar = full + 112, sigslot = full + 120;
    const int tid = threadIdx.x, wg = tid >> 7, lane = tid & 31;
    if (TMP && tid >= 64 && tid < 76) {
        const CUtensorMap* maps[12] = {&mx, &mq, &mk, &mv, &mo, &mout, &mu, &my, &mkx, &mvx, &mkm, &mvm};
        const CUtensorMap* m = maps[0];
#pragma unroll
        for (int j = 1; j < 12; j++) if (tid - 64 == j) m = maps[j];
        asm volatile("prefetch.tensormap [%0];" ::"l"(m) : "memory");
    }
    int q0 = blockIdx.x;
    const int wide0 = q0 - ((int)gridDim.x - O_WIDE * 4);
    if (tid == 0) {
        if (q0 >= 32 && wide0 < 0) q0 = 32 + atomicAdd(g_ctr + C_NEXT, 1);
        for (int i = 0; i < 6; i++) { mbar_init(full + n6_bar(i), 1); mbar_init(empty + n6_bar(i), 8); }
        for (int i = 0; i < 2; i++) { mbar_init(ifull + 8 * i, 1); mbar_init(iempty + 8 * i, 8); }
        mbar_init(sigbar, 8); mbar_init(stgbar, 1);
        asm volatile("fence.proxy.async.shared::cta;" ::: "memory");
    }
    __syncthreads();
    if (wg == 0) {
        reg_dec<40>();
        if (tid >= 32 && tid < 64) {
            for (int n = 0;; n++) {
                mbar_wait_long(sigbar, n & 1);
                int item; asm volatile("ld.shared.u32 %0, [%1];" : "=r"(item) : "r"(sigslot + 4 * (n & 1)) : "memory");
                const int type = item >> 16, b = (item >> 8) & 255, i = item & 255;
                if (type == IT_END) break;
                if (type == IT_QA) {
                    if (lane == 0) {
                        for (int j = 0; j < 8; j++) {
                            const uint32_t src = sb + (j >= 4 ? G_STG + (j & 1) * 16384 : 3 * G_STAGE + (j & 1) * 20480) + ((j >> 1) & 1) * 8192;
                            asm volatile("cp.async.bulk.global.shared::cta.bulk_group [%0], [%1], 8192;"
                                ::"l"(g_ox + (size_t)(b * 64 + i * 4 + ((j >> 1) ^ 2)) * 8192 + (j & 1) * 4096), "r"(src) : "memory");
                            if ((j & 3) == 3) asm volatile("cp.async.bulk.commit_group;" ::: "memory");
                        }
                        asm volatile("cp.async.bulk.wait_group.read 1;" ::: "memory");
                        asm volatile("mbarrier.arrive.shared.b64 _, [%0], 8;" ::"r"(empty + 24) : "memory");
                        asm volatile("cp.async.bulk.wait_group 0;" ::: "memory");
                        mbar_arrive(stgbar);
                        asm volatile("fence.proxy.async.global;" ::: "memory");
                    }
                    __syncwarp();
                }
                if (type == IT_KV) { if (lane < 6) red_release(g_kvf + ((i & 15) * 6 + lane) * 16 + b, 1); }
                else if (lane == 0) red_release(g_ctr + C_QA_DONE + b, 1 << i);
            }
        } else if (tid < 32) {
            int it = 0;
            if (!KVN) asm volatile("griddepcontrol.wait;" ::: "memory");
            for (int n = 0;; n++) {
                int item = 0;
                if (lane == 0) {
                    if (n) q0 = 32 + atomicAdd(g_ctr + C_NEXT, 1);
                    item = n == 0 && wide0 >= 0 ? (IT_O << 16) | ((wide0 >> 2) << 8) | (wide0 & 3) : queue_item(q0);
                }
                item = __shfl_sync(0xffffffffu, item, 0);
                if (lane == 0) {
                    mbar_wait(iempty + 8 * (n & 1), ((n >> 1) & 1) ^ 1);
                    asm volatile("st.shared.u32 [%0], %1;" ::"r"(islot + 4 * (n & 1)), "r"(item) : "memory");
                    mbar_arrive(ifull + 8 * (n & 1));
                    const int type = item >> 16, b = (item >> 8) & 255, i = item & 255;
                    if (type == IT_QA || type == IT_KV) {
                        const CUtensorMap* mw = type == IT_QA ? &mq : i < 16 ? &mk : &mv;
                        bool ready = false;
                        for (int kb = 0; kb < 16; kb++, it++) {
                            const int st = it & 3;
                            mbar_wait(empty + 8 * st, ((it >> 2) & 1) ^ 1);
                            mbar_expect(full + 8 * st, G_STAGE);
                            const uint32_t a = sb + st * G_STAGE;
                            tma2d(a, &mx, kb * 64, b * 128, full + 8 * st);
                            tma3d(a + 16384, mw, 0, kb * 64, (i & 15) * 4, full + 8 * st);
                            tma3d(a + 32768, mw, 0, kb * 64, (i & 15) * 4 + 2, full + 8 * st);
                            if (type == IT_QA && kb == 3) ready = ld_acq(g_ctr + C_CHAIN + b) >= 96;
                            if (type == IT_QA && kb >= 3 && kb < 11) {
                                const size_t sh = (b * 4 + ((kb - 3) & 3)) * NH + i * 2;
                                asm volatile("cp.async.bulk.prefetch.L2.global [%0], 16384;" ::"l"((kb >= 7 ? g_vx : g_kx) + sh * 4096) : "memory");
                                if (ready) asm volatile("cp.async.bulk.prefetch.L2.global [%0], 4096;" ::"l"((kb >= 7 ? g_vm : g_km) + sh * 1024) : "memory");
                            }
                        }
                    }
                    if (type == IT_QA) {
                        wait_ctr(g_ctr + C_CHAIN + b, 96);
                        asm volatile("fence.proxy.async.global;" ::: "memory");
                        for (int st = 0; st < 4; st++, it++) {
                            mbar_wait(empty + 8 * st, ((it >> 2) & 1) ^ 1);
                            mbar_expect(full + 8 * st, 4 * 10240);
                            for (int g2 = 0; g2 < 2; g2++) {
                                tma3d(sb + st * G_STAGE + g2 * 20480, st < 2 ? &mkx : &mvx, 0, b * 4 + g2 * 2, (i * 2 + (st & 1)) * 16, full + 8 * st);
                                tma3d(sb + st * G_STAGE + g2 * 20480 + 16384, st < 2 ? &mkm : &mvm, 0, b * 4 + g2 * 2, (i * 2 + (st & 1)) * 16, full + 8 * st);
                            }
                        }
                    } else if (type == IT_O) {
                        const bool wide = b < O_WIDE;
                        int done = 0;
                        const int ns = wide ? 4 : 6;
                        for (int kb = 0, st = 0, r = 0; kb < 64; kb++) {
                            const uint32_t bo = n6_bar(st);
                            mbar_wait(empty + bo, (((st < 4 ? it >> 2 : 0) + r) & 1) ^ 1);
                            mbar_expect(full + bo, wide ? G_STAGE : 32768);
                            tma3d(sb + n6_b(st), &mo, 0, kb * 64, wide ? i * 4 : i * 2, full + bo);
                            if (wide) tma3d(sb + n6_b(st) + 16384, &mo, 0, kb * 64, i * 4 + 2, full + bo);
                            if (!(done >> (kb >> 2) & 1)) {
                                for (int sp = 0; sp < (1 << 20) && !((done = ld_acq(g_ctr + C_QA_DONE + b)) >> (kb >> 2) & 1); sp++) __nanosleep(64);
                                asm volatile("fence.proxy.async.global;" ::: "memory");
                            }
                            bulk_load(sb + n6_a(st), g_ox + (size_t)(b * 64 + kb) * 8192, 16384, full + bo);
                            if (++st == ns) { st = 0; r++; }
                        }
                        it += wide ? 64 : 44;
                    } else if (type == IT_S4) {
                        wait_ctr(g_ctr + C_CHAIN, 96);
                        asm volatile("fence.proxy.async.global;" ::: "memory");
                        mbar_wait(empty, ((it >> 2) & 1) ^ 1);
                        mbar_expect(full, 32768 + 12288);
                        bulk_load(sb + S4_KD, g_kd + i * 8 * 768, 12288, full);
                        for (int j = 0; j < 8; j++) tma2d(sb + j * 4096, &mu, i * 8, j * 256, full);
                        for (int st = 1; st < 4; st++) { mbar_wait(empty + 8 * st, ((it >> 2) & 1) ^ 1); mbar_arrive(full + 8 * st); }
                        it += 4;
                        mbar_wait_long(empty, ((it >> 2) & 1) ^ 1);
                    }
                }
                __syncwarp();
                if (item >> 16 == IT_END) break;
            }
            asm volatile("griddepcontrol.wait;" ::: "memory");
        }
    } else {
        reg_inc<232>();
        const int wu = __shfl_sync(0xffffffffu, tid >> 5, 0);
        const int wgi = (wu >> 2) - 1, wi = wu & 3;
        int it = 0, nqa = 0, nsig = 0, n = 0, item;
        auto next_item = [&]() {
            mbar_wait_long(ifull + 8 * (n & 1), (n >> 1) & 1);
            asm volatile("ld.shared.u32 %0, [%1];" : "=r"(item) : "r"(islot + 4 * (n & 1)) : "memory");
            __syncwarp();
            if (lane == 0) mbar_arrive(iempty + 8 * (n & 1));
        };
        auto signal = [&](int what) {
            if (tid == 128) asm volatile("st.shared.u32 [%0], %1;" ::"r"(sigslot + 4 * (nsig & 1)), "r"(what) : "memory");
            __syncwarp();
            if (lane == 0) mbar_arrive(sigbar);
            nsig++;
        };
        next_item();
        if (item >> 16 == IT_KV) {
            float acc[128];
            uint32_t pk[64];
            uint32_t* dst = nullptr;
            int prev = 0;
            do {
                WLOG(0);
#pragma unroll
                for (int kb = 0; kb < 16; kb++, it++) {
                    const int st = kb & 3;
                    mbar_wait(full + 8 * st, (it >> 2) & 1);
                    const uint64_t da = mkdesc(sb + st * G_STAGE + wgi * 8192, 16, 1024, 1);
                    const uint64_t db = mkdesc(sb + st * G_STAGE + 16384, 8192, 1024, 1);
                    wg_fence();
#pragma unroll
                    for (int k = 0; k < 4; k++) wgmma256(acc, da + k * 2, db + k * 128, kb | k);
                    wg_commit();
                    if (kb < KVS && dst) {
#pragma unroll
                        for (int j = kb * (64 / KVS); j < (kb + 1) * (64 / KVS); j++) st_out(dst + (j >> 1) * 128 + (j & 1) * 32, pk[j]);
                        if (kb == KVS - 1) signal(prev);
                    }
                    if (kb > 0) {
                        wg_wait<1>();
                        if (lane == 0) mbar_arrive(empty + 8 * ((kb - 1) & 3));
                    }
                }
                wg_wait<0>();
                if (lane == 0) mbar_arrive(empty + 8 * 3);
#pragma unroll
                for (int j = 0; j < 64; j++) pk[j] = pack_bf16(acc[2 * j], acc[2 * j + 1]);
                const int row = ((item >> 8) & 255) * 128 + wgi * 64 + wi * 16, nt = item & 255;
                dst = (uint32_t*)(nt < 16 ? g_kx : g_vx) + (size_t)((row >> 5) * 512 + (nt & 15) * 32) * 128 + (row & 31) * 4 + lane;
                prev = item;
                if (n == 0) {
#pragma unroll
                    for (int j = 0; j < 64; j++) dst[(j >> 1) * 128 + (j & 1) * 32] = pk[j];
                    signal(prev);
                    dst = nullptr;
                }
                WLOG(1);
                n++;
                next_item();
            } while (item >> 16 == IT_KV);
            if (dst) {
#pragma unroll
                for (int j = 0; j < 64; j++) dst[(j >> 1) * 128 + (j & 1) * 32] = pk[j];
                signal(prev);
            }
        }
        for (;; n++, next_item()) {
            const int type = item >> 16, b = (item >> 8) & 255, i = item & 255;
            const int lane = (tid & 31) + (item >> 24), wgi = (wu >> 2) - 1 + __shfl_sync(0xffffffffu, item >> 24, 0), wi = wu & 3;
            WLOG(0);
            if (type == IT_QA) {
                float acc[128];
                ST(sid, cw, 0);
                ST(sid, cw, 1);
                mainloop<256, 16, false>(acc, sb, wgi, full, empty, it, lane == 0);
                ST(sid, cw, 2);
                uint32_t q0[32], q1[32];
#pragma unroll
                for (int j = 0; j < 32; j++) { q0[j] = pack_bf16(acc[2 * j], acc[2 * j + 1]); q1[j] = pack_bf16(acc[64 + 2 * j], acc[65 + 2 * j]); }
                const uint32_t par = (it >> 2) & 1, so = sb + wgi * 20480;
                float sx0[32] = {}, sm0[8] = {}, sx1[32] = {}, sm1[8] = {};
                uint32_t p0[20], p1[20];
                if (lane == 0) asm volatile("cp.async.bulk.wait_group.read 0;" ::: "memory");
                mbar_wait(stgbar, (nqa++ & 1) ^ 1);
                bar_sync(3 + wgi, 128);
                mbar_wait_long(full, par);
                ST(sid, cw, 3);
                attn_scores(sx0, sm0, q0, so);
                ST(sid, cw, 7);
                mbar_wait(full + 8, par);
                attn_scores(sx1, sm1, q1, so + G_STAGE);
                float o0[64] = {}, o1[64] = {};
                if (ATT2) {
                    ST(sid, cw, 8);
                    wg_wait<0>();
                    ST(sid, cw, 9);
                    if (lane == 0) { mbar_arrive(empty); mbar_arrive(empty + 8); }
                    attn_softmax(p0, sx0, sm0, wi, lane);
                    attn_softmax(p1, sx1, sm1, wi, lane);
                    ST(sid, cw, 10);
                    mbar_wait(full + 16, par);
                    ST(sid, cw, 11);
                    attn_pv(o0, p0, so + 2 * G_STAGE);
                    ST(sid, cw, 4);
                } else {
                    wg_wait<1>();
                    if (lane == 0) mbar_arrive(empty);
                    attn_softmax(p0, sx0, sm0, wi, lane);
                    mbar_wait(full + 16, par);
                    attn_pv(o0, p0, so + 2 * G_STAGE);
                    wg_wait<1>();
                    if (lane == 0) mbar_arrive(empty + 8);
                    ST(sid, cw, 4);
                    attn_softmax(p1, sx1, sm1, wi, lane);
                }
                mbar_wait(full + 24, par);
                attn_pv(o1, p1, so + 3 * G_STAGE);
                wg_wait<1>();
                if (lane == 0) mbar_arrive(empty + 16);
                ST(sid, cw, 5);
                const uint32_t da = (wi * 2 + ((lane >> 3) & 1)) * 1024 + (lane >> 4) * 128 + (lane & 7) * 16;
                attn_stage(o0, sb + G_STG + wgi * 16384 + da);
                wg_wait<0>();
                bar_sync(3 + wgi, 128);
                attn_stage(o1, so + 3 * G_STAGE + da);
                asm volatile("fence.proxy.async.shared::cta;" ::: "memory");
                ST(sid, cw, 6);
                signal(item);
                it += 4;
            } else if (type == IT_O) {
                ST(b * 8 + i, wgi * 4 + wi, 8);
                mbar_wait_long(full, (it >> 2) & 1);
                ST(b * 8 + i, wgi * 4 + wi, 9);
                if (b < O_WIDE) o_item<256>(sb, wgi, wi, lane, full, empty, it, &mout, b * 128, i * 256, (nqa & 1) ^ 1);
                else o_item<128>(sb, wgi, wi, lane, full, empty, it, &mout, b * 128, i * 128, (nqa & 1) ^ 1);
            } else if (type == IT_S4) {
                mbar_wait_long(full, (it >> 2) & 1);
                mbar_wait(full + 24, (it >> 2) & 1);
                s4_item(sb, wgi * 4 + wi, lane, i, dsk, empty, &my, (nqa & 1) ^ 1);
                it += 4;
            } else break;
            WLOG(1);
        }
        bar_sync(2, 256);
        signal(item);
        if (lane == 0) asm volatile("cp.async.bulk.wait_group 0;" ::: "memory");
    }
}

typedef CUresult (*EncodeFn)(CUtensorMap*, CUtensorMapDataType, cuuint32_t, void*, const cuuint64_t*, const cuuint64_t*, const cuuint32_t*,
                             const cuuint32_t*, CUtensorMapInterleave, CUtensorMapSwizzle, CUtensorMapL2promotion, CUtensorMapFloatOOBfill);
static EncodeFn get_encode() {
    void* fn = nullptr; cudaDriverEntryPointQueryResult st;
    cudaGetDriverEntryPoint("cuTensorMapEncodeTiled", &fn, cudaEnableDefault, &st);
    return (EncodeFn)fn;
}
static void map_act(EncodeFn enc, CUtensorMap* m, const void* p, int rows, int cols, int boxr) {
    cuuint64_t dim[2] = {(cuuint64_t)cols, (cuuint64_t)rows}, str[1] = {(cuuint64_t)cols * 2};
    cuuint32_t box[2] = {64, (cuuint32_t)boxr}, es[2] = {1, 1};
    enc(m, CU_TENSOR_MAP_DATA_TYPE_BFLOAT16, 2, (void*)p, dim, str, box, es, CU_TENSOR_MAP_INTERLEAVE_NONE, CU_TENSOR_MAP_SWIZZLE_128B,
        CU_TENSOR_MAP_L2_PROMOTION_L2_128B, CU_TENSOR_MAP_FLOAT_OOB_FILL_NONE);
}
static void map_w(EncodeFn enc, CUtensorMap* m, const void* p, int k, int n) {
    cuuint64_t dim[3] = {64, (cuuint64_t)k, (cuuint64_t)n / 64}, str[2] = {(cuuint64_t)n * 2, 128};
    cuuint32_t box[3] = {64, 64, 2}, es[3] = {1, 1, 1};
    enc(m, CU_TENSOR_MAP_DATA_TYPE_BFLOAT16, 3, (void*)p, dim, str, box, es, CU_TENSOR_MAP_INTERLEAVE_NONE, CU_TENSOR_MAP_SWIZZLE_128B,
        CU_TENSOR_MAP_L2_PROMOTION_L2_256B, CU_TENSOR_MAP_FLOAT_OOB_FILL_NONE);
}

static void map_kv(EncodeFn enc, CUtensorMap* m, void* p, int n) {
    cuuint64_t dim[3] = {(cuuint64_t)n, NSEG, 512}, str[2] = {(cuuint64_t)n * 1024, (cuuint64_t)n * 2};
    cuuint32_t box[3] = {(cuuint32_t)n, 2, 16}, es[3] = {1, 1, 1};
    enc(m, CU_TENSOR_MAP_DATA_TYPE_BFLOAT16, 3, p, dim, str, box, es, CU_TENSOR_MAP_INTERLEAVE_NONE, CU_TENSOR_MAP_SWIZZLE_NONE,
        CU_TENSOR_MAP_L2_PROMOTION_NONE, CU_TENSOR_MAP_FLOAT_OOB_FILL_NONE);
}
static void map_box(EncodeFn enc, CUtensorMap* m, const void* p, int rows, int ld, int boxc, int boxr, CUtensorMapSwizzle sw,
                    CUtensorMapL2promotion promo = CU_TENSOR_MAP_L2_PROMOTION_NONE) {
    cuuint64_t dim[2] = {(cuuint64_t)ld, (cuuint64_t)rows}, str[1] = {(cuuint64_t)ld * 2};
    cuuint32_t box[2] = {(cuuint32_t)boxc, (cuuint32_t)boxr}, es[2] = {1, 1};
    enc(m, CU_TENSOR_MAP_DATA_TYPE_BFLOAT16, 2, (void*)p, dim, str, box, es, CU_TENSOR_MAP_INTERLEAVE_NONE, sw,
        promo, CU_TENSOR_MAP_FLOAT_OOB_FILL_NONE);
}

extern "C" void kernel_launch(void* const* d_in, const int* in_sizes, int n_in, void* d_out, int out_size) {
    const bf16* x = (const bf16*)d_in[0];
    const bf16* mem0 = (const bf16*)d_in[1];
    const bf16 *Wq = (const bf16*)d_in[2], *Wk = (const bf16*)d_in[3], *Wv = (const bf16*)d_in[4], *Wo = (const bf16*)d_in[5];
    static EncodeFn enc = nullptr;
    static int nsm = 0;
    static void* kv[4];
    if (!enc) {
        enc = get_encode();
        cudaGetSymbolAddress(&kv[0], g_kx); cudaGetSymbolAddress(&kv[1], g_vx); cudaGetSymbolAddress(&kv[2], g_km); cudaGetSymbolAddress(&kv[3], g_vm);
        cudaDeviceGetAttribute(&nsm, cudaDevAttrMultiProcessorCount, 0);
        cudaFuncSetAttribute(chain_kernel, cudaFuncAttributeMaxDynamicSharedMemorySize, CH_SMEM);
        cudaFuncSetAttribute(worker_kernel, cudaFuncAttributeMaxDynamicSharedMemorySize, G_SMEM);
    }
    CUtensorMap mx, mq, mk, mv, mo, mout, mu, my;
    map_act(enc, &mx, x, S_LEN, DM, 128);
    map_w(enc, &mq, Wq, DM, HD); map_w(enc, &mk, Wk, DM, HD); map_w(enc, &mv, Wv, DM, HD); map_w(enc, &mo, Wo, HD, DM);
    map_box(enc, &mout, d_out, S_LEN, 2 * DM, 64, 16, CU_TENSOR_MAP_SWIZZLE_128B);
    map_box(enc, &mu, d_in[7], S_LEN, DM, 8, 256, CU_TENSOR_MAP_SWIZZLE_NONE, (CUtensorMapL2promotion)PROMU);
    map_box(enc, &my, d_out, S_LEN, 2 * DM, 8, 256, CU_TENSOR_MAP_SWIZZLE_NONE);
    CUtensorMap mkx, mvx, mkm, mvm;
    map_kv(enc, &mkx, kv[0], 256); map_kv(enc, &mvx, kv[1], 256); map_kv(enc, &mkm, kv[2], 64); map_kv(enc, &mvm, kv[3], 64);
    CUtensorMap cq, ck, cv, co;
    map_box(enc, &cq, Wq, DM, HD, 32, 32, CU_TENSOR_MAP_SWIZZLE_64B, (CUtensorMapL2promotion)PROMO); map_box(enc, &ck, Wk, DM, HD, 32, 32, CU_TENSOR_MAP_SWIZZLE_64B, (CUtensorMapL2promotion)PROMO);
    map_box(enc, &cv, Wv, DM, HD, 32, 32, CU_TENSOR_MAP_SWIZZLE_64B, (CUtensorMapL2promotion)PROMO); map_box(enc, &co, Wo, HD, DM, 32, 16, CU_TENSOR_MAP_SWIZZLE_64B, (CUtensorMapL2promotion)PROMO);
    S4Params P = {(const bf16*)d_in[8], (const bf16*)d_in[9], (const bf16*)d_in[10], (const bf16*)d_in[11],
                  (const bf16*)d_in[12], (const bf16*)d_in[13], (const bf16*)d_in[14], (const bf16*)d_in[15]};
    int aware = 1;
    cudaLaunchAttribute at[1];
    at[0].id = cudaLaunchAttributeProgrammaticStreamSerialization;
    at[0].val.programmaticStreamSerializationAllowed = 1;
    cudaLaunchConfig_t cfg = {};
    cfg.stream = cudaStreamPerThread;
    cfg.gridDim = dim3(96); cfg.blockDim = dim3(CH_THREADS); cfg.dynamicSmemBytes = CH_SMEM;
    cudaLaunchKernelEx(&cfg, chain_kernel, cq, ck, cv, co, Wq, Wk, Wv, mem0, P, aware);
    cfg.attrs = at; cfg.numAttrs = 1;
    cfg.gridDim = dim3(nsm); cfg.blockDim = dim3(384); cfg.dynamicSmemBytes = G_SMEM;
    cudaLaunchKernelEx(&cfg, worker_kernel, mx, mq, mk, mv, mo, mout, mu, my, mkx, mvx, mkm, mvm, P.dsk);
}
```

```cpp
#include <cuda.h>
#include <cuda_runtime.h>
#include <cuda_bf16.h>
#include <stdint.h>
#include <stdio.h>
#include <string.h>

typedef __nv_bfloat16 bf16;

constexpr int S_LEN = 2048, DM = 1024, NH = 32, DH = 128, HD = 4096, NSEG = 64;
constexpr uint32_t SENT = 0xFFFFFFFFu;
constexpr int SPIN_LIMIT = 1 << 18;
#define REALL 0

__device__ __align__(1024) bf16 g_kx[S_LEN * HD];
__device__ __align__(1024) bf16 g_vx[S_LEN * HD];
__device__ __align__(1024) bf16 g_ox[S_LEN * HD];
__device__ __align__(1024) bf16 g_km[NSEG * NH * 8 * DH];
__device__ __align__(1024) bf16 g_vm[NSEG * NH * 8 * DH];
__device__ __align__(1024) bf16 g_kd[DM * 768 + 8192];
__device__ __align__(1024) char g_ring[2 << 20];
__device__ int g_kvf[96 * 16];
constexpr int C_NEXT = 0, C_CHAIN = 32, C_QA_DONE = 64, N_CTR = 96;
__device__ int g_ctr[N_CTR];

__device__ __forceinline__ uint32_t smem_u32(const void* p) { return (uint32_t)__cvta_generic_to_shared(p); }
__device__ __forceinline__ uint32_t clk() { uint32_t c; asm volatile("mov.u32 %0, %%clock;" : "=r"(c)::"memory"); return c; }
__device__ __forceinline__ uint32_t pack_bf16(float lo, float hi) {
    uint32_t r; asm("cvt.rn.bf16x2.f32 %0, %1, %2;" : "=r"(r) : "f"(hi), "f"(lo)); return r;
}
__device__ __forceinline__ uint32_t movm(uint32_t a) {
    uint32_t d; asm volatile("movmatrix.sync.aligned.m8n8.trans.b16 %0, %1;" : "=r"(d) : "r"(a)); return d;
}
__device__ __forceinline__ void mma16(float (&d)[4], const uint32_t (&a)[4], uint32_t b0, uint32_t b1) {
    asm volatile("mma.sync.aligned.m16n8k16.row.col.f32.bf16.bf16.f32 {%0,%1,%2,%3}, {%4,%5,%6,%7}, {%8,%9}, {%0,%1,%2,%3};"
        : "+f"(d[0]), "+f"(d[1]), "+f"(d[2]), "+f"(d[3]) : "r"(a[0]), "r"(a[1]), "r"(a[2]), "r"(a[3]), "r"(b0), "r"(b1));
}
__device__ __forceinline__ void mma16z(float (&d)[4], const uint32_t (&a)[4], uint32_t b0, uint32_t b1) {
    asm volatile("mma.sync.aligned.m16n8k16.row.col.f32.bf16.bf16.f32 {%0,%1,%2,%3}, {%4,%5,%6,%7}, {%8,%9}, {%10,%10,%10,%10};"
        : "=f"(d[0]), "=f"(d[1]), "=f"(d[2]), "=f"(d[3]) : "r"(a[0]), "r"(a[1]), "r"(a[2]), "r"(a[3]), "r"(b0), "r"(b1), "f"(0.f));
}
__device__ __forceinline__ void mma8z(float (&d)[4], uint32_t a0, uint32_t a1, uint32_t b0) {
    asm volatile("mma.sync.aligned.m16n8k8.row.col.f32.bf16.bf16.f32 {%0,%1,%2,%3}, {%4,%5}, {%6}, {%7,%7,%7,%7};"
        : "=f"(d[0]), "=f"(d[1]), "=f"(d[2]), "=f"(d[3]) : "r"(a0), "r"(a1), "r"(b0), "f"(0.f));
}
__device__ __forceinline__ void ldsm4t(uint32_t (&r)[4], uint32_t addr) {
    asm volatile("ldmatrix.sync.aligned.m8n8.x4.trans.shared.b16 {%0,%1,%2,%3}, [%4];"
        : "=r"(r[0]), "=r"(r[1]), "=r"(r[2]), "=r"(r[3]) : "r"(addr) : "memory");
}
__device__ __forceinline__ void ldsm4(uint32_t (&r)[4], uint32_t addr) {
    asm volatile("ldmatrix.sync.aligned.m8n8.x4.shared.b16 {%0,%1,%2,%3}, [%4];"
        : "=r"(r[0]), "=r"(r[1]), "=r"(r[2]), "=r"(r[3]) : "r"(addr) : "memory");
}
__device__ __forceinline__ float lds32(uint32_t a) {
    float v; asm volatile("ld.shared.f32 %0, [%1];" : "=f"(v) : "r"(a) : "memory"); return v;
}
__device__ __forceinline__ void st_async1(uint32_t dst, float v, uint32_t bar) {
    asm volatile("st.async.shared::cluster.mbarrier::complete_tx::bytes.f32 [%0], %1, [%2];" ::"r"(dst), "f"(v), "r"(bar) : "memory");
}
__device__ __forceinline__ void st_async2(uint32_t dst, float x, float y, uint32_t bar) {
    asm volatile("st.async.shared::cluster.mbarrier::complete_tx::bytes.v2.f32 [%0], {%1,%2}, [%3];" ::"r"(dst), "f"(x), "f"(y), "r"(bar) : "memory");
}
__device__ __forceinline__ void mma8(float (&d)[4], uint32_t a0, uint32_t a1, uint32_t b0) {
    asm volatile("mma.sync.aligned.m16n8k8.row.col.f32.bf16.bf16.f32 {%0,%1,%2,%3}, {%4,%5}, {%6}, {%0,%1,%2,%3};"
        : "+f"(d[0]), "+f"(d[1]), "+f"(d[2]), "+f"(d[3]) : "r"(a0), "r"(a1), "r"(b0));
}
__device__ __forceinline__ void cp16(uint32_t dst, const void* src) {
    asm volatile("cp.async.cg.shared.global [%0], [%1], 16;" ::"r"(dst), "l"(src) : "memory");
}
__device__ __forceinline__ void sts128(uint32_t a, const float (&v)[4]) {
    asm volatile("st.shared.v4.f32 [%0], {%1,%2,%3,%4};" ::"r"(a), "f"(v[0]), "f"(v[1]), "f"(v[2]), "f"(v[3]) : "memory");
}
__device__ __forceinline__ float4 lds128(uint32_t a) {
    float4 v; asm volatile("ld.shared.v4.f32 {%0,%1,%2,%3}, [%4];" : "=f"(v.x), "=f"(v.y), "=f"(v.z), "=f"(v.w) : "r"(a) : "memory"); return v;
}
__device__ __forceinline__ void sts64(uint32_t a, float x, float y) {
    asm volatile("st.shared.v2.f32 [%0], {%1,%2};" ::"r"(a), "f"(x), "f"(y) : "memory");
}
__device__ __forceinline__ float2 lds64(uint32_t a) {
    float2 v; asm volatile("ld.shared.v2.f32 {%0,%1}, [%2];" : "=f"(v.x), "=f"(v.y) : "r"(a) : "memory"); return v;
}
__device__ __forceinline__ void bar_sync(int id, int n) { asm volatile("bar.sync %0, %1;" ::"r"(id), "r"(n) : "memory"); }
__device__ __forceinline__ void bar_arrive(int id, int n) { asm volatile("bar.arrive %0, %1;" ::"r"(id), "r"(n) : "memory"); }
__device__ __forceinline__ uint32_t mapa(uint32_t a, uint32_t r) {
    uint32_t o; asm("mapa.shared::cluster.u32 %0, %1, %2;" : "=r"(o) : "r"(a), "r"(r)); return o;
}
__device__ __forceinline__ void st_async4(uint32_t dst, float4 v, uint32_t bar) {
    asm volatile("st.async.shared::cluster.mbarrier::complete_tx::bytes.v4.f32 [%0], {%1,%2,%3,%4}, [%5];"
        ::"r"(dst), "f"(v.x), "f"(v.y), "f"(v.z), "f"(v.w), "r"(bar) : "memory");
}
__device__ __forceinline__ void mbar_init(uint32_t bar, int n) { asm volatile("mbarrier.init.shared.b64 [%0], %1;" ::"r"(bar), "r"(n) : "memory"); }
__device__ __forceinline__ void mbar_expect(uint32_t bar, int bytes) {
    asm volatile("mbarrier.arrive.expect_tx.shared.b64 _, [%0], %1;" ::"r"(bar), "r"(bytes) : "memory");
}
__device__ __forceinline__ void bulk_load(uint32_t dst, const void* src, int bytes, uint32_t bar) {
    asm volatile("cp.async.bulk.shared::cluster.global.mbarrier::complete_tx::bytes [%0], [%1], %2, [%3];"
        ::"r"(dst), "l"(src), "r"(bytes), "r"(bar) : "memory");
}
__device__ __forceinline__ bool mbar_try(uint32_t bar, uint32_t par) {
    uint32_t ok;
    asm volatile("{.reg .pred p; mbarrier.try_wait.parity.shared::cta.b64 p, [%1], %2; selp.u32 %0, 1, 0, p;}"
        : "=r"(ok) : "r"(bar), "r"(par) : "memory");
    return ok;
}
__device__ __forceinline__ bool mbar_test(uint32_t bar, uint32_t par) {
    uint32_t ok;
    asm volatile("{.reg .pred p; mbarrier.test_wait.parity.shared::cta.b64 p, [%1], %2; selp.u32 %0, 1, 0, p;}"
        : "=r"(ok) : "r"(bar), "r"(par) : "memory");
    return ok;
}
__device__ __forceinline__ int ld_acq(const int* p) { int v; asm volatile("ld.acquire.gpu.global.s32 %0, [%1];" : "=r"(v) : "l"(p) : "memory"); return v; }
__device__ __forceinline__ void red_release(int* p, int v) { asm volatile("red.release.gpu.global.add.s32 [%0], %1;" ::"l"(p), "r"(v) : "memory"); }
__device__ __forceinline__ void fence_gpu() { asm volatile("fence.acq_rel.gpu;" ::: "memory"); }
__device__ __forceinline__ void wait_ctr(const int* p, int n) {
    for (int it = 0; it < (1 << 20) && ld_acq(p) < n; it++) __nanosleep(64);
}
__device__ __forceinline__ void mbar_wait(uint32_t bar, uint32_t par) {
    if (!mbar_try(bar, par))
        for (int it = 0; it < SPIN_LIMIT && !mbar_try(bar, par); it++) {}
}
__device__ __forceinline__ void mbar_wait_long(uint32_t bar, uint32_t par) {
    for (int it = 0; it < (1 << 24) && !mbar_try(bar, par); it++) {}
}
__device__ __forceinline__ float4 add4(float4 a, float4 b) { return make_float4(a.x + b.x, a.y + b.y, a.z + b.z, a.w + b.w); }
__device__ __forceinline__ float ex2(float x) { float y; asm("ex2.approx.ftz.f32 %0, %1;" : "=f"(y) : "f"(x)); return y; }

__device__ __forceinline__ void wgmma256(float (&d)[128], uint64_t da, uint64_t db, int acc) {
    asm volatile("{.reg .pred p; setp.ne.b32 p, %130, 0;\n"
        "wgmma.mma_async.sync.aligned.m64n256k16.f32.bf16.bf16 {"
        "%0,%1,%2,%3,%4,%5,%6,%7,%8,%9,%10,%11,%12,%13,%14,%15,"
        "%16,%17,%18,%19,%20,%21,%22,%23,%24,%25,%26,%27,%28,%29,%30,%31,"
        "%32,%33,%34,%35,%36,%37,%38,%39,%40,%41,%42,%43,%44,%45,%46,%47,"
        "%48,%49,%50,%51,%52,%53,%54,%55,%56,%57,%58,%59,%60,%61,%62,%63,"
        "%64,%65,%66,%67,%68,%69,%70,%71,%72,%73,%74,%75,%76,%77,%78,%79,"
        "%80,%81,%82,%83,%84,%85,%86,%87,%88,%89,%90,%91,%92,%93,%94,%95,"
        "%96,%97,%98,%99,%100,%101,%102,%103,%104,%105,%106,%107,%108,%109,%110,%111,"
        "%112,%113,%114,%115,%116,%117,%118,%119,%120,%121,%122,%123,%124,%125,%126,%127"
        "}, %128, %129, p, 1, 1, 0, 1;}"
        : "+f"(d[0]), "+f"(d[1]), "+f"(d[2]), "+f"(d[3]), "+f"(d[4]), "+f"(d[5]), "+f"(d[6]), "+f"(d[7]), "+f"(d[8]), "+f"(d[9]), "+f"(d[10]), "+f"(d[11]), "+f"(d[12]), "+f"(d[13]), "+f"(d[14]), "+f"(d[15]), "+f"(d[16]), "+f"(d[17]), "+f"(d[18]), "+f"(d[19]), "+f"(d[20]), "+f"(d[21]), "+f"(d[22]), "+f"(d[23]), "+f"(d[24]), "+f"(d[25]), "+f"(d[26]), "+f"(d[27]), "+f"(d[28]), "+f"(d[29]), "+f"(d[30]), "+f"(d[31]), "+f"(d[32]), "+f"(d[33]), "+f"(d[34]), "+f"(d[35]), "+f"(d[36]), "+f"(d[37]), "+f"(d[38]), "+f"(d[39]), "+f"(d[40]), "+f"(d[41]), "+f"(d[42]), "+f"(d[43]), "+f"(d[44]), "+f"(d[45]), "+f"(d[46]), "+f"(d[47]), "+f"(d[48]), "+f"(d[49]), "+f"(d[50]), "+f"(d[51]), "+f"(d[52]), "+f"(d[53]), "+f"(d[54]), "+f"(d[55]), "+f"(d[56]), "+f"(d[57]), "+f"(d[58]), "+f"(d[59]), "+f"(d[60]), "+f"(d[61]), "+f"(d[62]), "+f"(d[63]), "+f"(d[64]), "+f"(d[65]), "+f"(d[66]), "+f"(d[67]), "+f"(d[68]), "+f"(d[69]), "+f"(d[70]), "+f"(d[71]), "+f"(d[72]), "+f"(d[73]), "+f"(d[74]), "+f"(d[75]), "+f"(d[76]), "+f"(d[77]), "+f"(d[78]), "+f"(d[79]), "+f"(d[80]), "+f"(d[81]), "+f"(d[82]), "+f"(d[83]), "+f"(d[84]), "+f"(d[85]), "+f"(d[86]), "+f"(d[87]), "+f"(d[88]), "+f"(d[89]), "+f"(d[90]), "+f"(d[91]), "+f"(d[92]), "+f"(d[93]), "+f"(d[94]), "+f"(d[95]), "+f"(d[96]), "+f"(d[97]), "+f"(d[98]), "+f"(d[99]), "+f"(d[100]), "+f"(d[101]), "+f"(d[102]), "+f"(d[103]), "+f"(d[104]), "+f"(d[105]), "+f"(d[106]), "+f"(d[107]), "+f"(d[108]), "+f"(d[109]), "+f"(d[110]), "+f"(d[111]), "+f"(d[112]), "+f"(d[113]), "+f"(d[114]), "+f"(d[115]), "+f"(d[116]), "+f"(d[117]), "+f"(d[118]), "+f"(d[119]), "+f"(d[120]), "+f"(d[121]), "+f"(d[122]), "+f"(d[123]), "+f"(d[124]), "+f"(d[125]), "+f"(d[126]), "+f"(d[127])
        : "l"(da), "l"(db), "r"(acc));
}
__device__ __forceinline__ void wgmma128(float (&d)[64], uint64_t da, uint64_t db, int acc) {
    asm volatile("{.reg .pred p; setp.ne.b32 p, %66, 0;\n"
        "wgmma.mma_async.sync.aligned.m64n128k16.f32.bf16.bf16 {"
        "%0,%1,%2,%3,%4,%5,%6,%7,%8,%9,%10,%11,%12,%13,%14,%15,"
        "%16,%17,%18,%19,%20,%21,%22,%23,%24,%25,%26,%27,%28,%29,%30,%31,"
        "%32,%33,%34,%35,%36,%37,%38,%39,%40,%41,%42,%43,%44,%45,%46,%47,"
        "%48,%49,%50,%51,%52,%53,%54,%55,%56,%57,%58,%59,%60,%61,%62,%63"
        "}, %64, %65, p, 1, 1, 0, 1;}"
        : "+f"(d[0]), "+f"(d[1]), "+f"(d[2]), "+f"(d[3]), "+f"(d[4]), "+f"(d[5]), "+f"(d[6]), "+f"(d[7]), "+f"(d[8]), "+f"(d[9]), "+f"(d[10]), "+f"(d[11]), "+f"(d[12]), "+f"(d[13]), "+f"(d[14]), "+f"(d[15]), "+f"(d[16]), "+f"(d[17]), "+f"(d[18]), "+f"(d[19]), "+f"(d[20]), "+f"(d[21]), "+f"(d[22]), "+f"(d[23]), "+f"(d[24]), "+f"(d[25]), "+f"(d[26]), "+f"(d[27]), "+f"(d[28]), "+f"(d[29]), "+f"(d[30]), "+f"(d[31]), "+f"(d[32]), "+f"(d[33]), "+f"(d[34]), "+f"(d[35]), "+f"(d[36]), "+f"(d[37]), "+f"(d[38]), "+f"(d[39]), "+f"(d[40]), "+f"(d[41]), "+f"(d[42]), "+f"(d[43]), "+f"(d[44]), "+f"(d[45]), "+f"(d[46]), "+f"(d[47]), "+f"(d[48]), "+f"(d[49]), "+f"(d[50]), "+f"(d[51]), "+f"(d[52]), "+f"(d[53]), "+f"(d[54]), "+f"(d[55]), "+f"(d[56]), "+f"(d[57]), "+f"(d[58]), "+f"(d[59]), "+f"(d[60]), "+f"(d[61]), "+f"(d[62]), "+f"(d[63])
        : "l"(da), "l"(db), "r"(acc));
}
__device__ __forceinline__ void wg_fence() { asm volatile("wgmma.fence.sync.aligned;" ::: "memory"); }
__device__ __forceinline__ void wg_commit() { asm volatile("wgmma.commit_group.sync.aligned;" ::: "memory"); }
template <int N> __device__ __forceinline__ void wg_wait() { asm volatile("wgmma.wait_group.sync.aligned %0;" ::"n"(N) : "memory"); }
__device__ __forceinline__ uint64_t mkdesc(uint32_t addr, uint32_t lbo, uint32_t sbo, uint32_t sw) {
    return (uint64_t)((addr & 0x3FFFF) >> 4) | ((uint64_t)(lbo >> 4) << 16) | ((uint64_t)(sbo >> 4) << 32) | ((uint64_t)sw << 62);
}
__device__ __forceinline__ void tma2d(uint32_t dst, const CUtensorMap* m, int c0, int c1, uint32_t bar) {
    asm volatile("cp.async.bulk.tensor.2d.shared::cluster.global.mbarrier::complete_tx::bytes [%0], [%1, {%2, %3}], [%4];"
        ::"r"(dst), "l"(m), "r"(c0), "r"(c1), "r"(bar) : "memory");
}
__device__ __forceinline__ void tma3d(uint32_t dst, const CUtensorMap* m, int c0, int c1, int c2, uint32_t bar) {
    asm volatile("cp.async.bulk.tensor.3d.shared::cluster.global.mbarrier::complete_tx::bytes [%0], [%1, {%2, %3, %4}], [%5];"
        ::"r"(dst), "l"(m), "r"(c0), "r"(c1), "r"(c2), "r"(bar) : "memory");
}
__device__ __forceinline__ void tma3d_mc(uint32_t dst, const CUtensorMap* m, int c0, int c1, int c2, uint32_t bar, uint16_t mask) {
    asm volatile("cp.async.bulk.tensor.3d.shared::cluster.global.mbarrier::complete_tx::bytes.multicast::cluster [%0], [%1, {%2, %3, %4}], [%5], %6;"
        ::"r"(dst), "l"(m), "r"(c0), "r"(c1), "r"(c2), "r"(bar), "h"(mask) : "memory");
}
__device__ __forceinline__ void mbar_arrive(uint32_t bar) { asm volatile("mbarrier.arrive.shared.b64 _, [%0];" ::"r"(bar) : "memory"); }
__device__ __forceinline__ void mbar_arrive_remote(uint32_t bar) {
    asm volatile("mbarrier.arrive.shared::cluster.b64 _, [%0];" ::"r"(bar) : "memory");
}
template <int R> __device__ __forceinline__ void reg_inc() { asm volatile("setmaxnreg.inc.sync.aligned.u32 %0;" ::"n"(R)); }
template <int R> __device__ __forceinline__ void reg_dec() { asm volatile("setmaxnreg.dec.sync.aligned.u32 %0;" ::"n"(R)); }

#define ST(id, w, i)
constexpr int CH_NRES = 50;
constexpr int CH_WREG = CH_NRES * 512;
constexpr int CH_PART = 8 * CH_WREG;
constexpr int CH_SX = CH_PART + 16384;
constexpr int CH_MX = CH_SX + 3 * 1280;
constexpr int CH_QK = CH_MX;
constexpr int CH_XS = CH_MX + 3 * 512;
constexpr int CH_BAR = CH_XS + 5632;
constexpr int CH_SMEM = CH_BAR + 192;
constexpr int CH_THREADS = 384;

__device__ __forceinline__ char* ring_base() { return (char*)(((uintptr_t)g_ring + (1 << 20) - 1) & ~(uintptr_t)((1 << 20) - 1)); }
__device__ __forceinline__ uint32_t ring_off(int chunk, int side) {
    uint32_t o = ((chunk & 1) << 13) | ((chunk >> 1) << 16);
    uint32_t par = ((o >> 13) ^ (o >> 16) ^ (o >> 17) ^ (o >> 19) ^ side) & 1;
    return o | (par << 12);
}
__device__ __forceinline__ uint2 ld_poll(const char* p) {
    unsigned long long v; asm volatile("ld.relaxed.gpu.global.b64 %0, [%1];" : "=l"(v) : "l"(p) : "memory");
    return make_uint2((uint32_t)v, (uint32_t)(v >> 32));
}
__device__ __forceinline__ void st_pub(char* p, uint32_t x, uint32_t y) {
    unsigned long long v = ((unsigned long long)y << 32) | x;
    asm volatile("st.relaxed.gpu.global.b64 [%0], %1;" ::"l"(p), "l"(v) : "memory");
}
template <int N>
__device__ __forceinline__ void poll_issue(uint2 (&b)[N], const char* p, bool lastvalid) {
#pragma unroll
    for (int i = 0; i < N; i++) {
        if (i < N - 1 || lastvalid) b[i] = ld_poll(p + i * 256);
        else b[i] = make_uint2(0, 0);
    }
}
template <int N>
__device__ __forceinline__ int poll_check(uint2 (&b)[N], const char* p, uint32_t z) {
    int it = 0;
    uint32_t mx = z;
#pragma unroll
    for (int i = 0; i < N; i++) mx = max(mx, b[i].x);
    if (__any_sync(0xffffffffu, mx == SENT)) {
        do {
#pragma unroll
            for (int i = 0; i < N; i++)
                if ((REALL && i < 10) || b[i].x == SENT) b[i] = ld_poll(p + i * 256);
            mx = b[0].x;
#pragma unroll
            for (int i = 1; i < N; i++) mx = max(mx, b[i].x);
            it++;
        } while (__any_sync(0xffffffffu, mx == SENT && it < SPIN_LIMIT));
    }
    return it;
}
template <int N>
__device__ __forceinline__ uint32_t delay(uint32_t a) {
    uint32_t z = 0;
#pragma unroll
    for (int i = 0; i < N; i++) asm volatile("ld.volatile.shared.u32 %0, [%1];" : "=r"(z) : "r"(a + z) : "memory");
    return z;
}

#define PFKV 0
#define LDW 0
#define R1W 0
#define KGS 3
constexpr int KVN = 2;
#define FEN 1
#define XB 4
#define KEEP 100
#define PE 0
#define PROMO 2
#define PROMU 0
#define FNC 1
#define CL 8
#define PL 0
#define ML 4
#define MP 2
#define VCH_P 4
#define VCH_C 2
#define DLM 3
#define DLO 5
constexpr int OB = 0;
template <int PACE, int I0 = 0, int I1 = 12>
__device__ __forceinline__ void preload(uint32_t (&sw)[12][4], uint32_t a, uint32_t zero) {
    uint32_t z = 0;
#pragma unroll
    for (int i = I0; i < I1; i++) {
        if (PACE && i % (PACE ? PACE : 1) == 0) z = delay<1>(zero + z);
        ldsm4t(sw[i], a + z + i * 512);
    }
}
__device__ __forceinline__ void stsm4(uint32_t addr, uint32_t a, uint32_t b, uint32_t c, uint32_t d) {
    asm volatile("stmatrix.sync.aligned.m8n8.x4.shared.b16 [%0], {%1,%2,%3,%4};" ::"r"(addr), "r"(a), "r"(b), "r"(c), "r"(d) : "memory");
}
__device__ __forceinline__ void stsm4t(uint32_t addr, uint32_t a, uint32_t b, uint32_t c, uint32_t d) {
    asm volatile("stmatrix.sync.aligned.m8n8.x4.trans.shared.b16 [%0], {%1,%2,%3,%4};" ::"r"(addr), "r"(a), "r"(b), "r"(c), "r"(d) : "memory");
}
__device__ __forceinline__ void st_part(uint32_t addr, const float (&x)[4], const float (&y)[4]) {
    stsm4(addr, pack_bf16(x[0], x[1]), pack_bf16(x[2], x[3]), pack_bf16(y[0], y[1]), pack_bf16(y[2], y[3]));
}
template <bool TR>
__device__ __forceinline__ void red_part(uint32_t& lo, uint32_t& hi, uint32_t addr, uint32_t eye) {
    uint32_t a[4][4];
#pragma unroll
    for (int j = 0; j < 4; j++) { if (TR) ldsm4t(a[j], addr + j * 1024); else ldsm4(a[j], addr + j * 1024); }
    float r0[4], r1[4], r2[4], r3[4];
    mma16z(r0, a[0], eye, eye); mma16z(r1, a[1], eye, eye); mma16z(r2, a[2], eye, eye); mma16z(r3, a[3], eye, eye);
#pragma unroll
    for (int j = 0; j < 4; j++) r0[j] = ((r0[j] + r1[j]) + r2[j]) + r3[j];
    lo = pack_bf16(r0[0], r0[1]); hi = pack_bf16(r0[2], r0[3]);
}
__device__ __forceinline__ int o_chunk(int ks, int& pos) {
    const int cw = ks < 176 ? ks / 11 : 16 + (ks - 176) / 10;
    pos = ks - (cw < 16 ? 11 * cw : 176 + 10 * (cw - 16));
    return cw;
}

template <bool PV>
__device__ __forceinline__ void chain_loop(const uint32_t (&wa)[36][4], const uint32_t sb, const int w, const int lane0, const int rank,
                                           const int h, const int side) {
    const int rk1 = rank == 2 ? 0 : rank + 1, rk2 = rank == 0 ? 2 : rank - 1;
    const int nq = rank == 0 ? 6 : 5, u0 = rank == 0 ? 0 : 1 + 5 * rank, v0 = rank == 0 ? -6 : 3 * rank - 6;
    const uint32_t pt = CH_PART + (w >> 1) * 4096 + (w & 1) * 256;
    const uint32_t barS = sb + CH_BAR, barM = barS + 8, zero = barS + 24;
    char* const ring0 = ring_base();
    const uint32_t m_rd = ring_off(24 + w, side), o_rd = ring_off(rank * 8 + w, side);
    uint32_t pub;
    if (PV) { int pos, cw = o_chunk(h * 8 + v0 + w, pos); pub = (ring_off(cw, 0) & ~4096u) + pos * 256; }
    else pub = (ring_off(24 + (h >> 2), 0) & ~4096u) + ((2 * h + w) & 7) * 256;
    char* const kvo = (char*)(PV ? g_vm + 128 * (v0 + w) : g_km + 64 * (u0 + w)) + h * 2048;
    const bool mown = !PV && w == rank && rank < 2;
    uint32_t lo16 = lane0 * 16;
    uint32_t sw[12][4];
#pragma unroll
    for (int i = 0; i < 12; i++) ldsm4t(sw[i], sb + lo16 + w * CH_WREG + i * 512);

#pragma unroll 1
    for (int s = 0;; s++) {
        const bool last = s == NSEG - 1;
        const uint32_t slot = (s & 3) << 14;
        lo16 += delay<DLM>(zero);
        const uint32_t lane = lo16 >> 4, l16 = sb + lo16, wl = l16 + w * CH_WREG, pw = l16 + CH_PART + w * 512;
        const uint32_t xs = l16 + CH_XS + nq * 512 + (w - nq) * 1024;
        const uint32_t eye = ((lo16 >> 7) == (lane & 3)) ? ((lo16 & 64) ? 0x3F800000u : 0x3F80u) : 0u;
        uint2 b[8];
        const char* pm = ring0 + (m_rd + slot + (lo16 >> 1));
        poll_issue<8>(b, pm, true);
        preload<0, ML, 12>(sw, wl, zero);
        if (FNC & 1) bar_arrive(14, 256);
        poll_check<8>(b, pm, delay<FNC & 1>(zero));
        if ((OB || (XB & 1)) && !last) bar_arrive(8, 256 + OB);
        if (PV && !last && w == 7) bar_arrive(13, 64);
        {
            float acc[6][4];
#pragma unroll
            for (int kk = 0; kk < 8; kk++) {
                const int j = (2 * kk) % 12;
                if (kk == 0) { mma16z(acc[5], sw[0], b[0].x, b[0].y); mma16z(acc[4], sw[1], b[0].x, b[0].y); }
                else { mma16(acc[5], sw[j], b[kk].x, b[kk].y); mma16(acc[4], sw[j + 1], b[kk].x, b[kk].y); }
#pragma unroll
                for (int i = 0; i < 4; i++) {
                    if (kk == 0) mma16z(acc[i], wa[i * 8], b[0].x, b[0].y);
                    else mma16(acc[i], wa[i * 8 + kk], b[kk].x, b[kk].y);
                    if (i < 2) ldsm4t(sw[j + i], wl + (12 + 2 * kk + i) * 512);
                }
            }
            st_part(pw + 4 * 2048, acc[4], acc[5]);
            st_part(pw, acc[0], acc[1]);
            st_part(pw + 2 * 2048, acc[2], acc[3]);
        }
        uint32_t kv0, kv1;
        const uint32_t lp = l16 + (lane >> 4) * 256, pl = lp + pt;
        if (!PV) {
            bar_sync(1, last ? 256 : 256 + OB);
            red_part<true>(kv1, kv0, pl, eye);
            sts64(l16 + CH_QK + (w >> 1) * 512 + (w & 1) * 8, __uint_as_float(kv1), __uint_as_float(kv0));
            if (!last) bar_arrive(2, nq * 32 + 64 + OB);
        } else {
            bar_sync(1, last ? 256 : 256 + OB);
        }
        {
            float va[4][4];
            const float z = __uint_as_float(delay<1>(zero));
#pragma unroll
            for (int i = 0; i < 4; i++) va[i][0] = va[i][1] = va[i][2] = va[i][3] = z;
#pragma unroll
            for (int kk = 0; kk < 8; kk++) {
                const int c = (PV ? VCH_P : VCH_C) == 4 ? kk & 1 : 0;
                if (kk < 2) { mma16(va[c], wa[32 + 2 * kk], b[kk].x, b[kk].y); mma16(va[2 + c], wa[33 + 2 * kk], b[kk].x, b[kk].y); }
                else { mma16(va[c], sw[(2 * kk) % 12], b[kk].x, b[kk].y); mma16(va[2 + c], sw[(2 * kk + 1) % 12], b[kk].x, b[kk].y); }
            }
            if ((PV ? VCH_P : VCH_C) == 4) {
#pragma unroll
                for (int j = 0; j < 4; j++) { va[0][j] += va[1][j]; va[2][j] += va[3][j]; }
            }
            st_part(pw + 6 * 2048, va[0], va[2]);
        }
        if (PV) {
            uint32_t vt0[4], vt1[4];
            ldsm4t(vt0, xs); ldsm4t(vt1, xs + 512);
            if (w >= 6 && !last) {
                uint32_t kx[3][4];
#pragma unroll
                for (int j = 0; j < 3; j++)
                    ldsm4(kx[j], sb + CH_XS + j * 1024 + (j == 2 && nq == 5 ? 0 : ((lane >> 3) & 1) * 512) + (w - 6) * 256 + (lane >> 4) * 128 + (lane & 7) * 16);
                const uint32_t da = l16 + CH_SX + rank * 1280 + (w - 6) * 512, dc = sb + CH_SX + rank * 1280 + 1024 + lane * 8;
                bar_sync(2, nq * 32 + 64 + OB);
                uint32_t qk[3][4];
#pragma unroll
                for (int j = 0; j < 3; j++) {
                    const float4 v = lds128(l16 + CH_QK + j * 512);
                    qk[j][0] = __float_as_uint(v.x); qk[j][1] = __float_as_uint(v.y); qk[j][2] = __float_as_uint(v.z); qk[j][3] = __float_as_uint(v.w);
                }
                float s0[4], s1[4], s2[4], s3[4];
                mma16z(s0, qk[0], kx[0][0], kx[0][1]); mma16z(s1, qk[0], kx[0][2], kx[0][3]);
                mma16z(s2, qk[1], kx[1][0], kx[1][1]); mma16z(s3, qk[1], kx[1][2], kx[1][3]);
                if (nq == 5) qk[2][2] = qk[2][3] = 0;
                mma16(s0, qk[2], kx[2][0], kx[2][1]); mma16(s1, qk[2], kx[2][2], kx[2][3]);
                float m0[4], m1[4];
                mma16z(m0, qk[0], qk[0][1], qk[0][3]); mma16z(m1, qk[1], qk[1][1], qk[1][3]);
                mma16(m0, qk[2], qk[2][1], qk[2][3]);
                const float4 sv = make_float4(s0[0] + s2[0], s0[1] + s2[1], s1[0] + s3[0], s1[1] + s3[1]);
                st_async4(mapa(da, rk1), sv, mapa(barS, rk1));
                st_async4(mapa(da, rk2), sv, mapa(barS, rk2));
                {
                    const float c0 = m0[0] + m1[0], c1 = m0[1] + m1[1];
                    const int dr = w == 6 ? rk1 : rk2;
                    st_async2(mapa(dc, dr), c0, c1, mapa(barS, dr));
                    sts64(dc, c0, c1);
                }
                const float t4[4] = {sv.x, sv.y, sv.z, sv.w};
                sts128(da, t4);
            }
            bar_sync(3, last ? 256 : 256 + OB);
            if (!last && w == 7) bar_arrive(12, 64);
            red_part<false>(kv0, kv1, pl, eye);
            if (last) {
                uint32_t* d = (uint32_t*)(kvo + (uint32_t)(s * (NH * 2048) + lane * 4));
                d[0] = movm(kv0); d[32] = movm(kv1);
                break;
            }
            {
                const uint32_t sx = l16 + CH_SX, r0 = rank * 1280, r1 = rk1 * 1280, r2 = rk2 * 1280;
                float4 a0 = lds128(sx + r0), b0 = lds128(sx + 512 + r0);
                const float2 c0 = lds64(sx + 1024 + r0 - lane * 8);
                preload<0, 0, PE>(sw, wl + 28 * 512, zero);
                mbar_wait(barS, s & 1);
                const float4 a1 = lds128(sx + r1), a2 = lds128(sx + r2), b1 = lds128(sx + 512 + r1), b2 = lds128(sx + 512 + r2);
                const float2 c1 = lds64(sx + 1024 + r1 - lane * 8), c2 = lds64(sx + 1024 + r2 - lane * 8);
                a0 = add4(add4(a0, a1), a2); b0 = add4(add4(b0, b1), b2);
                float sc[10] = {a0.x, a0.y, a0.z, a0.w, b0.x, b0.y, b0.z, b0.w, c0.x + c1.x + c2.x, c0.y + c1.y + c2.y};
                float mx = fmaxf(fmaxf(fmaxf(sc[0], sc[1]), fmaxf(sc[2], sc[3])), fmaxf(fmaxf(sc[4], sc[5]), fmaxf(sc[6], sc[7])));
                mx = fmaxf(mx, fmaxf(sc[8], sc[9]));
                mx = fmaxf(fmaxf(mx, __shfl_xor_sync(0xffffffffu, mx, 1)),
                           fmaxf(__shfl_xor_sync(0xffffffffu, mx, 2), __shfl_xor_sync(0xffffffffu, mx, 3)));
                const float cs = 0.08838834764831845f * 1.4426950408889634f;
                const float mb = -mx * cs;
#pragma unroll
                for (int j = 0; j < 10; j++) sc[j] = ex2(fmaf(sc[j], cs, mb));
                uint32_t pf[5];
#pragma unroll
                for (int j = 0; j < 5; j++) pf[j] = pack_bf16(sc[2 * j], sc[2 * j + 1]);
                float o0[4], o1[4], o2[4], o3[4], o4[4], o5[4];
                const uint32_t p0[4] = {pf[0], 0, pf[1], 0}, p1[4] = {pf[2], 0, pf[3], 0};
                mma16z(o0, p0, vt0[0], vt0[1]); mma16z(o1, p0, vt1[0], vt1[1]);
                mma16z(o2, p1, vt0[2], vt0[3]); mma16z(o3, p1, vt1[2], vt1[3]);
                mma8z(o4, pf[4], 0, kv0); mma8z(o5, pf[4], 0, kv1);
                float sum = (((sc[0] + sc[1]) + (sc[2] + sc[3])) + ((sc[4] + sc[5]) + (sc[6] + sc[7]))) + (sc[8] + sc[9]);
                sum = (sum + __shfl_xor_sync(0xffffffffu, sum, 1)) + (__shfl_xor_sync(0xffffffffu, sum, 2) + __shfl_xor_sync(0xffffffffu, sum, 3));
                float inv; asm("rcp.approx.ftz.f32 %0, %1;" : "=f"(inv) : "f"(sum));
                const uint32_t ox = pack_bf16((o0[0] + o2[0] + o4[0]) * inv, (o0[1] + o2[1] + o4[1]) * inv);
                const uint32_t oy = pack_bf16((o1[0] + o3[0] + o5[0]) * inv, (o1[1] + o3[1] + o5[1]) * inv);
                char* const pp = ring0 + (pub + slot + (lo16 >> 1));
                st_pub(pp, ox, oy); st_pub(pp + 4096, ox, oy);
                if (OB || (XB & 4)) bar_arrive(10, (8 - nq) * 32 + OB);
                preload<0, PE, PL>(sw, wl + 28 * 512, zero);
            }
            kv0 = movm(kv0); kv1 = movm(kv1);
        } else {
            *(uint32_t*)(kvo + (uint32_t)(s * (NH * 2048) + lane * 4)) = kv0;
            bar_sync(3, last ? 256 : 256 + OB);
            if (last) break;
            preload<1, 0, CL>(sw, wl + 28 * 512, zero);
        }
        uint2 c[11];
        bar_sync(4, 256 + OB);
        const char* po = ring0 + (o_rd + slot + (lo16 >> 1) + delay<DLO>(zero));
        poll_issue<11>(c, po, rank < 2);
        preload<0, PV ? PL : CL, 12>(sw, wl + 28 * 512, zero);
        if (PV) { uint32_t* d = (uint32_t*)(kvo + (uint32_t)(s * (NH * 2048) + lane * 4)); d[0] = kv0; d[32] = kv1; }
        if (FNC & 2) bar_arrive(15, 256);
        poll_check<11>(c, po, delay<(FNC >> 1)>(zero));
        if (OB || (XB & 2)) bar_arrive(9, 256 + OB);
        {
            float acc[4][4];
#pragma unroll
            for (int f = 0; f < 22; f++) {
                const int kk = f >> 1, a = f & 3;
                if (f < 4) mma16z(acc[a], sw[f % 12], c[kk].x, c[kk].y);
                else mma16(acc[a], sw[f % 12], c[kk].x, c[kk].y);
                if (f + 12 < 22) ldsm4t(sw[f % 12], wl + (28 + f + 12) * 512);
            }
#pragma unroll
            for (int i = 0; i < 2; i++) {
#pragma unroll
                for (int j = 0; j < 4; j++) acc[i][j] += acc[i + 2][j];
                sts128(l16 + CH_PART + i * 4096 + w * 512, acc[i]);
            }
        }
        if (!PV && w < 2) {
            bar_sync(5, 288 + OB);
            float4 v[8];
#pragma unroll
            for (int i = 0; i < 8; i++) v[i] = lds128(l16 + CH_PART + w * 4096 + i * 512);
            float4 r = add4(add4(add4(v[0], v[1]), add4(v[2], v[3])), add4(add4(v[4], v[5]), add4(v[6], v[7])));
            if (!mown) st_async4(mapa(l16 + CH_MX + rank * 512, w), r, mapa(barM, w));
            bar_arrive(7, 256 + OB);
            if (mown) {
                mbar_wait(barM, s & 1);
                float4 x = lds128(l16 + CH_MX + (rank ^ 1) * 512), y = lds128(l16 + CH_MX + 2 * 512);
                r = add4(add4(x, r), y);
                const uint32_t mx = movm(pack_bf16(r.x, r.y)), my = movm(pack_bf16(r.z, r.w));
                const uint32_t ns = (slot + 0x4000) & 0xC000;
                char* const pp = ring0 + (pub + ns + (lo16 >> 1));
                st_pub(pp, mx, my); st_pub(pp + 4096, mx, my);
            }
            preload<0, 0, ML>(sw, wl, zero);
        } else {
            bar_arrive(5, 288 + OB);
            bar_sync(7, 256 + OB);
            preload<MP, 0, ML>(sw, wl, zero);
        }
        bar_sync(6, 320 + OB);
    }
    bar_arrive(6, 288);
}

__device__ __forceinline__ void chain_pace(const uint32_t sb, const int lane, const int rank, const int aware) {
    const uint32_t zero = sb + CH_BAR + 24;
    if (lane == 0) {
        char* ring = ring_base();
        uint32_t* p0 = (uint32_t*)(ring + ring_off(blockIdx.x & 15, 0) + 3072 + (blockIdx.x >> 4) * 128);
        uint32_t* p1 = (uint32_t*)(ring + ring_off(blockIdx.x & 15, 1) + 3072 + (blockIdx.x >> 4) * 128);
        *p0 = 0; *p1 = 0;
        int b0 = 1 << 30, b1 = 1 << 30; uint32_t v = 0;
        for (int r = 0; r < 4 || (r < 256 && !mbar_test(sb + CH_BAR + 16, 0)); r++) {
            uint32_t t0 = clk(); v = atomicExch(p0 + (v == 500), r); uint32_t t1 = v == 777 ? clk() + 1 : clk(); b0 = min(b0, (int)(t1 - t0));
            t0 = clk(); v = atomicExch(p1 + (v == 500), r); t1 = v == 777 ? clk() + 1 : clk(); b1 = min(b1, (int)(t1 - t0));
            asm volatile("st.volatile.shared.u32 [%0], %1;" ::"r"(zero + 4), "r"(aware ? (b1 < b0) ^ (aware - 1) : 0) : "memory");
        }
    }
    __syncwarp();
#pragma unroll 1
    for (int s = 1; s < NSEG; s++) {
        bar_sync(5, 288 + OB);
        bar_arrive(6, 320 + OB + (rank == 2 ? delay<18>(zero) : 0));
    }
}
__device__ __forceinline__ char* reset_ptr(const int lane, const int rank, const int h) {
    const int nq = rank == 0 ? 6 : 5, v0 = rank == 0 ? -6 : 3 * rank - 6;
    int pos, cw = o_chunk(h * 8 + v0 + min(max(5 + (lane >> 3), nq), 7), pos);
    if (lane >= 24 && rank < 2) { cw = 24 + (h >> 2); pos = (2 * h + rank) & 7; }
    return ring_base() + ((ring_off(cw, 0) & ~4096u) + pos * 256 + (lane & 7) * 16);
}
__device__ __forceinline__ void chain_chores(const uint32_t sb, const int lane, const int rank, const int h, const bf16* __restrict__ mem0) {
    const int nq = rank == 0 ? 6 : 5, u0 = rank == 0 ? 0 : 1 + 5 * rank, v0 = rank == 0 ? -6 : 3 * rank - 6;
    const uint32_t barS = sb + CH_BAR, barM = barS + 8, barX = barS + 16;
    auto xload = [&](int s) {
        mbar_expect(barX, 8192 - nq * 512);
        bulk_load(sb + CH_XS, g_kx + (size_t)(s * NH + h) * 4096 + u0 * 256, nq * 512, barX);
        bulk_load(sb + CH_XS + nq * 512, g_vx + (size_t)(s * NH + h) * 4096 + (v0 + nq) * 512, (8 - nq) * 1024, barX);
    };
    char* const rb = reset_ptr(lane, rank, h);
    int* const kvf = g_kvf + blockIdx.x * 16;
    if (rank < 2) {
        const uint32_t* p = (const uint32_t*)(mem0 + (lane >> 2) * DM + 32 * h + 16 * rank + 2 * (lane & 3));
        char* d = ring_base() + ((ring_off(24 + (h >> 2), 0) & ~4096u) + ((2 * h + rank) & 7) * 256 + lane * 8);
        const uint32_t x = p[0] == SENT ? 0x7FFF7FFFu : p[0];
        st_pub(d, x, p[4]); st_pub(d + 4096, x, p[4]);
    }
    if (lane == 0) {
        if (!KVN) __nanosleep(18000);
        wait_ctr(kvf, KVN);
        asm volatile("fence.proxy.async.global;" ::: "memory");
        xload(0);
    }
#pragma unroll 1
    for (int s = 0; s < NSEG - 1; s++) {
        if (lane == 0) {
            mbar_expect(barS, 2 * 1280);
            if (rank < 2) mbar_expect(barM, 2 * 512);
        }
        bar_sync(13, 64);
#pragma unroll
        for (int i = 0; i < 4; i++)
            asm volatile("st.relaxed.gpu.global.v4.u32 [%0], {%1,%1,%1,%1};" ::"l"(rb + ((((s + 2) & 3) << 14) + (i >> 1) * 4096 + (i & 1) * 128)), "r"(SENT) : "memory");
        if (FEN || (s & 3) == 0) fence_gpu();
        if (lane == 0 && (s & 3) == 0 && s) atomicAdd(g_ctr + C_CHAIN + (s >> 2) - 1, 1);
        if (lane == 0 && (s & 3) == 3) { wait_ctr(kvf + (s >> 2) + 1, KVN); asm volatile("fence.proxy.async.global;" ::: "memory"); }
        __syncwarp();
        bar_sync(12, 64);
        if (lane == 0) xload(s + 1);
        mbar_wait(barX, (s + 1) & 1);
        bar_sync(6, 320 + OB);
    }
    bar_sync(6, 288);
    fence_gpu();
    if (lane == 0) atomicAdd(g_ctr + C_CHAIN + 15, 1);
}

struct S4Params { const bf16 *Are, *Aim, *Bre, *Bim, *Cre, *Cim, *ldt, *dsk; };
__device__ __forceinline__ float2 cmul(float2 a, float2 b) { return make_float2(a.x * b.x - a.y * b.y, a.x * b.y + a.y * b.x); }
__device__ __forceinline__ float2 csq(float2 a) { return make_float2(a.x * a.x - a.y * a.y, (a.x + a.x) * a.y); }
__device__ __forceinline__ float2 cexp_t(float lr, float turns) {
    float f = (turns - rintf(turns)) * 6.283185307179586f, e = ex2(lr);
    return make_float2(e * __cosf(f), e * __sinf(f));
}
__device__ __forceinline__ float bf_at(uint2 v, int i) {
    const uint32_t w = i < 2 ? v.x : v.y;
    return __uint_as_float((i & 1) ? w & 0xFFFF0000u : w << 16);
}
__device__ __forceinline__ void kg_step(uint32_t (&a)[4][4], uint32_t (&b)[5][2], uint32_t pa, uint32_t pe, float x0) {
#pragma unroll
    for (int i = 0; i < 2; i++) {
        const float4 p = lds128(pa + i * 64);
        const float2 e8 = lds64(pe + i * 32), c = make_float2(p.z, p.w);
        const float mag = ex2(p.x * x0), ph = p.y * x0;
        float2 e0 = make_float2(mag * __cosf(ph), mag * __sinf(ph)), e1 = cmul(e0, e8);
#pragma unroll
        for (int j = 0; j < 4; j++) {
            a[j][2 * i] = pack_bf16(e0.x, e0.y); a[j][2 * i + 1] = pack_bf16(e1.x, e1.y);
            e0 = csq(e0); e1 = csq(e1);
        }
        float2 m = cmul(c, e0);
        b[0][i] = pack_bf16(m.x, -m.y);
#pragma unroll
        for (int j = 0; j < 4; j++) {
            m = cmul(c, e1);
            b[j + 1][i] = pack_bf16(m.x, -m.y);
            if (j < 3) e1 = csq(e1);
        }
    }
}
__device__ __forceinline__ void kg_mma(float (&kd)[5][4], const uint32_t (&a)[4][4], const uint32_t (&b)[5][2]) {
    mma16(kd[0], a[0], b[0][0], b[0][1]);
#pragma unroll
    for (int j = 0; j < 4; j++) mma16(kd[j + 1], a[j], b[j + 1][0], b[j + 1][1]);
}
struct KgRaw { uint2 v[6]; float ldt; };
__device__ __forceinline__ void kg_load(KgRaw& r, const S4Params& P, int d, int lane) {
    const bf16* src[6] = {P.Are, P.Aim, P.Bre, P.Bim, P.Cre, P.Cim};
#pragma unroll
    for (int j = 0; j < 6; j++) r.v[j] = __ldg((const uint2*)(src[j] + d * 128) + lane);
    r.ldt = __bfloat162float(P.ldt[d]);
}
__device__ __forceinline__ float kg_params(const KgRaw& r, uint32_t stg, int lane) {
    const float dt = __bfloat162float(__float2bfloat16(expf(r.ldt)));
    float k2048 = 0.f;
#pragma unroll
    for (int i = 0; i < 4; i++) {
        const float br = dt * bf_at(r.v[2], i), bi = dt * bf_at(r.v[3], i), cr = bf_at(r.v[4], i), ci = bf_at(r.v[5], i);
        const float zr = dt * bf_at(r.v[0], i) * 1.4426950408889634f;
        float zt = dt * bf_at(r.v[1], i) * 0.15915494309189535f;
        zt -= rintf(zt);
        const float v[4] = {zr, zt * 6.283185307179586f, cr * br - ci * bi, cr * bi + ci * br};
        const float2 e8 = cexp_t(8.f * zr, 8.f * zt), el = cexp_t(2048.f * zr, 2048.f * zt);
        k2048 += v[2] * el.x - v[3] * el.y;
        sts128(stg + (i * 32 + lane) * 16, v);
        sts64(stg + 2048 + (i * 32 + lane) * 8, e8.x, e8.y);
    }
#pragma unroll
    for (int o = 16; o; o >>= 1) k2048 += __shfl_xor_sync(0xffffffffu, k2048, o);
    __syncwarp();
    return k2048;
}
__device__ __forceinline__ void kg_store(const float (&kd)[5][4], float k2048, uint32_t stg, int d, int lane) {
    __syncwarp();
    const uint32_t ta = stg + (lane & 7) * 32 + ((lane >> 3) & 1) * 16 + (lane >> 4) * 256;
    stsm4t(ta, pack_bf16(kd[0][0], kd[0][1]), pack_bf16(kd[0][2], kd[0][3]), pack_bf16(kd[1][0], kd[1][1]), pack_bf16(kd[1][2], kd[1][3]));
    stsm4t(ta + 512, pack_bf16(kd[2][0], kd[2][1]), pack_bf16(kd[2][2], kd[2][3]), pack_bf16(kd[3][0], kd[3][1]), pack_bf16(kd[3][2], kd[3][3]));
    stsm4t(ta + 1024, pack_bf16(kd[4][0], kd[4][1]), pack_bf16(kd[4][2], kd[4][3]), pack_bf16(k2048, 0.f), 0);
    __syncwarp();
#pragma unroll
    for (int j = 0; j < 3; j++) ((float4*)(g_kd + d * 768))[j * 32 + lane] = lds128(stg + j * 512 + lane * 16);
    __syncwarp();
}

__global__ void __cluster_dims__(3, 1, 1) __launch_bounds__(CH_THREADS, 1)
chain_kernel(const __grid_constant__ CUtensorMap mq, const __grid_constant__ CUtensorMap mk, const __grid_constant__ CUtensorMap mv,
             const __grid_constant__ CUtensorMap mo, const bf16* __restrict__ Wq, const bf16* __restrict__ Wk, const bf16* __restrict__ Wv,
             const bf16* __restrict__ mem0, const __grid_constant__ S4Params P, int aware) {
    extern __shared__ __align__(1024) unsigned char smem[];
    const uint32_t sb = smem_u32(smem);
    const int tid = threadIdx.x, lane = tid & 31;
    const int w = __shfl_sync(0xffffffffu, tid >> 5, 0);
    int rank; asm("mov.u32 %0, %%cluster_ctarank;" : "=r"(rank));
    const int h = blockIdx.x / 3;
    if (tid == 0) {
        mbar_init(sb + CH_BAR, 1); mbar_init(sb + CH_BAR + 8, 1); mbar_init(sb + CH_BAR + 16, 1);
        for (int i = 0; i < 16; i++) mbar_init(sb + CH_BAR + 64 + i * 8, 1);
        *(int*)(smem + CH_BAR + 24) = 0; *(int*)(smem + CH_BAR + 28) = 0; *(int*)(smem + CH_BAR + 32) = 0;
        asm volatile("fence.mbarrier_init.release.cluster;" ::: "memory");
    }
    if (w == 10 && PFKV) {
        const int e = lane * 96 + blockIdx.x;
        if (e < 2048) asm volatile("cp.async.bulk.prefetch.L2.global [%0], 8192;" ::"l"(((e & 1) ? Wv : Wk) + (size_t)(e >> 1) * HD) : "memory");
        if (PFKV > 1) __nanosleep(PFKV);
    }
    if (w == 9) {
        char* const rb = reset_ptr(lane, rank, h);
#pragma unroll
        for (int i = 0; i < 8; i++)
            asm volatile("st.relaxed.gpu.global.v4.u32 [%0], {%1,%1,%1,%1};" ::"l"(rb + (((i >> 2) << 14) + ((i >> 1) & 1) * 4096 + (i & 1) * 128)), "r"(SENT) : "memory");
        if (lane < 16) g_kvf[blockIdx.x * 16 + lane] = 0;
        if (blockIdx.x == 0)
            for (int k = lane; k < N_CTR; k += 32) g_ctr[k] = 0;
        fence_gpu();
        __syncwarp();
        asm volatile("griddepcontrol.launch_dependents;" ::: "memory");
    }
    __syncthreads();
    asm volatile("barrier.cluster.arrive.relaxed.aligned;" ::: "memory");

    if (w >= 8) {
        reg_dec<24>();
        asm volatile("barrier.cluster.wait.aligned;" ::: "memory");
        if (w == 8) chain_pace(sb, lane, rank, aware);
        else if (w == 9) {
            chain_chores(sb, lane, rank, h, mem0);
            asm volatile("st.volatile.shared.u32 [%0], %1;" ::"r"(sb + CH_BAR + 32), "r"(0x3F803F80) : "memory");
        } else if (w == 11 && KEEP) {
#pragma unroll 1
            for (int it = 0; it < (1 << 22); it++) {
                int d0, d1;
                const uint32_t x = delay<1>(sb + CH_BAR + 32);
                asm volatile("mma.sync.aligned.m8n8k16.row.col.s32.s8.s8.s32 {%0,%1}, {%2}, {%2}, {%3,%3};" : "=r"(d0), "=r"(d1) : "r"(x), "r"(0));
                if (d0 | d1) break;
                if ((XB & 8) && lane == 0) asm volatile("st.relaxed.gpu.global.u32 [%0], %1;" ::"l"(g_kd + DM * 768 + blockIdx.x * 64), "r"(it) : "memory");
                if ((XB & 16) && lane == 0) ld_acq((int*)(g_kd + DM * 768 + blockIdx.x * 64));
                __nanosleep(KEEP);
            }
        }
    } else {
        reg_inc<240>();
        const int nq = rank == 0 ? 6 : 5;
        const int u0 = rank == 0 ? 0 : 1 + 5 * rank;
        const int v0 = rank == 0 ? -6 : 3 * rank - 6;
        const int gw = rank * 8 + w;
        const int ks0 = gw < 16 ? 11 * gw : 176 + 10 * (gw - 16);
        const int nko = gw < 16 ? 11 : 10;
        const uint32_t wr = sb + w * CH_WREG, bar0 = sb + CH_BAR + 64 + w * 16, bar1 = bar0 + 8;
        uint32_t wa[36][4];
        const uint32_t vst = sb + CH_PART + w * 2048;
        const int cq = h * DH + 8 * u0, cv = h * DH + 16 * (v0 + 6);
        const int r8 = lane >> 2, p = lane & 3;
        const bf16* src = p >= 2 ? ((p & 1) ? Wk : Wq) + cq + 32 : rank == 0 ? ((p & 1) ? Wk : Wq) + cq + 40 : Wv + cv - 16 + 8 * p;
        src += (size_t)(128 * w + r8) * HD;
        auto cp_rows = [&](int kh) {
            cp16(wr + ((kh >> 1) * 2 + (p >> 1)) * 512 + ((kh & 1) * 2 + (p & 1)) * 128 + r8 * 16, src + (size_t)kh * 8 * HD);
        };
        {
            int d = blockIdx.x * 8 + w, t = 0;
            const int d1 = 768 + blockIdx.x * 3 + w, nt = (w < 3 && d1 < DM) ? 32 : 16;
            const uint32_t stg = wr + 4096;
            KgRaw raw, raw1;
            kg_load(raw, P, d, lane);
            kg_load(raw1, P, min(d1, DM - 1), lane);
            float kd[5][4], k2048;
#pragma unroll 1
            for (int i = -LDW; i < 9 || t < nt; i++) {
                if (i >= 0 && i < 9) {
                    const uint32_t bar = bar0 + (i & 1) * 8;
                    if (i >= 2) mbar_wait(bar, ((i >> 1) - 1) & 1);
                    if (lane == 0) {
                        mbar_expect(bar, 2048);
                        if (i < 8) tma2d(wr + 8192 + (i & 1) * 8192 + (i >> 1) * 2048, (i & 1) ? &mk : &mq, cq, 128 * w + 32 * (i >> 1), bar);
                        else tma2d(vst, &mv, cv, 128 * w, bar);
                    }
                    if (i < 8) cp_rows(i);
                }
#pragma unroll 1
                for (int e = min(t + KGS, nt); t < e; t++) {
                    if ((t & 15) == 0) {
                        k2048 = kg_params(raw, stg, lane);
#pragma unroll
                        for (int j = 0; j < 20; j++) kd[j >> 2][j & 3] = 0.f;
                    }
                    uint32_t ka[4][4], kb[5][2];
                    kg_step(ka, kb, stg + ((t & 15) * 8 + (lane & 3)) * 16, stg + 2048 + ((t & 15) * 8 + (lane & 3)) * 8, (float)(lane >> 2));
                    kg_mma(kd, ka, kb);
                    if ((t & 15) == 15) { kg_store(kd, k2048, stg, d, lane); raw = raw1; d = d1; }
                }
            }
        }
        const uint32_t lrow = ((lane >> 4) * 8 + (lane & 7)) * 64, lsw = (lane >> 1) & 3, lh = (lane >> 3) & 1;
        mbar_wait(bar1, 1); mbar_wait(bar0, 0);
#pragma unroll
        for (int i = 0; i < 32; i++) ldsm4t(wa[i], wr + 8192 + lh * 8192 + (i & 7) * 1024 + lrow + (((i >> 3) ^ lsw) << 4));
#pragma unroll
        for (int i = 0; i < 4; i++) ldsm4t(wa[32 + i], vst + (i >> 1) * 1024 + lrow + ((((i & 1) * 2 + lh) ^ lsw) << 4));
        asm volatile("fence.proxy.async.shared::cta;" ::"r"(wa[31][0]), "r"(wa[35][0]) : "memory");
        __syncwarp();
        if (w < R1W) {
            if (lane == 0) {
                mbar_expect(bar1, 6144 + nko * 1024);
                for (int i = 0; i < 3; i++) tma2d(wr + 8192 + i * 2048, &mv, cv, 128 * w + 32 + 32 * i, bar1);
                for (int i = 0; i < nko; i++) tma2d(wr + 14336 + i * 1024, &mo, 32 * h, 16 * (ks0 + i), bar1);
            }
#pragma unroll 1
            for (int i = 8; i < 16; i++) cp_rows(i);
        } else {
#pragma unroll 1
            for (int i = 9; i < 18; i++) {
                const uint32_t bar = bar0 + (i & 1) * 8;
                if (i >= 11) mbar_wait(bar, ((i >> 1) - 1) & 1);
                if (lane == 0) {
                    const int j = 2 * (i - 12), nb = min(2, nko - j);
                    mbar_expect(bar, i < 12 ? 2048 : nb * 1024);
                    if (i < 12) tma2d(wr + 8192 + (i - 9) * 2048, &mv, cv, 128 * w + 32 * (i - 8), bar);
                    else for (int e = 0; e < nb; e++) tma2d(wr + 14336 + (j + e) * 1024, &mo, 32 * h, 16 * (ks0 + j + e), bar);
                }
                if (i < 17) cp_rows(i - 1);
            }
        }
        mbar_wait(bar0, 0); mbar_wait(bar1, 0);
#pragma unroll 1
        for (int i0 = -1; i0 < 17; i0 += 6) {
            uint32_t x[6][2][4];
#pragma unroll
            for (int i = 0; i < 6; i++) {
                const uint32_t a = wr + 8192 + max(i0 + i, 0) * 1024 + lrow;
                ldsm4t(x[i][0], a + ((lh ^ lsw) << 4)); ldsm4t(x[i][1], a + (((2 + lh) ^ lsw) << 4));
            }
            if (i0 == 11 && nko == 10) {
#pragma unroll
                for (int j = 0; j < 8; j++) x[5][j >> 2][j & 3] = 0;
            }
            __syncwarp();
#pragma unroll
            for (int i = 0; i < 6; i++) {
                const uint32_t a = wr + 8192 + max(i0 + i, 0) * 1024 + lane * 16;
                stsm4t(a, x[i][0][0], x[i][0][1], x[i][0][2], x[i][0][3]); stsm4t(a + 512, x[i][1][0], x[i][1][1], x[i][1][2], x[i][1][3]);
            }
        }
        asm volatile("cp.async.wait_all;" ::: "memory");
        asm volatile("barrier.cluster.wait.aligned;" ::: "memory");
        bar_sync(1, 256);
        mbar_wait_long(sb + CH_BAR + 16, 0);
        const int side = __shfl_sync(0xffffffffu, *(volatile int*)(smem + CH_BAR + 28), 0);
        if (w >= nq) chain_loop<true>(wa, sb, w, lane, rank, h, side);
        else chain_loop<false>(wa, sb, w, lane, rank, h, side);
    }
}

constexpr int G_STAGE = 49152, G_NST = 4;
constexpr int G_STG = G_NST * G_STAGE;
constexpr int G_BAR = G_STG + 32768;
constexpr int G_SMEM = G_BAR + 256 + 1024;

#define WLOG(e)
constexpr int IT_QA = 0, IT_O = 1, IT_S4 = 2, IT_END = 3, IT_KV = 4;
#define O_WIDE 10
#define TMP 1
#define ATT2 0
#define S4REL 4
#define KVI 2
#define KVF 2
#define KVS 8
#define STM 0
__device__ __forceinline__ void st_out(uint32_t* p, uint32_t v) {
    if (STM == 0) *p = v;
    else if (STM == 1) __stcs(p, v);
    else asm volatile("st.global.L1::no_allocate.u32 [%0], %1;" ::"l"(p), "r"(v) : "memory");
}
#define Q_N1 1
#define Q_S1 12
__device__ __forceinline__ int queue_item(int q) {
    if (q < 512) return (IT_KV << 16) | ((q >> 5) << 8) | (q & 31);
    q -= 512;
    if (q < 256) return (IT_QA << 16) | ((q >> 4) << 8) | (q & 15);
    q -= 256;
    if (q < Q_N1 * 8) return (IT_O << 16) | ((O_WIDE + (q >> 3)) << 8) | (q & 7);
    q -= Q_N1 * 8;
    if (q < Q_S1) return (IT_S4 << 16) | q;
    q -= Q_S1;
    if (q < (16 - O_WIDE - Q_N1) * 8) return (IT_O << 16) | ((O_WIDE + Q_N1 + (q >> 3)) << 8) | (q & 7);
    q -= (16 - O_WIDE - Q_N1) * 8;
    if (q < 128 - Q_S1) return (IT_S4 << 16) | (Q_S1 + q);
    return IT_END << 16;
}
__device__ __forceinline__ void tma2d_store(const CUtensorMap* m, uint32_t src, int c0, int c1) {
    asm volatile("cp.async.bulk.tensor.2d.global.shared::cta.bulk_group [%0, {%2, %3}], [%1];" ::"l"(m), "r"(src), "r"(c0), "r"(c1) : "memory");
}

__device__ __forceinline__ void wgmma_s64(float (&d)[32], uint32_t a0, uint32_t a1, uint32_t a2, uint32_t a3, uint64_t db, int acc) {
    asm volatile("{.reg .pred p; setp.ne.b32 p, %37, 0;\n"
        "wgmma.mma_async.sync.aligned.m64n64k16.f32.bf16.bf16 {"
        "%0,%1,%2,%3,%4,%5,%6,%7,%8,%9,%10,%11,%12,%13,%14,%15,"
        "%16,%17,%18,%19,%20,%21,%22,%23,%24,%25,%26,%27,%28,%29,%30,%31"
        "}, {%32,%33,%34,%35}, %36, p, 1, 1, 0;}"
        : "+f"(d[0]), "+f"(d[1]), "+f"(d[2]), "+f"(d[3]), "+f"(d[4]), "+f"(d[5]), "+f"(d[6]), "+f"(d[7]), "+f"(d[8]), "+f"(d[9]), "+f"(d[10]), "+f"(d[11]), "+f"(d[12]), "+f"(d[13]), "+f"(d[14]), "+f"(d[15]), "+f"(d[16]), "+f"(d[17]), "+f"(d[18]), "+f"(d[19]), "+f"(d[20]), "+f"(d[21]), "+f"(d[22]), "+f"(d[23]), "+f"(d[24]), "+f"(d[25]), "+f"(d[26]), "+f"(d[27]), "+f"(d[28]), "+f"(d[29]), "+f"(d[30]), "+f"(d[31])
        : "r"(a0), "r"(a1), "r"(a2), "r"(a3), "l"(db), "r"(acc));
}
__device__ __forceinline__ void wgmma_s16(float (&d)[8], uint32_t a0, uint32_t a1, uint32_t a2, uint32_t a3, uint64_t db, int acc) {
    asm volatile("{.reg .pred p; setp.ne.b32 p, %13, 0;\n"
        "wgmma.mma_async.sync.aligned.m64n16k16.f32.bf16.bf16 {"
        "%0,%1,%2,%3,%4,%5,%6,%7"
        "}, {%8,%9,%10,%11}, %12, p, 1, 1, 0;}"
        : "+f"(d[0]), "+f"(d[1]), "+f"(d[2]), "+f"(d[3]), "+f"(d[4]), "+f"(d[5]), "+f"(d[6]), "+f"(d[7])
        : "r"(a0), "r"(a1), "r"(a2), "r"(a3), "l"(db), "r"(acc));
}
__device__ __forceinline__ void wgmma_v128(float (&d)[64], uint32_t a0, uint32_t a1, uint32_t a2, uint32_t a3, uint64_t db, int acc) {
    asm volatile("{.reg .pred p; setp.ne.b32 p, %69, 0;\n"
        "wgmma.mma_async.sync.aligned.m64n128k16.f32.bf16.bf16 {"
        "%0,%1,%2,%3,%4,%5,%6,%7,%8,%9,%10,%11,%12,%13,%14,%15,"
        "%16,%17,%18,%19,%20,%21,%22,%23,%24,%25,%26,%27,%28,%29,%30,%31,"
        "%32,%33,%34,%35,%36,%37,%38,%39,%40,%41,%42,%43,%44,%45,%46,%47,"
        "%48,%49,%50,%51,%52,%53,%54,%55,%56,%57,%58,%59,%60,%61,%62,%63"
        "}, {%64,%65,%66,%67}, %68, p, 1, 1, 1;}"
        : "+f"(d[0]), "+f"(d[1]), "+f"(d[2]), "+f"(d[3]), "+f"(d[4]), "+f"(d[5]), "+f"(d[6]), "+f"(d[7]), "+f"(d[8]), "+f"(d[9]), "+f"(d[10]), "+f"(d[11]), "+f"(d[12]), "+f"(d[13]), "+f"(d[14]), "+f"(d[15]), "+f"(d[16]), "+f"(d[17]), "+f"(d[18]), "+f"(d[19]), "+f"(d[20]), "+f"(d[21]), "+f"(d[22]), "+f"(d[23]), "+f"(d[24]), "+f"(d[25]), "+f"(d[26]), "+f"(d[27]), "+f"(d[28]), "+f"(d[29]), "+f"(d[30]), "+f"(d[31]), "+f"(d[32]), "+f"(d[33]), "+f"(d[34]), "+f"(d[35]), "+f"(d[36]), "+f"(d[37]), "+f"(d[38]), "+f"(d[39]), "+f"(d[40]), "+f"(d[41]), "+f"(d[42]), "+f"(d[43]), "+f"(d[44]), "+f"(d[45]), "+f"(d[46]), "+f"(d[47]), "+f"(d[48]), "+f"(d[49]), "+f"(d[50]), "+f"(d[51]), "+f"(d[52]), "+f"(d[53]), "+f"(d[54]), "+f"(d[55]), "+f"(d[56]), "+f"(d[57]), "+f"(d[58]), "+f"(d[59]), "+f"(d[60]), "+f"(d[61]), "+f"(d[62]), "+f"(d[63])
        : "r"(a0), "r"(a1), "r"(a2), "r"(a3), "l"(db), "r"(acc));
}

__device__ __forceinline__ void attn_scores(float (&sx)[32], float (&sm)[8], const uint32_t (&q)[32], uint32_t sk) {
    const uint64_t dx = mkdesc(sk, 1024, 128, 0), dm = mkdesc(sk + 16384, 256, 128, 0);
    wg_fence();
#pragma unroll
    for (int ks = 0; ks < 8; ks++) {
        wgmma_s64(sx, q[4 * ks], q[4 * ks + 1], q[4 * ks + 2], q[4 * ks + 3], dx + ks * 128, ks);
        wgmma_s16(sm, q[4 * ks], q[4 * ks + 1], q[4 * ks + 2], q[4 * ks + 3], dm + ks * 32, ks);
    }
    wg_commit();
}
__device__ __forceinline__ void attn_softmax(uint32_t (&p)[20], const float (&sx)[32], const float (&sm)[8], int wi, int lane) {
    const bool sb = wi >= 2;
    const int r0 = (wi & 1) * 16 + (lane >> 2) - 2 * (lane & 3);
    float s[5][4];
#pragma unroll
    for (int j = 0; j < 4; j++) s[4][j] = sb ? sm[4 + j] : sm[j];
    float m0 = fmaxf(s[4][0], s[4][1]), m1 = fmaxf(s[4][2], s[4][3]);
#pragma unroll
    for (int j = 0; j < 4; j++) {
#pragma unroll
        for (int e = 0; e < 4; e++) s[j][e] = 8 * j + (e & 1) > r0 + 8 * (e >> 1) ? -INFINITY : sb ? sx[16 + 4 * j + e] : sx[4 * j + e];
        m0 = fmaxf(m0, fmaxf(s[j][0], s[j][1])); m1 = fmaxf(m1, fmaxf(s[j][2], s[j][3]));
    }
    m0 = fmaxf(m0, __shfl_xor_sync(0xffffffffu, m0, 1)); m1 = fmaxf(m1, __shfl_xor_sync(0xffffffffu, m1, 1));
    m0 = fmaxf(m0, __shfl_xor_sync(0xffffffffu, m0, 2)); m1 = fmaxf(m1, __shfl_xor_sync(0xffffffffu, m1, 2));
    const float cs = 0.08838834764831845f * 1.4426950408889634f;
    m0 *= -cs; m1 *= -cs;
    float l0 = 0, l1 = 0;
#pragma unroll
    for (int j = 0; j < 5; j++) {
        s[j][0] = ex2(fmaf(s[j][0], cs, m0)); s[j][1] = ex2(fmaf(s[j][1], cs, m0));
        s[j][2] = ex2(fmaf(s[j][2], cs, m1)); s[j][3] = ex2(fmaf(s[j][3], cs, m1));
        l0 += s[j][0] + s[j][1]; l1 += s[j][2] + s[j][3];
    }
    l0 += __shfl_xor_sync(0xffffffffu, l0, 1); l1 += __shfl_xor_sync(0xffffffffu, l1, 1);
    l0 += __shfl_xor_sync(0xffffffffu, l0, 2); l1 += __shfl_xor_sync(0xffffffffu, l1, 2);
    asm("rcp.approx.ftz.f32 %0, %0;" : "+f"(l0)); asm("rcp.approx.ftz.f32 %0, %0;" : "+f"(l1));
    const uint32_t ma = sb ? 0u : ~0u;
#pragma unroll
    for (int j = 0; j < 5; j++) {
        const uint32_t x = pack_bf16(s[j][0] * l0, s[j][1] * l0), y = pack_bf16(s[j][2] * l1, s[j][3] * l1);
        const int ia = j < 4 ? 2 * j : 16, ib = j < 4 ? 8 + 2 * j : 18;
        asm volatile("and.b32 %0, %4, %6; and.b32 %1, %5, %6; and.b32 %2, %4, %7; and.b32 %3, %5, %7;"
            : "=&r"(p[ia]), "=&r"(p[ia + 1]), "=&r"(p[ib]), "=&r"(p[ib + 1]) : "r"(x), "r"(y), "r"(ma), "r"(~ma));
    }
}
__device__ __forceinline__ void attn_pv(float (&o)[64], const uint32_t (&p)[20], uint32_t sv) {
    const uint64_t dx = mkdesc(sv, 128, 1024, 0), dm = mkdesc(sv + 16384, 128, 256, 0);
    wg_fence();
#pragma unroll
    for (int ks = 0; ks < 5; ks++) wgmma_v128(o, p[4 * ks], p[4 * ks + 1], p[4 * ks + 2], p[4 * ks + 3], ks < 4 ? dx + ks * 16 : dm, ks);
    wg_commit();
}
__device__ __forceinline__ void attn_stage(const float (&o)[64], uint32_t dst) {
#pragma unroll
    for (int u = 0; u < 16; u += 2)
        stsm4(dst + (u >> 3) * 8192 + (u & 7) * 128, pack_bf16(o[4 * u], o[4 * u + 1]), pack_bf16(o[4 * u + 2], o[4 * u + 3]),
              pack_bf16(o[4 * u + 4], o[4 * u + 5]), pack_bf16(o[4 * u + 6], o[4 * u + 7]));
}

template <int BN, int NKB, bool BLOCKED_A>
__device__ __forceinline__ void mainloop(float (&acc)[BN / 2], uint32_t sb, int wgi, uint32_t full, uint32_t empty, int& it, bool elect) {
#pragma unroll
    for (int j = 0; j < BN / 2; j++) acc[j] = 0.f;
#pragma unroll 1
    for (int k4 = 0; k4 < NKB; k4 += 4) {
#pragma unroll
        for (int st = 0; st < 4; st++, it++) {
            mbar_wait_long(full + 8 * st, (it >> 2) & 1);
            const uint64_t da = BLOCKED_A ? mkdesc(sb + st * G_STAGE + wgi * 8192, 128, 1024, 0) : mkdesc(sb + st * G_STAGE + wgi * 8192, 16, 1024, 1);
            const uint64_t db = mkdesc(sb + st * G_STAGE + 16384, 8192, 1024, 1);
            wg_fence();
#pragma unroll
            for (int k = 0; k < 4; k++) {
                if constexpr (BN == 256) wgmma256(acc, da + k * (BLOCKED_A ? 16 : 2), db + k * 128, 1);
                else wgmma128(acc, da + k * (BLOCKED_A ? 16 : 2), db + k * 128, 1);
            }
            wg_commit();
            if (k4 | st) {
                wg_wait<1>();
                if (elect) mbar_arrive(empty + 8 * ((st + 3) & 3));
            }
        }
    }
    wg_wait<0>();
    if (elect) mbar_arrive(empty + 8 * 3);
}

__device__ __forceinline__ uint32_t n6_a(int st) { return st < 4 ? st * G_STAGE : (2 * st - 8) * G_STAGE + 32768; }
__device__ __forceinline__ uint32_t n6_b(int st) { return st < 4 ? st * G_STAGE + 16384 : (2 * st - 7) * G_STAGE + 32768; }
__device__ __forceinline__ uint32_t n6_bar(int st) { return st < 4 ? 8 * st : 96 + 8 * st; }
__device__ __forceinline__ void mainloop6(float (&acc)[64], uint32_t sb, int wgi, uint32_t full, uint32_t empty, int& it, bool elect) {
#pragma unroll
    for (int j = 0; j < 64; j++) acc[j] = 0.f;
    int st = 0, prev = 0, r = 0;
#pragma unroll 1
    for (int kb = 0; kb < 64; kb++) {
        mbar_wait_long(full + n6_bar(st), ((st < 4 ? it >> 2 : 0) + r) & 1);
        const uint64_t da = mkdesc(sb + n6_a(st) + wgi * 8192, 128, 1024, 0), db = mkdesc(sb + n6_b(st), 8192, 1024, 1);
        wg_fence();
#pragma unroll
        for (int k = 0; k < 4; k++) wgmma128(acc, da + k * 16, db + k * 128, 1);
        wg_commit();
        if (kb) {
            wg_wait<1>();
            if (elect) mbar_arrive(empty + n6_bar(prev));
        }
        prev = st;
        if (++st == 6) { st = 0; r++; }
    }
    wg_wait<0>();
    if (elect) mbar_arrive(empty + 8 * 3);
    it += 44;
}

template <int BN>
__device__ __forceinline__ void o_item(uint32_t sb, int wgi, int wi, int lane, uint32_t full, uint32_t empty, int& it, const CUtensorMap* mout,
                                       int row0, int col0, uint32_t stgpar) {
    float acc[BN / 2];
    if constexpr (BN == 256) mainloop<BN, 64, true>(acc, sb, wgi, full, empty, it, lane == 0);
    else mainloop6(acc, sb, wgi, full, empty, it, lane == 0);
    ST((row0 >> 4) + (col0 / BN), wgi * 4 + wi, 10);
    mbar_wait(full + 104, stgpar);
    const uint32_t stg = sb + G_STG + (wgi * 4 + wi) * 4096;
    const int r = lane & 15, cu = lane >> 4;
#pragma unroll
    for (int hf = 0; hf < BN / 128; hf++) {
        if (lane == 0) asm volatile("cp.async.bulk.wait_group.read 0;" ::: "memory");
        __syncwarp();
#pragma unroll
        for (int j = 0; j < 8; j++) {
            const float* a = acc + hf * 64 + j * 8;
            stsm4(stg + (j >> 2) * 2048 + r * 128 + ((((j & 3) * 2 + cu) ^ (r & 7)) << 4),
                  pack_bf16(a[0], a[1]), pack_bf16(a[2], a[3]), pack_bf16(a[4], a[5]), pack_bf16(a[6], a[7]));
        }
        asm volatile("fence.proxy.async.shared::cta;" ::: "memory");
        __syncwarp();
        if (lane == 0) {
            tma2d_store(mout, stg, col0 + hf * 128, row0 + wgi * 64 + wi * 16);
            tma2d_store(mout, stg + 2048, col0 + hf * 128 + 64, row0 + wgi * 64 + wi * 16);
            asm volatile("cp.async.bulk.commit_group;" ::: "memory");
        }
    }
}

constexpr int S4_KD = 32768;
constexpr int S4_CH = 2 * G_STAGE;
constexpr int S4_HALF = 2304;
constexpr int S4_WD = 2 * S4_HALF;
constexpr int S4_T2 = S4_WD + 2304;
constexpr int S4_T3 = S4_T2 + 1024;
constexpr int S4_STRIDE = S4_T3 + 640 + 16;
__device__ __forceinline__ uint32_t addz(uint32_t x, uint32_t z) { uint32_t r; asm volatile("add.u32 %0, %1, %2;" : "=r"(r) : "r"(x), "r"(z)); return r; }
__device__ __forceinline__ uint32_t lds16(uint32_t a) { uint32_t v; asm volatile("ld.shared.u16 %0, [%1];" : "=r"(v) : "r"(a) : "memory"); return v; }
__device__ __forceinline__ uint32_t ldsu(uint32_t a) { return __float_as_uint(lds32(a)); }

template <int E0, int NE, int KP>
__device__ __forceinline__ void s4_windows(float (&acc)[8][2][4], uint32_t ut, uint32_t tw, int rho, int w, int lane, uint32_t z) {
    const int gt = (lane >> 2) - 2 * (lane & 3), p0 = rho == 16 ? -3 : -2, c = (lane >> 3) + p0;
    uint32_t band[2][4], ta[NE][4];
    {
        const uint64_t ones = ((uint64_t)((2u << 2 * w) - 1) << 32) >> (8 * p0 + 24 - gt + rho + w);
        uint32_t f[5];
#pragma unroll
        for (int m = 0; m < 5; m++) f[m] = ((((uint32_t)(ones >> (8 * m)) & 3) * 0x8001u) & 0x10001u) * 0x3F80u;
#pragma unroll
        for (int j = 0; j < 2; j++) { band[j][0] = f[2 * j + 1]; band[j][1] = addz(f[2 * j], z); band[j][2] = f[2 * j + 2]; band[j][3] = addz(f[2 * j + 1], z); }
    }
#pragma unroll
    for (int e = 0; e < NE; e++)
        asm volatile("ld.shared.u32 %0, [%4]; ld.shared.u32 %1, [%4+%5]; ld.volatile.shared.u32 %2, [%4+%6]; ld.volatile.shared.u32 %3, [%4];"
            : "=r"(ta[e][0]), "=r"(ta[e][1]), "=r"(ta[e][2]), "=r"(ta[e][3]) : "r"(tw + 16 * (E0 + e) * KP), "n"(8 * KP), "n"(-8 * KP) : "memory");
    const uint32_t ua = ut + (c & 1) * S4_HALF + (16 + (lane & 7) + (c >> 1)) * 16;
#pragma unroll
    for (int J = 0; J < 8 - E0; J++) {
        uint32_t u0[4], u1[4];
        ldsm4(u0, ua + J * 256); ldsm4(u1, ua + J * 256 + 128);
        float s0[4], s1[4];
        mma16z(s0, band[0], u0[0], u0[1]); mma16z(s1, band[0], u1[0], u1[1]);
        mma16(s0, band[1], u0[2], u0[3]); mma16(s1, band[1], u1[2], u1[3]);
        const uint32_t b00 = pack_bf16(s0[0], s0[1]), b01 = pack_bf16(s1[0], s1[1]), b10 = pack_bf16(s0[2], s0[3]), b11 = pack_bf16(s1[2], s1[3]);
#pragma unroll
        for (int e = 0; e < NE; e++)
            if (J + E0 + e < 8) { mma16(acc[J + E0 + e][0], ta[e], b00, b01); mma16(acc[J + E0 + e][1], ta[e], b10, b11); }
    }
}
template <int D0, int D1>
__device__ __forceinline__ void s4_dense(float (&acc)[8][2][4], uint32_t ua, const uint32_t (&b0)[4], const uint32_t (&b1)[4]) {
#pragma unroll
    for (int J = 0; J < 8 - D0; J++) {
        uint32_t a[4];
        ldsm4(a, ua + J * 256);
        mma16(acc[J + D0][0], a, b0[0], b0[1]); mma16(acc[J + D0][1], a, b0[2], b0[3]);
        if (J + D1 < 8) { mma16(acc[J + D1][0], a, b1[0], b1[1]); mma16(acc[J + D1][1], a, b1[2], b1[3]); }
    }
}
__device__ __forceinline__ void s4_words(uint32_t (&b)[4], uint32_t wd) {
    asm volatile("ld.shared.u32 %0, [%4]; ld.shared.u32 %1, [%4+-32]; ld.shared.u32 %2, [%4+32]; ld.volatile.shared.u32 %3, [%4];"
        : "=r"(b[0]), "=r"(b[1]), "=r"(b[2]), "=r"(b[3]) : "r"(wd) : "memory");
}

__device__ __forceinline__ void s4_item(uint32_t sb, int cw, int lane, int item, const bf16* __restrict__ dsk, uint32_t empty, const CUtensorMap* my, uint32_t stgpar) {
    const int gt = (lane >> 2) - 2 * (lane & 3);
    const uint32_t ch = sb + S4_CH + cw * S4_STRIDE, kd = sb + S4_KD + cw * 1536;
    const __nv_bfloat162 dk = __bfloat162bfloat162(dsk[item * 8 + cw]);
    ST(item, cw, 0);
    asm volatile("st.shared.v4.u32 [%0], {%1,%1,%1,%1};" ::"r"(ch + (lane >> 4) * S4_HALF + (lane & 15) * 16), "r"(0) : "memory");
    const uint32_t tch = sb + S4_CH + (lane & 7) * S4_STRIDE + ((lane >> 3) & 1) * S4_HALF + (16 + 16 * cw + (lane >> 4)) * 16;
#pragma unroll
    for (int i = 0; i < 8; i++) {
        uint32_t x[4];
        ldsm4t(x, sb + cw * 4096 + i * 512 + lane * 16);
        stsm4(tch + i * 32, x[0], x[1], x[2], x[3]);
    }
    const uint32_t k1024 = lds16(kd + 1024);
    {
        auto st4 = [](uint32_t a, uint32_t x, uint32_t y, uint32_t u, uint32_t v) {
            asm volatile("st.shared.v4.u32 [%0], {%1,%2,%3,%4};" ::"r"(a), "r"(x), "r"(y), "r"(u), "r"(v) : "memory");
        };
        const float4 p = lds128(kd + lane * 16);
        const uint32_t p0 = __float_as_uint(p.x), p1 = __float_as_uint(p.y), p2 = __float_as_uint(p.z), p3 = __float_as_uint(p.w);
        const uint32_t pm = lane ? ldsu(kd + lane * 16 - 4) : 0;
        const uint32_t wa = ch + S4_WD + 64 + lane * 32;
        st4(wa, __byte_perm(p0, pm, 0x7610), __byte_perm(p0, 0, 0x1032), __byte_perm(p1, p0, 0x7610), __byte_perm(p1, 0, 0x1032));
        st4(wa + 16, __byte_perm(p2, p1, 0x7610), __byte_perm(p2, 0, 0x1032), __byte_perm(p3, p2, 0x7610), __byte_perm(p3, 0, 0x1032));
        const float2 q = lds64(kd + 512 + lane * 8);
        const uint32_t q0 = __float_as_uint(q.x), q1 = __float_as_uint(q.y), q2 = ldsu(kd + 520 + lane * 8), k255 = ldsu(kd + 508);
        st4(wa + 1024, lane ? __byte_perm(q0, 0, 0x1010) : __byte_perm(q0, k255, 0x7610), __byte_perm(q0, 0, 0x1010), __byte_perm(q0, 0, 0x1032), __byte_perm(q1, q0, 0x7610));
        st4(wa + 1040, __byte_perm(q1, 0, 0x1010), __byte_perm(q1, 0, 0x1010), __byte_perm(q1, 0, 0x1032), __byte_perm(q2, q1, 0x7610));
        const uint32_t k512 = lane == 4 ? lds16(kd + 768) : 0;
        if (lane < 16) st4(ch + S4_WD + (lane < 4 ? 0 : 2048) + lane * 16, k512 * 0x10001u, k512 * 0x10001u, k512 * 0x10001u, k512 << 16);
        const float2 c = lds64(kd + 768 + lane * 8), d = lds64(kd + 760 + lane * 8);
        const uint32_t c0 = __float_as_uint(c.x), c1 = __float_as_uint(c.y), c2 = ldsu(kd + 776 + lane * 8);
        const uint32_t d0 = lane ? __float_as_uint(d.x) : 0, d1 = lane ? __float_as_uint(d.y) : 0, d2 = lane ? c0 : 0;
        st4(ch + S4_T2 + 256 + lane * 16, __byte_perm(c0, d0, 0x7632), __byte_perm(c1, d1, 0x5410), __byte_perm(c1, d1, 0x7632), __byte_perm(c2, d2, 0x5410));
        const uint32_t m = lane == 31 ? 0xFFFF0000u : 0;
        st4(ch + S4_T2 + (lane < 16 ? lane : lane == 31 ? 48 : lane + 33) * 16, c0 & m, (c1 << 16) & m, c1 & m, (c2 << 16) & m);
        const float2 e = lds64(kd + 1024 + lane * 8);
        const uint32_t e0 = __float_as_uint(e.x), e1 = __float_as_uint(e.y), e2 = ldsu(kd + 1032 + lane * 8), em = ldsu(kd + 1020 + lane * 8);
        st4(ch + S4_T3 + 128 + lane * 16, __byte_perm(e0, lane ? em : 0, 0x7632), __byte_perm(e1, lane ? e0 : 0, 0x5410), __byte_perm(e1, e0, 0x7632), __byte_perm(e2, e1, 0x5410));
        if (lane < 8) st4(ch + S4_T3 + lane * 16, 0, 0, 0, 0);
    }
    bar_sync(2, 256);
    ST(item, cw, 1);
    const uint32_t z = ldsu(ch);
    float acc[8][2][4];
#pragma unroll
    for (int j = 0; j < 16; j++) acc[j >> 1][j & 1][0] = acc[j >> 1][j & 1][1] = acc[j >> 1][j & 1][2] = acc[j >> 1][j & 1][3] = 0.f;
#pragma unroll 1
    for (int r = 1; r <= 4; r++) s4_windows<2, 3, 16>(acc, ch, ch + S4_T2 + (gt - 16) * 16 + 4 * r - 4, 4 * r, 2 - (r & 1), lane, z);
    ST(item, cw, 2);
#pragma unroll 1
    for (int r = 1; r <= 2; r++) s4_windows<4, 4, 8>(acc, ch, ch + S4_T3 + (gt - 48) * 8 + 4 * r - 4, 8 * r, 2 + r, lane, z);
    ST(item, cw, 3);
    const uint32_t ua = ch + (lane >> 4) * S4_HALF + (16 + (lane & 15)) * 16, wd = ch + S4_WD + 64 + gt * 4;
#pragma unroll 1
    for (int q = 0; q < 2; q++) {
        uint32_t b0[4], b1[4];
        s4_words(b0, wd + (q + 32) * 64);
#pragma unroll
        for (int j = 0; j < 4; j++) {
            const int x = 16 * q + gt + (j == 1 ? -8 : j == 2 ? 8 : 0) - 3;
            b1[j] = addz(((unsigned)x < 2u ? k1024 : 0u) | ((unsigned)(x - 1) < 2u ? k1024 << 16 : 0u), z);
        }
        s4_dense<2, 4>(acc, ua - q * 16, b0, b1);
    }
    {
        uint32_t b0[4], b1[4], c0[4], c1[4];
        s4_words(b0, wd); s4_words(b1, wd + 1024);
#pragma unroll 1
        for (int q = 0; q < 16; q += 2) {
            s4_words(c0, wd + q * 64 + 64); s4_words(c1, wd + q * 64 + 64 + 1024);
            s4_dense<0, 1>(acc, ua - q * 16, b0, b1);
            s4_words(b0, wd + q * 64 + 128); s4_words(b1, wd + q * 64 + 128 + 1024);
            s4_dense<0, 1>(acc, ua - q * 16 - 16, c0, c1);
            if (q == S4REL && lane == 0) { mbar_arrive(empty); mbar_arrive(empty + 8); }
        }
    }
    ST(item, cw, 4);
    mbar_wait(empty + 72, stgpar);
    if (lane == 0) asm volatile("cp.async.bulk.wait_group.read 0;" ::: "memory");
    __syncwarp();
#pragma unroll
    for (int I = 0; I < 8; I++) {
        uint32_t u[4];
        ldsm4(u, ua + I * 256);
#pragma unroll
        for (int j = 0; j < 4; j++) {
            const uint32_t y = pack_bf16(acc[I][j >> 1][2 * (j & 1)], acc[I][j >> 1][2 * (j & 1) + 1]);
            const __nv_bfloat162 r = __hadd2_rn(*(const __nv_bfloat162*)&y, __hmul2_rn(*(const __nv_bfloat162*)&u[j], dk));
            u[j] = *(const uint32_t*)&r;
        }
        stsm4(ua + I * 256, u[0], u[1], u[2], u[3]);
    }
    bar_sync(2, 256);
#pragma unroll
    for (int i = 0; i < 8; i++) {
        uint32_t y[4];
        ldsm4t(y, tch + i * 32);
        stsm4(sb + G_STG + cw * 4096 + i * 512 + lane * 16, y[0], y[1], y[2], y[3]);
    }
    asm volatile("fence.proxy.async.shared::cta;" ::: "memory");
    __syncwarp();
    if (lane == 0) {
        mbar_arrive(empty + 16); mbar_arrive(empty + 24);
        tma2d_store(my, sb + G_STG + cw * 4096, DM + item * 8, cw * 256);
        asm volatile("cp.async.bulk.commit_group;" ::: "memory");
    }
    ST(item, cw, 5);
}

__global__ void __launch_bounds__(384, 1)
worker_kernel(const __grid_constant__ CUtensorMap mx, const __grid_constant__ CUtensorMap mq, const __grid_constant__ CUtensorMap mk,
              const __grid_constant__ CUtensorMap mv, const __grid_constant__ CUtensorMap mo,
              const __grid_constant__ CUtensorMap mout, const __grid_constant__ CUtensorMap mu, const __grid_constant__ CUtensorMap my,
              const __grid_constant__ CUtensorMap mkx, const __grid_constant__ CUtensorMap mvx, const __grid_constant__ CUtensorMap mkm,
              const __grid_constant__ CUtensorMap mvm, const bf16* __restrict__ dsk) {
    extern __shared__ unsigned char smem_raw[];
    const uint32_t sb = (smem_u32(smem_raw) + 1023) & ~1023u;
    const uint32_t full = sb + G_BAR, empty = full + 32, ifull = full + 64, iempty = full + 80, islot = full + 96, stgbar = full + 104, sigbar = full + 112, sigslot = full + 120;
    const int tid = threadIdx.x, wg = tid >> 7, lane = tid & 31;
    if (TMP && tid >= 64 && tid < 76) {
        const CUtensorMap* maps[12] = {&mx, &mq, &mk, &mv, &mo, &mout, &mu, &my, &mkx, &mvx, &mkm, &mvm};
        const CUtensorMap* m = maps[0];
#pragma unroll
        for (int j = 1; j < 12; j++) if (tid - 64 == j) m = maps[j];
        asm volatile("prefetch.tensormap [%0];" ::"l"(m) : "memory");
    }
    int q0 = blockIdx.x;
    const int wide0 = q0 - ((int)gridDim.x - O_WIDE * 4);
    if (tid == 0) {
        if (q0 >= 32 && wide0 < 0) q0 = 32 + atomicAdd(g_ctr + C_NEXT, 1);
        for (int i = 0; i < 6; i++) { mbar_init(full + n6_bar(i), 1); mbar_init(empty + n6_bar(i), 8); }
        for (int i = 0; i < 2; i++) { mbar_init(ifull + 8 * i, 1); mbar_init(iempty + 8 * i, 8); }
        mbar_init(sigbar, 8); mbar_init(stgbar, 1);
        asm volatile("fence.proxy.async.shared::cta;" ::: "memory");
    }
    __syncthreads();
    if (wg == 0) {
        reg_dec<40>();
        if (tid >= 32 && tid < 64) {
            for (int n = 0;; n++) {
                mbar_wait_long(sigbar, n & 1);
                int item; asm volatile("ld.shared.u32 %0, [%1];" : "=r"(item) : "r"(sigslot + 4 * (n & 1)) : "memory");
                const int type = item >> 16, b = (item >> 8) & 255, i = item & 255;
                if (type == IT_END) break;
                if (type == IT_QA) {
                    if (lane == 0) {
                        for (int j = 0; j < 8; j++) {
                            const uint32_t src = sb + (j >= 4 ? G_STG + (j & 1) * 16384 : 3 * G_STAGE + (j & 1) * 20480) + ((j >> 1) & 1) * 8192;
                            asm volatile("cp.async.bulk.global.shared::cta.bulk_group [%0], [%1], 8192;"
                                ::"l"(g_ox + (size_t)(b * 64 + i * 4 + ((j >> 1) ^ 2)) * 8192 + (j & 1) * 4096), "r"(src) : "memory");
                            if ((j & 3) == 3) asm volatile("cp.async.bulk.commit_group;" ::: "memory");
                        }
                        asm volatile("cp.async.bulk.wait_group.read 1;" ::: "memory");
                        asm volatile("mbarrier.arrive.shared.b64 _, [%0], 8;" ::"r"(empty + 24) : "memory");
                        asm volatile("cp.async.bulk.wait_group 0;" ::: "memory");
                        mbar_arrive(stgbar);
                        asm volatile("fence.proxy.async.global;" ::: "memory");
                    }
                    __syncwarp();
                }
                if (type == IT_KV) { if (lane < 6) red_release(g_kvf + ((i & 15) * 6 + lane) * 16 + b, 1); }
                else if (lane == 0) red_release(g_ctr + C_QA_DONE + b, 1 << i);
            }
        } else if (tid < 32) {
            int it = 0;
            if (!KVN) asm volatile("griddepcontrol.wait;" ::: "memory");
            for (int n = 0;; n++) {
                int item = 0;
                if (lane == 0) {
                    if (n) q0 = 32 + atomicAdd(g_ctr + C_NEXT, 1);
                    item = n == 0 && wide0 >= 0 ? (IT_O << 16) | ((wide0 >> 2) << 8) | (wide0 & 3) : queue_item(q0);
                }
                item = __shfl_sync(0xffffffffu, item, 0);
                if (lane == 0) {
                    mbar_wait(iempty + 8 * (n & 1), ((n >> 1) & 1) ^ 1);
                    asm volatile("st.shared.u32 [%0], %1;" ::"r"(islot + 4 * (n & 1)), "r"(item) : "memory");
                    mbar_arrive(ifull + 8 * (n & 1));
                    const int type = item >> 16, b = (item >> 8) & 255, i = item & 255;
                    if (type == IT_QA || type == IT_KV) {
                        const CUtensorMap* mw = type == IT_QA ? &mq : i < 16 ? &mk : &mv;
                        bool ready = false;
                        for (int kb = 0; kb < 16; kb++, it++) {
                            const int st = it & 3;
                            mbar_wait(empty + 8 * st, ((it >> 2) & 1) ^ 1);
                            mbar_expect(full + 8 * st, G_STAGE);
                            const uint32_t a = sb + st * G_STAGE;
                            tma2d(a, &mx, kb * 64, b * 128, full + 8 * st);
                            tma3d(a + 16384, mw, 0, kb * 64, (i & 15) * 4, full + 8 * st);
                            tma3d(a + 32768, mw, 0, kb * 64, (i & 15) * 4 + 2, full + 8 * st);
                            if (type == IT_QA && kb == 3) ready = ld_acq(g_ctr + C_CHAIN + b) >= 96;
                            if (type == IT_QA && kb >= 3 && kb < 11) {
                                const size_t sh = (b * 4 + ((kb - 3) & 3)) * NH + i * 2;
                                asm volatile("cp.async.bulk.prefetch.L2.global [%0], 16384;" ::"l"((kb >= 7 ? g_vx : g_kx) + sh * 4096) : "memory");
                                if (ready) asm volatile("cp.async.bulk.prefetch.L2.global [%0], 4096;" ::"l"((kb >= 7 ? g_vm : g_km) + sh * 1024) : "memory");
                            }
                        }
                    }
                    if (type == IT_QA) {
                        wait_ctr(g_ctr + C_CHAIN + b, 96);
                        asm volatile("fence.proxy.async.global;" ::: "memory");
                        for (int st = 0; st < 4; st++, it++) {
                            mbar_wait(empty + 8 * st, ((it >> 2) & 1) ^ 1);
                            mbar_expect(full + 8 * st, 4 * 10240);
                            for (int g2 = 0; g2 < 2; g2++) {
                                tma3d(sb + st * G_STAGE + g2 * 20480, st < 2 ? &mkx : &mvx, 0, b * 4 + g2 * 2, (i * 2 + (st & 1)) * 16, full + 8 * st);
                                tma3d(sb + st * G_STAGE + g2 * 20480 + 16384, st < 2 ? &mkm : &mvm, 0, b * 4 + g2 * 2, (i * 2 + (st & 1)) * 16, full + 8 * st);
                            }
                        }
                    } else if (type == IT_O) {
                        const bool wide = b < O_WIDE;
                        int done = 0;
                        const int ns = wide ? 4 : 6;
                        for (int kb = 0, st = 0, r = 0; kb < 64; kb++) {
                            const uint32_t bo = n6_bar(st);
                            mbar_wait(empty + bo, (((st < 4 ? it >> 2 : 0) + r) & 1) ^ 1);
                            mbar_expect(full + bo, wide ? G_STAGE : 32768);
                            tma3d(sb + n6_b(st), &mo, 0, kb * 64, wide ? i * 4 : i * 2, full + bo);
                            if (wide) tma3d(sb + n6_b(st) + 16384, &mo, 0, kb * 64, i * 4 + 2, full + bo);
                            if (!(done >> (kb >> 2) & 1)) {
                                for (int sp = 0; sp < (1 << 20) && !((done = ld_acq(g_ctr + C_QA_DONE + b)) >> (kb >> 2) & 1); sp++) __nanosleep(64);
                                asm volatile("fence.proxy.async.global;" ::: "memory");
                            }
                            bulk_load(sb + n6_a(st), g_ox + (size_t)(b * 64 + kb) * 8192, 16384, full + bo);
                            if (++st == ns) { st = 0; r++; }
                        }
                        it += wide ? 64 : 44;
                    } else if (type == IT_S4) {
                        wait_ctr(g_ctr + C_CHAIN, 96);
                        asm volatile("fence.proxy.async.global;" ::: "memory");
                        mbar_wait(empty, ((it >> 2) & 1) ^ 1);
                        mbar_expect(full, 32768 + 12288);
                        bulk_load(sb + S4_KD, g_kd + i * 8 * 768, 12288, full);
                        for (int j = 0; j < 8; j++) tma2d(sb + j * 4096, &mu, i * 8, j * 256, full);
                        for (int st = 1; st < 4; st++) { mbar_wait(empty + 8 * st, ((it >> 2) & 1) ^ 1); mbar_arrive(full + 8 * st); }
                        it += 4;
                        mbar_wait_long(empty, ((it >> 2) & 1) ^ 1);
                    }
                }
                __syncwarp();
                if (item >> 16 == IT_END) break;
            }
            asm volatile("griddepcontrol.wait;" ::: "memory");
        }
    } else {
        reg_inc<232>();
        const int wu = __shfl_sync(0xffffffffu, tid >> 5, 0);
        const int wgi = (wu >> 2) - 1, wi = wu & 3;
        int it = 0, nqa = 0, nsig = 0, n = 0, item;
        auto next_item = [&]() {
            mbar_wait_long(ifull + 8 * (n & 1), (n >> 1) & 1);
            asm volatile("ld.shared.u32 %0, [%1];" : "=r"(item) : "r"(islot + 4 * (n & 1)) : "memory");
            __syncwarp();
            if (lane == 0) mbar_arrive(iempty + 8 * (n & 1));
        };
        auto signal = [&](int what) {
            if (tid == 128) asm volatile("st.shared.u32 [%0], %1;" ::"r"(sigslot + 4 * (nsig & 1)), "r"(what) : "memory");
            __syncwarp();
            if (lane == 0) mbar_arrive(sigbar);
            nsig++;
        };
        next_item();
        if (item >> 16 == IT_KV) {
            float acc[128];
            uint32_t pk[64];
            uint32_t* dst = nullptr;
            int prev = 0;
            do {
                WLOG(0);
#pragma unroll
                for (int kb = 0; kb < 16; kb++, it++) {
                    const int st = kb & 3;
                    mbar_wait(full + 8 * st, (it >> 2) & 1);
                    const uint64_t da = mkdesc(sb + st * G_STAGE + wgi * 8192, 16, 1024, 1);
                    const uint64_t db = mkdesc(sb + st * G_STAGE + 16384, 8192, 1024, 1);
                    wg_fence();
#pragma unroll
                    for (int k = 0; k < 4; k++) wgmma256(acc, da + k * 2, db + k * 128, kb | k);
                    wg_commit();
                    if (n <= KVI) {
                        if (kb < KVF && dst) {
#pragma unroll
                            for (int j = kb * (64 / KVF); j < (kb + 1) * (64 / KVF); j++) st_out(dst + (j >> 1) * 128 + (j & 1) * 32, pk[j]);
                            if (kb == KVF - 1) signal(prev);
                        }
                    } else if (kb < KVS) {
#pragma unroll
                        for (int j = kb * (64 / KVS); j < (kb + 1) * (64 / KVS); j++) st_out(dst + (j >> 1) * 128 + (j & 1) * 32, pk[j]);
                        if (kb == KVS - 1) signal(prev);
                    }
                    if (kb > 0) {
                        wg_wait<1>();
                        if (lane == 0) mbar_arrive(empty + 8 * ((kb - 1) & 3));
                    }
                }
                wg_wait<0>();
                if (lane == 0) mbar_arrive(empty + 8 * 3);
#pragma unroll
                for (int j = 0; j < 64; j++) pk[j] = pack_bf16(acc[2 * j], acc[2 * j + 1]);
                const int row = ((item >> 8) & 255) * 128 + wgi * 64 + wi * 16, nt = item & 255;
                dst = (uint32_t*)(nt < 16 ? g_kx : g_vx) + (size_t)((row >> 5) * 512 + (nt & 15) * 32) * 128 + (row & 31) * 4 + lane;
                prev = item;
                WLOG(1);
                n++;
                next_item();
            } while (item >> 16 == IT_KV);
            if (dst) {
#pragma unroll
                for (int j = 0; j < 64; j++) dst[(j >> 1) * 128 + (j & 1) * 32] = pk[j];
                signal(prev);
            }
        }
        for (;; n++, next_item()) {
            const int type = item >> 16, b = (item >> 8) & 255, i = item & 255;
            const int lane = (tid & 31) + (item >> 24), wgi = (wu >> 2) - 1 + __shfl_sync(0xffffffffu, item >> 24, 0), wi = wu & 3;
            WLOG(0);
            if (type == IT_QA) {
                float acc[128];
                ST(sid, cw, 0);
                ST(sid, cw, 1);
                mainloop<256, 16, false>(acc, sb, wgi, full, empty, it, lane == 0);
                ST(sid, cw, 2);
                uint32_t q0[32], q1[32];
#pragma unroll
                for (int j = 0; j < 32; j++) { q0[j] = pack_bf16(acc[2 * j], acc[2 * j + 1]); q1[j] = pack_bf16(acc[64 + 2 * j], acc[65 + 2 * j]); }
                const uint32_t par = (it >> 2) & 1, so = sb + wgi * 20480;
                float sx0[32] = {}, sm0[8] = {}, sx1[32] = {}, sm1[8] = {};
                uint32_t p0[20], p1[20];
                if (lane == 0) asm volatile("cp.async.bulk.wait_group.read 0;" ::: "memory");
                mbar_wait(stgbar, (nqa++ & 1) ^ 1);
                bar_sync(3 + wgi, 128);
                mbar_wait_long(full, par);
                ST(sid, cw, 3);
                attn_scores(sx0, sm0, q0, so);
                ST(sid, cw, 7);
                mbar_wait(full + 8, par);
                attn_scores(sx1, sm1, q1, so + G_STAGE);
                float o0[64] = {}, o1[64] = {};
                if (ATT2) {
                    ST(sid, cw, 8);
                    wg_wait<0>();
                    ST(sid, cw, 9);
                    if (lane == 0) { mbar_arrive(empty); mbar_arrive(empty + 8); }
                    attn_softmax(p0, sx0, sm0, wi, lane);
                    attn_softmax(p1, sx1, sm1, wi, lane);
                    ST(sid, cw, 10);
                    mbar_wait(full + 16, par);
                    ST(sid, cw, 11);
                    attn_pv(o0, p0, so + 2 * G_STAGE);
                    ST(sid, cw, 4);
                } else {
                    wg_wait<1>();
                    if (lane == 0) mbar_arrive(empty);
                    attn_softmax(p0, sx0, sm0, wi, lane);
                    mbar_wait(full + 16, par);
                    attn_pv(o0, p0, so + 2 * G_STAGE);
                    wg_wait<1>();
                    if (lane == 0) mbar_arrive(empty + 8);
                    ST(sid, cw, 4);
                    attn_softmax(p1, sx1, sm1, wi, lane);
                }
                mbar_wait(full + 24, par);
                attn_pv(o1, p1, so + 3 * G_STAGE);
                wg_wait<1>();
                if (lane == 0) mbar_arrive(empty + 16);
                ST(sid, cw, 5);
                const uint32_t da = (wi * 2 + ((lane >> 3) & 1)) * 1024 + (lane >> 4) * 128 + (lane & 7) * 16;
                attn_stage(o0, sb + G_STG + wgi * 16384 + da);
                wg_wait<0>();
                bar_sync(3 + wgi, 128);
                attn_stage(o1, so + 3 * G_STAGE + da);
                asm volatile("fence.proxy.async.shared::cta;" ::: "memory");
                ST(sid, cw, 6);
                signal(item);
                it += 4;
            } else if (type == IT_O) {
                ST(b * 8 + i, wgi * 4 + wi, 8);
                mbar_wait_long(full, (it >> 2) & 1);
                ST(b * 8 + i, wgi * 4 + wi, 9);
                if (b < O_WIDE) o_item<256>(sb, wgi, wi, lane, full, empty, it, &mout, b * 128, i * 256, (nqa & 1) ^ 1);
                else o_item<128>(sb, wgi, wi, lane, full, empty, it, &mout, b * 128, i * 128, (nqa & 1) ^ 1);
            } else if (type == IT_S4) {
                mbar_wait_long(full, (it >> 2) & 1);
                mbar_wait(full + 24, (it >> 2) & 1);
                s4_item(sb, wgi * 4 + wi, lane, i, dsk, empty, &my, (nqa & 1) ^ 1);
                it += 4;
            } else break;
            WLOG(1);
        }
        bar_sync(2, 256);
        signal(item);
        if (lane == 0) asm volatile("cp.async.bulk.wait_group 0;" ::: "memory");
    }
}

typedef CUresult (*EncodeFn)(CUtensorMap*, CUtensorMapDataType, cuuint32_t, void*, const cuuint64_t*, const cuuint64_t*, const cuuint32_t*,
                             const cuuint32_t*, CUtensorMapInterleave, CUtensorMapSwizzle, CUtensorMapL2promotion, CUtensorMapFloatOOBfill);
static EncodeFn get_encode() {
    void* fn = nullptr; cudaDriverEntryPointQueryResult st;
    cudaGetDriverEntryPoint("cuTensorMapEncodeTiled", &fn, cudaEnableDefault, &st);
    return (EncodeFn)fn;
}
static void map_act(EncodeFn enc, CUtensorMap* m, const void* p, int rows, int cols, int boxr) {
    cuuint64_t dim[2] = {(cuuint64_t)cols, (cuuint64_t)rows}, str[1] = {(cuuint64_t)cols * 2};
    cuuint32_t box[2] = {64, (cuuint32_t)boxr}, es[2] = {1, 1};
    enc(m, CU_TENSOR_MAP_DATA_TYPE_BFLOAT16, 2, (void*)p, dim, str, box, es, CU_TENSOR_MAP_INTERLEAVE_NONE, CU_TENSOR_MAP_SWIZZLE_128B,
        CU_TENSOR_MAP_L2_PROMOTION_L2_128B, CU_TENSOR_MAP_FLOAT_OOB_FILL_NONE);
}
static void map_w(EncodeFn enc, CUtensorMap* m, const void* p, int k, int n) {
    cuuint64_t dim[3] = {64, (cuuint64_t)k, (cuuint64_t)n / 64}, str[2] = {(cuuint64_t)n * 2, 128};
    cuuint32_t box[3] = {64, 64, 2}, es[3] = {1, 1, 1};
    enc(m, CU_TENSOR_MAP_DATA_TYPE_BFLOAT16, 3, (void*)p, dim, str, box, es, CU_TENSOR_MAP_INTERLEAVE_NONE, CU_TENSOR_MAP_SWIZZLE_128B,
        CU_TENSOR_MAP_L2_PROMOTION_L2_256B, CU_TENSOR_MAP_FLOAT_OOB_FILL_NONE);
}

static void map_kv(EncodeFn enc, CUtensorMap* m, void* p, int n) {
    cuuint64_t dim[3] = {(cuuint64_t)n, NSEG, 512}, str[2] = {(cuuint64_t)n * 1024, (cuuint64_t)n * 2};
    cuuint32_t box[3] = {(cuuint32_t)n, 2, 16}, es[3] = {1, 1, 1};
    enc(m, CU_TENSOR_MAP_DATA_TYPE_BFLOAT16, 3, p, dim, str, box, es, CU_TENSOR_MAP_INTERLEAVE_NONE, CU_TENSOR_MAP_SWIZZLE_NONE,
        CU_TENSOR_MAP_L2_PROMOTION_NONE, CU_TENSOR_MAP_FLOAT_OOB_FILL_NONE);
}
static void map_box(EncodeFn enc, CUtensorMap* m, const void* p, int rows, int ld, int boxc, int boxr, CUtensorMapSwizzle sw,
                    CUtensorMapL2promotion promo = CU_TENSOR_MAP_L2_PROMOTION_NONE) {
    cuuint64_t dim[2] = {(cuuint64_t)ld, (cuuint64_t)rows}, str[1] = {(cuuint64_t)ld * 2};
    cuuint32_t box[2] = {(cuuint32_t)boxc, (cuuint32_t)boxr}, es[2] = {1, 1};
    enc(m, CU_TENSOR_MAP_DATA_TYPE_BFLOAT16, 2, (void*)p, dim, str, box, es, CU_TENSOR_MAP_INTERLEAVE_NONE, sw,
        promo, CU_TENSOR_MAP_FLOAT_OOB_FILL_NONE);
}

extern "C" void kernel_launch(void* const* d_in, const int* in_sizes, int n_in, void* d_out, int out_size) {
    const bf16* x = (const bf16*)d_in[0];
    const bf16* mem0 = (const bf16*)d_in[1];
    const bf16 *Wq = (const bf16*)d_in[2], *Wk = (const bf16*)d_in[3], *Wv = (const bf16*)d_in[4], *Wo = (const bf16*)d_in[5];
    static EncodeFn enc = nullptr;
    static int nsm = 0;
    static void* kv[4];
    if (!enc) {
        enc = get_encode();
        cudaGetSymbolAddress(&kv[0], g_kx); cudaGetSymbolAddress(&kv[1], g_vx); cudaGetSymbolAddress(&kv[2], g_km); cudaGetSymbolAddress(&kv[3], g_vm);
        cudaDeviceGetAttribute(&nsm, cudaDevAttrMultiProcessorCount, 0);
        cudaFuncSetAttribute(chain_kernel, cudaFuncAttributeMaxDynamicSharedMemorySize, CH_SMEM);
        cudaFuncSetAttribute(worker_kernel, cudaFuncAttributeMaxDynamicSharedMemorySize, G_SMEM);
    }
    CUtensorMap mx, mq, mk, mv, mo, mout, mu, my;
    map_act(enc, &mx, x, S_LEN, DM, 128);
    map_w(enc, &mq, Wq, DM, HD); map_w(enc, &mk, Wk, DM, HD); map_w(enc, &mv, Wv, DM, HD); map_w(enc, &mo, Wo, HD, DM);
    map_box(enc, &mout, d_out, S_LEN, 2 * DM, 64, 16, CU_TENSOR_MAP_SWIZZLE_128B);
    map_box(enc, &mu, d_in[7], S_LEN, DM, 8, 256, CU_TENSOR_MAP_SWIZZLE_NONE, (CUtensorMapL2promotion)PROMU);
    map_box(enc, &my, d_out, S_LEN, 2 * DM, 8, 256, CU_TENSOR_MAP_SWIZZLE_NONE);
    CUtensorMap mkx, mvx, mkm, mvm;
    map_kv(enc, &mkx, kv[0], 256); map_kv(enc, &mvx, kv[1], 256); map_kv(enc, &mkm, kv[2], 64); map_kv(enc, &mvm, kv[3], 64);
    CUtensorMap cq, ck, cv, co;
    map_box(enc, &cq, Wq, DM, HD, 32, 32, CU_TENSOR_MAP_SWIZZLE_64B, (CUtensorMapL2promotion)PROMO); map_box(enc, &ck, Wk, DM, HD, 32, 32, CU_TENSOR_MAP_SWIZZLE_64B, (CUtensorMapL2promotion)PROMO);
    map_box(enc, &cv, Wv, DM, HD, 32, 32, CU_TENSOR_MAP_SWIZZLE_64B, (CUtensorMapL2promotion)PROMO); map_box(enc, &co, Wo, HD, DM, 32, 16, CU_TENSOR_MAP_SWIZZLE_64B, (CUtensorMapL2promotion)PROMO);
    S4Params P = {(const bf16*)d_in[8], (const bf16*)d_in[9], (const bf16*)d_in[10], (const bf16*)d_in[11],
                  (const bf16*)d_in[12], (const bf16*)d_in[13], (const bf16*)d_in[14], (const bf16*)d_in[15]};
    int aware = 1;
    cudaLaunchAttribute at[1];
    at[0].id = cudaLaunchAttributeProgrammaticStreamSerialization;
    at[0].val.programmaticStreamSerializationAllowed = 1;
    cudaLaunchConfig_t cfg = {};
    cfg.stream = cudaStreamPerThread;
    cfg.gridDim = dim3(96); cfg.blockDim = dim3(CH_THREADS); cfg.dynamicSmemBytes = CH_SMEM;
    cudaLaunchKernelEx(&cfg, chain_kernel, cq, ck, cv, co, Wq, Wk, Wv, mem0, P, aware);
    cfg.attrs = at; cfg.numAttrs = 1;
    cfg.gridDim = dim3(nsm); cfg.blockDim = dim3(384); cfg.dynamicSmemBytes = G_SMEM;
    cudaLaunchKernelEx(&cfg, worker_kernel, mx, mq, mk, mv, mo, mout, mu, my, mkx, mvx, mkm, mvm, P.dsk);
}
```

```cpp
#include <cuda.h>
#include <cuda_runtime.h>
#include <cuda_bf16.h>
#include <stdint.h>
#include <stdio.h>
#include <string.h>

typedef __nv_bfloat16 bf16;

constexpr int S_LEN = 2048, DM = 1024, NH = 32, DH = 128, HD = 4096, NSEG = 64;
constexpr uint32_t SENT = 0xFFFFFFFFu;
constexpr int SPIN_LIMIT = 1 << 18;
#define REALL 0

__device__ __align__(1024) bf16 g_kx[S_LEN * HD];
__device__ __align__(1024) bf16 g_vx[S_LEN * HD];
__device__ __align__(1024) bf16 g_ox[S_LEN * HD];
__device__ __align__(1024) bf16 g_km[NSEG * NH * 8 * DH];
__device__ __align__(1024) bf16 g_vm[NSEG * NH * 8 * DH];
__device__ __align__(1024) bf16 g_kd[DM * 768 + 8192];
__device__ __align__(1024) char g_ring[2 << 20];
__device__ int g_kvf[96 * 16];
constexpr int C_NEXT = 0, C_CHAIN = 32, C_QA_DONE = 64, N_CTR = 96;
__device__ int g_ctr[N_CTR];

__device__ __forceinline__ uint32_t smem_u32(const void* p) { return (uint32_t)__cvta_generic_to_shared(p); }
__device__ __forceinline__ uint32_t clk() { uint32_t c; asm volatile("mov.u32 %0, %%clock;" : "=r"(c)::"memory"); return c; }
__device__ __forceinline__ uint32_t pack_bf16(float lo, float hi) {
    uint32_t r; asm("cvt.rn.bf16x2.f32 %0, %1, %2;" : "=r"(r) : "f"(hi), "f"(lo)); return r;
}
__device__ __forceinline__ uint32_t movm(uint32_t a) {
    uint32_t d; asm volatile("movmatrix.sync.aligned.m8n8.trans.b16 %0, %1;" : "=r"(d) : "r"(a)); return d;
}
__device__ __forceinline__ void mma16(float (&d)[4], const uint32_t (&a)[4], uint32_t b0, uint32_t b1) {
    asm volatile("mma.sync.aligned.m16n8k16.row.col.f32.bf16.bf16.f32 {%0,%1,%2,%3}, {%4,%5,%6,%7}, {%8,%9}, {%0,%1,%2,%3};"
        : "+f"(d[0]), "+f"(d[1]), "+f"(d[2]), "+f"(d[3]) : "r"(a[0]), "r"(a[1]), "r"(a[2]), "r"(a[3]), "r"(b0), "r"(b1));
}
__device__ __forceinline__ void mma16z(float (&d)[4], const uint32_t (&a)[4], uint32_t b0, uint32_t b1) {
    asm volatile("mma.sync.aligned.m16n8k16.row.col.f32.bf16.bf16.f32 {%0,%1,%2,%3}, {%4,%5,%6,%7}, {%8,%9}, {%10,%10,%10,%10};"
        : "=f"(d[0]), "=f"(d[1]), "=f"(d[2]), "=f"(d[3]) : "r"(a[0]), "r"(a[1]), "r"(a[2]), "r"(a[3]), "r"(b0), "r"(b1), "f"(0.f));
}
__device__ __forceinline__ void mma8z(float (&d)[4], uint32_t a0, uint32_t a1, uint32_t b0) {
    asm volatile("mma.sync.aligned.m16n8k8.row.col.f32.bf16.bf16.f32 {%0,%1,%2,%3}, {%4,%5}, {%6}, {%7,%7,%7,%7};"
        : "=f"(d[0]), "=f"(d[1]), "=f"(d[2]), "=f"(d[3]) : "r"(a0), "r"(a1), "r"(b0), "f"(0.f));
}
__device__ __forceinline__ void ldsm4t(uint32_t (&r)[4], uint32_t addr) {
    asm volatile("ldmatrix.sync.aligned.m8n8.x4.trans.shared.b16 {%0,%1,%2,%3}, [%4];"
        : "=r"(r[0]), "=r"(r[1]), "=r"(r[2]), "=r"(r[3]) : "r"(addr) : "memory");
}
__device__ __forceinline__ void ldsm4(uint32_t (&r)[4], uint32_t addr) {
    asm volatile("ldmatrix.sync.aligned.m8n8.x4.shared.b16 {%0,%1,%2,%3}, [%4];"
        : "=r"(r[0]), "=r"(r[1]), "=r"(r[2]), "=r"(r[3]) : "r"(addr) : "memory");
}
__device__ __forceinline__ float lds32(uint32_t a) {
    float v; asm volatile("ld.shared.f32 %0, [%1];" : "=f"(v) : "r"(a) : "memory"); return v;
}
__device__ __forceinline__ void st_async1(uint32_t dst, float v, uint32_t bar) {
    asm volatile("st.async.shared::cluster.mbarrier::complete_tx::bytes.f32 [%0], %1, [%2];" ::"r"(dst), "f"(v), "r"(bar) : "memory");
}
__device__ __forceinline__ void st_async2(uint32_t dst, float x, float y, uint32_t bar) {
    asm volatile("st.async.shared::cluster.mbarrier::complete_tx::bytes.v2.f32 [%0], {%1,%2}, [%3];" ::"r"(dst), "f"(x), "f"(y), "r"(bar) : "memory");
}
__device__ __forceinline__ void mma8(float (&d)[4], uint32_t a0, uint32_t a1, uint32_t b0) {
    asm volatile("mma.sync.aligned.m16n8k8.row.col.f32.bf16.bf16.f32 {%0,%1,%2,%3}, {%4,%5}, {%6}, {%0,%1,%2,%3};"
        : "+f"(d[0]), "+f"(d[1]), "+f"(d[2]), "+f"(d[3]) : "r"(a0), "r"(a1), "r"(b0));
}
__device__ __forceinline__ void cp16(uint32_t dst, const void* src) {
    asm volatile("cp.async.cg.shared.global [%0], [%1], 16;" ::"r"(dst), "l"(src) : "memory");
}
__device__ __forceinline__ void sts128(uint32_t a, const float (&v)[4]) {
    asm volatile("st.shared.v4.f32 [%0], {%1,%2,%3,%4};" ::"r"(a), "f"(v[0]), "f"(v[1]), "f"(v[2]), "f"(v[3]) : "memory");
}
__device__ __forceinline__ float4 lds128(uint32_t a) {
    float4 v; asm volatile("ld.shared.v4.f32 {%0,%1,%2,%3}, [%4];" : "=f"(v.x), "=f"(v.y), "=f"(v.z), "=f"(v.w) : "r"(a) : "memory"); return v;
}
__device__ __forceinline__ void sts64(uint32_t a, float x, float y) {
    asm volatile("st.shared.v2.f32 [%0], {%1,%2};" ::"r"(a), "f"(x), "f"(y) : "memory");
}
__device__ __forceinline__ float2 lds64(uint32_t a) {
    float2 v; asm volatile("ld.shared.v2.f32 {%0,%1}, [%2];" : "=f"(v.x), "=f"(v.y) : "r"(a) : "memory"); return v;
}
__device__ __forceinline__ void bar_sync(int id, int n) { asm volatile("bar.sync %0, %1;" ::"r"(id), "r"(n) : "memory"); }
__device__ __forceinline__ void bar_arrive(int id, int n) { asm volatile("bar.arrive %0, %1;" ::"r"(id), "r"(n) : "memory"); }
__device__ __forceinline__ uint32_t mapa(uint32_t a, uint32_t r) {
    uint32_t o; asm("mapa.shared::cluster.u32 %0, %1, %2;" : "=r"(o) : "r"(a), "r"(r)); return o;
}
__device__ __forceinline__ void st_async4(uint32_t dst, float4 v, uint32_t bar) {
    asm volatile("st.async.shared::cluster.mbarrier::complete_tx::bytes.v4.f32 [%0], {%1,%2,%3,%4}, [%5];"
        ::"r"(dst), "f"(v.x), "f"(v.y), "f"(v.z), "f"(v.w), "r"(bar) : "memory");
}
__device__ __forceinline__ void mbar_init(uint32_t bar, int n) { asm volatile("mbarrier.init.shared.b64 [%0], %1;" ::"r"(bar), "r"(n) : "memory"); }
__device__ __forceinline__ void mbar_expect(uint32_t bar, int bytes) {
    asm volatile("mbarrier.arrive.expect_tx.shared.b64 _, [%0], %1;" ::"r"(bar), "r"(bytes) : "memory");
}
__device__ __forceinline__ void bulk_load(uint32_t dst, const void* src, int bytes, uint32_t bar) {
    asm volatile("cp.async.bulk.shared::cluster.global.mbarrier::complete_tx::bytes [%0], [%1], %2, [%3];"
        ::"r"(dst), "l"(src), "r"(bytes), "r"(bar) : "memory");
}
__device__ __forceinline__ bool mbar_try(uint32_t bar, uint32_t par) {
    uint32_t ok;
    asm volatile("{.reg .pred p; mbarrier.try_wait.parity.shared::cta.b64 p, [%1], %2; selp.u32 %0, 1, 0, p;}"
        : "=r"(ok) : "r"(bar), "r"(par) : "memory");
    return ok;
}
__device__ __forceinline__ bool mbar_test(uint32_t bar, uint32_t par) {
    uint32_t ok;
    asm volatile("{.reg .pred p; mbarrier.test_wait.parity.shared::cta.b64 p, [%1], %2; selp.u32 %0, 1, 0, p;}"
        : "=r"(ok) : "r"(bar), "r"(par) : "memory");
    return ok;
}
__device__ __forceinline__ int ld_acq(const int* p) { int v; asm volatile("ld.acquire.gpu.global.s32 %0, [%1];" : "=r"(v) : "l"(p) : "memory"); return v; }
__device__ __forceinline__ void red_release(int* p, int v) { asm volatile("red.release.gpu.global.add.s32 [%0], %1;" ::"l"(p), "r"(v) : "memory"); }
__device__ __forceinline__ void fence_gpu() { asm volatile("fence.acq_rel.gpu;" ::: "memory"); }
__device__ __forceinline__ void wait_ctr(const int* p, int n) {
    for (int it = 0; it < (1 << 20) && ld_acq(p) < n; it++) __nanosleep(64);
}
__device__ __forceinline__ void mbar_wait(uint32_t bar, uint32_t par) {
    if (!mbar_try(bar, par))
        for (int it = 0; it < SPIN_LIMIT && !mbar_try(bar, par); it++) {}
}
__device__ __forceinline__ void mbar_wait_long(uint32_t bar, uint32_t par) {
    for (int it = 0; it < (1 << 24) && !mbar_try(bar, par); it++) {}
}
__device__ __forceinline__ float4 add4(float4 a, float4 b) { return make_float4(a.x + b.x, a.y + b.y, a.z + b.z, a.w + b.w); }
__device__ __forceinline__ float ex2(float x) { float y; asm("ex2.approx.ftz.f32 %0, %1;" : "=f"(y) : "f"(x)); return y; }

__device__ __forceinline__ void wgmma256(float (&d)[128], uint64_t da, uint64_t db, int acc) {
    asm volatile("{.reg .pred p; setp.ne.b32 p, %130, 0;\n"
        "wgmma.mma_async.sync.aligned.m64n256k16.f32.bf16.bf16 {"
        "%0,%1,%2,%3,%4,%5,%6,%7,%8,%9,%10,%11,%12,%13,%14,%15,"
        "%16,%17,%18,%19,%20,%21,%22,%23,%24,%25,%26,%27,%28,%29,%30,%31,"
        "%32,%33,%34,%35,%36,%37,%38,%39,%40,%41,%42,%43,%44,%45,%46,%47,"
        "%48,%49,%50,%51,%52,%53,%54,%55,%56,%57,%58,%59,%60,%61,%62,%63,"
        "%64,%65,%66,%67,%68,%69,%70,%71,%72,%73,%74,%75,%76,%77,%78,%79,"
        "%80,%81,%82,%83,%84,%85,%86,%87,%88,%89,%90,%91,%92,%93,%94,%95,"
        "%96,%97,%98,%99,%100,%101,%102,%103,%104,%105,%106,%107,%108,%109,%110,%111,"
        "%112,%113,%114,%115,%116,%117,%118,%119,%120,%121,%122,%123,%124,%125,%126,%127"
        "}, %128, %129, p, 1, 1, 0, 1;}"
        : "+f"(d[0]), "+f"(d[1]), "+f"(d[2]), "+f"(d[3]), "+f"(d[4]), "+f"(d[5]), "+f"(d[6]), "+f"(d[7]), "+f"(d[8]), "+f"(d[9]), "+f"(d[10]), "+f"(d[11]), "+f"(d[12]), "+f"(d[13]), "+f"(d[14]), "+f"(d[15]), "+f"(d[16]), "+f"(d[17]), "+f"(d[18]), "+f"(d[19]), "+f"(d[20]), "+f"(d[21]), "+f"(d[22]), "+f"(d[23]), "+f"(d[24]), "+f"(d[25]), "+f"(d[26]), "+f"(d[27]), "+f"(d[28]), "+f"(d[29]), "+f"(d[30]), "+f"(d[31]), "+f"(d[32]), "+f"(d[33]), "+f"(d[34]), "+f"(d[35]), "+f"(d[36]), "+f"(d[37]), "+f"(d[38]), "+f"(d[39]), "+f"(d[40]), "+f"(d[41]), "+f"(d[42]), "+f"(d[43]), "+f"(d[44]), "+f"(d[45]), "+f"(d[46]), "+f"(d[47]), "+f"(d[48]), "+f"(d[49]), "+f"(d[50]), "+f"(d[51]), "+f"(d[52]), "+f"(d[53]), "+f"(d[54]), "+f"(d[55]), "+f"(d[56]), "+f"(d[57]), "+f"(d[58]), "+f"(d[59]), "+f"(d[60]), "+f"(d[61]), "+f"(d[62]), "+f"(d[63]), "+f"(d[64]), "+f"(d[65]), "+f"(d[66]), "+f"(d[67]), "+f"(d[68]), "+f"(d[69]), "+f"(d[70]), "+f"(d[71]), "+f"(d[72]), "+f"(d[73]), "+f"(d[74]), "+f"(d[75]), "+f"(d[76]), "+f"(d[77]), "+f"(d[78]), "+f"(d[79]), "+f"(d[80]), "+f"(d[81]), "+f"(d[82]), "+f"(d[83]), "+f"(d[84]), "+f"(d[85]), "+f"(d[86]), "+f"(d[87]), "+f"(d[88]), "+f"(d[89]), "+f"(d[90]), "+f"(d[91]), "+f"(d[92]), "+f"(d[93]), "+f"(d[94]), "+f"(d[95]), "+f"(d[96]), "+f"(d[97]), "+f"(d[98]), "+f"(d[99]), "+f"(d[100]), "+f"(d[101]), "+f"(d[102]), "+f"(d[103]), "+f"(d[104]), "+f"(d[105]), "+f"(d[106]), "+f"(d[107]), "+f"(d[108]), "+f"(d[109]), "+f"(d[110]), "+f"(d[111]), "+f"(d[112]), "+f"(d[113]), "+f"(d[114]), "+f"(d[115]), "+f"(d[116]), "+f"(d[117]), "+f"(d[118]), "+f"(d[119]), "+f"(d[120]), "+f"(d[121]), "+f"(d[122]), "+f"(d[123]), "+f"(d[124]), "+f"(d[125]), "+f"(d[126]), "+f"(d[127])
        : "l"(da), "l"(db), "r"(acc));
}
__device__ __forceinline__ void wgmma128(float (&d)[64], uint64_t da, uint64_t db, int acc) {
    asm volatile("{.reg .pred p; setp.ne.b32 p, %66, 0;\n"
        "wgmma.mma_async.sync.aligned.m64n128k16.f32.bf16.bf16 {"
        "%0,%1,%2,%3,%4,%5,%6,%7,%8,%9,%10,%11,%12,%13,%14,%15,"
        "%16,%17,%18,%19,%20,%21,%22,%23,%24,%25,%26,%27,%28,%29,%30,%31,"
        "%32,%33,%34,%35,%36,%37,%38,%39,%40,%41,%42,%43,%44,%45,%46,%47,"
        "%48,%49,%50,%51,%52,%53,%54,%55,%56,%57,%58,%59,%60,%61,%62,%63"
        "}, %64, %65, p, 1, 1, 0, 1;}"
        : "+f"(d[0]), "+f"(d[1]), "+f"(d[2]), "+f"(d[3]), "+f"(d[4]), "+f"(d[5]), "+f"(d[6]), "+f"(d[7]), "+f"(d[8]), "+f"(d[9]), "+f"(d[10]), "+f"(d[11]), "+f"(d[12]), "+f"(d[13]), "+f"(d[14]), "+f"(d[15]), "+f"(d[16]), "+f"(d[17]), "+f"(d[18]), "+f"(d[19]), "+f"(d[20]), "+f"(d[21]), "+f"(d[22]), "+f"(d[23]), "+f"(d[24]), "+f"(d[25]), "+f"(d[26]), "+f"(d[27]), "+f"(d[28]), "+f"(d[29]), "+f"(d[30]), "+f"(d[31]), "+f"(d[32]), "+f"(d[33]), "+f"(d[34]), "+f"(d[35]), "+f"(d[36]), "+f"(d[37]), "+f"(d[38]), "+f"(d[39]), "+f"(d[40]), "+f"(d[41]), "+f"(d[42]), "+f"(d[43]), "+f"(d[44]), "+f"(d[45]), "+f"(d[46]), "+f"(d[47]), "+f"(d[48]), "+f"(d[49]), "+f"(d[50]), "+f"(d[51]), "+f"(d[52]), "+f"(d[53]), "+f"(d[54]), "+f"(d[55]), "+f"(d[56]), "+f"(d[57]), "+f"(d[58]), "+f"(d[59]), "+f"(d[60]), "+f"(d[61]), "+f"(d[62]), "+f"(d[63])
        : "l"(da), "l"(db), "r"(acc));
}
__device__ __forceinline__ void wg_fence() { asm volatile("wgmma.fence.sync.aligned;" ::: "memory"); }
__device__ __forceinline__ void wg_commit() { asm volatile("wgmma.commit_group.sync.aligned;" ::: "memory"); }
template <int N> __device__ __forceinline__ void wg_wait() { asm volatile("wgmma.wait_group.sync.aligned %0;" ::"n"(N) : "memory"); }
__device__ __forceinline__ uint64_t mkdesc(uint32_t addr, uint32_t lbo, uint32_t sbo, uint32_t sw) {
    return (uint64_t)((addr & 0x3FFFF) >> 4) | ((uint64_t)(lbo >> 4) << 16) | ((uint64_t)(sbo >> 4) << 32) | ((uint64_t)sw << 62);
}
__device__ __forceinline__ void tma2d(uint32_t dst, const CUtensorMap* m, int c0, int c1, uint32_t bar) {
    asm volatile("cp.async.bulk.tensor.2d.shared::cluster.global.mbarrier::complete_tx::bytes [%0], [%1, {%2, %3}], [%4];"
        ::"r"(dst), "l"(m), "r"(c0), "r"(c1), "r"(bar) : "memory");
}
__device__ __forceinline__ void tma3d(uint32_t dst, const CUtensorMap* m, int c0, int c1, int c2, uint32_t bar) {
    asm volatile("cp.async.bulk.tensor.3d.shared::cluster.global.mbarrier::complete_tx::bytes [%0], [%1, {%2, %3, %4}], [%5];"
        ::"r"(dst), "l"(m), "r"(c0), "r"(c1), "r"(c2), "r"(bar) : "memory");
}
__device__ __forceinline__ void tma3d_mc(uint32_t dst, const CUtensorMap* m, int c0, int c1, int c2, uint32_t bar, uint16_t mask) {
    asm volatile("cp.async.bulk.tensor.3d.shared::cluster.global.mbarrier::complete_tx::bytes.multicast::cluster [%0], [%1, {%2, %3, %4}], [%5], %6;"
        ::"r"(dst), "l"(m), "r"(c0), "r"(c1), "r"(c2), "r"(bar), "h"(mask) : "memory");
}
__device__ __forceinline__ void mbar_arrive(uint32_t bar) { asm volatile("mbarrier.arrive.shared.b64 _, [%0];" ::"r"(bar) : "memory"); }
__device__ __forceinline__ void mbar_arrive_remote(uint32_t bar) {
    asm volatile("mbarrier.arrive.shared::cluster.b64 _, [%0];" ::"r"(bar) : "memory");
}
template <int R> __device__ __forceinline__ void reg_inc() { asm volatile("setmaxnreg.inc.sync.aligned.u32 %0;" ::"n"(R)); }
template <int R> __device__ __forceinline__ void reg_dec() { asm volatile("setmaxnreg.dec.sync.aligned.u32 %0;" ::"n"(R)); }

#define ST(id, w, i)
constexpr int CH_NRES = 50;
constexpr int CH_WREG = CH_NRES * 512;
constexpr int CH_PART = 8 * CH_WREG;
constexpr int CH_SX = CH_PART + 16384;
constexpr int CH_MX = CH_SX + 3 * 1280;
constexpr int CH_QK = CH_MX;
constexpr int CH_XS = CH_MX + 3 * 512;
constexpr int CH_BAR = CH_XS + 5632;
constexpr int CH_SMEM = CH_BAR + 192;
constexpr int CH_THREADS = 384;

__device__ __forceinline__ char* ring_base() { return (char*)(((uintptr_t)g_ring + (1 << 20) - 1) & ~(uintptr_t)((1 << 20) - 1)); }
__device__ __forceinline__ uint32_t ring_off(int chunk, int side) {
    uint32_t o = ((chunk & 1) << 13) | ((chunk >> 1) << 16);
    uint32_t par = ((o >> 13) ^ (o >> 16) ^ (o >> 17) ^ (o >> 19) ^ side) & 1;
    return o | (par << 12);
}
__device__ __forceinline__ uint2 ld_poll(const char* p) {
    unsigned long long v; asm volatile("ld.relaxed.gpu.global.b64 %0, [%1];" : "=l"(v) : "l"(p) : "memory");
    return make_uint2((uint32_t)v, (uint32_t)(v >> 32));
}
__device__ __forceinline__ void st_pub(char* p, uint32_t x, uint32_t y) {
    unsigned long long v = ((unsigned long long)y << 32) | x;
    asm volatile("st.relaxed.gpu.global.b64 [%0], %1;" ::"l"(p), "l"(v) : "memory");
}
template <int N>
__device__ __forceinline__ void poll_issue(uint2 (&b)[N], const char* p, bool lastvalid) {
#pragma unroll
    for (int i = 0; i < N; i++) {
        if (i < N - 1 || lastvalid) b[i] = ld_poll(p + i * 256);
        else b[i] = make_uint2(0, 0);
    }
}
template <int N>
__device__ __forceinline__ int poll_check(uint2 (&b)[N], const char* p, uint32_t z) {
    int it = 0;
    uint32_t mx = z;
#pragma unroll
    for (int i = 0; i < N; i++) mx = max(mx, b[i].x);
    if (__any_sync(0xffffffffu, mx == SENT)) {
        do {
#pragma unroll
            for (int i = 0; i < N; i++)
                if ((REALL && i < 10) || b[i].x == SENT) b[i] = ld_poll(p + i * 256);
            mx = b[0].x;
#pragma unroll
            for (int i = 1; i < N; i++) mx = max(mx, b[i].x);
            it++;
        } while (__any_sync(0xffffffffu, mx == SENT && it < SPIN_LIMIT));
    }
    return it;
}
template <int N>
__device__ __forceinline__ uint32_t delay(uint32_t a) {
    uint32_t z = 0;
#pragma unroll
    for (int i = 0; i < N; i++) asm volatile("ld.volatile.shared.u32 %0, [%1];" : "=r"(z) : "r"(a + z) : "memory");
    return z;
}

#define PFKV 0
#define LDW 0
#define PACE2 18
#define R1W 0
#define KGS 3
constexpr int KVN = 2;
#define FEN 1
#define XB 4
#define KEEP 100
#define PE 0
#define PROMO 2
#define PROMU 0
#define FNC 1
#define CL 8
#define PL 0
#define ML 4
#define MP 2
#define VCH_P 4
#define VCH_C 2
#define DLM 3
#define DLO 5
constexpr int OB = 0;
template <int PACE, int I0 = 0, int I1 = 12>
__device__ __forceinline__ void preload(uint32_t (&sw)[12][4], uint32_t a, uint32_t zero) {
    uint32_t z = 0;
#pragma unroll
    for (int i = I0; i < I1; i++) {
        if (PACE && i % (PACE ? PACE : 1) == 0) z = delay<1>(zero + z);
        ldsm4t(sw[i], a + z + i * 512);
    }
}
__device__ __forceinline__ void stsm4(uint32_t addr, uint32_t a, uint32_t b, uint32_t c, uint32_t d) {
    asm volatile("stmatrix.sync.aligned.m8n8.x4.shared.b16 [%0], {%1,%2,%3,%4};" ::"r"(addr), "r"(a), "r"(b), "r"(c), "r"(d) : "memory");
}
__device__ __forceinline__ void stsm4t(uint32_t addr, uint32_t a, uint32_t b, uint32_t c, uint32_t d) {
    asm volatile("stmatrix.sync.aligned.m8n8.x4.trans.shared.b16 [%0], {%1,%2,%3,%4};" ::"r"(addr), "r"(a), "r"(b), "r"(c), "r"(d) : "memory");
}
__device__ __forceinline__ void st_part(uint32_t addr, const float (&x)[4], const float (&y)[4]) {
    stsm4(addr, pack_bf16(x[0], x[1]), pack_bf16(x[2], x[3]), pack_bf16(y[0], y[1]), pack_bf16(y[2], y[3]));
}
template <bool TR>
__device__ __forceinline__ void red_part(uint32_t& lo, uint32_t& hi, uint32_t addr, uint32_t eye) {
    uint32_t a[4][4];
#pragma unroll
    for (int j = 0; j < 4; j++) { if (TR) ldsm4t(a[j], addr + j * 1024); else ldsm4(a[j], addr + j * 1024); }
    float r0[4], r1[4], r2[4], r3[4];
    mma16z(r0, a[0], eye, eye); mma16z(r1, a[1], eye, eye); mma16z(r2, a[2], eye, eye); mma16z(r3, a[3], eye, eye);
#pragma unroll
    for (int j = 0; j < 4; j++) r0[j] = ((r0[j] + r1[j]) + r2[j]) + r3[j];
    lo = pack_bf16(r0[0], r0[1]); hi = pack_bf16(r0[2], r0[3]);
}
__device__ __forceinline__ int o_chunk(int ks, int& pos) {
    const int cw = ks < 176 ? ks / 11 : 16 + (ks - 176) / 10;
    pos = ks - (cw < 16 ? 11 * cw : 176 + 10 * (cw - 16));
    return cw;
}

template <bool PV>
__device__ __forceinline__ void chain_loop(const uint32_t (&wa)[36][4], const uint32_t sb, const int w, const int lane0, const int rank,
                                           const int h, const int side) {
    const int rk1 = rank == 2 ? 0 : rank + 1, rk2 = rank == 0 ? 2 : rank - 1;
    const int nq = rank == 0 ? 6 : 5, u0 = rank == 0 ? 0 : 1 + 5 * rank, v0 = rank == 0 ? -6 : 3 * rank - 6;
    const uint32_t pt = CH_PART + (w >> 1) * 4096 + (w & 1) * 256;
    const uint32_t barS = sb + CH_BAR, barM = barS + 8, zero = barS + 24;
    char* const ring0 = ring_base();
    const uint32_t m_rd = ring_off(24 + w, side), o_rd = ring_off(rank * 8 + w, side);
    uint32_t pub;
    if (PV) { int pos, cw = o_chunk(h * 8 + v0 + w, pos); pub = (ring_off(cw, 0) & ~4096u) + pos * 256; }
    else pub = (ring_off(24 + (h >> 2), 0) & ~4096u) + ((2 * h + w) & 7) * 256;
    char* const kvo = (char*)(PV ? g_vm + 128 * (v0 + w) : g_km + 64 * (u0 + w)) + h * 2048;
    const bool mown = !PV && w == rank && rank < 2;
    uint32_t lo16 = lane0 * 16;
    uint32_t sw[12][4];
#pragma unroll
    for (int i = 0; i < 12; i++) ldsm4t(sw[i], sb + lo16 + w * CH_WREG + i * 512);

#pragma unroll 1
    for (int s = 0;; s++) {
        const bool last = s == NSEG - 1;
        const uint32_t slot = (s & 3) << 14;
        lo16 += delay<DLM>(zero);
        const uint32_t lane = lo16 >> 4, l16 = sb + lo16, wl = l16 + w * CH_WREG, pw = l16 + CH_PART + w * 512;
        const uint32_t xs = l16 + CH_XS + nq * 512 + (w - nq) * 1024;
        const uint32_t eye = ((lo16 >> 7) == (lane & 3)) ? ((lo16 & 64) ? 0x3F800000u : 0x3F80u) : 0u;
        uint2 b[8];
        const char* pm = ring0 + (m_rd + slot + (lo16 >> 1));
        poll_issue<8>(b, pm, true);
        preload<0, ML, 12>(sw, wl, zero);
        if (FNC & 1) bar_arrive(14, 256);
        poll_check<8>(b, pm, delay<FNC & 1>(zero));
        if ((OB || (XB & 1)) && !last) bar_arrive(8, 256 + OB);
        if (PV && !last && w == 7) bar_arrive(13, 64);
        {
            float acc[6][4];
#pragma unroll
            for (int kk = 0; kk < 8; kk++) {
                const int j = (2 * kk) % 12;
                if (kk == 0) { mma16z(acc[5], sw[0], b[0].x, b[0].y); mma16z(acc[4], sw[1], b[0].x, b[0].y); }
                else { mma16(acc[5], sw[j], b[kk].x, b[kk].y); mma16(acc[4], sw[j + 1], b[kk].x, b[kk].y); }
#pragma unroll
                for (int i = 0; i < 4; i++) {
                    if (kk == 0) mma16z(acc[i], wa[i * 8], b[0].x, b[0].y);
                    else mma16(acc[i], wa[i * 8 + kk], b[kk].x, b[kk].y);
                    if (i < 2) ldsm4t(sw[j + i], wl + (12 + 2 * kk + i) * 512);
                }
            }
            st_part(pw + 4 * 2048, acc[4], acc[5]);
            st_part(pw, acc[0], acc[1]);
            st_part(pw + 2 * 2048, acc[2], acc[3]);
        }
        uint32_t kv0, kv1;
        const uint32_t lp = l16 + (lane >> 4) * 256, pl = lp + pt;
        if (!PV) {
            bar_sync(1, last ? 256 : 256 + OB);
            red_part<true>(kv1, kv0, pl, eye);
            sts64(l16 + CH_QK + (w >> 1) * 512 + (w & 1) * 8, __uint_as_float(kv1), __uint_as_float(kv0));
            if (!last) bar_arrive(2, nq * 32 + 64 + OB);
        } else {
            bar_sync(1, last ? 256 : 256 + OB);
        }
        {
            float va[4][4];
            const float z = __uint_as_float(delay<1>(zero));
#pragma unroll
            for (int i = 0; i < 4; i++) va[i][0] = va[i][1] = va[i][2] = va[i][3] = z;
#pragma unroll
            for (int kk = 0; kk < 8; kk++) {
                const int c = (PV ? VCH_P : VCH_C) == 4 ? kk & 1 : 0;
                if (kk < 2) { mma16(va[c], wa[32 + 2 * kk], b[kk].x, b[kk].y); mma16(va[2 + c], wa[33 + 2 * kk], b[kk].x, b[kk].y); }
                else { mma16(va[c], sw[(2 * kk) % 12], b[kk].x, b[kk].y); mma16(va[2 + c], sw[(2 * kk + 1) % 12], b[kk].x, b[kk].y); }
            }
            if ((PV ? VCH_P : VCH_C) == 4) {
#pragma unroll
                for (int j = 0; j < 4; j++) { va[0][j] += va[1][j]; va[2][j] += va[3][j]; }
            }
            st_part(pw + 6 * 2048, va[0], va[2]);
        }
        if (PV) {
            uint32_t vt0[4], vt1[4];
            ldsm4t(vt0, xs); ldsm4t(vt1, xs + 512);
            if (w >= 6 && !last) {
                uint32_t kx[3][4];
#pragma unroll
                for (int j = 0; j < 3; j++)
                    ldsm4(kx[j], sb + CH_XS + j * 1024 + (j == 2 && nq == 5 ? 0 : ((lane >> 3) & 1) * 512) + (w - 6) * 256 + (lane >> 4) * 128 + (lane & 7) * 16);
                const uint32_t da = l16 + CH_SX + rank * 1280 + (w - 6) * 512, dc = sb + CH_SX + rank * 1280 + 1024 + lane * 8;
                bar_sync(2, nq * 32 + 64 + OB);
                uint32_t qk[3][4];
#pragma unroll
                for (int j = 0; j < 3; j++) {
                    const float4 v = lds128(l16 + CH_QK + j * 512);
                    qk[j][0] = __float_as_uint(v.x); qk[j][1] = __float_as_uint(v.y); qk[j][2] = __float_as_uint(v.z); qk[j][3] = __float_as_uint(v.w);
                }
                float s0[4], s1[4], s2[4], s3[4];
                mma16z(s0, qk[0], kx[0][0], kx[0][1]); mma16z(s1, qk[0], kx[0][2], kx[0][3]);
                mma16z(s2, qk[1], kx[1][0], kx[1][1]); mma16z(s3, qk[1], kx[1][2], kx[1][3]);
                if (nq == 5) qk[2][2] = qk[2][3] = 0;
                mma16(s0, qk[2], kx[2][0], kx[2][1]); mma16(s1, qk[2], kx[2][2], kx[2][3]);
                float m0[4], m1[4];
                mma16z(m0, qk[0], qk[0][1], qk[0][3]); mma16z(m1, qk[1], qk[1][1], qk[1][3]);
                mma16(m0, qk[2], qk[2][1], qk[2][3]);
                const float4 sv = make_float4(s0[0] + s2[0], s0[1] + s2[1], s1[0] + s3[0], s1[1] + s3[1]);
                st_async4(mapa(da, rk1), sv, mapa(barS, rk1));
                st_async4(mapa(da, rk2), sv, mapa(barS, rk2));
                {
                    const float c0 = m0[0] + m1[0], c1 = m0[1] + m1[1];
                    const int dr = w == 6 ? rk1 : rk2;
                    st_async2(mapa(dc, dr), c0, c1, mapa(barS, dr));
                    sts64(dc, c0, c1);
                }
                const float t4[4] = {sv.x, sv.y, sv.z, sv.w};
                sts128(da, t4);
            }
            bar_sync(3, last ? 256 : 256 + OB);
            if (!last && w == 7) bar_arrive(12, 64);
            red_part<false>(kv0, kv1, pl, eye);
            if (last) {
                uint32_t* d = (uint32_t*)(kvo + (uint32_t)(s * (NH * 2048) + lane * 4));
                d[0] = movm(kv0); d[32] = movm(kv1);
                break;
            }
            {
                const uint32_t sx = l16 + CH_SX, r0 = rank * 1280, r1 = rk1 * 1280, r2 = rk2 * 1280;
                float4 a0 = lds128(sx + r0), b0 = lds128(sx + 512 + r0);
                const float2 c0 = lds64(sx + 1024 + r0 - lane * 8);
                preload<0, 0, PE>(sw, wl + 28 * 512, zero);
                mbar_wait(barS, s & 1);
                const float4 a1 = lds128(sx + r1), a2 = lds128(sx + r2), b1 = lds128(sx + 512 + r1), b2 = lds128(sx + 512 + r2);
                const float2 c1 = lds64(sx + 1024 + r1 - lane * 8), c2 = lds64(sx + 1024 + r2 - lane * 8);
                a0 = add4(add4(a0, a1), a2); b0 = add4(add4(b0, b1), b2);
                float sc[10] = {a0.x, a0.y, a0.z, a0.w, b0.x, b0.y, b0.z, b0.w, c0.x + c1.x + c2.x, c0.y + c1.y + c2.y};
                float mx = fmaxf(fmaxf(fmaxf(sc[0], sc[1]), fmaxf(sc[2], sc[3])), fmaxf(fmaxf(sc[4], sc[5]), fmaxf(sc[6], sc[7])));
                mx = fmaxf(mx, fmaxf(sc[8], sc[9]));
                mx = fmaxf(fmaxf(mx, __shfl_xor_sync(0xffffffffu, mx, 1)),
                           fmaxf(__shfl_xor_sync(0xffffffffu, mx, 2), __shfl_xor_sync(0xffffffffu, mx, 3)));
                const float cs = 0.08838834764831845f * 1.4426950408889634f;
                const float mb = -mx * cs;
#pragma unroll
                for (int j = 0; j < 10; j++) sc[j] = ex2(fmaf(sc[j], cs, mb));
                uint32_t pf[5];
#pragma unroll
                for (int j = 0; j < 5; j++) pf[j] = pack_bf16(sc[2 * j], sc[2 * j + 1]);
                float o0[4], o1[4], o2[4], o3[4], o4[4], o5[4];
                const uint32_t p0[4] = {pf[0], 0, pf[1], 0}, p1[4] = {pf[2], 0, pf[3], 0};
                mma16z(o0, p0, vt0[0], vt0[1]); mma16z(o1, p0, vt1[0], vt1[1]);
                mma16z(o2, p1, vt0[2], vt0[3]); mma16z(o3, p1, vt1[2], vt1[3]);
                mma8z(o4, pf[4], 0, kv0); mma8z(o5, pf[4], 0, kv1);
                float sum = (((sc[0] + sc[1]) + (sc[2] + sc[3])) + ((sc[4] + sc[5]) + (sc[6] + sc[7]))) + (sc[8] + sc[9]);
                sum = (sum + __shfl_xor_sync(0xffffffffu, sum, 1)) + (__shfl_xor_sync(0xffffffffu, sum, 2) + __shfl_xor_sync(0xffffffffu, sum, 3));
                float inv; asm("rcp.approx.ftz.f32 %0, %1;" : "=f"(inv) : "f"(sum));
                const uint32_t ox = pack_bf16((o0[0] + o2[0] + o4[0]) * inv, (o0[1] + o2[1] + o4[1]) * inv);
                const uint32_t oy = pack_bf16((o1[0] + o3[0] + o5[0]) * inv, (o1[1] + o3[1] + o5[1]) * inv);
                char* const pp = ring0 + (pub + slot + (lo16 >> 1));
                st_pub(pp, ox, oy); st_pub(pp + 4096, ox, oy);
                if (OB || (XB & 4)) bar_arrive(10, (8 - nq) * 32 + OB);
                preload<0, PE, PL>(sw, wl + 28 * 512, zero);
            }
            kv0 = movm(kv0); kv1 = movm(kv1);
        } else {
            *(uint32_t*)(kvo + (uint32_t)(s * (NH * 2048) + lane * 4)) = kv0;
            bar_sync(3, last ? 256 : 256 + OB);
            if (last) break;
            preload<1, 0, CL>(sw, wl + 28 * 512, zero);
        }
        uint2 c[11];
        bar_sync(4, 256 + OB);
        const char* po = ring0 + (o_rd + slot + (lo16 >> 1) + delay<DLO>(zero));
        poll_issue<11>(c, po, rank < 2);
        preload<0, PV ? PL : CL, 12>(sw, wl + 28 * 512, zero);
        if (PV) { uint32_t* d = (uint32_t*)(kvo + (uint32_t)(s * (NH * 2048) + lane * 4)); d[0] = kv0; d[32] = kv1; }
        if (FNC & 2) bar_arrive(15, 256);
        poll_check<11>(c, po, delay<(FNC >> 1)>(zero));
        if (OB || (XB & 2)) bar_arrive(9, 256 + OB);
        {
            float acc[4][4];
#pragma unroll
            for (int f = 0; f < 22; f++) {
                const int kk = f >> 1, a = f & 3;
                if (f < 4) mma16z(acc[a], sw[f % 12], c[kk].x, c[kk].y);
                else mma16(acc[a], sw[f % 12], c[kk].x, c[kk].y);
                if (f + 12 < 22) ldsm4t(sw[f % 12], wl + (28 + f + 12) * 512);
            }
#pragma unroll
            for (int i = 0; i < 2; i++) {
#pragma unroll
                for (int j = 0; j < 4; j++) acc[i][j] += acc[i + 2][j];
                sts128(l16 + CH_PART + i * 4096 + w * 512, acc[i]);
            }
        }
        if (!PV && w < 2) {
            bar_sync(5, 288 + OB);
            float4 v[8];
#pragma unroll
            for (int i = 0; i < 8; i++) v[i] = lds128(l16 + CH_PART + w * 4096 + i * 512);
            float4 r = add4(add4(add4(v[0], v[1]), add4(v[2], v[3])), add4(add4(v[4], v[5]), add4(v[6], v[7])));
            if (!mown) st_async4(mapa(l16 + CH_MX + rank * 512, w), r, mapa(barM, w));
            bar_arrive(7, 256 + OB);
            if (mown) {
                mbar_wait(barM, s & 1);
                float4 x = lds128(l16 + CH_MX + (rank ^ 1) * 512), y = lds128(l16 + CH_MX + 2 * 512);
                r = add4(add4(x, r), y);
                const uint32_t mx = movm(pack_bf16(r.x, r.y)), my = movm(pack_bf16(r.z, r.w));
                const uint32_t ns = (slot + 0x4000) & 0xC000;
                char* const pp = ring0 + (pub + ns + (lo16 >> 1));
                st_pub(pp, mx, my); st_pub(pp + 4096, mx, my);
            }
            preload<0, 0, ML>(sw, wl, zero);
        } else {
            bar_arrive(5, 288 + OB);
            bar_sync(7, 256 + OB);
            preload<MP, 0, ML>(sw, wl, zero);
        }
        bar_sync(6, 320 + OB);
    }
    bar_arrive(6, 288);
}

__device__ __forceinline__ void chain_pace(const uint32_t sb, const int lane, const int rank, const int aware) {
    const uint32_t zero = sb + CH_BAR + 24;
    if (lane == 0) {
        char* ring = ring_base();
        uint32_t* p0 = (uint32_t*)(ring + ring_off(blockIdx.x & 15, 0) + 3072 + (blockIdx.x >> 4) * 128);
        uint32_t* p1 = (uint32_t*)(ring + ring_off(blockIdx.x & 15, 1) + 3072 + (blockIdx.x >> 4) * 128);
        *p0 = 0; *p1 = 0;
        int b0 = 1 << 30, b1 = 1 << 30; uint32_t v = 0;
        for (int r = 0; r < 4 || (r < 256 && !mbar_test(sb + CH_BAR + 16, 0)); r++) {
            uint32_t t0 = clk(); v = atomicExch(p0 + (v == 500), r); uint32_t t1 = v == 777 ? clk() + 1 : clk(); b0 = min(b0, (int)(t1 - t0));
            t0 = clk(); v = atomicExch(p1 + (v == 500), r); t1 = v == 777 ? clk() + 1 : clk(); b1 = min(b1, (int)(t1 - t0));
            asm volatile("st.volatile.shared.u32 [%0], %1;" ::"r"(zero + 4), "r"(aware ? (b1 < b0) ^ (aware - 1) : 0) : "memory");
        }
    }
    __syncwarp();
#pragma unroll 1
    for (int s = 1; s < NSEG; s++) {
        bar_sync(5, 288 + OB);
        bar_arrive(6, 320 + OB + (rank == 2 ? delay<PACE2>(zero) : 0));
    }
}
__device__ __forceinline__ char* reset_ptr(const int lane, const int rank, const int h) {
    const int nq = rank == 0 ? 6 : 5, v0 = rank == 0 ? -6 : 3 * rank - 6;
    int pos, cw = o_chunk(h * 8 + v0 + min(max(5 + (lane >> 3), nq), 7), pos);
    if (lane >= 24 && rank < 2) { cw = 24 + (h >> 2); pos = (2 * h + rank) & 7; }
    return ring_base() + ((ring_off(cw, 0) & ~4096u) + pos * 256 + (lane & 7) * 16);
}
__device__ __forceinline__ void chain_chores(const uint32_t sb, const int lane, const int rank, const int h, const bf16* __restrict__ mem0) {
    const int nq = rank == 0 ? 6 : 5, u0 = rank == 0 ? 0 : 1 + 5 * rank, v0 = rank == 0 ? -6 : 3 * rank - 6;
    const uint32_t barS = sb + CH_BAR, barM = barS + 8, barX = barS + 16;
    auto xload = [&](int s) {
        mbar_expect(barX, 8192 - nq * 512);
        bulk_load(sb + CH_XS, g_kx + (size_t)(s * NH + h) * 4096 + u0 * 256, nq * 512, barX);
        bulk_load(sb + CH_XS + nq * 512, g_vx + (size_t)(s * NH + h) * 4096 + (v0 + nq) * 512, (8 - nq) * 1024, barX);
    };
    char* const rb = reset_ptr(lane, rank, h);
    int* const kvf = g_kvf + blockIdx.x * 16;
    if (rank < 2) {
        const uint32_t* p = (const uint32_t*)(mem0 + (lane >> 2) * DM + 32 * h + 16 * rank + 2 * (lane & 3));
        char* d = ring_base() + ((ring_off(24 + (h >> 2), 0) & ~4096u) + ((2 * h + rank) & 7) * 256 + lane * 8);
        const uint32_t x = p[0] == SENT ? 0x7FFF7FFFu : p[0];
        st_pub(d, x, p[4]); st_pub(d + 4096, x, p[4]);
    }
    if (lane == 0) {
        if (!KVN) __nanosleep(18000);
        wait_ctr(kvf, KVN);
        asm volatile("fence.proxy.async.global;" ::: "memory");
        xload(0);
    }
#pragma unroll 1
    for (int s = 0; s < NSEG - 1; s++) {
        if (lane == 0) {
            mbar_expect(barS, 2 * 1280);
            if (rank < 2) mbar_expect(barM, 2 * 512);
        }
        bar_sync(13, 64);
#pragma unroll
        for (int i = 0; i < 4; i++)
            asm volatile("st.relaxed.gpu.global.v4.u32 [%0], {%1,%1,%1,%1};" ::"l"(rb + ((((s + 2) & 3) << 14) + (i >> 1) * 4096 + (i & 1) * 128)), "r"(SENT) : "memory");
        if (FEN || (s & 3) == 0) fence_gpu();
        if (lane == 0 && (s & 3) == 0 && s) atomicAdd(g_ctr + C_CHAIN + (s >> 2) - 1, 1);
        if (lane == 0 && (s & 3) == 3) { wait_ctr(kvf + (s >> 2) + 1, KVN); asm volatile("fence.proxy.async.global;" ::: "memory"); }
        __syncwarp();
        bar_sync(12, 64);
        if (lane == 0) xload(s + 1);
        mbar_wait(barX, (s + 1) & 1);
        bar_sync(6, 320 + OB);
    }
    bar_sync(6, 288);
    fence_gpu();
    if (lane == 0) atomicAdd(g_ctr + C_CHAIN + 15, 1);
}

struct S4Params { const bf16 *Are, *Aim, *Bre, *Bim, *Cre, *Cim, *ldt, *dsk; };
__device__ __forceinline__ float2 cmul(float2 a, float2 b) { return make_float2(a.x * b.x - a.y * b.y, a.x * b.y + a.y * b.x); }
__device__ __forceinline__ float2 csq(float2 a) { return make_float2(a.x * a.x - a.y * a.y, (a.x + a.x) * a.y); }
__device__ __forceinline__ float2 cexp_t(float lr, float turns) {
    float f = (turns - rintf(turns)) * 6.283185307179586f, e = ex2(lr);
    return make_float2(e * __cosf(f), e * __sinf(f));
}
__device__ __forceinline__ float bf_at(uint2 v, int i) {
    const uint32_t w = i < 2 ? v.x : v.y;
    return __uint_as_float((i & 1) ? w & 0xFFFF0000u : w << 16);
}
__device__ __forceinline__ void kg_step(uint32_t (&a)[4][4], uint32_t (&b)[5][2], uint32_t pa, uint32_t pe, float x0) {
#pragma unroll
    for (int i = 0; i < 2; i++) {
        const float4 p = lds128(pa + i * 64);
        const float2 e8 = lds64(pe + i * 32), c = make_float2(p.z, p.w);
        const float mag = ex2(p.x * x0), ph = p.y * x0;
        float2 e0 = make_float2(mag * __cosf(ph), mag * __sinf(ph)), e1 = cmul(e0, e8);
#pragma unroll
        for (int j = 0; j < 4; j++) {
            a[j][2 * i] = pack_bf16(e0.x, e0.y); a[j][2 * i + 1] = pack_bf16(e1.x, e1.y);
            e0 = csq(e0); e1 = csq(e1);
        }
        float2 m = cmul(c, e0);
        b[0][i] = pack_bf16(m.x, -m.y);
#pragma unroll
        for (int j = 0; j < 4; j++) {
            m = cmul(c, e1);
            b[j + 1][i] = pack_bf16(m.x, -m.y);
            if (j < 3) e1 = csq(e1);
        }
    }
}
__device__ __forceinline__ void kg_mma(float (&kd)[5][4], const uint32_t (&a)[4][4], const uint32_t (&b)[5][2]) {
    mma16(kd[0], a[0], b[0][0], b[0][1]);
#pragma unroll
    for (int j = 0; j < 4; j++) mma16(kd[j + 1], a[j], b[j + 1][0], b[j + 1][1]);
}
struct KgRaw { uint2 v[6]; float ldt; };
__device__ __forceinline__ void kg_load(KgRaw& r, const S4Params& P, int d, int lane) {
    const bf16* src[6] = {P.Are, P.Aim, P.Bre, P.Bim, P.Cre, P.Cim};
#pragma unroll
    for (int j = 0; j < 6; j++) r.v[j] = __ldg((const uint2*)(src[j] + d * 128) + lane);
    r.ldt = __bfloat162float(P.ldt[d]);
}
__device__ __forceinline__ float kg_params(const KgRaw& r, uint32_t stg, int lane) {
    const float dt = __bfloat162float(__float2bfloat16(expf(r.ldt)));
    float k2048 = 0.f;
#pragma unroll
    for (int i = 0; i < 4; i++) {
        const float br = dt * bf_at(r.v[2], i), bi = dt * bf_at(r.v[3], i), cr = bf_at(r.v[4], i), ci = bf_at(r.v[5], i);
        const float zr = dt * bf_at(r.v[0], i) * 1.4426950408889634f;
        float zt = dt * bf_at(r.v[1], i) * 0.15915494309189535f;
        zt -= rintf(zt);
        const float v[4] = {zr, zt * 6.283185307179586f, cr * br - ci * bi, cr * bi + ci * br};
        const float2 e8 = cexp_t(8.f * zr, 8.f * zt), el = cexp_t(2048.f * zr, 2048.f * zt);
        k2048 += v[2] * el.x - v[3] * el.y;
        sts128(stg + (i * 32 + lane) * 16, v);
        sts64(stg + 2048 + (i * 32 + lane) * 8, e8.x, e8.y);
    }
#pragma unroll
    for (int o = 16; o; o >>= 1) k2048 += __shfl_xor_sync(0xffffffffu, k2048, o);
    __syncwarp();
    return k2048;
}
__device__ __forceinline__ void kg_store(const float (&kd)[5][4], float k2048, uint32_t stg, int d, int lane) {
    __syncwarp();
    const uint32_t ta = stg + (lane & 7) * 32 + ((lane >> 3) & 1) * 16 + (lane >> 4) * 256;
    stsm4t(ta, pack_bf16(kd[0][0], kd[0][1]), pack_bf16(kd[0][2], kd[0][3]), pack_bf16(kd[1][0], kd[1][1]), pack_bf16(kd[1][2], kd[1][3]));
    stsm4t(ta + 512, pack_bf16(kd[2][0], kd[2][1]), pack_bf16(kd[2][2], kd[2][3]), pack_bf16(kd[3][0], kd[3][1]), pack_bf16(kd[3][2], kd[3][3]));
    stsm4t(ta + 1024, pack_bf16(kd[4][0], kd[4][1]), pack_bf16(kd[4][2], kd[4][3]), pack_bf16(k2048, 0.f), 0);
    __syncwarp();
#pragma unroll
    for (int j = 0; j < 3; j++) ((float4*)(g_kd + d * 768))[j * 32 + lane] = lds128(stg + j * 512 + lane * 16);
    __syncwarp();
}

__global__ void __cluster_dims__(3, 1, 1) __launch_bounds__(CH_THREADS, 1)
chain_kernel(const __grid_constant__ CUtensorMap mq, const __grid_constant__ CUtensorMap mk, const __grid_constant__ CUtensorMap mv,
             const __grid_constant__ CUtensorMap mo, const bf16* __restrict__ Wq, const bf16* __restrict__ Wk, const bf16* __restrict__ Wv,
             const bf16* __restrict__ mem0, const __grid_constant__ S4Params P, int aware) {
    extern __shared__ __align__(1024) unsigned char smem[];
    const uint32_t sb = smem_u32(smem);
    const int tid = threadIdx.x, lane = tid & 31;
    const int w = __shfl_sync(0xffffffffu, tid >> 5, 0);
    int rank; asm("mov.u32 %0, %%cluster_ctarank;" : "=r"(rank));
    const int h = blockIdx.x / 3;
    if (tid == 0) {
        mbar_init(sb + CH_BAR, 1); mbar_init(sb + CH_BAR + 8, 1); mbar_init(sb + CH_BAR + 16, 1);
        for (int i = 0; i < 16; i++) mbar_init(sb + CH_BAR + 64 + i * 8, 1);
        *(int*)(smem + CH_BAR + 24) = 0; *(int*)(smem + CH_BAR + 28) = 0; *(int*)(smem + CH_BAR + 32) = 0;
        asm volatile("fence.mbarrier_init.release.cluster;" ::: "memory");
    }
    if (w == 10 && PFKV) {
        const int e = lane * 96 + blockIdx.x;
        if (e < 2048) asm volatile("cp.async.bulk.prefetch.L2.global [%0], 8192;" ::"l"(((e & 1) ? Wv : Wk) + (size_t)(e >> 1) * HD) : "memory");
        if (PFKV > 1) __nanosleep(PFKV);
    }
    if (w == 9) {
        char* const rb = reset_ptr(lane, rank, h);
#pragma unroll
        for (int i = 0; i < 8; i++)
            asm volatile("st.relaxed.gpu.global.v4.u32 [%0], {%1,%1,%1,%1};" ::"l"(rb + (((i >> 2) << 14) + ((i >> 1) & 1) * 4096 + (i & 1) * 128)), "r"(SENT) : "memory");
        if (lane < 16) g_kvf[blockIdx.x * 16 + lane] = 0;
        if (blockIdx.x == 0)
            for (int k = lane; k < N_CTR; k += 32) g_ctr[k] = 0;
        fence_gpu();
        __syncwarp();
        asm volatile("griddepcontrol.launch_dependents;" ::: "memory");
    }
    __syncthreads();
    asm volatile("barrier.cluster.arrive.relaxed.aligned;" ::: "memory");

    if (w >= 8) {
        reg_dec<24>();
        asm volatile("barrier.cluster.wait.aligned;" ::: "memory");
        if (w == 8) chain_pace(sb, lane, rank, aware);
        else if (w == 9) {
            chain_chores(sb, lane, rank, h, mem0);
            asm volatile("st.volatile.shared.u32 [%0], %1;" ::"r"(sb + CH_BAR + 32), "r"(0x3F803F80) : "memory");
        } else if (w == 11 && KEEP) {
#pragma unroll 1
            for (int it = 0; it < (1 << 22); it++) {
                int d0, d1;
                const uint32_t x = delay<1>(sb + CH_BAR + 32);
                asm volatile("mma.sync.aligned.m8n8k16.row.col.s32.s8.s8.s32 {%0,%1}, {%2}, {%2}, {%3,%3};" : "=r"(d0), "=r"(d1) : "r"(x), "r"(0));
                if (d0 | d1) break;
                if ((XB & 8) && lane == 0) asm volatile("st.relaxed.gpu.global.u32 [%0], %1;" ::"l"(g_kd + DM * 768 + blockIdx.x * 64), "r"(it) : "memory");
                if ((XB & 16) && lane == 0) ld_acq((int*)(g_kd + DM * 768 + blockIdx.x * 64));
                __nanosleep(KEEP);
            }
        }
    } else {
        reg_inc<240>();
        const int nq = rank == 0 ? 6 : 5;
        const int u0 = rank == 0 ? 0 : 1 + 5 * rank;
        const int v0 = rank == 0 ? -6 : 3 * rank - 6;
        const int gw = rank * 8 + w;
        const int ks0 = gw < 16 ? 11 * gw : 176 + 10 * (gw - 16);
        const int nko = gw < 16 ? 11 : 10;
        const uint32_t wr = sb + w * CH_WREG, bar0 = sb + CH_BAR + 64 + w * 16, bar1 = bar0 + 8;
        uint32_t wa[36][4];
        const uint32_t vst = sb + CH_PART + w * 2048;
        const int cq = h * DH + 8 * u0, cv = h * DH + 16 * (v0 + 6);
        const int r8 = lane >> 2, p = lane & 3;
        const bf16* src = p >= 2 ? ((p & 1) ? Wk : Wq) + cq + 32 : rank == 0 ? ((p & 1) ? Wk : Wq) + cq + 40 : Wv + cv - 16 + 8 * p;
        src += (size_t)(128 * w + r8) * HD;
        auto cp_rows = [&](int kh) {
            cp16(wr + ((kh >> 1) * 2 + (p >> 1)) * 512 + ((kh & 1) * 2 + (p & 1)) * 128 + r8 * 16, src + (size_t)kh * 8 * HD);
        };
        {
            int d = blockIdx.x * 8 + w, t = 0;
            const int d1 = 768 + blockIdx.x * 3 + w, nt = (w < 3 && d1 < DM) ? 32 : 16;
            const uint32_t stg = wr + 4096;
            KgRaw raw, raw1;
            kg_load(raw, P, d, lane);
            kg_load(raw1, P, min(d1, DM - 1), lane);
            float kd[5][4], k2048;
#pragma unroll 1
            for (int i = -LDW; i < 9 || t < nt; i++) {
                if (i >= 0 && i < 9) {
                    const uint32_t bar = bar0 + (i & 1) * 8;
                    if (i >= 2) mbar_wait(bar, ((i >> 1) - 1) & 1);
                    if (lane == 0) {
                        mbar_expect(bar, 2048);
                        if (i < 8) tma2d(wr + 8192 + (i & 1) * 8192 + (i >> 1) * 2048, (i & 1) ? &mk : &mq, cq, 128 * w + 32 * (i >> 1), bar);
                        else tma2d(vst, &mv, cv, 128 * w, bar);
                    }
                    if (i < 8) cp_rows(i);
                }
#pragma unroll 1
                for (int e = min(t + KGS, nt); t < e; t++) {
                    if ((t & 15) == 0) {
                        k2048 = kg_params(raw, stg, lane);
#pragma unroll
                        for (int j = 0; j < 20; j++) kd[j >> 2][j & 3] = 0.f;
                    }
                    uint32_t ka[4][4], kb[5][2];
                    kg_step(ka, kb, stg + ((t & 15) * 8 + (lane & 3)) * 16, stg + 2048 + ((t & 15) * 8 + (lane & 3)) * 8, (float)(lane >> 2));
                    kg_mma(kd, ka, kb);
                    if ((t & 15) == 15) { kg_store(kd, k2048, stg, d, lane); raw = raw1; d = d1; }
                }
            }
        }
        const uint32_t lrow = ((lane >> 4) * 8 + (lane & 7)) * 64, lsw = (lane >> 1) & 3, lh = (lane >> 3) & 1;
        mbar_wait(bar1, 1); mbar_wait(bar0, 0);
#pragma unroll
        for (int i = 0; i < 32; i++) ldsm4t(wa[i], wr + 8192 + lh * 8192 + (i & 7) * 1024 + lrow + (((i >> 3) ^ lsw) << 4));
#pragma unroll
        for (int i = 0; i < 4; i++) ldsm4t(wa[32 + i], vst + (i >> 1) * 1024 + lrow + ((((i & 1) * 2 + lh) ^ lsw) << 4));
        asm volatile("fence.proxy.async.shared::cta;" ::"r"(wa[31][0]), "r"(wa[35][0]) : "memory");
        __syncwarp();
        if (w < R1W) {
            if (lane == 0) {
                mbar_expect(bar1, 6144 + nko * 1024);
                for (int i = 0; i < 3; i++) tma2d(wr + 8192 + i * 2048, &mv, cv, 128 * w + 32 + 32 * i, bar1);
                for (int i = 0; i < nko; i++) tma2d(wr + 14336 + i * 1024, &mo, 32 * h, 16 * (ks0 + i), bar1);
            }
#pragma unroll 1
            for (int i = 8; i < 16; i++) cp_rows(i);
        } else {
#pragma unroll 1
            for (int i = 9; i < 18; i++) {
                const uint32_t bar = bar0 + (i & 1) * 8;
                if (i >= 11) mbar_wait(bar, ((i >> 1) - 1) & 1);
                if (lane == 0) {
                    const int j = 2 * (i - 12), nb = min(2, nko - j);
                    mbar_expect(bar, i < 12 ? 2048 : nb * 1024);
                    if (i < 12) tma2d(wr + 8192 + (i - 9) * 2048, &mv, cv, 128 * w + 32 * (i - 8), bar);
                    else for (int e = 0; e < nb; e++) tma2d(wr + 14336 + (j + e) * 1024, &mo, 32 * h, 16 * (ks0 + j + e), bar);
                }
                if (i < 17) cp_rows(i - 1);
            }
        }
        mbar_wait(bar0, 0); mbar_wait(bar1, 0);
#pragma unroll 1
        for (int i0 = -1; i0 < 17; i0 += 6) {
            uint32_t x[6][2][4];
#pragma unroll
            for (int i = 0; i < 6; i++) {
                const uint32_t a = wr + 8192 + max(i0 + i, 0) * 1024 + lrow;
                ldsm4t(x[i][0], a + ((lh ^ lsw) << 4)); ldsm4t(x[i][1], a + (((2 + lh) ^ lsw) << 4));
            }
            if (i0 == 11 && nko == 10) {
#pragma unroll
                for (int j = 0; j < 8; j++) x[5][j >> 2][j & 3] = 0;
            }
            __syncwarp();
#pragma unroll
            for (int i = 0; i < 6; i++) {
                const uint32_t a = wr + 8192 + max(i0 + i, 0) * 1024 + lane * 16;
                stsm4t(a, x[i][0][0], x[i][0][1], x[i][0][2], x[i][0][3]); stsm4t(a + 512, x[i][1][0], x[i][1][1], x[i][1][2], x[i][1][3]);
            }
        }
        asm volatile("cp.async.wait_all;" ::: "memory");
        asm volatile("barrier.cluster.wait.aligned;" ::: "memory");
        bar_sync(1, 256);
        mbar_wait_long(sb + CH_BAR + 16, 0);
        const int side = __shfl_sync(0xffffffffu, *(volatile int*)(smem + CH_BAR + 28), 0);
        if (w >= nq) chain_loop<true>(wa, sb, w, lane, rank, h, side);
        else chain_loop<false>(wa, sb, w, lane, rank, h, side);
    }
}

constexpr int G_STAGE = 49152, G_NST = 4;
constexpr int G_STG = G_NST * G_STAGE;
constexpr int G_BAR = G_STG + 32768;
constexpr int G_SMEM = G_BAR + 256 + 1024;

#define WLOG(e)
constexpr int IT_QA = 0, IT_O = 1, IT_S4 = 2, IT_END = 3, IT_KV = 4;
#define O_WIDE 10
#define TMP 1
#define PING 1
#define S4REL 4
#define KVI 2
#define KVF 2
#define KVS 8
#define STM 0
__device__ __forceinline__ void st_out(uint32_t* p, uint32_t v) {
    if (STM == 0) *p = v;
    else if (STM == 1) __stcs(p, v);
    else asm volatile("st.global.L1::no_allocate.u32 [%0], %1;" ::"l"(p), "r"(v) : "memory");
}
#define Q_N1 1
#define Q_S1 16
__device__ __forceinline__ int queue_item(int q) {
    if (q < 512) return (IT_KV << 16) | ((q >> 5) << 8) | (q & 31);
    q -= 512;
    if (q < 256) return (IT_QA << 16) | ((q >> 4) << 8) | (q & 15);
    q -= 256;
    if (q < Q_N1 * 8) return (IT_O << 16) | ((O_WIDE + (q >> 3)) << 8) | (q & 7);
    q -= Q_N1 * 8;
    if (q < Q_S1) return (IT_S4 << 16) | q;
    q -= Q_S1;
    if (q < (16 - O_WIDE - Q_N1) * 8) return (IT_O << 16) | ((O_WIDE + Q_N1 + (q >> 3)) << 8) | (q & 7);
    q -= (16 - O_WIDE - Q_N1) * 8;
    if (q < 128 - Q_S1) return (IT_S4 << 16) | (Q_S1 + q);
    return IT_END << 16;
}
__device__ __forceinline__ void tma2d_store(const CUtensorMap* m, uint32_t src, int c0, int c1) {
    asm volatile("cp.async.bulk.tensor.2d.global.shared::cta.bulk_group [%0, {%2, %3}], [%1];" ::"l"(m), "r"(src), "r"(c0), "r"(c1) : "memory");
}

__device__ __forceinline__ void wgmma_s64(float (&d)[32], uint32_t a0, uint32_t a1, uint32_t a2, uint32_t a3, uint64_t db, int acc) {
    asm volatile("{.reg .pred p; setp.ne.b32 p, %37, 0;\n"
        "wgmma.mma_async.sync.aligned.m64n64k16.f32.bf16.bf16 {"
        "%0,%1,%2,%3,%4,%5,%6,%7,%8,%9,%10,%11,%12,%13,%14,%15,"
        "%16,%17,%18,%19,%20,%21,%22,%23,%24,%25,%26,%27,%28,%29,%30,%31"
        "}, {%32,%33,%34,%35}, %36, p, 1, 1, 0;}"
        : "+f"(d[0]), "+f"(d[1]), "+f"(d[2]), "+f"(d[3]), "+f"(d[4]), "+f"(d[5]), "+f"(d[6]), "+f"(d[7]), "+f"(d[8]), "+f"(d[9]), "+f"(d[10]), "+f"(d[11]), "+f"(d[12]), "+f"(d[13]), "+f"(d[14]), "+f"(d[15]), "+f"(d[16]), "+f"(d[17]), "+f"(d[18]), "+f"(d[19]), "+f"(d[20]), "+f"(d[21]), "+f"(d[22]), "+f"(d[23]), "+f"(d[24]), "+f"(d[25]), "+f"(d[26]), "+f"(d[27]), "+f"(d[28]), "+f"(d[29]), "+f"(d[30]), "+f"(d[31])
        : "r"(a0), "r"(a1), "r"(a2), "r"(a3), "l"(db), "r"(acc));
}
__device__ __forceinline__ void wgmma_s16(float (&d)[8], uint32_t a0, uint32_t a1, uint32_t a2, uint32_t a3, uint64_t db, int acc) {
    asm volatile("{.reg .pred p; setp.ne.b32 p, %13, 0;\n"
        "wgmma.mma_async.sync.aligned.m64n16k16.f32.bf16.bf16 {"
        "%0,%1,%2,%3,%4,%5,%6,%7"
        "}, {%8,%9,%10,%11}, %12, p, 1, 1, 0;}"
        : "+f"(d[0]), "+f"(d[1]), "+f"(d[2]), "+f"(d[3]), "+f"(d[4]), "+f"(d[5]), "+f"(d[6]), "+f"(d[7])
        : "r"(a0), "r"(a1), "r"(a2), "r"(a3), "l"(db), "r"(acc));
}
__device__ __forceinline__ void wgmma_v128(float (&d)[64], uint32_t a0, uint32_t a1, uint32_t a2, uint32_t a3, uint64_t db, int acc) {
    asm volatile("{.reg .pred p; setp.ne.b32 p, %69, 0;\n"
        "wgmma.mma_async.sync.aligned.m64n128k16.f32.bf16.bf16 {"
        "%0,%1,%2,%3,%4,%5,%6,%7,%8,%9,%10,%11,%12,%13,%14,%15,"
        "%16,%17,%18,%19,%20,%21,%22,%23,%24,%25,%26,%27,%28,%29,%30,%31,"
        "%32,%33,%34,%35,%36,%37,%38,%39,%40,%41,%42,%43,%44,%45,%46,%47,"
        "%48,%49,%50,%51,%52,%53,%54,%55,%56,%57,%58,%59,%60,%61,%62,%63"
        "}, {%64,%65,%66,%67}, %68, p, 1, 1, 1;}"
        : "+f"(d[0]), "+f"(d[1]), "+f"(d[2]), "+f"(d[3]), "+f"(d[4]), "+f"(d[5]), "+f"(d[6]), "+f"(d[7]), "+f"(d[8]), "+f"(d[9]), "+f"(d[10]), "+f"(d[11]), "+f"(d[12]), "+f"(d[13]), "+f"(d[14]), "+f"(d[15]), "+f"(d[16]), "+f"(d[17]), "+f"(d[18]), "+f"(d[19]), "+f"(d[20]), "+f"(d[21]), "+f"(d[22]), "+f"(d[23]), "+f"(d[24]), "+f"(d[25]), "+f"(d[26]), "+f"(d[27]), "+f"(d[28]), "+f"(d[29]), "+f"(d[30]), "+f"(d[31]), "+f"(d[32]), "+f"(d[33]), "+f"(d[34]), "+f"(d[35]), "+f"(d[36]), "+f"(d[37]), "+f"(d[38]), "+f"(d[39]), "+f"(d[40]), "+f"(d[41]), "+f"(d[42]), "+f"(d[43]), "+f"(d[44]), "+f"(d[45]), "+f"(d[46]), "+f"(d[47]), "+f"(d[48]), "+f"(d[49]), "+f"(d[50]), "+f"(d[51]), "+f"(d[52]), "+f"(d[53]), "+f"(d[54]), "+f"(d[55]), "+f"(d[56]), "+f"(d[57]), "+f"(d[58]), "+f"(d[59]), "+f"(d[60]), "+f"(d[61]), "+f"(d[62]), "+f"(d[63])
        : "r"(a0), "r"(a1), "r"(a2), "r"(a3), "l"(db), "r"(acc));
}

__device__ __forceinline__ void attn_scores(float (&sx)[32], float (&sm)[8], const uint32_t (&q)[32], uint32_t sk) {
    const uint64_t dx = mkdesc(sk, 1024, 128, 0), dm = mkdesc(sk + 16384, 256, 128, 0);
    wg_fence();
#pragma unroll
    for (int ks = 0; ks < 8; ks++) {
        wgmma_s64(sx, q[4 * ks], q[4 * ks + 1], q[4 * ks + 2], q[4 * ks + 3], dx + ks * 128, ks);
        wgmma_s16(sm, q[4 * ks], q[4 * ks + 1], q[4 * ks + 2], q[4 * ks + 3], dm + ks * 32, ks);
    }
    wg_commit();
}
template <bool HI>
__device__ __forceinline__ void attn_softmax(uint32_t (&p)[2][20], const float (&sx)[2][32], const float (&sm)[2][8], bool sb, int lane) {
    constexpr int NF = HI ? 2 : 0, NT = NF + 3;
    const int gt = (lane >> 2) - 2 * (lane & 3);
    const float cs = 0.08838834764831845f * 1.4426950408889634f;
    float s[2][NT][4], m[4], l[4];
#pragma unroll
    for (int h = 0; h < 2; h++) {
#pragma unroll
        for (int j = 0; j < NT; j++)
#pragma unroll
            for (int e = 0; e < 4; e++) s[h][j][e] = j == NT - 1 ? (sb ? sm[h][4 + e] : sm[h][e]) : (sb ? sx[h][16 + 4 * j + e] : sx[h][4 * j + e]);
        if (gt < 0) s[h][NF][0] = s[h][NF + 1][2] = -INFINITY;
        if (gt < 1) s[h][NF][1] = s[h][NF + 1][3] = -INFINITY;
        m[2 * h] = fmaxf(s[h][0][0], s[h][0][1]); m[2 * h + 1] = fmaxf(s[h][0][2], s[h][0][3]);
#pragma unroll
        for (int j = 1; j < NT; j++) {
            if (j != NF + 1) m[2 * h] = fmaxf(m[2 * h], fmaxf(s[h][j][0], s[h][j][1]));
            m[2 * h + 1] = fmaxf(m[2 * h + 1], fmaxf(s[h][j][2], s[h][j][3]));
        }
    }
#pragma unroll
    for (int r = 0; r < 4; r++) m[r] = fmaxf(m[r], __shfl_xor_sync(0xffffffffu, m[r], 1));
#pragma unroll
    for (int r = 0; r < 4; r++) m[r] = fmaxf(m[r], __shfl_xor_sync(0xffffffffu, m[r], 2)) * -cs;
#pragma unroll
    for (int r = 0; r < 4; r++) {
        l[r] = 0.f;
#pragma unroll
        for (int j = 0; j < NT; j++)
            if ((r & 1) || j != NF + 1) {
                float* v = &s[r >> 1][j][2 * (r & 1)];
                v[0] = ex2(fmaf(v[0], cs, m[r])); v[1] = ex2(fmaf(v[1], cs, m[r]));
                l[r] += v[0] + v[1];
            }
    }
#pragma unroll
    for (int r = 0; r < 4; r++) l[r] += __shfl_xor_sync(0xffffffffu, l[r], 1);
#pragma unroll
    for (int r = 0; r < 4; r++) { l[r] += __shfl_xor_sync(0xffffffffu, l[r], 2); asm("rcp.approx.ftz.f32 %0, %0;" : "+f"(l[r])); }
    const uint32_t ma = sb ? 0u : ~0u;
#pragma unroll
    for (int h = 0; h < 2; h++)
#pragma unroll
        for (int j = 0; j < 5; j++) {
            const bool on = j == 4 || j < NF + 2;
            const int k = j == 4 ? NT - 1 : on ? j : 0, ia = j < 4 ? 2 * j : 16, ib = j < 4 ? 8 + 2 * j : 18;
            const uint32_t x = on && j != NF + 1 ? pack_bf16(s[h][k][0] * l[2 * h], s[h][k][1] * l[2 * h]) : 0;
            const uint32_t y = on ? pack_bf16(s[h][k][2] * l[2 * h + 1], s[h][k][3] * l[2 * h + 1]) : 0;
            asm volatile("and.b32 %0, %4, %6; and.b32 %1, %5, %6; and.b32 %2, %4, %7; and.b32 %3, %5, %7;"
                : "=&r"(p[h][ia]), "=&r"(p[h][ia + 1]), "=&r"(p[h][ib]), "=&r"(p[h][ib + 1]) : "r"(x), "r"(y), "r"(ma), "r"(~ma));
        }
}
__device__ __forceinline__ void attn_pv(float (&o)[64], const uint32_t (&p)[20], uint32_t sv) {
    const uint64_t dx = mkdesc(sv, 128, 1024, 0), dm = mkdesc(sv + 16384, 128, 256, 0);
    wg_fence();
#pragma unroll
    for (int ks = 0; ks < 5; ks++) wgmma_v128(o, p[4 * ks], p[4 * ks + 1], p[4 * ks + 2], p[4 * ks + 3], ks < 4 ? dx + ks * 16 : dm, ks);
    wg_commit();
}
__device__ __forceinline__ void attn_stage(const float (&o)[64], uint32_t dst) {
#pragma unroll
    for (int u = 0; u < 16; u += 2)
        stsm4(dst + (u >> 3) * 8192 + (u & 7) * 128, pack_bf16(o[4 * u], o[4 * u + 1]), pack_bf16(o[4 * u + 2], o[4 * u + 3]),
              pack_bf16(o[4 * u + 4], o[4 * u + 5]), pack_bf16(o[4 * u + 6], o[4 * u + 7]));
}

template <int BN, int NKB, bool BLOCKED_A>
__device__ __forceinline__ void mainloop(float (&acc)[BN / 2], uint32_t sb, int wgi, uint32_t full, uint32_t empty, int& it, bool elect) {
#pragma unroll
    for (int j = 0; j < BN / 2; j++) acc[j] = 0.f;
#pragma unroll 1
    for (int k4 = 0; k4 < NKB; k4 += 4) {
#pragma unroll
        for (int st = 0; st < 4; st++, it++) {
            mbar_wait_long(full + 8 * st, (it >> 2) & 1);
            const uint64_t da = BLOCKED_A ? mkdesc(sb + st * G_STAGE + wgi * 8192, 128, 1024, 0) : mkdesc(sb + st * G_STAGE + wgi * 8192, 16, 1024, 1);
            const uint64_t db = mkdesc(sb + st * G_STAGE + 16384, 8192, 1024, 1);
            wg_fence();
#pragma unroll
            for (int k = 0; k < 4; k++) {
                if constexpr (BN == 256) wgmma256(acc, da + k * (BLOCKED_A ? 16 : 2), db + k * 128, 1);
                else wgmma128(acc, da + k * (BLOCKED_A ? 16 : 2), db + k * 128, 1);
            }
            wg_commit();
            if (k4 | st) {
                wg_wait<1>();
                if (elect) mbar_arrive(empty + 8 * ((st + 3) & 3));
            }
        }
    }
    wg_wait<0>();
    if (elect) mbar_arrive(empty + 8 * 3);
}

__device__ __forceinline__ uint32_t n6_a(int st) { return st < 4 ? st * G_STAGE : (2 * st - 8) * G_STAGE + 32768; }
__device__ __forceinline__ uint32_t n6_b(int st) { return st < 4 ? st * G_STAGE + 16384 : (2 * st - 7) * G_STAGE + 32768; }
__device__ __forceinline__ uint32_t n6_bar(int st) { return st < 4 ? 8 * st : 96 + 8 * st; }
__device__ __forceinline__ void mainloop6(float (&acc)[64], uint32_t sb, int wgi, uint32_t full, uint32_t empty, int& it, bool elect) {
#pragma unroll
    for (int j = 0; j < 64; j++) acc[j] = 0.f;
    int st = 0, prev = 0, r = 0;
#pragma unroll 1
    for (int kb = 0; kb < 64; kb++) {
        mbar_wait_long(full + n6_bar(st), ((st < 4 ? it >> 2 : 0) + r) & 1);
        const uint64_t da = mkdesc(sb + n6_a(st) + wgi * 8192, 128, 1024, 0), db = mkdesc(sb + n6_b(st), 8192, 1024, 1);
        wg_fence();
#pragma unroll
        for (int k = 0; k < 4; k++) wgmma128(acc, da + k * 16, db + k * 128, 1);
        wg_commit();
        if (kb) {
            wg_wait<1>();
            if (elect) mbar_arrive(empty + n6_bar(prev));
        }
        prev = st;
        if (++st == 6) { st = 0; r++; }
    }
    wg_wait<0>();
    if (elect) mbar_arrive(empty + 8 * 3);
    it += 44;
}

template <int BN>
__device__ __forceinline__ void o_item(uint32_t sb, int wgi, int wi, int lane, uint32_t full, uint32_t empty, int& it, const CUtensorMap* mout,
                                       int row0, int col0, uint32_t stgpar) {
    float acc[BN / 2];
    if constexpr (BN == 256) mainloop<BN, 64, true>(acc, sb, wgi, full, empty, it, lane == 0);
    else mainloop6(acc, sb, wgi, full, empty, it, lane == 0);
    ST((row0 >> 4) + (col0 / BN), wgi * 4 + wi, 10);
    mbar_wait(full + 104, stgpar);
    const uint32_t stg = sb + G_STG + (wgi * 4 + wi) * 4096;
    const int r = lane & 15, cu = lane >> 4;
#pragma unroll
    for (int hf = 0; hf < BN / 128; hf++) {
        if (lane == 0) asm volatile("cp.async.bulk.wait_group.read 0;" ::: "memory");
        __syncwarp();
#pragma unroll
        for (int j = 0; j < 8; j++) {
            const float* a = acc + hf * 64 + j * 8;
            stsm4(stg + (j >> 2) * 2048 + r * 128 + ((((j & 3) * 2 + cu) ^ (r & 7)) << 4),
                  pack_bf16(a[0], a[1]), pack_bf16(a[2], a[3]), pack_bf16(a[4], a[5]), pack_bf16(a[6], a[7]));
        }
        asm volatile("fence.proxy.async.shared::cta;" ::: "memory");
        __syncwarp();
        if (lane == 0) {
            tma2d_store(mout, stg, col0 + hf * 128, row0 + wgi * 64 + wi * 16);
            tma2d_store(mout, stg + 2048, col0 + hf * 128 + 64, row0 + wgi * 64 + wi * 16);
            asm volatile("cp.async.bulk.commit_group;" ::: "memory");
        }
    }
}

constexpr int S4_KD = 32768;
constexpr int S4_CH = 2 * G_STAGE;
constexpr int S4_HALF = 2304;
constexpr int S4_WD = 2 * S4_HALF;
constexpr int S4_T2 = S4_WD + 2304;
constexpr int S4_T3 = S4_T2 + 1024;
constexpr int S4_STRIDE = S4_T3 + 640 + 16;
__device__ __forceinline__ uint32_t addz(uint32_t x, uint32_t z) { uint32_t r; asm volatile("add.u32 %0, %1, %2;" : "=r"(r) : "r"(x), "r"(z)); return r; }
__device__ __forceinline__ uint32_t lds16(uint32_t a) { uint32_t v; asm volatile("ld.shared.u16 %0, [%1];" : "=r"(v) : "r"(a) : "memory"); return v; }
__device__ __forceinline__ uint32_t ldsu(uint32_t a) { return __float_as_uint(lds32(a)); }

template <int E0, int NE, int KP>
__device__ __forceinline__ void s4_windows(float (&acc)[8][2][4], uint32_t ut, uint32_t tw, int rho, int w, int lane, uint32_t z) {
    const int gt = (lane >> 2) - 2 * (lane & 3), p0 = rho == 16 ? -3 : -2, c = (lane >> 3) + p0;
    uint32_t band[2][4], ta[NE][4];
    {
        const uint64_t ones = ((uint64_t)((2u << 2 * w) - 1) << 32) >> (8 * p0 + 24 - gt + rho + w);
        uint32_t f[5];
#pragma unroll
        for (int m = 0; m < 5; m++) f[m] = ((((uint32_t)(ones >> (8 * m)) & 3) * 0x8001u) & 0x10001u) * 0x3F80u;
#pragma unroll
        for (int j = 0; j < 2; j++) { band[j][0] = f[2 * j + 1]; band[j][1] = addz(f[2 * j], z); band[j][2] = f[2 * j + 2]; band[j][3] = addz(f[2 * j + 1], z); }
    }
#pragma unroll
    for (int e = 0; e < NE; e++)
        asm volatile("ld.shared.u32 %0, [%4]; ld.shared.u32 %1, [%4+%5]; ld.volatile.shared.u32 %2, [%4+%6]; ld.volatile.shared.u32 %3, [%4];"
            : "=r"(ta[e][0]), "=r"(ta[e][1]), "=r"(ta[e][2]), "=r"(ta[e][3]) : "r"(tw + 16 * (E0 + e) * KP), "n"(8 * KP), "n"(-8 * KP) : "memory");
    const uint32_t ua = ut + (c & 1) * S4_HALF + (16 + (lane & 7) + (c >> 1)) * 16;
#pragma unroll
    for (int J = 0; J < 8 - E0; J++) {
        uint32_t u0[4], u1[4];
        ldsm4(u0, ua + J * 256); ldsm4(u1, ua + J * 256 + 128);
        float s0[4], s1[4];
        mma16z(s0, band[0], u0[0], u0[1]); mma16z(s1, band[0], u1[0], u1[1]);
        mma16(s0, band[1], u0[2], u0[3]); mma16(s1, band[1], u1[2], u1[3]);
        const uint32_t b00 = pack_bf16(s0[0], s0[1]), b01 = pack_bf16(s1[0], s1[1]), b10 = pack_bf16(s0[2], s0[3]), b11 = pack_bf16(s1[2], s1[3]);
#pragma unroll
        for (int e = 0; e < NE; e++)
            if (J + E0 + e < 8) { mma16(acc[J + E0 + e][0], ta[e], b00, b01); mma16(acc[J + E0 + e][1], ta[e], b10, b11); }
    }
}
template <int D0, int D1>
__device__ __forceinline__ void s4_dense(float (&acc)[8][2][4], uint32_t ua, const uint32_t (&b0)[4], const uint32_t (&b1)[4]) {
#pragma unroll
    for (int J = 0; J < 8 - D0; J++) {
        uint32_t a[4];
        ldsm4(a, ua + J * 256);
        mma16(acc[J + D0][0], a, b0[0], b0[1]); mma16(acc[J + D0][1], a, b0[2], b0[3]);
        if (J + D1 < 8) { mma16(acc[J + D1][0], a, b1[0], b1[1]); mma16(acc[J + D1][1], a, b1[2], b1[3]); }
    }
}
__device__ __forceinline__ void s4_words(uint32_t (&b)[4], uint32_t wd) {
    asm volatile("ld.shared.u32 %0, [%4]; ld.shared.u32 %1, [%4+-32]; ld.shared.u32 %2, [%4+32]; ld.volatile.shared.u32 %3, [%4];"
        : "=r"(b[0]), "=r"(b[1]), "=r"(b[2]), "=r"(b[3]) : "r"(wd) : "memory");
}

__device__ __forceinline__ void s4_item(uint32_t sb, int cw, int lane, int item, const bf16* __restrict__ dsk, uint32_t empty, const CUtensorMap* my, uint32_t stgpar) {
    const int gt = (lane >> 2) - 2 * (lane & 3);
    const uint32_t ch = sb + S4_CH + cw * S4_STRIDE, kd = sb + S4_KD + cw * 1536;
    const __nv_bfloat162 dk = __bfloat162bfloat162(dsk[item * 8 + cw]);
    ST(item, cw, 0);
    asm volatile("st.shared.v4.u32 [%0], {%1,%1,%1,%1};" ::"r"(ch + (lane >> 4) * S4_HALF + (lane & 15) * 16), "r"(0) : "memory");
    const uint32_t tch = sb + S4_CH + (lane & 7) * S4_STRIDE + ((lane >> 3) & 1) * S4_HALF + (16 + 16 * cw + (lane >> 4)) * 16;
#pragma unroll
    for (int i = 0; i < 8; i++) {
        uint32_t x[4];
        ldsm4t(x, sb + cw * 4096 + i * 512 + lane * 16);
        stsm4(tch + i * 32, x[0], x[1], x[2], x[3]);
    }
    const uint32_t k1024 = lds16(kd + 1024);
    {
        auto st4 = [](uint32_t a, uint32_t x, uint32_t y, uint32_t u, uint32_t v) {
            asm volatile("st.shared.v4.u32 [%0], {%1,%2,%3,%4};" ::"r"(a), "r"(x), "r"(y), "r"(u), "r"(v) : "memory");
        };
        const float4 p = lds128(kd + lane * 16);
        const uint32_t p0 = __float_as_uint(p.x), p1 = __float_as_uint(p.y), p2 = __float_as_uint(p.z), p3 = __float_as_uint(p.w);
        const uint32_t pm = lane ? ldsu(kd + lane * 16 - 4) : 0;
        const uint32_t wa = ch + S4_WD + 64 + lane * 32;
        st4(wa, __byte_perm(p0, pm, 0x7610), __byte_perm(p0, 0, 0x1032), __byte_perm(p1, p0, 0x7610), __byte_perm(p1, 0, 0x1032));
        st4(wa + 16, __byte_perm(p2, p1, 0x7610), __byte_perm(p2, 0, 0x1032), __byte_perm(p3, p2, 0x7610), __byte_perm(p3, 0, 0x1032));
        const float2 q = lds64(kd + 512 + lane * 8);
        const uint32_t q0 = __float_as_uint(q.x), q1 = __float_as_uint(q.y), q2 = ldsu(kd + 520 + lane * 8), k255 = ldsu(kd + 508);
        st4(wa + 1024, lane ? __byte_perm(q0, 0, 0x1010) : __byte_perm(q0, k255, 0x7610), __byte_perm(q0, 0, 0x1010), __byte_perm(q0, 0, 0x1032), __byte_perm(q1, q0, 0x7610));
        st4(wa + 1040, __byte_perm(q1, 0, 0x1010), __byte_perm(q1, 0, 0x1010), __byte_perm(q1, 0, 0x1032), __byte_perm(q2, q1, 0x7610));
        const uint32_t k512 = lane == 4 ? lds16(kd + 768) : 0;
        if (lane < 16) st4(ch + S4_WD + (lane < 4 ? 0 : 2048) + lane * 16, k512 * 0x10001u, k512 * 0x10001u, k512 * 0x10001u, k512 << 16);
        const float2 c = lds64(kd + 768 + lane * 8), d = lds64(kd + 760 + lane * 8);
        const uint32_t c0 = __float_as_uint(c.x), c1 = __float_as_uint(c.y), c2 = ldsu(kd + 776 + lane * 8);
        const uint32_t d0 = lane ? __float_as_uint(d.x) : 0, d1 = lane ? __float_as_uint(d.y) : 0, d2 = lane ? c0 : 0;
        st4(ch + S4_T2 + 256 + lane * 16, __byte_perm(c0, d0, 0x7632), __byte_perm(c1, d1, 0x5410), __byte_perm(c1, d1, 0x7632), __byte_perm(c2, d2, 0x5410));
        const uint32_t m = lane == 31 ? 0xFFFF0000u : 0;
        st4(ch + S4_T2 + (lane < 16 ? lane : lane == 31 ? 48 : lane + 33) * 16, c0 & m, (c1 << 16) & m, c1 & m, (c2 << 16) & m);
        const float2 e = lds64(kd + 1024 + lane * 8);
        const uint32_t e0 = __float_as_uint(e.x), e1 = __float_as_uint(e.y), e2 = ldsu(kd + 1032 + lane * 8), em = ldsu(kd + 1020 + lane * 8);
        st4(ch + S4_T3 + 128 + lane * 16, __byte_perm(e0, lane ? em : 0, 0x7632), __byte_perm(e1, lane ? e0 : 0, 0x5410), __byte_perm(e1, e0, 0x7632), __byte_perm(e2, e1, 0x5410));
        if (lane < 8) st4(ch + S4_T3 + lane * 16, 0, 0, 0, 0);
    }
    bar_sync(2, 256);
    ST(item, cw, 1);
    const uint32_t z = ldsu(ch);
    float acc[8][2][4];
#pragma unroll
    for (int j = 0; j < 16; j++) acc[j >> 1][j & 1][0] = acc[j >> 1][j & 1][1] = acc[j >> 1][j & 1][2] = acc[j >> 1][j & 1][3] = 0.f;
#pragma unroll 1
    for (int r = 1; r <= 4; r++) s4_windows<2, 3, 16>(acc, ch, ch + S4_T2 + (gt - 16) * 16 + 4 * r - 4, 4 * r, 2 - (r & 1), lane, z);
    ST(item, cw, 2);
#pragma unroll 1
    for (int r = 1; r <= 2; r++) s4_windows<4, 4, 8>(acc, ch, ch + S4_T3 + (gt - 48) * 8 + 4 * r - 4, 8 * r, 2 + r, lane, z);
    ST(item, cw, 3);
    const uint32_t ua = ch + (lane >> 4) * S4_HALF + (16 + (lane & 15)) * 16, wd = ch + S4_WD + 64 + gt * 4;
#pragma unroll 1
    for (int q = 0; q < 2; q++) {
        uint32_t b0[4], b1[4];
        s4_words(b0, wd + (q + 32) * 64);
#pragma unroll
        for (int j = 0; j < 4; j++) {
            const int x = 16 * q + gt + (j == 1 ? -8 : j == 2 ? 8 : 0) - 3;
            b1[j] = addz(((unsigned)x < 2u ? k1024 : 0u) | ((unsigned)(x - 1) < 2u ? k1024 << 16 : 0u), z);
        }
        s4_dense<2, 4>(acc, ua - q * 16, b0, b1);
    }
    {
        uint32_t b0[4], b1[4], c0[4], c1[4];
        s4_words(b0, wd); s4_words(b1, wd + 1024);
#pragma unroll 1
        for (int q = 0; q < 16; q += 2) {
            s4_words(c0, wd + q * 64 + 64); s4_words(c1, wd + q * 64 + 64 + 1024);
            s4_dense<0, 1>(acc, ua - q * 16, b0, b1);
            s4_words(b0, wd + q * 64 + 128); s4_words(b1, wd + q * 64 + 128 + 1024);
            s4_dense<0, 1>(acc, ua - q * 16 - 16, c0, c1);
            if (q == S4REL && lane == 0) { mbar_arrive(empty); mbar_arrive(empty + 8); }
        }
    }
    ST(item, cw, 4);
    mbar_wait(empty + 72, stgpar);
    if (lane == 0) asm volatile("cp.async.bulk.wait_group.read 0;" ::: "memory");
    __syncwarp();
#pragma unroll
    for (int I = 0; I < 8; I++) {
        uint32_t u[4];
        ldsm4(u, ua + I * 256);
#pragma unroll
        for (int j = 0; j < 4; j++) {
            const uint32_t y = pack_bf16(acc[I][j >> 1][2 * (j & 1)], acc[I][j >> 1][2 * (j & 1) + 1]);
            const __nv_bfloat162 r = __hadd2_rn(*(const __nv_bfloat162*)&y, __hmul2_rn(*(const __nv_bfloat162*)&u[j], dk));
            u[j] = *(const uint32_t*)&r;
        }
        stsm4(ua + I * 256, u[0], u[1], u[2], u[3]);
    }
    bar_sync(2, 256);
#pragma unroll
    for (int i = 0; i < 8; i++) {
        uint32_t y[4];
        ldsm4t(y, tch + i * 32);
        stsm4(sb + G_STG + cw * 4096 + i * 512 + lane * 16, y[0], y[1], y[2], y[3]);
    }
    asm volatile("fence.proxy.async.shared::cta;" ::: "memory");
    __syncwarp();
    if (lane == 0) {
        mbar_arrive(empty + 16); mbar_arrive(empty + 24);
        tma2d_store(my, sb + G_STG + cw * 4096, DM + item * 8, cw * 256);
        asm volatile("cp.async.bulk.commit_group;" ::: "memory");
    }
    ST(item, cw, 5);
}

__global__ void __launch_bounds__(384, 1)
worker_kernel(const __grid_constant__ CUtensorMap mx, const __grid_constant__ CUtensorMap mq, const __grid_constant__ CUtensorMap mk,
              const __grid_constant__ CUtensorMap mv, const __grid_constant__ CUtensorMap mo,
              const __grid_constant__ CUtensorMap mout, const __grid_constant__ CUtensorMap mu, const __grid_constant__ CUtensorMap my,
              const __grid_constant__ CUtensorMap mkx, const __grid_constant__ CUtensorMap mvx, const __grid_constant__ CUtensorMap mkm,
              const __grid_constant__ CUtensorMap mvm, const bf16* __restrict__ dsk) {
    extern __shared__ unsigned char smem_raw[];
    const uint32_t sb = (smem_u32(smem_raw) + 1023) & ~1023u;
    const uint32_t full = sb + G_BAR, empty = full + 32, ifull = full + 64, iempty = full + 80, islot = full + 96, stgbar = full + 104, sigbar = full + 112, sigslot = full + 120;
    const int tid = threadIdx.x, wg = tid >> 7, lane = tid & 31;
    if (TMP && tid >= 64 && tid < 76) {
        const CUtensorMap* maps[12] = {&mx, &mq, &mk, &mv, &mo, &mout, &mu, &my, &mkx, &mvx, &mkm, &mvm};
        const CUtensorMap* m = maps[0];
#pragma unroll
        for (int j = 1; j < 12; j++) if (tid - 64 == j) m = maps[j];
        asm volatile("prefetch.tensormap [%0];" ::"l"(m) : "memory");
    }
    int q0 = blockIdx.x;
    const int wide0 = q0 - ((int)gridDim.x - O_WIDE * 4);
    if (tid == 0) {
        if (q0 >= 32 && wide0 < 0) q0 = 32 + atomicAdd(g_ctr + C_NEXT, 1);
        for (int i = 0; i < 6; i++) { mbar_init(full + n6_bar(i), 1); mbar_init(empty + n6_bar(i), 8); }
        for (int i = 0; i < 2; i++) { mbar_init(ifull + 8 * i, 1); mbar_init(iempty + 8 * i, 8); }
        mbar_init(sigbar, 8); mbar_init(stgbar, 1);
        asm volatile("fence.proxy.async.shared::cta;" ::: "memory");
    }
    __syncthreads();
    if (wg == 0) {
        reg_dec<40>();
        if (tid >= 32 && tid < 64) {
            for (int n = 0;; n++) {
                mbar_wait_long(sigbar, n & 1);
                int item; asm volatile("ld.shared.u32 %0, [%1];" : "=r"(item) : "r"(sigslot + 4 * (n & 1)) : "memory");
                const int type = item >> 16, b = (item >> 8) & 255, i = item & 255;
                if (type == IT_END) break;
                if (type == IT_QA) {
                    if (lane == 0) {
                        for (int j = 0; j < 8; j++) {
                            const uint32_t src = sb + (j >= 4 ? G_STG + (j & 1) * 16384 : 3 * G_STAGE + (j & 1) * 20480) + ((j >> 1) & 1) * 8192;
                            asm volatile("cp.async.bulk.global.shared::cta.bulk_group [%0], [%1], 8192;"
                                ::"l"(g_ox + (size_t)(b * 64 + i * 4 + ((j >> 1) ^ 2)) * 8192 + (j & 1) * 4096), "r"(src) : "memory");
                            if ((j & 3) == 3) asm volatile("cp.async.bulk.commit_group;" ::: "memory");
                        }
                        asm volatile("cp.async.bulk.wait_group.read 1;" ::: "memory");
                        asm volatile("mbarrier.arrive.shared.b64 _, [%0], 8;" ::"r"(empty + 24) : "memory");
                        asm volatile("cp.async.bulk.wait_group 0;" ::: "memory");
                        mbar_arrive(stgbar);
                        asm volatile("fence.proxy.async.global;" ::: "memory");
                    }
                    __syncwarp();
                }
                if (type == IT_KV) { if (lane < 6) red_release(g_kvf + ((i & 15) * 6 + lane) * 16 + b, 1); }
                else if (lane == 0) red_release(g_ctr + C_QA_DONE + b, 1 << i);
            }
        } else if (tid < 32) {
            int it = 0;
            if (!KVN) asm volatile("griddepcontrol.wait;" ::: "memory");
            for (int n = 0;; n++) {
                int item = 0;
                if (lane == 0) {
                    if (n) q0 = 32 + atomicAdd(g_ctr + C_NEXT, 1);
                    item = n == 0 && wide0 >= 0 ? (IT_O << 16) | ((wide0 >> 2) << 8) | (wide0 & 3) : queue_item(q0);
                }
                item = __shfl_sync(0xffffffffu, item, 0);
                if (lane == 0) {
                    mbar_wait(iempty + 8 * (n & 1), ((n >> 1) & 1) ^ 1);
                    asm volatile("st.shared.u32 [%0], %1;" ::"r"(islot + 4 * (n & 1)), "r"(item) : "memory");
                    mbar_arrive(ifull + 8 * (n & 1));
                    const int type = item >> 16, b = (item >> 8) & 255, i = item & 255;
                    if (type == IT_QA || type == IT_KV) {
                        const CUtensorMap* mw = type == IT_QA ? &mq : i < 16 ? &mk : &mv;
                        bool ready = false;
                        for (int kb = 0; kb < 16; kb++, it++) {
                            const int st = it & 3;
                            mbar_wait(empty + 8 * st, ((it >> 2) & 1) ^ 1);
                            mbar_expect(full + 8 * st, G_STAGE);
                            const uint32_t a = sb + st * G_STAGE;
                            tma2d(a, &mx, kb * 64, b * 128, full + 8 * st);
                            tma3d(a + 16384, mw, 0, kb * 64, (i & 15) * 4, full + 8 * st);
                            tma3d(a + 32768, mw, 0, kb * 64, (i & 15) * 4 + 2, full + 8 * st);
                            if (type == IT_QA && kb == 3) ready = ld_acq(g_ctr + C_CHAIN + b) >= 96;
                            if (type == IT_QA && kb >= 3 && kb < 11) {
                                const size_t sh = (b * 4 + ((kb - 3) & 3)) * NH + i * 2;
                                asm volatile("cp.async.bulk.prefetch.L2.global [%0], 16384;" ::"l"((kb >= 7 ? g_vx : g_kx) + sh * 4096) : "memory");
                                if (ready) asm volatile("cp.async.bulk.prefetch.L2.global [%0], 4096;" ::"l"((kb >= 7 ? g_vm : g_km) + sh * 1024) : "memory");
                            }
                        }
                    }
                    if (type == IT_QA) {
                        wait_ctr(g_ctr + C_CHAIN + b, 96);
                        asm volatile("fence.proxy.async.global;" ::: "memory");
                        for (int st = 0; st < 4; st++, it++) {
                            mbar_wait(empty + 8 * st, ((it >> 2) & 1) ^ 1);
                            mbar_expect(full + 8 * st, 4 * 10240);
                            for (int g2 = 0; g2 < 2; g2++) {
                                tma3d(sb + st * G_STAGE + g2 * 20480, st < 2 ? &mkx : &mvx, 0, b * 4 + g2 * 2, (i * 2 + (st & 1)) * 16, full + 8 * st);
                                tma3d(sb + st * G_STAGE + g2 * 20480 + 16384, st < 2 ? &mkm : &mvm, 0, b * 4 + g2 * 2, (i * 2 + (st & 1)) * 16, full + 8 * st);
                            }
                        }
                    } else if (type == IT_O) {
                        const bool wide = b < O_WIDE;
                        int done = 0;
                        const int ns = wide ? 4 : 6;
                        for (int kb = 0, st = 0, r = 0; kb < 64; kb++) {
                            const uint32_t bo = n6_bar(st);
                            mbar_wait(empty + bo, (((st < 4 ? it >> 2 : 0) + r) & 1) ^ 1);
                            mbar_expect(full + bo, wide ? G_STAGE : 32768);
                            tma3d(sb + n6_b(st), &mo, 0, kb * 64, wide ? i * 4 : i * 2, full + bo);
                            if (wide) tma3d(sb + n6_b(st) + 16384, &mo, 0, kb * 64, i * 4 + 2, full + bo);
                            if (!(done >> (kb >> 2) & 1)) {
                                for (int sp = 0; sp < (1 << 20) && !((done = ld_acq(g_ctr + C_QA_DONE + b)) >> (kb >> 2) & 1); sp++) __nanosleep(64);
                                asm volatile("fence.proxy.async.global;" ::: "memory");
                            }
                            bulk_load(sb + n6_a(st), g_ox + (size_t)(b * 64 + kb) * 8192, 16384, full + bo);
                            if (++st == ns) { st = 0; r++; }
                        }
                        it += wide ? 64 : 44;
                    } else if (type == IT_S4) {
                        wait_ctr(g_ctr + C_CHAIN, 96);
                        asm volatile("fence.proxy.async.global;" ::: "memory");
                        mbar_wait(empty, ((it >> 2) & 1) ^ 1);
                        mbar_expect(full, 32768 + 12288);
                        bulk_load(sb + S4_KD, g_kd + i * 8 * 768, 12288, full);
                        for (int j = 0; j < 8; j++) tma2d(sb + j * 4096, &mu, i * 8, j * 256, full);
                        for (int st = 1; st < 4; st++) { mbar_wait(empty + 8 * st, ((it >> 2) & 1) ^ 1); mbar_arrive(full + 8 * st); }
                        it += 4;
                        mbar_wait_long(empty, ((it >> 2) & 1) ^ 1);
                    }
                }
                __syncwarp();
                if (item >> 16 == IT_END) break;
            }
            asm volatile("griddepcontrol.wait;" ::: "memory");
        }
    } else {
        reg_inc<232>();
        const int wu = __shfl_sync(0xffffffffu, tid >> 5, 0);
        const int wgi = (wu >> 2) - 1, wi = wu & 3;
        int it = 0, nqa = 0, nsig = 0, n = 0, item;
        auto next_item = [&]() {
            mbar_wait_long(ifull + 8 * (n & 1), (n >> 1) & 1);
            asm volatile("ld.shared.u32 %0, [%1];" : "=r"(item) : "r"(islot + 4 * (n & 1)) : "memory");
            __syncwarp();
            if (lane == 0) mbar_arrive(iempty + 8 * (n & 1));
        };
        auto signal = [&](int what) {
            if (tid == 128) asm volatile("st.shared.u32 [%0], %1;" ::"r"(sigslot + 4 * (nsig & 1)), "r"(what) : "memory");
            __syncwarp();
            if (lane == 0) mbar_arrive(sigbar);
            nsig++;
        };
        next_item();
        if (item >> 16 == IT_KV) {
            float acc[128];
            uint32_t pk[64];
            uint32_t* dst = nullptr;
            int prev = 0;
            do {
                WLOG(0);
#pragma unroll
                for (int kb = 0; kb < 16; kb++, it++) {
                    const int st = kb & 3;
                    mbar_wait(full + 8 * st, (it >> 2) & 1);
                    const uint64_t da = mkdesc(sb + st * G_STAGE + wgi * 8192, 16, 1024, 1);
                    const uint64_t db = mkdesc(sb + st * G_STAGE + 16384, 8192, 1024, 1);
                    wg_fence();
#pragma unroll
                    for (int k = 0; k < 4; k++) wgmma256(acc, da + k * 2, db + k * 128, kb | k);
                    wg_commit();
                    if (n <= KVI) {
                        if (kb < KVF && dst) {
#pragma unroll
                            for (int j = kb * (64 / KVF); j < (kb + 1) * (64 / KVF); j++) st_out(dst + (j >> 1) * 128 + (j & 1) * 32, pk[j]);
                            if (kb == KVF - 1) signal(prev);
                        }
                    } else if (kb < KVS) {
#pragma unroll
                        for (int j = kb * (64 / KVS); j < (kb + 1) * (64 / KVS); j++) st_out(dst + (j >> 1) * 128 + (j & 1) * 32, pk[j]);
                        if (kb == KVS - 1) signal(prev);
                    }
                    if (kb > 0) {
                        wg_wait<1>();
                        if (lane == 0) mbar_arrive(empty + 8 * ((kb - 1) & 3));
                    }
                }
                wg_wait<0>();
                if (lane == 0) mbar_arrive(empty + 8 * 3);
#pragma unroll
                for (int j = 0; j < 64; j++) pk[j] = pack_bf16(acc[2 * j], acc[2 * j + 1]);
                const int row = ((item >> 8) & 255) * 128 + wgi * 64 + wi * 16, nt = item & 255;
                dst = (uint32_t*)(nt < 16 ? g_kx : g_vx) + (size_t)((row >> 5) * 512 + (nt & 15) * 32) * 128 + (row & 31) * 4 + lane;
                prev = item;
                WLOG(1);
                n++;
                next_item();
            } while (item >> 16 == IT_KV);
            if (dst) {
#pragma unroll
                for (int j = 0; j < 64; j++) dst[(j >> 1) * 128 + (j & 1) * 32] = pk[j];
                signal(prev);
            }
        }
        for (;; n++, next_item()) {
            const int type = item >> 16, b = (item >> 8) & 255, i = item & 255;
            const int lane = (tid & 31) + (item >> 24), wgi = (wu >> 2) - 1 + __shfl_sync(0xffffffffu, item >> 24, 0), wi = wu & 3;
            WLOG(0);
            if (type == IT_QA) {
                float acc[128];
                ST(sid, cw, 0);
                ST(sid, cw, 1);
                mainloop<256, 16, false>(acc, sb, wgi, full, empty, it, lane == 0);
                ST(sid, cw, 2);
                uint32_t q0[32], q1[32];
#pragma unroll
                for (int j = 0; j < 32; j++) q0[j] = pack_bf16(acc[2 * j], acc[2 * j + 1]);
                const uint32_t par = (it >> 2) & 1, so = sb + wgi * 20480;
                float sx[2][32] = {}, sm[2][8] = {};
                uint32_t p[2][20];
                mbar_wait_long(full, par);
                ST(sid, cw, 3);
                if (PING && wgi == 0) bar_sync(5, 256);
                attn_scores(sx[0], sm[0], q0, so);
                ST(sid, cw, 7);
#pragma unroll
                for (int j = 0; j < 32; j++) asm volatile("cvt.rn.bf16x2.f32 %0, %1, %2;" : "=r"(q1[j]) : "f"(acc[65 + 2 * j]), "f"(acc[64 + 2 * j]));
                mbar_wait(full + 8, par);
                attn_scores(sx[1], sm[1], q1, so + G_STAGE);
                if (PING && wgi == 1) bar_arrive(5, 256);
                if (lane == 0) asm volatile("cp.async.bulk.wait_group.read 0;" ::: "memory");
                mbar_wait(stgbar, (nqa++ & 1) ^ 1);
                bar_sync(3 + wgi, 128);
                float o0[64] = {}, o1[64] = {};
                wg_wait<0>();
                ST(sid, cw, 9);
                if (lane == 0) { mbar_arrive(empty); mbar_arrive(empty + 8); }
                if (wi & 1) attn_softmax<true>(p, sx, sm, wi >= 2, lane);
                else attn_softmax<false>(p, sx, sm, wi >= 2, lane);
                ST(sid, cw, 10);
                mbar_wait(full + 16, par);
                attn_pv(o0, p[0], so + 2 * G_STAGE);
                mbar_wait(full + 24, par);
                attn_pv(o1, p[1], so + 3 * G_STAGE);
                wg_wait<1>();
                if (lane == 0) mbar_arrive(empty + 16);
                ST(sid, cw, 5);
                const uint32_t da = (wi * 2 + ((lane >> 3) & 1)) * 1024 + (lane >> 4) * 128 + (lane & 7) * 16;
                attn_stage(o0, sb + G_STG + wgi * 16384 + da);
                wg_wait<0>();
                bar_sync(3 + wgi, 128);
                attn_stage(o1, so + 3 * G_STAGE + da);
                asm volatile("fence.proxy.async.shared::cta;" ::: "memory");
                ST(sid, cw, 6);
                signal(item);
                it += 4;
            } else if (type == IT_O) {
                ST(b * 8 + i, wgi * 4 + wi, 8);
                mbar_wait_long(full, (it >> 2) & 1);
                ST(b * 8 + i, wgi * 4 + wi, 9);
                if (b < O_WIDE) o_item<256>(sb, wgi, wi, lane, full, empty, it, &mout, b * 128, i * 256, (nqa & 1) ^ 1);
                else o_item<128>(sb, wgi, wi, lane, full, empty, it, &mout, b * 128, i * 128, (nqa & 1) ^ 1);
            } else if (type == IT_S4) {
                mbar_wait_long(full, (it >> 2) & 1);
                mbar_wait(full + 24, (it >> 2) & 1);
                s4_item(sb, wgi * 4 + wi, lane, i, dsk, empty, &my, (nqa & 1) ^ 1);
                it += 4;
            } else break;
            WLOG(1);
        }
        bar_sync(2, 256);
        signal(item);
        if (lane == 0) asm volatile("cp.async.bulk.wait_group 0;" ::: "memory");
    }
}

typedef CUresult (*EncodeFn)(CUtensorMap*, CUtensorMapDataType, cuuint32_t, void*, const cuuint64_t*, const cuuint64_t*, const cuuint32_t*,
                             const cuuint32_t*, CUtensorMapInterleave, CUtensorMapSwizzle, CUtensorMapL2promotion, CUtensorMapFloatOOBfill);
static EncodeFn get_encode() {
    void* fn = nullptr; cudaDriverEntryPointQueryResult st;
    cudaGetDriverEntryPoint("cuTensorMapEncodeTiled", &fn, cudaEnableDefault, &st);
    return (EncodeFn)fn;
}
static void map_act(EncodeFn enc, CUtensorMap* m, const void* p, int rows, int cols, int boxr) {
    cuuint64_t dim[2] = {(cuuint64_t)cols, (cuuint64_t)rows}, str[1] = {(cuuint64_t)cols * 2};
    cuuint32_t box[2] = {64, (cuuint32_t)boxr}, es[2] = {1, 1};
    enc(m, CU_TENSOR_MAP_DATA_TYPE_BFLOAT16, 2, (void*)p, dim, str, box, es, CU_TENSOR_MAP_INTERLEAVE_NONE, CU_TENSOR_MAP_SWIZZLE_128B,
        CU_TENSOR_MAP_L2_PROMOTION_L2_128B, CU_TENSOR_MAP_FLOAT_OOB_FILL_NONE);
}
static void map_w(EncodeFn enc, CUtensorMap* m, const void* p, int k, int n) {
    cuuint64_t dim[3] = {64, (cuuint64_t)k, (cuuint64_t)n / 64}, str[2] = {(cuuint64_t)n * 2, 128};
    cuuint32_t box[3] = {64, 64, 2}, es[3] = {1, 1, 1};
    enc(m, CU_TENSOR_MAP_DATA_TYPE_BFLOAT16, 3, (void*)p, dim, str, box, es, CU_TENSOR_MAP_INTERLEAVE_NONE, CU_TENSOR_MAP_SWIZZLE_128B,
        CU_TENSOR_MAP_L2_PROMOTION_L2_256B, CU_TENSOR_MAP_FLOAT_OOB_FILL_NONE);
}

static void map_kv(EncodeFn enc, CUtensorMap* m, void* p, int n) {
    cuuint64_t dim[3] = {(cuuint64_t)n, NSEG, 512}, str[2] = {(cuuint64_t)n * 1024, (cuuint64_t)n * 2};
    cuuint32_t box[3] = {(cuuint32_t)n, 2, 16}, es[3] = {1, 1, 1};
    enc(m, CU_TENSOR_MAP_DATA_TYPE_BFLOAT16, 3, p, dim, str, box, es, CU_TENSOR_MAP_INTERLEAVE_NONE, CU_TENSOR_MAP_SWIZZLE_NONE,
        CU_TENSOR_MAP_L2_PROMOTION_NONE, CU_TENSOR_MAP_FLOAT_OOB_FILL_NONE);
}
static void map_box(EncodeFn enc, CUtensorMap* m, const void* p, int rows, int ld, int boxc, int boxr, CUtensorMapSwizzle sw,
                    CUtensorMapL2promotion promo = CU_TENSOR_MAP_L2_PROMOTION_NONE) {
    cuuint64_t dim[2] = {(cuuint64_t)ld, (cuuint64_t)rows}, str[1] = {(cuuint64_t)ld * 2};
    cuuint32_t box[2] = {(cuuint32_t)boxc, (cuuint32_t)boxr}, es[2] = {1, 1};
    enc(m, CU_TENSOR_MAP_DATA_TYPE_BFLOAT16, 2, (void*)p, dim, str, box, es, CU_TENSOR_MAP_INTERLEAVE_NONE, sw,
        promo, CU_TENSOR_MAP_FLOAT_OOB_FILL_NONE);
}

extern "C" void kernel_launch(void* const* d_in, const int* in_sizes, int n_in, void* d_out, int out_size) {
    const bf16* x = (const bf16*)d_in[0];
    const bf16* mem0 = (const bf16*)d_in[1];
    const bf16 *Wq = (const bf16*)d_in[2], *Wk = (const bf16*)d_in[3], *Wv = (const bf16*)d_in[4], *Wo = (const bf16*)d_in[5];
    static EncodeFn enc = nullptr;
    static int nsm = 0;
    static void* kv[4];
    if (!enc) {
        enc = get_encode();
        cudaGetSymbolAddress(&kv[0], g_kx); cudaGetSymbolAddress(&kv[1], g_vx); cudaGetSymbolAddress(&kv[2], g_km); cudaGetSymbolAddress(&kv[3], g_vm);
        cudaDeviceGetAttribute(&nsm, cudaDevAttrMultiProcessorCount, 0);
        cudaFuncSetAttribute(chain_kernel, cudaFuncAttributeMaxDynamicSharedMemorySize, CH_SMEM);
        cudaFuncSetAttribute(worker_kernel, cudaFuncAttributeMaxDynamicSharedMemorySize, G_SMEM);
    }
    CUtensorMap mx, mq, mk, mv, mo, mout, mu, my;
    map_act(enc, &mx, x, S_LEN, DM, 128);
    map_w(enc, &mq, Wq, DM, HD); map_w(enc, &mk, Wk, DM, HD); map_w(enc, &mv, Wv, DM, HD); map_w(enc, &mo, Wo, HD, DM);
    map_box(enc, &mout, d_out, S_LEN, 2 * DM, 64, 16, CU_TENSOR_MAP_SWIZZLE_128B);
    map_box(enc, &mu, d_in[7], S_LEN, DM, 8, 256, CU_TENSOR_MAP_SWIZZLE_NONE, (CUtensorMapL2promotion)PROMU);
    map_box(enc, &my, d_out, S_LEN, 2 * DM, 8, 256, CU_TENSOR_MAP_SWIZZLE_NONE);
    CUtensorMap mkx, mvx, mkm, mvm;
    map_kv(enc, &mkx, kv[0], 256); map_kv(enc, &mvx, kv[1], 256); map_kv(enc, &mkm, kv[2], 64); map_kv(enc, &mvm, kv[3], 64);
    CUtensorMap cq, ck, cv, co;
    map_box(enc, &cq, Wq, DM, HD, 32, 32, CU_TENSOR_MAP_SWIZZLE_64B, (CUtensorMapL2promotion)PROMO); map_box(enc, &ck, Wk, DM, HD, 32, 32, CU_TENSOR_MAP_SWIZZLE_64B, (CUtensorMapL2promotion)PROMO);
    map_box(enc, &cv, Wv, DM, HD, 32, 32, CU_TENSOR_MAP_SWIZZLE_64B, (CUtensorMapL2promotion)PROMO); map_box(enc, &co, Wo, HD, DM, 32, 16, CU_TENSOR_MAP_SWIZZLE_64B, (CUtensorMapL2promotion)PROMO);
    S4Params P = {(const bf16*)d_in[8], (const bf16*)d_in[9], (const bf16*)d_in[10], (const bf16*)d_in[11],
                  (const bf16*)d_in[12], (const bf16*)d_in[13], (const bf16*)d_in[14], (const bf16*)d_in[15]};
    int aware = 1;
    cudaLaunchAttribute at[1];
    at[0].id = cudaLaunchAttributeProgrammaticStreamSerialization;
    at[0].val.programmaticStreamSerializationAllowed = 1;
    cudaLaunchConfig_t cfg = {};
    cfg.stream = cudaStreamPerThread;
    cfg.gridDim = dim3(96); cfg.blockDim = dim3(CH_THREADS); cfg.dynamicSmemBytes = CH_SMEM;
    cudaLaunchKernelEx(&cfg, chain_kernel, cq, ck, cv, co, Wq, Wk, Wv, mem0, P, aware);
    cfg.attrs = at; cfg.numAttrs = 1;
    cfg.gridDim = dim3(nsm); cfg.blockDim = dim3(384); cfg.dynamicSmemBytes = G_SMEM;
    cudaLaunchKernelEx(&cfg, worker_kernel, mx, mq, mk, mv, mo, mout, mu, my, mkx, mvx, mkm, mvm, P.dsk);
}
```

```cpp
#include <cuda.h>
#include <cuda_runtime.h>
#include <cuda_bf16.h>
#include <stdint.h>
#include <stdio.h>
#include <string.h>

typedef __nv_bfloat16 bf16;

constexpr int S_LEN = 2048, DM = 1024, NH = 32, DH = 128, HD = 4096, NSEG = 64;
constexpr uint32_t SENT = 0xFFFFFFFFu;
constexpr int SPIN_LIMIT = 1 << 18;
#define REALL 0

__device__ __align__(1024) bf16 g_kx[S_LEN * HD];
__device__ __align__(1024) bf16 g_vx[S_LEN * HD];
__device__ __align__(1024) bf16 g_ox[S_LEN * HD];
__device__ __align__(1024) bf16 g_km[NSEG * NH * 8 * DH];
__device__ __align__(1024) bf16 g_vm[NSEG * NH * 8 * DH];
__device__ __align__(1024) bf16 g_kd[DM * 768 + 8192];
__device__ __align__(1024) char g_ring[2 << 20];
__device__ int g_kvf[96 * 16];
constexpr int C_NEXT = 0, C_CHAIN = 32, C_QA_DONE = 64, N_CTR = 96;
__device__ int g_ctr[N_CTR];

__device__ __forceinline__ uint32_t smem_u32(const void* p) { return (uint32_t)__cvta_generic_to_shared(p); }
__device__ __forceinline__ uint32_t clk() { uint32_t c; asm volatile("mov.u32 %0, %%clock;" : "=r"(c)::"memory"); return c; }
__device__ __forceinline__ uint32_t pack_bf16(float lo, float hi) {
    uint32_t r; asm("cvt.rn.bf16x2.f32 %0, %1, %2;" : "=r"(r) : "f"(hi), "f"(lo)); return r;
}
__device__ __forceinline__ uint32_t movm(uint32_t a) {
    uint32_t d; asm volatile("movmatrix.sync.aligned.m8n8.trans.b16 %0, %1;" : "=r"(d) : "r"(a)); return d;
}
__device__ __forceinline__ void mma16(float (&d)[4], const uint32_t (&a)[4], uint32_t b0, uint32_t b1) {
    asm volatile("mma.sync.aligned.m16n8k16.row.col.f32.bf16.bf16.f32 {%0,%1,%2,%3}, {%4,%5,%6,%7}, {%8,%9}, {%0,%1,%2,%3};"
        : "+f"(d[0]), "+f"(d[1]), "+f"(d[2]), "+f"(d[3]) : "r"(a[0]), "r"(a[1]), "r"(a[2]), "r"(a[3]), "r"(b0), "r"(b1));
}
__device__ __forceinline__ void mma16z(float (&d)[4], const uint32_t (&a)[4], uint32_t b0, uint32_t b1) {
    asm volatile("mma.sync.aligned.m16n8k16.row.col.f32.bf16.bf16.f32 {%0,%1,%2,%3}, {%4,%5,%6,%7}, {%8,%9}, {%10,%10,%10,%10};"
        : "=f"(d[0]), "=f"(d[1]), "=f"(d[2]), "=f"(d[3]) : "r"(a[0]), "r"(a[1]), "r"(a[2]), "r"(a[3]), "r"(b0), "r"(b1), "f"(0.f));
}
__device__ __forceinline__ void mma8z(float (&d)[4], uint32_t a0, uint32_t a1, uint32_t b0) {
    asm volatile("mma.sync.aligned.m16n8k8.row.col.f32.bf16.bf16.f32 {%0,%1,%2,%3}, {%4,%5}, {%6}, {%7,%7,%7,%7};"
        : "=f"(d[0]), "=f"(d[1]), "=f"(d[2]), "=f"(d[3]) : "r"(a0), "r"(a1), "r"(b0), "f"(0.f));
}
__device__ __forceinline__ void ldsm4t(uint32_t (&r)[4], uint32_t addr) {
    asm volatile("ldmatrix.sync.aligned.m8n8.x4.trans.shared.b16 {%0,%1,%2,%3}, [%4];"
        : "=r"(r[0]), "=r"(r[1]), "=r"(r[2]), "=r"(r[3]) : "r"(addr) : "memory");
}
__device__ __forceinline__ void ldsm4(uint32_t (&r)[4], uint32_t addr) {
    asm volatile("ldmatrix.sync.aligned.m8n8.x4.shared.b16 {%0,%1,%2,%3}, [%4];"
        : "=r"(r[0]), "=r"(r[1]), "=r"(r[2]), "=r"(r[3]) : "r"(addr) : "memory");
}
__device__ __forceinline__ float lds32(uint32_t a) {
    float v; asm volatile("ld.shared.f32 %0, [%1];" : "=f"(v) : "r"(a) : "memory"); return v;
}
__device__ __forceinline__ void st_async1(uint32_t dst, float v, uint32_t bar) {
    asm volatile("st.async.shared::cluster.mbarrier::complete_tx::bytes.f32 [%0], %1, [%2];" ::"r"(dst), "f"(v), "r"(bar) : "memory");
}
__device__ __forceinline__ void st_async2(uint32_t dst, float x, float y, uint32_t bar) {
    asm volatile("st.async.shared::cluster.mbarrier::complete_tx::bytes.v2.f32 [%0], {%1,%2}, [%3];" ::"r"(dst), "f"(x), "f"(y), "r"(bar) : "memory");
}
__device__ __forceinline__ void mma8(float (&d)[4], uint32_t a0, uint32_t a1, uint32_t b0) {
    asm volatile("mma.sync.aligned.m16n8k8.row.col.f32.bf16.bf16.f32 {%0,%1,%2,%3}, {%4,%5}, {%6}, {%0,%1,%2,%3};"
        : "+f"(d[0]), "+f"(d[1]), "+f"(d[2]), "+f"(d[3]) : "r"(a0), "r"(a1), "r"(b0));
}
__device__ __forceinline__ void cp16(uint32_t dst, const void* src) {
    asm volatile("cp.async.cg.shared.global [%0], [%1], 16;" ::"r"(dst), "l"(src) : "memory");
}
__device__ __forceinline__ void sts128(uint32_t a, const float (&v)[4]) {
    asm volatile("st.shared.v4.f32 [%0], {%1,%2,%3,%4};" ::"r"(a), "f"(v[0]), "f"(v[1]), "f"(v[2]), "f"(v[3]) : "memory");
}
__device__ __forceinline__ float4 lds128(uint32_t a) {
    float4 v; asm volatile("ld.shared.v4.f32 {%0,%1,%2,%3}, [%4];" : "=f"(v.x), "=f"(v.y), "=f"(v.z), "=f"(v.w) : "r"(a) : "memory"); return v;
}
__device__ __forceinline__ void sts64(uint32_t a, float x, float y) {
    asm volatile("st.shared.v2.f32 [%0], {%1,%2};" ::"r"(a), "f"(x), "f"(y) : "memory");
}
__device__ __forceinline__ float2 lds64(uint32_t a) {
    float2 v; asm volatile("ld.shared.v2.f32 {%0,%1}, [%2];" : "=f"(v.x), "=f"(v.y) : "r"(a) : "memory"); return v;
}
__device__ __forceinline__ void bar_sync(int id, int n) { asm volatile("bar.sync %0, %1;" ::"r"(id), "r"(n) : "memory"); }
__device__ __forceinline__ void bar_arrive(int id, int n) { asm volatile("bar.arrive %0, %1;" ::"r"(id), "r"(n) : "memory"); }
__device__ __forceinline__ uint32_t mapa(uint32_t a, uint32_t r) {
    uint32_t o; asm("mapa.shared::cluster.u32 %0, %1, %2;" : "=r"(o) : "r"(a), "r"(r)); return o;
}
__device__ __forceinline__ void st_async4(uint32_t dst, float4 v, uint32_t bar) {
    asm volatile("st.async.shared::cluster.mbarrier::complete_tx::bytes.v4.f32 [%0], {%1,%2,%3,%4}, [%5];"
        ::"r"(dst), "f"(v.x), "f"(v.y), "f"(v.z), "f"(v.w), "r"(bar) : "memory");
}
__device__ __forceinline__ void mbar_init(uint32_t bar, int n) { asm volatile("mbarrier.init.shared.b64 [%0], %1;" ::"r"(bar), "r"(n) : "memory"); }
__device__ __forceinline__ void mbar_expect(uint32_t bar, int bytes) {
    asm volatile("mbarrier.arrive.expect_tx.shared.b64 _, [%0], %1;" ::"r"(bar), "r"(bytes) : "memory");
}
__device__ __forceinline__ void bulk_load(uint32_t dst, const void* src, int bytes, uint32_t bar) {
    asm volatile("cp.async.bulk.shared::cluster.global.mbarrier::complete_tx::bytes [%0], [%1], %2, [%3];"
        ::"r"(dst), "l"(src), "r"(bytes), "r"(bar) : "memory");
}
__device__ __forceinline__ bool mbar_try(uint32_t bar, uint32_t par) {
    uint32_t ok;
    asm volatile("{.reg .pred p; mbarrier.try_wait.parity.shared::cta.b64 p, [%1], %2; selp.u32 %0, 1, 0, p;}"
        : "=r"(ok) : "r"(bar), "r"(par) : "memory");
    return ok;
}
__device__ __forceinline__ bool mbar_test(uint32_t bar, uint32_t par) {
    uint32_t ok;
    asm volatile("{.reg .pred p; mbarrier.test_wait.parity.shared::cta.b64 p, [%1], %2; selp.u32 %0, 1, 0, p;}"
        : "=r"(ok) : "r"(bar), "r"(par) : "memory");
    return ok;
}
__device__ __forceinline__ int ld_acq(const int* p) { int v; asm volatile("ld.acquire.gpu.global.s32 %0, [%1];" : "=r"(v) : "l"(p) : "memory"); return v; }
__device__ __forceinline__ void red_release(int* p, int v) { asm volatile("red.release.gpu.global.add.s32 [%0], %1;" ::"l"(p), "r"(v) : "memory"); }
__device__ __forceinline__ void fence_gpu() { asm volatile("fence.acq_rel.gpu;" ::: "memory"); }
__device__ __forceinline__ void wait_ctr(const int* p, int n) {
    for (int it = 0; it < (1 << 20) && ld_acq(p) < n; it++) __nanosleep(64);
}
__device__ __forceinline__ void mbar_wait(uint32_t bar, uint32_t par) {
    if (!mbar_try(bar, par))
        for (int it = 0; it < SPIN_LIMIT && !mbar_try(bar, par); it++) {}
}
__device__ __forceinline__ void mbar_wait_long(uint32_t bar, uint32_t par) {
    for (int it = 0; it < (1 << 24) && !mbar_try(bar, par); it++) {}
}
__device__ __forceinline__ float4 add4(float4 a, float4 b) { return make_float4(a.x + b.x, a.y + b.y, a.z + b.z, a.w + b.w); }
__device__ __forceinline__ float ex2(float x) { float y; asm("ex2.approx.ftz.f32 %0, %1;" : "=f"(y) : "f"(x)); return y; }

__device__ __forceinline__ void wgmma256(float (&d)[128], uint64_t da, uint64_t db, int acc) {
    asm volatile("{.reg .pred p; setp.ne.b32 p, %130, 0;\n"
        "wgmma.mma_async.sync.aligned.m64n256k16.f32.bf16.bf16 {"
        "%0,%1,%2,%3,%4,%5,%6,%7,%8,%9,%10,%11,%12,%13,%14,%15,"
        "%16,%17,%18,%19,%20,%21,%22,%23,%24,%25,%26,%27,%28,%29,%30,%31,"
        "%32,%33,%34,%35,%36,%37,%38,%39,%40,%41,%42,%43,%44,%45,%46,%47,"
        "%48,%49,%50,%51,%52,%53,%54,%55,%56,%57,%58,%59,%60,%61,%62,%63,"
        "%64,%65,%66,%67,%68,%69,%70,%71,%72,%73,%74,%75,%76,%77,%78,%79,"
        "%80,%81,%82,%83,%84,%85,%86,%87,%88,%89,%90,%91,%92,%93,%94,%95,"
        "%96,%97,%98,%99,%100,%101,%102,%103,%104,%105,%106,%107,%108,%109,%110,%111,"
        "%112,%113,%114,%115,%116,%117,%118,%119,%120,%121,%122,%123,%124,%125,%126,%127"
        "}, %128, %129, p, 1, 1, 0, 1;}"
        : "+f"(d[0]), "+f"(d[1]), "+f"(d[2]), "+f"(d[3]), "+f"(d[4]), "+f"(d[5]), "+f"(d[6]), "+f"(d[7]), "+f"(d[8]), "+f"(d[9]), "+f"(d[10]), "+f"(d[11]), "+f"(d[12]), "+f"(d[13]), "+f"(d[14]), "+f"(d[15]), "+f"(d[16]), "+f"(d[17]), "+f"(d[18]), "+f"(d[19]), "+f"(d[20]), "+f"(d[21]), "+f"(d[22]), "+f"(d[23]), "+f"(d[24]), "+f"(d[25]), "+f"(d[26]), "+f"(d[27]), "+f"(d[28]), "+f"(d[29]), "+f"(d[30]), "+f"(d[31]), "+f"(d[32]), "+f"(d[33]), "+f"(d[34]), "+f"(d[35]), "+f"(d[36]), "+f"(d[37]), "+f"(d[38]), "+f"(d[39]), "+f"(d[40]), "+f"(d[41]), "+f"(d[42]), "+f"(d[43]), "+f"(d[44]), "+f"(d[45]), "+f"(d[46]), "+f"(d[47]), "+f"(d[48]), "+f"(d[49]), "+f"(d[50]), "+f"(d[51]), "+f"(d[52]), "+f"(d[53]), "+f"(d[54]), "+f"(d[55]), "+f"(d[56]), "+f"(d[57]), "+f"(d[58]), "+f"(d[59]), "+f"(d[60]), "+f"(d[61]), "+f"(d[62]), "+f"(d[63]), "+f"(d[64]), "+f"(d[65]), "+f"(d[66]), "+f"(d[67]), "+f"(d[68]), "+f"(d[69]), "+f"(d[70]), "+f"(d[71]), "+f"(d[72]), "+f"(d[73]), "+f"(d[74]), "+f"(d[75]), "+f"(d[76]), "+f"(d[77]), "+f"(d[78]), "+f"(d[79]), "+f"(d[80]), "+f"(d[81]), "+f"(d[82]), "+f"(d[83]), "+f"(d[84]), "+f"(d[85]), "+f"(d[86]), "+f"(d[87]), "+f"(d[88]), "+f"(d[89]), "+f"(d[90]), "+f"(d[91]), "+f"(d[92]), "+f"(d[93]), "+f"(d[94]), "+f"(d[95]), "+f"(d[96]), "+f"(d[97]), "+f"(d[98]), "+f"(d[99]), "+f"(d[100]), "+f"(d[101]), "+f"(d[102]), "+f"(d[103]), "+f"(d[104]), "+f"(d[105]), "+f"(d[106]), "+f"(d[107]), "+f"(d[108]), "+f"(d[109]), "+f"(d[110]), "+f"(d[111]), "+f"(d[112]), "+f"(d[113]), "+f"(d[114]), "+f"(d[115]), "+f"(d[116]), "+f"(d[117]), "+f"(d[118]), "+f"(d[119]), "+f"(d[120]), "+f"(d[121]), "+f"(d[122]), "+f"(d[123]), "+f"(d[124]), "+f"(d[125]), "+f"(d[126]), "+f"(d[127])
        : "l"(da), "l"(db), "r"(acc));
}
__device__ __forceinline__ void wgmma128(float (&d)[64], uint64_t da, uint64_t db, int acc) {
    asm volatile("{.reg .pred p; setp.ne.b32 p, %66, 0;\n"
        "wgmma.mma_async.sync.aligned.m64n128k16.f32.bf16.bf16 {"
        "%0,%1,%2,%3,%4,%5,%6,%7,%8,%9,%10,%11,%12,%13,%14,%15,"
        "%16,%17,%18,%19,%20,%21,%22,%23,%24,%25,%26,%27,%28,%29,%30,%31,"
        "%32,%33,%34,%35,%36,%37,%38,%39,%40,%41,%42,%43,%44,%45,%46,%47,"
        "%48,%49,%50,%51,%52,%53,%54,%55,%56,%57,%58,%59,%60,%61,%62,%63"
        "}, %64, %65, p, 1, 1, 0, 1;}"
        : "+f"(d[0]), "+f"(d[1]), "+f"(d[2]), "+f"(d[3]), "+f"(d[4]), "+f"(d[5]), "+f"(d[6]), "+f"(d[7]), "+f"(d[8]), "+f"(d[9]), "+f"(d[10]), "+f"(d[11]), "+f"(d[12]), "+f"(d[13]), "+f"(d[14]), "+f"(d[15]), "+f"(d[16]), "+f"(d[17]), "+f"(d[18]), "+f"(d[19]), "+f"(d[20]), "+f"(d[21]), "+f"(d[22]), "+f"(d[23]), "+f"(d[24]), "+f"(d[25]), "+f"(d[26]), "+f"(d[27]), "+f"(d[28]), "+f"(d[29]), "+f"(d[30]), "+f"(d[31]), "+f"(d[32]), "+f"(d[33]), "+f"(d[34]), "+f"(d[35]), "+f"(d[36]), "+f"(d[37]), "+f"(d[38]), "+f"(d[39]), "+f"(d[40]), "+f"(d[41]), "+f"(d[42]), "+f"(d[43]), "+f"(d[44]), "+f"(d[45]), "+f"(d[46]), "+f"(d[47]), "+f"(d[48]), "+f"(d[49]), "+f"(d[50]), "+f"(d[51]), "+f"(d[52]), "+f"(d[53]), "+f"(d[54]), "+f"(d[55]), "+f"(d[56]), "+f"(d[57]), "+f"(d[58]), "+f"(d[59]), "+f"(d[60]), "+f"(d[61]), "+f"(d[62]), "+f"(d[63])
        : "l"(da), "l"(db), "r"(acc));
}
__device__ __forceinline__ void wg_fence() { asm volatile("wgmma.fence.sync.aligned;" ::: "memory"); }
__device__ __forceinline__ void wg_commit() { asm volatile("wgmma.commit_group.sync.aligned;" ::: "memory"); }
template <int N> __device__ __forceinline__ void wg_wait() { asm volatile("wgmma.wait_group.sync.aligned %0;" ::"n"(N) : "memory"); }
__device__ __forceinline__ uint64_t mkdesc(uint32_t addr, uint32_t lbo, uint32_t sbo, uint32_t sw) {
    return (uint64_t)((addr & 0x3FFFF) >> 4) | ((uint64_t)(lbo >> 4) << 16) | ((uint64_t)(sbo >> 4) << 32) | ((uint64_t)sw << 62);
}
__device__ __forceinline__ void tma2d(uint32_t dst, const CUtensorMap* m, int c0, int c1, uint32_t bar) {
    asm volatile("cp.async.bulk.tensor.2d.shared::cluster.global.mbarrier::complete_tx::bytes [%0], [%1, {%2, %3}], [%4];"
        ::"r"(dst), "l"(m), "r"(c0), "r"(c1), "r"(bar) : "memory");
}
__device__ __forceinline__ void tma3d(uint32_t dst, const CUtensorMap* m, int c0, int c1, int c2, uint32_t bar) {
    asm volatile("cp.async.bulk.tensor.3d.shared::cluster.global.mbarrier::complete_tx::bytes [%0], [%1, {%2, %3, %4}], [%5];"
        ::"r"(dst), "l"(m), "r"(c0), "r"(c1), "r"(c2), "r"(bar) : "memory");
}
__device__ __forceinline__ void tma3d_mc(uint32_t dst, const CUtensorMap* m, int c0, int c1, int c2, uint32_t bar, uint16_t mask) {
    asm volatile("cp.async.bulk.tensor.3d.shared::cluster.global.mbarrier::complete_tx::bytes.multicast::cluster [%0], [%1, {%2, %3, %4}], [%5], %6;"
        ::"r"(dst), "l"(m), "r"(c0), "r"(c1), "r"(c2), "r"(bar), "h"(mask) : "memory");
}
__device__ __forceinline__ void mbar_arrive(uint32_t bar) { asm volatile("mbarrier.arrive.shared.b64 _, [%0];" ::"r"(bar) : "memory"); }
__device__ __forceinline__ void mbar_arrive_remote(uint32_t bar) {
    asm volatile("mbarrier.arrive.shared::cluster.b64 _, [%0];" ::"r"(bar) : "memory");
}
template <int R> __device__ __forceinline__ void reg_inc() { asm volatile("setmaxnreg.inc.sync.aligned.u32 %0;" ::"n"(R)); }
template <int R> __device__ __forceinline__ void reg_dec() { asm volatile("setmaxnreg.dec.sync.aligned.u32 %0;" ::"n"(R)); }

#define ST(id, w, i)
constexpr int CH_NRES = 50;
constexpr int CH_WREG = CH_NRES * 512;
constexpr int CH_PART = 8 * CH_WREG;
constexpr int CH_SX = CH_PART + 16384;
constexpr int CH_MX = CH_SX + 3 * 1280;
constexpr int CH_QK = CH_MX;
constexpr int CH_XS = CH_MX + 3 * 512;
constexpr int CH_BAR = CH_XS + 5632;
constexpr int CH_SMEM = CH_BAR + 192;
constexpr int CH_THREADS = 384;

__device__ __forceinline__ char* ring_base() { return (char*)(((uintptr_t)g_ring + (1 << 20) - 1) & ~(uintptr_t)((1 << 20) - 1)); }
__device__ __forceinline__ uint32_t ring_off(int chunk, int side) {
    uint32_t o = ((chunk & 1) << 13) | ((chunk >> 1) << 16);
    uint32_t par = ((o >> 13) ^ (o >> 16) ^ (o >> 17) ^ (o >> 19) ^ side) & 1;
    return o | (par << 12);
}
__device__ __forceinline__ uint2 ld_poll(const char* p) {
    unsigned long long v; asm volatile("ld.relaxed.gpu.global.b64 %0, [%1];" : "=l"(v) : "l"(p) : "memory");
    return make_uint2((uint32_t)v, (uint32_t)(v >> 32));
}
__device__ __forceinline__ void st_pub(char* p, uint32_t x, uint32_t y) {
    unsigned long long v = ((unsigned long long)y << 32) | x;
    asm volatile("st.relaxed.gpu.global.b64 [%0], %1;" ::"l"(p), "l"(v) : "memory");
}
template <int N>
__device__ __forceinline__ void poll_issue(uint2 (&b)[N], const char* p, bool lastvalid) {
#pragma unroll
    for (int i = 0; i < N; i++) {
        if (i < N - 1 || lastvalid) b[i] = ld_poll(p + i * 256);
        else b[i] = make_uint2(0, 0);
    }
}
template <int N>
__device__ __forceinline__ int poll_check(uint2 (&b)[N], const char* p, uint32_t z) {
    int it = 0;
    uint32_t mx = z;
#pragma unroll
    for (int i = 0; i < N; i++) mx = max(mx, b[i].x);
    if (__any_sync(0xffffffffu, mx == SENT)) {
        do {
#pragma unroll
            for (int i = 0; i < N; i++)
                if ((REALL && i < 10) || b[i].x == SENT) b[i] = ld_poll(p + i * 256);
            mx = b[0].x;
#pragma unroll
            for (int i = 1; i < N; i++) mx = max(mx, b[i].x);
            it++;
        } while (__any_sync(0xffffffffu, mx == SENT && it < SPIN_LIMIT));
    }
    return it;
}
template <int N>
__device__ __forceinline__ uint32_t delay(uint32_t a) {
    uint32_t z = 0;
#pragma unroll
    for (int i = 0; i < N; i++) asm volatile("ld.volatile.shared.u32 %0, [%1];" : "=r"(z) : "r"(a + z) : "memory");
    return z;
}

#define PFKV 0
#define LDW 0
#define PACE2 18
#define R1W 0
#define KGS 3
constexpr int KVN = 2;
#define FEN 1
#define XB 4
#define KEEP 100
#define PE 0
#define PROMO 2
#define PROMU 0
#define FNC 1
#define CL 8
#define PL 0
#define ML 4
#define MP 2
#define VCH_P 4
#define VCH_C 2
#define DLM 3
#define DLO 5
constexpr int OB = 0;
template <int PACE, int I0 = 0, int I1 = 12>
__device__ __forceinline__ void preload(uint32_t (&sw)[12][4], uint32_t a, uint32_t zero) {
    uint32_t z = 0;
#pragma unroll
    for (int i = I0; i < I1; i++) {
        if (PACE && i % (PACE ? PACE : 1) == 0) z = delay<1>(zero + z);
        ldsm4t(sw[i], a + z + i * 512);
    }
}
__device__ __forceinline__ void stsm4(uint32_t addr, uint32_t a, uint32_t b, uint32_t c, uint32_t d) {
    asm volatile("stmatrix.sync.aligned.m8n8.x4.shared.b16 [%0], {%1,%2,%3,%4};" ::"r"(addr), "r"(a), "r"(b), "r"(c), "r"(d) : "memory");
}
__device__ __forceinline__ void stsm4t(uint32_t addr, uint32_t a, uint32_t b, uint32_t c, uint32_t d) {
    asm volatile("stmatrix.sync.aligned.m8n8.x4.trans.shared.b16 [%0], {%1,%2,%3,%4};" ::"r"(addr), "r"(a), "r"(b), "r"(c), "r"(d) : "memory");
}
__device__ __forceinline__ void st_part(uint32_t addr, const float (&x)[4], const float (&y)[4]) {
    stsm4(addr, pack_bf16(x[0], x[1]), pack_bf16(x[2], x[3]), pack_bf16(y[0], y[1]), pack_bf16(y[2], y[3]));
}
template <bool TR>
__device__ __forceinline__ void red_part(uint32_t& lo, uint32_t& hi, uint32_t addr, uint32_t eye) {
    uint32_t a[4][4];
#pragma unroll
    for (int j = 0; j < 4; j++) { if (TR) ldsm4t(a[j], addr + j * 1024); else ldsm4(a[j], addr + j * 1024); }
    float r0[4], r1[4], r2[4], r3[4];
    mma16z(r0, a[0], eye, eye); mma16z(r1, a[1], eye, eye); mma16z(r2, a[2], eye, eye); mma16z(r3, a[3], eye, eye);
#pragma unroll
    for (int j = 0; j < 4; j++) r0[j] = ((r0[j] + r1[j]) + r2[j]) + r3[j];
    lo = pack_bf16(r0[0], r0[1]); hi = pack_bf16(r0[2], r0[3]);
}
__device__ __forceinline__ int o_chunk(int ks, int& pos) {
    const int cw = ks < 176 ? ks / 11 : 16 + (ks - 176) / 10;
    pos = ks - (cw < 16 ? 11 * cw : 176 + 10 * (cw - 16));
    return cw;
}

template <bool PV>
__device__ __forceinline__ void chain_loop(const uint32_t (&wa)[36][4], const uint32_t sb, const int w, const int lane0, const int rank,
                                           const int h, const int side) {
    const int rk1 = rank == 2 ? 0 : rank + 1, rk2 = rank == 0 ? 2 : rank - 1;
    const int nq = rank == 0 ? 6 : 5, u0 = rank == 0 ? 0 : 1 + 5 * rank, v0 = rank == 0 ? -6 : 3 * rank - 6;
    const uint32_t pt = CH_PART + (w >> 1) * 4096 + (w & 1) * 256;
    const uint32_t barS = sb + CH_BAR, barM = barS + 8, zero = barS + 24;
    char* const ring0 = ring_base();
    const uint32_t m_rd = ring_off(24 + w, side), o_rd = ring_off(rank * 8 + w, side);
    uint32_t pub;
    if (PV) { int pos, cw = o_chunk(h * 8 + v0 + w, pos); pub = (ring_off(cw, 0) & ~4096u) + pos * 256; }
    else pub = (ring_off(24 + (h >> 2), 0) & ~4096u) + ((2 * h + w) & 7) * 256;
    char* const kvo = (char*)(PV ? g_vm + 128 * (v0 + w) : g_km + 64 * (u0 + w)) + h * 2048;
    const bool mown = !PV && w == rank && rank < 2;
    uint32_t lo16 = lane0 * 16;
    uint32_t sw[12][4];
#pragma unroll
    for (int i = 0; i < 12; i++) ldsm4t(sw[i], sb + lo16 + w * CH_WREG + i * 512);

#pragma unroll 1
    for (int s = 0;; s++) {
        const bool last = s == NSEG - 1;
        const uint32_t slot = (s & 3) << 14;
        lo16 += delay<DLM>(zero);
        const uint32_t lane = lo16 >> 4, l16 = sb + lo16, wl = l16 + w * CH_WREG, pw = l16 + CH_PART + w * 512;
        const uint32_t xs = l16 + CH_XS + nq * 512 + (w - nq) * 1024;
        const uint32_t eye = ((lo16 >> 7) == (lane & 3)) ? ((lo16 & 64) ? 0x3F800000u : 0x3F80u) : 0u;
        uint2 b[8];
        const char* pm = ring0 + (m_rd + slot + (lo16 >> 1));
        poll_issue<8>(b, pm, true);
        preload<0, ML, 12>(sw, wl, zero);
        if (FNC & 1) bar_arrive(14, 256);
        poll_check<8>(b, pm, delay<FNC & 1>(zero));
        if ((OB || (XB & 1)) && !last) bar_arrive(8, 256 + OB);
        if (PV && !last && w == 7) bar_arrive(13, 64);
        {
            float acc[6][4];
#pragma unroll
            for (int kk = 0; kk < 8; kk++) {
                const int j = (2 * kk) % 12;
                if (kk == 0) { mma16z(acc[5], sw[0], b[0].x, b[0].y); mma16z(acc[4], sw[1], b[0].x, b[0].y); }
                else { mma16(acc[5], sw[j], b[kk].x, b[kk].y); mma16(acc[4], sw[j + 1], b[kk].x, b[kk].y); }
#pragma unroll
                for (int i = 0; i < 4; i++) {
                    if (kk == 0) mma16z(acc[i], wa[i * 8], b[0].x, b[0].y);
                    else mma16(acc[i], wa[i * 8 + kk], b[kk].x, b[kk].y);
                    if (i < 2) ldsm4t(sw[j + i], wl + (12 + 2 * kk + i) * 512);
                }
            }
            st_part(pw + 4 * 2048, acc[4], acc[5]);
            st_part(pw, acc[0], acc[1]);
            st_part(pw + 2 * 2048, acc[2], acc[3]);
        }
        uint32_t kv0, kv1;
        const uint32_t lp = l16 + (lane >> 4) * 256, pl = lp + pt;
        if (!PV) {
            bar_sync(1, last ? 256 : 256 + OB);
            red_part<true>(kv1, kv0, pl, eye);
            sts64(l16 + CH_QK + (w >> 1) * 512 + (w & 1) * 8, __uint_as_float(kv1), __uint_as_float(kv0));
            if (!last) bar_arrive(2, nq * 32 + 64 + OB);
        } else {
            bar_sync(1, last ? 256 : 256 + OB);
        }
        {
            float va[4][4];
            const float z = __uint_as_float(delay<1>(zero));
#pragma unroll
            for (int i = 0; i < 4; i++) va[i][0] = va[i][1] = va[i][2] = va[i][3] = z;
#pragma unroll
            for (int kk = 0; kk < 8; kk++) {
                const int c = (PV ? VCH_P : VCH_C) == 4 ? kk & 1 : 0;
                if (kk < 2) { mma16(va[c], wa[32 + 2 * kk], b[kk].x, b[kk].y); mma16(va[2 + c], wa[33 + 2 * kk], b[kk].x, b[kk].y); }
                else { mma16(va[c], sw[(2 * kk) % 12], b[kk].x, b[kk].y); mma16(va[2 + c], sw[(2 * kk + 1) % 12], b[kk].x, b[kk].y); }
            }
            if ((PV ? VCH_P : VCH_C) == 4) {
#pragma unroll
                for (int j = 0; j < 4; j++) { va[0][j] += va[1][j]; va[2][j] += va[3][j]; }
            }
            st_part(pw + 6 * 2048, va[0], va[2]);
        }
        if (PV) {
            uint32_t vt0[4], vt1[4];
            ldsm4t(vt0, xs); ldsm4t(vt1, xs + 512);
            if (w >= 6 && !last) {
                uint32_t kx[3][4];
#pragma unroll
                for (int j = 0; j < 3; j++)
                    ldsm4(kx[j], sb + CH_XS + j * 1024 + (j == 2 && nq == 5 ? 0 : ((lane >> 3) & 1) * 512) + (w - 6) * 256 + (lane >> 4) * 128 + (lane & 7) * 16);
                const uint32_t da = l16 + CH_SX + rank * 1280 + (w - 6) * 512, dc = sb + CH_SX + rank * 1280 + 1024 + lane * 8;
                bar_sync(2, nq * 32 + 64 + OB);
                uint32_t qk[3][4];
#pragma unroll
                for (int j = 0; j < 3; j++) {
                    const float4 v = lds128(l16 + CH_QK + j * 512);
                    qk[j][0] = __float_as_uint(v.x); qk[j][1] = __float_as_uint(v.y); qk[j][2] = __float_as_uint(v.z); qk[j][3] = __float_as_uint(v.w);
                }
                float s0[4], s1[4], s2[4], s3[4];
                mma16z(s0, qk[0], kx[0][0], kx[0][1]); mma16z(s1, qk[0], kx[0][2], kx[0][3]);
                mma16z(s2, qk[1], kx[1][0], kx[1][1]); mma16z(s3, qk[1], kx[1][2], kx[1][3]);
                if (nq == 5) qk[2][2] = qk[2][3] = 0;
                mma16(s0, qk[2], kx[2][0], kx[2][1]); mma16(s1, qk[2], kx[2][2], kx[2][3]);
                float m0[4], m1[4];
                mma16z(m0, qk[0], qk[0][1], qk[0][3]); mma16z(m1, qk[1], qk[1][1], qk[1][3]);
                mma16(m0, qk[2], qk[2][1], qk[2][3]);
                const float4 sv = make_float4(s0[0] + s2[0], s0[1] + s2[1], s1[0] + s3[0], s1[1] + s3[1]);
                st_async4(mapa(da, rk1), sv, mapa(barS, rk1));
                st_async4(mapa(da, rk2), sv, mapa(barS, rk2));
                {
                    const float c0 = m0[0] + m1[0], c1 = m0[1] + m1[1];
                    const int dr = w == 6 ? rk1 : rk2;
                    st_async2(mapa(dc, dr), c0, c1, mapa(barS, dr));
                    sts64(dc, c0, c1);
                }
                const float t4[4] = {sv.x, sv.y, sv.z, sv.w};
                sts128(da, t4);
            }
            bar_sync(3, last ? 256 : 256 + OB);
            if (!last && w == 7) bar_arrive(12, 64);
            red_part<false>(kv0, kv1, pl, eye);
            if (last) {
                uint32_t* d = (uint32_t*)(kvo + (uint32_t)(s * (NH * 2048) + lane * 4));
                d[0] = movm(kv0); d[32] = movm(kv1);
                break;
            }
            {
                const uint32_t sx = l16 + CH_SX, r0 = rank * 1280, r1 = rk1 * 1280, r2 = rk2 * 1280;
                float4 a0 = lds128(sx + r0), b0 = lds128(sx + 512 + r0);
                const float2 c0 = lds64(sx + 1024 + r0 - lane * 8);
                preload<0, 0, PE>(sw, wl + 28 * 512, zero);
                mbar_wait(barS, s & 1);
                const float4 a1 = lds128(sx + r1), a2 = lds128(sx + r2), b1 = lds128(sx + 512 + r1), b2 = lds128(sx + 512 + r2);
                const float2 c1 = lds64(sx + 1024 + r1 - lane * 8), c2 = lds64(sx + 1024 + r2 - lane * 8);
                a0 = add4(add4(a0, a1), a2); b0 = add4(add4(b0, b1), b2);
                float sc[10] = {a0.x, a0.y, a0.z, a0.w, b0.x, b0.y, b0.z, b0.w, c0.x + c1.x + c2.x, c0.y + c1.y + c2.y};
                float mx = fmaxf(fmaxf(fmaxf(sc[0], sc[1]), fmaxf(sc[2], sc[3])), fmaxf(fmaxf(sc[4], sc[5]), fmaxf(sc[6], sc[7])));
                mx = fmaxf(mx, fmaxf(sc[8], sc[9]));
                mx = fmaxf(fmaxf(mx, __shfl_xor_sync(0xffffffffu, mx, 1)),
                           fmaxf(__shfl_xor_sync(0xffffffffu, mx, 2), __shfl_xor_sync(0xffffffffu, mx, 3)));
                const float cs = 0.08838834764831845f * 1.4426950408889634f;
                const float mb = -mx * cs;
#pragma unroll
                for (int j = 0; j < 10; j++) sc[j] = ex2(fmaf(sc[j], cs, mb));
                uint32_t pf[5];
#pragma unroll
                for (int j = 0; j < 5; j++) pf[j] = pack_bf16(sc[2 * j], sc[2 * j + 1]);
                float o0[4], o1[4], o2[4], o3[4], o4[4], o5[4];
                const uint32_t p0[4] = {pf[0], 0, pf[1], 0}, p1[4] = {pf[2], 0, pf[3], 0};
                mma16z(o0, p0, vt0[0], vt0[1]); mma16z(o1, p0, vt1[0], vt1[1]);
                mma16z(o2, p1, vt0[2], vt0[3]); mma16z(o3, p1, vt1[2], vt1[3]);
                mma8z(o4, pf[4], 0, kv0); mma8z(o5, pf[4], 0, kv1);
                float sum = (((sc[0] + sc[1]) + (sc[2] + sc[3])) + ((sc[4] + sc[5]) + (sc[6] + sc[7]))) + (sc[8] + sc[9]);
                sum = (sum + __shfl_xor_sync(0xffffffffu, sum, 1)) + (__shfl_xor_sync(0xffffffffu, sum, 2) + __shfl_xor_sync(0xffffffffu, sum, 3));
                float inv; asm("rcp.approx.ftz.f32 %0, %1;" : "=f"(inv) : "f"(sum));
                const uint32_t ox = pack_bf16((o0[0] + o2[0] + o4[0]) * inv, (o0[1] + o2[1] + o4[1]) * inv);
                const uint32_t oy = pack_bf16((o1[0] + o3[0] + o5[0]) * inv, (o1[1] + o3[1] + o5[1]) * inv);
                char* const pp = ring0 + (pub + slot + (lo16 >> 1));
                st_pub(pp, ox, oy); st_pub(pp + 4096, ox, oy);
                if (OB || (XB & 4)) bar_arrive(10, (8 - nq) * 32 + OB);
                preload<0, PE, PL>(sw, wl + 28 * 512, zero);
            }
            kv0 = movm(kv0); kv1 = movm(kv1);
        } else {
            *(uint32_t*)(kvo + (uint32_t)(s * (NH * 2048) + lane * 4)) = kv0;
            bar_sync(3, last ? 256 : 256 + OB);
            if (last) break;
            preload<1, 0, CL>(sw, wl + 28 * 512, zero);
        }
        uint2 c[11];
        bar_sync(4, 256 + OB);
        const char* po = ring0 + (o_rd + slot + (lo16 >> 1) + delay<DLO>(zero));
        poll_issue<11>(c, po, rank < 2);
        preload<0, PV ? PL : CL, 12>(sw, wl + 28 * 512, zero);
        if (PV) { uint32_t* d = (uint32_t*)(kvo + (uint32_t)(s * (NH * 2048) + lane * 4)); d[0] = kv0; d[32] = kv1; }
        if (FNC & 2) bar_arrive(15, 256);
        poll_check<11>(c, po, delay<(FNC >> 1)>(zero));
        if (OB || (XB & 2)) bar_arrive(9, 256 + OB);
        {
            float acc[4][4];
#pragma unroll
            for (int f = 0; f < 22; f++) {
                const int kk = f >> 1, a = f & 3;
                if (f < 4) mma16z(acc[a], sw[f % 12], c[kk].x, c[kk].y);
                else mma16(acc[a], sw[f % 12], c[kk].x, c[kk].y);
                if (f + 12 < 22) ldsm4t(sw[f % 12], wl + (28 + f + 12) * 512);
            }
#pragma unroll
            for (int i = 0; i < 2; i++) {
#pragma unroll
                for (int j = 0; j < 4; j++) acc[i][j] += acc[i + 2][j];
                sts128(l16 + CH_PART + i * 4096 + w * 512, acc[i]);
            }
        }
        if (!PV && w < 2) {
            bar_sync(5, 288 + OB);
            float4 v[8];
#pragma unroll
            for (int i = 0; i < 8; i++) v[i] = lds128(l16 + CH_PART + w * 4096 + i * 512);
            float4 r = add4(add4(add4(v[0], v[1]), add4(v[2], v[3])), add4(add4(v[4], v[5]), add4(v[6], v[7])));
            if (!mown) st_async4(mapa(l16 + CH_MX + rank * 512, w), r, mapa(barM, w));
            bar_arrive(7, 256 + OB);
            if (mown) {
                mbar_wait(barM, s & 1);
                float4 x = lds128(l16 + CH_MX + (rank ^ 1) * 512), y = lds128(l16 + CH_MX + 2 * 512);
                r = add4(add4(x, r), y);
                const uint32_t mx = movm(pack_bf16(r.x, r.y)), my = movm(pack_bf16(r.z, r.w));
                const uint32_t ns = (slot + 0x4000) & 0xC000;
                char* const pp = ring0 + (pub + ns + (lo16 >> 1));
                st_pub(pp, mx, my); st_pub(pp + 4096, mx, my);
            }
            preload<0, 0, ML>(sw, wl, zero);
        } else {
            bar_arrive(5, 288 + OB);
            bar_sync(7, 256 + OB);
            preload<MP, 0, ML>(sw, wl, zero);
        }
        bar_sync(6, 320 + OB);
    }
    bar_arrive(6, 288);
}

__device__ __forceinline__ void chain_pace(const uint32_t sb, const int lane, const int rank, const int aware) {
    const uint32_t zero = sb + CH_BAR + 24;
    if (lane == 0) {
        char* ring = ring_base();
        uint32_t* p0 = (uint32_t*)(ring + ring_off(blockIdx.x & 15, 0) + 3072 + (blockIdx.x >> 4) * 128);
        uint32_t* p1 = (uint32_t*)(ring + ring_off(blockIdx.x & 15, 1) + 3072 + (blockIdx.x >> 4) * 128);
        *p0 = 0; *p1 = 0;
        int b0 = 1 << 30, b1 = 1 << 30; uint32_t v = 0;
        for (int r = 0; r < 4 || (r < 256 && !mbar_test(sb + CH_BAR + 16, 0)); r++) {
            uint32_t t0 = clk(); v = atomicExch(p0 + (v == 500), r); uint32_t t1 = v == 777 ? clk() + 1 : clk(); b0 = min(b0, (int)(t1 - t0));
            t0 = clk(); v = atomicExch(p1 + (v == 500), r); t1 = v == 777 ? clk() + 1 : clk(); b1 = min(b1, (int)(t1 - t0));
            asm volatile("st.volatile.shared.u32 [%0], %1;" ::"r"(zero + 4), "r"(aware ? (b1 < b0) ^ (aware - 1) : 0) : "memory");
        }
    }
    __syncwarp();
#pragma unroll 1
    for (int s = 1; s < NSEG; s++) {
        bar_sync(5, 288 + OB);
        bar_arrive(6, 320 + OB + (rank == 2 ? delay<PACE2>(zero) : 0));
    }
}
__device__ __forceinline__ char* reset_ptr(const int lane, const int rank, const int h) {
    const int nq = rank == 0 ? 6 : 5, v0 = rank == 0 ? -6 : 3 * rank - 6;
    int pos, cw = o_chunk(h * 8 + v0 + min(max(5 + (lane >> 3), nq), 7), pos);
    if (lane >= 24 && rank < 2) { cw = 24 + (h >> 2); pos = (2 * h + rank) & 7; }
    return ring_base() + ((ring_off(cw, 0) & ~4096u) + pos * 256 + (lane & 7) * 16);
}
__device__ __forceinline__ void chain_chores(const uint32_t sb, const int lane, const int rank, const int h, const bf16* __restrict__ mem0) {
    const int nq = rank == 0 ? 6 : 5, u0 = rank == 0 ? 0 : 1 + 5 * rank, v0 = rank == 0 ? -6 : 3 * rank - 6;
    const uint32_t barS = sb + CH_BAR, barM = barS + 8, barX = barS + 16;
    auto xload = [&](int s) {
        mbar_expect(barX, 8192 - nq * 512);
        bulk_load(sb + CH_XS, g_kx + (size_t)(s * NH + h) * 4096 + u0 * 256, nq * 512, barX);
        bulk_load(sb + CH_XS + nq * 512, g_vx + (size_t)(s * NH + h) * 4096 + (v0 + nq) * 512, (8 - nq) * 1024, barX);
    };
    char* const rb = reset_ptr(lane, rank, h);
    int* const kvf = g_kvf + blockIdx.x * 16;
    if (rank < 2) {
        const uint32_t* p = (const uint32_t*)(mem0 + (lane >> 2) * DM + 32 * h + 16 * rank + 2 * (lane & 3));
        char* d = ring_base() + ((ring_off(24 + (h >> 2), 0) & ~4096u) + ((2 * h + rank) & 7) * 256 + lane * 8);
        const uint32_t x = p[0] == SENT ? 0x7FFF7FFFu : p[0];
        st_pub(d, x, p[4]); st_pub(d + 4096, x, p[4]);
    }
    if (lane == 0) {
        if (!KVN) __nanosleep(18000);
        wait_ctr(kvf, KVN);
        asm volatile("fence.proxy.async.global;" ::: "memory");
        xload(0);
    }
#pragma unroll 1
    for (int s = 0; s < NSEG - 1; s++) {
        if (lane == 0) {
            mbar_expect(barS, 2 * 1280);
            if (rank < 2) mbar_expect(barM, 2 * 512);
        }
        bar_sync(13, 64);
#pragma unroll
        for (int i = 0; i < 4; i++)
            asm volatile("st.relaxed.gpu.global.v4.u32 [%0], {%1,%1,%1,%1};" ::"l"(rb + ((((s + 2) & 3) << 14) + (i >> 1) * 4096 + (i & 1) * 128)), "r"(SENT) : "memory");
        if (FEN || (s & 3) == 0) fence_gpu();
        if (lane == 0 && (s & 3) == 0 && s) atomicAdd(g_ctr + C_CHAIN + (s >> 2) - 1, 1);
        if (lane == 0 && (s & 3) == 3) { wait_ctr(kvf + (s >> 2) + 1, KVN); asm volatile("fence.proxy.async.global;" ::: "memory"); }
        __syncwarp();
        bar_sync(12, 64);
        if (lane == 0) xload(s + 1);
        mbar_wait(barX, (s + 1) & 1);
        bar_sync(6, 320 + OB);
    }
    bar_sync(6, 288);
    fence_gpu();
    if (lane == 0) atomicAdd(g_ctr + C_CHAIN + 15, 1);
}

struct S4Params { const bf16 *Are, *Aim, *Bre, *Bim, *Cre, *Cim, *ldt, *dsk; };
__device__ __forceinline__ float2 cmul(float2 a, float2 b) { return make_float2(a.x * b.x - a.y * b.y, a.x * b.y + a.y * b.x); }
__device__ __forceinline__ float2 csq(float2 a) { return make_float2(a.x * a.x - a.y * a.y, (a.x + a.x) * a.y); }
__device__ __forceinline__ float2 cexp_t(float lr, float turns) {
    float f = (turns - rintf(turns)) * 6.283185307179586f, e = ex2(lr);
    return make_float2(e * __cosf(f), e * __sinf(f));
}
__device__ __forceinline__ float bf_at(uint2 v, int i) {
    const uint32_t w = i < 2 ? v.x : v.y;
    return __uint_as_float((i & 1) ? w & 0xFFFF0000u : w << 16);
}
__device__ __forceinline__ void kg_step(uint32_t (&a)[4][4], uint32_t (&b)[5][2], uint32_t pa, uint32_t pe, float x0) {
#pragma unroll
    for (int i = 0; i < 2; i++) {
        const float4 p = lds128(pa + i * 64);
        const float2 e8 = lds64(pe + i * 32), c = make_float2(p.z, p.w);
        const float mag = ex2(p.x * x0), ph = p.y * x0;
        float2 e0 = make_float2(mag * __cosf(ph), mag * __sinf(ph)), e1 = cmul(e0, e8);
#pragma unroll
        for (int j = 0; j < 4; j++) {
            a[j][2 * i] = pack_bf16(e0.x, e0.y); a[j][2 * i + 1] = pack_bf16(e1.x, e1.y);
            e0 = csq(e0); e1 = csq(e1);
        }
        float2 m = cmul(c, e0);
        b[0][i] = pack_bf16(m.x, -m.y);
#pragma unroll
        for (int j = 0; j < 4; j++) {
            m = cmul(c, e1);
            b[j + 1][i] = pack_bf16(m.x, -m.y);
            if (j < 3) e1 = csq(e1);
        }
    }
}
__device__ __forceinline__ void kg_mma(float (&kd)[5][4], const uint32_t (&a)[4][4], const uint32_t (&b)[5][2]) {
    mma16(kd[0], a[0], b[0][0], b[0][1]);
#pragma unroll
    for (int j = 0; j < 4; j++) mma16(kd[j + 1], a[j], b[j + 1][0], b[j + 1][1]);
}
struct KgRaw { uint2 v[6]; float ldt; };
__device__ __forceinline__ void kg_load(KgRaw& r, const S4Params& P, int d, int lane) {
    const bf16* src[6] = {P.Are, P.Aim, P.Bre, P.Bim, P.Cre, P.Cim};
#pragma unroll
    for (int j = 0; j < 6; j++) r.v[j] = __ldg((const uint2*)(src[j] + d * 128) + lane);
    r.ldt = __bfloat162float(P.ldt[d]);
}
__device__ __forceinline__ float kg_params(const KgRaw& r, uint32_t stg, int lane) {
    const float dt = __bfloat162float(__float2bfloat16(expf(r.ldt)));
    float k2048 = 0.f;
#pragma unroll
    for (int i = 0; i < 4; i++) {
        const float br = dt * bf_at(r.v[2], i), bi = dt * bf_at(r.v[3], i), cr = bf_at(r.v[4], i), ci = bf_at(r.v[5], i);
        const float zr = dt * bf_at(r.v[0], i) * 1.4426950408889634f;
        float zt = dt * bf_at(r.v[1], i) * 0.15915494309189535f;
        zt -= rintf(zt);
        const float v[4] = {zr, zt * 6.283185307179586f, cr * br - ci * bi, cr * bi + ci * br};
        const float2 e8 = cexp_t(8.f * zr, 8.f * zt), el = cexp_t(2048.f * zr, 2048.f * zt);
        k2048 += v[2] * el.x - v[3] * el.y;
        sts128(stg + (i * 32 + lane) * 16, v);
        sts64(stg + 2048 + (i * 32 + lane) * 8, e8.x, e8.y);
    }
#pragma unroll
    for (int o = 16; o; o >>= 1) k2048 += __shfl_xor_sync(0xffffffffu, k2048, o);
    __syncwarp();
    return k2048;
}
__device__ __forceinline__ void kg_store(const float (&kd)[5][4], float k2048, uint32_t stg, int d, int lane) {
    __syncwarp();
    const uint32_t ta = stg + (lane & 7) * 32 + ((lane >> 3) & 1) * 16 + (lane >> 4) * 256;
    stsm4t(ta, pack_bf16(kd[0][0], kd[0][1]), pack_bf16(kd[0][2], kd[0][3]), pack_bf16(kd[1][0], kd[1][1]), pack_bf16(kd[1][2], kd[1][3]));
    stsm4t(ta + 512, pack_bf16(kd[2][0], kd[2][1]), pack_bf16(kd[2][2], kd[2][3]), pack_bf16(kd[3][0], kd[3][1]), pack_bf16(kd[3][2], kd[3][3]));
    stsm4t(ta + 1024, pack_bf16(kd[4][0], kd[4][1]), pack_bf16(kd[4][2], kd[4][3]), pack_bf16(k2048, 0.f), 0);
    __syncwarp();
#pragma unroll
    for (int j = 0; j < 3; j++) ((float4*)(g_kd + d * 768))[j * 32 + lane] = lds128(stg + j * 512 + lane * 16);
    __syncwarp();
}

__global__ void __cluster_dims__(3, 1, 1) __launch_bounds__(CH_THREADS, 1)
chain_kernel(const __grid_constant__ CUtensorMap mq, const __grid_constant__ CUtensorMap mk, const __grid_constant__ CUtensorMap mv,
             const __grid_constant__ CUtensorMap mo, const bf16* __restrict__ Wq, const bf16* __restrict__ Wk, const bf16* __restrict__ Wv,
             const bf16* __restrict__ mem0, const __grid_constant__ S4Params P, int aware) {
    extern __shared__ __align__(1024) unsigned char smem[];
    const uint32_t sb = smem_u32(smem);
    const int tid = threadIdx.x, lane = tid & 31;
    const int w = __shfl_sync(0xffffffffu, tid >> 5, 0);
    int rank; asm("mov.u32 %0, %%cluster_ctarank;" : "=r"(rank));
    const int h = blockIdx.x / 3;
    if (tid == 0) {
        mbar_init(sb + CH_BAR, 1); mbar_init(sb + CH_BAR + 8, 1); mbar_init(sb + CH_BAR + 16, 1);
        for (int i = 0; i < 16; i++) mbar_init(sb + CH_BAR + 64 + i * 8, 1);
        *(int*)(smem + CH_BAR + 24) = 0; *(int*)(smem + CH_BAR + 28) = 0; *(int*)(smem + CH_BAR + 32) = 0;
        asm volatile("fence.mbarrier_init.release.cluster;" ::: "memory");
    }
    if (w == 10 && PFKV) {
        const int e = lane * 96 + blockIdx.x;
        if (e < 2048) asm volatile("cp.async.bulk.prefetch.L2.global [%0], 8192;" ::"l"(((e & 1) ? Wv : Wk) + (size_t)(e >> 1) * HD) : "memory");
        if (PFKV > 1) __nanosleep(PFKV);
    }
    if (w == 9) {
        char* const rb = reset_ptr(lane, rank, h);
#pragma unroll
        for (int i = 0; i < 8; i++)
            asm volatile("st.relaxed.gpu.global.v4.u32 [%0], {%1,%1,%1,%1};" ::"l"(rb + (((i >> 2) << 14) + ((i >> 1) & 1) * 4096 + (i & 1) * 128)), "r"(SENT) : "memory");
        if (lane < 16) g_kvf[blockIdx.x * 16 + lane] = 0;
        if (blockIdx.x == 0)
            for (int k = lane; k < N_CTR; k += 32) g_ctr[k] = 0;
        fence_gpu();
        __syncwarp();
        asm volatile("griddepcontrol.launch_dependents;" ::: "memory");
    }
    __syncthreads();
    asm volatile("barrier.cluster.arrive.relaxed.aligned;" ::: "memory");

    if (w >= 8) {
        reg_dec<24>();
        asm volatile("barrier.cluster.wait.aligned;" ::: "memory");
        if (w == 8) chain_pace(sb, lane, rank, aware);
        else if (w == 9) {
            chain_chores(sb, lane, rank, h, mem0);
            asm volatile("st.volatile.shared.u32 [%0], %1;" ::"r"(sb + CH_BAR + 32), "r"(0x3F803F80) : "memory");
        } else if (w == 11 && KEEP) {
#pragma unroll 1
            for (int it = 0; it < (1 << 22); it++) {
                int d0, d1;
                const uint32_t x = delay<1>(sb + CH_BAR + 32);
                asm volatile("mma.sync.aligned.m8n8k16.row.col.s32.s8.s8.s32 {%0,%1}, {%2}, {%2}, {%3,%3};" : "=r"(d0), "=r"(d1) : "r"(x), "r"(0));
                if (d0 | d1) break;
                if ((XB & 8) && lane == 0) asm volatile("st.relaxed.gpu.global.u32 [%0], %1;" ::"l"(g_kd + DM * 768 + blockIdx.x * 64), "r"(it) : "memory");
                if ((XB & 16) && lane == 0) ld_acq((int*)(g_kd + DM * 768 + blockIdx.x * 64));
                __nanosleep(KEEP);
            }
        }
    } else {
        reg_inc<240>();
        const int nq = rank == 0 ? 6 : 5;
        const int u0 = rank == 0 ? 0 : 1 + 5 * rank;
        const int v0 = rank == 0 ? -6 : 3 * rank - 6;
        const int gw = rank * 8 + w;
        const int ks0 = gw < 16 ? 11 * gw : 176 + 10 * (gw - 16);
        const int nko = gw < 16 ? 11 : 10;
        const uint32_t wr = sb + w * CH_WREG, bar0 = sb + CH_BAR + 64 + w * 16, bar1 = bar0 + 8;
        uint32_t wa[36][4];
        const uint32_t vst = sb + CH_PART + w * 2048;
        const int cq = h * DH + 8 * u0, cv = h * DH + 16 * (v0 + 6);
        const int r8 = lane >> 2, p = lane & 3;
        const bf16* src = p >= 2 ? ((p & 1) ? Wk : Wq) + cq + 32 : rank == 0 ? ((p & 1) ? Wk : Wq) + cq + 40 : Wv + cv - 16 + 8 * p;
        src += (size_t)(128 * w + r8) * HD;
        auto cp_rows = [&](int kh) {
            cp16(wr + ((kh >> 1) * 2 + (p >> 1)) * 512 + ((kh & 1) * 2 + (p & 1)) * 128 + r8 * 16, src + (size_t)kh * 8 * HD);
        };
        {
            int d = blockIdx.x * 8 + w, t = 0;
            const int d1 = 768 + blockIdx.x * 3 + w, nt = (w < 3 && d1 < DM) ? 32 : 16;
            const uint32_t stg = wr + 4096;
            KgRaw raw, raw1;
            kg_load(raw, P, d, lane);
            kg_load(raw1, P, min(d1, DM - 1), lane);
            float kd[5][4], k2048;
#pragma unroll 1
            for (int i = -LDW; i < 9 || t < nt; i++) {
                if (i >= 0 && i < 9) {
                    const uint32_t bar = bar0 + (i & 1) * 8;
                    if (i >= 2) mbar_wait(bar, ((i >> 1) - 1) & 1);
                    if (lane == 0) {
                        mbar_expect(bar, 2048);
                        if (i < 8) tma2d(wr + 8192 + (i & 1) * 8192 + (i >> 1) * 2048, (i & 1) ? &mk : &mq, cq, 128 * w + 32 * (i >> 1), bar);
                        else tma2d(vst, &mv, cv, 128 * w, bar);
                    }
                    if (i < 8) cp_rows(i);
                }
#pragma unroll 1
                for (int e = min(t + KGS, nt); t < e; t++) {
                    if ((t & 15) == 0) {
                        k2048 = kg_params(raw, stg, lane);
#pragma unroll
                        for (int j = 0; j < 20; j++) kd[j >> 2][j & 3] = 0.f;
                    }
                    uint32_t ka[4][4], kb[5][2];
                    kg_step(ka, kb, stg + ((t & 15) * 8 + (lane & 3)) * 16, stg + 2048 + ((t & 15) * 8 + (lane & 3)) * 8, (float)(lane >> 2));
                    kg_mma(kd, ka, kb);
                    if ((t & 15) == 15) { kg_store(kd, k2048, stg, d, lane); raw = raw1; d = d1; }
                }
            }
        }
        const uint32_t lrow = ((lane >> 4) * 8 + (lane & 7)) * 64, lsw = (lane >> 1) & 3, lh = (lane >> 3) & 1;
        mbar_wait(bar1, 1); mbar_wait(bar0, 0);
#pragma unroll
        for (int i = 0; i < 32; i++) ldsm4t(wa[i], wr + 8192 + lh * 8192 + (i & 7) * 1024 + lrow + (((i >> 3) ^ lsw) << 4));
#pragma unroll
        for (int i = 0; i < 4; i++) ldsm4t(wa[32 + i], vst + (i >> 1) * 1024 + lrow + ((((i & 1) * 2 + lh) ^ lsw) << 4));
        asm volatile("fence.proxy.async.shared::cta;" ::"r"(wa[31][0]), "r"(wa[35][0]) : "memory");
        __syncwarp();
        if (w < R1W) {
            if (lane == 0) {
                mbar_expect(bar1, 6144 + nko * 1024);
                for (int i = 0; i < 3; i++) tma2d(wr + 8192 + i * 2048, &mv, cv, 128 * w + 32 + 32 * i, bar1);
                for (int i = 0; i < nko; i++) tma2d(wr + 14336 + i * 1024, &mo, 32 * h, 16 * (ks0 + i), bar1);
            }
#pragma unroll 1
            for (int i = 8; i < 16; i++) cp_rows(i);
        } else {
#pragma unroll 1
            for (int i = 9; i < 18; i++) {
                const uint32_t bar = bar0 + (i & 1) * 8;
                if (i >= 11) mbar_wait(bar, ((i >> 1) - 1) & 1);
                if (lane == 0) {
                    const int j = 2 * (i - 12), nb = min(2, nko - j);
                    mbar_expect(bar, i < 12 ? 2048 : nb * 1024);
                    if (i < 12) tma2d(wr + 8192 + (i - 9) * 2048, &mv, cv, 128 * w + 32 * (i - 8), bar);
                    else for (int e = 0; e < nb; e++) tma2d(wr + 14336 + (j + e) * 1024, &mo, 32 * h, 16 * (ks0 + j + e), bar);
                }
                if (i < 17) cp_rows(i - 1);
            }
        }
        mbar_wait(bar0, 0); mbar_wait(bar1, 0);
#pragma unroll 1
        for (int i0 = -1; i0 < 17; i0 += 6) {
            uint32_t x[6][2][4];
#pragma unroll
            for (int i = 0; i < 6; i++) {
                const uint32_t a = wr + 8192 + max(i0 + i, 0) * 1024 + lrow;
                ldsm4t(x[i][0], a + ((lh ^ lsw) << 4)); ldsm4t(x[i][1], a + (((2 + lh) ^ lsw) << 4));
            }
            if (i0 == 11 && nko == 10) {
#pragma unroll
                for (int j = 0; j < 8; j++) x[5][j >> 2][j & 3] = 0;
            }
            __syncwarp();
#pragma unroll
            for (int i = 0; i < 6; i++) {
                const uint32_t a = wr + 8192 + max(i0 + i, 0) * 1024 + lane * 16;
                stsm4t(a, x[i][0][0], x[i][0][1], x[i][0][2], x[i][0][3]); stsm4t(a + 512, x[i][1][0], x[i][1][1], x[i][1][2], x[i][1][3]);
            }
        }
        asm volatile("cp.async.wait_all;" ::: "memory");
        asm volatile("barrier.cluster.wait.aligned;" ::: "memory");
        bar_sync(1, 256);
        mbar_wait_long(sb + CH_BAR + 16, 0);
        const int side = __shfl_sync(0xffffffffu, *(volatile int*)(smem + CH_BAR + 28), 0);
        if (w >= nq) chain_loop<true>(wa, sb, w, lane, rank, h, side);
        else chain_loop<false>(wa, sb, w, lane, rank, h, side);
    }
}

constexpr int G_STAGE = 49152, G_NST = 4;
constexpr int G_STG = G_NST * G_STAGE;
constexpr int G_BAR = G_STG + 32768;
constexpr int G_SMEM = G_BAR + 256 + 1024;

#define WLOG(e)
constexpr int IT_QA = 0, IT_O = 1, IT_S4 = 2, IT_END = 3, IT_KV = 4;
#define O_WIDE 10
#define TMP 1
#define PING 1
#define S4DIR 5
#define S4REL 4
#define KVI 2
#define KVF 2
#define KVS 8
#define STM 0
__device__ __forceinline__ void st_out(uint32_t* p, uint32_t v) {
    if (STM == 0) *p = v;
    else if (STM == 1) __stcs(p, v);
    else asm volatile("st.global.L1::no_allocate.u32 [%0], %1;" ::"l"(p), "r"(v) : "memory");
}
#define Q_N1 1
#define Q_S1 16
__device__ __forceinline__ int queue_item(int q) {
    if (q < 512) return (IT_KV << 16) | ((q >> 5) << 8) | (q & 31);
    q -= 512;
    if (q < 256) return (IT_QA << 16) | ((q >> 4) << 8) | (q & 15);
    q -= 256;
    if (q < Q_N1 * 8) return (IT_O << 16) | ((O_WIDE + (q >> 3)) << 8) | (q & 7);
    q -= Q_N1 * 8;
    if (q < Q_S1) return (IT_S4 << 16) | q;
    q -= Q_S1;
    if (q < (16 - O_WIDE - Q_N1) * 8) return (IT_O << 16) | ((O_WIDE + Q_N1 + (q >> 3)) << 8) | (q & 7);
    q -= (16 - O_WIDE - Q_N1) * 8;
    if (q < 128 - Q_S1) return (IT_S4 << 16) | (Q_S1 + q);
    return IT_END << 16;
}
__device__ __forceinline__ void tma2d_store(const CUtensorMap* m, uint32_t src, int c0, int c1) {
    asm volatile("cp.async.bulk.tensor.2d.global.shared::cta.bulk_group [%0, {%2, %3}], [%1];" ::"l"(m), "r"(src), "r"(c0), "r"(c1) : "memory");
}

__device__ __forceinline__ void wgmma_s64(float (&d)[32], uint32_t a0, uint32_t a1, uint32_t a2, uint32_t a3, uint64_t db, int acc) {
    asm volatile("{.reg .pred p; setp.ne.b32 p, %37, 0;\n"
        "wgmma.mma_async.sync.aligned.m64n64k16.f32.bf16.bf16 {"
        "%0,%1,%2,%3,%4,%5,%6,%7,%8,%9,%10,%11,%12,%13,%14,%15,"
        "%16,%17,%18,%19,%20,%21,%22,%23,%24,%25,%26,%27,%28,%29,%30,%31"
        "}, {%32,%33,%34,%35}, %36, p, 1, 1, 0;}"
        : "+f"(d[0]), "+f"(d[1]), "+f"(d[2]), "+f"(d[3]), "+f"(d[4]), "+f"(d[5]), "+f"(d[6]), "+f"(d[7]), "+f"(d[8]), "+f"(d[9]), "+f"(d[10]), "+f"(d[11]), "+f"(d[12]), "+f"(d[13]), "+f"(d[14]), "+f"(d[15]), "+f"(d[16]), "+f"(d[17]), "+f"(d[18]), "+f"(d[19]), "+f"(d[20]), "+f"(d[21]), "+f"(d[22]), "+f"(d[23]), "+f"(d[24]), "+f"(d[25]), "+f"(d[26]), "+f"(d[27]), "+f"(d[28]), "+f"(d[29]), "+f"(d[30]), "+f"(d[31])
        : "r"(a0), "r"(a1), "r"(a2), "r"(a3), "l"(db), "r"(acc));
}
__device__ __forceinline__ void wgmma_s16(float (&d)[8], uint32_t a0, uint32_t a1, uint32_t a2, uint32_t a3, uint64_t db, int acc) {
    asm volatile("{.reg .pred p; setp.ne.b32 p, %13, 0;\n"
        "wgmma.mma_async.sync.aligned.m64n16k16.f32.bf16.bf16 {"
        "%0,%1,%2,%3,%4,%5,%6,%7"
        "}, {%8,%9,%10,%11}, %12, p, 1, 1, 0;}"
        : "+f"(d[0]), "+f"(d[1]), "+f"(d[2]), "+f"(d[3]), "+f"(d[4]), "+f"(d[5]), "+f"(d[6]), "+f"(d[7])
        : "r"(a0), "r"(a1), "r"(a2), "r"(a3), "l"(db), "r"(acc));
}
__device__ __forceinline__ void wgmma_v128(float (&d)[64], uint32_t a0, uint32_t a1, uint32_t a2, uint32_t a3, uint64_t db, int acc) {
    asm volatile("{.reg .pred p; setp.ne.b32 p, %69, 0;\n"
        "wgmma.mma_async.sync.aligned.m64n128k16.f32.bf16.bf16 {"
        "%0,%1,%2,%3,%4,%5,%6,%7,%8,%9,%10,%11,%12,%13,%14,%15,"
        "%16,%17,%18,%19,%20,%21,%22,%23,%24,%25,%26,%27,%28,%29,%30,%31,"
        "%32,%33,%34,%35,%36,%37,%38,%39,%40,%41,%42,%43,%44,%45,%46,%47,"
        "%48,%49,%50,%51,%52,%53,%54,%55,%56,%57,%58,%59,%60,%61,%62,%63"
        "}, {%64,%65,%66,%67}, %68, p, 1, 1, 1;}"
        : "+f"(d[0]), "+f"(d[1]), "+f"(d[2]), "+f"(d[3]), "+f"(d[4]), "+f"(d[5]), "+f"(d[6]), "+f"(d[7]), "+f"(d[8]), "+f"(d[9]), "+f"(d[10]), "+f"(d[11]), "+f"(d[12]), "+f"(d[13]), "+f"(d[14]), "+f"(d[15]), "+f"(d[16]), "+f"(d[17]), "+f"(d[18]), "+f"(d[19]), "+f"(d[20]), "+f"(d[21]), "+f"(d[22]), "+f"(d[23]), "+f"(d[24]), "+f"(d[25]), "+f"(d[26]), "+f"(d[27]), "+f"(d[28]), "+f"(d[29]), "+f"(d[30]), "+f"(d[31]), "+f"(d[32]), "+f"(d[33]), "+f"(d[34]), "+f"(d[35]), "+f"(d[36]), "+f"(d[37]), "+f"(d[38]), "+f"(d[39]), "+f"(d[40]), "+f"(d[41]), "+f"(d[42]), "+f"(d[43]), "+f"(d[44]), "+f"(d[45]), "+f"(d[46]), "+f"(d[47]), "+f"(d[48]), "+f"(d[49]), "+f"(d[50]), "+f"(d[51]), "+f"(d[52]), "+f"(d[53]), "+f"(d[54]), "+f"(d[55]), "+f"(d[56]), "+f"(d[57]), "+f"(d[58]), "+f"(d[59]), "+f"(d[60]), "+f"(d[61]), "+f"(d[62]), "+f"(d[63])
        : "r"(a0), "r"(a1), "r"(a2), "r"(a3), "l"(db), "r"(acc));
}

__device__ __forceinline__ void attn_scores(float (&sx)[32], float (&sm)[8], const uint32_t (&q)[32], uint32_t sk) {
    const uint64_t dx = mkdesc(sk, 1024, 128, 0), dm = mkdesc(sk + 16384, 256, 128, 0);
    wg_fence();
#pragma unroll
    for (int ks = 0; ks < 8; ks++) {
        wgmma_s64(sx, q[4 * ks], q[4 * ks + 1], q[4 * ks + 2], q[4 * ks + 3], dx + ks * 128, ks);
        wgmma_s16(sm, q[4 * ks], q[4 * ks + 1], q[4 * ks + 2], q[4 * ks + 3], dm + ks * 32, ks);
    }
    wg_commit();
}
template <bool HI>
__device__ __forceinline__ void attn_softmax(uint32_t (&p)[2][20], const float (&sx)[2][32], const float (&sm)[2][8], bool sb, int lane) {
    constexpr int NF = HI ? 2 : 0, NT = NF + 3;
    const int gt = (lane >> 2) - 2 * (lane & 3);
    const float cs = 0.08838834764831845f * 1.4426950408889634f;
    float s[2][NT][4], m[4], l[4];
#pragma unroll
    for (int h = 0; h < 2; h++) {
#pragma unroll
        for (int j = 0; j < NT; j++)
#pragma unroll
            for (int e = 0; e < 4; e++) s[h][j][e] = j == NT - 1 ? (sb ? sm[h][4 + e] : sm[h][e]) : (sb ? sx[h][16 + 4 * j + e] : sx[h][4 * j + e]);
        if (gt < 0) s[h][NF][0] = s[h][NF + 1][2] = -INFINITY;
        if (gt < 1) s[h][NF][1] = s[h][NF + 1][3] = -INFINITY;
        m[2 * h] = fmaxf(s[h][0][0], s[h][0][1]); m[2 * h + 1] = fmaxf(s[h][0][2], s[h][0][3]);
#pragma unroll
        for (int j = 1; j < NT; j++) {
            if (j != NF + 1) m[2 * h] = fmaxf(m[2 * h], fmaxf(s[h][j][0], s[h][j][1]));
            m[2 * h + 1] = fmaxf(m[2 * h + 1], fmaxf(s[h][j][2], s[h][j][3]));
        }
    }
#pragma unroll
    for (int r = 0; r < 4; r++) m[r] = fmaxf(m[r], __shfl_xor_sync(0xffffffffu, m[r], 1));
#pragma unroll
    for (int r = 0; r < 4; r++) m[r] = fmaxf(m[r], __shfl_xor_sync(0xffffffffu, m[r], 2)) * -cs;
#pragma unroll
    for (int r = 0; r < 4; r++) {
        l[r] = 0.f;
#pragma unroll
        for (int j = 0; j < NT; j++)
            if ((r & 1) || j != NF + 1) {
                float* v = &s[r >> 1][j][2 * (r & 1)];
                v[0] = ex2(fmaf(v[0], cs, m[r])); v[1] = ex2(fmaf(v[1], cs, m[r]));
                l[r] += v[0] + v[1];
            }
    }
#pragma unroll
    for (int r = 0; r < 4; r++) l[r] += __shfl_xor_sync(0xffffffffu, l[r], 1);
#pragma unroll
    for (int r = 0; r < 4; r++) { l[r] += __shfl_xor_sync(0xffffffffu, l[r], 2); asm("rcp.approx.ftz.f32 %0, %0;" : "+f"(l[r])); }
    const uint32_t ma = sb ? 0u : ~0u;
#pragma unroll
    for (int h = 0; h < 2; h++)
#pragma unroll
        for (int j = 0; j < 5; j++) {
            const bool on = j == 4 || j < NF + 2;
            const int k = j == 4 ? NT - 1 : on ? j : 0, ia = j < 4 ? 2 * j : 16, ib = j < 4 ? 8 + 2 * j : 18;
            const uint32_t x = on && j != NF + 1 ? pack_bf16(s[h][k][0] * l[2 * h], s[h][k][1] * l[2 * h]) : 0;
            const uint32_t y = on ? pack_bf16(s[h][k][2] * l[2 * h + 1], s[h][k][3] * l[2 * h + 1]) : 0;
            asm volatile("and.b32 %0, %4, %6; and.b32 %1, %5, %6; and.b32 %2, %4, %7; and.b32 %3, %5, %7;"
                : "=&r"(p[h][ia]), "=&r"(p[h][ia + 1]), "=&r"(p[h][ib]), "=&r"(p[h][ib + 1]) : "r"(x), "r"(y), "r"(ma), "r"(~ma));
        }
}
__device__ __forceinline__ void attn_pv(float (&o)[64], const uint32_t (&p)[20], uint32_t sv) {
    const uint64_t dx = mkdesc(sv, 128, 1024, 0), dm = mkdesc(sv + 16384, 128, 256, 0);
    wg_fence();
#pragma unroll
    for (int ks = 0; ks < 5; ks++) wgmma_v128(o, p[4 * ks], p[4 * ks + 1], p[4 * ks + 2], p[4 * ks + 3], ks < 4 ? dx + ks * 16 : dm, ks);
    wg_commit();
}
__device__ __forceinline__ void attn_stage(const float (&o)[64], uint32_t dst) {
#pragma unroll
    for (int u = 0; u < 16; u += 2)
        stsm4(dst + (u >> 3) * 8192 + (u & 7) * 128, pack_bf16(o[4 * u], o[4 * u + 1]), pack_bf16(o[4 * u + 2], o[4 * u + 3]),
              pack_bf16(o[4 * u + 4], o[4 * u + 5]), pack_bf16(o[4 * u + 6], o[4 * u + 7]));
}

template <int BN, int NKB, bool BLOCKED_A>
__device__ __forceinline__ void mainloop(float (&acc)[BN / 2], uint32_t sb, int wgi, uint32_t full, uint32_t empty, int& it, bool elect) {
#pragma unroll
    for (int j = 0; j < BN / 2; j++) acc[j] = 0.f;
#pragma unroll 1
    for (int k4 = 0; k4 < NKB; k4 += 4) {
#pragma unroll
        for (int st = 0; st < 4; st++, it++) {
            mbar_wait_long(full + 8 * st, (it >> 2) & 1);
            const uint64_t da = BLOCKED_A ? mkdesc(sb + st * G_STAGE + wgi * 8192, 128, 1024, 0) : mkdesc(sb + st * G_STAGE + wgi * 8192, 16, 1024, 1);
            const uint64_t db = mkdesc(sb + st * G_STAGE + 16384, 8192, 1024, 1);
            wg_fence();
#pragma unroll
            for (int k = 0; k < 4; k++) {
                if constexpr (BN == 256) wgmma256(acc, da + k * (BLOCKED_A ? 16 : 2), db + k * 128, 1);
                else wgmma128(acc, da + k * (BLOCKED_A ? 16 : 2), db + k * 128, 1);
            }
            wg_commit();
            if (k4 | st) {
                wg_wait<1>();
                if (elect) mbar_arrive(empty + 8 * ((st + 3) & 3));
            }
        }
    }
    wg_wait<0>();
    if (elect) mbar_arrive(empty + 8 * 3);
}

__device__ __forceinline__ uint32_t n6_a(int st) { return st < 4 ? st * G_STAGE : (2 * st - 8) * G_STAGE + 32768; }
__device__ __forceinline__ uint32_t n6_b(int st) { return st < 4 ? st * G_STAGE + 16384 : (2 * st - 7) * G_STAGE + 32768; }
__device__ __forceinline__ uint32_t n6_bar(int st) { return st < 4 ? 8 * st : 96 + 8 * st; }
__device__ __forceinline__ void mainloop6(float (&acc)[64], uint32_t sb, int wgi, uint32_t full, uint32_t empty, int& it, bool elect) {
#pragma unroll
    for (int j = 0; j < 64; j++) acc[j] = 0.f;
    int st = 0, prev = 0, r = 0;
#pragma unroll 1
    for (int kb = 0; kb < 64; kb++) {
        mbar_wait_long(full + n6_bar(st), ((st < 4 ? it >> 2 : 0) + r) & 1);
        const uint64_t da = mkdesc(sb + n6_a(st) + wgi * 8192, 128, 1024, 0), db = mkdesc(sb + n6_b(st), 8192, 1024, 1);
        wg_fence();
#pragma unroll
        for (int k = 0; k < 4; k++) wgmma128(acc, da + k * 16, db + k * 128, 1);
        wg_commit();
        if (kb) {
            wg_wait<1>();
            if (elect) mbar_arrive(empty + n6_bar(prev));
        }
        prev = st;
        if (++st == 6) { st = 0; r++; }
    }
    wg_wait<0>();
    if (elect) mbar_arrive(empty + 8 * 3);
    it += 44;
}

template <int BN>
__device__ __forceinline__ void o_item(uint32_t sb, int wgi, int wi, int lane, uint32_t full, uint32_t empty, int& it, const CUtensorMap* mout,
                                       int row0, int col0, uint32_t stgpar) {
    float acc[BN / 2];
    if constexpr (BN == 256) mainloop<BN, 64, true>(acc, sb, wgi, full, empty, it, lane == 0);
    else mainloop6(acc, sb, wgi, full, empty, it, lane == 0);
    ST((row0 >> 4) + (col0 / BN), wgi * 4 + wi, 10);
    mbar_wait(full + 104, stgpar);
    const uint32_t stg = sb + G_STG + (wgi * 4 + wi) * 4096;
    const int r = lane & 15, cu = lane >> 4;
#pragma unroll
    for (int hf = 0; hf < BN / 128; hf++) {
        if (lane == 0) asm volatile("cp.async.bulk.wait_group.read 0;" ::: "memory");
        __syncwarp();
#pragma unroll
        for (int j = 0; j < 8; j++) {
            const float* a = acc + hf * 64 + j * 8;
            stsm4(stg + (j >> 2) * 2048 + r * 128 + ((((j & 3) * 2 + cu) ^ (r & 7)) << 4),
                  pack_bf16(a[0], a[1]), pack_bf16(a[2], a[3]), pack_bf16(a[4], a[5]), pack_bf16(a[6], a[7]));
        }
        asm volatile("fence.proxy.async.shared::cta;" ::: "memory");
        __syncwarp();
        if (lane == 0) {
            tma2d_store(mout, stg, col0 + hf * 128, row0 + wgi * 64 + wi * 16);
            tma2d_store(mout, stg + 2048, col0 + hf * 128 + 64, row0 + wgi * 64 + wi * 16);
            asm volatile("cp.async.bulk.commit_group;" ::: "memory");
        }
    }
}

constexpr int S4_KD = 32768;
constexpr int S4_CH = 2 * G_STAGE;
constexpr int S4_HALF = 2304;
constexpr int S4_WD = 2 * S4_HALF;
constexpr int S4_T2 = S4_WD + 2304;
constexpr int S4_T3 = S4_T2 + 1024;
constexpr int S4_STRIDE = S4_T3 + 640 + 16;
__device__ __forceinline__ uint32_t addz(uint32_t x, uint32_t z) { uint32_t r; asm volatile("add.u32 %0, %1, %2;" : "=r"(r) : "r"(x), "r"(z)); return r; }
__device__ __forceinline__ uint32_t lds16(uint32_t a) { uint32_t v; asm volatile("ld.shared.u16 %0, [%1];" : "=r"(v) : "r"(a) : "memory"); return v; }
__device__ __forceinline__ uint32_t ldsu(uint32_t a) { return __float_as_uint(lds32(a)); }

template <int E0, int NE, int KP>
__device__ __forceinline__ void s4_windows(float (&acc)[8][2][4], uint32_t ut, uint32_t tw, int rho, int w, int lane, uint32_t z) {
    const int gt = (lane >> 2) - 2 * (lane & 3), p0 = rho == 16 ? -3 : -2, c = (lane >> 3) + p0;
    uint32_t band[2][4], ta[NE][4];
    {
        const uint64_t ones = ((uint64_t)((2u << 2 * w) - 1) << 32) >> (8 * p0 + 24 - gt + rho + w);
        uint32_t f[5];
#pragma unroll
        for (int m = 0; m < 5; m++) f[m] = ((((uint32_t)(ones >> (8 * m)) & 3) * 0x8001u) & 0x10001u) * 0x3F80u;
#pragma unroll
        for (int j = 0; j < 2; j++) { band[j][0] = f[2 * j + 1]; band[j][1] = addz(f[2 * j], z); band[j][2] = f[2 * j + 2]; band[j][3] = addz(f[2 * j + 1], z); }
    }
#pragma unroll
    for (int e = 0; e < NE; e++)
        asm volatile("ld.shared.u32 %0, [%4]; ld.shared.u32 %1, [%4+%5]; ld.volatile.shared.u32 %2, [%4+%6]; ld.volatile.shared.u32 %3, [%4];"
            : "=r"(ta[e][0]), "=r"(ta[e][1]), "=r"(ta[e][2]), "=r"(ta[e][3]) : "r"(tw + 16 * (E0 + e) * KP), "n"(8 * KP), "n"(-8 * KP) : "memory");
    const uint32_t ua = ut + (c & 1) * S4_HALF + (16 + (lane & 7) + (c >> 1)) * 16;
#pragma unroll
    for (int J = 0; J < 8 - E0; J++) {
        uint32_t u0[4], u1[4];
        ldsm4(u0, ua + J * 256); ldsm4(u1, ua + J * 256 + 128);
        float s0[4], s1[4];
        mma16z(s0, band[0], u0[0], u0[1]); mma16z(s1, band[0], u1[0], u1[1]);
        mma16(s0, band[1], u0[2], u0[3]); mma16(s1, band[1], u1[2], u1[3]);
        const uint32_t b00 = pack_bf16(s0[0], s0[1]), b01 = pack_bf16(s1[0], s1[1]), b10 = pack_bf16(s0[2], s0[3]), b11 = pack_bf16(s1[2], s1[3]);
#pragma unroll
        for (int e = 0; e < NE; e++)
            if (J + E0 + e < 8) { mma16(acc[J + E0 + e][0], ta[e], b00, b01); mma16(acc[J + E0 + e][1], ta[e], b10, b11); }
    }
}
template <int D0, int D1>
__device__ __forceinline__ void s4_dense(float (&acc)[8][2][4], uint32_t ua, const uint32_t (&b0)[4], const uint32_t (&b1)[4]) {
#pragma unroll
    for (int J = 0; J < 8 - D0; J++) {
        uint32_t a[4];
        ldsm4(a, ua + J * 256);
        mma16(acc[J + D0][0], a, b0[0], b0[1]); mma16(acc[J + D0][1], a, b0[2], b0[3]);
        if (J + D1 < 8) { mma16(acc[J + D1][0], a, b1[0], b1[1]); mma16(acc[J + D1][1], a, b1[2], b1[3]); }
    }
}
__device__ __forceinline__ void s4_words(uint32_t (&b)[4], uint32_t wd) {
    asm volatile("ld.shared.u32 %0, [%4]; ld.shared.u32 %1, [%4+-32]; ld.shared.u32 %2, [%4+32]; ld.volatile.shared.u32 %3, [%4];"
        : "=r"(b[0]), "=r"(b[1]), "=r"(b[2]), "=r"(b[3]) : "r"(wd) : "memory");
}

__device__ __forceinline__ void s4_item(uint32_t sb, int cw, int lane, int item, const bf16* __restrict__ dsk, uint32_t empty, const CUtensorMap* my, uint32_t stgpar,
                                        bf16* __restrict__ out, uint32_t nbar, uint32_t npar, uint32_t nslot) {
    const int gt = (lane >> 2) - 2 * (lane & 3);
    const uint32_t ch = sb + S4_CH + cw * S4_STRIDE, kd = sb + S4_KD + cw * 1536;
    const __nv_bfloat162 dk = __bfloat162bfloat162(dsk[item * 8 + cw]);
    ST(item, cw, 0);
    asm volatile("st.shared.v4.u32 [%0], {%1,%1,%1,%1};" ::"r"(ch + (lane >> 4) * S4_HALF + (lane & 15) * 16), "r"(0) : "memory");
    const uint32_t tch = sb + S4_CH + (lane & 7) * S4_STRIDE + ((lane >> 3) & 1) * S4_HALF + (16 + 16 * cw + (lane >> 4)) * 16;
#pragma unroll
    for (int i = 0; i < 8; i++) {
        uint32_t x[4];
        ldsm4t(x, sb + cw * 4096 + i * 512 + lane * 16);
        stsm4(tch + i * 32, x[0], x[1], x[2], x[3]);
    }
    const uint32_t k1024 = lds16(kd + 1024);
    {
        auto st4 = [](uint32_t a, uint32_t x, uint32_t y, uint32_t u, uint32_t v) {
            asm volatile("st.shared.v4.u32 [%0], {%1,%2,%3,%4};" ::"r"(a), "r"(x), "r"(y), "r"(u), "r"(v) : "memory");
        };
        const float4 p = lds128(kd + lane * 16);
        const uint32_t p0 = __float_as_uint(p.x), p1 = __float_as_uint(p.y), p2 = __float_as_uint(p.z), p3 = __float_as_uint(p.w);
        const uint32_t pm = lane ? ldsu(kd + lane * 16 - 4) : 0;
        const uint32_t wa = ch + S4_WD + 64 + lane * 32;
        st4(wa, __byte_perm(p0, pm, 0x7610), __byte_perm(p0, 0, 0x1032), __byte_perm(p1, p0, 0x7610), __byte_perm(p1, 0, 0x1032));
        st4(wa + 16, __byte_perm(p2, p1, 0x7610), __byte_perm(p2, 0, 0x1032), __byte_perm(p3, p2, 0x7610), __byte_perm(p3, 0, 0x1032));
        const float2 q = lds64(kd + 512 + lane * 8);
        const uint32_t q0 = __float_as_uint(q.x), q1 = __float_as_uint(q.y), q2 = ldsu(kd + 520 + lane * 8), k255 = ldsu(kd + 508);
        st4(wa + 1024, lane ? __byte_perm(q0, 0, 0x1010) : __byte_perm(q0, k255, 0x7610), __byte_perm(q0, 0, 0x1010), __byte_perm(q0, 0, 0x1032), __byte_perm(q1, q0, 0x7610));
        st4(wa + 1040, __byte_perm(q1, 0, 0x1010), __byte_perm(q1, 0, 0x1010), __byte_perm(q1, 0, 0x1032), __byte_perm(q2, q1, 0x7610));
        const uint32_t k512 = lane == 4 ? lds16(kd + 768) : 0;
        if (lane < 16) st4(ch + S4_WD + (lane < 4 ? 0 : 2048) + lane * 16, k512 * 0x10001u, k512 * 0x10001u, k512 * 0x10001u, k512 << 16);
        const float2 c = lds64(kd + 768 + lane * 8), d = lds64(kd + 760 + lane * 8);
        const uint32_t c0 = __float_as_uint(c.x), c1 = __float_as_uint(c.y), c2 = ldsu(kd + 776 + lane * 8);
        const uint32_t d0 = lane ? __float_as_uint(d.x) : 0, d1 = lane ? __float_as_uint(d.y) : 0, d2 = lane ? c0 : 0;
        st4(ch + S4_T2 + 256 + lane * 16, __byte_perm(c0, d0, 0x7632), __byte_perm(c1, d1, 0x5410), __byte_perm(c1, d1, 0x7632), __byte_perm(c2, d2, 0x5410));
        const uint32_t m = lane == 31 ? 0xFFFF0000u : 0;
        st4(ch + S4_T2 + (lane < 16 ? lane : lane == 31 ? 48 : lane + 33) * 16, c0 & m, (c1 << 16) & m, c1 & m, (c2 << 16) & m);
        const float2 e = lds64(kd + 1024 + lane * 8);
        const uint32_t e0 = __float_as_uint(e.x), e1 = __float_as_uint(e.y), e2 = ldsu(kd + 1032 + lane * 8), em = ldsu(kd + 1020 + lane * 8);
        st4(ch + S4_T3 + 128 + lane * 16, __byte_perm(e0, lane ? em : 0, 0x7632), __byte_perm(e1, lane ? e0 : 0, 0x5410), __byte_perm(e1, e0, 0x7632), __byte_perm(e2, e1, 0x5410));
        if (lane < 8) st4(ch + S4_T3 + lane * 16, 0, 0, 0, 0);
    }
    bar_sync(2, 256);
    ST(item, cw, 1);
    const uint32_t z = ldsu(ch);
    float acc[8][2][4];
#pragma unroll
    for (int j = 0; j < 16; j++) acc[j >> 1][j & 1][0] = acc[j >> 1][j & 1][1] = acc[j >> 1][j & 1][2] = acc[j >> 1][j & 1][3] = 0.f;
#pragma unroll 1
    for (int r = 1; r <= 4; r++) s4_windows<2, 3, 16>(acc, ch, ch + S4_T2 + (gt - 16) * 16 + 4 * r - 4, 4 * r, 2 - (r & 1), lane, z);
    ST(item, cw, 2);
#pragma unroll 1
    for (int r = 1; r <= 2; r++) s4_windows<4, 4, 8>(acc, ch, ch + S4_T3 + (gt - 48) * 8 + 4 * r - 4, 8 * r, 2 + r, lane, z);
    ST(item, cw, 3);
    const uint32_t ua = ch + (lane >> 4) * S4_HALF + (16 + (lane & 15)) * 16, wd = ch + S4_WD + 64 + gt * 4;
#pragma unroll 1
    for (int q = 0; q < 2; q++) {
        uint32_t b0[4], b1[4];
        s4_words(b0, wd + (q + 32) * 64);
#pragma unroll
        for (int j = 0; j < 4; j++) {
            const int x = 16 * q + gt + (j == 1 ? -8 : j == 2 ? 8 : 0) - 3;
            b1[j] = addz(((unsigned)x < 2u ? k1024 : 0u) | ((unsigned)(x - 1) < 2u ? k1024 << 16 : 0u), z);
        }
        s4_dense<2, 4>(acc, ua - q * 16, b0, b1);
    }
    {
        uint32_t b0[4], b1[4], c0[4], c1[4];
        s4_words(b0, wd); s4_words(b1, wd + 1024);
#pragma unroll 1
        for (int q = 0; q < 16; q += 2) {
            s4_words(c0, wd + q * 64 + 64); s4_words(c1, wd + q * 64 + 64 + 1024);
            s4_dense<0, 1>(acc, ua - q * 16, b0, b1);
            s4_words(b0, wd + q * 64 + 128); s4_words(b1, wd + q * 64 + 128 + 1024);
            s4_dense<0, 1>(acc, ua - q * 16 - 16, c0, c1);
            if (q == S4REL && lane == 0) { mbar_arrive(empty); mbar_arrive(empty + 8); }
        }
    }
    ST(item, cw, 4);
    mbar_wait(empty + 72, stgpar);
    if (lane == 0) asm volatile("cp.async.bulk.wait_group.read 0;" ::: "memory");
    __syncwarp();
#pragma unroll
    for (int I = 0; I < 8; I++) {
        uint32_t u[4];
        ldsm4(u, ua + I * 256);
#pragma unroll
        for (int j = 0; j < 4; j++) {
            const uint32_t y = pack_bf16(acc[I][j >> 1][2 * (j & 1)], acc[I][j >> 1][2 * (j & 1) + 1]);
            const __nv_bfloat162 r = __hadd2_rn(*(const __nv_bfloat162*)&y, __hmul2_rn(*(const __nv_bfloat162*)&u[j], dk));
            u[j] = *(const uint32_t*)&r;
        }
        stsm4(ua + I * 256, u[0], u[1], u[2], u[3]);
    }
    bar_sync(2, 256);
    uint32_t y[8][4];
#pragma unroll
    for (int i = 0; i < 8; i++) ldsm4t(y[i], tch + i * 32);
    if (cw < S4DIR && mbar_test(nbar, npar) && ldsu(nslot) == (IT_END << 16)) {
        uint32_t* const dst = (uint32_t*)(out + (size_t)(cw * 256 + (lane >> 2)) * (2 * DM) + DM + item * 8) + (lane & 3);
#pragma unroll
        for (int i = 0; i < 32; i++) dst[i * 8 * DM] = y[i >> 2][i & 3];
        return;
    }
#pragma unroll
    for (int i = 0; i < 8; i++) stsm4(sb + G_STG + cw * 4096 + i * 512 + lane * 16, y[i][0], y[i][1], y[i][2], y[i][3]);
    asm volatile("fence.proxy.async.shared::cta;" ::: "memory");
    __syncwarp();
    if (lane == 0) {
        mbar_arrive(empty + 16); mbar_arrive(empty + 24);
        tma2d_store(my, sb + G_STG + cw * 4096, DM + item * 8, cw * 256);
        asm volatile("cp.async.bulk.commit_group;" ::: "memory");
    }
    ST(item, cw, 5);
}

__global__ void __launch_bounds__(384, 1)
worker_kernel(const __grid_constant__ CUtensorMap mx, const __grid_constant__ CUtensorMap mq, const __grid_constant__ CUtensorMap mk,
              const __grid_constant__ CUtensorMap mv, const __grid_constant__ CUtensorMap mo,
              const __grid_constant__ CUtensorMap mout, const __grid_constant__ CUtensorMap mu, const __grid_constant__ CUtensorMap my,
              const __grid_constant__ CUtensorMap mkx, const __grid_constant__ CUtensorMap mvx, const __grid_constant__ CUtensorMap mkm,
              const __grid_constant__ CUtensorMap mvm, const bf16* __restrict__ dsk, bf16* __restrict__ out) {
    extern __shared__ unsigned char smem_raw[];
    const uint32_t sb = (smem_u32(smem_raw) + 1023) & ~1023u;
    const uint32_t full = sb + G_BAR, empty = full + 32, ifull = full + 64, iempty = full + 80, islot = full + 96, stgbar = full + 104, sigbar = full + 112, sigslot = full + 120;
    const int tid = threadIdx.x, wg = tid >> 7, lane = tid & 31;
    if (TMP && tid >= 64 && tid < 76) {
        const CUtensorMap* maps[12] = {&mx, &mq, &mk, &mv, &mo, &mout, &mu, &my, &mkx, &mvx, &mkm, &mvm};
        const CUtensorMap* m = maps[0];
#pragma unroll
        for (int j = 1; j < 12; j++) if (tid - 64 == j) m = maps[j];
        asm volatile("prefetch.tensormap [%0];" ::"l"(m) : "memory");
    }
    int q0 = blockIdx.x;
    const int wide0 = q0 - ((int)gridDim.x - O_WIDE * 4);
    if (tid == 0) {
        if (q0 >= 32 && wide0 < 0) q0 = 32 + atomicAdd(g_ctr + C_NEXT, 1);
        for (int i = 0; i < 6; i++) { mbar_init(full + n6_bar(i), 1); mbar_init(empty + n6_bar(i), 8); }
        for (int i = 0; i < 2; i++) { mbar_init(ifull + 8 * i, 1); mbar_init(iempty + 8 * i, 8); }
        mbar_init(sigbar, 8); mbar_init(stgbar, 1);
        asm volatile("fence.proxy.async.shared::cta;" ::: "memory");
    }
    __syncthreads();
    if (wg == 0) {
        reg_dec<40>();
        if (tid >= 32 && tid < 64) {
            for (int n = 0;; n++) {
                mbar_wait_long(sigbar, n & 1);
                int item; asm volatile("ld.shared.u32 %0, [%1];" : "=r"(item) : "r"(sigslot + 4 * (n & 1)) : "memory");
                const int type = item >> 16, b = (item >> 8) & 255, i = item & 255;
                if (type == IT_END) break;
                if (type == IT_QA) {
                    if (lane == 0) {
                        for (int j = 0; j < 8; j++) {
                            const uint32_t src = sb + (j >= 4 ? G_STG + (j & 1) * 16384 : 3 * G_STAGE + (j & 1) * 20480) + ((j >> 1) & 1) * 8192;
                            asm volatile("cp.async.bulk.global.shared::cta.bulk_group [%0], [%1], 8192;"
                                ::"l"(g_ox + (size_t)(b * 64 + i * 4 + ((j >> 1) ^ 2)) * 8192 + (j & 1) * 4096), "r"(src) : "memory");
                            if ((j & 3) == 3) asm volatile("cp.async.bulk.commit_group;" ::: "memory");
                        }
                        asm volatile("cp.async.bulk.wait_group.read 1;" ::: "memory");
                        asm volatile("mbarrier.arrive.shared.b64 _, [%0], 8;" ::"r"(empty + 24) : "memory");
                        asm volatile("cp.async.bulk.wait_group 0;" ::: "memory");
                        mbar_arrive(stgbar);
                        asm volatile("fence.proxy.async.global;" ::: "memory");
                    }
                    __syncwarp();
                }
                if (type == IT_KV) { if (lane < 6) red_release(g_kvf + ((i & 15) * 6 + lane) * 16 + b, 1); }
                else if (lane == 0) red_release(g_ctr + C_QA_DONE + b, 1 << i);
            }
        } else if (tid < 32) {
            int it = 0;
            if (!KVN) asm volatile("griddepcontrol.wait;" ::: "memory");
            for (int n = 0;; n++) {
                int item = 0;
                if (lane == 0) {
                    if (n) q0 = 32 + atomicAdd(g_ctr + C_NEXT, 1);
                    item = n == 0 && wide0 >= 0 ? (IT_O << 16) | ((wide0 >> 2) << 8) | (wide0 & 3) : queue_item(q0);
                }
                item = __shfl_sync(0xffffffffu, item, 0);
                if (lane == 0) {
                    mbar_wait(iempty + 8 * (n & 1), ((n >> 1) & 1) ^ 1);
                    asm volatile("st.shared.u32 [%0], %1;" ::"r"(islot + 4 * (n & 1)), "r"(item) : "memory");
                    mbar_arrive(ifull + 8 * (n & 1));
                    const int type = item >> 16, b = (item >> 8) & 255, i = item & 255;
                    if (type == IT_QA || type == IT_KV) {
                        const CUtensorMap* mw = type == IT_QA ? &mq : i < 16 ? &mk : &mv;
                        bool ready = false;
                        for (int kb = 0; kb < 16; kb++, it++) {
                            const int st = it & 3;
                            mbar_wait(empty + 8 * st, ((it >> 2) & 1) ^ 1);
                            mbar_expect(full + 8 * st, G_STAGE);
                            const uint32_t a = sb + st * G_STAGE;
                            tma2d(a, &mx, kb * 64, b * 128, full + 8 * st);
                            tma3d(a + 16384, mw, 0, kb * 64, (i & 15) * 4, full + 8 * st);
                            tma3d(a + 32768, mw, 0, kb * 64, (i & 15) * 4 + 2, full + 8 * st);
                            if (type == IT_QA && kb == 3) ready = ld_acq(g_ctr + C_CHAIN + b) >= 96;
                            if (type == IT_QA && kb >= 3 && kb < 11) {
                                const size_t sh = (b * 4 + ((kb - 3) & 3)) * NH + i * 2;
                                asm volatile("cp.async.bulk.prefetch.L2.global [%0], 16384;" ::"l"((kb >= 7 ? g_vx : g_kx) + sh * 4096) : "memory");
                                if (ready) asm volatile("cp.async.bulk.prefetch.L2.global [%0], 4096;" ::"l"((kb >= 7 ? g_vm : g_km) + sh * 1024) : "memory");
                            }
                        }
                    }
                    if (type == IT_QA) {
                        wait_ctr(g_ctr + C_CHAIN + b, 96);
                        asm volatile("fence.proxy.async.global;" ::: "memory");
                        for (int st = 0; st < 4; st++, it++) {
                            mbar_wait(empty + 8 * st, ((it >> 2) & 1) ^ 1);
                            mbar_expect(full + 8 * st, 4 * 10240);
                            for (int g2 = 0; g2 < 2; g2++) {
                                tma3d(sb + st * G_STAGE + g2 * 20480, st < 2 ? &mkx : &mvx, 0, b * 4 + g2 * 2, (i * 2 + (st & 1)) * 16, full + 8 * st);
                                tma3d(sb + st * G_STAGE + g2 * 20480 + 16384, st < 2 ? &mkm : &mvm, 0, b * 4 + g2 * 2, (i * 2 + (st & 1)) * 16, full + 8 * st);
                            }
                        }
                    } else if (type == IT_O) {
                        const bool wide = b < O_WIDE;
                        int done = 0;
                        const int ns = wide ? 4 : 6;
                        for (int kb = 0, st = 0, r = 0; kb < 64; kb++) {
                            const uint32_t bo = n6_bar(st);
                            mbar_wait(empty + bo, (((st < 4 ? it >> 2 : 0) + r) & 1) ^ 1);
                            mbar_expect(full + bo, wide ? G_STAGE : 32768);
                            tma3d(sb + n6_b(st), &mo, 0, kb * 64, wide ? i * 4 : i * 2, full + bo);
                            if (wide) tma3d(sb + n6_b(st) + 16384, &mo, 0, kb * 64, i * 4 + 2, full + bo);
                            if (!(done >> (kb >> 2) & 1)) {
                                for (int sp = 0; sp < (1 << 20) && !((done = ld_acq(g_ctr + C_QA_DONE + b)) >> (kb >> 2) & 1); sp++) __nanosleep(64);
                                asm volatile("fence.proxy.async.global;" ::: "memory");
                            }
                            bulk_load(sb + n6_a(st), g_ox + (size_t)(b * 64 + kb) * 8192, 16384, full + bo);
                            if (++st == ns) { st = 0; r++; }
                        }
                        it += wide ? 64 : 44;
                    } else if (type == IT_S4) {
                        wait_ctr(g_ctr + C_CHAIN, 96);
                        asm volatile("fence.proxy.async.global;" ::: "memory");
                        mbar_wait(empty, ((it >> 2) & 1) ^ 1);
                        mbar_expect(full, 32768 + 12288);
                        bulk_load(sb + S4_KD, g_kd + i * 8 * 768, 12288, full);
                        for (int j = 0; j < 8; j++) tma2d(sb + j * 4096, &mu, i * 8, j * 256, full);
                        for (int st = 1; st < 4; st++) { mbar_wait(empty + 8 * st, ((it >> 2) & 1) ^ 1); mbar_arrive(full + 8 * st); }
                        it += 4;
                        mbar_wait_long(empty, ((it >> 2) & 1) ^ 1);
                    }
                }
                __syncwarp();
                if (item >> 16 == IT_END) break;
            }
            asm volatile("griddepcontrol.wait;" ::: "memory");
        }
    } else {
        reg_inc<232>();
        const int wu = __shfl_sync(0xffffffffu, tid >> 5, 0);
        const int wgi = (wu >> 2) - 1, wi = wu & 3;
        int it = 0, nqa = 0, nsig = 0, n = 0, item;
        auto next_item = [&]() {
            mbar_wait_long(ifull + 8 * (n & 1), (n >> 1) & 1);
            asm volatile("ld.shared.u32 %0, [%1];" : "=r"(item) : "r"(islot + 4 * (n & 1)) : "memory");
            __syncwarp();
            if (lane == 0) mbar_arrive(iempty + 8 * (n & 1));
        };
        auto signal = [&](int what) {
            if (tid == 128) asm volatile("st.shared.u32 [%0], %1;" ::"r"(sigslot + 4 * (nsig & 1)), "r"(what) : "memory");
            __syncwarp();
            if (lane == 0) mbar_arrive(sigbar);
            nsig++;
        };
        next_item();
        if (item >> 16 == IT_KV) {
            float acc[128];
            uint32_t pk[64];
            uint32_t* dst = nullptr;
            int prev = 0;
            do {
                WLOG(0);
#pragma unroll
                for (int kb = 0; kb < 16; kb++, it++) {
                    const int st = kb & 3;
                    mbar_wait(full + 8 * st, (it >> 2) & 1);
                    const uint64_t da = mkdesc(sb + st * G_STAGE + wgi * 8192, 16, 1024, 1);
                    const uint64_t db = mkdesc(sb + st * G_STAGE + 16384, 8192, 1024, 1);
                    wg_fence();
#pragma unroll
                    for (int k = 0; k < 4; k++) wgmma256(acc, da + k * 2, db + k * 128, kb | k);
                    wg_commit();
                    if (n <= KVI) {
                        if (kb < KVF && dst) {
#pragma unroll
                            for (int j = kb * (64 / KVF); j < (kb + 1) * (64 / KVF); j++) st_out(dst + (j >> 1) * 128 + (j & 1) * 32, pk[j]);
                            if (kb == KVF - 1) signal(prev);
                        }
                    } else if (kb < KVS) {
#pragma unroll
                        for (int j = kb * (64 / KVS); j < (kb + 1) * (64 / KVS); j++) st_out(dst + (j >> 1) * 128 + (j & 1) * 32, pk[j]);
                        if (kb == KVS - 1) signal(prev);
                    }
                    if (kb > 0) {
                        wg_wait<1>();
                        if (lane == 0) mbar_arrive(empty + 8 * ((kb - 1) & 3));
                    }
                }
                wg_wait<0>();
                if (lane == 0) mbar_arrive(empty + 8 * 3);
#pragma unroll
                for (int j = 0; j < 64; j++) pk[j] = pack_bf16(acc[2 * j], acc[2 * j + 1]);
                const int row = ((item >> 8) & 255) * 128 + wgi * 64 + wi * 16, nt = item & 255;
                dst = (uint32_t*)(nt < 16 ? g_kx : g_vx) + (size_t)((row >> 5) * 512 + (nt & 15) * 32) * 128 + (row & 31) * 4 + lane;
                prev = item;
                WLOG(1);
                n++;
                next_item();
            } while (item >> 16 == IT_KV);
            if (dst) {
#pragma unroll
                for (int j = 0; j < 64; j++) dst[(j >> 1) * 128 + (j & 1) * 32] = pk[j];
                signal(prev);
            }
        }
        for (;; n++, next_item()) {
            const int type = item >> 16, b = (item >> 8) & 255, i = item & 255;
            const int lane = (tid & 31) + (item >> 24), wgi = (wu >> 2) - 1 + __shfl_sync(0xffffffffu, item >> 24, 0), wi = wu & 3;
            WLOG(0);
            if (type == IT_QA) {
                float acc[128];
                ST(sid, cw, 0);
                ST(sid, cw, 1);
                mainloop<256, 16, false>(acc, sb, wgi, full, empty, it, lane == 0);
                ST(sid, cw, 2);
                uint32_t q0[32], q1[32];
#pragma unroll
                for (int j = 0; j < 32; j++) q0[j] = pack_bf16(acc[2 * j], acc[2 * j + 1]);
                const uint32_t par = (it >> 2) & 1, so = sb + wgi * 20480;
                float sx[2][32] = {}, sm[2][8] = {};
                uint32_t p[2][20];
                mbar_wait_long(full, par);
                ST(sid, cw, 3);
                if (PING && wgi == 0) bar_sync(5, 256);
                attn_scores(sx[0], sm[0], q0, so);
                ST(sid, cw, 7);
#pragma unroll
                for (int j = 0; j < 32; j++) asm volatile("cvt.rn.bf16x2.f32 %0, %1, %2;" : "=r"(q1[j]) : "f"(acc[65 + 2 * j]), "f"(acc[64 + 2 * j]));
                mbar_wait(full + 8, par);
                attn_scores(sx[1], sm[1], q1, so + G_STAGE);
                if (PING && wgi == 1) bar_arrive(5, 256);
                if (lane == 0) asm volatile("cp.async.bulk.wait_group.read 0;" ::: "memory");
                mbar_wait(stgbar, (nqa++ & 1) ^ 1);
                bar_sync(3 + wgi, 128);
                float o0[64] = {}, o1[64] = {};
                wg_wait<0>();
                ST(sid, cw, 9);
                if (lane == 0) { mbar_arrive(empty); mbar_arrive(empty + 8); }
                if (wi & 1) attn_softmax<true>(p, sx, sm, wi >= 2, lane);
                else attn_softmax<false>(p, sx, sm, wi >= 2, lane);
                ST(sid, cw, 10);
                mbar_wait(full + 16, par);
                attn_pv(o0, p[0], so + 2 * G_STAGE);
                mbar_wait(full + 24, par);
                attn_pv(o1, p[1], so + 3 * G_STAGE);
                wg_wait<1>();
                if (lane == 0) mbar_arrive(empty + 16);
                ST(sid, cw, 5);
                const uint32_t da = (wi * 2 + ((lane >> 3) & 1)) * 1024 + (lane >> 4) * 128 + (lane & 7) * 16;
                attn_stage(o0, sb + G_STG + wgi * 16384 + da);
                wg_wait<0>();
                bar_sync(3 + wgi, 128);
                attn_stage(o1, so + 3 * G_STAGE + da);
                asm volatile("fence.proxy.async.shared::cta;" ::: "memory");
                ST(sid, cw, 6);
                signal(item);
                it += 4;
            } else if (type == IT_O) {
                ST(b * 8 + i, wgi * 4 + wi, 8);
                mbar_wait_long(full, (it >> 2) & 1);
                ST(b * 8 + i, wgi * 4 + wi, 9);
                if (b < O_WIDE) o_item<256>(sb, wgi, wi, lane, full, empty, it, &mout, b * 128, i * 256, (nqa & 1) ^ 1);
                else o_item<128>(sb, wgi, wi, lane, full, empty, it, &mout, b * 128, i * 128, (nqa & 1) ^ 1);
            } else if (type == IT_S4) {
                mbar_wait_long(full, (it >> 2) & 1);
                mbar_wait(full + 24, (it >> 2) & 1);
                s4_item(sb, wgi * 4 + wi, lane, i, dsk, empty, &my, (nqa & 1) ^ 1, out, ifull + 8 * ((n + 1) & 1), ((n + 1) >> 1) & 1, islot + 4 * ((n + 1) & 1));
                it += 4;
            } else break;
            WLOG(1);
        }
        bar_sync(2, 256);
        signal(item);
        if (lane == 0) asm volatile("cp.async.bulk.wait_group 0;" ::: "memory");
    }
}

typedef CUresult (*EncodeFn)(CUtensorMap*, CUtensorMapDataType, cuuint32_t, void*, const cuuint64_t*, const cuuint64_t*, const cuuint32_t*,
                             const cuuint32_t*, CUtensorMapInterleave, CUtensorMapSwizzle, CUtensorMapL2promotion, CUtensorMapFloatOOBfill);
static EncodeFn get_encode() {
    void* fn = nullptr; cudaDriverEntryPointQueryResult st;
    cudaGetDriverEntryPoint("cuTensorMapEncodeTiled", &fn, cudaEnableDefault, &st);
    return (EncodeFn)fn;
}
static void map_act(EncodeFn enc, CUtensorMap* m, const void* p, int rows, int cols, int boxr) {
    cuuint64_t dim[2] = {(cuuint64_t)cols, (cuuint64_t)rows}, str[1] = {(cuuint64_t)cols * 2};
    cuuint32_t box[2] = {64, (cuuint32_t)boxr}, es[2] = {1, 1};
    enc(m, CU_TENSOR_MAP_DATA_TYPE_BFLOAT16, 2, (void*)p, dim, str, box, es, CU_TENSOR_MAP_INTERLEAVE_NONE, CU_TENSOR_MAP_SWIZZLE_128B,
        CU_TENSOR_MAP_L2_PROMOTION_L2_128B, CU_TENSOR_MAP_FLOAT_OOB_FILL_NONE);
}
static void map_w(EncodeFn enc, CUtensorMap* m, const void* p, int k, int n) {
    cuuint64_t dim[3] = {64, (cuuint64_t)k, (cuuint64_t)n / 64}, str[2] = {(cuuint64_t)n * 2, 128};
    cuuint32_t box[3] = {64, 64, 2}, es[3] = {1, 1, 1};
    enc(m, CU_TENSOR_MAP_DATA_TYPE_BFLOAT16, 3, (void*)p, dim, str, box, es, CU_TENSOR_MAP_INTERLEAVE_NONE, CU_TENSOR_MAP_SWIZZLE_128B,
        CU_TENSOR_MAP_L2_PROMOTION_L2_256B, CU_TENSOR_MAP_FLOAT_OOB_FILL_NONE);
}

static void map_kv(EncodeFn enc, CUtensorMap* m, void* p, int n) {
    cuuint64_t dim[3] = {(cuuint64_t)n, NSEG, 512}, str[2] = {(cuuint64_t)n * 1024, (cuuint64_t)n * 2};
    cuuint32_t box[3] = {(cuuint32_t)n, 2, 16}, es[3] = {1, 1, 1};
    enc(m, CU_TENSOR_MAP_DATA_TYPE_BFLOAT16, 3, p, dim, str, box, es, CU_TENSOR_MAP_INTERLEAVE_NONE, CU_TENSOR_MAP_SWIZZLE_NONE,
        CU_TENSOR_MAP_L2_PROMOTION_NONE, CU_TENSOR_MAP_FLOAT_OOB_FILL_NONE);
}
static void map_box(EncodeFn enc, CUtensorMap* m, const void* p, int rows, int ld, int boxc, int boxr, CUtensorMapSwizzle sw,
                    CUtensorMapL2promotion promo = CU_TENSOR_MAP_L2_PROMOTION_NONE) {
    cuuint64_t dim[2] = {(cuuint64_t)ld, (cuuint64_t)rows}, str[1] = {(cuuint64_t)ld * 2};
    cuuint32_t box[2] = {(cuuint32_t)boxc, (cuuint32_t)boxr}, es[2] = {1, 1};
    enc(m, CU_TENSOR_MAP_DATA_TYPE_BFLOAT16, 2, (void*)p, dim, str, box, es, CU_TENSOR_MAP_INTERLEAVE_NONE, sw,
        promo, CU_TENSOR_MAP_FLOAT_OOB_FILL_NONE);
}

extern "C" void kernel_launch(void* const* d_in, const int* in_sizes, int n_in, void* d_out, int out_size) {
    const bf16* x = (const bf16*)d_in[0];
    const bf16* mem0 = (const bf16*)d_in[1];
    const bf16 *Wq = (const bf16*)d_in[2], *Wk = (const bf16*)d_in[3], *Wv = (const bf16*)d_in[4], *Wo = (const bf16*)d_in[5];
    static EncodeFn enc = nullptr;
    static int nsm = 0;
    static void* kv[4];
    if (!enc) {
        enc = get_encode();
        cudaGetSymbolAddress(&kv[0], g_kx); cudaGetSymbolAddress(&kv[1], g_vx); cudaGetSymbolAddress(&kv[2], g_km); cudaGetSymbolAddress(&kv[3], g_vm);
        cudaDeviceGetAttribute(&nsm, cudaDevAttrMultiProcessorCount, 0);
        cudaFuncSetAttribute(chain_kernel, cudaFuncAttributeMaxDynamicSharedMemorySize, CH_SMEM);
        cudaFuncSetAttribute(worker_kernel, cudaFuncAttributeMaxDynamicSharedMemorySize, G_SMEM);
    }
    CUtensorMap mx, mq, mk, mv, mo, mout, mu, my;
    map_act(enc, &mx, x, S_LEN, DM, 128);
    map_w(enc, &mq, Wq, DM, HD); map_w(enc, &mk, Wk, DM, HD); map_w(enc, &mv, Wv, DM, HD); map_w(enc, &mo, Wo, HD, DM);
    map_box(enc, &mout, d_out, S_LEN, 2 * DM, 64, 16, CU_TENSOR_MAP_SWIZZLE_128B);
    map_box(enc, &mu, d_in[7], S_LEN, DM, 8, 256, CU_TENSOR_MAP_SWIZZLE_NONE, (CUtensorMapL2promotion)PROMU);
    map_box(enc, &my, d_out, S_LEN, 2 * DM, 8, 256, CU_TENSOR_MAP_SWIZZLE_NONE);
    CUtensorMap mkx, mvx, mkm, mvm;
    map_kv(enc, &mkx, kv[0], 256); map_kv(enc, &mvx, kv[1], 256); map_kv(enc, &mkm, kv[2], 64); map_kv(enc, &mvm, kv[3], 64);
    CUtensorMap cq, ck, cv, co;
    map_box(enc, &cq, Wq, DM, HD, 32, 32, CU_TENSOR_MAP_SWIZZLE_64B, (CUtensorMapL2promotion)PROMO); map_box(enc, &ck, Wk, DM, HD, 32, 32, CU_TENSOR_MAP_SWIZZLE_64B, (CUtensorMapL2promotion)PROMO);
    map_box(enc, &cv, Wv, DM, HD, 32, 32, CU_TENSOR_MAP_SWIZZLE_64B, (CUtensorMapL2promotion)PROMO); map_box(enc, &co, Wo, HD, DM, 32, 16, CU_TENSOR_MAP_SWIZZLE_64B, (CUtensorMapL2promotion)PROMO);
    S4Params P = {(const bf16*)d_in[8], (const bf16*)d_in[9], (const bf16*)d_in[10], (const bf16*)d_in[11],
                  (const bf16*)d_in[12], (const bf16*)d_in[13], (const bf16*)d_in[14], (const bf16*)d_in[15]};
    int aware = 1;
    cudaLaunchAttribute at[1];
    at[0].id = cudaLaunchAttributeProgrammaticStreamSerialization;
    at[0].val.programmaticStreamSerializationAllowed = 1;
    cudaLaunchConfig_t cfg = {};
    cfg.stream = cudaStreamPerThread;
    cfg.gridDim = dim3(96); cfg.blockDim = dim3(CH_THREADS); cfg.dynamicSmemBytes = CH_SMEM;
    cudaLaunchKernelEx(&cfg, chain_kernel, cq, ck, cv, co, Wq, Wk, Wv, mem0, P, aware);
    cfg.attrs = at; cfg.numAttrs = 1;
    cfg.gridDim = dim3(nsm); cfg.blockDim = dim3(384); cfg.dynamicSmemBytes = G_SMEM;
    cudaLaunchKernelEx(&cfg, worker_kernel, mx, mq, mk, mv, mo, mout, mu, my, mkx, mvx, mkm, mvm, P.dsk, (bf16*)d_out);
}
```

```cpp
#include <cuda.h>
#include <cuda_runtime.h>
#include <cuda_bf16.h>
#include <stdint.h>
#include <stdio.h>
#include <string.h>

typedef __nv_bfloat16 bf16;

constexpr int S_LEN = 2048, DM = 1024, NH = 32, DH = 128, HD = 4096, NSEG = 64;
constexpr uint32_t SENT = 0xFFFFFFFFu;
constexpr int SPIN_LIMIT = 1 << 18;
#define REALL 0

__device__ __align__(1024) bf16 g_kx[S_LEN * HD];
__device__ __align__(1024) bf16 g_vx[S_LEN * HD];
__device__ __align__(1024) bf16 g_ox[S_LEN * HD];
__device__ __align__(1024) bf16 g_km[NSEG * NH * 8 * DH];
__device__ __align__(1024) bf16 g_vm[NSEG * NH * 8 * DH];
__device__ __align__(1024) bf16 g_kd[DM * 768 + 8192];
__device__ __align__(1024) char g_ring[2 << 20];
__device__ int g_kvf[96 * 16];
constexpr int C_NEXT = 0, C_CHAIN = 32, C_QA_DONE = 64, N_CTR = 96;
__device__ int g_ctr[N_CTR];

__device__ __forceinline__ uint32_t smem_u32(const void* p) { return (uint32_t)__cvta_generic_to_shared(p); }
__device__ __forceinline__ uint32_t clk() { uint32_t c; asm volatile("mov.u32 %0, %%clock;" : "=r"(c)::"memory"); return c; }
__device__ __forceinline__ uint32_t pack_bf16(float lo, float hi) {
    uint32_t r; asm("cvt.rn.bf16x2.f32 %0, %1, %2;" : "=r"(r) : "f"(hi), "f"(lo)); return r;
}
__device__ __forceinline__ uint32_t movm(uint32_t a) {
    uint32_t d; asm volatile("movmatrix.sync.aligned.m8n8.trans.b16 %0, %1;" : "=r"(d) : "r"(a)); return d;
}
__device__ __forceinline__ void mma16(float (&d)[4], const uint32_t (&a)[4], uint32_t b0, uint32_t b1) {
    asm volatile("mma.sync.aligned.m16n8k16.row.col.f32.bf16.bf16.f32 {%0,%1,%2,%3}, {%4,%5,%6,%7}, {%8,%9}, {%0,%1,%2,%3};"
        : "+f"(d[0]), "+f"(d[1]), "+f"(d[2]), "+f"(d[3]) : "r"(a[0]), "r"(a[1]), "r"(a[2]), "r"(a[3]), "r"(b0), "r"(b1));
}
__device__ __forceinline__ void mma16z(float (&d)[4], const uint32_t (&a)[4], uint32_t b0, uint32_t b1) {
    asm volatile("mma.sync.aligned.m16n8k16.row.col.f32.bf16.bf16.f32 {%0,%1,%2,%3}, {%4,%5,%6,%7}, {%8,%9}, {%10,%10,%10,%10};"
        : "=f"(d[0]), "=f"(d[1]), "=f"(d[2]), "=f"(d[3]) : "r"(a[0]), "r"(a[1]), "r"(a[2]), "r"(a[3]), "r"(b0), "r"(b1), "f"(0.f));
}
__device__ __forceinline__ void mma8z(float (&d)[4], uint32_t a0, uint32_t a1, uint32_t b0) {
    asm volatile("mma.sync.aligned.m16n8k8.row.col.f32.bf16.bf16.f32 {%0,%1,%2,%3}, {%4,%5}, {%6}, {%7,%7,%7,%7};"
        : "=f"(d[0]), "=f"(d[1]), "=f"(d[2]), "=f"(d[3]) : "r"(a0), "r"(a1), "r"(b0), "f"(0.f));
}
__device__ __forceinline__ void ldsm4t(uint32_t (&r)[4], uint32_t addr) {
    asm volatile("ldmatrix.sync.aligned.m8n8.x4.trans.shared.b16 {%0,%1,%2,%3}, [%4];"
        : "=r"(r[0]), "=r"(r[1]), "=r"(r[2]), "=r"(r[3]) : "r"(addr) : "memory");
}
__device__ __forceinline__ void ldsm4(uint32_t (&r)[4], uint32_t addr) {
    asm volatile("ldmatrix.sync.aligned.m8n8.x4.shared.b16 {%0,%1,%2,%3}, [%4];"
        : "=r"(r[0]), "=r"(r[1]), "=r"(r[2]), "=r"(r[3]) : "r"(addr) : "memory");
}
__device__ __forceinline__ float lds32(uint32_t a) {
    float v; asm volatile("ld.shared.f32 %0, [%1];" : "=f"(v) : "r"(a) : "memory"); return v;
}
__device__ __forceinline__ void st_async1(uint32_t dst, float v, uint32_t bar) {
    asm volatile("st.async.shared::cluster.mbarrier::complete_tx::bytes.f32 [%0], %1, [%2];" ::"r"(dst), "f"(v), "r"(bar) : "memory");
}
__device__ __forceinline__ void st_async2(uint32_t dst, float x, float y, uint32_t bar) {
    asm volatile("st.async.shared::cluster.mbarrier::complete_tx::bytes.v2.f32 [%0], {%1,%2}, [%3];" ::"r"(dst), "f"(x), "f"(y), "r"(bar) : "memory");
}
__device__ __forceinline__ void mma8(float (&d)[4], uint32_t a0, uint32_t a1, uint32_t b0) {
    asm volatile("mma.sync.aligned.m16n8k8.row.col.f32.bf16.bf16.f32 {%0,%1,%2,%3}, {%4,%5}, {%6}, {%0,%1,%2,%3};"
        : "+f"(d[0]), "+f"(d[1]), "+f"(d[2]), "+f"(d[3]) : "r"(a0), "r"(a1), "r"(b0));
}
__device__ __forceinline__ void cp16(uint32_t dst, const void* src) {
    asm volatile("cp.async.cg.shared.global [%0], [%1], 16;" ::"r"(dst), "l"(src) : "memory");
}
__device__ __forceinline__ void sts128(uint32_t a, const float (&v)[4]) {
    asm volatile("st.shared.v4.f32 [%0], {%1,%2,%3,%4};" ::"r"(a), "f"(v[0]), "f"(v[1]), "f"(v[2]), "f"(v[3]) : "memory");
}
__device__ __forceinline__ float4 lds128(uint32_t a) {
    float4 v; asm volatile("ld.shared.v4.f32 {%0,%1,%2,%3}, [%4];" : "=f"(v.x), "=f"(v.y), "=f"(v.z), "=f"(v.w) : "r"(a) : "memory"); return v;
}
__device__ __forceinline__ void sts64(uint32_t a, float x, float y) {
    asm volatile("st.shared.v2.f32 [%0], {%1,%2};" ::"r"(a), "f"(x), "f"(y) : "memory");
}
__device__ __forceinline__ float2 lds64(uint32_t a) {
    float2 v; asm volatile("ld.shared.v2.f32 {%0,%1}, [%2];" : "=f"(v.x), "=f"(v.y) : "r"(a) : "memory"); return v;
}
__device__ __forceinline__ void bar_sync(int id, int n) { asm volatile("bar.sync %0, %1;" ::"r"(id), "r"(n) : "memory"); }
__device__ __forceinline__ void bar_arrive(int id, int n) { asm volatile("bar.arrive %0, %1;" ::"r"(id), "r"(n) : "memory"); }
__device__ __forceinline__ uint32_t mapa(uint32_t a, uint32_t r) {
    uint32_t o; asm("mapa.shared::cluster.u32 %0, %1, %2;" : "=r"(o) : "r"(a), "r"(r)); return o;
}
__device__ __forceinline__ void st_async4(uint32_t dst, float4 v, uint32_t bar) {
    asm volatile("st.async.shared::cluster.mbarrier::complete_tx::bytes.v4.f32 [%0], {%1,%2,%3,%4}, [%5];"
        ::"r"(dst), "f"(v.x), "f"(v.y), "f"(v.z), "f"(v.w), "r"(bar) : "memory");
}
__device__ __forceinline__ void mbar_init(uint32_t bar, int n) { asm volatile("mbarrier.init.shared.b64 [%0], %1;" ::"r"(bar), "r"(n) : "memory"); }
__device__ __forceinline__ void mbar_expect(uint32_t bar, int bytes) {
    asm volatile("mbarrier.arrive.expect_tx.shared.b64 _, [%0], %1;" ::"r"(bar), "r"(bytes) : "memory");
}
__device__ __forceinline__ void bulk_load(uint32_t dst, const void* src, int bytes, uint32_t bar) {
    asm volatile("cp.async.bulk.shared::cluster.global.mbarrier::complete_tx::bytes [%0], [%1], %2, [%3];"
        ::"r"(dst), "l"(src), "r"(bytes), "r"(bar) : "memory");
}
__device__ __forceinline__ bool mbar_try(uint32_t bar, uint32_t par) {
    uint32_t ok;
    asm volatile("{.reg .pred p; mbarrier.try_wait.parity.shared::cta.b64 p, [%1], %2; selp.u32 %0, 1, 0, p;}"
        : "=r"(ok) : "r"(bar), "r"(par) : "memory");
    return ok;
}
__device__ __forceinline__ bool mbar_test(uint32_t bar, uint32_t par) {
    uint32_t ok;
    asm volatile("{.reg .pred p; mbarrier.test_wait.parity.shared::cta.b64 p, [%1], %2; selp.u32 %0, 1, 0, p;}"
        : "=r"(ok) : "r"(bar), "r"(par) : "memory");
    return ok;
}
__device__ __forceinline__ int ld_acq(const int* p) { int v; asm volatile("ld.acquire.gpu.global.s32 %0, [%1];" : "=r"(v) : "l"(p) : "memory"); return v; }
__device__ __forceinline__ void red_release(int* p, int v) { asm volatile("red.release.gpu.global.add.s32 [%0], %1;" ::"l"(p), "r"(v) : "memory"); }
__device__ __forceinline__ void fence_gpu() { asm volatile("fence.acq_rel.gpu;" ::: "memory"); }
__device__ __forceinline__ void wait_ctr(const int* p, int n) {
#pragma unroll 1
    for (int it = 0; it < (1 << 20) && ld_acq(p) < n; it++) __nanosleep(64);
}
__device__ __forceinline__ void mbar_wait(uint32_t bar, uint32_t par) {
    if (!mbar_try(bar, par)) {
#pragma unroll 1
        for (int it = 0; it < SPIN_LIMIT && !mbar_try(bar, par); it++) {}
    }
}
__device__ __forceinline__ void mbar_wait_long(uint32_t bar, uint32_t par) {
    for (int it = 0; it < (1 << 24) && !mbar_try(bar, par); it++) {}
}
__device__ __forceinline__ float4 add4(float4 a, float4 b) { return make_float4(a.x + b.x, a.y + b.y, a.z + b.z, a.w + b.w); }
__device__ __forceinline__ float ex2(float x) { float y; asm("ex2.approx.ftz.f32 %0, %1;" : "=f"(y) : "f"(x)); return y; }

__device__ __forceinline__ void wgmma256(float (&d)[128], uint64_t da, uint64_t db, int acc) {
    asm volatile("{.reg .pred p; setp.ne.b32 p, %130, 0;\n"
        "wgmma.mma_async.sync.aligned.m64n256k16.f32.bf16.bf16 {"
        "%0,%1,%2,%3,%4,%5,%6,%7,%8,%9,%10,%11,%12,%13,%14,%15,"
        "%16,%17,%18,%19,%20,%21,%22,%23,%24,%25,%26,%27,%28,%29,%30,%31,"
        "%32,%33,%34,%35,%36,%37,%38,%39,%40,%41,%42,%43,%44,%45,%46,%47,"
        "%48,%49,%50,%51,%52,%53,%54,%55,%56,%57,%58,%59,%60,%61,%62,%63,"
        "%64,%65,%66,%67,%68,%69,%70,%71,%72,%73,%74,%75,%76,%77,%78,%79,"
        "%80,%81,%82,%83,%84,%85,%86,%87,%88,%89,%90,%91,%92,%93,%94,%95,"
        "%96,%97,%98,%99,%100,%101,%102,%103,%104,%105,%106,%107,%108,%109,%110,%111,"
        "%112,%113,%114,%115,%116,%117,%118,%119,%120,%121,%122,%123,%124,%125,%126,%127"
        "}, %128, %129, p, 1, 1, 0, 1;}"
        : "+f"(d[0]), "+f"(d[1]), "+f"(d[2]), "+f"(d[3]), "+f"(d[4]), "+f"(d[5]), "+f"(d[6]), "+f"(d[7]), "+f"(d[8]), "+f"(d[9]), "+f"(d[10]), "+f"(d[11]), "+f"(d[12]), "+f"(d[13]), "+f"(d[14]), "+f"(d[15]), "+f"(d[16]), "+f"(d[17]), "+f"(d[18]), "+f"(d[19]), "+f"(d[20]), "+f"(d[21]), "+f"(d[22]), "+f"(d[23]), "+f"(d[24]), "+f"(d[25]), "+f"(d[26]), "+f"(d[27]), "+f"(d[28]), "+f"(d[29]), "+f"(d[30]), "+f"(d[31]), "+f"(d[32]), "+f"(d[33]), "+f"(d[34]), "+f"(d[35]), "+f"(d[36]), "+f"(d[37]), "+f"(d[38]), "+f"(d[39]), "+f"(d[40]), "+f"(d[41]), "+f"(d[42]), "+f"(d[43]), "+f"(d[44]), "+f"(d[45]), "+f"(d[46]), "+f"(d[47]), "+f"(d[48]), "+f"(d[49]), "+f"(d[50]), "+f"(d[51]), "+f"(d[52]), "+f"(d[53]), "+f"(d[54]), "+f"(d[55]), "+f"(d[56]), "+f"(d[57]), "+f"(d[58]), "+f"(d[59]), "+f"(d[60]), "+f"(d[61]), "+f"(d[62]), "+f"(d[63]), "+f"(d[64]), "+f"(d[65]), "+f"(d[66]), "+f"(d[67]), "+f"(d[68]), "+f"(d[69]), "+f"(d[70]), "+f"(d[71]), "+f"(d[72]), "+f"(d[73]), "+f"(d[74]), "+f"(d[75]), "+f"(d[76]), "+f"(d[77]), "+f"(d[78]), "+f"(d[79]), "+f"(d[80]), "+f"(d[81]), "+f"(d[82]), "+f"(d[83]), "+f"(d[84]), "+f"(d[85]), "+f"(d[86]), "+f"(d[87]), "+f"(d[88]), "+f"(d[89]), "+f"(d[90]), "+f"(d[91]), "+f"(d[92]), "+f"(d[93]), "+f"(d[94]), "+f"(d[95]), "+f"(d[96]), "+f"(d[97]), "+f"(d[98]), "+f"(d[99]), "+f"(d[100]), "+f"(d[101]), "+f"(d[102]), "+f"(d[103]), "+f"(d[104]), "+f"(d[105]), "+f"(d[106]), "+f"(d[107]), "+f"(d[108]), "+f"(d[109]), "+f"(d[110]), "+f"(d[111]), "+f"(d[112]), "+f"(d[113]), "+f"(d[114]), "+f"(d[115]), "+f"(d[116]), "+f"(d[117]), "+f"(d[118]), "+f"(d[119]), "+f"(d[120]), "+f"(d[121]), "+f"(d[122]), "+f"(d[123]), "+f"(d[124]), "+f"(d[125]), "+f"(d[126]), "+f"(d[127])
        : "l"(da), "l"(db), "r"(acc));
}
__device__ __forceinline__ void wgmma128(float (&d)[64], uint64_t da, uint64_t db, int acc) {
    asm volatile("{.reg .pred p; setp.ne.b32 p, %66, 0;\n"
        "wgmma.mma_async.sync.aligned.m64n128k16.f32.bf16.bf16 {"
        "%0,%1,%2,%3,%4,%5,%6,%7,%8,%9,%10,%11,%12,%13,%14,%15,"
        "%16,%17,%18,%19,%20,%21,%22,%23,%24,%25,%26,%27,%28,%29,%30,%31,"
        "%32,%33,%34,%35,%36,%37,%38,%39,%40,%41,%42,%43,%44,%45,%46,%47,"
        "%48,%49,%50,%51,%52,%53,%54,%55,%56,%57,%58,%59,%60,%61,%62,%63"
        "}, %64, %65, p, 1, 1, 0, 1;}"
        : "+f"(d[0]), "+f"(d[1]), "+f"(d[2]), "+f"(d[3]), "+f"(d[4]), "+f"(d[5]), "+f"(d[6]), "+f"(d[7]), "+f"(d[8]), "+f"(d[9]), "+f"(d[10]), "+f"(d[11]), "+f"(d[12]), "+f"(d[13]), "+f"(d[14]), "+f"(d[15]), "+f"(d[16]), "+f"(d[17]), "+f"(d[18]), "+f"(d[19]), "+f"(d[20]), "+f"(d[21]), "+f"(d[22]), "+f"(d[23]), "+f"(d[24]), "+f"(d[25]), "+f"(d[26]), "+f"(d[27]), "+f"(d[28]), "+f"(d[29]), "+f"(d[30]), "+f"(d[31]), "+f"(d[32]), "+f"(d[33]), "+f"(d[34]), "+f"(d[35]), "+f"(d[36]), "+f"(d[37]), "+f"(d[38]), "+f"(d[39]), "+f"(d[40]), "+f"(d[41]), "+f"(d[42]), "+f"(d[43]), "+f"(d[44]), "+f"(d[45]), "+f"(d[46]), "+f"(d[47]), "+f"(d[48]), "+f"(d[49]), "+f"(d[50]), "+f"(d[51]), "+f"(d[52]), "+f"(d[53]), "+f"(d[54]), "+f"(d[55]), "+f"(d[56]), "+f"(d[57]), "+f"(d[58]), "+f"(d[59]), "+f"(d[60]), "+f"(d[61]), "+f"(d[62]), "+f"(d[63])
        : "l"(da), "l"(db), "r"(acc));
}
__device__ __forceinline__ void wg_fence() { asm volatile("wgmma.fence.sync.aligned;" ::: "memory"); }
__device__ __forceinline__ void wg_commit() { asm volatile("wgmma.commit_group.sync.aligned;" ::: "memory"); }
template <int N> __device__ __forceinline__ void wg_wait() { asm volatile("wgmma.wait_group.sync.aligned %0;" ::"n"(N) : "memory"); }
__device__ __forceinline__ uint64_t mkdesc(uint32_t addr, uint32_t lbo, uint32_t sbo, uint32_t sw) {
    return (uint64_t)((addr & 0x3FFFF) >> 4) | ((uint64_t)(lbo >> 4) << 16) | ((uint64_t)(sbo >> 4) << 32) | ((uint64_t)sw << 62);
}
__device__ __forceinline__ void tma2d(uint32_t dst, const CUtensorMap* m, int c0, int c1, uint32_t bar) {
    asm volatile("cp.async.bulk.tensor.2d.shared::cluster.global.mbarrier::complete_tx::bytes [%0], [%1, {%2, %3}], [%4];"
        ::"r"(dst), "l"(m), "r"(c0), "r"(c1), "r"(bar) : "memory");
}
__device__ __forceinline__ void tma3d(uint32_t dst, const CUtensorMap* m, int c0, int c1, int c2, uint32_t bar) {
    asm volatile("cp.async.bulk.tensor.3d.shared::cluster.global.mbarrier::complete_tx::bytes [%0], [%1, {%2, %3, %4}], [%5];"
        ::"r"(dst), "l"(m), "r"(c0), "r"(c1), "r"(c2), "r"(bar) : "memory");
}
__device__ __forceinline__ void tma3d_mc(uint32_t dst, const CUtensorMap* m, int c0, int c1, int c2, uint32_t bar, uint16_t mask) {
    asm volatile("cp.async.bulk.tensor.3d.shared::cluster.global.mbarrier::complete_tx::bytes.multicast::cluster [%0], [%1, {%2, %3, %4}], [%5], %6;"
        ::"r"(dst), "l"(m), "r"(c0), "r"(c1), "r"(c2), "r"(bar), "h"(mask) : "memory");
}
__device__ __forceinline__ void mbar_arrive(uint32_t bar) { asm volatile("mbarrier.arrive.shared.b64 _, [%0];" ::"r"(bar) : "memory"); }
__device__ __forceinline__ void mbar_arrive_remote(uint32_t bar) {
    asm volatile("mbarrier.arrive.shared::cluster.b64 _, [%0];" ::"r"(bar) : "memory");
}
__device__ __forceinline__ bool elect() {
    uint32_t p;
    asm volatile("{.reg .pred p; elect.sync _|p, 0xffffffff; selp.u32 %0, 1, 0, p;}" : "=r"(p));
    return p;
}
template <int R> __device__ __forceinline__ void reg_inc() { asm volatile("setmaxnreg.inc.sync.aligned.u32 %0;" ::"n"(R)); }
template <int R> __device__ __forceinline__ void reg_dec() { asm volatile("setmaxnreg.dec.sync.aligned.u32 %0;" ::"n"(R)); }

#define ST(id, w, i)
constexpr int CH_NRES = 50;
constexpr int CH_WREG = CH_NRES * 512;
constexpr int CH_PART = 8 * CH_WREG;
constexpr int CH_SX = CH_PART + 16384;
constexpr int CH_MX = CH_SX + 3 * 1280;
constexpr int CH_QK = CH_MX;
constexpr int CH_XS = CH_MX + 3 * 512;
constexpr int CH_BAR = CH_XS + 5632;
constexpr int CH_SMEM = CH_BAR + 192;
constexpr int CH_THREADS = 384;

__device__ __forceinline__ char* ring_base() { return (char*)(((uintptr_t)g_ring + (1 << 20) - 1) & ~(uintptr_t)((1 << 20) - 1)); }
__device__ __forceinline__ uint32_t ring_off(int chunk, int side) {
    uint32_t o = ((chunk & 1) << 13) | ((chunk >> 1) << 16);
    uint32_t par = ((o >> 13) ^ (o >> 16) ^ (o >> 17) ^ (o >> 19) ^ side) & 1;
    return o | (par << 12);
}
__device__ __forceinline__ uint2 ld_poll(const char* p) {
    unsigned long long v; asm volatile("ld.relaxed.gpu.global.b64 %0, [%1];" : "=l"(v) : "l"(p) : "memory");
    return make_uint2((uint32_t)v, (uint32_t)(v >> 32));
}
__device__ __forceinline__ void st_pub(char* p, uint32_t x, uint32_t y) {
    unsigned long long v = ((unsigned long long)y << 32) | x;
    asm volatile("st.relaxed.gpu.global.b64 [%0], %1;" ::"l"(p), "l"(v) : "memory");
}
template <int N>
__device__ __forceinline__ void poll_issue(uint2 (&b)[N], const char* p, bool lastvalid) {
#pragma unroll
    for (int i = 0; i < N; i++) {
        if (i < N - 1 || lastvalid) b[i] = ld_poll(p + i * 256);
        else b[i] = make_uint2(0, 0);
    }
}
template <int N>
__device__ __forceinline__ int poll_check(uint2 (&b)[N], const char* p, uint32_t z) {
    int it = 0;
    uint32_t mx = z;
#pragma unroll
    for (int i = 0; i < N; i++) mx = max(mx, b[i].x);
    if (__any_sync(0xffffffffu, mx == SENT)) {
        do {
#pragma unroll
            for (int i = 0; i < N; i++)
                if ((REALL && i < 10) || b[i].x == SENT) b[i] = ld_poll(p + i * 256);
            mx = b[0].x;
#pragma unroll
            for (int i = 1; i < N; i++) mx = max(mx, b[i].x);
            it++;
        } while (__any_sync(0xffffffffu, mx == SENT && it < SPIN_LIMIT));
    }
    return it;
}
template <int N>
__device__ __forceinline__ uint32_t delay(uint32_t a) {
    uint32_t z = 0;
#pragma unroll
    for (int i = 0; i < N; i++) asm volatile("ld.volatile.shared.u32 %0, [%1];" : "=r"(z) : "r"(a + z) : "memory");
    return z;
}

#define PFKV 0
#define LDW 0
#define PACE2 18
#define KGS 3
constexpr int KVN = 2;
#define FEN 1
#define XB 4
#define KEEP 100
#define PE 0
#define PROMO 2
#define PROMU 0
#define FNC 1
#define CL 8
#define PL 0
#define ML 4
#define MP 2
#define VCH_P 4
#define VCH_C 2
#define DLM 3
#define DLO 5
constexpr int OB = 0;
template <int PACE, int I0 = 0, int I1 = 12>
__device__ __forceinline__ void preload(uint32_t (&sw)[12][4], uint32_t a, uint32_t zero) {
    uint32_t z = 0;
#pragma unroll
    for (int i = I0; i < I1; i++) {
        if (PACE && i % (PACE ? PACE : 1) == 0) z = delay<1>(zero + z);
        ldsm4t(sw[i], a + z + i * 512);
    }
}
__device__ __forceinline__ void stsm4(uint32_t addr, uint32_t a, uint32_t b, uint32_t c, uint32_t d) {
    asm volatile("stmatrix.sync.aligned.m8n8.x4.shared.b16 [%0], {%1,%2,%3,%4};" ::"r"(addr), "r"(a), "r"(b), "r"(c), "r"(d) : "memory");
}
__device__ __forceinline__ void stsm4t(uint32_t addr, uint32_t a, uint32_t b, uint32_t c, uint32_t d) {
    asm volatile("stmatrix.sync.aligned.m8n8.x4.trans.shared.b16 [%0], {%1,%2,%3,%4};" ::"r"(addr), "r"(a), "r"(b), "r"(c), "r"(d) : "memory");
}
__device__ __forceinline__ void st_part(uint32_t addr, const float (&x)[4], const float (&y)[4]) {
    stsm4(addr, pack_bf16(x[0], x[1]), pack_bf16(x[2], x[3]), pack_bf16(y[0], y[1]), pack_bf16(y[2], y[3]));
}
template <bool TR>
__device__ __forceinline__ void red_part(uint32_t& lo, uint32_t& hi, uint32_t addr, uint32_t eye) {
    uint32_t a[4][4];
#pragma unroll
    for (int j = 0; j < 4; j++) { if (TR) ldsm4t(a[j], addr + j * 1024); else ldsm4(a[j], addr + j * 1024); }
    float r0[4], r1[4], r2[4], r3[4];
    mma16z(r0, a[0], eye, eye); mma16z(r1, a[1], eye, eye); mma16z(r2, a[2], eye, eye); mma16z(r3, a[3], eye, eye);
#pragma unroll
    for (int j = 0; j < 4; j++) r0[j] = ((r0[j] + r1[j]) + r2[j]) + r3[j];
    lo = pack_bf16(r0[0], r0[1]); hi = pack_bf16(r0[2], r0[3]);
}
__device__ __forceinline__ int o_chunk(int ks, int& pos) {
    const int cw = ks < 176 ? ks / 11 : 16 + (ks - 176) / 10;
    pos = ks - (cw < 16 ? 11 * cw : 176 + 10 * (cw - 16));
    return cw;
}

template <bool PV>
__device__ __forceinline__ void chain_loop(const uint32_t (&wa)[36][4], const uint32_t sb, const int w, const int lane0, const int rank,
                                           const int h, const int side) {
    const int rk1 = rank == 2 ? 0 : rank + 1, rk2 = rank == 0 ? 2 : rank - 1;
    const int nq = rank == 0 ? 6 : 5, u0 = rank == 0 ? 0 : 1 + 5 * rank, v0 = rank == 0 ? -6 : 3 * rank - 6;
    const uint32_t pt = CH_PART + (w >> 1) * 4096 + (w & 1) * 256;
    const uint32_t barS = sb + CH_BAR, barM = barS + 8, zero = barS + 24;
    char* const ring0 = ring_base();
    const uint32_t m_rd = ring_off(24 + w, side), o_rd = ring_off(rank * 8 + w, side);
    uint32_t pub;
    if (PV) { int pos, cw = o_chunk(h * 8 + v0 + w, pos); pub = (ring_off(cw, 0) & ~4096u) + pos * 256; }
    else pub = (ring_off(24 + (h >> 2), 0) & ~4096u) + ((2 * h + w) & 7) * 256;
    char* const kvo = (char*)(PV ? g_vm + 128 * (v0 + w) : g_km + 64 * (u0 + w)) + h * 2048;
    const bool mown = !PV && w == rank && rank < 2;
    uint32_t lo16 = lane0 * 16;
    uint32_t sw[12][4];
#pragma unroll
    for (int i = 0; i < 12; i++) ldsm4t(sw[i], sb + lo16 + w * CH_WREG + i * 512);

#pragma unroll 1
    for (int s = 0;; s++) {
        const bool last = s == NSEG - 1;
        const uint32_t slot = (s & 3) << 14;
        lo16 += delay<DLM>(zero);
        const uint32_t lane = lo16 >> 4, l16 = sb + lo16, wl = l16 + w * CH_WREG, pw = l16 + CH_PART + w * 512;
        const uint32_t xs = l16 + CH_XS + nq * 512 + (w - nq) * 1024;
        const uint32_t eye = ((lo16 >> 7) == (lane & 3)) ? ((lo16 & 64) ? 0x3F800000u : 0x3F80u) : 0u;
        uint2 b[8];
        const char* pm = ring0 + (m_rd + slot + (lo16 >> 1));
        poll_issue<8>(b, pm, true);
        preload<0, ML, 12>(sw, wl, zero);
        if (FNC & 1) bar_arrive(14, 256);
        poll_check<8>(b, pm, delay<FNC & 1>(zero));
        if ((OB || (XB & 1)) && !last) bar_arrive(8, 256 + OB);
        if (PV && !last && w == 7) bar_arrive(13, 64);
        {
            float acc[6][4];
#pragma unroll
            for (int kk = 0; kk < 8; kk++) {
                const int j = (2 * kk) % 12;
                if (kk == 0) { mma16z(acc[5], sw[0], b[0].x, b[0].y); mma16z(acc[4], sw[1], b[0].x, b[0].y); }
                else { mma16(acc[5], sw[j], b[kk].x, b[kk].y); mma16(acc[4], sw[j + 1], b[kk].x, b[kk].y); }
#pragma unroll
                for (int i = 0; i < 4; i++) {
                    if (kk == 0) mma16z(acc[i], wa[i * 8], b[0].x, b[0].y);
                    else mma16(acc[i], wa[i * 8 + kk], b[kk].x, b[kk].y);
                    if (i < 2) ldsm4t(sw[j + i], wl + (12 + 2 * kk + i) * 512);
                }
            }
            st_part(pw + 4 * 2048, acc[4], acc[5]);
            st_part(pw, acc[0], acc[1]);
            st_part(pw + 2 * 2048, acc[2], acc[3]);
        }
        uint32_t kv0, kv1;
        const uint32_t lp = l16 + (lane >> 4) * 256, pl = lp + pt;
        if (!PV) {
            bar_sync(1, last ? 256 : 256 + OB);
            red_part<true>(kv1, kv0, pl, eye);
            sts64(l16 + CH_QK + (w >> 1) * 512 + (w & 1) * 8, __uint_as_float(kv1), __uint_as_float(kv0));
            if (!last) bar_arrive(2, nq * 32 + 64 + OB);
        } else {
            bar_sync(1, last ? 256 : 256 + OB);
        }
        {
            float va[4][4];
            const float z = __uint_as_float(delay<1>(zero));
#pragma unroll
            for (int i = 0; i < 4; i++) va[i][0] = va[i][1] = va[i][2] = va[i][3] = z;
#pragma unroll
            for (int kk = 0; kk < 8; kk++) {
                const int c = (PV ? VCH_P : VCH_C) == 4 ? kk & 1 : 0;
                if (kk < 2) { mma16(va[c], wa[32 + 2 * kk], b[kk].x, b[kk].y); mma16(va[2 + c], wa[33 + 2 * kk], b[kk].x, b[kk].y); }
                else { mma16(va[c], sw[(2 * kk) % 12], b[kk].x, b[kk].y); mma16(va[2 + c], sw[(2 * kk + 1) % 12], b[kk].x, b[kk].y); }
            }
            if ((PV ? VCH_P : VCH_C) == 4) {
#pragma unroll
                for (int j = 0; j < 4; j++) { va[0][j] += va[1][j]; va[2][j] += va[3][j]; }
            }
            st_part(pw + 6 * 2048, va[0], va[2]);
        }
        if (PV) {
            uint32_t vt0[4], vt1[4];
            ldsm4t(vt0, xs); ldsm4t(vt1, xs + 512);
            if (w >= 6 && !last) {
                uint32_t kx[3][4];
#pragma unroll
                for (int j = 0; j < 3; j++)
                    ldsm4(kx[j], sb + CH_XS + j * 1024 + (j == 2 && nq == 5 ? 0 : ((lane >> 3) & 1) * 512) + (w - 6) * 256 + (lane >> 4) * 128 + (lane & 7) * 16);
                const uint32_t da = l16 + CH_SX + rank * 1280 + (w - 6) * 512, dc = sb + CH_SX + rank * 1280 + 1024 + lane * 8;
                bar_sync(2, nq * 32 + 64 + OB);
                uint32_t qk[3][4];
#pragma unroll
                for (int j = 0; j < 3; j++) {
                    const float4 v = lds128(l16 + CH_QK + j * 512);
                    qk[j][0] = __float_as_uint(v.x); qk[j][1] = __float_as_uint(v.y); qk[j][2] = __float_as_uint(v.z); qk[j][3] = __float_as_uint(v.w);
                }
                float s0[4], s1[4], s2[4], s3[4];
                mma16z(s0, qk[0], kx[0][0], kx[0][1]); mma16z(s1, qk[0], kx[0][2], kx[0][3]);
                mma16z(s2, qk[1], kx[1][0], kx[1][1]); mma16z(s3, qk[1], kx[1][2], kx[1][3]);
                if (nq == 5) qk[2][2] = qk[2][3] = 0;
                mma16(s0, qk[2], kx[2][0], kx[2][1]); mma16(s1, qk[2], kx[2][2], kx[2][3]);
                float m0[4], m1[4];
                mma16z(m0, qk[0], qk[0][1], qk[0][3]); mma16z(m1, qk[1], qk[1][1], qk[1][3]);
                mma16(m0, qk[2], qk[2][1], qk[2][3]);
                const float4 sv = make_float4(s0[0] + s2[0], s0[1] + s2[1], s1[0] + s3[0], s1[1] + s3[1]);
                st_async4(mapa(da, rk1), sv, mapa(barS, rk1));
                st_async4(mapa(da, rk2), sv, mapa(barS, rk2));
                {
                    const float c0 = m0[0] + m1[0], c1 = m0[1] + m1[1];
                    const int dr = w == 6 ? rk1 : rk2;
                    st_async2(mapa(dc, dr), c0, c1, mapa(barS, dr));
                    sts64(dc, c0, c1);
                }
                const float t4[4] = {sv.x, sv.y, sv.z, sv.w};
                sts128(da, t4);
            }
            bar_sync(3, last ? 256 : 256 + OB);
            if (!last && w == 7) bar_arrive(12, 64);
            red_part<false>(kv0, kv1, pl, eye);
            if (last) {
                uint32_t* d = (uint32_t*)(kvo + (uint32_t)(s * (NH * 2048) + lane * 4));
                d[0] = movm(kv0); d[32] = movm(kv1);
                break;
            }
            {
                const uint32_t sx = l16 + CH_SX, r0 = rank * 1280, r1 = rk1 * 1280, r2 = rk2 * 1280;
                float4 a0 = lds128(sx + r0), b0 = lds128(sx + 512 + r0);
                const float2 c0 = lds64(sx + 1024 + r0 - lane * 8);
                preload<0, 0, PE>(sw, wl + 28 * 512, zero);
                mbar_wait(barS, s & 1);
                const float4 a1 = lds128(sx + r1), a2 = lds128(sx + r2), b1 = lds128(sx + 512 + r1), b2 = lds128(sx + 512 + r2);
                const float2 c1 = lds64(sx + 1024 + r1 - lane * 8), c2 = lds64(sx + 1024 + r2 - lane * 8);
                a0 = add4(add4(a0, a1), a2); b0 = add4(add4(b0, b1), b2);
                float sc[10] = {a0.x, a0.y, a0.z, a0.w, b0.x, b0.y, b0.z, b0.w, c0.x + c1.x + c2.x, c0.y + c1.y + c2.y};
                float mx = fmaxf(fmaxf(fmaxf(sc[0], sc[1]), fmaxf(sc[2], sc[3])), fmaxf(fmaxf(sc[4], sc[5]), fmaxf(sc[6], sc[7])));
                mx = fmaxf(mx, fmaxf(sc[8], sc[9]));
                mx = fmaxf(fmaxf(mx, __shfl_xor_sync(0xffffffffu, mx, 1)),
                           fmaxf(__shfl_xor_sync(0xffffffffu, mx, 2), __shfl_xor_sync(0xffffffffu, mx, 3)));
                const float cs = 0.08838834764831845f * 1.4426950408889634f;
                const float mb = -mx * cs;
#pragma unroll
                for (int j = 0; j < 10; j++) sc[j] = ex2(fmaf(sc[j], cs, mb));
                uint32_t pf[5];
#pragma unroll
                for (int j = 0; j < 5; j++) pf[j] = pack_bf16(sc[2 * j], sc[2 * j + 1]);
                float o0[4], o1[4], o2[4], o3[4], o4[4], o5[4];
                const uint32_t p0[4] = {pf[0], 0, pf[1], 0}, p1[4] = {pf[2], 0, pf[3], 0};
                mma16z(o0, p0, vt0[0], vt0[1]); mma16z(o1, p0, vt1[0], vt1[1]);
                mma16z(o2, p1, vt0[2], vt0[3]); mma16z(o3, p1, vt1[2], vt1[3]);
                mma8z(o4, pf[4], 0, kv0); mma8z(o5, pf[4], 0, kv1);
                float sum = (((sc[0] + sc[1]) + (sc[2] + sc[3])) + ((sc[4] + sc[5]) + (sc[6] + sc[7]))) + (sc[8] + sc[9]);
                sum = (sum + __shfl_xor_sync(0xffffffffu, sum, 1)) + (__shfl_xor_sync(0xffffffffu, sum, 2) + __shfl_xor_sync(0xffffffffu, sum, 3));
                float inv; asm("rcp.approx.ftz.f32 %0, %1;" : "=f"(inv) : "f"(sum));
                const uint32_t ox = pack_bf16((o0[0] + o2[0] + o4[0]) * inv, (o0[1] + o2[1] + o4[1]) * inv);
                const uint32_t oy = pack_bf16((o1[0] + o3[0] + o5[0]) * inv, (o1[1] + o3[1] + o5[1]) * inv);
                char* const pp = ring0 + (pub + slot + (lo16 >> 1));
                st_pub(pp, ox, oy); st_pub(pp + 4096, ox, oy);
                if (OB || (XB & 4)) bar_arrive(10, (8 - nq) * 32 + OB);
                preload<0, PE, PL>(sw, wl + 28 * 512, zero);
            }
            kv0 = movm(kv0); kv1 = movm(kv1);
        } else {
            *(uint32_t*)(kvo + (uint32_t)(s * (NH * 2048) + lane * 4)) = kv0;
            bar_sync(3, last ? 256 : 256 + OB);
            if (last) break;
            preload<1, 0, CL>(sw, wl + 28 * 512, zero);
        }
        uint2 c[11];
        bar_sync(4, 256 + OB);
        const char* po = ring0 + (o_rd + slot + (lo16 >> 1) + delay<DLO>(zero));
        poll_issue<11>(c, po, rank < 2);
        preload<0, PV ? PL : CL, 12>(sw, wl + 28 * 512, zero);
        if (PV) { uint32_t* d = (uint32_t*)(kvo + (uint32_t)(s * (NH * 2048) + lane * 4)); d[0] = kv0; d[32] = kv1; }
        if (FNC & 2) bar_arrive(15, 256);
        poll_check<11>(c, po, delay<(FNC >> 1)>(zero));
        if (OB || (XB & 2)) bar_arrive(9, 256 + OB);
        {
            float acc[4][4];
#pragma unroll
            for (int f = 0; f < 22; f++) {
                const int kk = f >> 1, a = f & 3;
                if (f < 4) mma16z(acc[a], sw[f % 12], c[kk].x, c[kk].y);
                else mma16(acc[a], sw[f % 12], c[kk].x, c[kk].y);
                if (f + 12 < 22) ldsm4t(sw[f % 12], wl + (28 + f + 12) * 512);
            }
#pragma unroll
            for (int i = 0; i < 2; i++) {
#pragma unroll
                for (int j = 0; j < 4; j++) acc[i][j] += acc[i + 2][j];
                sts128(l16 + CH_PART + i * 4096 + w * 512, acc[i]);
            }
        }
        if (!PV && w < 2) {
            bar_sync(5, 288 + OB);
            float4 v[8];
#pragma unroll
            for (int i = 0; i < 8; i++) v[i] = lds128(l16 + CH_PART + w * 4096 + i * 512);
            float4 r = add4(add4(add4(v[0], v[1]), add4(v[2], v[3])), add4(add4(v[4], v[5]), add4(v[6], v[7])));
            if (!mown) st_async4(mapa(l16 + CH_MX + rank * 512, w), r, mapa(barM, w));
            bar_arrive(7, 256 + OB);
            if (mown) {
                mbar_wait(barM, s & 1);
                float4 x = lds128(l16 + CH_MX + (rank ^ 1) * 512), y = lds128(l16 + CH_MX + 2 * 512);
                r = add4(add4(x, r), y);
                const uint32_t mx = movm(pack_bf16(r.x, r.y)), my = movm(pack_bf16(r.z, r.w));
                const uint32_t ns = (slot + 0x4000) & 0xC000;
                char* const pp = ring0 + (pub + ns + (lo16 >> 1));
                st_pub(pp, mx, my); st_pub(pp + 4096, mx, my);
            }
            preload<0, 0, ML>(sw, wl, zero);
        } else {
            bar_arrive(5, 288 + OB);
            bar_sync(7, 256 + OB);
            preload<MP, 0, ML>(sw, wl, zero);
        }
        bar_sync(6, 320 + OB);
    }
    bar_arrive(6, 288);
}

__device__ __forceinline__ void chain_pace(const uint32_t sb, const int lane, const int rank, const int aware) {
    const uint32_t zero = sb + CH_BAR + 24;
    if (lane == 0) {
        char* ring = ring_base();
        uint32_t* p0 = (uint32_t*)(ring + ring_off(blockIdx.x & 15, 0) + 3072 + (blockIdx.x >> 4) * 128);
        uint32_t* p1 = (uint32_t*)(ring + ring_off(blockIdx.x & 15, 1) + 3072 + (blockIdx.x >> 4) * 128);
        *p0 = 0; *p1 = 0;
        int b0 = 1 << 30, b1 = 1 << 30; uint32_t v = 0;
        for (int r = 0; r < 4 || (r < 256 && !mbar_test(sb + CH_BAR + 16, 0)); r++) {
            uint32_t t0 = clk(); v = atomicExch(p0 + (v == 500), r); uint32_t t1 = v == 777 ? clk() + 1 : clk(); b0 = min(b0, (int)(t1 - t0));
            t0 = clk(); v = atomicExch(p1 + (v == 500), r); t1 = v == 777 ? clk() + 1 : clk(); b1 = min(b1, (int)(t1 - t0));
            asm volatile("st.volatile.shared.u32 [%0], %1;" ::"r"(zero + 4), "r"(aware ? (b1 < b0) ^ (aware - 1) : 0) : "memory");
        }
    }
    __syncwarp();
#pragma unroll 1
    for (int s = 1; s < NSEG; s++) {
        bar_sync(5, 288 + OB);
        bar_arrive(6, 320 + OB + (rank == 2 ? delay<PACE2>(zero) : 0));
    }
}
__device__ __forceinline__ char* reset_ptr(const int lane, const int rank, const int h) {
    const int nq = rank == 0 ? 6 : 5, v0 = rank == 0 ? -6 : 3 * rank - 6;
    int pos, cw = o_chunk(h * 8 + v0 + min(max(5 + (lane >> 3), nq), 7), pos);
    if (lane >= 24 && rank < 2) { cw = 24 + (h >> 2); pos = (2 * h + rank) & 7; }
    return ring_base() + ((ring_off(cw, 0) & ~4096u) + pos * 256 + (lane & 7) * 16);
}
__device__ __forceinline__ void chain_chores(const uint32_t sb, const int lane, const int rank, const int h, const bf16* __restrict__ mem0) {
    const int nq = rank == 0 ? 6 : 5, u0 = rank == 0 ? 0 : 1 + 5 * rank, v0 = rank == 0 ? -6 : 3 * rank - 6;
    const uint32_t barS = sb + CH_BAR, barM = barS + 8, barX = barS + 16;
    auto xload = [&](int s) {
        mbar_expect(barX, 8192 - nq * 512);
        bulk_load(sb + CH_XS, g_kx + (size_t)(s * NH + h) * 4096 + u0 * 256, nq * 512, barX);
        bulk_load(sb + CH_XS + nq * 512, g_vx + (size_t)(s * NH + h) * 4096 + (v0 + nq) * 512, (8 - nq) * 1024, barX);
    };
    char* const rb = reset_ptr(lane, rank, h);
    int* const kvf = g_kvf + blockIdx.x * 16;
    if (rank < 2) {
        const uint32_t* p = (const uint32_t*)(mem0 + (lane >> 2) * DM + 32 * h + 16 * rank + 2 * (lane & 3));
        char* d = ring_base() + ((ring_off(24 + (h >> 2), 0) & ~4096u) + ((2 * h + rank) & 7) * 256 + lane * 8);
        const uint32_t x = p[0] == SENT ? 0x7FFF7FFFu : p[0];
        st_pub(d, x, p[4]); st_pub(d + 4096, x, p[4]);
    }
    if (!KVN) __nanosleep(18000);
    wait_ctr(kvf, KVN);
    asm volatile("fence.proxy.async.global;" ::: "memory");
    if (elect()) xload(0);
#pragma unroll 1
    for (int s = 0; s < NSEG - 1; s++) {
        if (lane == 0) {
            mbar_expect(barS, 2 * 1280);
            if (rank < 2) mbar_expect(barM, 2 * 512);
        }
        bar_sync(13, 64);
#pragma unroll
        for (int i = 0; i < 4; i++)
            asm volatile("st.relaxed.gpu.global.v4.u32 [%0], {%1,%1,%1,%1};" ::"l"(rb + ((((s + 2) & 3) << 14) + (i >> 1) * 4096 + (i & 1) * 128)), "r"(SENT) : "memory");
        if (FEN || (s & 3) == 0) fence_gpu();
        if (lane == 0 && (s & 3) == 0 && s) atomicAdd(g_ctr + C_CHAIN + (s >> 2) - 1, 1);
        if ((s & 3) == 3) { wait_ctr(kvf + (s >> 2) + 1, KVN); asm volatile("fence.proxy.async.global;" ::: "memory"); }
        __syncwarp();
        bar_sync(12, 64);
        if (elect()) xload(s + 1);
        mbar_wait(barX, (s + 1) & 1);
        bar_sync(6, 320 + OB);
    }
    bar_sync(6, 288);
    fence_gpu();
    if (lane == 0) atomicAdd(g_ctr + C_CHAIN + 15, 1);
}

struct S4Params { const bf16 *Are, *Aim, *Bre, *Bim, *Cre, *Cim, *ldt, *dsk; };
__device__ __forceinline__ float2 cmul(float2 a, float2 b) { return make_float2(a.x * b.x - a.y * b.y, a.x * b.y + a.y * b.x); }
__device__ __forceinline__ float2 csq(float2 a) { return make_float2(a.x * a.x - a.y * a.y, (a.x + a.x) * a.y); }
__device__ __forceinline__ float2 cexp_t(float lr, float turns) {
    float f = (turns - rintf(turns)) * 6.283185307179586f, e = ex2(lr);
    return make_float2(e * __cosf(f), e * __sinf(f));
}
__device__ __forceinline__ float bf_at(uint2 v, int i) {
    const uint32_t w = i < 2 ? v.x : v.y;
    return __uint_as_float((i & 1) ? w & 0xFFFF0000u : w << 16);
}
__device__ __forceinline__ void kg_step(uint32_t (&a)[4][4], uint32_t (&b)[5][2], uint32_t pa, uint32_t pe, float x0) {
#pragma unroll
    for (int i = 0; i < 2; i++) {
        const float4 p = lds128(pa + i * 64);
        const float2 e8 = lds64(pe + i * 32), c = make_float2(p.z, p.w);
        const float mag = ex2(p.x * x0), ph = p.y * x0;
        float2 e0 = make_float2(mag * __cosf(ph), mag * __sinf(ph)), e1 = cmul(e0, e8);
#pragma unroll
        for (int j = 0; j < 4; j++) {
            a[j][2 * i] = pack_bf16(e0.x, e0.y); a[j][2 * i + 1] = pack_bf16(e1.x, e1.y);
            e0 = csq(e0); e1 = csq(e1);
        }
        float2 m = cmul(c, e0);
        b[0][i] = pack_bf16(m.x, -m.y);
#pragma unroll
        for (int j = 0; j < 4; j++) {
            m = cmul(c, e1);
            b[j + 1][i] = pack_bf16(m.x, -m.y);
            if (j < 3) e1 = csq(e1);
        }
    }
}
__device__ __forceinline__ void kg_mma(float (&kd)[5][4], const uint32_t (&a)[4][4], const uint32_t (&b)[5][2]) {
    mma16(kd[0], a[0], b[0][0], b[0][1]);
#pragma unroll
    for (int j = 0; j < 4; j++) mma16(kd[j + 1], a[j], b[j + 1][0], b[j + 1][1]);
}
struct KgRaw { uint2 v[6]; float ldt; };
__device__ __forceinline__ void kg_load(KgRaw& r, const S4Params& P, int d, int lane) {
    const bf16* src[6] = {P.Are, P.Aim, P.Bre, P.Bim, P.Cre, P.Cim};
#pragma unroll
    for (int j = 0; j < 6; j++) r.v[j] = __ldg((const uint2*)(src[j] + d * 128) + lane);
    r.ldt = __bfloat162float(P.ldt[d]);
}
__device__ __forceinline__ float kg_params(const KgRaw& r, uint32_t stg, int lane) {
    const float dt = __bfloat162float(__float2bfloat16(expf(r.ldt)));
    float k2048 = 0.f;
#pragma unroll
    for (int i = 0; i < 4; i++) {
        const float br = dt * bf_at(r.v[2], i), bi = dt * bf_at(r.v[3], i), cr = bf_at(r.v[4], i), ci = bf_at(r.v[5], i);
        const float zr = dt * bf_at(r.v[0], i) * 1.4426950408889634f;
        float zt = dt * bf_at(r.v[1], i) * 0.15915494309189535f;
        zt -= rintf(zt);
        const float v[4] = {zr, zt * 6.283185307179586f, cr * br - ci * bi, cr * bi + ci * br};
        const float2 e8 = cexp_t(8.f * zr, 8.f * zt), el = cexp_t(2048.f * zr, 2048.f * zt);
        k2048 += v[2] * el.x - v[3] * el.y;
        sts128(stg + (i * 32 + lane) * 16, v);
        sts64(stg + 2048 + (i * 32 + lane) * 8, e8.x, e8.y);
    }
#pragma unroll
    for (int o = 16; o; o >>= 1) k2048 += __shfl_xor_sync(0xffffffffu, k2048, o);
    __syncwarp();
    return k2048;
}
__device__ __forceinline__ void kg_store(const float (&kd)[5][4], float k2048, uint32_t stg, int d, int lane) {
    __syncwarp();
    const uint32_t ta = stg + (lane & 7) * 32 + ((lane >> 3) & 1) * 16 + (lane >> 4) * 256;
    stsm4t(ta, pack_bf16(kd[0][0], kd[0][1]), pack_bf16(kd[0][2], kd[0][3]), pack_bf16(kd[1][0], kd[1][1]), pack_bf16(kd[1][2], kd[1][3]));
    stsm4t(ta + 512, pack_bf16(kd[2][0], kd[2][1]), pack_bf16(kd[2][2], kd[2][3]), pack_bf16(kd[3][0], kd[3][1]), pack_bf16(kd[3][2], kd[3][3]));
    stsm4t(ta + 1024, pack_bf16(kd[4][0], kd[4][1]), pack_bf16(kd[4][2], kd[4][3]), pack_bf16(k2048, 0.f), 0);
    __syncwarp();
#pragma unroll
    for (int j = 0; j < 3; j++) ((float4*)(g_kd + d * 768))[j * 32 + lane] = lds128(stg + j * 512 + lane * 16);
    __syncwarp();
}

__global__ void __cluster_dims__(3, 1, 1) __launch_bounds__(CH_THREADS, 1)
chain_kernel(const __grid_constant__ CUtensorMap mq, const __grid_constant__ CUtensorMap mk, const __grid_constant__ CUtensorMap mv,
             const __grid_constant__ CUtensorMap mo, const bf16* __restrict__ Wq, const bf16* __restrict__ Wk, const bf16* __restrict__ Wv,
             const bf16* __restrict__ mem0, const __grid_constant__ S4Params P, int aware) {
    extern __shared__ __align__(1024) unsigned char smem[];
    const uint32_t sb = smem_u32(smem);
    const int tid = threadIdx.x, lane = tid & 31;
    const int w = __shfl_sync(0xffffffffu, tid >> 5, 0);
    int rank; asm("mov.u32 %0, %%cluster_ctarank;" : "=r"(rank));
    const int h = blockIdx.x / 3;
    if (tid == 0) {
        mbar_init(sb + CH_BAR, 1); mbar_init(sb + CH_BAR + 8, 1); mbar_init(sb + CH_BAR + 16, 1);
        for (int i = 0; i < 16; i++) mbar_init(sb + CH_BAR + 64 + i * 8, 1);
        *(int*)(smem + CH_BAR + 24) = 0; *(int*)(smem + CH_BAR + 28) = 0; *(int*)(smem + CH_BAR + 32) = 0;
        asm volatile("fence.mbarrier_init.release.cluster;" ::: "memory");
    }
    if (w == 10 && PFKV) {
        const int e = lane * 96 + blockIdx.x;
        if (e < 2048) asm volatile("cp.async.bulk.prefetch.L2.global [%0], 8192;" ::"l"(((e & 1) ? Wv : Wk) + (size_t)(e >> 1) * HD) : "memory");
        if (PFKV > 1) __nanosleep(PFKV);
    }
    if (w == 9) {
        char* const rb = reset_ptr(lane, rank, h);
#pragma unroll
        for (int i = 0; i < 8; i++)
            asm volatile("st.relaxed.gpu.global.v4.u32 [%0], {%1,%1,%1,%1};" ::"l"(rb + (((i >> 2) << 14) + ((i >> 1) & 1) * 4096 + (i & 1) * 128)), "r"(SENT) : "memory");
        if (lane < 16) g_kvf[blockIdx.x * 16 + lane] = 0;
        if (blockIdx.x == 0)
            for (int k = lane; k < N_CTR; k += 32) g_ctr[k] = 0;
        fence_gpu();
        __syncwarp();
        asm volatile("griddepcontrol.launch_dependents;" ::: "memory");
    }
    __syncthreads();
    asm volatile("barrier.cluster.arrive.relaxed.aligned;" ::: "memory");

    if (w >= 8) {
        reg_dec<24>();
        asm volatile("barrier.cluster.wait.aligned;" ::: "memory");
        if (w == 8) chain_pace(sb, lane, rank, aware);
        else if (w == 9) {
            chain_chores(sb, lane, rank, h, mem0);
            asm volatile("st.volatile.shared.u32 [%0], %1;" ::"r"(sb + CH_BAR + 32), "r"(0x3F803F80) : "memory");
        } else if (w == 11 && KEEP) {
#pragma unroll 1
            for (int it = 0; it < (1 << 22); it++) {
                int d0, d1;
                const uint32_t x = delay<1>(sb + CH_BAR + 32);
                asm volatile("mma.sync.aligned.m8n8k16.row.col.s32.s8.s8.s32 {%0,%1}, {%2}, {%2}, {%3,%3};" : "=r"(d0), "=r"(d1) : "r"(x), "r"(0));
                if (d0 | d1) break;
                if ((XB & 8) && lane == 0) asm volatile("st.relaxed.gpu.global.u32 [%0], %1;" ::"l"(g_kd + DM * 768 + blockIdx.x * 64), "r"(it) : "memory");
                if ((XB & 16) && lane == 0) ld_acq((int*)(g_kd + DM * 768 + blockIdx.x * 64));
                __nanosleep(KEEP);
            }
        }
    } else {
        reg_inc<240>();
        const int nq = rank == 0 ? 6 : 5;
        const int u0 = rank == 0 ? 0 : 1 + 5 * rank;
        const int v0 = rank == 0 ? -6 : 3 * rank - 6;
        const int gw = rank * 8 + w;
        const int ks0 = gw < 16 ? 11 * gw : 176 + 10 * (gw - 16);
        const int nko = gw < 16 ? 11 : 10;
        const uint32_t wr = sb + w * CH_WREG, bar0 = sb + CH_BAR + 64 + w * 16, bar1 = bar0 + 8;
        uint32_t wa[36][4];
        const uint32_t vst = sb + CH_PART + w * 2048;
        const int cq = h * DH + 8 * u0, cv = h * DH + 16 * (v0 + 6);
        const int r8 = lane >> 2, p = lane & 3;
        const bf16* src = p >= 2 ? ((p & 1) ? Wk : Wq) + cq + 32 : rank == 0 ? ((p & 1) ? Wk : Wq) + cq + 40 : Wv + cv - 16 + 8 * p;
        src += (size_t)(128 * w + r8) * HD;
        auto cp_rows = [&](int kh) {
            cp16(wr + ((kh >> 1) * 2 + (p >> 1)) * 512 + ((kh & 1) * 2 + (p & 1)) * 128 + r8 * 16, src + (size_t)kh * 8 * HD);
        };
        {
            int d = blockIdx.x * 8 + w, t = 0;
            const int d1 = 768 + blockIdx.x * 3 + w, nt = (w < 3 && d1 < DM) ? 32 : 16;
            const uint32_t stg = wr + 4096;
            KgRaw raw, raw1;
            kg_load(raw, P, d, lane);
            kg_load(raw1, P, min(d1, DM - 1), lane);
            float kd[5][4], k2048;
#pragma unroll 1
            for (int i = -LDW; i < 9 || t < nt; i++) {
                if (i >= 0 && i < 9) {
                    const uint32_t bar = bar0 + (i & 1) * 8;
                    if (i >= 2) mbar_wait(bar, ((i >> 1) - 1) & 1);
                    if (elect()) {
                        mbar_expect(bar, 2048);
                        if (i < 8) tma2d(wr + 8192 + (i & 1) * 8192 + (i >> 1) * 2048, (i & 1) ? &mk : &mq, cq, 128 * w + 32 * (i >> 1), bar);
                        else tma2d(vst, &mv, cv, 128 * w, bar);
                    }
                    if (i < 8) cp_rows(i);
                }
#pragma unroll 1
                for (int e = min(t + KGS, nt); t < e; t++) {
                    if ((t & 15) == 0) {
                        k2048 = kg_params(raw, stg, lane);
#pragma unroll
                        for (int j = 0; j < 20; j++) kd[j >> 2][j & 3] = 0.f;
                    }
                    uint32_t ka[4][4], kb[5][2];
                    kg_step(ka, kb, stg + ((t & 15) * 8 + (lane & 3)) * 16, stg + 2048 + ((t & 15) * 8 + (lane & 3)) * 8, (float)(lane >> 2));
                    kg_mma(kd, ka, kb);
                    if ((t & 15) == 15) { kg_store(kd, k2048, stg, d, lane); raw = raw1; d = d1; }
                }
            }
        }
        const uint32_t lrow = ((lane >> 4) * 8 + (lane & 7)) * 64, lsw = (lane >> 1) & 3, lh = (lane >> 3) & 1;
        mbar_wait(bar1, 1); mbar_wait(bar0, 0);
#pragma unroll
        for (int i = 0; i < 32; i++) ldsm4t(wa[i], wr + 8192 + lh * 8192 + (i & 7) * 1024 + lrow + (((i >> 3) ^ lsw) << 4));
#pragma unroll
        for (int i = 0; i < 4; i++) ldsm4t(wa[32 + i], vst + (i >> 1) * 1024 + lrow + ((((i & 1) * 2 + lh) ^ lsw) << 4));
        asm volatile("fence.proxy.async.shared::cta;" ::"r"(wa[31][0]), "r"(wa[35][0]) : "memory");
        __syncwarp();
#pragma unroll 1
        for (int i = 9; i < 18; i++) {
            const uint32_t bar = bar0 + (i & 1) * 8;
            if (i >= 11) mbar_wait(bar, ((i >> 1) - 1) & 1);
            if (elect()) {
                const int j = 2 * (i - 12), nb = min(2, nko - j);
                mbar_expect(bar, i < 12 ? 2048 : nb * 1024);
                if (i < 12) tma2d(wr + 8192 + (i - 9) * 2048, &mv, cv, 128 * w + 32 * (i - 8), bar);
                else {
                    if (nb > 0) tma2d(wr + 14336 + j * 1024, &mo, 32 * h, 16 * (ks0 + j), bar);
                    if (nb > 1) tma2d(wr + 15360 + j * 1024, &mo, 32 * h, 16 * (ks0 + j + 1), bar);
                }
            }
            if (i < 17) cp_rows(i - 1);
        }
        mbar_wait(bar0, 0); mbar_wait(bar1, 0);
#pragma unroll 1
        for (int i0 = -1; i0 < 17; i0 += 6) {
            uint32_t x[6][2][4];
#pragma unroll
            for (int i = 0; i < 6; i++) {
                const uint32_t a = wr + 8192 + max(i0 + i, 0) * 1024 + lrow;
                ldsm4t(x[i][0], a + ((lh ^ lsw) << 4)); ldsm4t(x[i][1], a + (((2 + lh) ^ lsw) << 4));
            }
            if (i0 == 11 && nko == 10) {
#pragma unroll
                for (int j = 0; j < 8; j++) x[5][j >> 2][j & 3] = 0;
            }
            __syncwarp();
#pragma unroll
            for (int i = 0; i < 6; i++) {
                const uint32_t a = wr + 8192 + max(i0 + i, 0) * 1024 + lane * 16;
                stsm4t(a, x[i][0][0], x[i][0][1], x[i][0][2], x[i][0][3]); stsm4t(a + 512, x[i][1][0], x[i][1][1], x[i][1][2], x[i][1][3]);
            }
        }
        asm volatile("cp.async.wait_all;" ::: "memory");
        asm volatile("barrier.cluster.wait.aligned;" ::: "memory");
        bar_sync(1, 256);
        mbar_wait_long(sb + CH_BAR + 16, 0);
        const int side = __shfl_sync(0xffffffffu, *(volatile int*)(smem + CH_BAR + 28), 0);
        if (w >= nq) chain_loop<true>(wa, sb, w, lane, rank, h, side);
        else chain_loop<false>(wa, sb, w, lane, rank, h, side);
    }
}

constexpr int G_STAGE = 49152, G_NST = 4;
constexpr int G_STG = G_NST * G_STAGE;
constexpr int G_BAR = G_STG + 32768;
constexpr int G_SMEM = G_BAR + 256 + 1024;

#define WLOG(e)
constexpr int IT_QA = 0, IT_O = 1, IT_S4 = 2, IT_END = 3, IT_KV = 4;
#define O_WIDE 10
#define PING 1
#define S4DIR 5
#define S4REL 4
#define KVI 2
#define KVF 2
#define KVS 8
#define STM 0
__device__ __forceinline__ void st_out(uint32_t* p, uint32_t v) {
    if (STM == 0) *p = v;
    else if (STM == 1) __stcs(p, v);
    else asm volatile("st.global.L1::no_allocate.u32 [%0], %1;" ::"l"(p), "r"(v) : "memory");
}
#define Q_N1 1
#define Q_S1 16
__device__ __forceinline__ int queue_item(int q) {
    if (q < 512) return (IT_KV << 16) | ((q >> 5) << 8) | (q & 31);
    q -= 512;
    if (q < 256) return (IT_QA << 16) | ((q >> 4) << 8) | (q & 15);
    q -= 256;
    if (q < Q_N1 * 8) return (IT_O << 16) | ((O_WIDE + (q >> 3)) << 8) | (q & 7);
    q -= Q_N1 * 8;
    if (q < Q_S1) return (IT_S4 << 16) | q;
    q -= Q_S1;
    if (q < (16 - O_WIDE - Q_N1) * 8) return (IT_O << 16) | ((O_WIDE + Q_N1 + (q >> 3)) << 8) | (q & 7);
    q -= (16 - O_WIDE - Q_N1) * 8;
    if (q < 128 - Q_S1) return (IT_S4 << 16) | (Q_S1 + q);
    return IT_END << 16;
}
__device__ __forceinline__ void tma2d_store(const CUtensorMap* m, uint32_t src, int c0, int c1) {
    asm volatile("cp.async.bulk.tensor.2d.global.shared::cta.bulk_group [%0, {%2, %3}], [%1];" ::"l"(m), "r"(src), "r"(c0), "r"(c1) : "memory");
}

__device__ __forceinline__ void wgmma_s64(float (&d)[32], uint32_t a0, uint32_t a1, uint32_t a2, uint32_t a3, uint64_t db, int acc) {
    asm volatile("{.reg .pred p; setp.ne.b32 p, %37, 0;\n"
        "wgmma.mma_async.sync.aligned.m64n64k16.f32.bf16.bf16 {"
        "%0,%1,%2,%3,%4,%5,%6,%7,%8,%9,%10,%11,%12,%13,%14,%15,"
        "%16,%17,%18,%19,%20,%21,%22,%23,%24,%25,%26,%27,%28,%29,%30,%31"
        "}, {%32,%33,%34,%35}, %36, p, 1, 1, 0;}"
        : "+f"(d[0]), "+f"(d[1]), "+f"(d[2]), "+f"(d[3]), "+f"(d[4]), "+f"(d[5]), "+f"(d[6]), "+f"(d[7]), "+f"(d[8]), "+f"(d[9]), "+f"(d[10]), "+f"(d[11]), "+f"(d[12]), "+f"(d[13]), "+f"(d[14]), "+f"(d[15]), "+f"(d[16]), "+f"(d[17]), "+f"(d[18]), "+f"(d[19]), "+f"(d[20]), "+f"(d[21]), "+f"(d[22]), "+f"(d[23]), "+f"(d[24]), "+f"(d[25]), "+f"(d[26]), "+f"(d[27]), "+f"(d[28]), "+f"(d[29]), "+f"(d[30]), "+f"(d[31])
        : "r"(a0), "r"(a1), "r"(a2), "r"(a3), "l"(db), "r"(acc));
}
__device__ __forceinline__ void wgmma_s16(float (&d)[8], uint32_t a0, uint32_t a1, uint32_t a2, uint32_t a3, uint64_t db, int acc) {
    asm volatile("{.reg .pred p; setp.ne.b32 p, %13, 0;\n"
        "wgmma.mma_async.sync.aligned.m64n16k16.f32.bf16.bf16 {"
        "%0,%1,%2,%3,%4,%5,%6,%7"
        "}, {%8,%9,%10,%11}, %12, p, 1, 1, 0;}"
        : "+f"(d[0]), "+f"(d[1]), "+f"(d[2]), "+f"(d[3]), "+f"(d[4]), "+f"(d[5]), "+f"(d[6]), "+f"(d[7])
        : "r"(a0), "r"(a1), "r"(a2), "r"(a3), "l"(db), "r"(acc));
}
__device__ __forceinline__ void wgmma_v128(float (&d)[64], uint32_t a0, uint32_t a1, uint32_t a2, uint32_t a3, uint64_t db, int acc) {
    asm volatile("{.reg .pred p; setp.ne.b32 p, %69, 0;\n"
        "wgmma.mma_async.sync.aligned.m64n128k16.f32.bf16.bf16 {"
        "%0,%1,%2,%3,%4,%5,%6,%7,%8,%9,%10,%11,%12,%13,%14,%15,"
        "%16,%17,%18,%19,%20,%21,%22,%23,%24,%25,%26,%27,%28,%29,%30,%31,"
        "%32,%33,%34,%35,%36,%37,%38,%39,%40,%41,%42,%43,%44,%45,%46,%47,"
        "%48,%49,%50,%51,%52,%53,%54,%55,%56,%57,%58,%59,%60,%61,%62,%63"
        "}, {%64,%65,%66,%67}, %68, p, 1, 1, 1;}"
        : "+f"(d[0]), "+f"(d[1]), "+f"(d[2]), "+f"(d[3]), "+f"(d[4]), "+f"(d[5]), "+f"(d[6]), "+f"(d[7]), "+f"(d[8]), "+f"(d[9]), "+f"(d[10]), "+f"(d[11]), "+f"(d[12]), "+f"(d[13]), "+f"(d[14]), "+f"(d[15]), "+f"(d[16]), "+f"(d[17]), "+f"(d[18]), "+f"(d[19]), "+f"(d[20]), "+f"(d[21]), "+f"(d[22]), "+f"(d[23]), "+f"(d[24]), "+f"(d[25]), "+f"(d[26]), "+f"(d[27]), "+f"(d[28]), "+f"(d[29]), "+f"(d[30]), "+f"(d[31]), "+f"(d[32]), "+f"(d[33]), "+f"(d[34]), "+f"(d[35]), "+f"(d[36]), "+f"(d[37]), "+f"(d[38]), "+f"(d[39]), "+f"(d[40]), "+f"(d[41]), "+f"(d[42]), "+f"(d[43]), "+f"(d[44]), "+f"(d[45]), "+f"(d[46]), "+f"(d[47]), "+f"(d[48]), "+f"(d[49]), "+f"(d[50]), "+f"(d[51]), "+f"(d[52]), "+f"(d[53]), "+f"(d[54]), "+f"(d[55]), "+f"(d[56]), "+f"(d[57]), "+f"(d[58]), "+f"(d[59]), "+f"(d[60]), "+f"(d[61]), "+f"(d[62]), "+f"(d[63])
        : "r"(a0), "r"(a1), "r"(a2), "r"(a3), "l"(db), "r"(acc));
}

__device__ __forceinline__ void attn_scores(float (&sx)[32], float (&sm)[8], const uint32_t (&q)[32], uint32_t sk) {
    const uint64_t dx = mkdesc(sk, 1024, 128, 0), dm = mkdesc(sk + 16384, 256, 128, 0);
    wg_fence();
#pragma unroll
    for (int ks = 0; ks < 8; ks++) {
        wgmma_s64(sx, q[4 * ks], q[4 * ks + 1], q[4 * ks + 2], q[4 * ks + 3], dx + ks * 128, ks);
        wgmma_s16(sm, q[4 * ks], q[4 * ks + 1], q[4 * ks + 2], q[4 * ks + 3], dm + ks * 32, ks);
    }
    wg_commit();
}
template <bool HI>
__device__ __forceinline__ void attn_softmax(uint32_t (&p)[2][20], const float (&sx)[2][32], const float (&sm)[2][8], bool sb, int lane) {
    constexpr int NF = HI ? 2 : 0, NT = NF + 3;
    const int gt = (lane >> 2) - 2 * (lane & 3);
    const float cs = 0.08838834764831845f * 1.4426950408889634f;
    float s[2][NT][4], m[4], l[4];
#pragma unroll
    for (int h = 0; h < 2; h++) {
#pragma unroll
        for (int j = 0; j < NT; j++)
#pragma unroll
            for (int e = 0; e < 4; e++) s[h][j][e] = j == NT - 1 ? (sb ? sm[h][4 + e] : sm[h][e]) : (sb ? sx[h][16 + 4 * j + e] : sx[h][4 * j + e]);
        if (gt < 0) s[h][NF][0] = s[h][NF + 1][2] = -INFINITY;
        if (gt < 1) s[h][NF][1] = s[h][NF + 1][3] = -INFINITY;
        m[2 * h] = fmaxf(s[h][0][0], s[h][0][1]); m[2 * h + 1] = fmaxf(s[h][0][2], s[h][0][3]);
#pragma unroll
        for (int j = 1; j < NT; j++) {
            if (j != NF + 1) m[2 * h] = fmaxf(m[2 * h], fmaxf(s[h][j][0], s[h][j][1]));
            m[2 * h + 1] = fmaxf(m[2 * h + 1], fmaxf(s[h][j][2], s[h][j][3]));
        }
    }
#pragma unroll
    for (int r = 0; r < 4; r++) m[r] = fmaxf(m[r], __shfl_xor_sync(0xffffffffu, m[r], 1));
#pragma unroll
    for (int r = 0; r < 4; r++) m[r] = fmaxf(m[r], __shfl_xor_sync(0xffffffffu, m[r], 2)) * -cs;
#pragma unroll
    for (int r = 0; r < 4; r++) {
        l[r] = 0.f;
#pragma unroll
        for (int j = 0; j < NT; j++)
            if ((r & 1) || j != NF + 1) {
                float* v = &s[r >> 1][j][2 * (r & 1)];
                v[0] = ex2(fmaf(v[0], cs, m[r])); v[1] = ex2(fmaf(v[1], cs, m[r]));
                l[r] += v[0] + v[1];
            }
    }
#pragma unroll
    for (int r = 0; r < 4; r++) l[r] += __shfl_xor_sync(0xffffffffu, l[r], 1);
#pragma unroll
    for (int r = 0; r < 4; r++) { l[r] += __shfl_xor_sync(0xffffffffu, l[r], 2); asm("rcp.approx.ftz.f32 %0, %0;" : "+f"(l[r])); }
    const uint32_t ma = sb ? 0u : ~0u;
#pragma unroll
    for (int h = 0; h < 2; h++)
#pragma unroll
        for (int j = 0; j < 5; j++) {
            const bool on = j == 4 || j < NF + 2;
            const int k = j == 4 ? NT - 1 : on ? j : 0, ia = j < 4 ? 2 * j : 16, ib = j < 4 ? 8 + 2 * j : 18;
            const uint32_t x = on && j != NF + 1 ? pack_bf16(s[h][k][0] * l[2 * h], s[h][k][1] * l[2 * h]) : 0;
            const uint32_t y = on ? pack_bf16(s[h][k][2] * l[2 * h + 1], s[h][k][3] * l[2 * h + 1]) : 0;
            asm volatile("and.b32 %0, %4, %6; and.b32 %1, %5, %6; and.b32 %2, %4, %7; and.b32 %3, %5, %7;"
                : "=&r"(p[h][ia]), "=&r"(p[h][ia + 1]), "=&r"(p[h][ib]), "=&r"(p[h][ib + 1]) : "r"(x), "r"(y), "r"(ma), "r"(~ma));
        }
}
__device__ __forceinline__ void attn_pv(float (&o)[64], const uint32_t (&p)[20], uint32_t sv) {
    const uint64_t dx = mkdesc(sv, 128, 1024, 0), dm = mkdesc(sv + 16384, 128, 256, 0);
    wg_fence();
#pragma unroll
    for (int ks = 0; ks < 5; ks++) wgmma_v128(o, p[4 * ks], p[4 * ks + 1], p[4 * ks + 2], p[4 * ks + 3], ks < 4 ? dx + ks * 16 : dm, ks);
    wg_commit();
}
__device__ __forceinline__ void attn_stage(const float (&o)[64], uint32_t dst) {
#pragma unroll
    for (int u = 0; u < 16; u += 2)
        stsm4(dst + (u >> 3) * 8192 + (u & 7) * 128, pack_bf16(o[4 * u], o[4 * u + 1]), pack_bf16(o[4 * u + 2], o[4 * u + 3]),
              pack_bf16(o[4 * u + 4], o[4 * u + 5]), pack_bf16(o[4 * u + 6], o[4 * u + 7]));
}

template <int BN, int NKB, bool BLOCKED_A>
__device__ __forceinline__ void mainloop(float (&acc)[BN / 2], uint32_t sb, int wgi, uint32_t full, uint32_t empty, int& it, bool elect) {
#pragma unroll
    for (int j = 0; j < BN / 2; j++) acc[j] = 0.f;
#pragma unroll 1
    for (int k4 = 0; k4 < NKB; k4 += 4) {
#pragma unroll
        for (int st = 0; st < 4; st++, it++) {
            mbar_wait_long(full + 8 * st, (it >> 2) & 1);
            const uint64_t da = BLOCKED_A ? mkdesc(sb + st * G_STAGE + wgi * 8192, 128, 1024, 0) : mkdesc(sb + st * G_STAGE + wgi * 8192, 16, 1024, 1);
            const uint64_t db = mkdesc(sb + st * G_STAGE + 16384, 8192, 1024, 1);
            wg_fence();
#pragma unroll
            for (int k = 0; k < 4; k++) {
                if constexpr (BN == 256) wgmma256(acc, da + k * (BLOCKED_A ? 16 : 2), db + k * 128, 1);
                else wgmma128(acc, da + k * (BLOCKED_A ? 16 : 2), db + k * 128, 1);
            }
            wg_commit();
            if (k4 | st) {
                wg_wait<1>();
                if (elect) mbar_arrive(empty + 8 * ((st + 3) & 3));
            }
        }
    }
    wg_wait<0>();
    if (elect) mbar_arrive(empty + 8 * 3);
}

__device__ __forceinline__ uint32_t n6_a(int st) { return st < 4 ? st * G_STAGE : (2 * st - 8) * G_STAGE + 32768; }
__device__ __forceinline__ uint32_t n6_b(int st) { return st < 4 ? st * G_STAGE + 16384 : (2 * st - 7) * G_STAGE + 32768; }
__device__ __forceinline__ uint32_t n6_bar(int st) { return st < 4 ? 8 * st : 96 + 8 * st; }
__device__ __forceinline__ void mainloop6(float (&acc)[64], uint32_t sb, int wgi, uint32_t full, uint32_t empty, int& it, bool elect) {
#pragma unroll
    for (int j = 0; j < 64; j++) acc[j] = 0.f;
    int st = 0, prev = 0, r = 0;
#pragma unroll 1
    for (int kb = 0; kb < 64; kb++) {
        mbar_wait_long(full + n6_bar(st), ((st < 4 ? it >> 2 : 0) + r) & 1);
        const uint64_t da = mkdesc(sb + n6_a(st) + wgi * 8192, 128, 1024, 0), db = mkdesc(sb + n6_b(st), 8192, 1024, 1);
        wg_fence();
#pragma unroll
        for (int k = 0; k < 4; k++) wgmma128(acc, da + k * 16, db + k * 128, 1);
        wg_commit();
        if (kb) {
            wg_wait<1>();
            if (elect) mbar_arrive(empty + n6_bar(prev));
        }
        prev = st;
        if (++st == 6) { st = 0; r++; }
    }
    wg_wait<0>();
    if (elect) mbar_arrive(empty + 8 * 3);
    it += 44;
}

template <int BN>
__device__ __forceinline__ void o_item(uint32_t sb, int wgi, int wi, int lane, uint32_t full, uint32_t empty, int& it, const CUtensorMap* mout,
                                       int row0, int col0, uint32_t stgpar) {
    float acc[BN / 2];
    if constexpr (BN == 256) mainloop<BN, 64, true>(acc, sb, wgi, full, empty, it, lane == 0);
    else mainloop6(acc, sb, wgi, full, empty, it, lane == 0);
    ST((row0 >> 4) + (col0 / BN), wgi * 4 + wi, 10);
    mbar_wait(full + 104, stgpar);
    const uint32_t stg = sb + G_STG + (wgi * 4 + wi) * 4096;
    const int r = lane & 15, cu = lane >> 4;
#pragma unroll
    for (int hf = 0; hf < BN / 128; hf++) {
        if (elect()) asm volatile("cp.async.bulk.wait_group.read 0;" ::: "memory");
        __syncwarp();
#pragma unroll
        for (int j = 0; j < 8; j++) {
            const float* a = acc + hf * 64 + j * 8;
            stsm4(stg + (j >> 2) * 2048 + r * 128 + ((((j & 3) * 2 + cu) ^ (r & 7)) << 4),
                  pack_bf16(a[0], a[1]), pack_bf16(a[2], a[3]), pack_bf16(a[4], a[5]), pack_bf16(a[6], a[7]));
        }
        asm volatile("fence.proxy.async.shared::cta;" ::: "memory");
        __syncwarp();
        if (elect()) {
            tma2d_store(mout, stg, col0 + hf * 128, row0 + wgi * 64 + wi * 16);
            tma2d_store(mout, stg + 2048, col0 + hf * 128 + 64, row0 + wgi * 64 + wi * 16);
            asm volatile("cp.async.bulk.commit_group;" ::: "memory");
        }
    }
}

constexpr int S4_KD = 32768;
constexpr int S4_CH = 2 * G_STAGE;
constexpr int S4_HALF = 2304;
constexpr int S4_WD = 2 * S4_HALF;
constexpr int S4_T2 = S4_WD + 2304;
constexpr int S4_T3 = S4_T2 + 1024;
constexpr int S4_STRIDE = S4_T3 + 640 + 16;
__device__ __forceinline__ uint32_t addz(uint32_t x, uint32_t z) { uint32_t r; asm volatile("add.u32 %0, %1, %2;" : "=r"(r) : "r"(x), "r"(z)); return r; }
__device__ __forceinline__ uint32_t lds16(uint32_t a) { uint32_t v; asm volatile("ld.shared.u16 %0, [%1];" : "=r"(v) : "r"(a) : "memory"); return v; }
__device__ __forceinline__ uint32_t ldsu(uint32_t a) { return __float_as_uint(lds32(a)); }

template <int E0, int NE, int KP>
__device__ __forceinline__ void s4_windows(float (&acc)[8][2][4], uint32_t ut, uint32_t tw, int rho, int w, int lane, uint32_t z) {
    const int gt = (lane >> 2) - 2 * (lane & 3), p0 = rho == 16 ? -3 : -2, c = (lane >> 3) + p0;
    uint32_t band[2][4], ta[NE][4];
    {
        const uint64_t ones = ((uint64_t)((2u << 2 * w) - 1) << 32) >> (8 * p0 + 24 - gt + rho + w);
        uint32_t f[5];
#pragma unroll
        for (int m = 0; m < 5; m++) f[m] = ((((uint32_t)(ones >> (8 * m)) & 3) * 0x8001u) & 0x10001u) * 0x3F80u;
#pragma unroll
        for (int j = 0; j < 2; j++) { band[j][0] = f[2 * j + 1]; band[j][1] = addz(f[2 * j], z); band[j][2] = f[2 * j + 2]; band[j][3] = addz(f[2 * j + 1], z); }
    }
#pragma unroll
    for (int e = 0; e < NE; e++)
        asm volatile("ld.shared.u32 %0, [%4]; ld.shared.u32 %1, [%4+%5]; ld.volatile.shared.u32 %2, [%4+%6]; ld.volatile.shared.u32 %3, [%4];"
            : "=r"(ta[e][0]), "=r"(ta[e][1]), "=r"(ta[e][2]), "=r"(ta[e][3]) : "r"(tw + 16 * (E0 + e) * KP), "n"(8 * KP), "n"(-8 * KP) : "memory");
    const uint32_t ua = ut + (c & 1) * S4_HALF + (16 + (lane & 7) + (c >> 1)) * 16;
#pragma unroll
    for (int J = 0; J < 8 - E0; J++) {
        uint32_t u0[4], u1[4];
        ldsm4(u0, ua + J * 256); ldsm4(u1, ua + J * 256 + 128);
        float s0[4], s1[4];
        mma16z(s0, band[0], u0[0], u0[1]); mma16z(s1, band[0], u1[0], u1[1]);
        mma16(s0, band[1], u0[2], u0[3]); mma16(s1, band[1], u1[2], u1[3]);
        const uint32_t b00 = pack_bf16(s0[0], s0[1]), b01 = pack_bf16(s1[0], s1[1]), b10 = pack_bf16(s0[2], s0[3]), b11 = pack_bf16(s1[2], s1[3]);
#pragma unroll
        for (int e = 0; e < NE; e++)
            if (J + E0 + e < 8) { mma16(acc[J + E0 + e][0], ta[e], b00, b01); mma16(acc[J + E0 + e][1], ta[e], b10, b11); }
    }
}
template <int D0, int D1>
__device__ __forceinline__ void s4_dense(float (&acc)[8][2][4], uint32_t ua, const uint32_t (&b0)[4], const uint32_t (&b1)[4]) {
#pragma unroll
    for (int J = 0; J < 8 - D0; J++) {
        uint32_t a[4];
        ldsm4(a, ua + J * 256);
        mma16(acc[J + D0][0], a, b0[0], b0[1]); mma16(acc[J + D0][1], a, b0[2], b0[3]);
        if (J + D1 < 8) { mma16(acc[J + D1][0], a, b1[0], b1[1]); mma16(acc[J + D1][1], a, b1[2], b1[3]); }
    }
}
__device__ __forceinline__ void s4_words(uint32_t (&b)[4], uint32_t wd) {
    asm volatile("ld.shared.u32 %0, [%4]; ld.shared.u32 %1, [%4+-32]; ld.shared.u32 %2, [%4+32]; ld.volatile.shared.u32 %3, [%4];"
        : "=r"(b[0]), "=r"(b[1]), "=r"(b[2]), "=r"(b[3]) : "r"(wd) : "memory");
}

__device__ __forceinline__ void s4_item(uint32_t sb, int cw, int lane, int item, const bf16* __restrict__ dsk, uint32_t empty, const CUtensorMap* my, uint32_t stgpar,
                                        bf16* __restrict__ out, uint32_t nbar, uint32_t npar, uint32_t nslot) {
    const int gt = (lane >> 2) - 2 * (lane & 3);
    const uint32_t ch = sb + S4_CH + cw * S4_STRIDE, kd = sb + S4_KD + cw * 1536;
    const __nv_bfloat162 dk = __bfloat162bfloat162(dsk[item * 8 + cw]);
    ST(item, cw, 0);
    asm volatile("st.shared.v4.u32 [%0], {%1,%1,%1,%1};" ::"r"(ch + (lane >> 4) * S4_HALF + (lane & 15) * 16), "r"(0) : "memory");
    const uint32_t tch = sb + S4_CH + (lane & 7) * S4_STRIDE + ((lane >> 3) & 1) * S4_HALF + (16 + 16 * cw + (lane >> 4)) * 16;
#pragma unroll
    for (int i = 0; i < 8; i++) {
        uint32_t x[4];
        ldsm4t(x, sb + cw * 4096 + i * 512 + lane * 16);
        stsm4(tch + i * 32, x[0], x[1], x[2], x[3]);
    }
    const uint32_t k1024 = lds16(kd + 1024);
    {
        auto st4 = [](uint32_t a, uint32_t x, uint32_t y, uint32_t u, uint32_t v) {
            asm volatile("st.shared.v4.u32 [%0], {%1,%2,%3,%4};" ::"r"(a), "r"(x), "r"(y), "r"(u), "r"(v) : "memory");
        };
        const float4 p = lds128(kd + lane * 16);
        const uint32_t p0 = __float_as_uint(p.x), p1 = __float_as_uint(p.y), p2 = __float_as_uint(p.z), p3 = __float_as_uint(p.w);
        const uint32_t pm = lane ? ldsu(kd + lane * 16 - 4) : 0;
        const uint32_t wa = ch + S4_WD + 64 + lane * 32;
        st4(wa, __byte_perm(p0, pm, 0x7610), __byte_perm(p0, 0, 0x1032), __byte_perm(p1, p0, 0x7610), __byte_perm(p1, 0, 0x1032));
        st4(wa + 16, __byte_perm(p2, p1, 0x7610), __byte_perm(p2, 0, 0x1032), __byte_perm(p3, p2, 0x7610), __byte_perm(p3, 0, 0x1032));
        const float2 q = lds64(kd + 512 + lane * 8);
        const uint32_t q0 = __float_as_uint(q.x), q1 = __float_as_uint(q.y), q2 = ldsu(kd + 520 + lane * 8), k255 = ldsu(kd + 508);
        st4(wa + 1024, lane ? __byte_perm(q0, 0, 0x1010) : __byte_perm(q0, k255, 0x7610), __byte_perm(q0, 0, 0x1010), __byte_perm(q0, 0, 0x1032), __byte_perm(q1, q0, 0x7610));
        st4(wa + 1040, __byte_perm(q1, 0, 0x1010), __byte_perm(q1, 0, 0x1010), __byte_perm(q1, 0, 0x1032), __byte_perm(q2, q1, 0x7610));
        const uint32_t k512 = lane == 4 ? lds16(kd + 768) : 0;
        if (lane < 16) st4(ch + S4_WD + (lane < 4 ? 0 : 2048) + lane * 16, k512 * 0x10001u, k512 * 0x10001u, k512 * 0x10001u, k512 << 16);
        const float2 c = lds64(kd + 768 + lane * 8), d = lds64(kd + 760 + lane * 8);
        const uint32_t c0 = __float_as_uint(c.x), c1 = __float_as_uint(c.y), c2 = ldsu(kd + 776 + lane * 8);
        const uint32_t d0 = lane ? __float_as_uint(d.x) : 0, d1 = lane ? __float_as_uint(d.y) : 0, d2 = lane ? c0 : 0;
        st4(ch + S4_T2 + 256 + lane * 16, __byte_perm(c0, d0, 0x7632), __byte_perm(c1, d1, 0x5410), __byte_perm(c1, d1, 0x7632), __byte_perm(c2, d2, 0x5410));
        const uint32_t m = lane == 31 ? 0xFFFF0000u : 0;
        st4(ch + S4_T2 + (lane < 16 ? lane : lane == 31 ? 48 : lane + 33) * 16, c0 & m, (c1 << 16) & m, c1 & m, (c2 << 16) & m);
        const float2 e = lds64(kd + 1024 + lane * 8);
        const uint32_t e0 = __float_as_uint(e.x), e1 = __float_as_uint(e.y), e2 = ldsu(kd + 1032 + lane * 8), em = ldsu(kd + 1020 + lane * 8);
        st4(ch + S4_T3 + 128 + lane * 16, __byte_perm(e0, lane ? em : 0, 0x7632), __byte_perm(e1, lane ? e0 : 0, 0x5410), __byte_perm(e1, e0, 0x7632), __byte_perm(e2, e1, 0x5410));
        if (lane < 8) st4(ch + S4_T3 + lane * 16, 0, 0, 0, 0);
    }
    bar_sync(2, 256);
    ST(item, cw, 1);
    const uint32_t z = ldsu(ch);
    float acc[8][2][4];
#pragma unroll
    for (int j = 0; j < 16; j++) acc[j >> 1][j & 1][0] = acc[j >> 1][j & 1][1] = acc[j >> 1][j & 1][2] = acc[j >> 1][j & 1][3] = 0.f;
#pragma unroll 1
    for (int r = 1; r <= 4; r++) s4_windows<2, 3, 16>(acc, ch, ch + S4_T2 + (gt - 16) * 16 + 4 * r - 4, 4 * r, 2 - (r & 1), lane, z);
    ST(item, cw, 2);
#pragma unroll 1
    for (int r = 1; r <= 2; r++) s4_windows<4, 4, 8>(acc, ch, ch + S4_T3 + (gt - 48) * 8 + 4 * r - 4, 8 * r, 2 + r, lane, z);
    ST(item, cw, 3);
    const uint32_t ua = ch + (lane >> 4) * S4_HALF + (16 + (lane & 15)) * 16, wd = ch + S4_WD + 64 + gt * 4;
#pragma unroll 1
    for (int q = 0; q < 2; q++) {
        uint32_t b0[4], b1[4];
        s4_words(b0, wd + (q + 32) * 64);
#pragma unroll
        for (int j = 0; j < 4; j++) {
            const int x = 16 * q + gt + (j == 1 ? -8 : j == 2 ? 8 : 0) - 3;
            b1[j] = addz(((unsigned)x < 2u ? k1024 : 0u) | ((unsigned)(x - 1) < 2u ? k1024 << 16 : 0u), z);
        }
        s4_dense<2, 4>(acc, ua - q * 16, b0, b1);
    }
    {
        uint32_t b0[4], b1[4], c0[4], c1[4];
        s4_words(b0, wd); s4_words(b1, wd + 1024);
#pragma unroll 1
        for (int q = 0; q < 16; q += 2) {
            s4_words(c0, wd + q * 64 + 64); s4_words(c1, wd + q * 64 + 64 + 1024);
            s4_dense<0, 1>(acc, ua - q * 16, b0, b1);
            s4_words(b0, wd + q * 64 + 128); s4_words(b1, wd + q * 64 + 128 + 1024);
            s4_dense<0, 1>(acc, ua - q * 16 - 16, c0, c1);
            if (q == S4REL && lane == 0) { mbar_arrive(empty); mbar_arrive(empty + 8); }
        }
    }
    ST(item, cw, 4);
    mbar_wait(empty + 72, stgpar);
    if (elect()) asm volatile("cp.async.bulk.wait_group.read 0;" ::: "memory");
    __syncwarp();
#pragma unroll
    for (int I = 0; I < 8; I++) {
        uint32_t u[4];
        ldsm4(u, ua + I * 256);
#pragma unroll
        for (int j = 0; j < 4; j++) {
            const uint32_t y = pack_bf16(acc[I][j >> 1][2 * (j & 1)], acc[I][j >> 1][2 * (j & 1) + 1]);
            const __nv_bfloat162 r = __hadd2_rn(*(const __nv_bfloat162*)&y, __hmul2_rn(*(const __nv_bfloat162*)&u[j], dk));
            u[j] = *(const uint32_t*)&r;
        }
        stsm4(ua + I * 256, u[0], u[1], u[2], u[3]);
    }
    bar_sync(2, 256);
    uint32_t y[8][4];
#pragma unroll
    for (int i = 0; i < 8; i++) ldsm4t(y[i], tch + i * 32);
    if (cw < S4DIR && mbar_test(nbar, npar) && ldsu(nslot) == (IT_END << 16)) {
        uint32_t* const dst = (uint32_t*)(out + (size_t)(cw * 256 + (lane >> 2)) * (2 * DM) + DM + item * 8) + (lane & 3);
#pragma unroll
        for (int i = 0; i < 32; i++) dst[i * 8 * DM] = y[i >> 2][i & 3];
        return;
    }
#pragma unroll
    for (int i = 0; i < 8; i++) stsm4(sb + G_STG + cw * 4096 + i * 512 + lane * 16, y[i][0], y[i][1], y[i][2], y[i][3]);
    asm volatile("fence.proxy.async.shared::cta;" ::: "memory");
    __syncwarp();
    if (elect()) {
        mbar_arrive(empty + 16); mbar_arrive(empty + 24);
        tma2d_store(my, sb + G_STG + cw * 4096, DM + item * 8, cw * 256);
        asm volatile("cp.async.bulk.commit_group;" ::: "memory");
    }
    ST(item, cw, 5);
}

struct Maps { CUtensorMap m[13]; };
__global__ void __launch_bounds__(384, 1)
worker_kernel(const __grid_constant__ Maps M, const bf16* __restrict__ dsk, bf16* __restrict__ out) {
    const CUtensorMap &mx = M.m[0], &mq = M.m[1], &mo = M.m[4], &mout = M.m[5], &mu = M.m[6], &my = M.m[7];
    extern __shared__ unsigned char smem_raw[];
    const uint32_t sb = (smem_u32(smem_raw) + 1023) & ~1023u;
    const uint32_t full = sb + G_BAR, empty = full + 32, ifull = full + 64, iempty = full + 80, islot = full + 96, stgbar = full + 104, sigbar = full + 112, sigslot = full + 120;
    const int tid = threadIdx.x, wg = tid >> 7, lane = tid & 31;
    int q0 = blockIdx.x;
    const int nfirst = min(32, (int)gridDim.x - 96), wide0 = q0 - ((int)gridDim.x - O_WIDE * 4);
    if (tid == 0 && q0 >= nfirst && wide0 < 0) q0 = nfirst + atomicAdd(g_ctr + C_NEXT, 1);
    if (tid >= 32 && tid < 50) {
        const int j = tid - 32;
        mbar_init(j < 12 ? full + (j >= 6 ? 32 : 0) + n6_bar(j >= 6 ? j - 6 : j) : j < 16 ? ifull + 8 * (j - 12) : stgbar + 8 * (j - 16),
                  (j >= 6 && j < 12) || j == 14 || j == 15 || j == 17 ? 8 : 1);
        asm volatile("fence.proxy.async.shared::cta;" ::: "memory");
    }
    if (tid >= 64 && tid < 77) asm volatile("prefetch.tensormap [%0];" ::"l"(&M.m[tid - 64]) : "memory");
    __syncthreads();
    if (wg == 0) {
        reg_dec<40>();
        if (tid >= 32 && tid < 64) {
            for (int n = 0;; n++) {
                mbar_wait_long(sigbar, n & 1);
                int item; asm volatile("ld.shared.u32 %0, [%1];" : "=r"(item) : "r"(sigslot + 4 * (n & 1)) : "memory");
                const int type = item >> 16, b = (item >> 8) & 255, i = item & 255;
                if (type == IT_END) break;
                if (type == IT_QA) {
                    if (elect()) {
#pragma unroll
                        for (int j = 0; j < 8; j++) {
                            const uint32_t src = sb + (j >= 4 ? G_STG + (j & 1) * 16384 : 3 * G_STAGE + (j & 1) * 20480) + ((j >> 1) & 1) * 8192;
                            asm volatile("cp.async.bulk.global.shared::cta.bulk_group [%0], [%1], 8192;"
                                ::"l"(g_ox + (size_t)(b * 64 + i * 4 + ((j >> 1) ^ 2)) * 8192 + (j & 1) * 4096), "r"(src) : "memory");
                            if ((j & 3) == 3) asm volatile("cp.async.bulk.commit_group;" ::: "memory");
                        }
                        asm volatile("cp.async.bulk.wait_group.read 1;" ::: "memory");
                        asm volatile("mbarrier.arrive.shared.b64 _, [%0], 8;" ::"r"(empty + 24) : "memory");
                        asm volatile("cp.async.bulk.wait_group 0;" ::: "memory");
                        mbar_arrive(stgbar);
                        asm volatile("fence.proxy.async.global;" ::: "memory");
                    }
                    __syncwarp();
                }
                if (type == IT_KV) { if (lane < 6) red_release(g_kvf + ((i & 15) * 6 + lane) * 16 + b, 1); }
                else if (lane == 0) red_release(g_ctr + C_QA_DONE + b, 1 << i);
            }
        } else if (tid < 32) {
            int it = 0;
            bool tables = false;
            if (!KVN) asm volatile("griddepcontrol.wait;" ::: "memory");
            for (int n = 0;; n++) {
                int item = 0;
                if (lane == 0) {
                    if (n) q0 = nfirst + atomicAdd(g_ctr + C_NEXT, 1);
                    item = n == 0 && wide0 >= 0 ? (IT_O << 16) | ((wide0 >> 2) << 8) | (wide0 & 3) : queue_item(q0);
                }
                item = __shfl_sync(0xffffffffu, item, 0);
                mbar_wait(iempty + 8 * (n & 1), ((n >> 1) & 1) ^ 1);
                if (lane == 0) {
                    asm volatile("st.shared.u32 [%0], %1;" ::"r"(islot + 4 * (n & 1)), "r"(item) : "memory");
                    mbar_arrive(ifull + 8 * (n & 1));
                }
                const int type = item >> 16, b = (item >> 8) & 255, i = item & 255;
                bool ready = false;
                if (type == IT_QA || type == IT_KV) {
                    const CUtensorMap* mw = &mq + (type == IT_QA ? 0 : 1 + (i >> 4));
#pragma unroll 1
                    for (int kb = 0; kb < 16; kb++, it++) {
                        const int st = it & 3;
                        mbar_wait(empty + 8 * st, ((it >> 2) & 1) ^ 1);
                        if (elect()) {
                            mbar_expect(full + 8 * st, G_STAGE);
                            tma2d(sb + st * G_STAGE, &mx, kb * 64, b * 128, full + 8 * st);
                            tma3d(sb + st * G_STAGE + 16384, mw, 0, kb * 64, (i & 15) * 4, full + 8 * st);
                        }
                        if (type == IT_QA && kb == 3) ready = __all_sync(0xffffffffu, ld_acq(g_ctr + C_CHAIN + b) >= 96);
                        if (ready && kb < 11 && elect()) {
                            const size_t sh = (b * 4 + ((kb - 3) & 3)) * NH + i * 2;
                            asm volatile("cp.async.bulk.prefetch.L2.global [%0], 16384;" ::"l"((kb >= 7 ? g_vx : g_kx) + sh * 4096) : "memory");
                            asm volatile("cp.async.bulk.prefetch.L2.global [%0], 4096;" ::"l"((kb >= 7 ? g_vm : g_km) + sh * 1024) : "memory");
                        }
                    }
                }
                if (type == IT_QA) {
                    if (!ready) wait_ctr(g_ctr + C_CHAIN + b, 96);
                    tables = true;
                    asm volatile("fence.proxy.async.global;" ::: "memory");
#pragma unroll 1
                    for (int st = 0; st < 4; st++, it++) {
                        mbar_wait(empty + 8 * st, ((it >> 2) & 1) ^ 1);
                        if (elect()) {
                            mbar_expect(full + 8 * st, 4 * 10240);
#pragma unroll
                            for (int j = 0; j < 4; j++)
                                tma3d(sb + st * G_STAGE + (j >> 1) * 20480 + (j & 1) * 16384, &M.m[8 + (st >> 1) + (j & 1) * 2], 0, b * 4 + (j & 2),
                                      (i * 2 + (st & 1)) * 16, full + 8 * st);
                        }
                    }
                } else if (type == IT_O) {
                    const bool wide = b < O_WIDE;
                    const CUtensorMap* mw = wide ? &mo : &M.m[12];
                    int done = 0;
                    const int ns = wide ? 4 : 6;
#pragma unroll 1
                    for (int kb = 0, st = 0, r = 0; kb < 64; kb++) {
                        const uint32_t bo = n6_bar(st);
                        mbar_wait(empty + bo, (((st < 4 ? it >> 2 : 0) + r) & 1) ^ 1);
                        if (elect()) {
                            mbar_expect(full + bo, wide ? G_STAGE : 32768);
                            tma3d(sb + n6_b(st), mw, 0, kb * 64, wide ? i * 4 : i * 2, full + bo);
                        }
                        if (!(done >> (kb >> 2) & 1)) {
#pragma unroll 1
                            for (int sp = 0; sp < (1 << 20) && !((done = __shfl_sync(0xffffffffu, ld_acq(g_ctr + C_QA_DONE + b), 0)) >> (kb >> 2) & 1); sp++)
                                __nanosleep(64);
                            asm volatile("fence.proxy.async.global;" ::: "memory");
                        }
                        if (elect()) bulk_load(sb + n6_a(st), g_ox + (size_t)(b * 64 + kb) * 8192, 16384, full + bo);
                        if (++st == ns) { st = 0; r++; }
                    }
                    it += wide ? 64 : 44;
                } else if (type == IT_S4) {
                    mbar_wait(empty, ((it >> 2) & 1) ^ 1);
                    if (elect()) {
                        mbar_expect(full, 32768 + 12288);
#pragma unroll
                        for (int j = 0; j < 8; j++) tma2d(sb + j * 4096, &mu, i * 8, j * 256, full);
                    }
                    if (!tables) { wait_ctr(g_ctr + C_CHAIN, 96); asm volatile("fence.proxy.async.global;" ::: "memory"); }
                    tables = true;
                    if (elect()) bulk_load(sb + S4_KD, g_kd + i * 8 * 768, 12288, full);
#pragma unroll 1
                    for (int st = 1; st < 4; st++) { mbar_wait(empty + 8 * st, ((it >> 2) & 1) ^ 1); if (lane == 0) mbar_arrive(full + 8 * st); }
                    it += 4;
                    mbar_wait_long(empty, ((it >> 2) & 1) ^ 1);
                }
                if (item >> 16 == IT_END) break;
            }
            asm volatile("griddepcontrol.wait;" ::: "memory");
        }
    } else {
        reg_inc<232>();
        const int wu = __shfl_sync(0xffffffffu, tid >> 5, 0);
        const int wgi = (wu >> 2) - 1, wi = wu & 3;
        int it = 0, nqa = 0, nsig = 0, n = 0, item;
        auto next_item = [&]() {
            mbar_wait_long(ifull + 8 * (n & 1), (n >> 1) & 1);
            asm volatile("ld.shared.u32 %0, [%1];" : "=r"(item) : "r"(islot + 4 * (n & 1)) : "memory");
            __syncwarp();
            if (lane == 0) mbar_arrive(iempty + 8 * (n & 1));
        };
        auto signal = [&](int what) {
            if (tid == 128) asm volatile("st.shared.u32 [%0], %1;" ::"r"(sigslot + 4 * (nsig & 1)), "r"(what) : "memory");
            __syncwarp();
            if (lane == 0) mbar_arrive(sigbar);
            nsig++;
        };
        next_item();
        if (item >> 16 == IT_KV) {
            float acc[128];
            uint32_t pk[64];
            uint32_t* dst = nullptr;
            int prev = 0;
            do {
                WLOG(0);
#pragma unroll
                for (int kb = 0; kb < 16; kb++, it++) {
                    const int st = kb & 3;
                    mbar_wait(full + 8 * st, (it >> 2) & 1);
                    const uint64_t da = mkdesc(sb + st * G_STAGE + wgi * 8192, 16, 1024, 1);
                    const uint64_t db = mkdesc(sb + st * G_STAGE + 16384, 8192, 1024, 1);
                    wg_fence();
#pragma unroll
                    for (int k = 0; k < 4; k++) wgmma256(acc, da + k * 2, db + k * 128, kb | k);
                    wg_commit();
                    if (n <= KVI) {
                        if (kb < KVF && dst) {
#pragma unroll
                            for (int j = kb * (64 / KVF); j < (kb + 1) * (64 / KVF); j++) st_out(dst + (j >> 1) * 128 + (j & 1) * 32, pk[j]);
                            if (kb == KVF - 1) signal(prev);
                        }
                    } else if (kb < KVS) {
#pragma unroll
                        for (int j = kb * (64 / KVS); j < (kb + 1) * (64 / KVS); j++) st_out(dst + (j >> 1) * 128 + (j & 1) * 32, pk[j]);
                        if (kb == KVS - 1) signal(prev);
                    }
                    if (kb > 0) {
                        wg_wait<1>();
                        if (lane == 0) mbar_arrive(empty + 8 * ((kb - 1) & 3));
                    }
                }
                wg_wait<0>();
                if (lane == 0) mbar_arrive(empty + 8 * 3);
#pragma unroll
                for (int j = 0; j < 64; j++) pk[j] = pack_bf16(acc[2 * j], acc[2 * j + 1]);
                const int row = ((item >> 8) & 255) * 128 + wgi * 64 + wi * 16, nt = item & 255;
                dst = (uint32_t*)(nt < 16 ? g_kx : g_vx) + (size_t)((row >> 5) * 512 + (nt & 15) * 32) * 128 + (row & 31) * 4 + lane;
                prev = item;
                WLOG(1);
                n++;
                next_item();
            } while (item >> 16 == IT_KV);
            if (dst) {
#pragma unroll
                for (int j = 0; j < 64; j++) dst[(j >> 1) * 128 + (j & 1) * 32] = pk[j];
                signal(prev);
            }
        }
        for (;; n++, next_item()) {
            const int type = item >> 16, b = (item >> 8) & 255, i = item & 255;
            const int lane = (tid & 31) + (item >> 24), wgi = (wu >> 2) - 1 + __shfl_sync(0xffffffffu, item >> 24, 0), wi = wu & 3;
            WLOG(0);
            if (type == IT_QA) {
                float acc[128];
                ST(sid, cw, 0);
                ST(sid, cw, 1);
                mainloop<256, 16, false>(acc, sb, wgi, full, empty, it, lane == 0);
                ST(sid, cw, 2);
                uint32_t q0[32], q1[32];
#pragma unroll
                for (int j = 0; j < 32; j++) q0[j] = pack_bf16(acc[2 * j], acc[2 * j + 1]);
                const uint32_t par = (it >> 2) & 1, so = sb + wgi * 20480;
                float sx[2][32] = {}, sm[2][8] = {};
                uint32_t p[2][20];
                mbar_wait_long(full, par);
                ST(sid, cw, 3);
                if (PING && wgi == 0) bar_sync(5, 256);
                attn_scores(sx[0], sm[0], q0, so);
                ST(sid, cw, 7);
#pragma unroll
                for (int j = 0; j < 32; j++) asm volatile("cvt.rn.bf16x2.f32 %0, %1, %2;" : "=r"(q1[j]) : "f"(acc[65 + 2 * j]), "f"(acc[64 + 2 * j]));
                mbar_wait(full + 8, par);
                attn_scores(sx[1], sm[1], q1, so + G_STAGE);
                if (PING && wgi == 1) bar_arrive(5, 256);
                if (elect()) asm volatile("cp.async.bulk.wait_group.read 0;" ::: "memory");
                mbar_wait(stgbar, (nqa++ & 1) ^ 1);
                bar_sync(3 + wgi, 128);
                float o0[64] = {}, o1[64] = {};
                wg_wait<0>();
                ST(sid, cw, 9);
                if (lane == 0) { mbar_arrive(empty); mbar_arrive(empty + 8); }
                if (wi & 1) attn_softmax<true>(p, sx, sm, wi >= 2, lane);
                else attn_softmax<false>(p, sx, sm, wi >= 2, lane);
                ST(sid, cw, 10);
                mbar_wait(full + 16, par);
                attn_pv(o0, p[0], so + 2 * G_STAGE);
                mbar_wait(full + 24, par);
                attn_pv(o1, p[1], so + 3 * G_STAGE);
                wg_wait<1>();
                if (lane == 0) mbar_arrive(empty + 16);
                ST(sid, cw, 5);
                const uint32_t da = (wi * 2 + ((lane >> 3) & 1)) * 1024 + (lane >> 4) * 128 + (lane & 7) * 16;
                attn_stage(o0, sb + G_STG + wgi * 16384 + da);
                wg_wait<0>();
                bar_sync(3 + wgi, 128);
                attn_stage(o1, so + 3 * G_STAGE + da);
                asm volatile("fence.proxy.async.shared::cta;" ::: "memory");
                ST(sid, cw, 6);
                signal(item);
                it += 4;
            } else if (type == IT_O) {
                ST(b * 8 + i, wgi * 4 + wi, 8);
                mbar_wait_long(full, (it >> 2) & 1);
                ST(b * 8 + i, wgi * 4 + wi, 9);
                if (b < O_WIDE) o_item<256>(sb, wgi, wi, lane, full, empty, it, &mout, b * 128, i * 256, (nqa & 1) ^ 1);
                else o_item<128>(sb, wgi, wi, lane, full, empty, it, &mout, b * 128, i * 128, (nqa & 1) ^ 1);
            } else if (type == IT_S4) {
                mbar_wait_long(full, (it >> 2) & 1);
                mbar_wait(full + 24, (it >> 2) & 1);
                s4_item(sb, wgi * 4 + wi, lane, i, dsk, empty, &my, (nqa & 1) ^ 1, out, ifull + 8 * ((n + 1) & 1), ((n + 1) >> 1) & 1, islot + 4 * ((n + 1) & 1));
                it += 4;
            } else break;
            WLOG(1);
        }
        bar_sync(2, 256);
        signal(item);
        if (elect()) asm volatile("cp.async.bulk.wait_group 0;" ::: "memory");
    }
}

typedef CUresult (*EncodeFn)(CUtensorMap*, CUtensorMapDataType, cuuint32_t, void*, const cuuint64_t*, const cuuint64_t*, const cuuint32_t*,
                             const cuuint32_t*, CUtensorMapInterleave, CUtensorMapSwizzle, CUtensorMapL2promotion, CUtensorMapFloatOOBfill);
static EncodeFn get_encode() {
    void* fn = nullptr; cudaDriverEntryPointQueryResult st;
    cudaGetDriverEntryPoint("cuTensorMapEncodeTiled", &fn, cudaEnableDefault, &st);
    return (EncodeFn)fn;
}
static void map_act(EncodeFn enc, CUtensorMap* m, const void* p, int rows, int cols, int boxr) {
    cuuint64_t dim[2] = {(cuuint64_t)cols, (cuuint64_t)rows}, str[1] = {(cuuint64_t)cols * 2};
    cuuint32_t box[2] = {64, (cuuint32_t)boxr}, es[2] = {1, 1};
    enc(m, CU_TENSOR_MAP_DATA_TYPE_BFLOAT16, 2, (void*)p, dim, str, box, es, CU_TENSOR_MAP_INTERLEAVE_NONE, CU_TENSOR_MAP_SWIZZLE_128B,
        CU_TENSOR_MAP_L2_PROMOTION_L2_128B, CU_TENSOR_MAP_FLOAT_OOB_FILL_NONE);
}
static void map_w(EncodeFn enc, CUtensorMap* m, const void* p, int k, int n, int groups = 4) {
    cuuint64_t dim[3] = {64, (cuuint64_t)k, (cuuint64_t)n / 64}, str[2] = {(cuuint64_t)n * 2, 128};
    cuuint32_t box[3] = {64, 64, (cuuint32_t)groups}, es[3] = {1, 1, 1};
    enc(m, CU_TENSOR_MAP_DATA_TYPE_BFLOAT16, 3, (void*)p, dim, str, box, es, CU_TENSOR_MAP_INTERLEAVE_NONE, CU_TENSOR_MAP_SWIZZLE_128B,
        CU_TENSOR_MAP_L2_PROMOTION_L2_256B, CU_TENSOR_MAP_FLOAT_OOB_FILL_NONE);
}

static void map_kv(EncodeFn enc, CUtensorMap* m, void* p, int n) {
    cuuint64_t dim[3] = {(cuuint64_t)n, NSEG, 512}, str[2] = {(cuuint64_t)n * 1024, (cuuint64_t)n * 2};
    cuuint32_t box[3] = {(cuuint32_t)n, 2, 16}, es[3] = {1, 1, 1};
    enc(m, CU_TENSOR_MAP_DATA_TYPE_BFLOAT16, 3, p, dim, str, box, es, CU_TENSOR_MAP_INTERLEAVE_NONE, CU_TENSOR_MAP_SWIZZLE_NONE,
        CU_TENSOR_MAP_L2_PROMOTION_NONE, CU_TENSOR_MAP_FLOAT_OOB_FILL_NONE);
}
static void map_box(EncodeFn enc, CUtensorMap* m, const void* p, int rows, int ld, int boxc, int boxr, CUtensorMapSwizzle sw,
                    CUtensorMapL2promotion promo = CU_TENSOR_MAP_L2_PROMOTION_NONE) {
    cuuint64_t dim[2] = {(cuuint64_t)ld, (cuuint64_t)rows}, str[1] = {(cuuint64_t)ld * 2};
    cuuint32_t box[2] = {(cuuint32_t)boxc, (cuuint32_t)boxr}, es[2] = {1, 1};
    enc(m, CU_TENSOR_MAP_DATA_TYPE_BFLOAT16, 2, (void*)p, dim, str, box, es, CU_TENSOR_MAP_INTERLEAVE_NONE, sw,
        promo, CU_TENSOR_MAP_FLOAT_OOB_FILL_NONE);
}

extern "C" void kernel_launch(void* const* d_in, const int* in_sizes, int n_in, void* d_out, int out_size) {
    const bf16* x = (const bf16*)d_in[0];
    const bf16* mem0 = (const bf16*)d_in[1];
    const bf16 *Wq = (const bf16*)d_in[2], *Wk = (const bf16*)d_in[3], *Wv = (const bf16*)d_in[4], *Wo = (const bf16*)d_in[5];
    static EncodeFn enc = nullptr;
    static int nsm = 0;
    static void* kv[4];
    if (!enc) {
        enc = get_encode();
        cudaGetSymbolAddress(&kv[0], g_kx); cudaGetSymbolAddress(&kv[1], g_vx); cudaGetSymbolAddress(&kv[2], g_km); cudaGetSymbolAddress(&kv[3], g_vm);
        cudaDeviceGetAttribute(&nsm, cudaDevAttrMultiProcessorCount, 0);
        cudaFuncSetAttribute(chain_kernel, cudaFuncAttributeMaxDynamicSharedMemorySize, CH_SMEM);
        cudaFuncSetAttribute(worker_kernel, cudaFuncAttributeMaxDynamicSharedMemorySize, G_SMEM);
    }
    Maps M;
    CUtensorMap &mx = M.m[0], &mq = M.m[1], &mk = M.m[2], &mv = M.m[3], &mo = M.m[4], &mout = M.m[5], &mu = M.m[6], &my = M.m[7];
    map_act(enc, &mx, x, S_LEN, DM, 128);
    map_w(enc, &mq, Wq, DM, HD); map_w(enc, &mk, Wk, DM, HD); map_w(enc, &mv, Wv, DM, HD); map_w(enc, &mo, Wo, HD, DM);
    map_w(enc, &M.m[12], Wo, HD, DM, 2);
    map_box(enc, &mout, d_out, S_LEN, 2 * DM, 64, 16, CU_TENSOR_MAP_SWIZZLE_128B);
    map_box(enc, &mu, d_in[7], S_LEN, DM, 8, 256, CU_TENSOR_MAP_SWIZZLE_NONE, (CUtensorMapL2promotion)PROMU);
    map_box(enc, &my, d_out, S_LEN, 2 * DM, 8, 256, CU_TENSOR_MAP_SWIZZLE_NONE);
    for (int i = 0; i < 4; i++) map_kv(enc, &M.m[8 + i], kv[i], i < 2 ? 256 : 64);
    CUtensorMap cq, ck, cv, co;
    map_box(enc, &cq, Wq, DM, HD, 32, 32, CU_TENSOR_MAP_SWIZZLE_64B, (CUtensorMapL2promotion)PROMO); map_box(enc, &ck, Wk, DM, HD, 32, 32, CU_TENSOR_MAP_SWIZZLE_64B, (CUtensorMapL2promotion)PROMO);
    map_box(enc, &cv, Wv, DM, HD, 32, 32, CU_TENSOR_MAP_SWIZZLE_64B, (CUtensorMapL2promotion)PROMO); map_box(enc, &co, Wo, HD, DM, 32, 16, CU_TENSOR_MAP_SWIZZLE_64B, (CUtensorMapL2promotion)PROMO);
    S4Params P = {(const bf16*)d_in[8], (const bf16*)d_in[9], (const bf16*)d_in[10], (const bf16*)d_in[11],
                  (const bf16*)d_in[12], (const bf16*)d_in[13], (const bf16*)d_in[14], (const bf16*)d_in[15]};
    int aware = 1;
    cudaLaunchAttribute at[1];
    at[0].id = cudaLaunchAttributeProgrammaticStreamSerialization;
    at[0].val.programmaticStreamSerializationAllowed = 1;
    cudaLaunchConfig_t cfg = {};
    cfg.stream = cudaStreamPerThread;
    cfg.gridDim = dim3(96); cfg.blockDim = dim3(CH_THREADS); cfg.dynamicSmemBytes = CH_SMEM;
    cudaLaunchKernelEx(&cfg, chain_kernel, cq, ck, cv, co, Wq, Wk, Wv, mem0, P, aware);
    cfg.attrs = at; cfg.numAttrs = 1;
    cfg.gridDim = dim3(nsm); cfg.blockDim = dim3(384); cfg.dynamicSmemBytes = G_SMEM;
    cudaLaunchKernelEx(&cfg, worker_kernel, M, P.dsk, (bf16*)d_out);
}
```

```cpp
#include <cuda.h>
#include <cuda_runtime.h>
#include <cuda_bf16.h>
#include <stdint.h>
#include <stdio.h>
#include <string.h>

typedef __nv_bfloat16 bf16;

constexpr int S_LEN = 2048, DM = 1024, NH = 32, DH = 128, HD = 4096, NSEG = 64;
constexpr uint32_t SENT = 0xFFFFFFFFu;
constexpr int SPIN_LIMIT = 1 << 18;
#define REALL 0

__device__ __align__(1024) bf16 g_kx[S_LEN * HD];
__device__ __align__(1024) bf16 g_vx[S_LEN * HD];
__device__ __align__(1024) bf16 g_ox[S_LEN * HD];
__device__ __align__(1024) bf16 g_km[NSEG * NH * 8 * DH];
__device__ __align__(1024) bf16 g_vm[NSEG * NH * 8 * DH];
__device__ __align__(1024) bf16 g_kd[DM * 768 + 8192];
__device__ __align__(1024) char g_ring[2 << 20];
__device__ int g_kvf[96 * 16];
constexpr int C_NEXT = 0, C_CHAIN = 32, C_QA_DONE = 64, N_CTR = 96;
__device__ int g_ctr[N_CTR];

__device__ __forceinline__ uint32_t smem_u32(const void* p) { return (uint32_t)__cvta_generic_to_shared(p); }
__device__ __forceinline__ uint32_t clk() { uint32_t c; asm volatile("mov.u32 %0, %%clock;" : "=r"(c)::"memory"); return c; }
__device__ __forceinline__ uint32_t pack_bf16(float lo, float hi) {
    uint32_t r; asm("cvt.rn.bf16x2.f32 %0, %1, %2;" : "=r"(r) : "f"(hi), "f"(lo)); return r;
}
__device__ __forceinline__ uint32_t movm(uint32_t a) {
    uint32_t d; asm volatile("movmatrix.sync.aligned.m8n8.trans.b16 %0, %1;" : "=r"(d) : "r"(a)); return d;
}
__device__ __forceinline__ void mma16(float (&d)[4], const uint32_t (&a)[4], uint32_t b0, uint32_t b1) {
    asm volatile("mma.sync.aligned.m16n8k16.row.col.f32.bf16.bf16.f32 {%0,%1,%2,%3}, {%4,%5,%6,%7}, {%8,%9}, {%0,%1,%2,%3};"
        : "+f"(d[0]), "+f"(d[1]), "+f"(d[2]), "+f"(d[3]) : "r"(a[0]), "r"(a[1]), "r"(a[2]), "r"(a[3]), "r"(b0), "r"(b1));
}
__device__ __forceinline__ void mma16z(float (&d)[4], const uint32_t (&a)[4], uint32_t b0, uint32_t b1) {
    asm volatile("mma.sync.aligned.m16n8k16.row.col.f32.bf16.bf16.f32 {%0,%1,%2,%3}, {%4,%5,%6,%7}, {%8,%9}, {%10,%10,%10,%10};"
        : "=f"(d[0]), "=f"(d[1]), "=f"(d[2]), "=f"(d[3]) : "r"(a[0]), "r"(a[1]), "r"(a[2]), "r"(a[3]), "r"(b0), "r"(b1), "f"(0.f));
}
__device__ __forceinline__ void mma8z(float (&d)[4], uint32_t a0, uint32_t a1, uint32_t b0) {
    asm volatile("mma.sync.aligned.m16n8k8.row.col.f32.bf16.bf16.f32 {%0,%1,%2,%3}, {%4,%5}, {%6}, {%7,%7,%7,%7};"
        : "=f"(d[0]), "=f"(d[1]), "=f"(d[2]), "=f"(d[3]) : "r"(a0), "r"(a1), "r"(b0), "f"(0.f));
}
__device__ __forceinline__ void ldsm4t(uint32_t (&r)[4], uint32_t addr) {
    asm volatile("ldmatrix.sync.aligned.m8n8.x4.trans.shared.b16 {%0,%1,%2,%3}, [%4];"
        : "=r"(r[0]), "=r"(r[1]), "=r"(r[2]), "=r"(r[3]) : "r"(addr) : "memory");
}
__device__ __forceinline__ void ldsm4(uint32_t (&r)[4], uint32_t addr) {
    asm volatile("ldmatrix.sync.aligned.m8n8.x4.shared.b16 {%0,%1,%2,%3}, [%4];"
        : "=r"(r[0]), "=r"(r[1]), "=r"(r[2]), "=r"(r[3]) : "r"(addr) : "memory");
}
__device__ __forceinline__ float lds32(uint32_t a) {
    float v; asm volatile("ld.shared.f32 %0, [%1];" : "=f"(v) : "r"(a) : "memory"); return v;
}
__device__ __forceinline__ void st_async1(uint32_t dst, float v, uint32_t bar) {
    asm volatile("st.async.shared::cluster.mbarrier::complete_tx::bytes.f32 [%0], %1, [%2];" ::"r"(dst), "f"(v), "r"(bar) : "memory");
}
__device__ __forceinline__ void st_async2(uint32_t dst, float x, float y, uint32_t bar) {
    asm volatile("st.async.shared::cluster.mbarrier::complete_tx::bytes.v2.f32 [%0], {%1,%2}, [%3];" ::"r"(dst), "f"(x), "f"(y), "r"(bar) : "memory");
}
__device__ __forceinline__ void mma8(float (&d)[4], uint32_t a0, uint32_t a1, uint32_t b0) {
    asm volatile("mma.sync.aligned.m16n8k8.row.col.f32.bf16.bf16.f32 {%0,%1,%2,%3}, {%4,%5}, {%6}, {%0,%1,%2,%3};"
        : "+f"(d[0]), "+f"(d[1]), "+f"(d[2]), "+f"(d[3]) : "r"(a0), "r"(a1), "r"(b0));
}
__device__ __forceinline__ void cp16(uint32_t dst, const void* src) {
    asm volatile("cp.async.cg.shared.global [%0], [%1], 16;" ::"r"(dst), "l"(src) : "memory");
}
__device__ __forceinline__ void sts128(uint32_t a, const float (&v)[4]) {
    asm volatile("st.shared.v4.f32 [%0], {%1,%2,%3,%4};" ::"r"(a), "f"(v[0]), "f"(v[1]), "f"(v[2]), "f"(v[3]) : "memory");
}
__device__ __forceinline__ float4 lds128(uint32_t a) {
    float4 v; asm volatile("ld.shared.v4.f32 {%0,%1,%2,%3}, [%4];" : "=f"(v.x), "=f"(v.y), "=f"(v.z), "=f"(v.w) : "r"(a) : "memory"); return v;
}
__device__ __forceinline__ void sts64(uint32_t a, float x, float y) {
    asm volatile("st.shared.v2.f32 [%0], {%1,%2};" ::"r"(a), "f"(x), "f"(y) : "memory");
}
__device__ __forceinline__ float2 lds64(uint32_t a) {
    float2 v; asm volatile("ld.shared.v2.f32 {%0,%1}, [%2];" : "=f"(v.x), "=f"(v.y) : "r"(a) : "memory"); return v;
}
__device__ __forceinline__ void bar_sync(int id, int n) { asm volatile("bar.sync %0, %1;" ::"r"(id), "r"(n) : "memory"); }
__device__ __forceinline__ void bar_arrive(int id, int n) { asm volatile("bar.arrive %0, %1;" ::"r"(id), "r"(n) : "memory"); }
__device__ __forceinline__ uint32_t mapa(uint32_t a, uint32_t r) {
    uint32_t o; asm("mapa.shared::cluster.u32 %0, %1, %2;" : "=r"(o) : "r"(a), "r"(r)); return o;
}
__device__ __forceinline__ void st_async4(uint32_t dst, float4 v, uint32_t bar) {
    asm volatile("st.async.shared::cluster.mbarrier::complete_tx::bytes.v4.f32 [%0], {%1,%2,%3,%4}, [%5];"
        ::"r"(dst), "f"(v.x), "f"(v.y), "f"(v.z), "f"(v.w), "r"(bar) : "memory");
}
__device__ __forceinline__ void mbar_init(uint32_t bar, int n) { asm volatile("mbarrier.init.shared.b64 [%0], %1;" ::"r"(bar), "r"(n) : "memory"); }
__device__ __forceinline__ void mbar_expect(uint32_t bar, int bytes) {
    asm volatile("mbarrier.arrive.expect_tx.shared.b64 _, [%0], %1;" ::"r"(bar), "r"(bytes) : "memory");
}
__device__ __forceinline__ void bulk_load(uint32_t dst, const void* src, int bytes, uint32_t bar) {
    asm volatile("cp.async.bulk.shared::cluster.global.mbarrier::complete_tx::bytes [%0], [%1], %2, [%3];"
        ::"r"(dst), "l"(src), "r"(bytes), "r"(bar) : "memory");
}
__device__ __forceinline__ bool mbar_try(uint32_t bar, uint32_t par) {
    uint32_t ok;
    asm volatile("{.reg .pred p; mbarrier.try_wait.parity.shared::cta.b64 p, [%1], %2; selp.u32 %0, 1, 0, p;}"
        : "=r"(ok) : "r"(bar), "r"(par) : "memory");
    return ok;
}
__device__ __forceinline__ bool mbar_test(uint32_t bar, uint32_t par) {
    uint32_t ok;
    asm volatile("{.reg .pred p; mbarrier.test_wait.parity.shared::cta.b64 p, [%1], %2; selp.u32 %0, 1, 0, p;}"
        : "=r"(ok) : "r"(bar), "r"(par) : "memory");
    return ok;
}
__device__ __forceinline__ int ld_acq(const int* p) { int v; asm volatile("ld.acquire.gpu.global.s32 %0, [%1];" : "=r"(v) : "l"(p) : "memory"); return v; }
__device__ __forceinline__ void red_release(int* p, int v) { asm volatile("red.release.gpu.global.add.s32 [%0], %1;" ::"l"(p), "r"(v) : "memory"); }
__device__ __forceinline__ void fence_gpu() { asm volatile("fence.acq_rel.gpu;" ::: "memory"); }
__device__ __forceinline__ void wait_ctr(const int* p, int n) {
#pragma unroll 1
    for (int it = 0; it < (1 << 20) && ld_acq(p) < n; it++) __nanosleep(64);
}
__device__ __forceinline__ void mbar_wait(uint32_t bar, uint32_t par) {
    if (!mbar_try(bar, par)) {
#pragma unroll 1
        for (int it = 0; it < SPIN_LIMIT && !mbar_try(bar, par); it++) {}
    }
}
__device__ __forceinline__ void mbar_wait_long(uint32_t bar, uint32_t par) {
    for (int it = 0; it < (1 << 24) && !mbar_try(bar, par); it++) {}
}
__device__ __forceinline__ float4 add4(float4 a, float4 b) { return make_float4(a.x + b.x, a.y + b.y, a.z + b.z, a.w + b.w); }
__device__ __forceinline__ float ex2(float x) { float y; asm("ex2.approx.ftz.f32 %0, %1;" : "=f"(y) : "f"(x)); return y; }

__device__ __forceinline__ void wgmma256(float (&d)[128], uint64_t da, uint64_t db, int acc) {
    asm volatile("{.reg .pred p; setp.ne.b32 p, %130, 0;\n"
        "wgmma.mma_async.sync.aligned.m64n256k16.f32.bf16.bf16 {"
        "%0,%1,%2,%3,%4,%5,%6,%7,%8,%9,%10,%11,%12,%13,%14,%15,"
        "%16,%17,%18,%19,%20,%21,%22,%23,%24,%25,%26,%27,%28,%29,%30,%31,"
        "%32,%33,%34,%35,%36,%37,%38,%39,%40,%41,%42,%43,%44,%45,%46,%47,"
        "%48,%49,%50,%51,%52,%53,%54,%55,%56,%57,%58,%59,%60,%61,%62,%63,"
        "%64,%65,%66,%67,%68,%69,%70,%71,%72,%73,%74,%75,%76,%77,%78,%79,"
        "%80,%81,%82,%83,%84,%85,%86,%87,%88,%89,%90,%91,%92,%93,%94,%95,"
        "%96,%97,%98,%99,%100,%101,%102,%103,%104,%105,%106,%107,%108,%109,%110,%111,"
        "%112,%113,%114,%115,%116,%117,%118,%119,%120,%121,%122,%123,%124,%125,%126,%127"
        "}, %128, %129, p, 1, 1, 0, 1;}"
        : "+f"(d[0]), "+f"(d[1]), "+f"(d[2]), "+f"(d[3]), "+f"(d[4]), "+f"(d[5]), "+f"(d[6]), "+f"(d[7]), "+f"(d[8]), "+f"(d[9]), "+f"(d[10]), "+f"(d[11]), "+f"(d[12]), "+f"(d[13]), "+f"(d[14]), "+f"(d[15]), "+f"(d[16]), "+f"(d[17]), "+f"(d[18]), "+f"(d[19]), "+f"(d[20]), "+f"(d[21]), "+f"(d[22]), "+f"(d[23]), "+f"(d[24]), "+f"(d[25]), "+f"(d[26]), "+f"(d[27]), "+f"(d[28]), "+f"(d[29]), "+f"(d[30]), "+f"(d[31]), "+f"(d[32]), "+f"(d[33]), "+f"(d[34]), "+f"(d[35]), "+f"(d[36]), "+f"(d[37]), "+f"(d[38]), "+f"(d[39]), "+f"(d[40]), "+f"(d[41]), "+f"(d[42]), "+f"(d[43]), "+f"(d[44]), "+f"(d[45]), "+f"(d[46]), "+f"(d[47]), "+f"(d[48]), "+f"(d[49]), "+f"(d[50]), "+f"(d[51]), "+f"(d[52]), "+f"(d[53]), "+f"(d[54]), "+f"(d[55]), "+f"(d[56]), "+f"(d[57]), "+f"(d[58]), "+f"(d[59]), "+f"(d[60]), "+f"(d[61]), "+f"(d[62]), "+f"(d[63]), "+f"(d[64]), "+f"(d[65]), "+f"(d[66]), "+f"(d[67]), "+f"(d[68]), "+f"(d[69]), "+f"(d[70]), "+f"(d[71]), "+f"(d[72]), "+f"(d[73]), "+f"(d[74]), "+f"(d[75]), "+f"(d[76]), "+f"(d[77]), "+f"(d[78]), "+f"(d[79]), "+f"(d[80]), "+f"(d[81]), "+f"(d[82]), "+f"(d[83]), "+f"(d[84]), "+f"(d[85]), "+f"(d[86]), "+f"(d[87]), "+f"(d[88]), "+f"(d[89]), "+f"(d[90]), "+f"(d[91]), "+f"(d[92]), "+f"(d[93]), "+f"(d[94]), "+f"(d[95]), "+f"(d[96]), "+f"(d[97]), "+f"(d[98]), "+f"(d[99]), "+f"(d[100]), "+f"(d[101]), "+f"(d[102]), "+f"(d[103]), "+f"(d[104]), "+f"(d[105]), "+f"(d[106]), "+f"(d[107]), "+f"(d[108]), "+f"(d[109]), "+f"(d[110]), "+f"(d[111]), "+f"(d[112]), "+f"(d[113]), "+f"(d[114]), "+f"(d[115]), "+f"(d[116]), "+f"(d[117]), "+f"(d[118]), "+f"(d[119]), "+f"(d[120]), "+f"(d[121]), "+f"(d[122]), "+f"(d[123]), "+f"(d[124]), "+f"(d[125]), "+f"(d[126]), "+f"(d[127])
        : "l"(da), "l"(db), "r"(acc));
}
__device__ __forceinline__ void wgmma128(float (&d)[64], uint64_t da, uint64_t db, int acc) {
    asm volatile("{.reg .pred p; setp.ne.b32 p, %66, 0;\n"
        "wgmma.mma_async.sync.aligned.m64n128k16.f32.bf16.bf16 {"
        "%0,%1,%2,%3,%4,%5,%6,%7,%8,%9,%10,%11,%12,%13,%14,%15,"
        "%16,%17,%18,%19,%20,%21,%22,%23,%24,%25,%26,%27,%28,%29,%30,%31,"
        "%32,%33,%34,%35,%36,%37,%38,%39,%40,%41,%42,%43,%44,%45,%46,%47,"
        "%48,%49,%50,%51,%52,%53,%54,%55,%56,%57,%58,%59,%60,%61,%62,%63"
        "}, %64, %65, p, 1, 1, 0, 1;}"
        : "+f"(d[0]), "+f"(d[1]), "+f"(d[2]), "+f"(d[3]), "+f"(d[4]), "+f"(d[5]), "+f"(d[6]), "+f"(d[7]), "+f"(d[8]), "+f"(d[9]), "+f"(d[10]), "+f"(d[11]), "+f"(d[12]), "+f"(d[13]), "+f"(d[14]), "+f"(d[15]), "+f"(d[16]), "+f"(d[17]), "+f"(d[18]), "+f"(d[19]), "+f"(d[20]), "+f"(d[21]), "+f"(d[22]), "+f"(d[23]), "+f"(d[24]), "+f"(d[25]), "+f"(d[26]), "+f"(d[27]), "+f"(d[28]), "+f"(d[29]), "+f"(d[30]), "+f"(d[31]), "+f"(d[32]), "+f"(d[33]), "+f"(d[34]), "+f"(d[35]), "+f"(d[36]), "+f"(d[37]), "+f"(d[38]), "+f"(d[39]), "+f"(d[40]), "+f"(d[41]), "+f"(d[42]), "+f"(d[43]), "+f"(d[44]), "+f"(d[45]), "+f"(d[46]), "+f"(d[47]), "+f"(d[48]), "+f"(d[49]), "+f"(d[50]), "+f"(d[51]), "+f"(d[52]), "+f"(d[53]), "+f"(d[54]), "+f"(d[55]), "+f"(d[56]), "+f"(d[57]), "+f"(d[58]), "+f"(d[59]), "+f"(d[60]), "+f"(d[61]), "+f"(d[62]), "+f"(d[63])
        : "l"(da), "l"(db), "r"(acc));
}
__device__ __forceinline__ void wg_fence() { asm volatile("wgmma.fence.sync.aligned;" ::: "memory"); }
__device__ __forceinline__ void wg_commit() { asm volatile("wgmma.commit_group.sync.aligned;" ::: "memory"); }
template <int N> __device__ __forceinline__ void wg_wait() { asm volatile("wgmma.wait_group.sync.aligned %0;" ::"n"(N) : "memory"); }
__device__ __forceinline__ uint64_t mkdesc(uint32_t addr, uint32_t lbo, uint32_t sbo, uint32_t sw) {
    return (uint64_t)((addr & 0x3FFFF) >> 4) | ((uint64_t)(lbo >> 4) << 16) | ((uint64_t)(sbo >> 4) << 32) | ((uint64_t)sw << 62);
}
__device__ __forceinline__ void tma2d(uint32_t dst, const CUtensorMap* m, int c0, int c1, uint32_t bar) {
    asm volatile("cp.async.bulk.tensor.2d.shared::cluster.global.mbarrier::complete_tx::bytes [%0], [%1, {%2, %3}], [%4];"
        ::"r"(dst), "l"(m), "r"(c0), "r"(c1), "r"(bar) : "memory");
}
__device__ __forceinline__ void tma3d(uint32_t dst, const CUtensorMap* m, int c0, int c1, int c2, uint32_t bar) {
    asm volatile("cp.async.bulk.tensor.3d.shared::cluster.global.mbarrier::complete_tx::bytes [%0], [%1, {%2, %3, %4}], [%5];"
        ::"r"(dst), "l"(m), "r"(c0), "r"(c1), "r"(c2), "r"(bar) : "memory");
}
__device__ __forceinline__ void tma3d_mc(uint32_t dst, const CUtensorMap* m, int c0, int c1, int c2, uint32_t bar, uint16_t mask) {
    asm volatile("cp.async.bulk.tensor.3d.shared::cluster.global.mbarrier::complete_tx::bytes.multicast::cluster [%0], [%1, {%2, %3, %4}], [%5], %6;"
        ::"r"(dst), "l"(m), "r"(c0), "r"(c1), "r"(c2), "r"(bar), "h"(mask) : "memory");
}
__device__ __forceinline__ void mbar_arrive(uint32_t bar) { asm volatile("mbarrier.arrive.shared.b64 _, [%0];" ::"r"(bar) : "memory"); }
__device__ __forceinline__ void mbar_arrive_remote(uint32_t bar) {
    asm volatile("mbarrier.arrive.shared::cluster.b64 _, [%0];" ::"r"(bar) : "memory");
}
__device__ __forceinline__ bool elect() {
    uint32_t p;
    asm volatile("{.reg .pred p; elect.sync _|p, 0xffffffff; selp.u32 %0, 1, 0, p;}" : "=r"(p));
    return p;
}
template <int R> __device__ __forceinline__ void reg_inc() { asm volatile("setmaxnreg.inc.sync.aligned.u32 %0;" ::"n"(R)); }
template <int R> __device__ __forceinline__ void reg_dec() { asm volatile("setmaxnreg.dec.sync.aligned.u32 %0;" ::"n"(R)); }

#define ST(id, w, i)
constexpr int CH_NRES = 50;
constexpr int CH_WREG = CH_NRES * 512;
constexpr int CH_PART = 8 * CH_WREG;
constexpr int CH_SX = CH_PART + 16384;
constexpr int CH_MX = CH_SX + 3 * 1280;
constexpr int CH_QK = CH_MX;
constexpr int CH_XS = CH_MX + 3 * 512;
constexpr int CH_BAR = CH_XS + 5632;
constexpr int CH_SMEM = CH_BAR + 192;
constexpr int CH_THREADS = 384;

__device__ __forceinline__ char* ring_base() { return (char*)(((uintptr_t)g_ring + (1 << 20) - 1) & ~(uintptr_t)((1 << 20) - 1)); }
__device__ __forceinline__ uint32_t ring_off(int chunk, int side) {
    uint32_t o = ((chunk & 1) << 13) | ((chunk >> 1) << 16);
    uint32_t par = ((o >> 13) ^ (o >> 16) ^ (o >> 17) ^ (o >> 19) ^ side) & 1;
    return o | (par << 12);
}
__device__ __forceinline__ uint2 ld_poll(const char* p) {
    unsigned long long v; asm volatile("ld.relaxed.gpu.global.b64 %0, [%1];" : "=l"(v) : "l"(p) : "memory");
    return make_uint2((uint32_t)v, (uint32_t)(v >> 32));
}
__device__ __forceinline__ void st_pub(char* p, uint32_t x, uint32_t y) {
    unsigned long long v = ((unsigned long long)y << 32) | x;
    asm volatile("st.relaxed.gpu.global.b64 [%0], %1;" ::"l"(p), "l"(v) : "memory");
}
template <int N>
__device__ __forceinline__ void poll_issue(uint2 (&b)[N], const char* p, bool lastvalid) {
#pragma unroll
    for (int i = 0; i < N; i++) {
        if (i < N - 1 || lastvalid) b[i] = ld_poll(p + i * 256);
        else b[i] = make_uint2(0, 0);
    }
}
template <int N>
__device__ __forceinline__ int poll_check(uint2 (&b)[N], const char* p, uint32_t z) {
    int it = 0;
    uint32_t mx = z;
#pragma unroll
    for (int i = 0; i < N; i++) mx = max(mx, b[i].x);
    if (__any_sync(0xffffffffu, mx == SENT)) {
        do {
#pragma unroll
            for (int i = 0; i < N; i++)
                if ((REALL && i < 10) || b[i].x == SENT) b[i] = ld_poll(p + i * 256);
            mx = b[0].x;
#pragma unroll
            for (int i = 1; i < N; i++) mx = max(mx, b[i].x);
            it++;
        } while (__any_sync(0xffffffffu, mx == SENT && it < SPIN_LIMIT));
    }
    return it;
}
template <int N>
__device__ __forceinline__ uint32_t delay(uint32_t a) {
    uint32_t z = 0;
#pragma unroll
    for (int i = 0; i < N; i++) asm volatile("ld.volatile.shared.u32 %0, [%1];" : "=r"(z) : "r"(a + z) : "memory");
    return z;
}

#define PFKV 0
#define LDW 0
#define PACE2 18
#define KGS 3
constexpr int KVN = 2;
#define FEN 1
#define XB 4
#define KEEP 100
#define PE 0
#define PROMO 2
#define PROMU 0
#define FNC 1
#define CL 8
#define PL 0
#define ML 4
#define MP 2
#define VCH_P 4
#define VCH_C 2
#define DLM 3
#define DLO 5
constexpr int OB = 0;
template <int PACE, int I0 = 0, int I1 = 12>
__device__ __forceinline__ void preload(uint32_t (&sw)[12][4], uint32_t a, uint32_t zero) {
    uint32_t z = 0;
#pragma unroll
    for (int i = I0; i < I1; i++) {
        if (PACE && i % (PACE ? PACE : 1) == 0) z = delay<1>(zero + z);
        ldsm4t(sw[i], a + z + i * 512);
    }
}
__device__ __forceinline__ void stsm4(uint32_t addr, uint32_t a, uint32_t b, uint32_t c, uint32_t d) {
    asm volatile("stmatrix.sync.aligned.m8n8.x4.shared.b16 [%0], {%1,%2,%3,%4};" ::"r"(addr), "r"(a), "r"(b), "r"(c), "r"(d) : "memory");
}
__device__ __forceinline__ void stsm4t(uint32_t addr, uint32_t a, uint32_t b, uint32_t c, uint32_t d) {
    asm volatile("stmatrix.sync.aligned.m8n8.x4.trans.shared.b16 [%0], {%1,%2,%3,%4};" ::"r"(addr), "r"(a), "r"(b), "r"(c), "r"(d) : "memory");
}
__device__ __forceinline__ void st_part(uint32_t addr, const float (&x)[4], const float (&y)[4]) {
    stsm4(addr, pack_bf16(x[0], x[1]), pack_bf16(x[2], x[3]), pack_bf16(y[0], y[1]), pack_bf16(y[2], y[3]));
}
template <bool TR>
__device__ __forceinline__ void red_part(uint32_t& lo, uint32_t& hi, uint32_t addr, uint32_t eye) {
    uint32_t a[4][4];
#pragma unroll
    for (int j = 0; j < 4; j++) { if (TR) ldsm4t(a[j], addr + j * 1024); else ldsm4(a[j], addr + j * 1024); }
    float r0[4], r1[4], r2[4], r3[4];
    mma16z(r0, a[0], eye, eye); mma16z(r1, a[1], eye, eye); mma16z(r2, a[2], eye, eye); mma16z(r3, a[3], eye, eye);
#pragma unroll
    for (int j = 0; j < 4; j++) r0[j] = ((r0[j] + r1[j]) + r2[j]) + r3[j];
    lo = pack_bf16(r0[0], r0[1]); hi = pack_bf16(r0[2], r0[3]);
}
__device__ __forceinline__ int o_chunk(int ks, int& pos) {
    const int cw = ks < 176 ? ks / 11 : 16 + (ks - 176) / 10;
    pos = ks - (cw < 16 ? 11 * cw : 176 + 10 * (cw - 16));
    return cw;
}

template <bool PV>
__device__ __forceinline__ void chain_loop(const uint32_t (&wa)[36][4], const uint32_t sb, const int w, const int lane0, const int rank,
                                           const int h, const int side) {
    const int rk1 = rank == 2 ? 0 : rank + 1, rk2 = rank == 0 ? 2 : rank - 1;
    const int nq = rank == 0 ? 6 : 5, u0 = rank == 0 ? 0 : 1 + 5 * rank, v0 = rank == 0 ? -6 : 3 * rank - 6;
    const uint32_t pt = CH_PART + (w >> 1) * 4096 + (w & 1) * 256;
    const uint32_t barS = sb + CH_BAR, barM = barS + 8, zero = barS + 24;
    char* const ring0 = ring_base();
    const uint32_t m_rd = ring_off(24 + w, side), o_rd = ring_off(rank * 8 + w, side);
    uint32_t pub;
    if (PV) { int pos, cw = o_chunk(h * 8 + v0 + w, pos); pub = (ring_off(cw, 0) & ~4096u) + pos * 256; }
    else pub = (ring_off(24 + (h >> 2), 0) & ~4096u) + ((2 * h + w) & 7) * 256;
    char* const kvo = (char*)(PV ? g_vm + 128 * (v0 + w) : g_km + 64 * (u0 + w)) + h * 2048;
    const bool mown = !PV && w == rank && rank < 2;
    uint32_t lo16 = lane0 * 16;
    uint32_t sw[12][4];
#pragma unroll
    for (int i = 0; i < 12; i++) ldsm4t(sw[i], sb + lo16 + w * CH_WREG + i * 512);

#pragma unroll 1
    for (int s = 0;; s++) {
        const bool last = s == NSEG - 1;
        const uint32_t slot = (s & 3) << 14;
        lo16 += delay<DLM>(zero);
        const uint32_t lane = lo16 >> 4, l16 = sb + lo16, wl = l16 + w * CH_WREG, pw = l16 + CH_PART + w * 512;
        const uint32_t xs = l16 + CH_XS + nq * 512 + (w - nq) * 1024;
        const uint32_t eye = ((lo16 >> 7) == (lane & 3)) ? ((lo16 & 64) ? 0x3F800000u : 0x3F80u) : 0u;
        uint2 b[8];
        const char* pm = ring0 + (m_rd + slot + (lo16 >> 1));
        poll_issue<8>(b, pm, true);
        preload<0, ML, 12>(sw, wl, zero);
        if (FNC & 1) bar_arrive(14, 256);
        poll_check<8>(b, pm, delay<FNC & 1>(zero));
        if ((OB || (XB & 1)) && !last) bar_arrive(8, 256 + OB);
        if (PV && !last && w == 7) bar_arrive(13, 64);
        {
            float acc[6][4];
#pragma unroll
            for (int kk = 0; kk < 8; kk++) {
                const int j = (2 * kk) % 12;
                if (kk == 0) { mma16z(acc[5], sw[0], b[0].x, b[0].y); mma16z(acc[4], sw[1], b[0].x, b[0].y); }
                else { mma16(acc[5], sw[j], b[kk].x, b[kk].y); mma16(acc[4], sw[j + 1], b[kk].x, b[kk].y); }
#pragma unroll
                for (int i = 0; i < 4; i++) {
                    if (kk == 0) mma16z(acc[i], wa[i * 8], b[0].x, b[0].y);
                    else mma16(acc[i], wa[i * 8 + kk], b[kk].x, b[kk].y);
                    if (i < 2) ldsm4t(sw[j + i], wl + (12 + 2 * kk + i) * 512);
                }
            }
            st_part(pw + 4 * 2048, acc[4], acc[5]);
            st_part(pw, acc[0], acc[1]);
            st_part(pw + 2 * 2048, acc[2], acc[3]);
        }
        uint32_t kv0, kv1;
        const uint32_t lp = l16 + (lane >> 4) * 256, pl = lp + pt;
        if (!PV) {
            bar_sync(1, last ? 256 : 256 + OB);
            red_part<true>(kv1, kv0, pl, eye);
            sts64(l16 + CH_QK + (w >> 1) * 512 + (w & 1) * 8, __uint_as_float(kv1), __uint_as_float(kv0));
            if (!last) bar_arrive(2, nq * 32 + 64 + OB);
        } else {
            bar_sync(1, last ? 256 : 256 + OB);
        }
        {
            float va[4][4];
            const float z = __uint_as_float(delay<1>(zero));
#pragma unroll
            for (int i = 0; i < 4; i++) va[i][0] = va[i][1] = va[i][2] = va[i][3] = z;
#pragma unroll
            for (int kk = 0; kk < 8; kk++) {
                const int c = (PV ? VCH_P : VCH_C) == 4 ? kk & 1 : 0;
                if (kk < 2) { mma16(va[c], wa[32 + 2 * kk], b[kk].x, b[kk].y); mma16(va[2 + c], wa[33 + 2 * kk], b[kk].x, b[kk].y); }
                else { mma16(va[c], sw[(2 * kk) % 12], b[kk].x, b[kk].y); mma16(va[2 + c], sw[(2 * kk + 1) % 12], b[kk].x, b[kk].y); }
            }
            if ((PV ? VCH_P : VCH_C) == 4) {
#pragma unroll
                for (int j = 0; j < 4; j++) { va[0][j] += va[1][j]; va[2][j] += va[3][j]; }
            }
            st_part(pw + 6 * 2048, va[0], va[2]);
        }
        if (PV) {
            uint32_t vt0[4], vt1[4];
            ldsm4t(vt0, xs); ldsm4t(vt1, xs + 512);
            if (w >= 6 && !last) {
                uint32_t kx[3][4];
#pragma unroll
                for (int j = 0; j < 3; j++)
                    ldsm4(kx[j], sb + CH_XS + j * 1024 + (j == 2 && nq == 5 ? 0 : ((lane >> 3) & 1) * 512) + (w - 6) * 256 + (lane >> 4) * 128 + (lane & 7) * 16);
                const uint32_t da = l16 + CH_SX + rank * 1280 + (w - 6) * 512, dc = sb + CH_SX + rank * 1280 + 1024 + lane * 8;
                bar_sync(2, nq * 32 + 64 + OB);
                uint32_t qk[3][4];
#pragma unroll
                for (int j = 0; j < 3; j++) {
                    const float4 v = lds128(l16 + CH_QK + j * 512);
                    qk[j][0] = __float_as_uint(v.x); qk[j][1] = __float_as_uint(v.y); qk[j][2] = __float_as_uint(v.z); qk[j][3] = __float_as_uint(v.w);
                }
                float s0[4], s1[4], s2[4], s3[4];
                mma16z(s0, qk[0], kx[0][0], kx[0][1]); mma16z(s1, qk[0], kx[0][2], kx[0][3]);
                mma16z(s2, qk[1], kx[1][0], kx[1][1]); mma16z(s3, qk[1], kx[1][2], kx[1][3]);
                if (nq == 5) qk[2][2] = qk[2][3] = 0;
                mma16(s0, qk[2], kx[2][0], kx[2][1]); mma16(s1, qk[2], kx[2][2], kx[2][3]);
                float m0[4], m1[4];
                mma16z(m0, qk[0], qk[0][1], qk[0][3]); mma16z(m1, qk[1], qk[1][1], qk[1][3]);
                mma16(m0, qk[2], qk[2][1], qk[2][3]);
                const float4 sv = make_float4(s0[0] + s2[0], s0[1] + s2[1], s1[0] + s3[0], s1[1] + s3[1]);
                st_async4(mapa(da, rk1), sv, mapa(barS, rk1));
                st_async4(mapa(da, rk2), sv, mapa(barS, rk2));
                {
                    const float c0 = m0[0] + m1[0], c1 = m0[1] + m1[1];
                    const int dr = w == 6 ? rk1 : rk2;
                    st_async2(mapa(dc, dr), c0, c1, mapa(barS, dr));
                    sts64(dc, c0, c1);
                }
                const float t4[4] = {sv.x, sv.y, sv.z, sv.w};
                sts128(da, t4);
            }
            bar_sync(3, last ? 256 : 256 + OB);
            if (!last && w == 7) bar_arrive(12, 64);
            red_part<false>(kv0, kv1, pl, eye);
            if (last) {
                uint32_t* d = (uint32_t*)(kvo + (uint32_t)(s * (NH * 2048) + lane * 4));
                d[0] = movm(kv0); d[32] = movm(kv1);
                break;
            }
            {
                const uint32_t sx = l16 + CH_SX, r0 = rank * 1280, r1 = rk1 * 1280, r2 = rk2 * 1280;
                float4 a0 = lds128(sx + r0), b0 = lds128(sx + 512 + r0);
                const float2 c0 = lds64(sx + 1024 + r0 - lane * 8);
                preload<0, 0, PE>(sw, wl + 28 * 512, zero);
                mbar_wait(barS, s & 1);
                const float4 a1 = lds128(sx + r1), a2 = lds128(sx + r2), b1 = lds128(sx + 512 + r1), b2 = lds128(sx + 512 + r2);
                const float2 c1 = lds64(sx + 1024 + r1 - lane * 8), c2 = lds64(sx + 1024 + r2 - lane * 8);
                a0 = add4(add4(a0, a1), a2); b0 = add4(add4(b0, b1), b2);
                float sc[10] = {a0.x, a0.y, a0.z, a0.w, b0.x, b0.y, b0.z, b0.w, c0.x + c1.x + c2.x, c0.y + c1.y + c2.y};
                float mx = fmaxf(fmaxf(fmaxf(sc[0], sc[1]), fmaxf(sc[2], sc[3])), fmaxf(fmaxf(sc[4], sc[5]), fmaxf(sc[6], sc[7])));
                mx = fmaxf(mx, fmaxf(sc[8], sc[9]));
                mx = fmaxf(fmaxf(mx, __shfl_xor_sync(0xffffffffu, mx, 1)),
                           fmaxf(__shfl_xor_sync(0xffffffffu, mx, 2), __shfl_xor_sync(0xffffffffu, mx, 3)));
                const float cs = 0.08838834764831845f * 1.4426950408889634f;
                const float mb = -mx * cs;
#pragma unroll
                for (int j = 0; j < 10; j++) sc[j] = ex2(fmaf(sc[j], cs, mb));
                uint32_t pf[5];
#pragma unroll
                for (int j = 0; j < 5; j++) pf[j] = pack_bf16(sc[2 * j], sc[2 * j + 1]);
                float o0[4], o1[4], o2[4], o3[4], o4[4], o5[4];
                const uint32_t p0[4] = {pf[0], 0, pf[1], 0}, p1[4] = {pf[2], 0, pf[3], 0};
                mma16z(o0, p0, vt0[0], vt0[1]); mma16z(o1, p0, vt1[0], vt1[1]);
                mma16z(o2, p1, vt0[2], vt0[3]); mma16z(o3, p1, vt1[2], vt1[3]);
                mma8z(o4, pf[4], 0, kv0); mma8z(o5, pf[4], 0, kv1);
                float sum = (((sc[0] + sc[1]) + (sc[2] + sc[3])) + ((sc[4] + sc[5]) + (sc[6] + sc[7]))) + (sc[8] + sc[9]);
                sum = (sum + __shfl_xor_sync(0xffffffffu, sum, 1)) + (__shfl_xor_sync(0xffffffffu, sum, 2) + __shfl_xor_sync(0xffffffffu, sum, 3));
                float inv; asm("rcp.approx.ftz.f32 %0, %1;" : "=f"(inv) : "f"(sum));
                const uint32_t ox = pack_bf16((o0[0] + o2[0] + o4[0]) * inv, (o0[1] + o2[1] + o4[1]) * inv);
                const uint32_t oy = pack_bf16((o1[0] + o3[0] + o5[0]) * inv, (o1[1] + o3[1] + o5[1]) * inv);
                char* const pp = ring0 + (pub + slot + (lo16 >> 1));
                st_pub(pp, ox, oy); st_pub(pp + 4096, ox, oy);
                if (OB || (XB & 4)) bar_arrive(10, (8 - nq) * 32 + OB);
                preload<0, PE, PL>(sw, wl + 28 * 512, zero);
            }
            kv0 = movm(kv0); kv1 = movm(kv1);
        } else {
            *(uint32_t*)(kvo + (uint32_t)(s * (NH * 2048) + lane * 4)) = kv0;
            bar_sync(3, last ? 256 : 256 + OB);
            if (last) break;
            preload<1, 0, CL>(sw, wl + 28 * 512, zero);
        }
        uint2 c[11];
        bar_sync(4, 256 + OB);
        const char* po = ring0 + (o_rd + slot + (lo16 >> 1) + delay<DLO>(zero));
        poll_issue<11>(c, po, rank < 2);
        preload<0, PV ? PL : CL, 12>(sw, wl + 28 * 512, zero);
        if (PV) { uint32_t* d = (uint32_t*)(kvo + (uint32_t)(s * (NH * 2048) + lane * 4)); d[0] = kv0; d[32] = kv1; }
        if (FNC & 2) bar_arrive(15, 256);
        poll_check<11>(c, po, delay<(FNC >> 1)>(zero));
        if (OB || (XB & 2)) bar_arrive(9, 256 + OB);
        {
            float acc[4][4];
#pragma unroll
            for (int f = 0; f < 22; f++) {
                const int kk = f >> 1, a = f & 3;
                if (f < 4) mma16z(acc[a], sw[f % 12], c[kk].x, c[kk].y);
                else mma16(acc[a], sw[f % 12], c[kk].x, c[kk].y);
                if (f + 12 < 22) ldsm4t(sw[f % 12], wl + (28 + f + 12) * 512);
            }
#pragma unroll
            for (int i = 0; i < 2; i++) {
#pragma unroll
                for (int j = 0; j < 4; j++) acc[i][j] += acc[i + 2][j];
                sts128(l16 + CH_PART + i * 4096 + w * 512, acc[i]);
            }
        }
        if (!PV && w < 2) {
            bar_sync(5, 288 + OB);
            float4 v[8];
#pragma unroll
            for (int i = 0; i < 8; i++) v[i] = lds128(l16 + CH_PART + w * 4096 + i * 512);
            float4 r = add4(add4(add4(v[0], v[1]), add4(v[2], v[3])), add4(add4(v[4], v[5]), add4(v[6], v[7])));
            if (!mown) st_async4(mapa(l16 + CH_MX + rank * 512, w), r, mapa(barM, w));
            bar_arrive(7, 256 + OB);
            if (mown) {
                mbar_wait(barM, s & 1);
                float4 x = lds128(l16 + CH_MX + (rank ^ 1) * 512), y = lds128(l16 + CH_MX + 2 * 512);
                r = add4(add4(x, r), y);
                const uint32_t mx = movm(pack_bf16(r.x, r.y)), my = movm(pack_bf16(r.z, r.w));
                const uint32_t ns = (slot + 0x4000) & 0xC000;
                char* const pp = ring0 + (pub + ns + (lo16 >> 1));
                st_pub(pp, mx, my); st_pub(pp + 4096, mx, my);
            }
            preload<0, 0, ML>(sw, wl, zero);
        } else {
            bar_arrive(5, 288 + OB);
            bar_sync(7, 256 + OB);
            preload<MP, 0, ML>(sw, wl, zero);
        }
        bar_sync(6, 320 + OB);
    }
    bar_arrive(6, 288);
}

__device__ __forceinline__ void chain_pace(const uint32_t sb, const int lane, const int rank, const int aware) {
    const uint32_t zero = sb + CH_BAR + 24;
    if (lane == 0) {
        char* ring = ring_base();
        uint32_t* p0 = (uint32_t*)(ring + ring_off(blockIdx.x & 15, 0) + 3072 + (blockIdx.x >> 4) * 128);
        uint32_t* p1 = (uint32_t*)(ring + ring_off(blockIdx.x & 15, 1) + 3072 + (blockIdx.x >> 4) * 128);
        *p0 = 0; *p1 = 0;
        int b0 = 1 << 30, b1 = 1 << 30; uint32_t v = 0;
        for (int r = 0; r < 4 || (r < 256 && !mbar_test(sb + CH_BAR + 16, 0)); r++) {
            uint32_t t0 = clk(); v = atomicExch(p0 + (v == 500), r); uint32_t t1 = v == 777 ? clk() + 1 : clk(); b0 = min(b0, (int)(t1 - t0));
            t0 = clk(); v = atomicExch(p1 + (v == 500), r); t1 = v == 777 ? clk() + 1 : clk(); b1 = min(b1, (int)(t1 - t0));
            asm volatile("st.volatile.shared.u32 [%0], %1;" ::"r"(zero + 4), "r"(aware ? (b1 < b0) ^ (aware - 1) : 0) : "memory");
        }
    }
    __syncwarp();
#pragma unroll 1
    for (int s = 1; s < NSEG; s++) {
        bar_sync(5, 288 + OB);
        bar_arrive(6, 320 + OB + (rank == 2 ? delay<PACE2>(zero) : 0));
    }
}
__device__ __forceinline__ char* reset_ptr(const int lane, const int rank, const int h) {
    const int nq = rank == 0 ? 6 : 5, v0 = rank == 0 ? -6 : 3 * rank - 6;
    int pos, cw = o_chunk(h * 8 + v0 + min(max(5 + (lane >> 3), nq), 7), pos);
    if (lane >= 24 && rank < 2) { cw = 24 + (h >> 2); pos = (2 * h + rank) & 7; }
    return ring_base() + ((ring_off(cw, 0) & ~4096u) + pos * 256 + (lane & 7) * 16);
}
__device__ __forceinline__ void chain_chores(const uint32_t sb, const int lane, const int rank, const int h, const bf16* __restrict__ mem0) {
    const int nq = rank == 0 ? 6 : 5, u0 = rank == 0 ? 0 : 1 + 5 * rank, v0 = rank == 0 ? -6 : 3 * rank - 6;
    const uint32_t barS = sb + CH_BAR, barM = barS + 8, barX = barS + 16;
    auto xload = [&](int s) {
        mbar_expect(barX, 8192 - nq * 512);
        bulk_load(sb + CH_XS, g_kx + (size_t)(s * NH + h) * 4096 + u0 * 256, nq * 512, barX);
        bulk_load(sb + CH_XS + nq * 512, g_vx + (size_t)(s * NH + h) * 4096 + (v0 + nq) * 512, (8 - nq) * 1024, barX);
    };
    char* const rb = reset_ptr(lane, rank, h);
    int* const kvf = g_kvf + blockIdx.x * 16;
    if (rank < 2) {
        const uint32_t* p = (const uint32_t*)(mem0 + (lane >> 2) * DM + 32 * h + 16 * rank + 2 * (lane & 3));
        char* d = ring_base() + ((ring_off(24 + (h >> 2), 0) & ~4096u) + ((2 * h + rank) & 7) * 256 + lane * 8);
        const uint32_t x = p[0] == SENT ? 0x7FFF7FFFu : p[0];
        st_pub(d, x, p[4]); st_pub(d + 4096, x, p[4]);
    }
    if (!KVN) __nanosleep(18000);
    wait_ctr(kvf, KVN);
    asm volatile("fence.proxy.async.global;" ::: "memory");
    if (elect()) xload(0);
#pragma unroll 1
    for (int s = 0; s < NSEG - 1; s++) {
        if (lane == 0) {
            mbar_expect(barS, 2 * 1280);
            if (rank < 2) mbar_expect(barM, 2 * 512);
        }
        bar_sync(13, 64);
#pragma unroll
        for (int i = 0; i < 4; i++)
            asm volatile("st.relaxed.gpu.global.v4.u32 [%0], {%1,%1,%1,%1};" ::"l"(rb + ((((s + 2) & 3) << 14) + (i >> 1) * 4096 + (i & 1) * 128)), "r"(SENT) : "memory");
        if (FEN || (s & 3) == 0) fence_gpu();
        if (lane == 0 && (s & 3) == 0 && s) atomicAdd(g_ctr + C_CHAIN + (s >> 2) - 1, 1);
        if ((s & 3) == 3) { wait_ctr(kvf + (s >> 2) + 1, KVN); asm volatile("fence.proxy.async.global;" ::: "memory"); }
        __syncwarp();
        bar_sync(12, 64);
        if (elect()) xload(s + 1);
        mbar_wait(barX, (s + 1) & 1);
        bar_sync(6, 320 + OB);
    }
    bar_sync(6, 288);
    fence_gpu();
    if (lane == 0) atomicAdd(g_ctr + C_CHAIN + 15, 1);
}

struct S4Params { const bf16 *Are, *Aim, *Bre, *Bim, *Cre, *Cim, *ldt, *dsk; };
__device__ __forceinline__ float2 cmul(float2 a, float2 b) { return make_float2(a.x * b.x - a.y * b.y, a.x * b.y + a.y * b.x); }
__device__ __forceinline__ float2 csq(float2 a) { return make_float2(a.x * a.x - a.y * a.y, (a.x + a.x) * a.y); }
__device__ __forceinline__ float2 cexp_t(float lr, float turns) {
    float f = (turns - rintf(turns)) * 6.283185307179586f, e = ex2(lr);
    return make_float2(e * __cosf(f), e * __sinf(f));
}
__device__ __forceinline__ float bf_at(uint2 v, int i) {
    const uint32_t w = i < 2 ? v.x : v.y;
    return __uint_as_float((i & 1) ? w & 0xFFFF0000u : w << 16);
}
__device__ __forceinline__ void kg_step(uint32_t (&a)[4][4], uint32_t (&b)[5][2], uint32_t pa, uint32_t pe, float x0) {
#pragma unroll
    for (int i = 0; i < 2; i++) {
        const float4 p = lds128(pa + i * 64);
        const float2 e8 = lds64(pe + i * 32), c = make_float2(p.z, p.w);
        const float mag = ex2(p.x * x0), ph = p.y * x0;
        float2 e0 = make_float2(mag * __cosf(ph), mag * __sinf(ph)), e1 = cmul(e0, e8);
#pragma unroll
        for (int j = 0; j < 4; j++) {
            a[j][2 * i] = pack_bf16(e0.x, e0.y); a[j][2 * i + 1] = pack_bf16(e1.x, e1.y);
            e0 = csq(e0); e1 = csq(e1);
        }
        float2 m = cmul(c, e0);
        b[0][i] = pack_bf16(m.x, -m.y);
#pragma unroll
        for (int j = 0; j < 4; j++) {
            m = cmul(c, e1);
            b[j + 1][i] = pack_bf16(m.x, -m.y);
            if (j < 3) e1 = csq(e1);
        }
    }
}
__device__ __forceinline__ void kg_mma(float (&kd)[5][4], const uint32_t (&a)[4][4], const uint32_t (&b)[5][2]) {
    mma16(kd[0], a[0], b[0][0], b[0][1]);
#pragma unroll
    for (int j = 0; j < 4; j++) mma16(kd[j + 1], a[j], b[j + 1][0], b[j + 1][1]);
}
struct KgRaw { uint2 v[6]; float ldt; };
__device__ __forceinline__ void kg_load(KgRaw& r, const S4Params& P, int d, int lane) {
    const bf16* src[6] = {P.Are, P.Aim, P.Bre, P.Bim, P.Cre, P.Cim};
#pragma unroll
    for (int j = 0; j < 6; j++) r.v[j] = __ldg((const uint2*)(src[j] + d * 128) + lane);
    r.ldt = __bfloat162float(P.ldt[d]);
}
__device__ __forceinline__ float kg_params(const KgRaw& r, uint32_t stg, int lane) {
    const float dt = __bfloat162float(__float2bfloat16(expf(r.ldt)));
    float k2048 = 0.f;
#pragma unroll
    for (int i = 0; i < 4; i++) {
        const float br = dt * bf_at(r.v[2], i), bi = dt * bf_at(r.v[3], i), cr = bf_at(r.v[4], i), ci = bf_at(r.v[5], i);
        const float zr = dt * bf_at(r.v[0], i) * 1.4426950408889634f;
        float zt = dt * bf_at(r.v[1], i) * 0.15915494309189535f;
        zt -= rintf(zt);
        const float v[4] = {zr, zt * 6.283185307179586f, cr * br - ci * bi, cr * bi + ci * br};
        const float2 e8 = cexp_t(8.f * zr, 8.f * zt), el = cexp_t(2048.f * zr, 2048.f * zt);
        k2048 += v[2] * el.x - v[3] * el.y;
        sts128(stg + (i * 32 + lane) * 16, v);
        sts64(stg + 2048 + (i * 32 + lane) * 8, e8.x, e8.y);
    }
#pragma unroll
    for (int o = 16; o; o >>= 1) k2048 += __shfl_xor_sync(0xffffffffu, k2048, o);
    __syncwarp();
    return k2048;
}
__device__ __forceinline__ void kg_store(const float (&kd)[5][4], float k2048, uint32_t stg, int d, int lane) {
    __syncwarp();
    const uint32_t ta = stg + (lane & 7) * 32 + ((lane >> 3) & 1) * 16 + (lane >> 4) * 256;
    stsm4t(ta, pack_bf16(kd[0][0], kd[0][1]), pack_bf16(kd[0][2], kd[0][3]), pack_bf16(kd[1][0], kd[1][1]), pack_bf16(kd[1][2], kd[1][3]));
    stsm4t(ta + 512, pack_bf16(kd[2][0], kd[2][1]), pack_bf16(kd[2][2], kd[2][3]), pack_bf16(kd[3][0], kd[3][1]), pack_bf16(kd[3][2], kd[3][3]));
    stsm4t(ta + 1024, pack_bf16(kd[4][0], kd[4][1]), pack_bf16(kd[4][2], kd[4][3]), pack_bf16(k2048, 0.f), 0);
    __syncwarp();
#pragma unroll
    for (int j = 0; j < 3; j++) ((float4*)(g_kd + d * 768))[j * 32 + lane] = lds128(stg + j * 512 + lane * 16);
    __syncwarp();
}

__global__ void __cluster_dims__(3, 1, 1) __launch_bounds__(CH_THREADS, 1)
chain_kernel(const __grid_constant__ CUtensorMap mq, const __grid_constant__ CUtensorMap mk, const __grid_constant__ CUtensorMap mv,
             const __grid_constant__ CUtensorMap mo, const bf16* __restrict__ Wq, const bf16* __restrict__ Wk, const bf16* __restrict__ Wv,
             const bf16* __restrict__ mem0, const __grid_constant__ S4Params P, int aware) {
    extern __shared__ __align__(1024) unsigned char smem[];
    const uint32_t sb = smem_u32(smem);
    const int tid = threadIdx.x, lane = tid & 31;
    const int w = __shfl_sync(0xffffffffu, tid >> 5, 0);
    int rank; asm("mov.u32 %0, %%cluster_ctarank;" : "=r"(rank));
    const int h = blockIdx.x / 3;
    if (tid == 0) {
        mbar_init(sb + CH_BAR, 1); mbar_init(sb + CH_BAR + 8, 1); mbar_init(sb + CH_BAR + 16, 1);
        for (int i = 0; i < 16; i++) mbar_init(sb + CH_BAR + 64 + i * 8, 1);
        *(int*)(smem + CH_BAR + 24) = 0; *(int*)(smem + CH_BAR + 28) = 0; *(int*)(smem + CH_BAR + 32) = 0;
        asm volatile("fence.mbarrier_init.release.cluster;" ::: "memory");
    }
    if (w == 10 && PFKV) {
        const int e = lane * 96 + blockIdx.x;
        if (e < 2048) asm volatile("cp.async.bulk.prefetch.L2.global [%0], 8192;" ::"l"(((e & 1) ? Wv : Wk) + (size_t)(e >> 1) * HD) : "memory");
        if (PFKV > 1) __nanosleep(PFKV);
    }
    if (w == 9) {
        char* const rb = reset_ptr(lane, rank, h);
#pragma unroll
        for (int i = 0; i < 8; i++)
            asm volatile("st.relaxed.gpu.global.v4.u32 [%0], {%1,%1,%1,%1};" ::"l"(rb + (((i >> 2) << 14) + ((i >> 1) & 1) * 4096 + (i & 1) * 128)), "r"(SENT) : "memory");
        if (lane < 16) g_kvf[blockIdx.x * 16 + lane] = 0;
        if (blockIdx.x == 0)
            for (int k = lane; k < N_CTR; k += 32) g_ctr[k] = 0;
        fence_gpu();
        __syncwarp();
        asm volatile("griddepcontrol.launch_dependents;" ::: "memory");
    }
    __syncthreads();
    asm volatile("barrier.cluster.arrive.relaxed.aligned;" ::: "memory");

    if (w >= 8) {
        reg_dec<24>();
        asm volatile("barrier.cluster.wait.aligned;" ::: "memory");
        if (w == 8) chain_pace(sb, lane, rank, aware);
        else if (w == 9) {
            chain_chores(sb, lane, rank, h, mem0);
            asm volatile("st.volatile.shared.u32 [%0], %1;" ::"r"(sb + CH_BAR + 32), "r"(0x3F803F80) : "memory");
        } else if (w == 11 && KEEP) {
#pragma unroll 1
            for (int it = 0; it < (1 << 22); it++) {
                int d0, d1;
                const uint32_t x = delay<1>(sb + CH_BAR + 32);
                asm volatile("mma.sync.aligned.m8n8k16.row.col.s32.s8.s8.s32 {%0,%1}, {%2}, {%2}, {%3,%3};" : "=r"(d0), "=r"(d1) : "r"(x), "r"(0));
                if (d0 | d1) break;
                if ((XB & 8) && lane == 0) asm volatile("st.relaxed.gpu.global.u32 [%0], %1;" ::"l"(g_kd + DM * 768 + blockIdx.x * 64), "r"(it) : "memory");
                if ((XB & 16) && lane == 0) ld_acq((int*)(g_kd + DM * 768 + blockIdx.x * 64));
                __nanosleep(KEEP);
            }
        }
    } else {
        reg_inc<240>();
        const int nq = rank == 0 ? 6 : 5;
        const int u0 = rank == 0 ? 0 : 1 + 5 * rank;
        const int v0 = rank == 0 ? -6 : 3 * rank - 6;
        const int gw = rank * 8 + w;
        const int ks0 = gw < 16 ? 11 * gw : 176 + 10 * (gw - 16);
        const int nko = gw < 16 ? 11 : 10;
        const uint32_t wr = sb + w * CH_WREG, bar0 = sb + CH_BAR + 64 + w * 16, bar1 = bar0 + 8;
        uint32_t wa[36][4];
        const uint32_t vst = sb + CH_PART + w * 2048;
        const int cq = h * DH + 8 * u0, cv = h * DH + 16 * (v0 + 6);
        const int r8 = lane >> 2, p = lane & 3;
        const bf16* src = p >= 2 ? ((p & 1) ? Wk : Wq) + cq + 32 : rank == 0 ? ((p & 1) ? Wk : Wq) + cq + 40 : Wv + cv - 16 + 8 * p;
        src += (size_t)(128 * w + r8) * HD;
        auto cp_rows = [&](int kh) {
            cp16(wr + ((kh >> 1) * 2 + (p >> 1)) * 512 + ((kh & 1) * 2 + (p & 1)) * 128 + r8 * 16, src + (size_t)kh * 8 * HD);
        };
        {
            int d = blockIdx.x * 8 + w, t = 0;
            const int d1 = 768 + blockIdx.x * 3 + w, nt = (w < 3 && d1 < DM) ? 32 : 16;
            const uint32_t stg = wr + 4096;
            KgRaw raw, raw1;
            kg_load(raw, P, d, lane);
            kg_load(raw1, P, min(d1, DM - 1), lane);
            float kd[5][4], k2048;
#pragma unroll 1
            for (int i = -LDW; i < 9 || t < nt; i++) {
                if (i >= 0 && i < 9) {
                    const uint32_t bar = bar0 + (i & 1) * 8;
                    if (i >= 2) mbar_wait(bar, ((i >> 1) - 1) & 1);
                    if (elect()) {
                        mbar_expect(bar, 2048);
                        if (i < 8) tma2d(wr + 8192 + (i & 1) * 8192 + (i >> 1) * 2048, (i & 1) ? &mk : &mq, cq, 128 * w + 32 * (i >> 1), bar);
                        else tma2d(vst, &mv, cv, 128 * w, bar);
                    }
                    if (i < 8) cp_rows(i);
                }
#pragma unroll 1
                for (int e = min(t + KGS, nt); t < e; t++) {
                    if ((t & 15) == 0) {
                        k2048 = kg_params(raw, stg, lane);
#pragma unroll
                        for (int j = 0; j < 20; j++) kd[j >> 2][j & 3] = 0.f;
                    }
                    uint32_t ka[4][4], kb[5][2];
                    kg_step(ka, kb, stg + ((t & 15) * 8 + (lane & 3)) * 16, stg + 2048 + ((t & 15) * 8 + (lane & 3)) * 8, (float)(lane >> 2));
                    kg_mma(kd, ka, kb);
                    if ((t & 15) == 15) { kg_store(kd, k2048, stg, d, lane); raw = raw1; d = d1; }
                }
            }
        }
        const uint32_t lrow = ((lane >> 4) * 8 + (lane & 7)) * 64, lsw = (lane >> 1) & 3, lh = (lane >> 3) & 1;
        mbar_wait(bar1, 1); mbar_wait(bar0, 0);
#pragma unroll
        for (int i = 0; i < 32; i++) ldsm4t(wa[i], wr + 8192 + lh * 8192 + (i & 7) * 1024 + lrow + (((i >> 3) ^ lsw) << 4));
#pragma unroll
        for (int i = 0; i < 4; i++) ldsm4t(wa[32 + i], vst + (i >> 1) * 1024 + lrow + ((((i & 1) * 2 + lh) ^ lsw) << 4));
        asm volatile("fence.proxy.async.shared::cta;" ::"r"(wa[31][0]), "r"(wa[35][0]) : "memory");
        __syncwarp();
#pragma unroll 1
        for (int i = 9; i < 18; i++) {
            const uint32_t bar = bar0 + (i & 1) * 8;
            if (i >= 11) mbar_wait(bar, ((i >> 1) - 1) & 1);
            if (elect()) {
                const int j = 2 * (i - 12), nb = min(2, nko - j);
                mbar_expect(bar, i < 12 ? 2048 : nb * 1024);
                if (i < 12) tma2d(wr + 8192 + (i - 9) * 2048, &mv, cv, 128 * w + 32 * (i - 8), bar);
                else {
                    if (nb > 0) tma2d(wr + 14336 + j * 1024, &mo, 32 * h, 16 * (ks0 + j), bar);
                    if (nb > 1) tma2d(wr + 15360 + j * 1024, &mo, 32 * h, 16 * (ks0 + j + 1), bar);
                }
            }
            if (i < 17) cp_rows(i - 1);
        }
        mbar_wait(bar0, 0); mbar_wait(bar1, 0);
#pragma unroll 1
        for (int i0 = -1; i0 < 17; i0 += 6) {
            uint32_t x[6][2][4];
#pragma unroll
            for (int i = 0; i < 6; i++) {
                const uint32_t a = wr + 8192 + max(i0 + i, 0) * 1024 + lrow;
                ldsm4t(x[i][0], a + ((lh ^ lsw) << 4)); ldsm4t(x[i][1], a + (((2 + lh) ^ lsw) << 4));
            }
            if (i0 == 11 && nko == 10) {
#pragma unroll
                for (int j = 0; j < 8; j++) x[5][j >> 2][j & 3] = 0;
            }
            __syncwarp();
#pragma unroll
            for (int i = 0; i < 6; i++) {
                const uint32_t a = wr + 8192 + max(i0 + i, 0) * 1024 + lane * 16;
                stsm4t(a, x[i][0][0], x[i][0][1], x[i][0][2], x[i][0][3]); stsm4t(a + 512, x[i][1][0], x[i][1][1], x[i][1][2], x[i][1][3]);
            }
        }
        asm volatile("cp.async.wait_all;" ::: "memory");
        asm volatile("barrier.cluster.wait.aligned;" ::: "memory");
        bar_sync(1, 256);
        mbar_wait_long(sb + CH_BAR + 16, 0);
        const int side = __shfl_sync(0xffffffffu, *(volatile int*)(smem + CH_BAR + 28), 0);
        if (w >= nq) chain_loop<true>(wa, sb, w, lane, rank, h, side);
        else chain_loop<false>(wa, sb, w, lane, rank, h, side);
    }
}

constexpr int G_STAGE = 49152, G_NST = 4;
constexpr int G_STG = G_NST * G_STAGE;
constexpr int G_BAR = G_STG + 32768;
constexpr int G_SMEM = G_BAR + 256 + 1024;

#define WLOG(e)
constexpr int IT_QA = 0, IT_O = 1, IT_S4 = 2, IT_END = 3, IT_KV = 4;
#define O_WIDE 10
#define PING 1
#define S4DIR 5
#define S4REL 4
#define KVI 2
#define KVF 2
#define KVS 8
#define STM 0
__device__ __forceinline__ void st_out(uint32_t* p, uint32_t v) {
    if (STM == 0) *p = v;
    else if (STM == 1) __stcs(p, v);
    else asm volatile("st.global.L1::no_allocate.u32 [%0], %1;" ::"l"(p), "r"(v) : "memory");
}
#define Q_N1 1
#define Q_S1 16
__device__ __forceinline__ int queue_item(int q) {
    if (q < 512) return (IT_KV << 16) | ((q >> 5) << 8) | (q & 31);
    q -= 512;
    if (q < 256) return (IT_QA << 16) | ((q >> 4) << 8) | (q & 15);
    q -= 256;
    if (q < Q_N1 * 8) return (IT_O << 16) | ((O_WIDE + (q >> 3)) << 8) | (q & 7);
    q -= Q_N1 * 8;
    if (q < Q_S1) return (IT_S4 << 16) | q;
    q -= Q_S1;
    if (q < (16 - O_WIDE - Q_N1) * 8) return (IT_O << 16) | ((O_WIDE + Q_N1 + (q >> 3)) << 8) | (q & 7);
    q -= (16 - O_WIDE - Q_N1) * 8;
    if (q < 128 - Q_S1) return (IT_S4 << 16) | (Q_S1 + q);
    return IT_END << 16;
}
__device__ __forceinline__ void tma2d_store(const CUtensorMap* m, uint32_t src, int c0, int c1) {
    asm volatile("cp.async.bulk.tensor.2d.global.shared::cta.bulk_group [%0, {%2, %3}], [%1];" ::"l"(m), "r"(src), "r"(c0), "r"(c1) : "memory");
}

__device__ __forceinline__ void wgmma_s64(float (&d)[32], uint32_t a0, uint32_t a1, uint32_t a2, uint32_t a3, uint64_t db, int acc) {
    asm volatile("{.reg .pred p; setp.ne.b32 p, %37, 0;\n"
        "wgmma.mma_async.sync.aligned.m64n64k16.f32.bf16.bf16 {"
        "%0,%1,%2,%3,%4,%5,%6,%7,%8,%9,%10,%11,%12,%13,%14,%15,"
        "%16,%17,%18,%19,%20,%21,%22,%23,%24,%25,%26,%27,%28,%29,%30,%31"
        "}, {%32,%33,%34,%35}, %36, p, 1, 1, 0;}"
        : "+f"(d[0]), "+f"(d[1]), "+f"(d[2]), "+f"(d[3]), "+f"(d[4]), "+f"(d[5]), "+f"(d[6]), "+f"(d[7]), "+f"(d[8]), "+f"(d[9]), "+f"(d[10]), "+f"(d[11]), "+f"(d[12]), "+f"(d[13]), "+f"(d[14]), "+f"(d[15]), "+f"(d[16]), "+f"(d[17]), "+f"(d[18]), "+f"(d[19]), "+f"(d[20]), "+f"(d[21]), "+f"(d[22]), "+f"(d[23]), "+f"(d[24]), "+f"(d[25]), "+f"(d[26]), "+f"(d[27]), "+f"(d[28]), "+f"(d[29]), "+f"(d[30]), "+f"(d[31])
        : "r"(a0), "r"(a1), "r"(a2), "r"(a3), "l"(db), "r"(acc));
}
__device__ __forceinline__ void wgmma_s16(float (&d)[8], uint32_t a0, uint32_t a1, uint32_t a2, uint32_t a3, uint64_t db, int acc) {
    asm volatile("{.reg .pred p; setp.ne.b32 p, %13, 0;\n"
        "wgmma.mma_async.sync.aligned.m64n16k16.f32.bf16.bf16 {"
        "%0,%1,%2,%3,%4,%5,%6,%7"
        "}, {%8,%9,%10,%11}, %12, p, 1, 1, 0;}"
        : "+f"(d[0]), "+f"(d[1]), "+f"(d[2]), "+f"(d[3]), "+f"(d[4]), "+f"(d[5]), "+f"(d[6]), "+f"(d[7])
        : "r"(a0), "r"(a1), "r"(a2), "r"(a3), "l"(db), "r"(acc));
}
__device__ __forceinline__ void wgmma_v128(float (&d)[64], uint32_t a0, uint32_t a1, uint32_t a2, uint32_t a3, uint64_t db, int acc) {
    asm volatile("{.reg .pred p; setp.ne.b32 p, %69, 0;\n"
        "wgmma.mma_async.sync.aligned.m64n128k16.f32.bf16.bf16 {"
        "%0,%1,%2,%3,%4,%5,%6,%7,%8,%9,%10,%11,%12,%13,%14,%15,"
        "%16,%17,%18,%19,%20,%21,%22,%23,%24,%25,%26,%27,%28,%29,%30,%31,"
        "%32,%33,%34,%35,%36,%37,%38,%39,%40,%41,%42,%43,%44,%45,%46,%47,"
        "%48,%49,%50,%51,%52,%53,%54,%55,%56,%57,%58,%59,%60,%61,%62,%63"
        "}, {%64,%65,%66,%67}, %68, p, 1, 1, 1;}"
        : "+f"(d[0]), "+f"(d[1]), "+f"(d[2]), "+f"(d[3]), "+f"(d[4]), "+f"(d[5]), "+f"(d[6]), "+f"(d[7]), "+f"(d[8]), "+f"(d[9]), "+f"(d[10]), "+f"(d[11]), "+f"(d[12]), "+f"(d[13]), "+f"(d[14]), "+f"(d[15]), "+f"(d[16]), "+f"(d[17]), "+f"(d[18]), "+f"(d[19]), "+f"(d[20]), "+f"(d[21]), "+f"(d[22]), "+f"(d[23]), "+f"(d[24]), "+f"(d[25]), "+f"(d[26]), "+f"(d[27]), "+f"(d[28]), "+f"(d[29]), "+f"(d[30]), "+f"(d[31]), "+f"(d[32]), "+f"(d[33]), "+f"(d[34]), "+f"(d[35]), "+f"(d[36]), "+f"(d[37]), "+f"(d[38]), "+f"(d[39]), "+f"(d[40]), "+f"(d[41]), "+f"(d[42]), "+f"(d[43]), "+f"(d[44]), "+f"(d[45]), "+f"(d[46]), "+f"(d[47]), "+f"(d[48]), "+f"(d[49]), "+f"(d[50]), "+f"(d[51]), "+f"(d[52]), "+f"(d[53]), "+f"(d[54]), "+f"(d[55]), "+f"(d[56]), "+f"(d[57]), "+f"(d[58]), "+f"(d[59]), "+f"(d[60]), "+f"(d[61]), "+f"(d[62]), "+f"(d[63])
        : "r"(a0), "r"(a1), "r"(a2), "r"(a3), "l"(db), "r"(acc));
}

__device__ __forceinline__ void attn_scores(float (&sx)[32], float (&sm)[8], const uint32_t (&q)[32], uint32_t sk) {
    const uint64_t dx = mkdesc(sk, 1024, 128, 0), dm = mkdesc(sk + 16384, 256, 128, 0);
    wg_fence();
#pragma unroll
    for (int ks = 0; ks < 8; ks++) {
        wgmma_s64(sx, q[4 * ks], q[4 * ks + 1], q[4 * ks + 2], q[4 * ks + 3], dx + ks * 128, ks);
        wgmma_s16(sm, q[4 * ks], q[4 * ks + 1], q[4 * ks + 2], q[4 * ks + 3], dm + ks * 32, ks);
    }
    wg_commit();
}
template <bool HI>
__device__ __forceinline__ void attn_softmax(uint32_t (&p)[2][20], const float (&sx)[2][32], const float (&sm)[2][8], bool sb, int lane) {
    constexpr int NF = HI ? 2 : 0, NT = NF + 3;
    const int gt = (lane >> 2) - 2 * (lane & 3);
    const float cs = 0.08838834764831845f * 1.4426950408889634f;
    float s[2][NT][4], m[4], l[4];
#pragma unroll
    for (int h = 0; h < 2; h++) {
#pragma unroll
        for (int j = 0; j < NT; j++)
#pragma unroll
            for (int e = 0; e < 4; e++) s[h][j][e] = j == NT - 1 ? (sb ? sm[h][4 + e] : sm[h][e]) : (sb ? sx[h][16 + 4 * j + e] : sx[h][4 * j + e]);
        if (gt < 0) s[h][NF][0] = s[h][NF + 1][2] = -INFINITY;
        if (gt < 1) s[h][NF][1] = s[h][NF + 1][3] = -INFINITY;
        m[2 * h] = fmaxf(s[h][0][0], s[h][0][1]); m[2 * h + 1] = fmaxf(s[h][0][2], s[h][0][3]);
#pragma unroll
        for (int j = 1; j < NT; j++) {
            if (j != NF + 1) m[2 * h] = fmaxf(m[2 * h], fmaxf(s[h][j][0], s[h][j][1]));
            m[2 * h + 1] = fmaxf(m[2 * h + 1], fmaxf(s[h][j][2], s[h][j][3]));
        }
    }
#pragma unroll
    for (int r = 0; r < 4; r++) m[r] = fmaxf(m[r], __shfl_xor_sync(0xffffffffu, m[r], 1));
#pragma unroll
    for (int r = 0; r < 4; r++) m[r] = fmaxf(m[r], __shfl_xor_sync(0xffffffffu, m[r], 2)) * -cs;
#pragma unroll
    for (int r = 0; r < 4; r++) {
        l[r] = 0.f;
#pragma unroll
        for (int j = 0; j < NT; j++)
            if ((r & 1) || j != NF + 1) {
                float* v = &s[r >> 1][j][2 * (r & 1)];
                v[0] = ex2(fmaf(v[0], cs, m[r])); v[1] = ex2(fmaf(v[1], cs, m[r]));
                l[r] += v[0] + v[1];
            }
    }
#pragma unroll
    for (int r = 0; r < 4; r++) l[r] += __shfl_xor_sync(0xffffffffu, l[r], 1);
#pragma unroll
    for (int r = 0; r < 4; r++) { l[r] += __shfl_xor_sync(0xffffffffu, l[r], 2); asm("rcp.approx.ftz.f32 %0, %0;" : "+f"(l[r])); }
    const uint32_t ma = sb ? 0u : ~0u;
#pragma unroll
    for (int h = 0; h < 2; h++)
#pragma unroll
        for (int j = 0; j < 5; j++) {
            const bool on = j == 4 || j < NF + 2;
            const int k = j == 4 ? NT - 1 : on ? j : 0, ia = j < 4 ? 2 * j : 16, ib = j < 4 ? 8 + 2 * j : 18;
            const uint32_t x = on && j != NF + 1 ? pack_bf16(s[h][k][0] * l[2 * h], s[h][k][1] * l[2 * h]) : 0;
            const uint32_t y = on ? pack_bf16(s[h][k][2] * l[2 * h + 1], s[h][k][3] * l[2 * h + 1]) : 0;
            asm volatile("and.b32 %0, %4, %6; and.b32 %1, %5, %6; and.b32 %2, %4, %7; and.b32 %3, %5, %7;"
                : "=&r"(p[h][ia]), "=&r"(p[h][ia + 1]), "=&r"(p[h][ib]), "=&r"(p[h][ib + 1]) : "r"(x), "r"(y), "r"(ma), "r"(~ma));
        }
}
__device__ __forceinline__ void attn_pv(float (&o)[64], const uint32_t (&p)[20], uint32_t sv) {
    const uint64_t dx = mkdesc(sv, 128, 1024, 0), dm = mkdesc(sv + 16384, 128, 256, 0);
    wg_fence();
#pragma unroll
    for (int ks = 0; ks < 5; ks++) wgmma_v128(o, p[4 * ks], p[4 * ks + 1], p[4 * ks + 2], p[4 * ks + 3], ks < 4 ? dx + ks * 16 : dm, ks);
    wg_commit();
}
__device__ __forceinline__ void attn_stage(const float (&o)[64], uint32_t dst) {
#pragma unroll
    for (int u = 0; u < 16; u += 2)
        stsm4(dst + (u >> 3) * 8192 + (u & 7) * 128, pack_bf16(o[4 * u], o[4 * u + 1]), pack_bf16(o[4 * u + 2], o[4 * u + 3]),
              pack_bf16(o[4 * u + 4], o[4 * u + 5]), pack_bf16(o[4 * u + 6], o[4 * u + 7]));
}

template <int BN, int NKB, bool BLOCKED_A>
__device__ __forceinline__ void mainloop(float (&acc)[BN / 2], uint32_t sb, int wgi, uint32_t full, uint32_t empty, int& it, bool elect) {
#pragma unroll
    for (int j = 0; j < BN / 2; j++) acc[j] = 0.f;
#pragma unroll 1
    for (int k4 = 0; k4 < NKB; k4 += 4) {
#pragma unroll
        for (int st = 0; st < 4; st++, it++) {
            mbar_wait_long(full + 8 * st, (it >> 2) & 1);
            const uint64_t da = BLOCKED_A ? mkdesc(sb + st * G_STAGE + wgi * 8192, 128, 1024, 0) : mkdesc(sb + st * G_STAGE + wgi * 8192, 16, 1024, 1);
            const uint64_t db = mkdesc(sb + st * G_STAGE + 16384, 8192, 1024, 1);
            wg_fence();
#pragma unroll
            for (int k = 0; k < 4; k++) {
                if constexpr (BN == 256) wgmma256(acc, da + k * (BLOCKED_A ? 16 : 2), db + k * 128, 1);
                else wgmma128(acc, da + k * (BLOCKED_A ? 16 : 2), db + k * 128, 1);
            }
            wg_commit();
            if (k4 | st) {
                wg_wait<1>();
                if (elect) mbar_arrive(empty + 8 * ((st + 3) & 3));
            }
        }
    }
    wg_wait<0>();
    if (elect) mbar_arrive(empty + 8 * 3);
}

__device__ __forceinline__ uint32_t n6_a(int st) { return st < 4 ? st * G_STAGE : (2 * st - 8) * G_STAGE + 32768; }
__device__ __forceinline__ uint32_t n6_b(int st) { return st < 4 ? st * G_STAGE + 16384 : (2 * st - 7) * G_STAGE + 32768; }
__device__ __forceinline__ uint32_t n6_bar(int st) { return st < 4 ? 8 * st : 96 + 8 * st; }
__device__ __forceinline__ void mainloop6(float (&acc)[64], uint32_t sb, int wgi, uint32_t full, uint32_t empty, int& it, bool elect) {
#pragma unroll
    for (int j = 0; j < 64; j++) acc[j] = 0.f;
    int st = 0, prev = 0, r = 0;
#pragma unroll 1
    for (int kb = 0; kb < 64; kb++) {
        mbar_wait_long(full + n6_bar(st), ((st < 4 ? it >> 2 : 0) + r) & 1);
        const uint64_t da = mkdesc(sb + n6_a(st) + wgi * 8192, 128, 1024, 0), db = mkdesc(sb + n6_b(st), 8192, 1024, 1);
        wg_fence();
#pragma unroll
        for (int k = 0; k < 4; k++) wgmma128(acc, da + k * 16, db + k * 128, 1);
        wg_commit();
        if (kb) {
            wg_wait<1>();
            if (elect) mbar_arrive(empty + n6_bar(prev));
        }
        prev = st;
        if (++st == 6) { st = 0; r++; }
    }
    wg_wait<0>();
    if (elect) mbar_arrive(empty + 8 * 3);
    it += 44;
}

template <int BN>
__device__ __forceinline__ void o_item(uint32_t sb, int wgi, int wi, int lane, uint32_t full, uint32_t empty, int& it, const CUtensorMap* mout,
                                       int row0, int col0, uint32_t stgpar) {
    float acc[BN / 2];
    if constexpr (BN == 256) mainloop<BN, 64, true>(acc, sb, wgi, full, empty, it, lane == 0);
    else mainloop6(acc, sb, wgi, full, empty, it, lane == 0);
    ST((row0 >> 4) + (col0 / BN), wgi * 4 + wi, 10);
    mbar_wait(full + 104, stgpar);
    const uint32_t stg = sb + G_STG + (wgi * 4 + wi) * 4096;
    const int r = lane & 15, cu = lane >> 4;
#pragma unroll
    for (int hf = 0; hf < BN / 128; hf++) {
        if (elect()) asm volatile("cp.async.bulk.wait_group.read 0;" ::: "memory");
        __syncwarp();
#pragma unroll
        for (int j = 0; j < 8; j++) {
            const float* a = acc + hf * 64 + j * 8;
            stsm4(stg + (j >> 2) * 2048 + r * 128 + ((((j & 3) * 2 + cu) ^ (r & 7)) << 4),
                  pack_bf16(a[0], a[1]), pack_bf16(a[2], a[3]), pack_bf16(a[4], a[5]), pack_bf16(a[6], a[7]));
        }
        asm volatile("fence.proxy.async.shared::cta;" ::: "memory");
        __syncwarp();
        if (elect()) {
            tma2d_store(mout, stg, col0 + hf * 128, row0 + wgi * 64 + wi * 16);
            tma2d_store(mout, stg + 2048, col0 + hf * 128 + 64, row0 + wgi * 64 + wi * 16);
            asm volatile("cp.async.bulk.commit_group;" ::: "memory");
        }
    }
}

constexpr int S4_KD = 32768;
constexpr int S4_CH = 2 * G_STAGE;
constexpr int S4_HALF = 2304;
constexpr int S4_WD = 2 * S4_HALF;
constexpr int S4_T2 = S4_WD + 2304;
constexpr int S4_T3 = S4_T2 + 1024;
constexpr int S4_STRIDE = S4_T3 + 640 + 16;
__device__ __forceinline__ uint32_t addz(uint32_t x, uint32_t z) { uint32_t r; asm volatile("add.u32 %0, %1, %2;" : "=r"(r) : "r"(x), "r"(z)); return r; }
__device__ __forceinline__ uint32_t lds16(uint32_t a) { uint32_t v; asm volatile("ld.shared.u16 %0, [%1];" : "=r"(v) : "r"(a) : "memory"); return v; }
__device__ __forceinline__ uint32_t ldsu(uint32_t a) { return __float_as_uint(lds32(a)); }

template <int E0, int NE, int KP>
__device__ __forceinline__ void s4_windows(float (&acc)[8][2][4], uint32_t ut, uint32_t tw, int rho, int w, int lane, uint32_t z) {
    const int gt = (lane >> 2) - 2 * (lane & 3), p0 = rho == 16 ? -3 : -2, c = (lane >> 3) + p0;
    uint32_t band[2][4], ta[NE][4];
    {
        const uint64_t ones = ((uint64_t)((2u << 2 * w) - 1) << 32) >> (8 * p0 + 24 - gt + rho + w);
        uint32_t f[5];
#pragma unroll
        for (int m = 0; m < 5; m++) f[m] = ((((uint32_t)(ones >> (8 * m)) & 3) * 0x8001u) & 0x10001u) * 0x3F80u;
#pragma unroll
        for (int j = 0; j < 2; j++) { band[j][0] = f[2 * j + 1]; band[j][1] = addz(f[2 * j], z); band[j][2] = f[2 * j + 2]; band[j][3] = addz(f[2 * j + 1], z); }
    }
#pragma unroll
    for (int e = 0; e < NE; e++)
        asm volatile("ld.shared.u32 %0, [%4]; ld.shared.u32 %1, [%4+%5]; ld.volatile.shared.u32 %2, [%4+%6]; ld.volatile.shared.u32 %3, [%4];"
            : "=r"(ta[e][0]), "=r"(ta[e][1]), "=r"(ta[e][2]), "=r"(ta[e][3]) : "r"(tw + 16 * (E0 + e) * KP), "n"(8 * KP), "n"(-8 * KP) : "memory");
    const uint32_t ua = ut + (c & 1) * S4_HALF + (16 + (lane & 7) + (c >> 1)) * 16;
#pragma unroll
    for (int J = 0; J < 8 - E0; J++) {
        uint32_t u0[4], u1[4];
        ldsm4(u0, ua + J * 256); ldsm4(u1, ua + J * 256 + 128);
        float s0[4], s1[4];
        mma16z(s0, band[0], u0[0], u0[1]); mma16z(s1, band[0], u1[0], u1[1]);
        mma16(s0, band[1], u0[2], u0[3]); mma16(s1, band[1], u1[2], u1[3]);
        const uint32_t b00 = pack_bf16(s0[0], s0[1]), b01 = pack_bf16(s1[0], s1[1]), b10 = pack_bf16(s0[2], s0[3]), b11 = pack_bf16(s1[2], s1[3]);
#pragma unroll
        for (int e = 0; e < NE; e++)
            if (J + E0 + e < 8) { mma16(acc[J + E0 + e][0], ta[e], b00, b01); mma16(acc[J + E0 + e][1], ta[e], b10, b11); }
    }
}
template <int D0, int D1>
__device__ __forceinline__ void s4_dense(float (&acc)[8][2][4], uint32_t ua, const uint32_t (&b0)[4], const uint32_t (&b1)[4]) {
#pragma unroll
    for (int J = 0; J < 8 - D0; J++) {
        uint32_t a[4];
        ldsm4(a, ua + J * 256);
        mma16(acc[J + D0][0], a, b0[0], b0[1]); mma16(acc[J + D0][1], a, b0[2], b0[3]);
        if (J + D1 < 8) { mma16(acc[J + D1][0], a, b1[0], b1[1]); mma16(acc[J + D1][1], a, b1[2], b1[3]); }
    }
}
__device__ __forceinline__ void s4_words(uint32_t (&b)[4], uint32_t wd) {
    asm volatile("ld.shared.u32 %0, [%4]; ld.shared.u32 %1, [%4+-32]; ld.shared.u32 %2, [%4+32]; ld.volatile.shared.u32 %3, [%4];"
        : "=r"(b[0]), "=r"(b[1]), "=r"(b[2]), "=r"(b[3]) : "r"(wd) : "memory");
}

__device__ __forceinline__ void s4_item(uint32_t sb, int cw, int lane, int item, const bf16* __restrict__ dsk, uint32_t empty, const CUtensorMap* my, uint32_t stgpar,
                                        bf16* __restrict__ out, uint32_t nbar, uint32_t npar, uint32_t nslot) {
    const int gt = (lane >> 2) - 2 * (lane & 3);
    const uint32_t ch = sb + S4_CH + cw * S4_STRIDE, kd = sb + S4_KD + cw * 1536;
    const __nv_bfloat162 dk = __bfloat162bfloat162(dsk[item * 8 + cw]);
    ST(item, cw, 0);
    asm volatile("st.shared.v4.u32 [%0], {%1,%1,%1,%1};" ::"r"(ch + (lane >> 4) * S4_HALF + (lane & 15) * 16), "r"(0) : "memory");
    const uint32_t tch = sb + S4_CH + (lane & 7) * S4_STRIDE + ((lane >> 3) & 1) * S4_HALF + (16 + 16 * cw + (lane >> 4)) * 16;
#pragma unroll
    for (int i = 0; i < 8; i++) {
        uint32_t x[4];
        ldsm4t(x, sb + cw * 4096 + i * 512 + lane * 16);
        stsm4(tch + i * 32, x[0], x[1], x[2], x[3]);
    }
    const uint32_t k1024 = lds16(kd + 1024);
    {
        auto st4 = [](uint32_t a, uint32_t x, uint32_t y, uint32_t u, uint32_t v) {
            asm volatile("st.shared.v4.u32 [%0], {%1,%2,%3,%4};" ::"r"(a), "r"(x), "r"(y), "r"(u), "r"(v) : "memory");
        };
        const float4 p = lds128(kd + lane * 16);
        const uint32_t p0 = __float_as_uint(p.x), p1 = __float_as_uint(p.y), p2 = __float_as_uint(p.z), p3 = __float_as_uint(p.w);
        const uint32_t pm = lane ? ldsu(kd + lane * 16 - 4) : 0;
        const uint32_t wa = ch + S4_WD + 64 + lane * 32;
        st4(wa, __byte_perm(p0, pm, 0x7610), __byte_perm(p0, 0, 0x1032), __byte_perm(p1, p0, 0x7610), __byte_perm(p1, 0, 0x1032));
        st4(wa + 16, __byte_perm(p2, p1, 0x7610), __byte_perm(p2, 0, 0x1032), __byte_perm(p3, p2, 0x7610), __byte_perm(p3, 0, 0x1032));
        const float2 q = lds64(kd + 512 + lane * 8);
        const uint32_t q0 = __float_as_uint(q.x), q1 = __float_as_uint(q.y), q2 = ldsu(kd + 520 + lane * 8), k255 = ldsu(kd + 508);
        st4(wa + 1024, lane ? __byte_perm(q0, 0, 0x1010) : __byte_perm(q0, k255, 0x7610), __byte_perm(q0, 0, 0x1010), __byte_perm(q0, 0, 0x1032), __byte_perm(q1, q0, 0x7610));
        st4(wa + 1040, __byte_perm(q1, 0, 0x1010), __byte_perm(q1, 0, 0x1010), __byte_perm(q1, 0, 0x1032), __byte_perm(q2, q1, 0x7610));
        const uint32_t k512 = lane == 4 ? lds16(kd + 768) : 0;
        if (lane < 16) st4(ch + S4_WD + (lane < 4 ? 0 : 2048) + lane * 16, k512 * 0x10001u, k512 * 0x10001u, k512 * 0x10001u, k512 << 16);
        const float2 c = lds64(kd + 768 + lane * 8), d = lds64(kd + 760 + lane * 8);
        const uint32_t c0 = __float_as_uint(c.x), c1 = __float_as_uint(c.y), c2 = ldsu(kd + 776 + lane * 8);
        const uint32_t d0 = lane ? __float_as_uint(d.x) : 0, d1 = lane ? __float_as_uint(d.y) : 0, d2 = lane ? c0 : 0;
        st4(ch + S4_T2 + 256 + lane * 16, __byte_perm(c0, d0, 0x7632), __byte_perm(c1, d1, 0x5410), __byte_perm(c1, d1, 0x7632), __byte_perm(c2, d2, 0x5410));
        const uint32_t m = lane == 31 ? 0xFFFF0000u : 0;
        st4(ch + S4_T2 + (lane < 16 ? lane : lane == 31 ? 48 : lane + 33) * 16, c0 & m, (c1 << 16) & m, c1 & m, (c2 << 16) & m);
        const float2 e = lds64(kd + 1024 + lane * 8);
        const uint32_t e0 = __float_as_uint(e.x), e1 = __float_as_uint(e.y), e2 = ldsu(kd + 1032 + lane * 8), em = ldsu(kd + 1020 + lane * 8);
        st4(ch + S4_T3 + 128 + lane * 16, __byte_perm(e0, lane ? em : 0, 0x7632), __byte_perm(e1, lane ? e0 : 0, 0x5410), __byte_perm(e1, e0, 0x7632), __byte_perm(e2, e1, 0x5410));
        if (lane < 8) st4(ch + S4_T3 + lane * 16, 0, 0, 0, 0);
    }
    bar_sync(2, 256);
    ST(item, cw, 1);
    const uint32_t z = ldsu(ch);
    float acc[8][2][4];
#pragma unroll
    for (int j = 0; j < 16; j++) acc[j >> 1][j & 1][0] = acc[j >> 1][j & 1][1] = acc[j >> 1][j & 1][2] = acc[j >> 1][j & 1][3] = 0.f;
#pragma unroll 1
    for (int r = 1; r <= 4; r++) s4_windows<2, 3, 16>(acc, ch, ch + S4_T2 + (gt - 16) * 16 + 4 * r - 4, 4 * r, 2 - (r & 1), lane, z);
    ST(item, cw, 2);
#pragma unroll 1
    for (int r = 1; r <= 2; r++) s4_windows<4, 4, 8>(acc, ch, ch + S4_T3 + (gt - 48) * 8 + 4 * r - 4, 8 * r, 2 + r, lane, z);
    ST(item, cw, 3);
    const uint32_t ua = ch + (lane >> 4) * S4_HALF + (16 + (lane & 15)) * 16, wd = ch + S4_WD + 64 + gt * 4;
#pragma unroll 1
    for (int q = 0; q < 2; q++) {
        uint32_t b0[4], b1[4];
        s4_words(b0, wd + (q + 32) * 64);
#pragma unroll
        for (int j = 0; j < 4; j++) {
            const int x = 16 * q + gt + (j == 1 ? -8 : j == 2 ? 8 : 0) - 3;
            b1[j] = addz(((unsigned)x < 2u ? k1024 : 0u) | ((unsigned)(x - 1) < 2u ? k1024 << 16 : 0u), z);
        }
        s4_dense<2, 4>(acc, ua - q * 16, b0, b1);
    }
    {
        uint32_t b0[4], b1[4], c0[4], c1[4];
        s4_words(b0, wd); s4_words(b1, wd + 1024);
#pragma unroll 1
        for (int q = 0; q < 16; q += 2) {
            s4_words(c0, wd + q * 64 + 64); s4_words(c1, wd + q * 64 + 64 + 1024);
            s4_dense<0, 1>(acc, ua - q * 16, b0, b1);
            s4_words(b0, wd + q * 64 + 128); s4_words(b1, wd + q * 64 + 128 + 1024);
            s4_dense<0, 1>(acc, ua - q * 16 - 16, c0, c1);
            if (q == S4REL && lane == 0) { mbar_arrive(empty); mbar_arrive(empty + 8); }
        }
    }
    ST(item, cw, 4);
    mbar_wait(empty + 72, stgpar);
    if (elect()) asm volatile("cp.async.bulk.wait_group.read 0;" ::: "memory");
    __syncwarp();
#pragma unroll
    for (int I = 0; I < 8; I++) {
        uint32_t u[4];
        ldsm4(u, ua + I * 256);
#pragma unroll
        for (int j = 0; j < 4; j++) {
            const uint32_t y = pack_bf16(acc[I][j >> 1][2 * (j & 1)], acc[I][j >> 1][2 * (j & 1) + 1]);
            const __nv_bfloat162 r = __hadd2_rn(*(const __nv_bfloat162*)&y, __hmul2_rn(*(const __nv_bfloat162*)&u[j], dk));
            u[j] = *(const uint32_t*)&r;
        }
        stsm4(ua + I * 256, u[0], u[1], u[2], u[3]);
    }
    bar_sync(2, 256);
    uint32_t y[8][4];
#pragma unroll
    for (int i = 0; i < 8; i++) ldsm4t(y[i], tch + i * 32);
    if (cw < S4DIR && mbar_test(nbar, npar) && ldsu(nslot) == (IT_END << 16)) {
        uint32_t* const dst = (uint32_t*)(out + (size_t)(cw * 256 + (lane >> 2)) * (2 * DM) + DM + item * 8) + (lane & 3);
#pragma unroll
        for (int i = 0; i < 32; i++) dst[i * 8 * DM] = y[i >> 2][i & 3];
        return;
    }
#pragma unroll
    for (int i = 0; i < 8; i++) stsm4(sb + G_STG + cw * 4096 + i * 512 + lane * 16, y[i][0], y[i][1], y[i][2], y[i][3]);
    asm volatile("fence.proxy.async.shared::cta;" ::: "memory");
    __syncwarp();
    if (elect()) {
        mbar_arrive(empty + 16); mbar_arrive(empty + 24);
        tma2d_store(my, sb + G_STG + cw * 4096, DM + item * 8, cw * 256);
        asm volatile("cp.async.bulk.commit_group;" ::: "memory");
    }
    ST(item, cw, 5);
}

struct Maps { CUtensorMap m[13]; };
__global__ void __launch_bounds__(384, 1)
worker_kernel(const __grid_constant__ Maps M, const bf16* __restrict__ dsk, bf16* __restrict__ out) {
    const CUtensorMap &mx = M.m[0], &mq = M.m[1], &mo = M.m[4], &mout = M.m[5], &mu = M.m[6], &my = M.m[7];
    extern __shared__ unsigned char smem_raw[];
    const uint32_t sb = (smem_u32(smem_raw) + 1023) & ~1023u;
    const uint32_t full = sb + G_BAR, empty = full + 32, ifull = full + 64, iempty = full + 80, islot = full + 96, stgbar = full + 104, sigbar = full + 112, sigslot = full + 120;
    const int tid = threadIdx.x, wg = tid >> 7, lane = tid & 31;
    int q0 = blockIdx.x;
    const int nfirst = min(32, (int)gridDim.x - 96), wide0 = q0 - ((int)gridDim.x - O_WIDE * 4);
    if (tid == 0 && q0 >= nfirst && wide0 < 0) q0 = nfirst + atomicAdd(g_ctr + C_NEXT, 1);
    if ((tid >> 5) == 1 && elect()) {
#pragma unroll
        for (int i = 0; i < 6; i++) { mbar_init(full + n6_bar(i), 1); mbar_init(empty + n6_bar(i), 8); }
#pragma unroll
        for (int i = 0; i < 2; i++) { mbar_init(ifull + 8 * i, 1); mbar_init(iempty + 8 * i, 8); }
        mbar_init(sigbar, 8); mbar_init(stgbar, 1);
        asm volatile("fence.mbarrier_init.release.cluster;" ::: "memory");
    }
    if ((tid >> 5) == 2 && elect()) {
#pragma unroll
        for (int i = 0; i < 13; i++) asm volatile("prefetch.tensormap [%0];" ::"l"(&M.m[i]) : "memory");
    }
    __syncthreads();
    if (wg == 0) {
        reg_dec<40>();
        if (tid >= 32 && tid < 64) {
            for (int n = 0;; n++) {
                mbar_wait_long(sigbar, n & 1);
                int item; asm volatile("ld.shared.u32 %0, [%1];" : "=r"(item) : "r"(sigslot + 4 * (n & 1)) : "memory");
                const int type = item >> 16, b = (item >> 8) & 255, i = item & 255;
                if (type == IT_END) break;
                if (type == IT_QA) {
                    if (elect()) {
#pragma unroll
                        for (int j = 0; j < 8; j++) {
                            const uint32_t src = sb + (j >= 4 ? G_STG + (j & 1) * 16384 : 3 * G_STAGE + (j & 1) * 20480) + ((j >> 1) & 1) * 8192;
                            asm volatile("cp.async.bulk.global.shared::cta.bulk_group [%0], [%1], 8192;"
                                ::"l"(g_ox + (size_t)(b * 64 + i * 4 + ((j >> 1) ^ 2)) * 8192 + (j & 1) * 4096), "r"(src) : "memory");
                            if ((j & 3) == 3) asm volatile("cp.async.bulk.commit_group;" ::: "memory");
                        }
                        asm volatile("cp.async.bulk.wait_group.read 1;" ::: "memory");
                        asm volatile("mbarrier.arrive.shared.b64 _, [%0], 8;" ::"r"(empty + 24) : "memory");
                        asm volatile("cp.async.bulk.wait_group 0;" ::: "memory");
                        mbar_arrive(stgbar);
                        asm volatile("fence.proxy.async.global;" ::: "memory");
                    }
                    __syncwarp();
                }
                if (type == IT_KV) { if (lane < 6) red_release(g_kvf + ((i & 15) * 6 + lane) * 16 + b, 1); }
                else if (lane == 0) red_release(g_ctr + C_QA_DONE + b, 1 << i);
            }
        } else if (tid < 32) {
            int it = 0;
            bool tables = false;
            if (!KVN) asm volatile("griddepcontrol.wait;" ::: "memory");
            for (int n = 0;; n++) {
                int item = 0;
                if (lane == 0) {
                    if (n) q0 = nfirst + atomicAdd(g_ctr + C_NEXT, 1);
                    item = n == 0 && wide0 >= 0 ? (IT_O << 16) | ((wide0 >> 2) << 8) | (wide0 & 3) : queue_item(q0);
                }
                item = __shfl_sync(0xffffffffu, item, 0);
                mbar_wait(iempty + 8 * (n & 1), ((n >> 1) & 1) ^ 1);
                if (lane == 0) {
                    asm volatile("st.shared.u32 [%0], %1;" ::"r"(islot + 4 * (n & 1)), "r"(item) : "memory");
                    mbar_arrive(ifull + 8 * (n & 1));
                }
                const int type = item >> 16, b = (item >> 8) & 255, i = item & 255;
                bool ready = false;
                if (type == IT_QA || type == IT_KV) {
                    const CUtensorMap* mw = &mq + (type == IT_QA ? 0 : 1 + (i >> 4));
#pragma unroll 1
                    for (int kb = 0; kb < 16; kb++, it++) {
                        const int st = it & 3;
                        mbar_wait(empty + 8 * st, ((it >> 2) & 1) ^ 1);
                        if (elect()) {
                            mbar_expect(full + 8 * st, G_STAGE);
                            tma2d(sb + st * G_STAGE, &mx, kb * 64, b * 128, full + 8 * st);
                            tma3d(sb + st * G_STAGE + 16384, mw, 0, kb * 64, (i & 15) * 4, full + 8 * st);
                        }
                        if (type == IT_QA && kb == 3) ready = __all_sync(0xffffffffu, ld_acq(g_ctr + C_CHAIN + b) >= 96);
                        if (ready && kb < 11 && elect()) {
                            const size_t sh = (b * 4 + ((kb - 3) & 3)) * NH + i * 2;
                            asm volatile("cp.async.bulk.prefetch.L2.global [%0], 16384;" ::"l"((kb >= 7 ? g_vx : g_kx) + sh * 4096) : "memory");
                            asm volatile("cp.async.bulk.prefetch.L2.global [%0], 4096;" ::"l"((kb >= 7 ? g_vm : g_km) + sh * 1024) : "memory");
                        }
                    }
                }
                if (type == IT_QA) {
                    if (!ready) wait_ctr(g_ctr + C_CHAIN + b, 96);
                    tables = true;
                    asm volatile("fence.proxy.async.global;" ::: "memory");
#pragma unroll 1
                    for (int st = 0; st < 4; st++, it++) {
                        mbar_wait(empty + 8 * st, ((it >> 2) & 1) ^ 1);
                        if (elect()) {
                            mbar_expect(full + 8 * st, 4 * 10240);
#pragma unroll
                            for (int j = 0; j < 4; j++)
                                tma3d(sb + st * G_STAGE + (j >> 1) * 20480 + (j & 1) * 16384, &M.m[8 + (st >> 1) + (j & 1) * 2], 0, b * 4 + (j & 2),
                                      (i * 2 + (st & 1)) * 16, full + 8 * st);
                        }
                    }
                } else if (type == IT_O) {
                    const bool wide = b < O_WIDE;
                    const CUtensorMap* mw = wide ? &mo : &M.m[12];
                    int done = 0;
                    const int ns = wide ? 4 : 6;
#pragma unroll 1
                    for (int kb = 0, st = 0, r = 0; kb < 64; kb++) {
                        const uint32_t bo = n6_bar(st);
                        mbar_wait(empty + bo, (((st < 4 ? it >> 2 : 0) + r) & 1) ^ 1);
                        if (elect()) {
                            mbar_expect(full + bo, wide ? G_STAGE : 32768);
                            tma3d(sb + n6_b(st), mw, 0, kb * 64, wide ? i * 4 : i * 2, full + bo);
                        }
                        if (!(done >> (kb >> 2) & 1)) {
#pragma unroll 1
                            for (int sp = 0; sp < (1 << 20) && !((done = __shfl_sync(0xffffffffu, ld_acq(g_ctr + C_QA_DONE + b), 0)) >> (kb >> 2) & 1); sp++)
                                __nanosleep(64);
                            asm volatile("fence.proxy.async.global;" ::: "memory");
                        }
                        if (elect()) bulk_load(sb + n6_a(st), g_ox + (size_t)(b * 64 + kb) * 8192, 16384, full + bo);
                        if (++st == ns) { st = 0; r++; }
                    }
                    it += wide ? 64 : 44;
                } else if (type == IT_S4) {
                    mbar_wait(empty, ((it >> 2) & 1) ^ 1);
                    if (elect()) {
                        mbar_expect(full, 32768 + 12288);
#pragma unroll
                        for (int j = 0; j < 8; j++) tma2d(sb + j * 4096, &mu, i * 8, j * 256, full);
                    }
                    if (!tables) { wait_ctr(g_ctr + C_CHAIN, 96); asm volatile("fence.proxy.async.global;" ::: "memory"); }
                    tables = true;
                    if (elect()) bulk_load(sb + S4_KD, g_kd + i * 8 * 768, 12288, full);
#pragma unroll 1
                    for (int st = 1; st < 4; st++) { mbar_wait(empty + 8 * st, ((it >> 2) & 1) ^ 1); if (lane == 0) mbar_arrive(full + 8 * st); }
                    it += 4;
                    mbar_wait_long(empty, ((it >> 2) & 1) ^ 1);
                }
                if (item >> 16 == IT_END) break;
            }
            asm volatile("griddepcontrol.wait;" ::: "memory");
        }
    } else {
        reg_inc<232>();
        const int wu = __shfl_sync(0xffffffffu, tid >> 5, 0);
        const int wgi = (wu >> 2) - 1, wi = wu & 3;
        int it = 0, nqa = 0, nsig = 0, n = 0, item;
        auto next_item = [&]() {
            mbar_wait_long(ifull + 8 * (n & 1), (n >> 1) & 1);
            asm volatile("ld.shared.u32 %0, [%1];" : "=r"(item) : "r"(islot + 4 * (n & 1)) : "memory");
            __syncwarp();
            if (lane == 0) mbar_arrive(iempty + 8 * (n & 1));
        };
        auto signal = [&](int what) {
            if (tid == 128) asm volatile("st.shared.u32 [%0], %1;" ::"r"(sigslot + 4 * (nsig & 1)), "r"(what) : "memory");
            __syncwarp();
            if (lane == 0) mbar_arrive(sigbar);
            nsig++;
        };
        next_item();
        if (item >> 16 == IT_KV) {
            float acc[128];
            uint32_t pk[64];
            uint32_t* dst = nullptr;
            int prev = 0;
            do {
                WLOG(0);
#pragma unroll
                for (int kb = 0; kb < 16; kb++, it++) {
                    const int st = kb & 3;
                    mbar_wait(full + 8 * st, (it >> 2) & 1);
                    const uint64_t da = mkdesc(sb + st * G_STAGE + wgi * 8192, 16, 1024, 1);
                    const uint64_t db = mkdesc(sb + st * G_STAGE + 16384, 8192, 1024, 1);
                    wg_fence();
#pragma unroll
                    for (int k = 0; k < 4; k++) wgmma256(acc, da + k * 2, db + k * 128, kb | k);
                    wg_commit();
                    if (n <= KVI) {
                        if (kb < KVF && dst) {
#pragma unroll
                            for (int j = kb * (64 / KVF); j < (kb + 1) * (64 / KVF); j++) st_out(dst + (j >> 1) * 128 + (j & 1) * 32, pk[j]);
                            if (kb == KVF - 1) signal(prev);
                        }
                    } else if (kb < KVS) {
#pragma unroll
                        for (int j = kb * (64 / KVS); j < (kb + 1) * (64 / KVS); j++) st_out(dst + (j >> 1) * 128 + (j & 1) * 32, pk[j]);
                        if (kb == KVS - 1) signal(prev);
                    }
                    if (kb > 0) {
                        wg_wait<1>();
                        if (lane == 0) mbar_arrive(empty + 8 * ((kb - 1) & 3));
                    }
                }
                wg_wait<0>();
                if (lane == 0) mbar_arrive(empty + 8 * 3);
#pragma unroll
                for (int j = 0; j < 64; j++) pk[j] = pack_bf16(acc[2 * j], acc[2 * j + 1]);
                const int row = ((item >> 8) & 255) * 128 + wgi * 64 + wi * 16, nt = item & 255;
                dst = (uint32_t*)(nt < 16 ? g_kx : g_vx) + (size_t)((row >> 5) * 512 + (nt & 15) * 32) * 128 + (row & 31) * 4 + lane;
                prev = item;
                WLOG(1);
                n++;
                next_item();
            } while (item >> 16 == IT_KV);
            if (dst) {
#pragma unroll
                for (int j = 0; j < 64; j++) dst[(j >> 1) * 128 + (j & 1) * 32] = pk[j];
                signal(prev);
            }
        }
        for (;; n++, next_item()) {
            const int type = item >> 16, b = (item >> 8) & 255, i = item & 255;
            const int lane = (tid & 31) + (item >> 24), wgi = (wu >> 2) - 1 + __shfl_sync(0xffffffffu, item >> 24, 0), wi = wu & 3;
            WLOG(0);
            if (type == IT_QA) {
                float acc[128];
                ST(sid, cw, 0);
                ST(sid, cw, 1);
                mainloop<256, 16, false>(acc, sb, wgi, full, empty, it, lane == 0);
                ST(sid, cw, 2);
                uint32_t q0[32], q1[32];
#pragma unroll
                for (int j = 0; j < 32; j++) q0[j] = pack_bf16(acc[2 * j], acc[2 * j + 1]);
                const uint32_t par = (it >> 2) & 1, so = sb + wgi * 20480;
                float sx[2][32] = {}, sm[2][8] = {};
                uint32_t p[2][20];
                mbar_wait_long(full, par);
                ST(sid, cw, 3);
                if (PING && wgi == 0) bar_sync(5, 256);
                attn_scores(sx[0], sm[0], q0, so);
                ST(sid, cw, 7);
#pragma unroll
                for (int j = 0; j < 32; j++) asm volatile("cvt.rn.bf16x2.f32 %0, %1, %2;" : "=r"(q1[j]) : "f"(acc[65 + 2 * j]), "f"(acc[64 + 2 * j]));
                mbar_wait(full + 8, par);
                attn_scores(sx[1], sm[1], q1, so + G_STAGE);
                if (PING && wgi == 1) bar_arrive(5, 256);
                if (elect()) asm volatile("cp.async.bulk.wait_group.read 0;" ::: "memory");
                mbar_wait(stgbar, (nqa++ & 1) ^ 1);
                bar_sync(3 + wgi, 128);
                float o0[64] = {}, o1[64] = {};
                wg_wait<0>();
                ST(sid, cw, 9);
                if (lane == 0) { mbar_arrive(empty); mbar_arrive(empty + 8); }
                if (wi & 1) attn_softmax<true>(p, sx, sm, wi >= 2, lane);
                else attn_softmax<false>(p, sx, sm, wi >= 2, lane);
                ST(sid, cw, 10);
                mbar_wait(full + 16, par);
                attn_pv(o0, p[0], so + 2 * G_STAGE);
                mbar_wait(full + 24, par);
                attn_pv(o1, p[1], so + 3 * G_STAGE);
                wg_wait<1>();
                if (lane == 0) mbar_arrive(empty + 16);
                ST(sid, cw, 5);
                const uint32_t da = (wi * 2 + ((lane >> 3) & 1)) * 1024 + (lane >> 4) * 128 + (lane & 7) * 16;
                attn_stage(o0, sb + G_STG + wgi * 16384 + da);
                wg_wait<0>();
                bar_sync(3 + wgi, 128);
                attn_stage(o1, so + 3 * G_STAGE + da);
                asm volatile("fence.proxy.async.shared::cta;" ::: "memory");
                ST(sid, cw, 6);
                signal(item);
                it += 4;
            } else if (type == IT_O) {
                ST(b * 8 + i, wgi * 4 + wi, 8);
                mbar_wait_long(full, (it >> 2) & 1);
                ST(b * 8 + i, wgi * 4 + wi, 9);
                if (b < O_WIDE) o_item<256>(sb, wgi, wi, lane, full, empty, it, &mout, b * 128, i * 256, (nqa & 1) ^ 1);
                else o_item<128>(sb, wgi, wi, lane, full, empty, it, &mout, b * 128, i * 128, (nqa & 1) ^ 1);
            } else if (type == IT_S4) {
                mbar_wait_long(full, (it >> 2) & 1);
                mbar_wait(full + 24, (it >> 2) & 1);
                s4_item(sb, wgi * 4 + wi, lane, i, dsk, empty, &my, (nqa & 1) ^ 1, out, ifull + 8 * ((n + 1) & 1), ((n + 1) >> 1) & 1, islot + 4 * ((n + 1) & 1));
                it += 4;
            } else break;
            WLOG(1);
        }
        bar_sync(2, 256);
        signal(item);
        if (elect()) asm volatile("cp.async.bulk.wait_group 0;" ::: "memory");
    }
}

typedef CUresult (*EncodeFn)(CUtensorMap*, CUtensorMapDataType, cuuint32_t, void*, const cuuint64_t*, const cuuint64_t*, const cuuint32_t*,
                             const cuuint32_t*, CUtensorMapInterleave, CUtensorMapSwizzle, CUtensorMapL2promotion, CUtensorMapFloatOOBfill);
static EncodeFn get_encode() {
    void* fn = nullptr; cudaDriverEntryPointQueryResult st;
    cudaGetDriverEntryPoint("cuTensorMapEncodeTiled", &fn, cudaEnableDefault, &st);
    return (EncodeFn)fn;
}
static void map_act(EncodeFn enc, CUtensorMap* m, const void* p, int rows, int cols, int boxr) {
    cuuint64_t dim[2] = {(cuuint64_t)cols, (cuuint64_t)rows}, str[1] = {(cuuint64_t)cols * 2};
    cuuint32_t box[2] = {64, (cuuint32_t)boxr}, es[2] = {1, 1};
    enc(m, CU_TENSOR_MAP_DATA_TYPE_BFLOAT16, 2, (void*)p, dim, str, box, es, CU_TENSOR_MAP_INTERLEAVE_NONE, CU_TENSOR_MAP_SWIZZLE_128B,
        CU_TENSOR_MAP_L2_PROMOTION_L2_128B, CU_TENSOR_MAP_FLOAT_OOB_FILL_NONE);
}
static void map_w(EncodeFn enc, CUtensorMap* m, const void* p, int k, int n, int groups = 4) {
    cuuint64_t dim[3] = {64, (cuuint64_t)k, (cuuint64_t)n / 64}, str[2] = {(cuuint64_t)n * 2, 128};
    cuuint32_t box[3] = {64, 64, (cuuint32_t)groups}, es[3] = {1, 1, 1};
    enc(m, CU_TENSOR_MAP_DATA_TYPE_BFLOAT16, 3, (void*)p, dim, str, box, es, CU_TENSOR_MAP_INTERLEAVE_NONE, CU_TENSOR_MAP_SWIZZLE_128B,
        CU_TENSOR_MAP_L2_PROMOTION_L2_256B, CU_TENSOR_MAP_FLOAT_OOB_FILL_NONE);
}

static void map_kv(EncodeFn enc, CUtensorMap* m, void* p, int n) {
    cuuint64_t dim[3] = {(cuuint64_t)n, NSEG, 512}, str[2] = {(cuuint64_t)n * 1024, (cuuint64_t)n * 2};
    cuuint32_t box[3] = {(cuuint32_t)n, 2, 16}, es[3] = {1, 1, 1};
    enc(m, CU_TENSOR_MAP_DATA_TYPE_BFLOAT16, 3, p, dim, str, box, es, CU_TENSOR_MAP_INTERLEAVE_NONE, CU_TENSOR_MAP_SWIZZLE_NONE,
        CU_TENSOR_MAP_L2_PROMOTION_NONE, CU_TENSOR_MAP_FLOAT_OOB_FILL_NONE);
}
static void map_box(EncodeFn enc, CUtensorMap* m, const void* p, int rows, int ld, int boxc, int boxr, CUtensorMapSwizzle sw,
                    CUtensorMapL2promotion promo = CU_TENSOR_MAP_L2_PROMOTION_NONE) {
    cuuint64_t dim[2] = {(cuuint64_t)ld, (cuuint64_t)rows}, str[1] = {(cuuint64_t)ld * 2};
    cuuint32_t box[2] = {(cuuint32_t)boxc, (cuuint32_t)boxr}, es[2] = {1, 1};
    enc(m, CU_TENSOR_MAP_DATA_TYPE_BFLOAT16, 2, (void*)p, dim, str, box, es, CU_TENSOR_MAP_INTERLEAVE_NONE, sw,
        promo, CU_TENSOR_MAP_FLOAT_OOB_FILL_NONE);
}

extern "C" void kernel_launch(void* const* d_in, const int* in_sizes, int n_in, void* d_out, int out_size) {
    const bf16* x = (const bf16*)d_in[0];
    const bf16* mem0 = (const bf16*)d_in[1];
    const bf16 *Wq = (const bf16*)d_in[2], *Wk = (const bf16*)d_in[3], *Wv = (const bf16*)d_in[4], *Wo = (const bf16*)d_in[5];
    static EncodeFn enc = nullptr;
    static int nsm = 0;
    static void* kv[4];
    if (!enc) {
        enc = get_encode();
        cudaGetSymbolAddress(&kv[0], g_kx); cudaGetSymbolAddress(&kv[1], g_vx); cudaGetSymbolAddress(&kv[2], g_km); cudaGetSymbolAddress(&kv[3], g_vm);
        cudaDeviceGetAttribute(&nsm, cudaDevAttrMultiProcessorCount, 0);
        cudaFuncSetAttribute(chain_kernel, cudaFuncAttributeMaxDynamicSharedMemorySize, CH_SMEM);
        cudaFuncSetAttribute(worker_kernel, cudaFuncAttributeMaxDynamicSharedMemorySize, G_SMEM);
    }
    Maps M;
    CUtensorMap &mx = M.m[0], &mq = M.m[1], &mk = M.m[2], &mv = M.m[3], &mo = M.m[4], &mout = M.m[5], &mu = M.m[6], &my = M.m[7];
    map_act(enc, &mx, x, S_LEN, DM, 128);
    map_w(enc, &mq, Wq, DM, HD); map_w(enc, &mk, Wk, DM, HD); map_w(enc, &mv, Wv, DM, HD); map_w(enc, &mo, Wo, HD, DM);
    map_w(enc, &M.m[12], Wo, HD, DM, 2);
    map_box(enc, &mout, d_out, S_LEN, 2 * DM, 64, 16, CU_TENSOR_MAP_SWIZZLE_128B);
    map_box(enc, &mu, d_in[7], S_LEN, DM, 8, 256, CU_TENSOR_MAP_SWIZZLE_NONE, (CUtensorMapL2promotion)PROMU);
    map_box(enc, &my, d_out, S_LEN, 2 * DM, 8, 256, CU_TENSOR_MAP_SWIZZLE_NONE);
    for (int i = 0; i < 4; i++) map_kv(enc, &M.m[8 + i], kv[i], i < 2 ? 256 : 64);
    CUtensorMap cq, ck, cv, co;
    map_box(enc, &cq, Wq, DM, HD, 32, 32, CU_TENSOR_MAP_SWIZZLE_64B, (CUtensorMapL2promotion)PROMO); map_box(enc, &ck, Wk, DM, HD, 32, 32, CU_TENSOR_MAP_SWIZZLE_64B, (CUtensorMapL2promotion)PROMO);
    map_box(enc, &cv, Wv, DM, HD, 32, 32, CU_TENSOR_MAP_SWIZZLE_64B, (CUtensorMapL2promotion)PROMO); map_box(enc, &co, Wo, HD, DM, 32, 16, CU_TENSOR_MAP_SWIZZLE_64B, (CUtensorMapL2promotion)PROMO);
    S4Params P = {(const bf16*)d_in[8], (const bf16*)d_in[9], (const bf16*)d_in[10], (const bf16*)d_in[11],
                  (const bf16*)d_in[12], (const bf16*)d_in[13], (const bf16*)d_in[14], (const bf16*)d_in[15]};
    int aware = 1;
    cudaLaunchAttribute at[1];
    at[0].id = cudaLaunchAttributeProgrammaticStreamSerialization;
    at[0].val.programmaticStreamSerializationAllowed = 1;
    cudaLaunchConfig_t cfg = {};
    cfg.stream = cudaStreamPerThread;
    cfg.gridDim = dim3(96); cfg.blockDim = dim3(CH_THREADS); cfg.dynamicSmemBytes = CH_SMEM;
    cudaLaunchKernelEx(&cfg, chain_kernel, cq, ck, cv, co, Wq, Wk, Wv, mem0, P, aware);
    cfg.attrs = at; cfg.numAttrs = 1;
    cfg.gridDim = dim3(nsm); cfg.blockDim = dim3(384); cfg.dynamicSmemBytes = G_SMEM;
    cudaLaunchKernelEx(&cfg, worker_kernel, M, P.dsk, (bf16*)d_out);
}
```

```cpp
#include <cuda.h>
#include <cuda_runtime.h>
#include <cuda_bf16.h>
#include <stdint.h>
#include <stdio.h>
#include <string.h>

typedef __nv_bfloat16 bf16;

constexpr int S_LEN = 2048, DM = 1024, NH = 32, DH = 128, HD = 4096, NSEG = 64;
constexpr uint32_t SENT = 0xFFFFFFFFu;
constexpr int SPIN_LIMIT = 1 << 18;
#define REALL 0

__device__ __align__(1024) bf16 g_kx[S_LEN * HD];
__device__ __align__(1024) bf16 g_vx[S_LEN * HD];
__device__ __align__(1024) bf16 g_ox[S_LEN * HD];
__device__ __align__(1024) bf16 g_km[NSEG * NH * 8 * DH];
__device__ __align__(1024) bf16 g_vm[NSEG * NH * 8 * DH];
__device__ __align__(1024) bf16 g_kd[DM * 768 + 8192];
__device__ __align__(1024) char g_ring[2 << 20];
__device__ int g_kvf[96 * 16];
constexpr int C_NEXT = 0, C_CHAIN = 32, C_QA_DONE = 64, N_CTR = 96;
__device__ int g_ctr[N_CTR];

__device__ __forceinline__ uint32_t smem_u32(const void* p) { return (uint32_t)__cvta_generic_to_shared(p); }
__device__ __forceinline__ uint32_t clk() { uint32_t c; asm volatile("mov.u32 %0, %%clock;" : "=r"(c)::"memory"); return c; }
__device__ __forceinline__ uint32_t pack_bf16(float lo, float hi) {
    uint32_t r; asm("cvt.rn.bf16x2.f32 %0, %1, %2;" : "=r"(r) : "f"(hi), "f"(lo)); return r;
}
__device__ __forceinline__ uint32_t movm(uint32_t a) {
    uint32_t d; asm volatile("movmatrix.sync.aligned.m8n8.trans.b16 %0, %1;" : "=r"(d) : "r"(a)); return d;
}
__device__ __forceinline__ void mma16(float (&d)[4], const uint32_t (&a)[4], uint32_t b0, uint32_t b1) {
    asm volatile("mma.sync.aligned.m16n8k16.row.col.f32.bf16.bf16.f32 {%0,%1,%2,%3}, {%4,%5,%6,%7}, {%8,%9}, {%0,%1,%2,%3};"
        : "+f"(d[0]), "+f"(d[1]), "+f"(d[2]), "+f"(d[3]) : "r"(a[0]), "r"(a[1]), "r"(a[2]), "r"(a[3]), "r"(b0), "r"(b1));
}
__device__ __forceinline__ void mma16z(float (&d)[4], const uint32_t (&a)[4], uint32_t b0, uint32_t b1) {
    asm volatile("mma.sync.aligned.m16n8k16.row.col.f32.bf16.bf16.f32 {%0,%1,%2,%3}, {%4,%5,%6,%7}, {%8,%9}, {%10,%10,%10,%10};"
        : "=f"(d[0]), "=f"(d[1]), "=f"(d[2]), "=f"(d[3]) : "r"(a[0]), "r"(a[1]), "r"(a[2]), "r"(a[3]), "r"(b0), "r"(b1), "f"(0.f));
}
__device__ __forceinline__ void mma8z(float (&d)[4], uint32_t a0, uint32_t a1, uint32_t b0) {
    asm volatile("mma.sync.aligned.m16n8k8.row.col.f32.bf16.bf16.f32 {%0,%1,%2,%3}, {%4,%5}, {%6}, {%7,%7,%7,%7};"
        : "=f"(d[0]), "=f"(d[1]), "=f"(d[2]), "=f"(d[3]) : "r"(a0), "r"(a1), "r"(b0), "f"(0.f));
}
__device__ __forceinline__ void ldsm4t(uint32_t (&r)[4], uint32_t addr) {
    asm volatile("ldmatrix.sync.aligned.m8n8.x4.trans.shared.b16 {%0,%1,%2,%3}, [%4];"
        : "=r"(r[0]), "=r"(r[1]), "=r"(r[2]), "=r"(r[3]) : "r"(addr) : "memory");
}
__device__ __forceinline__ void ldsm4(uint32_t (&r)[4], uint32_t addr) {
    asm volatile("ldmatrix.sync.aligned.m8n8.x4.shared.b16 {%0,%1,%2,%3}, [%4];"
        : "=r"(r[0]), "=r"(r[1]), "=r"(r[2]), "=r"(r[3]) : "r"(addr) : "memory");
}
__device__ __forceinline__ float lds32(uint32_t a) {
    float v; asm volatile("ld.shared.f32 %0, [%1];" : "=f"(v) : "r"(a) : "memory"); return v;
}
__device__ __forceinline__ void st_async1(uint32_t dst, float v, uint32_t bar) {
    asm volatile("st.async.shared::cluster.mbarrier::complete_tx::bytes.f32 [%0], %1, [%2];" ::"r"(dst), "f"(v), "r"(bar) : "memory");
}
__device__ __forceinline__ void st_async2(uint32_t dst, float x, float y, uint32_t bar) {
    asm volatile("st.async.shared::cluster.mbarrier::complete_tx::bytes.v2.f32 [%0], {%1,%2}, [%3];" ::"r"(dst), "f"(x), "f"(y), "r"(bar) : "memory");
}
__device__ __forceinline__ void mma8(float (&d)[4], uint32_t a0, uint32_t a1, uint32_t b0) {
    asm volatile("mma.sync.aligned.m16n8k8.row.col.f32.bf16.bf16.f32 {%0,%1,%2,%3}, {%4,%5}, {%6}, {%0,%1,%2,%3};"
        : "+f"(d[0]), "+f"(d[1]), "+f"(d[2]), "+f"(d[3]) : "r"(a0), "r"(a1), "r"(b0));
}
__device__ __forceinline__ void cp16(uint32_t dst, const void* src) {
    asm volatile("cp.async.cg.shared.global [%0], [%1], 16;" ::"r"(dst), "l"(src) : "memory");
}
__device__ __forceinline__ void sts128(uint32_t a, const float (&v)[4]) {
    asm volatile("st.shared.v4.f32 [%0], {%1,%2,%3,%4};" ::"r"(a), "f"(v[0]), "f"(v[1]), "f"(v[2]), "f"(v[3]) : "memory");
}
__device__ __forceinline__ float4 lds128(uint32_t a) {
    float4 v; asm volatile("ld.shared.v4.f32 {%0,%1,%2,%3}, [%4];" : "=f"(v.x), "=f"(v.y), "=f"(v.z), "=f"(v.w) : "r"(a) : "memory"); return v;
}
__device__ __forceinline__ void sts64(uint32_t a, float x, float y) {
    asm volatile("st.shared.v2.f32 [%0], {%1,%2};" ::"r"(a), "f"(x), "f"(y) : "memory");
}
__device__ __forceinline__ float2 lds64(uint32_t a) {
    float2 v; asm volatile("ld.shared.v2.f32 {%0,%1}, [%2];" : "=f"(v.x), "=f"(v.y) : "r"(a) : "memory"); return v;
}
__device__ __forceinline__ void bar_sync(int id, int n) { asm volatile("bar.sync %0, %1;" ::"r"(id), "r"(n) : "memory"); }
__device__ __forceinline__ void bar_arrive(int id, int n) { asm volatile("bar.arrive %0, %1;" ::"r"(id), "r"(n) : "memory"); }
__device__ __forceinline__ uint32_t mapa(uint32_t a, uint32_t r) {
    uint32_t o; asm("mapa.shared::cluster.u32 %0, %1, %2;" : "=r"(o) : "r"(a), "r"(r)); return o;
}
__device__ __forceinline__ void st_async4(uint32_t dst, float4 v, uint32_t bar) {
    asm volatile("st.async.shared::cluster.mbarrier::complete_tx::bytes.v4.f32 [%0], {%1,%2,%3,%4}, [%5];"
        ::"r"(dst), "f"(v.x), "f"(v.y), "f"(v.z), "f"(v.w), "r"(bar) : "memory");
}
__device__ __forceinline__ void mbar_init(uint32_t bar, int n) { asm volatile("mbarrier.init.shared.b64 [%0], %1;" ::"r"(bar), "r"(n) : "memory"); }
__device__ __forceinline__ void mbar_expect(uint32_t bar, int bytes) {
    asm volatile("mbarrier.arrive.expect_tx.shared.b64 _, [%0], %1;" ::"r"(bar), "r"(bytes) : "memory");
}
__device__ __forceinline__ void bulk_load(uint32_t dst, const void* src, int bytes, uint32_t bar) {
    asm volatile("cp.async.bulk.shared::cluster.global.mbarrier::complete_tx::bytes [%0], [%1], %2, [%3];"
        ::"r"(dst), "l"(src), "r"(bytes), "r"(bar) : "memory");
}
__device__ __forceinline__ bool mbar_try(uint32_t bar, uint32_t par) {
    uint32_t ok;
    asm volatile("{.reg .pred p; mbarrier.try_wait.parity.shared::cta.b64 p, [%1], %2; selp.u32 %0, 1, 0, p;}"
        : "=r"(ok) : "r"(bar), "r"(par) : "memory");
    return ok;
}
__device__ __forceinline__ bool mbar_test(uint32_t bar, uint32_t par) {
    uint32_t ok;
    asm volatile("{.reg .pred p; mbarrier.test_wait.parity.shared::cta.b64 p, [%1], %2; selp.u32 %0, 1, 0, p;}"
        : "=r"(ok) : "r"(bar), "r"(par) : "memory");
    return ok;
}
__device__ __forceinline__ int ld_acq(const int* p) { int v; asm volatile("ld.acquire.gpu.global.s32 %0, [%1];" : "=r"(v) : "l"(p) : "memory"); return v; }
__device__ __forceinline__ void red_release(int* p, int v) { asm volatile("red.release.gpu.global.add.s32 [%0], %1;" ::"l"(p), "r"(v) : "memory"); }
__device__ __forceinline__ void fence_gpu() { asm volatile("fence.acq_rel.gpu;" ::: "memory"); }
__device__ __forceinline__ void wait_ctr(const int* p, int n) {
#pragma unroll 1
    for (int it = 0; it < (1 << 20) && ld_acq(p) < n; it++) __nanosleep(64);
}
__device__ __forceinline__ void mbar_wait(uint32_t bar, uint32_t par) {
    if (!mbar_try(bar, par)) {
#pragma unroll 1
        for (int it = 0; it < SPIN_LIMIT && !mbar_try(bar, par); it++) {}
    }
}
__device__ __forceinline__ void mbar_wait_long(uint32_t bar, uint32_t par) {
    for (int it = 0; it < (1 << 24) && !mbar_try(bar, par); it++) {}
}
__device__ __forceinline__ float4 add4(float4 a, float4 b) { return make_float4(a.x + b.x, a.y + b.y, a.z + b.z, a.w + b.w); }
__device__ __forceinline__ float ex2(float x) { float y; asm("ex2.approx.ftz.f32 %0, %1;" : "=f"(y) : "f"(x)); return y; }

__device__ __forceinline__ void wgmma256(float (&d)[128], uint64_t da, uint64_t db, int acc) {
    asm volatile("{.reg .pred p; setp.ne.b32 p, %130, 0;\n"
        "wgmma.mma_async.sync.aligned.m64n256k16.f32.bf16.bf16 {"
        "%0,%1,%2,%3,%4,%5,%6,%7,%8,%9,%10,%11,%12,%13,%14,%15,"
        "%16,%17,%18,%19,%20,%21,%22,%23,%24,%25,%26,%27,%28,%29,%30,%31,"
        "%32,%33,%34,%35,%36,%37,%38,%39,%40,%41,%42,%43,%44,%45,%46,%47,"
        "%48,%49,%50,%51,%52,%53,%54,%55,%56,%57,%58,%59,%60,%61,%62,%63,"
        "%64,%65,%66,%67,%68,%69,%70,%71,%72,%73,%74,%75,%76,%77,%78,%79,"
        "%80,%81,%82,%83,%84,%85,%86,%87,%88,%89,%90,%91,%92,%93,%94,%95,"
        "%96,%97,%98,%99,%100,%101,%102,%103,%104,%105,%106,%107,%108,%109,%110,%111,"
        "%112,%113,%114,%115,%116,%117,%118,%119,%120,%121,%122,%123,%124,%125,%126,%127"
        "}, %128, %129, p, 1, 1, 0, 1;}"
        : "+f"(d[0]), "+f"(d[1]), "+f"(d[2]), "+f"(d[3]), "+f"(d[4]), "+f"(d[5]), "+f"(d[6]), "+f"(d[7]), "+f"(d[8]), "+f"(d[9]), "+f"(d[10]), "+f"(d[11]), "+f"(d[12]), "+f"(d[13]), "+f"(d[14]), "+f"(d[15]), "+f"(d[16]), "+f"(d[17]), "+f"(d[18]), "+f"(d[19]), "+f"(d[20]), "+f"(d[21]), "+f"(d[22]), "+f"(d[23]), "+f"(d[24]), "+f"(d[25]), "+f"(d[26]), "+f"(d[27]), "+f"(d[28]), "+f"(d[29]), "+f"(d[30]), "+f"(d[31]), "+f"(d[32]), "+f"(d[33]), "+f"(d[34]), "+f"(d[35]), "+f"(d[36]), "+f"(d[37]), "+f"(d[38]), "+f"(d[39]), "+f"(d[40]), "+f"(d[41]), "+f"(d[42]), "+f"(d[43]), "+f"(d[44]), "+f"(d[45]), "+f"(d[46]), "+f"(d[47]), "+f"(d[48]), "+f"(d[49]), "+f"(d[50]), "+f"(d[51]), "+f"(d[52]), "+f"(d[53]), "+f"(d[54]), "+f"(d[55]), "+f"(d[56]), "+f"(d[57]), "+f"(d[58]), "+f"(d[59]), "+f"(d[60]), "+f"(d[61]), "+f"(d[62]), "+f"(d[63]), "+f"(d[64]), "+f"(d[65]), "+f"(d[66]), "+f"(d[67]), "+f"(d[68]), "+f"(d[69]), "+f"(d[70]), "+f"(d[71]), "+f"(d[72]), "+f"(d[73]), "+f"(d[74]), "+f"(d[75]), "+f"(d[76]), "+f"(d[77]), "+f"(d[78]), "+f"(d[79]), "+f"(d[80]), "+f"(d[81]), "+f"(d[82]), "+f"(d[83]), "+f"(d[84]), "+f"(d[85]), "+f"(d[86]), "+f"(d[87]), "+f"(d[88]), "+f"(d[89]), "+f"(d[90]), "+f"(d[91]), "+f"(d[92]), "+f"(d[93]), "+f"(d[94]), "+f"(d[95]), "+f"(d[96]), "+f"(d[97]), "+f"(d[98]), "+f"(d[99]), "+f"(d[100]), "+f"(d[101]), "+f"(d[102]), "+f"(d[103]), "+f"(d[104]), "+f"(d[105]), "+f"(d[106]), "+f"(d[107]), "+f"(d[108]), "+f"(d[109]), "+f"(d[110]), "+f"(d[111]), "+f"(d[112]), "+f"(d[113]), "+f"(d[114]), "+f"(d[115]), "+f"(d[116]), "+f"(d[117]), "+f"(d[118]), "+f"(d[119]), "+f"(d[120]), "+f"(d[121]), "+f"(d[122]), "+f"(d[123]), "+f"(d[124]), "+f"(d[125]), "+f"(d[126]), "+f"(d[127])
        : "l"(da), "l"(db), "r"(acc));
}
__device__ __forceinline__ void wgmma128(float (&d)[64], uint64_t da, uint64_t db, int acc) {
    asm volatile("{.reg .pred p; setp.ne.b32 p, %66, 0;\n"
        "wgmma.mma_async.sync.aligned.m64n128k16.f32.bf16.bf16 {"
        "%0,%1,%2,%3,%4,%5,%6,%7,%8,%9,%10,%11,%12,%13,%14,%15,"
        "%16,%17,%18,%19,%20,%21,%22,%23,%24,%25,%26,%27,%28,%29,%30,%31,"
        "%32,%33,%34,%35,%36,%37,%38,%39,%40,%41,%42,%43,%44,%45,%46,%47,"
        "%48,%49,%50,%51,%52,%53,%54,%55,%56,%57,%58,%59,%60,%61,%62,%63"
        "}, %64, %65, p, 1, 1, 0, 1;}"
        : "+f"(d[0]), "+f"(d[1]), "+f"(d[2]), "+f"(d[3]), "+f"(d[4]), "+f"(d[5]), "+f"(d[6]), "+f"(d[7]), "+f"(d[8]), "+f"(d[9]), "+f"(d[10]), "+f"(d[11]), "+f"(d[12]), "+f"(d[13]), "+f"(d[14]), "+f"(d[15]), "+f"(d[16]), "+f"(d[17]), "+f"(d[18]), "+f"(d[19]), "+f"(d[20]), "+f"(d[21]), "+f"(d[22]), "+f"(d[23]), "+f"(d[24]), "+f"(d[25]), "+f"(d[26]), "+f"(d[27]), "+f"(d[28]), "+f"(d[29]), "+f"(d[30]), "+f"(d[31]), "+f"(d[32]), "+f"(d[33]), "+f"(d[34]), "+f"(d[35]), "+f"(d[36]), "+f"(d[37]), "+f"(d[38]), "+f"(d[39]), "+f"(d[40]), "+f"(d[41]), "+f"(d[42]), "+f"(d[43]), "+f"(d[44]), "+f"(d[45]), "+f"(d[46]), "+f"(d[47]), "+f"(d[48]), "+f"(d[49]), "+f"(d[50]), "+f"(d[51]), "+f"(d[52]), "+f"(d[53]), "+f"(d[54]), "+f"(d[55]), "+f"(d[56]), "+f"(d[57]), "+f"(d[58]), "+f"(d[59]), "+f"(d[60]), "+f"(d[61]), "+f"(d[62]), "+f"(d[63])
        : "l"(da), "l"(db), "r"(acc));
}
__device__ __forceinline__ void wg_fence() { asm volatile("wgmma.fence.sync.aligned;" ::: "memory"); }
__device__ __forceinline__ void wg_commit() { asm volatile("wgmma.commit_group.sync.aligned;" ::: "memory"); }
template <int N> __device__ __forceinline__ void wg_wait() { asm volatile("wgmma.wait_group.sync.aligned %0;" ::"n"(N) : "memory"); }
__device__ __forceinline__ uint64_t mkdesc(uint32_t addr, uint32_t lbo, uint32_t sbo, uint32_t sw) {
    return (uint64_t)((addr & 0x3FFFF) >> 4) | ((uint64_t)(lbo >> 4) << 16) | ((uint64_t)(sbo >> 4) << 32) | ((uint64_t)sw << 62);
}
__device__ __forceinline__ void tma2d(uint32_t dst, const CUtensorMap* m, int c0, int c1, uint32_t bar) {
    asm volatile("cp.async.bulk.tensor.2d.shared::cluster.global.mbarrier::complete_tx::bytes [%0], [%1, {%2, %3}], [%4];"
        ::"r"(dst), "l"(m), "r"(c0), "r"(c1), "r"(bar) : "memory");
}
__device__ __forceinline__ void tma3d(uint32_t dst, const CUtensorMap* m, int c0, int c1, int c2, uint32_t bar) {
    asm volatile("cp.async.bulk.tensor.3d.shared::cluster.global.mbarrier::complete_tx::bytes [%0], [%1, {%2, %3, %4}], [%5];"
        ::"r"(dst), "l"(m), "r"(c0), "r"(c1), "r"(c2), "r"(bar) : "memory");
}
__device__ __forceinline__ void tma3d_mc(uint32_t dst, const CUtensorMap* m, int c0, int c1, int c2, uint32_t bar, uint16_t mask) {
    asm volatile("cp.async.bulk.tensor.3d.shared::cluster.global.mbarrier::complete_tx::bytes.multicast::cluster [%0], [%1, {%2, %3, %4}], [%5], %6;"
        ::"r"(dst), "l"(m), "r"(c0), "r"(c1), "r"(c2), "r"(bar), "h"(mask) : "memory");
}
__device__ __forceinline__ void mbar_arrive(uint32_t bar) { asm volatile("mbarrier.arrive.shared.b64 _, [%0];" ::"r"(bar) : "memory"); }
__device__ __forceinline__ void mbar_arrive_remote(uint32_t bar) {
    asm volatile("mbarrier.arrive.shared::cluster.b64 _, [%0];" ::"r"(bar) : "memory");
}
__device__ __forceinline__ bool elect() {
    uint32_t p;
    asm volatile("{.reg .pred p; elect.sync _|p, 0xffffffff; selp.u32 %0, 1, 0, p;}" : "=r"(p));
    return p;
}
template <int R> __device__ __forceinline__ void reg_inc() { asm volatile("setmaxnreg.inc.sync.aligned.u32 %0;" ::"n"(R)); }
template <int R> __device__ __forceinline__ void reg_dec() { asm volatile("setmaxnreg.dec.sync.aligned.u32 %0;" ::"n"(R)); }

#define ST(id, w, i)
constexpr int CH_NRES = 50;
constexpr int CH_WREG = CH_NRES * 512;
constexpr int CH_PART = 8 * CH_WREG;
constexpr int CH_SX = CH_PART + 16384;
constexpr int CH_MX = CH_SX + 3 * 1280;
constexpr int CH_QK = CH_MX;
constexpr int CH_XS = CH_MX + 3 * 512;
constexpr int CH_BAR = CH_XS + 5632;
constexpr int CH_SMEM = CH_BAR + 192;
constexpr int CH_THREADS = 384;

__device__ __forceinline__ char* ring_base() { return (char*)(((uintptr_t)g_ring + (1 << 20) - 1) & ~(uintptr_t)((1 << 20) - 1)); }
__device__ __forceinline__ uint32_t ring_off(int chunk, int side) {
    uint32_t o = ((chunk & 1) << 13) | ((chunk >> 1) << 16);
    uint32_t par = ((o >> 13) ^ (o >> 16) ^ (o >> 17) ^ (o >> 19) ^ side) & 1;
    return o | (par << 12);
}
__device__ __forceinline__ uint2 ld_poll(const char* p) {
    unsigned long long v; asm volatile("ld.relaxed.gpu.global.b64 %0, [%1];" : "=l"(v) : "l"(p) : "memory");
    return make_uint2((uint32_t)v, (uint32_t)(v >> 32));
}
__device__ __forceinline__ void st_pub(char* p, uint32_t x, uint32_t y) {
    unsigned long long v = ((unsigned long long)y << 32) | x;
    asm volatile("st.relaxed.gpu.global.b64 [%0], %1;" ::"l"(p), "l"(v) : "memory");
}
template <int N>
__device__ __forceinline__ void poll_issue(uint2 (&b)[N], const char* p, bool lastvalid) {
#pragma unroll
    for (int i = 0; i < N; i++) {
        if (i < N - 1 || lastvalid) b[i] = ld_poll(p + i * 256);
        else b[i] = make_uint2(0, 0);
    }
}
template <int N>
__device__ __forceinline__ int poll_check(uint2 (&b)[N], const char* p, uint32_t z) {
    int it = 0;
    uint32_t mx = z;
#pragma unroll
    for (int i = 0; i < N; i++) mx = max(mx, b[i].x);
    if (__any_sync(0xffffffffu, mx == SENT)) {
        do {
#pragma unroll
            for (int i = 0; i < N; i++)
                if ((REALL && i < 10) || b[i].x == SENT) b[i] = ld_poll(p + i * 256);
            mx = b[0].x;
#pragma unroll
            for (int i = 1; i < N; i++) mx = max(mx, b[i].x);
            it++;
        } while (__any_sync(0xffffffffu, mx == SENT && it < SPIN_LIMIT));
    }
    return it;
}
template <int N>
__device__ __forceinline__ uint32_t delay(uint32_t a) {
    uint32_t z = 0;
#pragma unroll
    for (int i = 0; i < N; i++) asm volatile("ld.volatile.shared.u32 %0, [%1];" : "=r"(z) : "r"(a + z) : "memory");
    return z;
}

#define PFKV 0
#define LDW 0
#define PACE2 18
#define KGS 2
constexpr int KVN = 2;
#define FEN 1
#define XB 4
#define KEEP 100
#define PE 0
#define PROMO 2
#define PROMU 0
#define FNC 1
#define CL 8
#define PL 0
#define ML 4
#define MP 2
#define VCH_P 4
#define VCH_C 2
#define DLM 3
#define DLO 5
constexpr int OB = 0;
template <int PACE, int I0 = 0, int I1 = 12>
__device__ __forceinline__ void preload(uint32_t (&sw)[12][4], uint32_t a, uint32_t zero) {
    uint32_t z = 0;
#pragma unroll
    for (int i = I0; i < I1; i++) {
        if (PACE && i % (PACE ? PACE : 1) == 0) z = delay<1>(zero + z);
        ldsm4t(sw[i], a + z + i * 512);
    }
}
__device__ __forceinline__ void stsm4(uint32_t addr, uint32_t a, uint32_t b, uint32_t c, uint32_t d) {
    asm volatile("stmatrix.sync.aligned.m8n8.x4.shared.b16 [%0], {%1,%2,%3,%4};" ::"r"(addr), "r"(a), "r"(b), "r"(c), "r"(d) : "memory");
}
__device__ __forceinline__ void stsm4t(uint32_t addr, uint32_t a, uint32_t b, uint32_t c, uint32_t d) {
    asm volatile("stmatrix.sync.aligned.m8n8.x4.trans.shared.b16 [%0], {%1,%2,%3,%4};" ::"r"(addr), "r"(a), "r"(b), "r"(c), "r"(d) : "memory");
}
__device__ __forceinline__ void st_part(uint32_t addr, const float (&x)[4], const float (&y)[4]) {
    stsm4(addr, pack_bf16(x[0], x[1]), pack_bf16(x[2], x[3]), pack_bf16(y[0], y[1]), pack_bf16(y[2], y[3]));
}
template <bool TR>
__device__ __forceinline__ void red_part(uint32_t& lo, uint32_t& hi, uint32_t addr, uint32_t eye) {
    uint32_t a[4][4];
#pragma unroll
    for (int j = 0; j < 4; j++) { if (TR) ldsm4t(a[j], addr + j * 1024); else ldsm4(a[j], addr + j * 1024); }
    float r0[4], r1[4], r2[4], r3[4];
    mma16z(r0, a[0], eye, eye); mma16z(r1, a[1], eye, eye); mma16z(r2, a[2], eye, eye); mma16z(r3, a[3], eye, eye);
#pragma unroll
    for (int j = 0; j < 4; j++) r0[j] = ((r0[j] + r1[j]) + r2[j]) + r3[j];
    lo = pack_bf16(r0[0], r0[1]); hi = pack_bf16(r0[2], r0[3]);
}
__device__ __forceinline__ int o_chunk(int ks, int& pos) {
    const int cw = ks < 176 ? ks / 11 : 16 + (ks - 176) / 10;
    pos = ks - (cw < 16 ? 11 * cw : 176 + 10 * (cw - 16));
    return cw;
}

template <bool PV>
__device__ __forceinline__ void chain_loop(const uint32_t (&wa)[36][4], const uint32_t sb, const int w, const int lane0, const int rank,
                                           const int h, const int side) {
    const int rk1 = rank == 2 ? 0 : rank + 1, rk2 = rank == 0 ? 2 : rank - 1;
    const int nq = rank == 0 ? 6 : 5, u0 = rank == 0 ? 0 : 1 + 5 * rank, v0 = rank == 0 ? -6 : 3 * rank - 6;
    const uint32_t pt = CH_PART + (w >> 1) * 4096 + (w & 1) * 256;
    const uint32_t barS = sb + CH_BAR, barM = barS + 8, zero = barS + 24;
    char* const ring0 = ring_base();
    const uint32_t m_rd = ring_off(24 + w, side), o_rd = ring_off(rank * 8 + w, side);
    uint32_t pub;
    if (PV) { int pos, cw = o_chunk(h * 8 + v0 + w, pos); pub = (ring_off(cw, 0) & ~4096u) + pos * 256; }
    else pub = (ring_off(24 + (h >> 2), 0) & ~4096u) + ((2 * h + w) & 7) * 256;
    char* const kvo = (char*)(PV ? g_vm + 128 * (v0 + w) : g_km + 64 * (u0 + w)) + h * 2048;
    const bool mown = !PV && w == rank && rank < 2;
    uint32_t lo16 = lane0 * 16;
    uint32_t sw[12][4];
#pragma unroll
    for (int i = 0; i < 12; i++) ldsm4t(sw[i], sb + lo16 + w * CH_WREG + i * 512);

#pragma unroll 1
    for (int s = 0;; s++) {
        const bool last = s == NSEG - 1;
        const uint32_t slot = (s & 3) << 14;
        lo16 += delay<DLM>(zero);
        const uint32_t lane = lo16 >> 4, l16 = sb + lo16, wl = l16 + w * CH_WREG, pw = l16 + CH_PART + w * 512;
        const uint32_t xs = l16 + CH_XS + nq * 512 + (w - nq) * 1024;
        const uint32_t eye = ((lo16 >> 7) == (lane & 3)) ? ((lo16 & 64) ? 0x3F800000u : 0x3F80u) : 0u;
        uint2 b[8];
        const char* pm = ring0 + (m_rd + slot + (lo16 >> 1));
        poll_issue<8>(b, pm, true);
        preload<0, ML, 12>(sw, wl, zero);
        if (FNC & 1) bar_arrive(14, 256);
        poll_check<8>(b, pm, delay<FNC & 1>(zero));
        if ((OB || (XB & 1)) && !last) bar_arrive(8, 256 + OB);
        if (PV && !last && w == 7) bar_arrive(13, 64);
        {
            float acc[6][4];
#pragma unroll
            for (int kk = 0; kk < 8; kk++) {
                const int j = (2 * kk) % 12;
                if (kk == 0) { mma16z(acc[5], sw[0], b[0].x, b[0].y); mma16z(acc[4], sw[1], b[0].x, b[0].y); }
                else { mma16(acc[5], sw[j], b[kk].x, b[kk].y); mma16(acc[4], sw[j + 1], b[kk].x, b[kk].y); }
#pragma unroll
                for (int i = 0; i < 4; i++) {
                    if (kk == 0) mma16z(acc[i], wa[i * 8], b[0].x, b[0].y);
                    else mma16(acc[i], wa[i * 8 + kk], b[kk].x, b[kk].y);
                    if (i < 2) ldsm4t(sw[j + i], wl + (12 + 2 * kk + i) * 512);
                }
            }
            st_part(pw + 4 * 2048, acc[4], acc[5]);
            st_part(pw, acc[0], acc[1]);
            st_part(pw + 2 * 2048, acc[2], acc[3]);
        }
        uint32_t kv0, kv1;
        const uint32_t lp = l16 + (lane >> 4) * 256, pl = lp + pt;
        if (!PV) {
            bar_sync(1, last ? 256 : 256 + OB);
            red_part<true>(kv1, kv0, pl, eye);
            sts64(l16 + CH_QK + (w >> 1) * 512 + (w & 1) * 8, __uint_as_float(kv1), __uint_as_float(kv0));
            if (!last) bar_arrive(2, nq * 32 + 64 + OB);
        } else {
            bar_sync(1, last ? 256 : 256 + OB);
        }
        {
            float va[4][4];
            const float z = __uint_as_float(delay<1>(zero));
#pragma unroll
            for (int i = 0; i < 4; i++) va[i][0] = va[i][1] = va[i][2] = va[i][3] = z;
#pragma unroll
            for (int kk = 0; kk < 8; kk++) {
                const int c = (PV ? VCH_P : VCH_C) == 4 ? kk & 1 : 0;
                if (kk < 2) { mma16(va[c], wa[32 + 2 * kk], b[kk].x, b[kk].y); mma16(va[2 + c], wa[33 + 2 * kk], b[kk].x, b[kk].y); }
                else { mma16(va[c], sw[(2 * kk) % 12], b[kk].x, b[kk].y); mma16(va[2 + c], sw[(2 * kk + 1) % 12], b[kk].x, b[kk].y); }
            }
            if ((PV ? VCH_P : VCH_C) == 4) {
#pragma unroll
                for (int j = 0; j < 4; j++) { va[0][j] += va[1][j]; va[2][j] += va[3][j]; }
            }
            st_part(pw + 6 * 2048, va[0], va[2]);
        }
        if (PV) {
            uint32_t vt0[4], vt1[4];
            ldsm4t(vt0, xs); ldsm4t(vt1, xs + 512);
            if (w >= 6 && !last) {
                uint32_t kx[3][4];
#pragma unroll
                for (int j = 0; j < 3; j++)
                    ldsm4(kx[j], sb + CH_XS + j * 1024 + (j == 2 && nq == 5 ? 0 : ((lane >> 3) & 1) * 512) + (w - 6) * 256 + (lane >> 4) * 128 + (lane & 7) * 16);
                const uint32_t da = l16 + CH_SX + rank * 1280 + (w - 6) * 512, dc = sb + CH_SX + rank * 1280 + 1024 + lane * 8;
                bar_sync(2, nq * 32 + 64 + OB);
                uint32_t qk[3][4];
#pragma unroll
                for (int j = 0; j < 3; j++) {
                    const float4 v = lds128(l16 + CH_QK + j * 512);
                    qk[j][0] = __float_as_uint(v.x); qk[j][1] = __float_as_uint(v.y); qk[j][2] = __float_as_uint(v.z); qk[j][3] = __float_as_uint(v.w);
                }
                float s0[4], s1[4], s2[4], s3[4];
                mma16z(s0, qk[0], kx[0][0], kx[0][1]); mma16z(s1, qk[0], kx[0][2], kx[0][3]);
                mma16z(s2, qk[1], kx[1][0], kx[1][1]); mma16z(s3, qk[1], kx[1][2], kx[1][3]);
                if (nq == 5) qk[2][2] = qk[2][3] = 0;
                mma16(s0, qk[2], kx[2][0], kx[2][1]); mma16(s1, qk[2], kx[2][2], kx[2][3]);
                float m0[4], m1[4];
                mma16z(m0, qk[0], qk[0][1], qk[0][3]); mma16z(m1, qk[1], qk[1][1], qk[1][3]);
                mma16(m0, qk[2], qk[2][1], qk[2][3]);
                const float4 sv = make_float4(s0[0] + s2[0], s0[1] + s2[1], s1[0] + s3[0], s1[1] + s3[1]);
                st_async4(mapa(da, rk1), sv, mapa(barS, rk1));
                st_async4(mapa(da, rk2), sv, mapa(barS, rk2));
                {
                    const float c0 = m0[0] + m1[0], c1 = m0[1] + m1[1];
                    const int dr = w == 6 ? rk1 : rk2;
                    st_async2(mapa(dc, dr), c0, c1, mapa(barS, dr));
                    sts64(dc, c0, c1);
                }
                const float t4[4] = {sv.x, sv.y, sv.z, sv.w};
                sts128(da, t4);
            }
            bar_sync(3, last ? 256 : 256 + OB);
            if (!last && w == 7) bar_arrive(12, 64);
            red_part<false>(kv0, kv1, pl, eye);
            if (last) {
                uint32_t* d = (uint32_t*)(kvo + (uint32_t)(s * (NH * 2048) + lane * 4));
                d[0] = movm(kv0); d[32] = movm(kv1);
                break;
            }
            {
                const uint32_t sx = l16 + CH_SX, r0 = rank * 1280, r1 = rk1 * 1280, r2 = rk2 * 1280;
                float4 a0 = lds128(sx + r0), b0 = lds128(sx + 512 + r0);
                const float2 c0 = lds64(sx + 1024 + r0 - lane * 8);
                preload<0, 0, PE>(sw, wl + 28 * 512, zero);
                mbar_wait(barS, s & 1);
                const float4 a1 = lds128(sx + r1), a2 = lds128(sx + r2), b1 = lds128(sx + 512 + r1), b2 = lds128(sx + 512 + r2);
                const float2 c1 = lds64(sx + 1024 + r1 - lane * 8), c2 = lds64(sx + 1024 + r2 - lane * 8);
                a0 = add4(add4(a0, a1), a2); b0 = add4(add4(b0, b1), b2);
                float sc[10] = {a0.x, a0.y, a0.z, a0.w, b0.x, b0.y, b0.z, b0.w, c0.x + c1.x + c2.x, c0.y + c1.y + c2.y};
                float mx = fmaxf(fmaxf(fmaxf(sc[0], sc[1]), fmaxf(sc[2], sc[3])), fmaxf(fmaxf(sc[4], sc[5]), fmaxf(sc[6], sc[7])));
                mx = fmaxf(mx, fmaxf(sc[8], sc[9]));
                mx = fmaxf(fmaxf(mx, __shfl_xor_sync(0xffffffffu, mx, 1)),
                           fmaxf(__shfl_xor_sync(0xffffffffu, mx, 2), __shfl_xor_sync(0xffffffffu, mx, 3)));
                const float cs = 0.08838834764831845f * 1.4426950408889634f;
                const float mb = -mx * cs;
#pragma unroll
                for (int j = 0; j < 10; j++) sc[j] = ex2(fmaf(sc[j], cs, mb));
                uint32_t pf[5];
#pragma unroll
                for (int j = 0; j < 5; j++) pf[j] = pack_bf16(sc[2 * j], sc[2 * j + 1]);
                float o0[4], o1[4], o2[4], o3[4], o4[4], o5[4];
                const uint32_t p0[4] = {pf[0], 0, pf[1], 0}, p1[4] = {pf[2], 0, pf[3], 0};
                mma16z(o0, p0, vt0[0], vt0[1]); mma16z(o1, p0, vt1[0], vt1[1]);
                mma16z(o2, p1, vt0[2], vt0[3]); mma16z(o3, p1, vt1[2], vt1[3]);
                mma8z(o4, pf[4], 0, kv0); mma8z(o5, pf[4], 0, kv1);
                float sum = (((sc[0] + sc[1]) + (sc[2] + sc[3])) + ((sc[4] + sc[5]) + (sc[6] + sc[7]))) + (sc[8] + sc[9]);
                sum = (sum + __shfl_xor_sync(0xffffffffu, sum, 1)) + (__shfl_xor_sync(0xffffffffu, sum, 2) + __shfl_xor_sync(0xffffffffu, sum, 3));
                float inv; asm("rcp.approx.ftz.f32 %0, %1;" : "=f"(inv) : "f"(sum));
                const uint32_t ox = pack_bf16((o0[0] + o2[0] + o4[0]) * inv, (o0[1] + o2[1] + o4[1]) * inv);
                const uint32_t oy = pack_bf16((o1[0] + o3[0] + o5[0]) * inv, (o1[1] + o3[1] + o5[1]) * inv);
                char* const pp = ring0 + (pub + slot + (lo16 >> 1));
                st_pub(pp, ox, oy); st_pub(pp + 4096, ox, oy);
                if (OB || (XB & 4)) bar_arrive(10, (8 - nq) * 32 + OB);
                preload<0, PE, PL>(sw, wl + 28 * 512, zero);
            }
            kv0 = movm(kv0); kv1 = movm(kv1);
        } else {
            *(uint32_t*)(kvo + (uint32_t)(s * (NH * 2048) + lane * 4)) = kv0;
            bar_sync(3, last ? 256 : 256 + OB);
            if (last) break;
            preload<1, 0, CL>(sw, wl + 28 * 512, zero);
        }
        uint2 c[11];
        bar_sync(4, 256 + OB);
        const char* po = ring0 + (o_rd + slot + (lo16 >> 1) + delay<DLO>(zero));
        poll_issue<11>(c, po, rank < 2);
        preload<0, PV ? PL : CL, 12>(sw, wl + 28 * 512, zero);
        if (PV) { uint32_t* d = (uint32_t*)(kvo + (uint32_t)(s * (NH * 2048) + lane * 4)); d[0] = kv0; d[32] = kv1; }
        if (FNC & 2) bar_arrive(15, 256);
        poll_check<11>(c, po, delay<(FNC >> 1)>(zero));
        if (OB || (XB & 2)) bar_arrive(9, 256 + OB);
        {
            float acc[4][4];
#pragma unroll
            for (int f = 0; f < 22; f++) {
                const int kk = f >> 1, a = f & 3;
                if (f < 4) mma16z(acc[a], sw[f % 12], c[kk].x, c[kk].y);
                else mma16(acc[a], sw[f % 12], c[kk].x, c[kk].y);
                if (f + 12 < 22) ldsm4t(sw[f % 12], wl + (28 + f + 12) * 512);
            }
#pragma unroll
            for (int i = 0; i < 2; i++) {
#pragma unroll
                for (int j = 0; j < 4; j++) acc[i][j] += acc[i + 2][j];
                sts128(l16 + CH_PART + i * 4096 + w * 512, acc[i]);
            }
        }
        if (!PV && w < 2) {
            bar_sync(5, 288 + OB);
            float4 v[8];
#pragma unroll
            for (int i = 0; i < 8; i++) v[i] = lds128(l16 + CH_PART + w * 4096 + i * 512);
            float4 r = add4(add4(add4(v[0], v[1]), add4(v[2], v[3])), add4(add4(v[4], v[5]), add4(v[6], v[7])));
            if (!mown) st_async4(mapa(l16 + CH_MX + rank * 512, w), r, mapa(barM, w));
            bar_arrive(7, 256 + OB);
            if (mown) {
                mbar_wait(barM, s & 1);
                float4 x = lds128(l16 + CH_MX + (rank ^ 1) * 512), y = lds128(l16 + CH_MX + 2 * 512);
                r = add4(add4(x, r), y);
                const uint32_t mx = movm(pack_bf16(r.x, r.y)), my = movm(pack_bf16(r.z, r.w));
                const uint32_t ns = (slot + 0x4000) & 0xC000;
                char* const pp = ring0 + (pub + ns + (lo16 >> 1));
                st_pub(pp, mx, my); st_pub(pp + 4096, mx, my);
            }
            preload<0, 0, ML>(sw, wl, zero);
        } else {
            bar_arrive(5, 288 + OB);
            bar_sync(7, 256 + OB);
            preload<MP, 0, ML>(sw, wl, zero);
        }
        bar_sync(6, 320 + OB);
    }
}

__device__ __forceinline__ void chain_pace(const uint32_t sb, const int lane, const int rank, const int aware) {
    const uint32_t zero = sb + CH_BAR + 24;
    if (lane == 0) {
        char* ring = ring_base();
        uint32_t* p0 = (uint32_t*)(ring + ring_off(blockIdx.x & 15, 0) + 3072 + (blockIdx.x >> 4) * 128);
        uint32_t* p1 = (uint32_t*)(ring + ring_off(blockIdx.x & 15, 1) + 3072 + (blockIdx.x >> 4) * 128);
        *p0 = 0; *p1 = 0;
        int b0 = 1 << 30, b1 = 1 << 30; uint32_t v = 0;
        for (int r = 0; r < 4 || (r < 256 && !mbar_test(sb + CH_BAR + 16, 0)); r++) {
            uint32_t t0 = clk(); v = atomicExch(p0 + (v == 500), r); uint32_t t1 = v == 777 ? clk() + 1 : clk(); b0 = min(b0, (int)(t1 - t0));
            t0 = clk(); v = atomicExch(p1 + (v == 500), r); t1 = v == 777 ? clk() + 1 : clk(); b1 = min(b1, (int)(t1 - t0));
            asm volatile("st.volatile.shared.u32 [%0], %1;" ::"r"(zero + 4), "r"(aware ? (b1 < b0) ^ (aware - 1) : 0) : "memory");
        }
    }
    __syncwarp();
#pragma unroll 1
    for (int s = 1; s < NSEG; s++) {
        bar_sync(5, 288 + OB);
        bar_arrive(6, 320 + OB + (rank == 2 ? delay<PACE2>(zero) : 0));
    }
}
__device__ __forceinline__ char* reset_ptr(const int lane, const int rank, const int h) {
    const int nq = rank == 0 ? 6 : 5, v0 = rank == 0 ? -6 : 3 * rank - 6;
    int pos, cw = o_chunk(h * 8 + v0 + min(max(5 + (lane >> 3), nq), 7), pos);
    if (lane >= 24 && rank < 2) { cw = 24 + (h >> 2); pos = (2 * h + rank) & 7; }
    return ring_base() + ((ring_off(cw, 0) & ~4096u) + pos * 256 + (lane & 7) * 16);
}
__device__ __forceinline__ void chain_chores(const uint32_t sb, const int lane, const int rank, const int h, const bf16* __restrict__ mem0) {
    const int nq = rank == 0 ? 6 : 5, u0 = rank == 0 ? 0 : 1 + 5 * rank, v0 = rank == 0 ? -6 : 3 * rank - 6;
    const uint32_t barS = sb + CH_BAR, barM = barS + 8, barX = barS + 16;
    auto xload = [&](int s) {
        mbar_expect(barX, 8192 - nq * 512);
        bulk_load(sb + CH_XS, g_kx + (size_t)(s * NH + h) * 4096 + u0 * 256, nq * 512, barX);
        bulk_load(sb + CH_XS + nq * 512, g_vx + (size_t)(s * NH + h) * 4096 + (v0 + nq) * 512, (8 - nq) * 1024, barX);
    };
    char* const rb = reset_ptr(lane, rank, h);
    int* const kvf = g_kvf + blockIdx.x * 16;
    if (rank < 2) {
        const uint32_t* p = (const uint32_t*)(mem0 + (lane >> 2) * DM + 32 * h + 16 * rank + 2 * (lane & 3));
        char* d = ring_base() + ((ring_off(24 + (h >> 2), 0) & ~4096u) + ((2 * h + rank) & 7) * 256 + lane * 8);
        const uint32_t x = p[0] == SENT ? 0x7FFF7FFFu : p[0];
        st_pub(d, x, p[4]); st_pub(d + 4096, x, p[4]);
    }
    if (!KVN) __nanosleep(18000);
    wait_ctr(kvf, KVN);
    asm volatile("fence.proxy.async.global;" ::: "memory");
    if (elect()) xload(0);
#pragma unroll 1
    for (int s = 0; s < NSEG - 1; s++) {
        if (lane == 0) {
            mbar_expect(barS, 2 * 1280);
            if (rank < 2) mbar_expect(barM, 2 * 512);
        }
        bar_sync(13, 64);
#pragma unroll
        for (int i = 0; i < 4; i++)
            asm volatile("st.relaxed.gpu.global.v4.u32 [%0], {%1,%1,%1,%1};" ::"l"(rb + ((((s + 2) & 3) << 14) + (i >> 1) * 4096 + (i & 1) * 128)), "r"(SENT) : "memory");
        if (FEN || (s & 3) == 0) fence_gpu();
        if (lane == 0 && (s & 3) == 0 && s) atomicAdd(g_ctr + C_CHAIN + (s >> 2) - 1, 1);
        if ((s & 3) == 3) { wait_ctr(kvf + (s >> 2) + 1, KVN); asm volatile("fence.proxy.async.global;" ::: "memory"); }
        __syncwarp();
        bar_sync(12, 64);
        if (elect()) xload(s + 1);
        mbar_wait(barX, (s + 1) & 1);
        bar_sync(6, 320 + OB);
    }
}

struct S4Params { const bf16 *Are, *Aim, *Bre, *Bim, *Cre, *Cim, *ldt, *dsk; };
__device__ __forceinline__ float2 cmul(float2 a, float2 b) { return make_float2(a.x * b.x - a.y * b.y, a.x * b.y + a.y * b.x); }
__device__ __forceinline__ float2 csq(float2 a) { return make_float2(a.x * a.x - a.y * a.y, (a.x + a.x) * a.y); }
__device__ __forceinline__ float2 cexp_t(float lr, float turns) {
    float f = (turns - rintf(turns)) * 6.283185307179586f, e = ex2(lr);
    return make_float2(e * __cosf(f), e * __sinf(f));
}
__device__ __forceinline__ float bf_at(uint2 v, int i) {
    const uint32_t w = i < 2 ? v.x : v.y;
    return __uint_as_float((i & 1) ? w & 0xFFFF0000u : w << 16);
}
__device__ __forceinline__ void kg_step(uint32_t (&a)[4][4], uint32_t (&b)[5][2], uint32_t pa, uint32_t pe, float x0) {
#pragma unroll
    for (int i = 0; i < 2; i++) {
        const float4 p = lds128(pa + i * 64);
        const float2 e8 = lds64(pe + i * 32), c = make_float2(p.z, p.w);
        const float mag = ex2(p.x * x0), ph = p.y * x0;
        float2 e0 = make_float2(mag * __cosf(ph), mag * __sinf(ph)), e1 = cmul(e0, e8);
#pragma unroll
        for (int j = 0; j < 4; j++) {
            a[j][2 * i] = pack_bf16(e0.x, e0.y); a[j][2 * i + 1] = pack_bf16(e1.x, e1.y);
            e0 = csq(e0); e1 = csq(e1);
        }
        float2 m = cmul(c, e0);
        b[0][i] = pack_bf16(m.x, -m.y);
#pragma unroll
        for (int j = 0; j < 4; j++) {
            m = cmul(c, e1);
            b[j + 1][i] = pack_bf16(m.x, -m.y);
            if (j < 3) e1 = csq(e1);
        }
    }
}
__device__ __forceinline__ void kg_mma(float (&kd)[5][4], const uint32_t (&a)[4][4], const uint32_t (&b)[5][2]) {
    mma16(kd[0], a[0], b[0][0], b[0][1]);
#pragma unroll
    for (int j = 0; j < 4; j++) mma16(kd[j + 1], a[j], b[j + 1][0], b[j + 1][1]);
}
struct KgRaw { uint2 v[6]; float ldt; };
__device__ __forceinline__ void kg_load(KgRaw& r, const S4Params& P, int d, int lane) {
    const bf16* src[6] = {P.Are, P.Aim, P.Bre, P.Bim, P.Cre, P.Cim};
#pragma unroll
    for (int j = 0; j < 6; j++) r.v[j] = __ldg((const uint2*)(src[j] + d * 128) + lane);
    r.ldt = __bfloat162float(P.ldt[d]);
}
__device__ __forceinline__ float kg_params(const KgRaw& r, uint32_t stg, int lane) {
    const float dt = __bfloat162float(__float2bfloat16(expf(r.ldt)));
    float k2048 = 0.f;
#pragma unroll
    for (int i = 0; i < 4; i++) {
        const float br = dt * bf_at(r.v[2], i), bi = dt * bf_at(r.v[3], i), cr = bf_at(r.v[4], i), ci = bf_at(r.v[5], i);
        const float zr = dt * bf_at(r.v[0], i) * 1.4426950408889634f;
        float zt = dt * bf_at(r.v[1], i) * 0.15915494309189535f;
        zt -= rintf(zt);
        const float v[4] = {zr, zt * 6.283185307179586f, cr * br - ci * bi, cr * bi + ci * br};
        const float2 e8 = cexp_t(8.f * zr, 8.f * zt), el = cexp_t(2048.f * zr, 2048.f * zt);
        k2048 += v[2] * el.x - v[3] * el.y;
        sts128(stg + (i * 32 + lane) * 16, v);
        sts64(stg + 2048 + (i * 32 + lane) * 8, e8.x, e8.y);
    }
#pragma unroll
    for (int o = 16; o; o >>= 1) k2048 += __shfl_xor_sync(0xffffffffu, k2048, o);
    __syncwarp();
    return k2048;
}
__device__ __forceinline__ void kg_store(const float (&kd)[5][4], float k2048, uint32_t stg, int d, int lane) {
    __syncwarp();
    const uint32_t ta = stg + (lane & 7) * 32 + ((lane >> 3) & 1) * 16 + (lane >> 4) * 256;
    stsm4t(ta, pack_bf16(kd[0][0], kd[0][1]), pack_bf16(kd[0][2], kd[0][3]), pack_bf16(kd[1][0], kd[1][1]), pack_bf16(kd[1][2], kd[1][3]));
    stsm4t(ta + 512, pack_bf16(kd[2][0], kd[2][1]), pack_bf16(kd[2][2], kd[2][3]), pack_bf16(kd[3][0], kd[3][1]), pack_bf16(kd[3][2], kd[3][3]));
    stsm4t(ta + 1024, pack_bf16(kd[4][0], kd[4][1]), pack_bf16(kd[4][2], kd[4][3]), pack_bf16(k2048, 0.f), 0);
    __syncwarp();
#pragma unroll
    for (int j = 0; j < 3; j++) ((float4*)(g_kd + d * 768))[j * 32 + lane] = lds128(stg + j * 512 + lane * 16);
    __syncwarp();
}

__global__ void __cluster_dims__(3, 1, 1) __launch_bounds__(CH_THREADS, 1)
chain_kernel(const __grid_constant__ CUtensorMap mq, const __grid_constant__ CUtensorMap mk, const __grid_constant__ CUtensorMap mv,
             const __grid_constant__ CUtensorMap mo, const bf16* __restrict__ Wq, const bf16* __restrict__ Wk, const bf16* __restrict__ Wv,
             const bf16* __restrict__ mem0, const __grid_constant__ S4Params P, int aware) {
    extern __shared__ __align__(1024) unsigned char smem[];
    const uint32_t sb = smem_u32(smem);
    const int tid = threadIdx.x, lane = tid & 31;
    const int w = __shfl_sync(0xffffffffu, tid >> 5, 0);
    int rank; asm("mov.u32 %0, %%cluster_ctarank;" : "=r"(rank));
    const int h = blockIdx.x / 3;
    if (tid == 0) {
        mbar_init(sb + CH_BAR, 1); mbar_init(sb + CH_BAR + 8, 1); mbar_init(sb + CH_BAR + 16, 1);
        for (int i = 0; i < 16; i++) mbar_init(sb + CH_BAR + 64 + i * 8, 1);
        *(int*)(smem + CH_BAR + 24) = 0; *(int*)(smem + CH_BAR + 28) = 0; *(int*)(smem + CH_BAR + 32) = 0;
        asm volatile("fence.mbarrier_init.release.cluster;" ::: "memory");
    }
    if (w == 10 && PFKV) {
        const int e = lane * 96 + blockIdx.x;
        if (e < 2048) asm volatile("cp.async.bulk.prefetch.L2.global [%0], 8192;" ::"l"(((e & 1) ? Wv : Wk) + (size_t)(e >> 1) * HD) : "memory");
        if (PFKV > 1) __nanosleep(PFKV);
    }
    if (w == 9) {
        char* const rb = reset_ptr(lane, rank, h);
#pragma unroll
        for (int i = 0; i < 8; i++)
            asm volatile("st.relaxed.gpu.global.v4.u32 [%0], {%1,%1,%1,%1};" ::"l"(rb + (((i >> 2) << 14) + ((i >> 1) & 1) * 4096 + (i & 1) * 128)), "r"(SENT) : "memory");
        if (lane < 16) g_kvf[blockIdx.x * 16 + lane] = 0;
        if (blockIdx.x == 0)
            for (int k = lane; k < N_CTR; k += 32) g_ctr[k] = 0;
        fence_gpu();
        __syncwarp();
        asm volatile("griddepcontrol.launch_dependents;" ::: "memory");
    }
    __syncthreads();
    asm volatile("barrier.cluster.arrive.relaxed.aligned;" ::: "memory");

    if (w >= 8) {
        reg_dec<24>();
        asm volatile("barrier.cluster.wait.aligned;" ::: "memory");
        if (w == 8) chain_pace(sb, lane, rank, aware);
        else if (w == 9) {
            chain_chores(sb, lane, rank, h, mem0);
            asm volatile("st.volatile.shared.u32 [%0], %1;" ::"r"(sb + CH_BAR + 32), "r"(0x3F803F80) : "memory");
        } else if (w == 11 && KEEP) {
#pragma unroll 1
            for (int it = 0; it < (1 << 22); it++) {
                int d0, d1;
                const uint32_t x = delay<1>(sb + CH_BAR + 32);
                asm volatile("mma.sync.aligned.m8n8k16.row.col.s32.s8.s8.s32 {%0,%1}, {%2}, {%2}, {%3,%3};" : "=r"(d0), "=r"(d1) : "r"(x), "r"(0));
                if (d0 | d1) break;
                if ((XB & 8) && lane == 0) asm volatile("st.relaxed.gpu.global.u32 [%0], %1;" ::"l"(g_kd + DM * 768 + blockIdx.x * 64), "r"(it) : "memory");
                if ((XB & 16) && lane == 0) ld_acq((int*)(g_kd + DM * 768 + blockIdx.x * 64));
                __nanosleep(KEEP);
            }
        }
    } else {
        reg_inc<240>();
        const int nq = rank == 0 ? 6 : 5;
        const int u0 = rank == 0 ? 0 : 1 + 5 * rank;
        const int v0 = rank == 0 ? -6 : 3 * rank - 6;
        const int gw = rank * 8 + w;
        const int ks0 = gw < 16 ? 11 * gw : 176 + 10 * (gw - 16);
        const int nko = gw < 16 ? 11 : 10;
        const uint32_t wr = sb + w * CH_WREG, bar0 = sb + CH_BAR + 64 + w * 16, bar1 = bar0 + 8;
        uint32_t wa[36][4];
        const uint32_t vst = sb + CH_PART + w * 2048;
        const int cq = h * DH + 8 * u0, cv = h * DH + 16 * (v0 + 6);
        const int r8 = lane >> 2, p = lane & 3;
        const bf16* src = p >= 2 ? ((p & 1) ? Wk : Wq) + cq + 32 : rank == 0 ? ((p & 1) ? Wk : Wq) + cq + 40 : Wv + cv - 16 + 8 * p;
        src += (size_t)(128 * w + r8) * HD;
        auto cp_rows = [&](int kh) {
            cp16(wr + ((kh >> 1) * 2 + (p >> 1)) * 512 + ((kh & 1) * 2 + (p & 1)) * 128 + r8 * 16, src + (size_t)kh * 8 * HD);
        };
        {
            int d = blockIdx.x * 8 + w, t = 0;
            const int d1 = 768 + blockIdx.x * 3 + w, nt = (w < 3 && d1 < DM) ? 32 : 16;
            const uint32_t stg = wr + 4096;
            KgRaw raw, raw1;
            kg_load(raw, P, d, lane);
            kg_load(raw1, P, min(d1, DM - 1), lane);
            float kd[5][4], k2048;
#pragma unroll 1
            for (int i = -LDW; i < 9 || t < nt; i++) {
                if (i >= 0 && i < 9) {
                    const uint32_t bar = bar0 + (i & 1) * 8;
                    if (i >= 2) mbar_wait(bar, ((i >> 1) - 1) & 1);
                    if (elect()) {
                        mbar_expect(bar, 2048);
                        if (i < 8) tma2d(wr + 8192 + (i & 1) * 8192 + (i >> 1) * 2048, (i & 1) ? &mk : &mq, cq, 128 * w + 32 * (i >> 1), bar);
                        else tma2d(vst, &mv, cv, 128 * w, bar);
                    }
                    if (i < 8) cp_rows(i);
                }
#pragma unroll 1
                for (int e = min(t + KGS, nt); t < e; t++) {
                    if ((t & 15) == 0) {
                        k2048 = kg_params(raw, stg, lane);
#pragma unroll
                        for (int j = 0; j < 20; j++) kd[j >> 2][j & 3] = 0.f;
                    }
                    uint32_t ka[4][4], kb[5][2];
                    kg_step(ka, kb, stg + ((t & 15) * 8 + (lane & 3)) * 16, stg + 2048 + ((t & 15) * 8 + (lane & 3)) * 8, (float)(lane >> 2));
                    kg_mma(kd, ka, kb);
                    if ((t & 15) == 15) { kg_store(kd, k2048, stg, d, lane); raw = raw1; d = d1; }
                }
            }
        }
        const uint32_t lrow = ((lane >> 4) * 8 + (lane & 7)) * 64, lsw = (lane >> 1) & 3, lh = (lane >> 3) & 1;
        mbar_wait(bar1, 1); mbar_wait(bar0, 0);
#pragma unroll
        for (int i = 0; i < 32; i++) ldsm4t(wa[i], wr + 8192 + lh * 8192 + (i & 7) * 1024 + lrow + (((i >> 3) ^ lsw) << 4));
#pragma unroll
        for (int i = 0; i < 4; i++) ldsm4t(wa[32 + i], vst + (i >> 1) * 1024 + lrow + ((((i & 1) * 2 + lh) ^ lsw) << 4));
        asm volatile("fence.proxy.async.shared::cta;" ::"r"(wa[31][0]), "r"(wa[35][0]) : "memory");
        __syncwarp();
#pragma unroll 1
        for (int i = 9; i < 18; i++) {
            const uint32_t bar = bar0 + (i & 1) * 8;
            if (i >= 11) mbar_wait(bar, ((i >> 1) - 1) & 1);
            if (elect()) {
                const int j = 2 * (i - 12), nb = min(2, nko - j);
                mbar_expect(bar, i < 12 ? 2048 : nb * 1024);
                if (i < 12) tma2d(wr + 8192 + (i - 9) * 2048, &mv, cv, 128 * w + 32 * (i - 8), bar);
                else {
                    if (nb > 0) tma2d(wr + 14336 + j * 1024, &mo, 32 * h, 16 * (ks0 + j), bar);
                    if (nb > 1) tma2d(wr + 15360 + j * 1024, &mo, 32 * h, 16 * (ks0 + j + 1), bar);
                }
            }
            if (i < 17) cp_rows(i - 1);
        }
        mbar_wait(bar0, 0); mbar_wait(bar1, 0);
#pragma unroll 1
        for (int i0 = -1; i0 < 17; i0 += 6) {
            uint32_t x[6][2][4];
#pragma unroll
            for (int i = 0; i < 6; i++) {
                const uint32_t a = wr + 8192 + max(i0 + i, 0) * 1024 + lrow;
                ldsm4t(x[i][0], a + ((lh ^ lsw) << 4)); ldsm4t(x[i][1], a + (((2 + lh) ^ lsw) << 4));
            }
            if (i0 == 11 && nko == 10) {
#pragma unroll
                for (int j = 0; j < 8; j++) x[5][j >> 2][j & 3] = 0;
            }
            __syncwarp();
#pragma unroll
            for (int i = 0; i < 6; i++) {
                const uint32_t a = wr + 8192 + max(i0 + i, 0) * 1024 + lane * 16;
                stsm4t(a, x[i][0][0], x[i][0][1], x[i][0][2], x[i][0][3]); stsm4t(a + 512, x[i][1][0], x[i][1][1], x[i][1][2], x[i][1][3]);
            }
        }
        asm volatile("cp.async.wait_all;" ::: "memory");
        asm volatile("barrier.cluster.wait.aligned;" ::: "memory");
        bar_sync(1, 256);
        mbar_wait_long(sb + CH_BAR + 16, 0);
        const int side = __shfl_sync(0xffffffffu, *(volatile int*)(smem + CH_BAR + 28), 0);
        if (w >= nq) chain_loop<true>(wa, sb, w, lane, rank, h, side);
        else chain_loop<false>(wa, sb, w, lane, rank, h, side);
    }
}

constexpr int G_STAGE = 49152, G_NST = 4;
constexpr int G_STG = G_NST * G_STAGE;
constexpr int G_BAR = G_STG + 32768;
constexpr int G_SMEM = G_BAR + 256 + 1024;

#define WLOG(e)
constexpr int IT_QA = 0, IT_O = 1, IT_S4 = 2, IT_END = 3, IT_KV = 4;
#define O_WIDE 10
#define PING 1
#define S4DIR 5
#define S4REL 4
#define KVI 2
#define KVF 2
#define KVS 8
#define STM 0
__device__ __forceinline__ void st_out(uint32_t* p, uint32_t v) {
    if (STM == 0) *p = v;
    else if (STM == 1) __stcs(p, v);
    else asm volatile("st.global.L1::no_allocate.u32 [%0], %1;" ::"l"(p), "r"(v) : "memory");
}
#define Q_N1 1
#define Q_S1 16
__device__ __forceinline__ int queue_item(int q) {
    if (q < 512) return (IT_KV << 16) | ((q >> 5) << 8) | (q & 31);
    q -= 512;
    if (q < 256) return (IT_QA << 16) | ((q >> 4) << 8) | (q & 15);
    q -= 256;
    if (q < Q_N1 * 8) return (IT_O << 16) | ((O_WIDE + (q >> 3)) << 8) | (q & 7);
    q -= Q_N1 * 8;
    if (q < Q_S1) return (IT_S4 << 16) | q;
    q -= Q_S1;
    if (q < (16 - O_WIDE - Q_N1) * 8) return (IT_O << 16) | ((O_WIDE + Q_N1 + (q >> 3)) << 8) | (q & 7);
    q -= (16 - O_WIDE - Q_N1) * 8;
    if (q < 128 - Q_S1) return (IT_S4 << 16) | (Q_S1 + q);
    return IT_END << 16;
}
__device__ __forceinline__ void tma2d_store(const CUtensorMap* m, uint32_t src, int c0, int c1) {
    asm volatile("cp.async.bulk.tensor.2d.global.shared::cta.bulk_group [%0, {%2, %3}], [%1];" ::"l"(m), "r"(src), "r"(c0), "r"(c1) : "memory");
}

__device__ __forceinline__ void wgmma_s64(float (&d)[32], uint32_t a0, uint32_t a1, uint32_t a2, uint32_t a3, uint64_t db, int acc) {
    asm volatile("{.reg .pred p; setp.ne.b32 p, %37, 0;\n"
        "wgmma.mma_async.sync.aligned.m64n64k16.f32.bf16.bf16 {"
        "%0,%1,%2,%3,%4,%5,%6,%7,%8,%9,%10,%11,%12,%13,%14,%15,"
        "%16,%17,%18,%19,%20,%21,%22,%23,%24,%25,%26,%27,%28,%29,%30,%31"
        "}, {%32,%33,%34,%35}, %36, p, 1, 1, 0;}"
        : "+f"(d[0]), "+f"(d[1]), "+f"(d[2]), "+f"(d[3]), "+f"(d[4]), "+f"(d[5]), "+f"(d[6]), "+f"(d[7]), "+f"(d[8]), "+f"(d[9]), "+f"(d[10]), "+f"(d[11]), "+f"(d[12]), "+f"(d[13]), "+f"(d[14]), "+f"(d[15]), "+f"(d[16]), "+f"(d[17]), "+f"(d[18]), "+f"(d[19]), "+f"(d[20]), "+f"(d[21]), "+f"(d[22]), "+f"(d[23]), "+f"(d[24]), "+f"(d[25]), "+f"(d[26]), "+f"(d[27]), "+f"(d[28]), "+f"(d[29]), "+f"(d[30]), "+f"(d[31])
        : "r"(a0), "r"(a1), "r"(a2), "r"(a3), "l"(db), "r"(acc));
}
__device__ __forceinline__ void wgmma_s16(float (&d)[8], uint32_t a0, uint32_t a1, uint32_t a2, uint32_t a3, uint64_t db, int acc) {
    asm volatile("{.reg .pred p; setp.ne.b32 p, %13, 0;\n"
        "wgmma.mma_async.sync.aligned.m64n16k16.f32.bf16.bf16 {"
        "%0,%1,%2,%3,%4,%5,%6,%7"
        "}, {%8,%9,%10,%11}, %12, p, 1, 1, 0;}"
        : "+f"(d[0]), "+f"(d[1]), "+f"(d[2]), "+f"(d[3]), "+f"(d[4]), "+f"(d[5]), "+f"(d[6]), "+f"(d[7])
        : "r"(a0), "r"(a1), "r"(a2), "r"(a3), "l"(db), "r"(acc));
}
__device__ __forceinline__ void wgmma_v128(float (&d)[64], uint32_t a0, uint32_t a1, uint32_t a2, uint32_t a3, uint64_t db, int acc) {
    asm volatile("{.reg .pred p; setp.ne.b32 p, %69, 0;\n"
        "wgmma.mma_async.sync.aligned.m64n128k16.f32.bf16.bf16 {"
        "%0,%1,%2,%3,%4,%5,%6,%7,%8,%9,%10,%11,%12,%13,%14,%15,"
        "%16,%17,%18,%19,%20,%21,%22,%23,%24,%25,%26,%27,%28,%29,%30,%31,"
        "%32,%33,%34,%35,%36,%37,%38,%39,%40,%41,%42,%43,%44,%45,%46,%47,"
        "%48,%49,%50,%51,%52,%53,%54,%55,%56,%57,%58,%59,%60,%61,%62,%63"
        "}, {%64,%65,%66,%67}, %68, p, 1, 1, 1;}"
        : "+f"(d[0]), "+f"(d[1]), "+f"(d[2]), "+f"(d[3]), "+f"(d[4]), "+f"(d[5]), "+f"(d[6]), "+f"(d[7]), "+f"(d[8]), "+f"(d[9]), "+f"(d[10]), "+f"(d[11]), "+f"(d[12]), "+f"(d[13]), "+f"(d[14]), "+f"(d[15]), "+f"(d[16]), "+f"(d[17]), "+f"(d[18]), "+f"(d[19]), "+f"(d[20]), "+f"(d[21]), "+f"(d[22]), "+f"(d[23]), "+f"(d[24]), "+f"(d[25]), "+f"(d[26]), "+f"(d[27]), "+f"(d[28]), "+f"(d[29]), "+f"(d[30]), "+f"(d[31]), "+f"(d[32]), "+f"(d[33]), "+f"(d[34]), "+f"(d[35]), "+f"(d[36]), "+f"(d[37]), "+f"(d[38]), "+f"(d[39]), "+f"(d[40]), "+f"(d[41]), "+f"(d[42]), "+f"(d[43]), "+f"(d[44]), "+f"(d[45]), "+f"(d[46]), "+f"(d[47]), "+f"(d[48]), "+f"(d[49]), "+f"(d[50]), "+f"(d[51]), "+f"(d[52]), "+f"(d[53]), "+f"(d[54]), "+f"(d[55]), "+f"(d[56]), "+f"(d[57]), "+f"(d[58]), "+f"(d[59]), "+f"(d[60]), "+f"(d[61]), "+f"(d[62]), "+f"(d[63])
        : "r"(a0), "r"(a1), "r"(a2), "r"(a3), "l"(db), "r"(acc));
}

__device__ __forceinline__ void attn_scores(float (&sx)[32], float (&sm)[8], const uint32_t (&q)[32], uint32_t sk) {
    const uint64_t dx = mkdesc(sk, 1024, 128, 0), dm = mkdesc(sk + 16384, 256, 128, 0);
    wg_fence();
#pragma unroll
    for (int ks = 0; ks < 8; ks++) {
        wgmma_s64(sx, q[4 * ks], q[4 * ks + 1], q[4 * ks + 2], q[4 * ks + 3], dx + ks * 128, ks);
        wgmma_s16(sm, q[4 * ks], q[4 * ks + 1], q[4 * ks + 2], q[4 * ks + 3], dm + ks * 32, ks);
    }
    wg_commit();
}
template <bool HI>
__device__ __forceinline__ void attn_softmax(uint32_t (&p)[2][20], const float (&sx)[2][32], const float (&sm)[2][8], bool sb, int lane) {
    constexpr int NF = HI ? 2 : 0, NT = NF + 3;
    const int gt = (lane >> 2) - 2 * (lane & 3);
    const float cs = 0.08838834764831845f * 1.4426950408889634f;
    float s[2][NT][4], m[4], l[4];
#pragma unroll
    for (int h = 0; h < 2; h++) {
#pragma unroll
        for (int j = 0; j < NT; j++)
#pragma unroll
            for (int e = 0; e < 4; e++) s[h][j][e] = j == NT - 1 ? (sb ? sm[h][4 + e] : sm[h][e]) : (sb ? sx[h][16 + 4 * j + e] : sx[h][4 * j + e]);
        if (gt < 0) s[h][NF][0] = s[h][NF + 1][2] = -INFINITY;
        if (gt < 1) s[h][NF][1] = s[h][NF + 1][3] = -INFINITY;
        m[2 * h] = fmaxf(s[h][0][0], s[h][0][1]); m[2 * h + 1] = fmaxf(s[h][0][2], s[h][0][3]);
#pragma unroll
        for (int j = 1; j < NT; j++) {
            if (j != NF + 1) m[2 * h] = fmaxf(m[2 * h], fmaxf(s[h][j][0], s[h][j][1]));
            m[2 * h + 1] = fmaxf(m[2 * h + 1], fmaxf(s[h][j][2], s[h][j][3]));
        }
    }
#pragma unroll
    for (int r = 0; r < 4; r++) m[r] = fmaxf(m[r], __shfl_xor_sync(0xffffffffu, m[r], 1));
#pragma unroll
    for (int r = 0; r < 4; r++) m[r] = fmaxf(m[r], __shfl_xor_sync(0xffffffffu, m[r], 2)) * -cs;
#pragma unroll
    for (int r = 0; r < 4; r++) {
        l[r] = 0.f;
#pragma unroll
        for (int j = 0; j < NT; j++)
            if ((r & 1) || j != NF + 1) {
                float* v = &s[r >> 1][j][2 * (r & 1)];
                v[0] = ex2(fmaf(v[0], cs, m[r])); v[1] = ex2(fmaf(v[1], cs, m[r]));
                l[r] += v[0] + v[1];
            }
    }
#pragma unroll
    for (int r = 0; r < 4; r++) l[r] += __shfl_xor_sync(0xffffffffu, l[r], 1);
#pragma unroll
    for (int r = 0; r < 4; r++) { l[r] += __shfl_xor_sync(0xffffffffu, l[r], 2); asm("rcp.approx.ftz.f32 %0, %0;" : "+f"(l[r])); }
    const uint32_t ma = sb ? 0u : ~0u;
#pragma unroll
    for (int h = 0; h < 2; h++)
#pragma unroll
        for (int j = 0; j < 5; j++) {
            const bool on = j == 4 || j < NF + 2;
            const int k = j == 4 ? NT - 1 : on ? j : 0, ia = j < 4 ? 2 * j : 16, ib = j < 4 ? 8 + 2 * j : 18;
            const uint32_t x = on && j != NF + 1 ? pack_bf16(s[h][k][0] * l[2 * h], s[h][k][1] * l[2 * h]) : 0;
            const uint32_t y = on ? pack_bf16(s[h][k][2] * l[2 * h + 1], s[h][k][3] * l[2 * h + 1]) : 0;
            asm volatile("and.b32 %0, %4, %6; and.b32 %1, %5, %6; and.b32 %2, %4, %7; and.b32 %3, %5, %7;"
                : "=&r"(p[h][ia]), "=&r"(p[h][ia + 1]), "=&r"(p[h][ib]), "=&r"(p[h][ib + 1]) : "r"(x), "r"(y), "r"(ma), "r"(~ma));
        }
}
__device__ __forceinline__ void attn_pv(float (&o)[64], const uint32_t (&p)[20], uint32_t sv) {
    const uint64_t dx = mkdesc(sv, 128, 1024, 0), dm = mkdesc(sv + 16384, 128, 256, 0);
    wg_fence();
#pragma unroll
    for (int ks = 0; ks < 5; ks++) wgmma_v128(o, p[4 * ks], p[4 * ks + 1], p[4 * ks + 2], p[4 * ks + 3], ks < 4 ? dx + ks * 16 : dm, ks);
    wg_commit();
}
__device__ __forceinline__ void attn_stage(const float (&o)[64], uint32_t dst) {
#pragma unroll
    for (int u = 0; u < 16; u += 2)
        stsm4(dst + (u >> 3) * 8192 + (u & 7) * 128, pack_bf16(o[4 * u], o[4 * u + 1]), pack_bf16(o[4 * u + 2], o[4 * u + 3]),
              pack_bf16(o[4 * u + 4], o[4 * u + 5]), pack_bf16(o[4 * u + 6], o[4 * u + 7]));
}

template <int BN, int NKB, bool BLOCKED_A>
__device__ __forceinline__ void mainloop(float (&acc)[BN / 2], uint32_t sb, int wgi, uint32_t full, uint32_t empty, int& it, bool elect) {
#pragma unroll
    for (int j = 0; j < BN / 2; j++) acc[j] = 0.f;
#pragma unroll 1
    for (int k4 = 0; k4 < NKB; k4 += 4) {
#pragma unroll
        for (int st = 0; st < 4; st++, it++) {
            mbar_wait_long(full + 8 * st, (it >> 2) & 1);
            const uint64_t da = BLOCKED_A ? mkdesc(sb + st * G_STAGE + wgi * 8192, 128, 1024, 0) : mkdesc(sb + st * G_STAGE + wgi * 8192, 16, 1024, 1);
            const uint64_t db = mkdesc(sb + st * G_STAGE + 16384, 8192, 1024, 1);
            wg_fence();
#pragma unroll
            for (int k = 0; k < 4; k++) {
                if constexpr (BN == 256) wgmma256(acc, da + k * (BLOCKED_A ? 16 : 2), db + k * 128, 1);
                else wgmma128(acc, da + k * (BLOCKED_A ? 16 : 2), db + k * 128, 1);
            }
            wg_commit();
            if (k4 | st) {
                wg_wait<1>();
                if (elect) mbar_arrive(empty + 8 * ((st + 3) & 3));
            }
        }
    }
    wg_wait<0>();
    if (elect) mbar_arrive(empty + 8 * 3);
}

__device__ __forceinline__ uint32_t n6_a(int st) { return st < 4 ? st * G_STAGE : (2 * st - 8) * G_STAGE + 32768; }
__device__ __forceinline__ uint32_t n6_b(int st) { return st < 4 ? st * G_STAGE + 16384 : (2 * st - 7) * G_STAGE + 32768; }
__device__ __forceinline__ uint32_t n6_bar(int st) { return st < 4 ? 8 * st : 96 + 8 * st; }
__device__ __forceinline__ void mainloop6(float (&acc)[64], uint32_t sb, int wgi, uint32_t full, uint32_t empty, int& it, bool elect) {
#pragma unroll
    for (int j = 0; j < 64; j++) acc[j] = 0.f;
    int st = 0, prev = 0, r = 0;
#pragma unroll 1
    for (int kb = 0; kb < 64; kb++) {
        mbar_wait_long(full + n6_bar(st), ((st < 4 ? it >> 2 : 0) + r) & 1);
        const uint64_t da = mkdesc(sb + n6_a(st) + wgi * 8192, 128, 1024, 0), db = mkdesc(sb + n6_b(st), 8192, 1024, 1);
        wg_fence();
#pragma unroll
        for (int k = 0; k < 4; k++) wgmma128(acc, da + k * 16, db + k * 128, 1);
        wg_commit();
        if (kb) {
            wg_wait<1>();
            if (elect) mbar_arrive(empty + n6_bar(prev));
        }
        prev = st;
        if (++st == 6) { st = 0; r++; }
    }
    wg_wait<0>();
    if (elect) mbar_arrive(empty + 8 * 3);
    it += 44;
}

template <int BN>
__device__ __forceinline__ void o_item(uint32_t sb, int wgi, int wi, int lane, uint32_t full, uint32_t empty, int& it, const CUtensorMap* mout,
                                       int row0, int col0, uint32_t stgpar) {
    float acc[BN / 2];
    if constexpr (BN == 256) mainloop<BN, 64, true>(acc, sb, wgi, full, empty, it, lane == 0);
    else mainloop6(acc, sb, wgi, full, empty, it, lane == 0);
    ST((row0 >> 4) + (col0 / BN), wgi * 4 + wi, 10);
    mbar_wait(full + 104, stgpar);
    const uint32_t stg = sb + G_STG + (wgi * 4 + wi) * 4096;
    const int r = lane & 15, cu = lane >> 4;
#pragma unroll
    for (int hf = 0; hf < BN / 128; hf++) {
        if (elect()) asm volatile("cp.async.bulk.wait_group.read 0;" ::: "memory");
        __syncwarp();
#pragma unroll
        for (int j = 0; j < 8; j++) {
            const float* a = acc + hf * 64 + j * 8;
            stsm4(stg + (j >> 2) * 2048 + r * 128 + ((((j & 3) * 2 + cu) ^ (r & 7)) << 4),
                  pack_bf16(a[0], a[1]), pack_bf16(a[2], a[3]), pack_bf16(a[4], a[5]), pack_bf16(a[6], a[7]));
        }
        asm volatile("fence.proxy.async.shared::cta;" ::: "memory");
        __syncwarp();
        if (elect()) {
            tma2d_store(mout, stg, col0 + hf * 128, row0 + wgi * 64 + wi * 16);
            tma2d_store(mout, stg + 2048, col0 + hf * 128 + 64, row0 + wgi * 64 + wi * 16);
            asm volatile("cp.async.bulk.commit_group;" ::: "memory");
        }
    }
}

constexpr int S4_KD = 32768;
constexpr int S4_CH = 2 * G_STAGE;
constexpr int S4_HALF = 2304;
constexpr int S4_WD = 2 * S4_HALF;
constexpr int S4_T2 = S4_WD + 2304;
constexpr int S4_T3 = S4_T2 + 1024;
constexpr int S4_STRIDE = S4_T3 + 640 + 16;
__device__ __forceinline__ uint32_t addz(uint32_t x, uint32_t z) { uint32_t r; asm volatile("add.u32 %0, %1, %2;" : "=r"(r) : "r"(x), "r"(z)); return r; }
__device__ __forceinline__ uint32_t lds16(uint32_t a) { uint32_t v; asm volatile("ld.shared.u16 %0, [%1];" : "=r"(v) : "r"(a) : "memory"); return v; }
__device__ __forceinline__ uint32_t ldsu(uint32_t a) { return __float_as_uint(lds32(a)); }

template <int E0, int NE, int KP>
__device__ __forceinline__ void s4_windows(float (&acc)[8][2][4], uint32_t ut, uint32_t tw, int rho, int w, int lane, uint32_t z) {
    const int gt = (lane >> 2) - 2 * (lane & 3), p0 = rho == 16 ? -3 : -2, c = (lane >> 3) + p0;
    uint32_t band[2][4], ta[NE][4];
    {
        const uint64_t ones = ((uint64_t)((2u << 2 * w) - 1) << 32) >> (8 * p0 + 24 - gt + rho + w);
        uint32_t f[5];
#pragma unroll
        for (int m = 0; m < 5; m++) f[m] = ((((uint32_t)(ones >> (8 * m)) & 3) * 0x8001u) & 0x10001u) * 0x3F80u;
#pragma unroll
        for (int j = 0; j < 2; j++) { band[j][0] = f[2 * j + 1]; band[j][1] = addz(f[2 * j], z); band[j][2] = f[2 * j + 2]; band[j][3] = addz(f[2 * j + 1], z); }
    }
#pragma unroll
    for (int e = 0; e < NE; e++)
        asm volatile("ld.shared.u32 %0, [%4]; ld.shared.u32 %1, [%4+%5]; ld.volatile.shared.u32 %2, [%4+%6]; ld.volatile.shared.u32 %3, [%4];"
            : "=r"(ta[e][0]), "=r"(ta[e][1]), "=r"(ta[e][2]), "=r"(ta[e][3]) : "r"(tw + 16 * (E0 + e) * KP), "n"(8 * KP), "n"(-8 * KP) : "memory");
    const uint32_t ua = ut + (c & 1) * S4_HALF + (16 + (lane & 7) + (c >> 1)) * 16;
#pragma unroll
    for (int J = 0; J < 8 - E0; J++) {
        uint32_t u0[4], u1[4];
        ldsm4(u0, ua + J * 256); ldsm4(u1, ua + J * 256 + 128);
        float s0[4], s1[4];
        mma16z(s0, band[0], u0[0], u0[1]); mma16z(s1, band[0], u1[0], u1[1]);
        mma16(s0, band[1], u0[2], u0[3]); mma16(s1, band[1], u1[2], u1[3]);
        const uint32_t b00 = pack_bf16(s0[0], s0[1]), b01 = pack_bf16(s1[0], s1[1]), b10 = pack_bf16(s0[2], s0[3]), b11 = pack_bf16(s1[2], s1[3]);
#pragma unroll
        for (int e = 0; e < NE; e++)
            if (J + E0 + e < 8) { mma16(acc[J + E0 + e][0], ta[e], b00, b01); mma16(acc[J + E0 + e][1], ta[e], b10, b11); }
    }
}
template <int D0, int D1>
__device__ __forceinline__ void s4_dense(float (&acc)[8][2][4], uint32_t ua, const uint32_t (&b0)[4], const uint32_t (&b1)[4]) {
#pragma unroll
    for (int J = 0; J < 8 - D0; J++) {
        uint32_t a[4];
        ldsm4(a, ua + J * 256);
        mma16(acc[J + D0][0], a, b0[0], b0[1]); mma16(acc[J + D0][1], a, b0[2], b0[3]);
        if (J + D1 < 8) { mma16(acc[J + D1][0], a, b1[0], b1[1]); mma16(acc[J + D1][1], a, b1[2], b1[3]); }
    }
}
__device__ __forceinline__ void s4_words(uint32_t (&b)[4], uint32_t wd) {
    asm volatile("ld.shared.u32 %0, [%4]; ld.shared.u32 %1, [%4+-32]; ld.shared.u32 %2, [%4+32]; ld.volatile.shared.u32 %3, [%4];"
        : "=r"(b[0]), "=r"(b[1]), "=r"(b[2]), "=r"(b[3]) : "r"(wd) : "memory");
}

__device__ __forceinline__ void s4_item(uint32_t sb, int cw, int lane, int item, const bf16* __restrict__ dsk, uint32_t empty, const CUtensorMap* my, uint32_t stgpar,
                                        bf16* __restrict__ out, uint32_t nbar, uint32_t npar, uint32_t nslot) {
    const int gt = (lane >> 2) - 2 * (lane & 3);
    const uint32_t ch = sb + S4_CH + cw * S4_STRIDE, kd = sb + S4_KD + cw * 1536;
    const __nv_bfloat162 dk = __bfloat162bfloat162(dsk[item * 8 + cw]);
    ST(item, cw, 0);
    asm volatile("st.shared.v4.u32 [%0], {%1,%1,%1,%1};" ::"r"(ch + (lane >> 4) * S4_HALF + (lane & 15) * 16), "r"(0) : "memory");
    const uint32_t tch = sb + S4_CH + (lane & 7) * S4_STRIDE + ((lane >> 3) & 1) * S4_HALF + (16 + 16 * cw + (lane >> 4)) * 16;
#pragma unroll
    for (int i = 0; i < 8; i++) {
        uint32_t x[4];
        ldsm4t(x, sb + cw * 4096 + i * 512 + lane * 16);
        stsm4(tch + i * 32, x[0], x[1], x[2], x[3]);
    }
    const uint32_t k1024 = lds16(kd + 1024);
    {
        auto st4 = [](uint32_t a, uint32_t x, uint32_t y, uint32_t u, uint32_t v) {
            asm volatile("st.shared.v4.u32 [%0], {%1,%2,%3,%4};" ::"r"(a), "r"(x), "r"(y), "r"(u), "r"(v) : "memory");
        };
        const float4 p = lds128(kd + lane * 16);
        const uint32_t p0 = __float_as_uint(p.x), p1 = __float_as_uint(p.y), p2 = __float_as_uint(p.z), p3 = __float_as_uint(p.w);
        const uint32_t pm = lane ? ldsu(kd + lane * 16 - 4) : 0;
        const uint32_t wa = ch + S4_WD + 64 + lane * 32;
        st4(wa, __byte_perm(p0, pm, 0x7610), __byte_perm(p0, 0, 0x1032), __byte_perm(p1, p0, 0x7610), __byte_perm(p1, 0, 0x1032));
        st4(wa + 16, __byte_perm(p2, p1, 0x7610), __byte_perm(p2, 0, 0x1032), __byte_perm(p3, p2, 0x7610), __byte_perm(p3, 0, 0x1032));
        const float2 q = lds64(kd + 512 + lane * 8);
        const uint32_t q0 = __float_as_uint(q.x), q1 = __float_as_uint(q.y), q2 = ldsu(kd + 520 + lane * 8), k255 = ldsu(kd + 508);
        st4(wa + 1024, lane ? __byte_perm(q0, 0, 0x1010) : __byte_perm(q0, k255, 0x7610), __byte_perm(q0, 0, 0x1010), __byte_perm(q0, 0, 0x1032), __byte_perm(q1, q0, 0x7610));
        st4(wa + 1040, __byte_perm(q1, 0, 0x1010), __byte_perm(q1, 0, 0x1010), __byte_perm(q1, 0, 0x1032), __byte_perm(q2, q1, 0x7610));
        const uint32_t k512 = lane == 4 ? lds16(kd + 768) : 0;
        if (lane < 16) st4(ch + S4_WD + (lane < 4 ? 0 : 2048) + lane * 16, k512 * 0x10001u, k512 * 0x10001u, k512 * 0x10001u, k512 << 16);
        const float2 c = lds64(kd + 768 + lane * 8), d = lds64(kd + 760 + lane * 8);
        const uint32_t c0 = __float_as_uint(c.x), c1 = __float_as_uint(c.y), c2 = ldsu(kd + 776 + lane * 8);
        const uint32_t d0 = lane ? __float_as_uint(d.x) : 0, d1 = lane ? __float_as_uint(d.y) : 0, d2 = lane ? c0 : 0;
        st4(ch + S4_T2 + 256 + lane * 16, __byte_perm(c0, d0, 0x7632), __byte_perm(c1, d1, 0x5410), __byte_perm(c1, d1, 0x7632), __byte_perm(c2, d2, 0x5410));
        const uint32_t m = lane == 31 ? 0xFFFF0000u : 0;
        st4(ch + S4_T2 + (lane < 16 ? lane : lane == 31 ? 48 : lane + 33) * 16, c0 & m, (c1 << 16) & m, c1 & m, (c2 << 16) & m);
        const float2 e = lds64(kd + 1024 + lane * 8);
        const uint32_t e0 = __float_as_uint(e.x), e1 = __float_as_uint(e.y), e2 = ldsu(kd + 1032 + lane * 8), em = ldsu(kd + 1020 + lane * 8);
        st4(ch + S4_T3 + 128 + lane * 16, __byte_perm(e0, lane ? em : 0, 0x7632), __byte_perm(e1, lane ? e0 : 0, 0x5410), __byte_perm(e1, e0, 0x7632), __byte_perm(e2, e1, 0x5410));
        if (lane < 8) st4(ch + S4_T3 + lane * 16, 0, 0, 0, 0);
    }
    bar_sync(2, 256);
    ST(item, cw, 1);
    const uint32_t z = ldsu(ch);
    float acc[8][2][4];
#pragma unroll
    for (int j = 0; j < 16; j++) acc[j >> 1][j & 1][0] = acc[j >> 1][j & 1][1] = acc[j >> 1][j & 1][2] = acc[j >> 1][j & 1][3] = 0.f;
#pragma unroll 1
    for (int r = 1; r <= 4; r++) s4_windows<2, 3, 16>(acc, ch, ch + S4_T2 + (gt - 16) * 16 + 4 * r - 4, 4 * r, 2 - (r & 1), lane, z);
    ST(item, cw, 2);
#pragma unroll 1
    for (int r = 1; r <= 2; r++) s4_windows<4, 4, 8>(acc, ch, ch + S4_T3 + (gt - 48) * 8 + 4 * r - 4, 8 * r, 2 + r, lane, z);
    ST(item, cw, 3);
    const uint32_t ua = ch + (lane >> 4) * S4_HALF + (16 + (lane & 15)) * 16, wd = ch + S4_WD + 64 + gt * 4;
#pragma unroll 1
    for (int q = 0; q < 2; q++) {
        uint32_t b0[4], b1[4];
        s4_words(b0, wd + (q + 32) * 64);
#pragma unroll
        for (int j = 0; j < 4; j++) {
            const int x = 16 * q + gt + (j == 1 ? -8 : j == 2 ? 8 : 0) - 3;
            b1[j] = addz(((unsigned)x < 2u ? k1024 : 0u) | ((unsigned)(x - 1) < 2u ? k1024 << 16 : 0u), z);
        }
        s4_dense<2, 4>(acc, ua - q * 16, b0, b1);
    }
    {
        uint32_t b0[4], b1[4], c0[4], c1[4];
        s4_words(b0, wd); s4_words(b1, wd + 1024);
#pragma unroll 1
        for (int q = 0; q < 16; q += 2) {
            s4_words(c0, wd + q * 64 + 64); s4_words(c1, wd + q * 64 + 64 + 1024);
            s4_dense<0, 1>(acc, ua - q * 16, b0, b1);
            s4_words(b0, wd + q * 64 + 128); s4_words(b1, wd + q * 64 + 128 + 1024);
            s4_dense<0, 1>(acc, ua - q * 16 - 16, c0, c1);
            if (q == S4REL && lane == 0) { mbar_arrive(empty); mbar_arrive(empty + 8); }
        }
    }
    ST(item, cw, 4);
    mbar_wait(empty + 72, stgpar);
    if (elect()) asm volatile("cp.async.bulk.wait_group.read 0;" ::: "memory");
    __syncwarp();
#pragma unroll
    for (int I = 0; I < 8; I++) {
        uint32_t u[4];
        ldsm4(u, ua + I * 256);
#pragma unroll
        for (int j = 0; j < 4; j++) {
            const uint32_t y = pack_bf16(acc[I][j >> 1][2 * (j & 1)], acc[I][j >> 1][2 * (j & 1) + 1]);
            const __nv_bfloat162 r = __hadd2_rn(*(const __nv_bfloat162*)&y, __hmul2_rn(*(const __nv_bfloat162*)&u[j], dk));
            u[j] = *(const uint32_t*)&r;
        }
        stsm4(ua + I * 256, u[0], u[1], u[2], u[3]);
    }
    bar_sync(2, 256);
    uint32_t y[8][4];
#pragma unroll
    for (int i = 0; i < 8; i++) ldsm4t(y[i], tch + i * 32);
    if (cw < S4DIR && mbar_test(nbar, npar) && ldsu(nslot) == (IT_END << 16)) {
        uint32_t* const dst = (uint32_t*)(out + (size_t)(cw * 256 + (lane >> 2)) * (2 * DM) + DM + item * 8) + (lane & 3);
#pragma unroll
        for (int i = 0; i < 32; i++) dst[i * 8 * DM] = y[i >> 2][i & 3];
        return;
    }
#pragma unroll
    for (int i = 0; i < 8; i++) stsm4(sb + G_STG + cw * 4096 + i * 512 + lane * 16, y[i][0], y[i][1], y[i][2], y[i][3]);
    asm volatile("fence.proxy.async.shared::cta;" ::: "memory");
    __syncwarp();
    if (elect()) {
        mbar_arrive(empty + 16); mbar_arrive(empty + 24);
        tma2d_store(my, sb + G_STG + cw * 4096, DM + item * 8, cw * 256);
        asm volatile("cp.async.bulk.commit_group;" ::: "memory");
    }
    ST(item, cw, 5);
}

struct Maps { CUtensorMap m[13]; };
__global__ void __launch_bounds__(384, 1)
worker_kernel(const __grid_constant__ Maps M, const bf16* __restrict__ dsk, bf16* __restrict__ out) {
    const CUtensorMap &mx = M.m[0], &mq = M.m[1], &mo = M.m[4], &mout = M.m[5], &mu = M.m[6], &my = M.m[7];
    extern __shared__ unsigned char smem_raw[];
    const uint32_t sb = (smem_u32(smem_raw) + 1023) & ~1023u;
    const uint32_t full = sb + G_BAR, empty = full + 32, ifull = full + 64, iempty = full + 80, islot = full + 96, stgbar = full + 104, sigbar = full + 112, sigslot = full + 120;
    const int tid = threadIdx.x, wg = tid >> 7, lane = tid & 31;
    int q0 = blockIdx.x;
    const int nfirst = min(32, (int)gridDim.x - 96), wide0 = q0 - ((int)gridDim.x - O_WIDE * 4);
    if (tid == 0 && q0 >= nfirst && wide0 < 0) q0 = nfirst + atomicAdd(g_ctr + C_NEXT, 1);
    if ((tid >> 5) == 1 && elect()) {
#pragma unroll
        for (int i = 0; i < 6; i++) { mbar_init(full + n6_bar(i), 1); mbar_init(empty + n6_bar(i), 8); }
#pragma unroll
        for (int i = 0; i < 2; i++) { mbar_init(ifull + 8 * i, 1); mbar_init(iempty + 8 * i, 8); }
        mbar_init(sigbar, 8); mbar_init(stgbar, 1);
        asm volatile("fence.mbarrier_init.release.cluster;" ::: "memory");
    }
    if ((tid >> 5) == 2 && elect()) {
#pragma unroll
        for (int i = 0; i < 13; i++) asm volatile("prefetch.tensormap [%0];" ::"l"(&M.m[i]) : "memory");
    }
    __syncthreads();
    if (wg == 0) {
        reg_dec<40>();
        if (tid >= 32 && tid < 64) {
            for (int n = 0;; n++) {
                mbar_wait_long(sigbar, n & 1);
                int item; asm volatile("ld.shared.u32 %0, [%1];" : "=r"(item) : "r"(sigslot + 4 * (n & 1)) : "memory");
                const int type = item >> 16, b = (item >> 8) & 255, i = item & 255;
                if (type == IT_END) break;
                if (type == IT_QA) {
                    if (elect()) {
#pragma unroll
                        for (int j = 0; j < 8; j++) {
                            const uint32_t src = sb + (j >= 4 ? G_STG + (j & 1) * 16384 : 3 * G_STAGE + (j & 1) * 20480) + ((j >> 1) & 1) * 8192;
                            asm volatile("cp.async.bulk.global.shared::cta.bulk_group [%0], [%1], 8192;"
                                ::"l"(g_ox + (size_t)(b * 64 + i * 4 + ((j >> 1) ^ 2)) * 8192 + (j & 1) * 4096), "r"(src) : "memory");
                            if ((j & 3) == 3) asm volatile("cp.async.bulk.commit_group;" ::: "memory");
                        }
                        asm volatile("cp.async.bulk.wait_group.read 1;" ::: "memory");
                        asm volatile("mbarrier.arrive.shared.b64 _, [%0], 8;" ::"r"(empty + 24) : "memory");
                        asm volatile("cp.async.bulk.wait_group 0;" ::: "memory");
                        mbar_arrive(stgbar);
                        asm volatile("fence.proxy.async.global;" ::: "memory");
                    }
                    __syncwarp();
                }
                if (type == IT_KV) { if (lane < 6) red_release(g_kvf + ((i & 15) * 6 + lane) * 16 + b, 1); }
                else if (lane == 0) red_release(g_ctr + C_QA_DONE + b, 1 << i);
            }
        } else if (tid < 32) {
            int it = 0;
            bool tables = false;
            if (!KVN) asm volatile("griddepcontrol.wait;" ::: "memory");
            for (int n = 0;; n++) {
                int item = 0;
                if (lane == 0) {
                    if (n) q0 = nfirst + atomicAdd(g_ctr + C_NEXT, 1);
                    item = n == 0 && wide0 >= 0 ? (IT_O << 16) | ((wide0 >> 2) << 8) | (wide0 & 3) : queue_item(q0);
                }
                item = __shfl_sync(0xffffffffu, item, 0);
                mbar_wait(iempty + 8 * (n & 1), ((n >> 1) & 1) ^ 1);
                if (lane == 0) {
                    asm volatile("st.shared.u32 [%0], %1;" ::"r"(islot + 4 * (n & 1)), "r"(item) : "memory");
                    mbar_arrive(ifull + 8 * (n & 1));
                }
                const int type = item >> 16, b = (item >> 8) & 255, i = item & 255;
                bool ready = false;
                if (type == IT_QA || type == IT_KV) {
                    const CUtensorMap* mw = &mq + (type == IT_QA ? 0 : 1 + (i >> 4));
#pragma unroll 1
                    for (int kb = 0; kb < 16; kb++, it++) {
                        const int st = it & 3;
                        mbar_wait(empty + 8 * st, ((it >> 2) & 1) ^ 1);
                        if (elect()) {
                            mbar_expect(full + 8 * st, G_STAGE);
                            tma2d(sb + st * G_STAGE, &mx, kb * 64, b * 128, full + 8 * st);
                            tma3d(sb + st * G_STAGE + 16384, mw, 0, kb * 64, (i & 15) * 4, full + 8 * st);
                        }
                        if (type == IT_QA && kb == 3) ready = __all_sync(0xffffffffu, ld_acq(g_ctr + C_CHAIN + b) >= 96);
                        if (ready && kb < 11 && elect()) {
                            const size_t sh = (b * 4 + ((kb - 3) & 3)) * NH + i * 2;
                            asm volatile("cp.async.bulk.prefetch.L2.global [%0], 16384;" ::"l"((kb >= 7 ? g_vx : g_kx) + sh * 4096) : "memory");
                            asm volatile("cp.async.bulk.prefetch.L2.global [%0], 4096;" ::"l"((kb >= 7 ? g_vm : g_km) + sh * 1024) : "memory");
                        }
                    }
                }
                if (type == IT_QA) {
                    if (b == 15) asm volatile("griddepcontrol.wait;" ::: "memory");
                    else if (!ready) wait_ctr(g_ctr + C_CHAIN + b, 96);
                    tables = true;
                    asm volatile("fence.proxy.async.global;" ::: "memory");
#pragma unroll 1
                    for (int st = 0; st < 4; st++, it++) {
                        mbar_wait(empty + 8 * st, ((it >> 2) & 1) ^ 1);
                        if (elect()) {
                            mbar_expect(full + 8 * st, 4 * 10240);
#pragma unroll
                            for (int j = 0; j < 4; j++)
                                tma3d(sb + st * G_STAGE + (j >> 1) * 20480 + (j & 1) * 16384, &M.m[8 + (st >> 1) + (j & 1) * 2], 0, b * 4 + (j & 2),
                                      (i * 2 + (st & 1)) * 16, full + 8 * st);
                        }
                    }
                } else if (type == IT_O) {
                    const bool wide = b < O_WIDE;
                    const CUtensorMap* mw = wide ? &mo : &M.m[12];
                    int done = 0;
                    const int ns = wide ? 4 : 6;
#pragma unroll 1
                    for (int kb = 0, st = 0, r = 0; kb < 64; kb++) {
                        const uint32_t bo = n6_bar(st);
                        mbar_wait(empty + bo, (((st < 4 ? it >> 2 : 0) + r) & 1) ^ 1);
                        if (elect()) {
                            mbar_expect(full + bo, wide ? G_STAGE : 32768);
                            tma3d(sb + n6_b(st), mw, 0, kb * 64, wide ? i * 4 : i * 2, full + bo);
                        }
                        if (!(done >> (kb >> 2) & 1)) {
#pragma unroll 1
                            for (int sp = 0; sp < (1 << 20) && !((done = __shfl_sync(0xffffffffu, ld_acq(g_ctr + C_QA_DONE + b), 0)) >> (kb >> 2) & 1); sp++)
                                __nanosleep(64);
                            asm volatile("fence.proxy.async.global;" ::: "memory");
                        }
                        if (elect()) bulk_load(sb + n6_a(st), g_ox + (size_t)(b * 64 + kb) * 8192, 16384, full + bo);
                        if (++st == ns) { st = 0; r++; }
                    }
                    it += wide ? 64 : 44;
                } else if (type == IT_S4) {
                    mbar_wait(empty, ((it >> 2) & 1) ^ 1);
                    if (elect()) {
                        mbar_expect(full, 32768 + 12288);
#pragma unroll
                        for (int j = 0; j < 8; j++) tma2d(sb + j * 4096, &mu, i * 8, j * 256, full);
                    }
                    if (!tables) { wait_ctr(g_ctr + C_CHAIN, 96); asm volatile("fence.proxy.async.global;" ::: "memory"); }
                    tables = true;
                    if (elect()) bulk_load(sb + S4_KD, g_kd + i * 8 * 768, 12288, full);
#pragma unroll 1
                    for (int st = 1; st < 4; st++) { mbar_wait(empty + 8 * st, ((it >> 2) & 1) ^ 1); if (lane == 0) mbar_arrive(full + 8 * st); }
                    it += 4;
                    mbar_wait_long(empty, ((it >> 2) & 1) ^ 1);
                }
                if (item >> 16 == IT_END) break;
            }
            asm volatile("griddepcontrol.wait;" ::: "memory");
        }
    } else {
        reg_inc<232>();
        const int wu = __shfl_sync(0xffffffffu, tid >> 5, 0);
        const int wgi = (wu >> 2) - 1, wi = wu & 3;
        int it = 0, nqa = 0, nsig = 0, n = 0, item;
        auto next_item = [&]() {
            mbar_wait_long(ifull + 8 * (n & 1), (n >> 1) & 1);
            asm volatile("ld.shared.u32 %0, [%1];" : "=r"(item) : "r"(islot + 4 * (n & 1)) : "memory");
            __syncwarp();
            if (lane == 0) mbar_arrive(iempty + 8 * (n & 1));
        };
        auto signal = [&](int what) {
            if (tid == 128) asm volatile("st.shared.u32 [%0], %1;" ::"r"(sigslot + 4 * (nsig & 1)), "r"(what) : "memory");
            __syncwarp();
            if (lane == 0) mbar_arrive(sigbar);
            nsig++;
        };
        next_item();
        if (item >> 16 == IT_KV) {
            float acc[128];
            uint32_t pk[64];
            uint32_t* dst = nullptr;
            int prev = 0;
            do {
                WLOG(0);
#pragma unroll
                for (int kb = 0; kb < 16; kb++, it++) {
                    const int st = kb & 3;
                    mbar_wait(full + 8 * st, (it >> 2) & 1);
                    const uint64_t da = mkdesc(sb + st * G_STAGE + wgi * 8192, 16, 1024, 1);
                    const uint64_t db = mkdesc(sb + st * G_STAGE + 16384, 8192, 1024, 1);
                    wg_fence();
#pragma unroll
                    for (int k = 0; k < 4; k++) wgmma256(acc, da + k * 2, db + k * 128, kb | k);
                    wg_commit();
                    if (n <= KVI) {
                        if (kb < KVF && dst) {
#pragma unroll
                            for (int j = kb * (64 / KVF); j < (kb + 1) * (64 / KVF); j++) st_out(dst + (j >> 1) * 128 + (j & 1) * 32, pk[j]);
                            if (kb == KVF - 1) signal(prev);
                        }
                    } else if (kb < KVS) {
#pragma unroll
                        for (int j = kb * (64 / KVS); j < (kb + 1) * (64 / KVS); j++) st_out(dst + (j >> 1) * 128 + (j & 1) * 32, pk[j]);
                        if (kb == KVS - 1) signal(prev);
                    }
                    if (kb > 0) {
                        wg_wait<1>();
                        if (lane == 0) mbar_arrive(empty + 8 * ((kb - 1) & 3));
                    }
                }
                wg_wait<0>();
                if (lane == 0) mbar_arrive(empty + 8 * 3);
#pragma unroll
                for (int j = 0; j < 64; j++) pk[j] = pack_bf16(acc[2 * j], acc[2 * j + 1]);
                const int row = ((item >> 8) & 255) * 128 + wgi * 64 + wi * 16, nt = item & 255;
                dst = (uint32_t*)(nt < 16 ? g_kx : g_vx) + (size_t)((row >> 5) * 512 + (nt & 15) * 32) * 128 + (row & 31) * 4 + lane;
                prev = item;
                WLOG(1);
                n++;
                next_item();
            } while (item >> 16 == IT_KV);
            if (dst) {
#pragma unroll
                for (int j = 0; j < 64; j++) dst[(j >> 1) * 128 + (j & 1) * 32] = pk[j];
                signal(prev);
            }
        }
        for (;; n++, next_item()) {
            const int type = item >> 16, b = (item >> 8) & 255, i = item & 255;
            const int lane = (tid & 31) + (item >> 24), wgi = (wu >> 2) - 1 + __shfl_sync(0xffffffffu, item >> 24, 0), wi = wu & 3;
            WLOG(0);
            if (type == IT_QA) {
                float acc[128];
                ST(sid, cw, 0);
                ST(sid, cw, 1);
                mainloop<256, 16, false>(acc, sb, wgi, full, empty, it, lane == 0);
                ST(sid, cw, 2);
                uint32_t q0[32], q1[32];
#pragma unroll
                for (int j = 0; j < 32; j++) q0[j] = pack_bf16(acc[2 * j], acc[2 * j + 1]);
                const uint32_t par = (it >> 2) & 1, so = sb + wgi * 20480;
                float sx[2][32] = {}, sm[2][8] = {};
                uint32_t p[2][20];
                mbar_wait_long(full, par);
                ST(sid, cw, 3);
                if (PING && wgi == 0) bar_sync(5, 256);
                attn_scores(sx[0], sm[0], q0, so);
                ST(sid, cw, 7);
#pragma unroll
                for (int j = 0; j < 32; j++) asm volatile("cvt.rn.bf16x2.f32 %0, %1, %2;" : "=r"(q1[j]) : "f"(acc[65 + 2 * j]), "f"(acc[64 + 2 * j]));
                mbar_wait(full + 8, par);
                attn_scores(sx[1], sm[1], q1, so + G_STAGE);
                if (PING && wgi == 1) bar_arrive(5, 256);
                if (elect()) asm volatile("cp.async.bulk.wait_group.read 0;" ::: "memory");
                mbar_wait(stgbar, (nqa++ & 1) ^ 1);
                bar_sync(3 + wgi, 128);
                float o0[64] = {}, o1[64] = {};
                wg_wait<0>();
                ST(sid, cw, 9);
                if (lane == 0) { mbar_arrive(empty); mbar_arrive(empty + 8); }
                if (wi & 1) attn_softmax<true>(p, sx, sm, wi >= 2, lane);
                else attn_softmax<false>(p, sx, sm, wi >= 2, lane);
                ST(sid, cw, 10);
                mbar_wait(full + 16, par);
                attn_pv(o0, p[0], so + 2 * G_STAGE);
                mbar_wait(full + 24, par);
                attn_pv(o1, p[1], so + 3 * G_STAGE);
                wg_wait<1>();
                if (lane == 0) mbar_arrive(empty + 16);
                ST(sid, cw, 5);
                const uint32_t da = (wi * 2 + ((lane >> 3) & 1)) * 1024 + (lane >> 4) * 128 + (lane & 7) * 16;
                attn_stage(o0, sb + G_STG + wgi * 16384 + da);
                wg_wait<0>();
                bar_sync(3 + wgi, 128);
                attn_stage(o1, so + 3 * G_STAGE + da);
                asm volatile("fence.proxy.async.shared::cta;" ::: "memory");
                ST(sid, cw, 6);
                signal(item);
                it += 4;
            } else if (type == IT_O) {
                ST(b * 8 + i, wgi * 4 + wi, 8);
                mbar_wait_long(full, (it >> 2) & 1);
                ST(b * 8 + i, wgi * 4 + wi, 9);
                if (b < O_WIDE) o_item<256>(sb, wgi, wi, lane, full, empty, it, &mout, b * 128, i * 256, (nqa & 1) ^ 1);
                else o_item<128>(sb, wgi, wi, lane, full, empty, it, &mout, b * 128, i * 128, (nqa & 1) ^ 1);
            } else if (type == IT_S4) {
                mbar_wait_long(full, (it >> 2) & 1);
                mbar_wait(full + 24, (it >> 2) & 1);
                s4_item(sb, wgi * 4 + wi, lane, i, dsk, empty, &my, (nqa & 1) ^ 1, out, ifull + 8 * ((n + 1) & 1), ((n + 1) >> 1) & 1, islot + 4 * ((n + 1) & 1));
                it += 4;
            } else break;
            WLOG(1);
        }
        bar_sync(2, 256);
        signal(item);
        if (elect()) asm volatile("cp.async.bulk.wait_group 0;" ::: "memory");
    }
}

typedef CUresult (*EncodeFn)(CUtensorMap*, CUtensorMapDataType, cuuint32_t, void*, const cuuint64_t*, const cuuint64_t*, const cuuint32_t*,
                             const cuuint32_t*, CUtensorMapInterleave, CUtensorMapSwizzle, CUtensorMapL2promotion, CUtensorMapFloatOOBfill);
static EncodeFn get_encode() {
    void* fn = nullptr; cudaDriverEntryPointQueryResult st;
    cudaGetDriverEntryPoint("cuTensorMapEncodeTiled", &fn, cudaEnableDefault, &st);
    return (EncodeFn)fn;
}
static void map_act(EncodeFn enc, CUtensorMap* m, const void* p, int rows, int cols, int boxr) {
    cuuint64_t dim[2] = {(cuuint64_t)cols, (cuuint64_t)rows}, str[1] = {(cuuint64_t)cols * 2};
    cuuint32_t box[2] = {64, (cuuint32_t)boxr}, es[2] = {1, 1};
    enc(m, CU_TENSOR_MAP_DATA_TYPE_BFLOAT16, 2, (void*)p, dim, str, box, es, CU_TENSOR_MAP_INTERLEAVE_NONE, CU_TENSOR_MAP_SWIZZLE_128B,
        CU_TENSOR_MAP_L2_PROMOTION_L2_128B, CU_TENSOR_MAP_FLOAT_OOB_FILL_NONE);
}
static void map_w(EncodeFn enc, CUtensorMap* m, const void* p, int k, int n, int groups = 4) {
    cuuint64_t dim[3] = {64, (cuuint64_t)k, (cuuint64_t)n / 64}, str[2] = {(cuuint64_t)n * 2, 128};
    cuuint32_t box[3] = {64, 64, (cuuint32_t)groups}, es[3] = {1, 1, 1};
    enc(m, CU_TENSOR_MAP_DATA_TYPE_BFLOAT16, 3, (void*)p, dim, str, box, es, CU_TENSOR_MAP_INTERLEAVE_NONE, CU_TENSOR_MAP_SWIZZLE_128B,
        CU_TENSOR_MAP_L2_PROMOTION_L2_256B, CU_TENSOR_MAP_FLOAT_OOB_FILL_NONE);
}

static void map_kv(EncodeFn enc, CUtensorMap* m, void* p, int n) {
    cuuint64_t dim[3] = {(cuuint64_t)n, NSEG, 512}, str[2] = {(cuuint64_t)n * 1024, (cuuint64_t)n * 2};
    cuuint32_t box[3] = {(cuuint32_t)n, 2, 16}, es[3] = {1, 1, 1};
    enc(m, CU_TENSOR_MAP_DATA_TYPE_BFLOAT16, 3, p, dim, str, box, es, CU_TENSOR_MAP_INTERLEAVE_NONE, CU_TENSOR_MAP_SWIZZLE_NONE,
        CU_TENSOR_MAP_L2_PROMOTION_NONE, CU_TENSOR_MAP_FLOAT_OOB_FILL_NONE);
}
static void map_box(EncodeFn enc, CUtensorMap* m, const void* p, int rows, int ld, int boxc, int boxr, CUtensorMapSwizzle sw,
                    CUtensorMapL2promotion promo = CU_TENSOR_MAP_L2_PROMOTION_NONE) {
    cuuint64_t dim[2] = {(cuuint64_t)ld, (cuuint64_t)rows}, str[1] = {(cuuint64_t)ld * 2};
    cuuint32_t box[2] = {(cuuint32_t)boxc, (cuuint32_t)boxr}, es[2] = {1, 1};
    enc(m, CU_TENSOR_MAP_DATA_TYPE_BFLOAT16, 2, (void*)p, dim, str, box, es, CU_TENSOR_MAP_INTERLEAVE_NONE, sw,
        promo, CU_TENSOR_MAP_FLOAT_OOB_FILL_NONE);
}

extern "C" void kernel_launch(void* const* d_in, const int* in_sizes, int n_in, void* d_out, int out_size) {
    const bf16* x = (const bf16*)d_in[0];
    const bf16* mem0 = (const bf16*)d_in[1];
    const bf16 *Wq = (const bf16*)d_in[2], *Wk = (const bf16*)d_in[3], *Wv = (const bf16*)d_in[4], *Wo = (const bf16*)d_in[5];
    static EncodeFn enc = nullptr;
    static int nsm = 0;
    static void* kv[4];
    if (!enc) {
        enc = get_encode();
        cudaGetSymbolAddress(&kv[0], g_kx); cudaGetSymbolAddress(&kv[1], g_vx); cudaGetSymbolAddress(&kv[2], g_km); cudaGetSymbolAddress(&kv[3], g_vm);
        cudaDeviceGetAttribute(&nsm, cudaDevAttrMultiProcessorCount, 0);
        cudaFuncSetAttribute(chain_kernel, cudaFuncAttributeMaxDynamicSharedMemorySize, CH_SMEM);
        cudaFuncSetAttribute(worker_kernel, cudaFuncAttributeMaxDynamicSharedMemorySize, G_SMEM);
    }
    Maps M;
    CUtensorMap &mx = M.m[0], &mq = M.m[1], &mk = M.m[2], &mv = M.m[3], &mo = M.m[4], &mout = M.m[5], &mu = M.m[6], &my = M.m[7];
    map_act(enc, &mx, x, S_LEN, DM, 128);
    map_w(enc, &mq, Wq, DM, HD); map_w(enc, &mk, Wk, DM, HD); map_w(enc, &mv, Wv, DM, HD); map_w(enc, &mo, Wo, HD, DM);
    map_w(enc, &M.m[12], Wo, HD, DM, 2);
    map_box(enc, &mout, d_out, S_LEN, 2 * DM, 64, 16, CU_TENSOR_MAP_SWIZZLE_128B);
    map_box(enc, &mu, d_in[7], S_LEN, DM, 8, 256, CU_TENSOR_MAP_SWIZZLE_NONE, (CUtensorMapL2promotion)PROMU);
    map_box(enc, &my, d_out, S_LEN, 2 * DM, 8, 256, CU_TENSOR_MAP_SWIZZLE_NONE);
    for (int i = 0; i < 4; i++) map_kv(enc, &M.m[8 + i], kv[i], i < 2 ? 256 : 64);
    CUtensorMap cq, ck, cv, co;
    map_box(enc, &cq, Wq, DM, HD, 32, 32, CU_TENSOR_MAP_SWIZZLE_64B, (CUtensorMapL2promotion)PROMO); map_box(enc, &ck, Wk, DM, HD, 32, 32, CU_TENSOR_MAP_SWIZZLE_64B, (CUtensorMapL2promotion)PROMO);
    map_box(enc, &cv, Wv, DM, HD, 32, 32, CU_TENSOR_MAP_SWIZZLE_64B, (CUtensorMapL2promotion)PROMO); map_box(enc, &co, Wo, HD, DM, 32, 16, CU_TENSOR_MAP_SWIZZLE_64B, (CUtensorMapL2promotion)PROMO);
    S4Params P = {(const bf16*)d_in[8], (const bf16*)d_in[9], (const bf16*)d_in[10], (const bf16*)d_in[11],
                  (const bf16*)d_in[12], (const bf16*)d_in[13], (const bf16*)d_in[14], (const bf16*)d_in[15]};
    int aware = 1;
    cudaLaunchAttribute at[1];
    at[0].id = cudaLaunchAttributeProgrammaticStreamSerialization;
    at[0].val.programmaticStreamSerializationAllowed = 1;
    cudaLaunchConfig_t cfg = {};
    cfg.stream = cudaStreamPerThread;
    cfg.gridDim = dim3(96); cfg.blockDim = dim3(CH_THREADS); cfg.dynamicSmemBytes = CH_SMEM;
    cudaLaunchKernelEx(&cfg, chain_kernel, cq, ck, cv, co, Wq, Wk, Wv, mem0, P, aware);
    cfg.attrs = at; cfg.numAttrs = 1;
    cfg.gridDim = dim3(nsm); cfg.blockDim = dim3(384); cfg.dynamicSmemBytes = G_SMEM;
    cudaLaunchKernelEx(&cfg, worker_kernel, M, P.dsk, (bf16*)d_out);
}
```

```cpp
#include <cuda.h>
#include <cuda_runtime.h>
#include <cuda_bf16.h>
#include <stdint.h>
#include <stdio.h>
#include <string.h>

typedef __nv_bfloat16 bf16;

constexpr int S_LEN = 2048, DM = 1024, NH = 32, DH = 128, HD = 4096, NSEG = 64;
constexpr uint32_t SENT = 0xFFFFFFFFu;
constexpr int SPIN_LIMIT = 1 << 18;
#define REALL 0

__device__ __align__(1024) bf16 g_kx[S_LEN * HD];
__device__ __align__(1024) bf16 g_vx[S_LEN * HD];
__device__ __align__(1024) bf16 g_ox[S_LEN * HD];
__device__ __align__(1024) bf16 g_km[NSEG * NH * 8 * DH];
__device__ __align__(1024) bf16 g_vm[NSEG * NH * 8 * DH];
__device__ __align__(1024) bf16 g_kd[DM * 768 + 8192];
__device__ __align__(1024) char g_ring[2 << 20];
__device__ int g_kvf[96 * 16];
constexpr int C_NEXT = 0, C_CHAIN = 32, C_QA_DONE = 64, N_CTR = 96;
__device__ int g_ctr[N_CTR];

__device__ __forceinline__ uint32_t smem_u32(const void* p) { return (uint32_t)__cvta_generic_to_shared(p); }
__device__ __forceinline__ uint32_t clk() { uint32_t c; asm volatile("mov.u32 %0, %%clock;" : "=r"(c)::"memory"); return c; }
__device__ __forceinline__ uint32_t pack_bf16(float lo, float hi) {
    uint32_t r; asm("cvt.rn.bf16x2.f32 %0, %1, %2;" : "=r"(r) : "f"(hi), "f"(lo)); return r;
}
__device__ __forceinline__ uint32_t movm(uint32_t a) {
    uint32_t d; asm volatile("movmatrix.sync.aligned.m8n8.trans.b16 %0, %1;" : "=r"(d) : "r"(a)); return d;
}
__device__ __forceinline__ void mma16(float (&d)[4], const uint32_t (&a)[4], uint32_t b0, uint32_t b1) {
    asm volatile("mma.sync.aligned.m16n8k16.row.col.f32.bf16.bf16.f32 {%0,%1,%2,%3}, {%4,%5,%6,%7}, {%8,%9}, {%0,%1,%2,%3};"
        : "+f"(d[0]), "+f"(d[1]), "+f"(d[2]), "+f"(d[3]) : "r"(a[0]), "r"(a[1]), "r"(a[2]), "r"(a[3]), "r"(b0), "r"(b1));
}
__device__ __forceinline__ void mma16z(float (&d)[4], const uint32_t (&a)[4], uint32_t b0, uint32_t b1) {
    asm volatile("mma.sync.aligned.m16n8k16.row.col.f32.bf16.bf16.f32 {%0,%1,%2,%3}, {%4,%5,%6,%7}, {%8,%9}, {%10,%10,%10,%10};"
        : "=f"(d[0]), "=f"(d[1]), "=f"(d[2]), "=f"(d[3]) : "r"(a[0]), "r"(a[1]), "r"(a[2]), "r"(a[3]), "r"(b0), "r"(b1), "f"(0.f));
}
__device__ __forceinline__ void mma8z(float (&d)[4], uint32_t a0, uint32_t a1, uint32_t b0) {
    asm volatile("mma.sync.aligned.m16n8k8.row.col.f32.bf16.bf16.f32 {%0,%1,%2,%3}, {%4,%5}, {%6}, {%7,%7,%7,%7};"
        : "=f"(d[0]), "=f"(d[1]), "=f"(d[2]), "=f"(d[3]) : "r"(a0), "r"(a1), "r"(b0), "f"(0.f));
}
__device__ __forceinline__ void ldsm4t(uint32_t (&r)[4], uint32_t addr) {
    asm volatile("ldmatrix.sync.aligned.m8n8.x4.trans.shared.b16 {%0,%1,%2,%3}, [%4];"
        : "=r"(r[0]), "=r"(r[1]), "=r"(r[2]), "=r"(r[3]) : "r"(addr) : "memory");
}
__device__ __forceinline__ void ldsm4(uint32_t (&r)[4], uint32_t addr) {
    asm volatile("ldmatrix.sync.aligned.m8n8.x4.shared.b16 {%0,%1,%2,%3}, [%4];"
        : "=r"(r[0]), "=r"(r[1]), "=r"(r[2]), "=r"(r[3]) : "r"(addr) : "memory");
}
__device__ __forceinline__ float lds32(uint32_t a) {
    float v; asm volatile("ld.shared.f32 %0, [%1];" : "=f"(v) : "r"(a) : "memory"); return v;
}
__device__ __forceinline__ void st_async1(uint32_t dst, float v, uint32_t bar) {
    asm volatile("st.async.shared::cluster.mbarrier::complete_tx::bytes.f32 [%0], %1, [%2];" ::"r"(dst), "f"(v), "r"(bar) : "memory");
}
__device__ __forceinline__ void st_async2(uint32_t dst, float x, float y, uint32_t bar) {
    asm volatile("st.async.shared::cluster.mbarrier::complete_tx::bytes.v2.f32 [%0], {%1,%2}, [%3];" ::"r"(dst), "f"(x), "f"(y), "r"(bar) : "memory");
}
__device__ __forceinline__ void mma8(float (&d)[4], uint32_t a0, uint32_t a1, uint32_t b0) {
    asm volatile("mma.sync.aligned.m16n8k8.row.col.f32.bf16.bf16.f32 {%0,%1,%2,%3}, {%4,%5}, {%6}, {%0,%1,%2,%3};"
        : "+f"(d[0]), "+f"(d[1]), "+f"(d[2]), "+f"(d[3]) : "r"(a0), "r"(a1), "r"(b0));
}
__device__ __forceinline__ void cp16(uint32_t dst, const void* src) {
    asm volatile("cp.async.cg.shared.global [%0], [%1], 16;" ::"r"(dst), "l"(src) : "memory");
}
__device__ __forceinline__ void sts128(uint32_t a, const float (&v)[4]) {
    asm volatile("st.shared.v4.f32 [%0], {%1,%2,%3,%4};" ::"r"(a), "f"(v[0]), "f"(v[1]), "f"(v[2]), "f"(v[3]) : "memory");
}
__device__ __forceinline__ float4 lds128(uint32_t a) {
    float4 v; asm volatile("ld.shared.v4.f32 {%0,%1,%2,%3}, [%4];" : "=f"(v.x), "=f"(v.y), "=f"(v.z), "=f"(v.w) : "r"(a) : "memory"); return v;
}
__device__ __forceinline__ void sts64(uint32_t a, float x, float y) {
    asm volatile("st.shared.v2.f32 [%0], {%1,%2};" ::"r"(a), "f"(x), "f"(y) : "memory");
}
__device__ __forceinline__ float2 lds64(uint32_t a) {
    float2 v; asm volatile("ld.shared.v2.f32 {%0,%1}, [%2];" : "=f"(v.x), "=f"(v.y) : "r"(a) : "memory"); return v;
}
__device__ __forceinline__ void bar_sync(int id, int n) { asm volatile("bar.sync %0, %1;" ::"r"(id), "r"(n) : "memory"); }
__device__ __forceinline__ void bar_arrive(int id, int n) { asm volatile("bar.arrive %0, %1;" ::"r"(id), "r"(n) : "memory"); }
__device__ __forceinline__ uint32_t mapa(uint32_t a, uint32_t r) {
    uint32_t o; asm("mapa.shared::cluster.u32 %0, %1, %2;" : "=r"(o) : "r"(a), "r"(r)); return o;
}
__device__ __forceinline__ void st_async4(uint32_t dst, float4 v, uint32_t bar) {
    asm volatile("st.async.shared::cluster.mbarrier::complete_tx::bytes.v4.f32 [%0], {%1,%2,%3,%4}, [%5];"
        ::"r"(dst), "f"(v.x), "f"(v.y), "f"(v.z), "f"(v.w), "r"(bar) : "memory");
}
__device__ __forceinline__ void mbar_init(uint32_t bar, int n) { asm volatile("mbarrier.init.shared.b64 [%0], %1;" ::"r"(bar), "r"(n) : "memory"); }
__device__ __forceinline__ void mbar_expect(uint32_t bar, int bytes) {
    asm volatile("mbarrier.arrive.expect_tx.shared.b64 _, [%0], %1;" ::"r"(bar), "r"(bytes) : "memory");
}
__device__ __forceinline__ void bulk_load(uint32_t dst, const void* src, int bytes, uint32_t bar) {
    asm volatile("cp.async.bulk.shared::cluster.global.mbarrier::complete_tx::bytes [%0], [%1], %2, [%3];"
        ::"r"(dst), "l"(src), "r"(bytes), "r"(bar) : "memory");
}
__device__ __forceinline__ bool mbar_try(uint32_t bar, uint32_t par) {
    uint32_t ok;
    asm volatile("{.reg .pred p; mbarrier.try_wait.parity.shared::cta.b64 p, [%1], %2; selp.u32 %0, 1, 0, p;}"
        : "=r"(ok) : "r"(bar), "r"(par) : "memory");
    return ok;
}
__device__ __forceinline__ bool mbar_test(uint32_t bar, uint32_t par) {
    uint32_t ok;
    asm volatile("{.reg .pred p; mbarrier.test_wait.parity.shared::cta.b64 p, [%1], %2; selp.u32 %0, 1, 0, p;}"
        : "=r"(ok) : "r"(bar), "r"(par) : "memory");
    return ok;
}
__device__ __forceinline__ int ld_acq(const int* p) { int v; asm volatile("ld.acquire.gpu.global.s32 %0, [%1];" : "=r"(v) : "l"(p) : "memory"); return v; }
__device__ __forceinline__ void red_release(int* p, int v) { asm volatile("red.release.gpu.global.add.s32 [%0], %1;" ::"l"(p), "r"(v) : "memory"); }
__device__ __forceinline__ void fence_gpu() { asm volatile("fence.acq_rel.gpu;" ::: "memory"); }
__device__ __forceinline__ void wait_ctr(const int* p, int n) {
#pragma unroll 1
    for (int it = 0; it < (1 << 20) && ld_acq(p) < n; it++) __nanosleep(64);
}
__device__ __forceinline__ void mbar_wait(uint32_t bar, uint32_t par) {
    if (!mbar_try(bar, par)) {
#pragma unroll 1
        for (int it = 0; it < SPIN_LIMIT && !mbar_try(bar, par); it++) {}
    }
}
__device__ __forceinline__ void mbar_wait_long(uint32_t bar, uint32_t par) {
    for (int it = 0; it < (1 << 24) && !mbar_try(bar, par); it++) {}
}
__device__ __forceinline__ float4 add4(float4 a, float4 b) { return make_float4(a.x + b.x, a.y + b.y, a.z + b.z, a.w + b.w); }
__device__ __forceinline__ float ex2(float x) { float y; asm("ex2.approx.ftz.f32 %0, %1;" : "=f"(y) : "f"(x)); return y; }

__device__ __forceinline__ void wgmma256(float (&d)[128], uint64_t da, uint64_t db, int acc) {
    asm volatile("{.reg .pred p; setp.ne.b32 p, %130, 0;\n"
        "wgmma.mma_async.sync.aligned.m64n256k16.f32.bf16.bf16 {"
        "%0,%1,%2,%3,%4,%5,%6,%7,%8,%9,%10,%11,%12,%13,%14,%15,"
        "%16,%17,%18,%19,%20,%21,%22,%23,%24,%25,%26,%27,%28,%29,%30,%31,"
        "%32,%33,%34,%35,%36,%37,%38,%39,%40,%41,%42,%43,%44,%45,%46,%47,"
        "%48,%49,%50,%51,%52,%53,%54,%55,%56,%57,%58,%59,%60,%61,%62,%63,"
        "%64,%65,%66,%67,%68,%69,%70,%71,%72,%73,%74,%75,%76,%77,%78,%79,"
        "%80,%81,%82,%83,%84,%85,%86,%87,%88,%89,%90,%91,%92,%93,%94,%95,"
        "%96,%97,%98,%99,%100,%101,%102,%103,%104,%105,%106,%107,%108,%109,%110,%111,"
        "%112,%113,%114,%115,%116,%117,%118,%119,%120,%121,%122,%123,%124,%125,%126,%127"
        "}, %128, %129, p, 1, 1, 0, 1;}"
        : "+f"(d[0]), "+f"(d[1]), "+f"(d[2]), "+f"(d[3]), "+f"(d[4]), "+f"(d[5]), "+f"(d[6]), "+f"(d[7]), "+f"(d[8]), "+f"(d[9]), "+f"(d[10]), "+f"(d[11]), "+f"(d[12]), "+f"(d[13]), "+f"(d[14]), "+f"(d[15]), "+f"(d[16]), "+f"(d[17]), "+f"(d[18]), "+f"(d[19]), "+f"(d[20]), "+f"(d[21]), "+f"(d[22]), "+f"(d[23]), "+f"(d[24]), "+f"(d[25]), "+f"(d[26]), "+f"(d[27]), "+f"(d[28]), "+f"(d[29]), "+f"(d[30]), "+f"(d[31]), "+f"(d[32]), "+f"(d[33]), "+f"(d[34]), "+f"(d[35]), "+f"(d[36]), "+f"(d[37]), "+f"(d[38]), "+f"(d[39]), "+f"(d[40]), "+f"(d[41]), "+f"(d[42]), "+f"(d[43]), "+f"(d[44]), "+f"(d[45]), "+f"(d[46]), "+f"(d[47]), "+f"(d[48]), "+f"(d[49]), "+f"(d[50]), "+f"(d[51]), "+f"(d[52]), "+f"(d[53]), "+f"(d[54]), "+f"(d[55]), "+f"(d[56]), "+f"(d[57]), "+f"(d[58]), "+f"(d[59]), "+f"(d[60]), "+f"(d[61]), "+f"(d[62]), "+f"(d[63]), "+f"(d[64]), "+f"(d[65]), "+f"(d[66]), "+f"(d[67]), "+f"(d[68]), "+f"(d[69]), "+f"(d[70]), "+f"(d[71]), "+f"(d[72]), "+f"(d[73]), "+f"(d[74]), "+f"(d[75]), "+f"(d[76]), "+f"(d[77]), "+f"(d[78]), "+f"(d[79]), "+f"(d[80]), "+f"(d[81]), "+f"(d[82]), "+f"(d[83]), "+f"(d[84]), "+f"(d[85]), "+f"(d[86]), "+f"(d[87]), "+f"(d[88]), "+f"(d[89]), "+f"(d[90]), "+f"(d[91]), "+f"(d[92]), "+f"(d[93]), "+f"(d[94]), "+f"(d[95]), "+f"(d[96]), "+f"(d[97]), "+f"(d[98]), "+f"(d[99]), "+f"(d[100]), "+f"(d[101]), "+f"(d[102]), "+f"(d[103]), "+f"(d[104]), "+f"(d[105]), "+f"(d[106]), "+f"(d[107]), "+f"(d[108]), "+f"(d[109]), "+f"(d[110]), "+f"(d[111]), "+f"(d[112]), "+f"(d[113]), "+f"(d[114]), "+f"(d[115]), "+f"(d[116]), "+f"(d[117]), "+f"(d[118]), "+f"(d[119]), "+f"(d[120]), "+f"(d[121]), "+f"(d[122]), "+f"(d[123]), "+f"(d[124]), "+f"(d[125]), "+f"(d[126]), "+f"(d[127])
        : "l"(da), "l"(db), "r"(acc));
}
__device__ __forceinline__ void wgmma128(float (&d)[64], uint64_t da, uint64_t db, int acc) {
    asm volatile("{.reg .pred p; setp.ne.b32 p, %66, 0;\n"
        "wgmma.mma_async.sync.aligned.m64n128k16.f32.bf16.bf16 {"
        "%0,%1,%2,%3,%4,%5,%6,%7,%8,%9,%10,%11,%12,%13,%14,%15,"
        "%16,%17,%18,%19,%20,%21,%22,%23,%24,%25,%26,%27,%28,%29,%30,%31,"
        "%32,%33,%34,%35,%36,%37,%38,%39,%40,%41,%42,%43,%44,%45,%46,%47,"
        "%48,%49,%50,%51,%52,%53,%54,%55,%56,%57,%58,%59,%60,%61,%62,%63"
        "}, %64, %65, p, 1, 1, 0, 1;}"
        : "+f"(d[0]), "+f"(d[1]), "+f"(d[2]), "+f"(d[3]), "+f"(d[4]), "+f"(d[5]), "+f"(d[6]), "+f"(d[7]), "+f"(d[8]), "+f"(d[9]), "+f"(d[10]), "+f"(d[11]), "+f"(d[12]), "+f"(d[13]), "+f"(d[14]), "+f"(d[15]), "+f"(d[16]), "+f"(d[17]), "+f"(d[18]), "+f"(d[19]), "+f"(d[20]), "+f"(d[21]), "+f"(d[22]), "+f"(d[23]), "+f"(d[24]), "+f"(d[25]), "+f"(d[26]), "+f"(d[27]), "+f"(d[28]), "+f"(d[29]), "+f"(d[30]), "+f"(d[31]), "+f"(d[32]), "+f"(d[33]), "+f"(d[34]), "+f"(d[35]), "+f"(d[36]), "+f"(d[37]), "+f"(d[38]), "+f"(d[39]), "+f"(d[40]), "+f"(d[41]), "+f"(d[42]), "+f"(d[43]), "+f"(d[44]), "+f"(d[45]), "+f"(d[46]), "+f"(d[47]), "+f"(d[48]), "+f"(d[49]), "+f"(d[50]), "+f"(d[51]), "+f"(d[52]), "+f"(d[53]), "+f"(d[54]), "+f"(d[55]), "+f"(d[56]), "+f"(d[57]), "+f"(d[58]), "+f"(d[59]), "+f"(d[60]), "+f"(d[61]), "+f"(d[62]), "+f"(d[63])
        : "l"(da), "l"(db), "r"(acc));
}
__device__ __forceinline__ void wg_fence() { asm volatile("wgmma.fence.sync.aligned;" ::: "memory"); }
__device__ __forceinline__ void wg_commit() { asm volatile("wgmma.commit_group.sync.aligned;" ::: "memory"); }
template <int N> __device__ __forceinline__ void wg_wait() { asm volatile("wgmma.wait_group.sync.aligned %0;" ::"n"(N) : "memory"); }
__device__ __forceinline__ uint64_t mkdesc(uint32_t addr, uint32_t lbo, uint32_t sbo, uint32_t sw) {
    return (uint64_t)((addr & 0x3FFFF) >> 4) | ((uint64_t)(lbo >> 4) << 16) | ((uint64_t)(sbo >> 4) << 32) | ((uint64_t)sw << 62);
}
__device__ __forceinline__ void tma2d(uint32_t dst, const CUtensorMap* m, int c0, int c1, uint32_t bar) {
    asm volatile("cp.async.bulk.tensor.2d.shared::cluster.global.mbarrier::complete_tx::bytes [%0], [%1, {%2, %3}], [%4];"
        ::"r"(dst), "l"(m), "r"(c0), "r"(c1), "r"(bar) : "memory");
}
__device__ __forceinline__ void tma3d(uint32_t dst, const CUtensorMap* m, int c0, int c1, int c2, uint32_t bar) {
    asm volatile("cp.async.bulk.tensor.3d.shared::cluster.global.mbarrier::complete_tx::bytes [%0], [%1, {%2, %3, %4}], [%5];"
        ::"r"(dst), "l"(m), "r"(c0), "r"(c1), "r"(c2), "r"(bar) : "memory");
}
__device__ __forceinline__ void tma3d_mc(uint32_t dst, const CUtensorMap* m, int c0, int c1, int c2, uint32_t bar, uint16_t mask) {
    asm volatile("cp.async.bulk.tensor.3d.shared::cluster.global.mbarrier::complete_tx::bytes.multicast::cluster [%0], [%1, {%2, %3, %4}], [%5], %6;"
        ::"r"(dst), "l"(m), "r"(c0), "r"(c1), "r"(c2), "r"(bar), "h"(mask) : "memory");
}
__device__ __forceinline__ void mbar_arrive(uint32_t bar) { asm volatile("mbarrier.arrive.shared.b64 _, [%0];" ::"r"(bar) : "memory"); }
__device__ __forceinline__ void mbar_arrive_remote(uint32_t bar) {
    asm volatile("mbarrier.arrive.shared::cluster.b64 _, [%0];" ::"r"(bar) : "memory");
}
__device__ __forceinline__ bool elect() {
    uint32_t p;
    asm volatile("{.reg .pred p; elect.sync _|p, 0xffffffff; selp.u32 %0, 1, 0, p;}" : "=r"(p));
    return p;
}
template <int R> __device__ __forceinline__ void reg_inc() { asm volatile("setmaxnreg.inc.sync.aligned.u32 %0;" ::"n"(R)); }
template <int R> __device__ __forceinline__ void reg_dec() { asm volatile("setmaxnreg.dec.sync.aligned.u32 %0;" ::"n"(R)); }

#define ST(id, w, i)
constexpr int CH_NRES = 50;
constexpr int CH_WREG = CH_NRES * 512;
constexpr int CH_PART = 8 * CH_WREG;
constexpr int CH_SX = CH_PART + 16384;
constexpr int CH_MX = CH_SX + 3 * 1280;
constexpr int CH_QK = CH_MX;
constexpr int CH_XS = CH_MX + 3 * 512;
constexpr int CH_BAR = CH_XS + 5632;
constexpr int CH_SMEM = CH_BAR + 192;
constexpr int CH_THREADS = 384;

__device__ __forceinline__ char* ring_base() { return (char*)(((uintptr_t)g_ring + (1 << 20) - 1) & ~(uintptr_t)((1 << 20) - 1)); }
__device__ __forceinline__ uint32_t ring_off(int chunk, int side) {
    uint32_t o = ((chunk & 1) << 13) | ((chunk >> 1) << 16);
    uint32_t par = ((o >> 13) ^ (o >> 16) ^ (o >> 17) ^ (o >> 19) ^ side) & 1;
    return o | (par << 12);
}
__device__ __forceinline__ uint2 ld_poll(const char* p) {
    unsigned long long v; asm volatile("ld.relaxed.gpu.global.b64 %0, [%1];" : "=l"(v) : "l"(p) : "memory");
    return make_uint2((uint32_t)v, (uint32_t)(v >> 32));
}
__device__ __forceinline__ void st_pub(char* p, uint32_t x, uint32_t y) {
    unsigned long long v = ((unsigned long long)y << 32) | x;
    asm volatile("st.relaxed.gpu.global.b64 [%0], %1;" ::"l"(p), "l"(v) : "memory");
}
template <int N>
__device__ __forceinline__ void poll_issue(uint2 (&b)[N], const char* p, bool lastvalid) {
#pragma unroll
    for (int i = 0; i < N; i++) {
        if (i < N - 1 || lastvalid) b[i] = ld_poll(p + i * 256);
        else b[i] = make_uint2(0, 0);
    }
}
template <int N>
__device__ __forceinline__ int poll_check(uint2 (&b)[N], const char* p, uint32_t z) {
    int it = 0;
    uint32_t mx = z;
#pragma unroll
    for (int i = 0; i < N; i++) mx = max(mx, b[i].x);
    if (__any_sync(0xffffffffu, mx == SENT)) {
        do {
#pragma unroll
            for (int i = 0; i < N; i++)
                if ((REALL && i < 10) || b[i].x == SENT) b[i] = ld_poll(p + i * 256);
            mx = b[0].x;
#pragma unroll
            for (int i = 1; i < N; i++) mx = max(mx, b[i].x);
            it++;
        } while (__any_sync(0xffffffffu, mx == SENT && it < SPIN_LIMIT));
    }
    return it;
}
template <int N>
__device__ __forceinline__ uint32_t delay(uint32_t a) {
    uint32_t z = 0;
#pragma unroll
    for (int i = 0; i < N; i++) asm volatile("ld.volatile.shared.u32 %0, [%1];" : "=r"(z) : "r"(a + z) : "memory");
    return z;
}

#define PFKV 0
#define LDW 0
#define GX 2
#define PACE2 18
#define KGS 2
constexpr int KVN = 2;
#define FEN 1
#define XB 4
#define KEEP 100
#define PE 0
#define PROMO 2
#define PROMU 0
#define FNC 3
#define CL 8
#define PL 0
#define ML 4
#define MP 2
#define VCH_P 4
#define VCH_C 2
#define DLM 3
#define DLO 5
constexpr int OB = 0;
template <int PACE, int I0 = 0, int I1 = 12>
__device__ __forceinline__ void preload(uint32_t (&sw)[12][4], uint32_t a, uint32_t zero) {
    uint32_t z = 0;
#pragma unroll
    for (int i = I0; i < I1; i++) {
        if (PACE && i % (PACE ? PACE : 1) == 0) z = delay<1>(zero + z);
        ldsm4t(sw[i], a + z + i * 512);
    }
}
__device__ __forceinline__ void stsm4(uint32_t addr, uint32_t a, uint32_t b, uint32_t c, uint32_t d) {
    asm volatile("stmatrix.sync.aligned.m8n8.x4.shared.b16 [%0], {%1,%2,%3,%4};" ::"r"(addr), "r"(a), "r"(b), "r"(c), "r"(d) : "memory");
}
__device__ __forceinline__ void stsm4t(uint32_t addr, uint32_t a, uint32_t b, uint32_t c, uint32_t d) {
    asm volatile("stmatrix.sync.aligned.m8n8.x4.trans.shared.b16 [%0], {%1,%2,%3,%4};" ::"r"(addr), "r"(a), "r"(b), "r"(c), "r"(d) : "memory");
}
__device__ __forceinline__ void st_part(uint32_t addr, const float (&x)[4], const float (&y)[4]) {
    stsm4(addr, pack_bf16(x[0], x[1]), pack_bf16(x[2], x[3]), pack_bf16(y[0], y[1]), pack_bf16(y[2], y[3]));
}
template <bool TR>
__device__ __forceinline__ void red_part(uint32_t& lo, uint32_t& hi, uint32_t addr, uint32_t eye) {
    uint32_t a[4][4];
#pragma unroll
    for (int j = 0; j < 4; j++) { if (TR) ldsm4t(a[j], addr + j * 1024); else ldsm4(a[j], addr + j * 1024); }
    float r0[4], r1[4], r2[4], r3[4];
    mma16z(r0, a[0], eye, eye); mma16z(r1, a[1], eye, eye); mma16z(r2, a[2], eye, eye); mma16z(r3, a[3], eye, eye);
#pragma unroll
    for (int j = 0; j < 4; j++) r0[j] = ((r0[j] + r1[j]) + r2[j]) + r3[j];
    lo = pack_bf16(r0[0], r0[1]); hi = pack_bf16(r0[2], r0[3]);
}
__device__ __forceinline__ int o_chunk(int ks, int& pos) {
    const int cw = ks < 176 ? ks / 11 : 16 + (ks - 176) / 10;
    pos = ks - (cw < 16 ? 11 * cw : 176 + 10 * (cw - 16));
    return cw;
}

template <bool PV>
__device__ __forceinline__ void chain_loop(const uint32_t (&wa)[36][4], const uint32_t sb, const int w, const int lane0, const int rank,
                                           const int h, const int side) {
    const int rk1 = rank == 2 ? 0 : rank + 1, rk2 = rank == 0 ? 2 : rank - 1;
    const int nq = rank == 0 ? 6 : 5, u0 = rank == 0 ? 0 : 1 + 5 * rank, v0 = rank == 0 ? -6 : 3 * rank - 6;
    const uint32_t pt = CH_PART + (w >> 1) * 4096 + (w & 1) * 256;
    const uint32_t barS = sb + CH_BAR, barM = barS + 8, zero = barS + 24;
    char* const ring0 = ring_base();
    const uint32_t m_rd = ring_off(24 + w, side), o_rd = ring_off(rank * 8 + w, side);
    uint32_t pub;
    if (PV) { int pos, cw = o_chunk(h * 8 + v0 + w, pos); pub = (ring_off(cw, 0) & ~4096u) + pos * 256; }
    else pub = (ring_off(24 + (h >> 2), 0) & ~4096u) + ((2 * h + w) & 7) * 256;
    char* const kvo = (char*)(PV ? g_vm + 128 * (v0 + w) : g_km + 64 * (u0 + w)) + h * 2048;
    const bool mown = !PV && w == rank && rank < 2;
    uint32_t lo16 = lane0 * 16;
    uint32_t sw[12][4];
#pragma unroll
    for (int i = 0; i < 12; i++) ldsm4t(sw[i], sb + lo16 + w * CH_WREG + i * 512);

#pragma unroll 1
    for (int s = 0;; s++) {
        const bool last = s == NSEG - 1;
        const uint32_t slot = (s & 3) << 14;
        lo16 += delay<DLM>(zero);
        const uint32_t lane = lo16 >> 4, l16 = sb + lo16, wl = l16 + w * CH_WREG, pw = l16 + CH_PART + w * 512;
        const uint32_t xs = l16 + CH_XS + nq * 512 + (w - nq) * 1024;
        const uint32_t eye = ((lo16 >> 7) == (lane & 3)) ? ((lo16 & 64) ? 0x3F800000u : 0x3F80u) : 0u;
        uint2 b[8];
        const char* pm = ring0 + (m_rd + slot + (lo16 >> 1));
        poll_issue<8>(b, pm, true);
        preload<0, ML, 12>(sw, wl, zero);
        if (FNC & 1) bar_arrive(14, 256);
        poll_check<8>(b, pm, delay<FNC & 1>(zero));
        if ((OB || (XB & 1)) && !last) bar_arrive(8, 256 + OB);
        if (PV && !last && w == 7) bar_arrive(13, 64);
        {
            float acc[6][4];
#pragma unroll
            for (int kk = 0; kk < 8; kk++) {
                const int j = (2 * kk) % 12;
                if (kk == 0) { mma16z(acc[5], sw[0], b[0].x, b[0].y); mma16z(acc[4], sw[1], b[0].x, b[0].y); }
                else { mma16(acc[5], sw[j], b[kk].x, b[kk].y); mma16(acc[4], sw[j + 1], b[kk].x, b[kk].y); }
#pragma unroll
                for (int i = 0; i < 4; i++) {
                    if (kk == 0) mma16z(acc[i], wa[i * 8], b[0].x, b[0].y);
                    else mma16(acc[i], wa[i * 8 + kk], b[kk].x, b[kk].y);
                    if (i < 2) ldsm4t(sw[j + i], wl + (12 + 2 * kk + i) * 512);
                }
            }
            st_part(pw + 4 * 2048, acc[4], acc[5]);
            st_part(pw, acc[0], acc[1]);
            st_part(pw + 2 * 2048, acc[2], acc[3]);
        }
        uint32_t kv0, kv1;
        const uint32_t lp = l16 + (lane >> 4) * 256, pl = lp + pt;
        if (!PV) {
            bar_sync(1, last ? 256 : 256 + OB);
            red_part<true>(kv1, kv0, pl, eye);
            sts64(l16 + CH_QK + (w >> 1) * 512 + (w & 1) * 8, __uint_as_float(kv1), __uint_as_float(kv0));
            if (!last) bar_arrive(2, nq * 32 + 64 + OB);
        } else {
            bar_sync(1, last ? 256 : 256 + OB);
        }
        {
            float va[4][4];
            const float z = __uint_as_float(delay<1>(zero));
#pragma unroll
            for (int i = 0; i < 4; i++) va[i][0] = va[i][1] = va[i][2] = va[i][3] = z;
#pragma unroll
            for (int kk = 0; kk < 8; kk++) {
                const int c = (PV ? VCH_P : VCH_C) == 4 ? kk & 1 : 0;
                if (kk < 2) { mma16(va[c], wa[32 + 2 * kk], b[kk].x, b[kk].y); mma16(va[2 + c], wa[33 + 2 * kk], b[kk].x, b[kk].y); }
                else { mma16(va[c], sw[(2 * kk) % 12], b[kk].x, b[kk].y); mma16(va[2 + c], sw[(2 * kk + 1) % 12], b[kk].x, b[kk].y); }
            }
            if ((PV ? VCH_P : VCH_C) == 4) {
#pragma unroll
                for (int j = 0; j < 4; j++) { va[0][j] += va[1][j]; va[2][j] += va[3][j]; }
            }
            st_part(pw + 6 * 2048, va[0], va[2]);
        }
        if (PV) {
            uint32_t vt0[4], vt1[4];
            ldsm4t(vt0, xs); ldsm4t(vt1, xs + 512);
            if (w >= 6 && !last) {
                uint32_t kx[3][4];
#pragma unroll
                for (int j = 0; j < 3; j++)
                    ldsm4(kx[j], sb + CH_XS + j * 1024 + (j == 2 && nq == 5 ? 0 : ((lane >> 3) & 1) * 512) + (w - 6) * 256 + (lane >> 4) * 128 + (lane & 7) * 16);
                const uint32_t da = l16 + CH_SX + rank * 1280 + (w - 6) * 512, dc = sb + CH_SX + rank * 1280 + 1024 + lane * 8;
                bar_sync(2, nq * 32 + 64 + OB);
                uint32_t qk[3][4];
#pragma unroll
                for (int j = 0; j < 3; j++) {
                    const float4 v = lds128(l16 + CH_QK + j * 512);
                    qk[j][0] = __float_as_uint(v.x); qk[j][1] = __float_as_uint(v.y); qk[j][2] = __float_as_uint(v.z); qk[j][3] = __float_as_uint(v.w);
                }
                float s0[4], s1[4], s2[4], s3[4];
                mma16z(s0, qk[0], kx[0][0], kx[0][1]); mma16z(s1, qk[0], kx[0][2], kx[0][3]);
                mma16z(s2, qk[1], kx[1][0], kx[1][1]); mma16z(s3, qk[1], kx[1][2], kx[1][3]);
                if (nq == 5) qk[2][2] = qk[2][3] = 0;
                mma16(s0, qk[2], kx[2][0], kx[2][1]); mma16(s1, qk[2], kx[2][2], kx[2][3]);
                float m0[4], m1[4];
                mma16z(m0, qk[0], qk[0][1], qk[0][3]); mma16z(m1, qk[1], qk[1][1], qk[1][3]);
                mma16(m0, qk[2], qk[2][1], qk[2][3]);
                const float4 sv = make_float4(s0[0] + s2[0], s0[1] + s2[1], s1[0] + s3[0], s1[1] + s3[1]);
                st_async4(mapa(da, rk1), sv, mapa(barS, rk1));
                st_async4(mapa(da, rk2), sv, mapa(barS, rk2));
                {
                    const float c0 = m0[0] + m1[0], c1 = m0[1] + m1[1];
                    const int dr = w == 6 ? rk1 : rk2;
                    st_async2(mapa(dc, dr), c0, c1, mapa(barS, dr));
                    sts64(dc, c0, c1);
                }
                const float t4[4] = {sv.x, sv.y, sv.z, sv.w};
                sts128(da, t4);
            }
            bar_sync(3, last ? 256 : 256 + OB);
            if (!last && w == 7) bar_arrive(12, 64);
            red_part<false>(kv0, kv1, pl, eye);
            if (last) {
                uint32_t* d = (uint32_t*)(kvo + (uint32_t)(s * (NH * 2048) + lane * 4));
                d[0] = movm(kv0); d[32] = movm(kv1);
                break;
            }
            {
                const uint32_t sx = l16 + CH_SX, r0 = rank * 1280, r1 = rk1 * 1280, r2 = rk2 * 1280;
                float4 a0 = lds128(sx + r0), b0 = lds128(sx + 512 + r0);
                const float2 c0 = lds64(sx + 1024 + r0 - lane * 8);
                preload<0, 0, PE>(sw, wl + 28 * 512, zero);
                mbar_wait(barS, s & 1);
                const float4 a1 = lds128(sx + r1), a2 = lds128(sx + r2), b1 = lds128(sx + 512 + r1), b2 = lds128(sx + 512 + r2);
                const float2 c1 = lds64(sx + 1024 + r1 - lane * 8), c2 = lds64(sx + 1024 + r2 - lane * 8);
                a0 = add4(add4(a0, a1), a2); b0 = add4(add4(b0, b1), b2);
                float sc[10] = {a0.x, a0.y, a0.z, a0.w, b0.x, b0.y, b0.z, b0.w, c0.x + c1.x + c2.x, c0.y + c1.y + c2.y};
                float mx = fmaxf(fmaxf(fmaxf(sc[0], sc[1]), fmaxf(sc[2], sc[3])), fmaxf(fmaxf(sc[4], sc[5]), fmaxf(sc[6], sc[7])));
                mx = fmaxf(mx, fmaxf(sc[8], sc[9]));
                mx = fmaxf(fmaxf(mx, __shfl_xor_sync(0xffffffffu, mx, 1)),
                           fmaxf(__shfl_xor_sync(0xffffffffu, mx, 2), __shfl_xor_sync(0xffffffffu, mx, 3)));
                const float cs = 0.08838834764831845f * 1.4426950408889634f;
                const float mb = -mx * cs;
#pragma unroll
                for (int j = 0; j < 10; j++) sc[j] = ex2(fmaf(sc[j], cs, mb));
                uint32_t pf[5];
#pragma unroll
                for (int j = 0; j < 5; j++) pf[j] = pack_bf16(sc[2 * j], sc[2 * j + 1]);
                float o0[4], o1[4], o2[4], o3[4], o4[4], o5[4];
                const uint32_t p0[4] = {pf[0], 0, pf[1], 0}, p1[4] = {pf[2], 0, pf[3], 0};
                mma16z(o0, p0, vt0[0], vt0[1]); mma16z(o1, p0, vt1[0], vt1[1]);
                mma16z(o2, p1, vt0[2], vt0[3]); mma16z(o3, p1, vt1[2], vt1[3]);
                mma8z(o4, pf[4], 0, kv0); mma8z(o5, pf[4], 0, kv1);
                float sum = (((sc[0] + sc[1]) + (sc[2] + sc[3])) + ((sc[4] + sc[5]) + (sc[6] + sc[7]))) + (sc[8] + sc[9]);
                sum = (sum + __shfl_xor_sync(0xffffffffu, sum, 1)) + (__shfl_xor_sync(0xffffffffu, sum, 2) + __shfl_xor_sync(0xffffffffu, sum, 3));
                float inv; asm("rcp.approx.ftz.f32 %0, %1;" : "=f"(inv) : "f"(sum));
                const uint32_t ox = pack_bf16((o0[0] + o2[0] + o4[0]) * inv, (o0[1] + o2[1] + o4[1]) * inv);
                const uint32_t oy = pack_bf16((o1[0] + o3[0] + o5[0]) * inv, (o1[1] + o3[1] + o5[1]) * inv);
                char* const pp = ring0 + (pub + slot + (lo16 >> 1));
                st_pub(pp, ox, oy); st_pub(pp + 4096, ox, oy);
                if (OB || (XB & 4)) bar_arrive(10, (8 - nq) * 32 + OB);
                preload<0, PE, PL>(sw, wl + 28 * 512, zero);
            }
            kv0 = movm(kv0); kv1 = movm(kv1);
        } else {
            *(uint32_t*)(kvo + (uint32_t)(s * (NH * 2048) + lane * 4)) = kv0;
            bar_sync(3, last ? 256 : 256 + OB);
            if (last) break;
            preload<1, 0, CL>(sw, wl + 28 * 512, zero);
        }
        uint2 c[11];
        bar_sync(4, 256 + OB);
        const char* po = ring0 + (o_rd + slot + (lo16 >> 1) + delay<DLO>(zero));
        poll_issue<11>(c, po, rank < 2);
        preload<0, PV ? PL : CL, 12>(sw, wl + 28 * 512, zero);
        if (PV) { uint32_t* d = (uint32_t*)(kvo + (uint32_t)(s * (NH * 2048) + lane * 4)); d[0] = kv0; d[32] = kv1; }
        {
            float acc[4][4];
            uint32_t sx[GX][4];
#pragma unroll
            for (int i = 0; i < GX; i++) ldsm4t(sx[i], wl + (40 + i) * 512);
            if (FNC & 2) bar_arrive(15, 256);
            poll_check<11>(c, po, delay<(FNC >> 1)>(zero));
            if (OB || (XB & 2)) bar_arrive(9, 256 + OB);
#pragma unroll
            for (int f = 0; f < 22; f++) {
                const int kk = f >> 1, a = f & 3;
                if (f < 4) mma16z(acc[a], sw[f], c[kk].x, c[kk].y);
                else if (f >= 12 && f < 12 + GX) mma16(acc[a], sx[f - 12], c[kk].x, c[kk].y);
                else mma16(acc[a], sw[f % (12 + GX)], c[kk].x, c[kk].y);
                if (f + 12 + GX < 22) ldsm4t(sw[f], wl + (40 + GX + f) * 512);
            }
#pragma unroll
            for (int i = 0; i < 2; i++) {
#pragma unroll
                for (int j = 0; j < 4; j++) acc[i][j] += acc[i + 2][j];
                sts128(l16 + CH_PART + i * 4096 + w * 512, acc[i]);
            }
        }
        if (!PV && w < 2) {
            bar_sync(5, 288 + OB);
            float4 v[8];
#pragma unroll
            for (int i = 0; i < 8; i++) v[i] = lds128(l16 + CH_PART + w * 4096 + i * 512);
            float4 r = add4(add4(add4(v[0], v[1]), add4(v[2], v[3])), add4(add4(v[4], v[5]), add4(v[6], v[7])));
            if (!mown) st_async4(mapa(l16 + CH_MX + rank * 512, w), r, mapa(barM, w));
            bar_arrive(7, 256 + OB);
            if (mown) {
                mbar_wait(barM, s & 1);
                float4 x = lds128(l16 + CH_MX + (rank ^ 1) * 512), y = lds128(l16 + CH_MX + 2 * 512);
                r = add4(add4(x, r), y);
                const uint32_t mx = movm(pack_bf16(r.x, r.y)), my = movm(pack_bf16(r.z, r.w));
                const uint32_t ns = (slot + 0x4000) & 0xC000;
                char* const pp = ring0 + (pub + ns + (lo16 >> 1));
                st_pub(pp, mx, my); st_pub(pp + 4096, mx, my);
            }
            preload<0, 0, ML>(sw, wl, zero);
        } else {
            bar_arrive(5, 288 + OB);
            bar_sync(7, 256 + OB);
            preload<MP, 0, ML>(sw, wl, zero);
        }
        bar_sync(6, 320 + OB);
    }
}

__device__ __forceinline__ void chain_pace(const uint32_t sb, const int lane, const int rank, const int aware) {
    const uint32_t zero = sb + CH_BAR + 24;
    if (lane == 0) {
        char* ring = ring_base();
        uint32_t* p0 = (uint32_t*)(ring + ring_off(blockIdx.x & 15, 0) + 3072 + (blockIdx.x >> 4) * 128);
        uint32_t* p1 = (uint32_t*)(ring + ring_off(blockIdx.x & 15, 1) + 3072 + (blockIdx.x >> 4) * 128);
        *p0 = 0; *p1 = 0;
        int b0 = 1 << 30, b1 = 1 << 30; uint32_t v = 0;
        for (int r = 0; r < 4 || (r < 256 && !mbar_test(sb + CH_BAR + 16, 0)); r++) {
            uint32_t t0 = clk(); v = atomicExch(p0 + (v == 500), r); uint32_t t1 = v == 777 ? clk() + 1 : clk(); b0 = min(b0, (int)(t1 - t0));
            t0 = clk(); v = atomicExch(p1 + (v == 500), r); t1 = v == 777 ? clk() + 1 : clk(); b1 = min(b1, (int)(t1 - t0));
            asm volatile("st.volatile.shared.u32 [%0], %1;" ::"r"(zero + 4), "r"(aware ? (b1 < b0) ^ (aware - 1) : 0) : "memory");
        }
    }
    __syncwarp();
#pragma unroll 1
    for (int s = 1; s < NSEG; s++) {
        bar_sync(5, 288 + OB);
        bar_arrive(6, 320 + OB + (rank == 2 ? delay<PACE2>(zero) : 0));
    }
}
__device__ __forceinline__ char* reset_ptr(const int lane, const int rank, const int h) {
    const int nq = rank == 0 ? 6 : 5, v0 = rank == 0 ? -6 : 3 * rank - 6;
    int pos, cw = o_chunk(h * 8 + v0 + min(max(5 + (lane >> 3), nq), 7), pos);
    if (lane >= 24 && rank < 2) { cw = 24 + (h >> 2); pos = (2 * h + rank) & 7; }
    return ring_base() + ((ring_off(cw, 0) & ~4096u) + pos * 256 + (lane & 7) * 16);
}
__device__ __forceinline__ void chain_chores(const uint32_t sb, const int lane, const int rank, const int h, const bf16* __restrict__ mem0) {
    const int nq = rank == 0 ? 6 : 5, u0 = rank == 0 ? 0 : 1 + 5 * rank, v0 = rank == 0 ? -6 : 3 * rank - 6;
    const uint32_t barS = sb + CH_BAR, barM = barS + 8, barX = barS + 16;
    auto xload = [&](int s) {
        mbar_expect(barX, 8192 - nq * 512);
        bulk_load(sb + CH_XS, g_kx + (size_t)(s * NH + h) * 4096 + u0 * 256, nq * 512, barX);
        bulk_load(sb + CH_XS + nq * 512, g_vx + (size_t)(s * NH + h) * 4096 + (v0 + nq) * 512, (8 - nq) * 1024, barX);
    };
    char* const rb = reset_ptr(lane, rank, h);
    int* const kvf = g_kvf + blockIdx.x * 16;
    if (rank < 2) {
        const uint32_t* p = (const uint32_t*)(mem0 + (lane >> 2) * DM + 32 * h + 16 * rank + 2 * (lane & 3));
        char* d = ring_base() + ((ring_off(24 + (h >> 2), 0) & ~4096u) + ((2 * h + rank) & 7) * 256 + lane * 8);
        const uint32_t x = p[0] == SENT ? 0x7FFF7FFFu : p[0];
        st_pub(d, x, p[4]); st_pub(d + 4096, x, p[4]);
    }
    if (!KVN) __nanosleep(18000);
    wait_ctr(kvf, KVN);
    asm volatile("fence.proxy.async.global;" ::: "memory");
    if (elect()) xload(0);
#pragma unroll 1
    for (int s = 0; s < NSEG - 1; s++) {
        if (lane == 0) {
            mbar_expect(barS, 2 * 1280);
            if (rank < 2) mbar_expect(barM, 2 * 512);
        }
        bar_sync(13, 64);
#pragma unroll
        for (int i = 0; i < 4; i++)
            asm volatile("st.relaxed.gpu.global.v4.u32 [%0], {%1,%1,%1,%1};" ::"l"(rb + ((((s + 2) & 3) << 14) + (i >> 1) * 4096 + (i & 1) * 128)), "r"(SENT) : "memory");
        if (FEN || (s & 3) == 0) fence_gpu();
        if (lane == 0 && (s & 3) == 0 && s) atomicAdd(g_ctr + C_CHAIN + (s >> 2) - 1, 1);
        if ((s & 3) == 3) { wait_ctr(kvf + (s >> 2) + 1, KVN); asm volatile("fence.proxy.async.global;" ::: "memory"); }
        __syncwarp();
        bar_sync(12, 64);
        if (elect()) xload(s + 1);
        mbar_wait(barX, (s + 1) & 1);
        bar_sync(6, 320 + OB);
    }
}

struct S4Params { const bf16 *Are, *Aim, *Bre, *Bim, *Cre, *Cim, *ldt, *dsk; };
__device__ __forceinline__ float2 cmul(float2 a, float2 b) { return make_float2(a.x * b.x - a.y * b.y, a.x * b.y + a.y * b.x); }
__device__ __forceinline__ float2 csq(float2 a) { return make_float2(a.x * a.x - a.y * a.y, (a.x + a.x) * a.y); }
__device__ __forceinline__ float2 cexp_t(float lr, float turns) {
    float f = (turns - rintf(turns)) * 6.283185307179586f, e = ex2(lr);
    return make_float2(e * __cosf(f), e * __sinf(f));
}
__device__ __forceinline__ float bf_at(uint2 v, int i) {
    const uint32_t w = i < 2 ? v.x : v.y;
    return __uint_as_float((i & 1) ? w & 0xFFFF0000u : w << 16);
}
__device__ __forceinline__ void kg_step(uint32_t (&a)[4][4], uint32_t (&b)[5][2], uint32_t pa, uint32_t pe, float x0) {
#pragma unroll
    for (int i = 0; i < 2; i++) {
        const float4 p = lds128(pa + i * 64);
        const float2 e8 = lds64(pe + i * 32), c = make_float2(p.z, p.w);
        const float mag = ex2(p.x * x0), ph = p.y * x0;
        float2 e0 = make_float2(mag * __cosf(ph), mag * __sinf(ph)), e1 = cmul(e0, e8);
#pragma unroll
        for (int j = 0; j < 4; j++) {
            a[j][2 * i] = pack_bf16(e0.x, e0.y); a[j][2 * i + 1] = pack_bf16(e1.x, e1.y);
            e0 = csq(e0); e1 = csq(e1);
        }
        float2 m = cmul(c, e0);
        b[0][i] = pack_bf16(m.x, -m.y);
#pragma unroll
        for (int j = 0; j < 4; j++) {
            m = cmul(c, e1);
            b[j + 1][i] = pack_bf16(m.x, -m.y);
            if (j < 3) e1 = csq(e1);
        }
    }
}
__device__ __forceinline__ void kg_mma(float (&kd)[5][4], const uint32_t (&a)[4][4], const uint32_t (&b)[5][2]) {
    mma16(kd[0], a[0], b[0][0], b[0][1]);
#pragma unroll
    for (int j = 0; j < 4; j++) mma16(kd[j + 1], a[j], b[j + 1][0], b[j + 1][1]);
}
struct KgRaw { uint2 v[6]; float ldt; };
__device__ __forceinline__ void kg_load(KgRaw& r, const S4Params& P, int d, int lane) {
    const bf16* src[6] = {P.Are, P.Aim, P.Bre, P.Bim, P.Cre, P.Cim};
#pragma unroll
    for (int j = 0; j < 6; j++) r.v[j] = __ldg((const uint2*)(src[j] + d * 128) + lane);
    r.ldt = __bfloat162float(P.ldt[d]);
}
__device__ __forceinline__ float kg_params(const KgRaw& r, uint32_t stg, int lane) {
    const float dt = __bfloat162float(__float2bfloat16(expf(r.ldt)));
    float k2048 = 0.f;
#pragma unroll
    for (int i = 0; i < 4; i++) {
        const float br = dt * bf_at(r.v[2], i), bi = dt * bf_at(r.v[3], i), cr = bf_at(r.v[4], i), ci = bf_at(r.v[5], i);
        const float zr = dt * bf_at(r.v[0], i) * 1.4426950408889634f;
        float zt = dt * bf_at(r.v[1], i) * 0.15915494309189535f;
        zt -= rintf(zt);
        const float v[4] = {zr, zt * 6.283185307179586f, cr * br - ci * bi, cr * bi + ci * br};
        const float2 e8 = cexp_t(8.f * zr, 8.f * zt), el = cexp_t(2048.f * zr, 2048.f * zt);
        k2048 += v[2] * el.x - v[3] * el.y;
        sts128(stg + (i * 32 + lane) * 16, v);
        sts64(stg + 2048 + (i * 32 + lane) * 8, e8.x, e8.y);
    }
#pragma unroll
    for (int o = 16; o; o >>= 1) k2048 += __shfl_xor_sync(0xffffffffu, k2048, o);
    __syncwarp();
    return k2048;
}
__device__ __forceinline__ void kg_store(const float (&kd)[5][4], float k2048, uint32_t stg, int d, int lane) {
    __syncwarp();
    const uint32_t ta = stg + (lane & 7) * 32 + ((lane >> 3) & 1) * 16 + (lane >> 4) * 256;
    stsm4t(ta, pack_bf16(kd[0][0], kd[0][1]), pack_bf16(kd[0][2], kd[0][3]), pack_bf16(kd[1][0], kd[1][1]), pack_bf16(kd[1][2], kd[1][3]));
    stsm4t(ta + 512, pack_bf16(kd[2][0], kd[2][1]), pack_bf16(kd[2][2], kd[2][3]), pack_bf16(kd[3][0], kd[3][1]), pack_bf16(kd[3][2], kd[3][3]));
    stsm4t(ta + 1024, pack_bf16(kd[4][0], kd[4][1]), pack_bf16(kd[4][2], kd[4][3]), pack_bf16(k2048, 0.f), 0);
    __syncwarp();
#pragma unroll
    for (int j = 0; j < 3; j++) ((float4*)(g_kd + d * 768))[j * 32 + lane] = lds128(stg + j * 512 + lane * 16);
    __syncwarp();
}

__global__ void __cluster_dims__(3, 1, 1) __launch_bounds__(CH_THREADS, 1)
chain_kernel(const __grid_constant__ CUtensorMap mq, const __grid_constant__ CUtensorMap mk, const __grid_constant__ CUtensorMap mv,
             const __grid_constant__ CUtensorMap mo, const bf16* __restrict__ Wq, const bf16* __restrict__ Wk, const bf16* __restrict__ Wv,
             const bf16* __restrict__ mem0, const __grid_constant__ S4Params P, int aware) {
    extern __shared__ __align__(1024) unsigned char smem[];
    const uint32_t sb = smem_u32(smem);
    const int tid = threadIdx.x, lane = tid & 31;
    const int w = __shfl_sync(0xffffffffu, tid >> 5, 0);
    int rank; asm("mov.u32 %0, %%cluster_ctarank;" : "=r"(rank));
    const int h = blockIdx.x / 3;
    if (tid == 0) {
        mbar_init(sb + CH_BAR, 1); mbar_init(sb + CH_BAR + 8, 1); mbar_init(sb + CH_BAR + 16, 1);
        for (int i = 0; i < 16; i++) mbar_init(sb + CH_BAR + 64 + i * 8, 1);
        *(int*)(smem + CH_BAR + 24) = 0; *(int*)(smem + CH_BAR + 28) = 0; *(int*)(smem + CH_BAR + 32) = 0;
        asm volatile("fence.mbarrier_init.release.cluster;" ::: "memory");
    }
    if (w == 10 && PFKV) {
        const int e = lane * 96 + blockIdx.x;
        if (e < 2048) asm volatile("cp.async.bulk.prefetch.L2.global [%0], 8192;" ::"l"(((e & 1) ? Wv : Wk) + (size_t)(e >> 1) * HD) : "memory");
        if (PFKV > 1) __nanosleep(PFKV);
    }
    if (w == 9) {
        char* const rb = reset_ptr(lane, rank, h);
#pragma unroll
        for (int i = 0; i < 8; i++)
            asm volatile("st.relaxed.gpu.global.v4.u32 [%0], {%1,%1,%1,%1};" ::"l"(rb + (((i >> 2) << 14) + ((i >> 1) & 1) * 4096 + (i & 1) * 128)), "r"(SENT) : "memory");
        if (lane < 16) g_kvf[blockIdx.x * 16 + lane] = 0;
        if (blockIdx.x == 0)
            for (int k = lane; k < N_CTR; k += 32) g_ctr[k] = 0;
        fence_gpu();
        __syncwarp();
        asm volatile("griddepcontrol.launch_dependents;" ::: "memory");
    }
    __syncthreads();
    asm volatile("barrier.cluster.arrive.relaxed.aligned;" ::: "memory");

    if (w >= 8) {
        reg_dec<24>();
        asm volatile("barrier.cluster.wait.aligned;" ::: "memory");
        if (w == 8) chain_pace(sb, lane, rank, aware);
        else if (w == 9) {
            chain_chores(sb, lane, rank, h, mem0);
            asm volatile("st.volatile.shared.u32 [%0], %1;" ::"r"(sb + CH_BAR + 32), "r"(0x3F803F80) : "memory");
        } else if (w == 11 && KEEP) {
#pragma unroll 1
            for (int it = 0; it < (1 << 22); it++) {
                int d0, d1;
                const uint32_t x = delay<1>(sb + CH_BAR + 32);
                asm volatile("mma.sync.aligned.m8n8k16.row.col.s32.s8.s8.s32 {%0,%1}, {%2}, {%2}, {%3,%3};" : "=r"(d0), "=r"(d1) : "r"(x), "r"(0));
                if (d0 | d1) break;
                if ((XB & 8) && lane == 0) asm volatile("st.relaxed.gpu.global.u32 [%0], %1;" ::"l"(g_kd + DM * 768 + blockIdx.x * 64), "r"(it) : "memory");
                if ((XB & 16) && lane == 0) ld_acq((int*)(g_kd + DM * 768 + blockIdx.x * 64));
                __nanosleep(KEEP);
            }
        }
    } else {
        reg_inc<240>();
        const int nq = rank == 0 ? 6 : 5;
        const int u0 = rank == 0 ? 0 : 1 + 5 * rank;
        const int v0 = rank == 0 ? -6 : 3 * rank - 6;
        const int gw = rank * 8 + w;
        const int ks0 = gw < 16 ? 11 * gw : 176 + 10 * (gw - 16);
        const int nko = gw < 16 ? 11 : 10;
        const uint32_t wr = sb + w * CH_WREG, bar0 = sb + CH_BAR + 64 + w * 16, bar1 = bar0 + 8;
        uint32_t wa[36][4];
        const uint32_t vst = sb + CH_PART + w * 2048;
        const int cq = h * DH + 8 * u0, cv = h * DH + 16 * (v0 + 6);
        const int r8 = lane >> 2, p = lane & 3;
        const bf16* src = p >= 2 ? ((p & 1) ? Wk : Wq) + cq + 32 : rank == 0 ? ((p & 1) ? Wk : Wq) + cq + 40 : Wv + cv - 16 + 8 * p;
        src += (size_t)(128 * w + r8) * HD;
        auto cp_rows = [&](int kh) {
            cp16(wr + ((kh >> 1) * 2 + (p >> 1)) * 512 + ((kh & 1) * 2 + (p & 1)) * 128 + r8 * 16, src + (size_t)kh * 8 * HD);
        };
        {
            int d = blockIdx.x * 8 + w, t = 0;
            const int d1 = 768 + blockIdx.x * 3 + w, nt = (w < 3 && d1 < DM) ? 32 : 16;
            const uint32_t stg = wr + 4096;
            KgRaw raw, raw1;
            kg_load(raw, P, d, lane);
            kg_load(raw1, P, min(d1, DM - 1), lane);
            float kd[5][4], k2048;
#pragma unroll 1
            for (int i = -LDW; i < 9 || t < nt; i++) {
                if (i >= 0 && i < 9) {
                    const uint32_t bar = bar0 + (i & 1) * 8;
                    if (i >= 2) mbar_wait(bar, ((i >> 1) - 1) & 1);
                    if (elect()) {
                        mbar_expect(bar, 2048);
                        if (i < 8) tma2d(wr + 8192 + (i & 1) * 8192 + (i >> 1) * 2048, (i & 1) ? &mk : &mq, cq, 128 * w + 32 * (i >> 1), bar);
                        else tma2d(vst, &mv, cv, 128 * w, bar);
                    }
                    if (i < 8) cp_rows(i);
                }
#pragma unroll 1
                for (int e = min(t + KGS, nt); t < e; t++) {
                    if ((t & 15) == 0) {
                        k2048 = kg_params(raw, stg, lane);
#pragma unroll
                        for (int j = 0; j < 20; j++) kd[j >> 2][j & 3] = 0.f;
                    }
                    uint32_t ka[4][4], kb[5][2];
                    kg_step(ka, kb, stg + ((t & 15) * 8 + (lane & 3)) * 16, stg + 2048 + ((t & 15) * 8 + (lane & 3)) * 8, (float)(lane >> 2));
                    kg_mma(kd, ka, kb);
                    if ((t & 15) == 15) { kg_store(kd, k2048, stg, d, lane); raw = raw1; d = d1; }
                }
            }
        }
        const uint32_t lrow = ((lane >> 4) * 8 + (lane & 7)) * 64, lsw = (lane >> 1) & 3, lh = (lane >> 3) & 1;
        mbar_wait(bar1, 1); mbar_wait(bar0, 0);
#pragma unroll
        for (int i = 0; i < 32; i++) ldsm4t(wa[i], wr + 8192 + lh * 8192 + (i & 7) * 1024 + lrow + (((i >> 3) ^ lsw) << 4));
#pragma unroll
        for (int i = 0; i < 4; i++) ldsm4t(wa[32 + i], vst + (i >> 1) * 1024 + lrow + ((((i & 1) * 2 + lh) ^ lsw) << 4));
        asm volatile("fence.proxy.async.shared::cta;" ::"r"(wa[31][0]), "r"(wa[35][0]) : "memory");
        __syncwarp();
#pragma unroll 1
        for (int i = 9; i < 18; i++) {
            const uint32_t bar = bar0 + (i & 1) * 8;
            if (i >= 11) mbar_wait(bar, ((i >> 1) - 1) & 1);
            if (elect()) {
                const int j = 2 * (i - 12), nb = min(2, nko - j);
                mbar_expect(bar, i < 12 ? 2048 : nb * 1024);
                if (i < 12) tma2d(wr + 8192 + (i - 9) * 2048, &mv, cv, 128 * w + 32 * (i - 8), bar);
                else {
                    if (nb > 0) tma2d(wr + 14336 + j * 1024, &mo, 32 * h, 16 * (ks0 + j), bar);
                    if (nb > 1) tma2d(wr + 15360 + j * 1024, &mo, 32 * h, 16 * (ks0 + j + 1), bar);
                }
            }
            if (i < 17) cp_rows(i - 1);
        }
        mbar_wait(bar0, 0); mbar_wait(bar1, 0);
#pragma unroll 1
        for (int i0 = -1; i0 < 17; i0 += 6) {
            uint32_t x[6][2][4];
#pragma unroll
            for (int i = 0; i < 6; i++) {
                const uint32_t a = wr + 8192 + max(i0 + i, 0) * 1024 + lrow;
                ldsm4t(x[i][0], a + ((lh ^ lsw) << 4)); ldsm4t(x[i][1], a + (((2 + lh) ^ lsw) << 4));
            }
            if (i0 == 11 && nko == 10) {
#pragma unroll
                for (int j = 0; j < 8; j++) x[5][j >> 2][j & 3] = 0;
            }
            __syncwarp();
#pragma unroll
            for (int i = 0; i < 6; i++) {
                const uint32_t a = wr + 8192 + max(i0 + i, 0) * 1024 + lane * 16;
                stsm4t(a, x[i][0][0], x[i][0][1], x[i][0][2], x[i][0][3]); stsm4t(a + 512, x[i][1][0], x[i][1][1], x[i][1][2], x[i][1][3]);
            }
        }
        asm volatile("cp.async.wait_all;" ::: "memory");
        asm volatile("barrier.cluster.wait.aligned;" ::: "memory");
        bar_sync(1, 256);
        mbar_wait_long(sb + CH_BAR + 16, 0);
        const int side = __shfl_sync(0xffffffffu, *(volatile int*)(smem + CH_BAR + 28), 0);
        if (w >= nq) chain_loop<true>(wa, sb, w, lane, rank, h, side);
        else chain_loop<false>(wa, sb, w, lane, rank, h, side);
    }
}

constexpr int G_STAGE = 49152, G_NST = 4;
constexpr int G_STG = G_NST * G_STAGE;
constexpr int G_BAR = G_STG + 32768;
constexpr int G_SMEM = G_BAR + 256 + 1024;

#define WLOG(e)
constexpr int IT_QA = 0, IT_O = 1, IT_S4 = 2, IT_END = 3, IT_KV = 4;
#define O_WIDE 14
#define PING 1
#define S4DIR 5
#define S4REL 4
#define KVI 2
#define KVF 2
#define KVS 8
#define STM 0
__device__ __forceinline__ void st_out(uint32_t* p, uint32_t v) {
    if (STM == 0) *p = v;
    else if (STM == 1) __stcs(p, v);
    else asm volatile("st.global.L1::no_allocate.u32 [%0], %1;" ::"l"(p), "r"(v) : "memory");
}
#define Q_S1 0
#define Q_B0 10
#define Q_T0 8
__device__ __forceinline__ int queue_item(int q) {
    if (q < 512) return (IT_KV << 16) | ((q >> 5) << 8) | (q & 31);
    q -= 512;
    if (q < Q_B0 * Q_T0) return (IT_QA << 16) | ((q % Q_B0) << 8) | (q / Q_B0);
    if (q < O_WIDE * Q_T0) return (IT_QA << 16) | ((q / Q_T0) << 8) | (q % Q_T0);
    if (q < O_WIDE * 16) return (IT_QA << 16) | ((q % O_WIDE) << 8) | (q / O_WIDE);
    q -= O_WIDE * 16;
    if (q < Q_S1) return (IT_S4 << 16) | q;
    q -= Q_S1;
    if (q < (16 - O_WIDE) * 8) return (IT_O << 16) | ((O_WIDE + (q >> 3)) << 8) | (q & 7);
    q -= (16 - O_WIDE) * 8;
    if (q < 128 - Q_S1) return (IT_S4 << 16) | (Q_S1 + q);
    return IT_END << 16;
}
constexpr int N_LATE = O_WIDE * 4 + (16 - O_WIDE) * 16;
static_assert(N_LATE <= 96, "first items of the late CTAs");
__device__ __forceinline__ int late_item(int j) {
    if (j < O_WIDE * 4) return (IT_O << 16) | ((j >> 2) << 8) | (j & 3);
    j -= O_WIDE * 4;
    return (IT_QA << 16) | ((O_WIDE + (j >> 4)) << 8) | (j & 15);
}
__device__ __forceinline__ void tma2d_store(const CUtensorMap* m, uint32_t src, int c0, int c1) {
    asm volatile("cp.async.bulk.tensor.2d.global.shared::cta.bulk_group [%0, {%2, %3}], [%1];" ::"l"(m), "r"(src), "r"(c0), "r"(c1) : "memory");
}

__device__ __forceinline__ void wgmma_s64(float (&d)[32], uint32_t a0, uint32_t a1, uint32_t a2, uint32_t a3, uint64_t db, int acc) {
    asm volatile("{.reg .pred p; setp.ne.b32 p, %37, 0;\n"
        "wgmma.mma_async.sync.aligned.m64n64k16.f32.bf16.bf16 {"
        "%0,%1,%2,%3,%4,%5,%6,%7,%8,%9,%10,%11,%12,%13,%14,%15,"
        "%16,%17,%18,%19,%20,%21,%22,%23,%24,%25,%26,%27,%28,%29,%30,%31"
        "}, {%32,%33,%34,%35}, %36, p, 1, 1, 0;}"
        : "+f"(d[0]), "+f"(d[1]), "+f"(d[2]), "+f"(d[3]), "+f"(d[4]), "+f"(d[5]), "+f"(d[6]), "+f"(d[7]), "+f"(d[8]), "+f"(d[9]), "+f"(d[10]), "+f"(d[11]), "+f"(d[12]), "+f"(d[13]), "+f"(d[14]), "+f"(d[15]), "+f"(d[16]), "+f"(d[17]), "+f"(d[18]), "+f"(d[19]), "+f"(d[20]), "+f"(d[21]), "+f"(d[22]), "+f"(d[23]), "+f"(d[24]), "+f"(d[25]), "+f"(d[26]), "+f"(d[27]), "+f"(d[28]), "+f"(d[29]), "+f"(d[30]), "+f"(d[31])
        : "r"(a0), "r"(a1), "r"(a2), "r"(a3), "l"(db), "r"(acc));
}
__device__ __forceinline__ void wgmma_s16(float (&d)[8], uint32_t a0, uint32_t a1, uint32_t a2, uint32_t a3, uint64_t db, int acc) {
    asm volatile("{.reg .pred p; setp.ne.b32 p, %13, 0;\n"
        "wgmma.mma_async.sync.aligned.m64n16k16.f32.bf16.bf16 {"
        "%0,%1,%2,%3,%4,%5,%6,%7"
        "}, {%8,%9,%10,%11}, %12, p, 1, 1, 0;}"
        : "+f"(d[0]), "+f"(d[1]), "+f"(d[2]), "+f"(d[3]), "+f"(d[4]), "+f"(d[5]), "+f"(d[6]), "+f"(d[7])
        : "r"(a0), "r"(a1), "r"(a2), "r"(a3), "l"(db), "r"(acc));
}
__device__ __forceinline__ void wgmma_v128(float (&d)[64], uint32_t a0, uint32_t a1, uint32_t a2, uint32_t a3, uint64_t db, int acc) {
    asm volatile("{.reg .pred p; setp.ne.b32 p, %69, 0;\n"
        "wgmma.mma_async.sync.aligned.m64n128k16.f32.bf16.bf16 {"
        "%0,%1,%2,%3,%4,%5,%6,%7,%8,%9,%10,%11,%12,%13,%14,%15,"
        "%16,%17,%18,%19,%20,%21,%22,%23,%24,%25,%26,%27,%28,%29,%30,%31,"
        "%32,%33,%34,%35,%36,%37,%38,%39,%40,%41,%42,%43,%44,%45,%46,%47,"
        "%48,%49,%50,%51,%52,%53,%54,%55,%56,%57,%58,%59,%60,%61,%62,%63"
        "}, {%64,%65,%66,%67}, %68, p, 1, 1, 1;}"
        : "+f"(d[0]), "+f"(d[1]), "+f"(d[2]), "+f"(d[3]), "+f"(d[4]), "+f"(d[5]), "+f"(d[6]), "+f"(d[7]), "+f"(d[8]), "+f"(d[9]), "+f"(d[10]), "+f"(d[11]), "+f"(d[12]), "+f"(d[13]), "+f"(d[14]), "+f"(d[15]), "+f"(d[16]), "+f"(d[17]), "+f"(d[18]), "+f"(d[19]), "+f"(d[20]), "+f"(d[21]), "+f"(d[22]), "+f"(d[23]), "+f"(d[24]), "+f"(d[25]), "+f"(d[26]), "+f"(d[27]), "+f"(d[28]), "+f"(d[29]), "+f"(d[30]), "+f"(d[31]), "+f"(d[32]), "+f"(d[33]), "+f"(d[34]), "+f"(d[35]), "+f"(d[36]), "+f"(d[37]), "+f"(d[38]), "+f"(d[39]), "+f"(d[40]), "+f"(d[41]), "+f"(d[42]), "+f"(d[43]), "+f"(d[44]), "+f"(d[45]), "+f"(d[46]), "+f"(d[47]), "+f"(d[48]), "+f"(d[49]), "+f"(d[50]), "+f"(d[51]), "+f"(d[52]), "+f"(d[53]), "+f"(d[54]), "+f"(d[55]), "+f"(d[56]), "+f"(d[57]), "+f"(d[58]), "+f"(d[59]), "+f"(d[60]), "+f"(d[61]), "+f"(d[62]), "+f"(d[63])
        : "r"(a0), "r"(a1), "r"(a2), "r"(a3), "l"(db), "r"(acc));
}

__device__ __forceinline__ void attn_scores(float (&sx)[32], float (&sm)[8], const uint32_t (&q)[32], uint32_t sk) {
    const uint64_t dx = mkdesc(sk, 1024, 128, 0), dm = mkdesc(sk + 16384, 256, 128, 0);
    wg_fence();
#pragma unroll
    for (int ks = 0; ks < 8; ks++) {
        wgmma_s64(sx, q[4 * ks], q[4 * ks + 1], q[4 * ks + 2], q[4 * ks + 3], dx + ks * 128, ks);
        wgmma_s16(sm, q[4 * ks], q[4 * ks + 1], q[4 * ks + 2], q[4 * ks + 3], dm + ks * 32, ks);
    }
    wg_commit();
}
template <bool HI>
__device__ __forceinline__ void attn_softmax(uint32_t (&p)[2][20], const float (&sx)[2][32], const float (&sm)[2][8], bool sb, int lane) {
    constexpr int NF = HI ? 2 : 0, NT = NF + 3;
    const int gt = (lane >> 2) - 2 * (lane & 3);
    const float cs = 0.08838834764831845f * 1.4426950408889634f;
    float s[2][NT][4], m[4], l[4];
#pragma unroll
    for (int h = 0; h < 2; h++) {
#pragma unroll
        for (int j = 0; j < NT; j++)
#pragma unroll
            for (int e = 0; e < 4; e++) s[h][j][e] = j == NT - 1 ? (sb ? sm[h][4 + e] : sm[h][e]) : (sb ? sx[h][16 + 4 * j + e] : sx[h][4 * j + e]);
        if (gt < 0) s[h][NF][0] = s[h][NF + 1][2] = -INFINITY;
        if (gt < 1) s[h][NF][1] = s[h][NF + 1][3] = -INFINITY;
        m[2 * h] = fmaxf(s[h][0][0], s[h][0][1]); m[2 * h + 1] = fmaxf(s[h][0][2], s[h][0][3]);
#pragma unroll
        for (int j = 1; j < NT; j++) {
            if (j != NF + 1) m[2 * h] = fmaxf(m[2 * h], fmaxf(s[h][j][0], s[h][j][1]));
            m[2 * h + 1] = fmaxf(m[2 * h + 1], fmaxf(s[h][j][2], s[h][j][3]));
        }
    }
#pragma unroll
    for (int r = 0; r < 4; r++) m[r] = fmaxf(m[r], __shfl_xor_sync(0xffffffffu, m[r], 1));
#pragma unroll
    for (int r = 0; r < 4; r++) m[r] = fmaxf(m[r], __shfl_xor_sync(0xffffffffu, m[r], 2)) * -cs;
#pragma unroll
    for (int r = 0; r < 4; r++) {
        l[r] = 0.f;
#pragma unroll
        for (int j = 0; j < NT; j++)
            if ((r & 1) || j != NF + 1) {
                float* v = &s[r >> 1][j][2 * (r & 1)];
                v[0] = ex2(fmaf(v[0], cs, m[r])); v[1] = ex2(fmaf(v[1], cs, m[r]));
                l[r] += v[0] + v[1];
            }
    }
#pragma unroll
    for (int r = 0; r < 4; r++) l[r] += __shfl_xor_sync(0xffffffffu, l[r], 1);
#pragma unroll
    for (int r = 0; r < 4; r++) { l[r] += __shfl_xor_sync(0xffffffffu, l[r], 2); asm("rcp.approx.ftz.f32 %0, %0;" : "+f"(l[r])); }
    const uint32_t ma = sb ? 0u : ~0u;
#pragma unroll
    for (int h = 0; h < 2; h++)
#pragma unroll
        for (int j = 0; j < 5; j++) {
            const bool on = j == 4 || j < NF + 2;
            const int k = j == 4 ? NT - 1 : on ? j : 0, ia = j < 4 ? 2 * j : 16, ib = j < 4 ? 8 + 2 * j : 18;
            const uint32_t x = on && j != NF + 1 ? pack_bf16(s[h][k][0] * l[2 * h], s[h][k][1] * l[2 * h]) : 0;
            const uint32_t y = on ? pack_bf16(s[h][k][2] * l[2 * h + 1], s[h][k][3] * l[2 * h + 1]) : 0;
            asm volatile("and.b32 %0, %4, %6; and.b32 %1, %5, %6; and.b32 %2, %4, %7; and.b32 %3, %5, %7;"
                : "=&r"(p[h][ia]), "=&r"(p[h][ia + 1]), "=&r"(p[h][ib]), "=&r"(p[h][ib + 1]) : "r"(x), "r"(y), "r"(ma), "r"(~ma));
        }
}
__device__ __forceinline__ void attn_pv(float (&o)[64], const uint32_t (&p)[20], uint32_t sv) {
    const uint64_t dx = mkdesc(sv, 128, 1024, 0), dm = mkdesc(sv + 16384, 128, 256, 0);
    wg_fence();
#pragma unroll
    for (int ks = 0; ks < 5; ks++) wgmma_v128(o, p[4 * ks], p[4 * ks + 1], p[4 * ks + 2], p[4 * ks + 3], ks < 4 ? dx + ks * 16 : dm, ks);
    wg_commit();
}
__device__ __forceinline__ void attn_stage(const float (&o)[64], uint32_t dst) {
#pragma unroll
    for (int u = 0; u < 16; u += 2)
        stsm4(dst + (u >> 3) * 8192 + (u & 7) * 128, pack_bf16(o[4 * u], o[4 * u + 1]), pack_bf16(o[4 * u + 2], o[4 * u + 3]),
              pack_bf16(o[4 * u + 4], o[4 * u + 5]), pack_bf16(o[4 * u + 6], o[4 * u + 7]));
}

template <int BN, int NKB, bool BLOCKED_A>
__device__ __forceinline__ void mainloop(float (&acc)[BN / 2], uint32_t sb, int wgi, uint32_t full, uint32_t empty, int& it, bool elect) {
#pragma unroll
    for (int j = 0; j < BN / 2; j++) acc[j] = 0.f;
#pragma unroll 1
    for (int k4 = 0; k4 < NKB; k4 += 4) {
#pragma unroll
        for (int st = 0; st < 4; st++, it++) {
            mbar_wait_long(full + 8 * st, (it >> 2) & 1);
            const uint64_t da = BLOCKED_A ? mkdesc(sb + st * G_STAGE + wgi * 8192, 128, 1024, 0) : mkdesc(sb + st * G_STAGE + wgi * 8192, 16, 1024, 1);
            const uint64_t db = mkdesc(sb + st * G_STAGE + 16384, 8192, 1024, 1);
            wg_fence();
#pragma unroll
            for (int k = 0; k < 4; k++) {
                if constexpr (BN == 256) wgmma256(acc, da + k * (BLOCKED_A ? 16 : 2), db + k * 128, 1);
                else wgmma128(acc, da + k * (BLOCKED_A ? 16 : 2), db + k * 128, 1);
            }
            wg_commit();
            if (k4 | st) {
                wg_wait<1>();
                if (elect) mbar_arrive(empty + 8 * ((st + 3) & 3));
            }
        }
    }
    wg_wait<0>();
    if (elect) mbar_arrive(empty + 8 * 3);
}

__device__ __forceinline__ uint32_t n6_a(int st) { return st < 4 ? st * G_STAGE : (2 * st - 8) * G_STAGE + 32768; }
__device__ __forceinline__ uint32_t n6_b(int st) { return st < 4 ? st * G_STAGE + 16384 : (2 * st - 7) * G_STAGE + 32768; }
__device__ __forceinline__ uint32_t n6_bar(int st) { return st < 4 ? 8 * st : 96 + 8 * st; }
__device__ __forceinline__ void mainloop6(float (&acc)[64], uint32_t sb, int wgi, uint32_t full, uint32_t empty, int& it, bool elect) {
#pragma unroll
    for (int j = 0; j < 64; j++) acc[j] = 0.f;
    int st = 0, prev = 0, r = 0;
#pragma unroll 1
    for (int kb = 0; kb < 64; kb++) {
        mbar_wait_long(full + n6_bar(st), ((st < 4 ? it >> 2 : 0) + r) & 1);
        const uint64_t da = mkdesc(sb + n6_a(st) + wgi * 8192, 128, 1024, 0), db = mkdesc(sb + n6_b(st), 8192, 1024, 1);
        wg_fence();
#pragma unroll
        for (int k = 0; k < 4; k++) wgmma128(acc, da + k * 16, db + k * 128, 1);
        wg_commit();
        if (kb) {
            wg_wait<1>();
            if (elect) mbar_arrive(empty + n6_bar(prev));
        }
        prev = st;
        if (++st == 6) { st = 0; r++; }
    }
    wg_wait<0>();
    if (elect) mbar_arrive(empty + 8 * 3);
    it += 44;
}

template <int BN>
__device__ __forceinline__ void o_item(uint32_t sb, int wgi, int wi, int lane, uint32_t full, uint32_t empty, int& it, const CUtensorMap* mout,
                                       int row0, int col0, uint32_t stgpar) {
    float acc[BN / 2];
    if constexpr (BN == 256) mainloop<BN, 64, true>(acc, sb, wgi, full, empty, it, lane == 0);
    else mainloop6(acc, sb, wgi, full, empty, it, lane == 0);
    ST((row0 >> 4) + (col0 / BN), wgi * 4 + wi, 10);
    mbar_wait(full + 104, stgpar);
    const uint32_t stg = sb + G_STG + (wgi * 4 + wi) * 4096;
    const int r = lane & 15, cu = lane >> 4;
#pragma unroll
    for (int hf = 0; hf < BN / 128; hf++) {
        if (elect()) asm volatile("cp.async.bulk.wait_group.read 0;" ::: "memory");
        __syncwarp();
#pragma unroll
        for (int j = 0; j < 8; j++) {
            const float* a = acc + hf * 64 + j * 8;
            stsm4(stg + (j >> 2) * 2048 + r * 128 + ((((j & 3) * 2 + cu) ^ (r & 7)) << 4),
                  pack_bf16(a[0], a[1]), pack_bf16(a[2], a[3]), pack_bf16(a[4], a[5]), pack_bf16(a[6], a[7]));
        }
        asm volatile("fence.proxy.async.shared::cta;" ::: "memory");
        __syncwarp();
        if (elect()) {
            tma2d_store(mout, stg, col0 + hf * 128, row0 + wgi * 64 + wi * 16);
            tma2d_store(mout, stg + 2048, col0 + hf * 128 + 64, row0 + wgi * 64 + wi * 16);
            asm volatile("cp.async.bulk.commit_group;" ::: "memory");
        }
    }
}

constexpr int S4_KD = 32768;
constexpr int S4_CH = 2 * G_STAGE;
constexpr int S4_HALF = 2304;
constexpr int S4_WD = 2 * S4_HALF;
constexpr int S4_T2 = S4_WD + 2304;
constexpr int S4_T3 = S4_T2 + 1024;
constexpr int S4_STRIDE = S4_T3 + 640 + 16;
__device__ __forceinline__ uint32_t addz(uint32_t x, uint32_t z) { uint32_t r; asm volatile("add.u32 %0, %1, %2;" : "=r"(r) : "r"(x), "r"(z)); return r; }
__device__ __forceinline__ uint32_t lds16(uint32_t a) { uint32_t v; asm volatile("ld.shared.u16 %0, [%1];" : "=r"(v) : "r"(a) : "memory"); return v; }
__device__ __forceinline__ uint32_t ldsu(uint32_t a) { return __float_as_uint(lds32(a)); }

template <int E0, int NE, int KP>
__device__ __forceinline__ void s4_windows(float (&acc)[8][2][4], uint32_t ut, uint32_t tw, int rho, int w, int lane, uint32_t z) {
    const int gt = (lane >> 2) - 2 * (lane & 3), p0 = rho == 16 ? -3 : -2, c = (lane >> 3) + p0;
    uint32_t band[2][4], ta[NE][4];
    {
        const uint64_t ones = ((uint64_t)((2u << 2 * w) - 1) << 32) >> (8 * p0 + 24 - gt + rho + w);
        uint32_t f[5];
#pragma unroll
        for (int m = 0; m < 5; m++) f[m] = ((((uint32_t)(ones >> (8 * m)) & 3) * 0x8001u) & 0x10001u) * 0x3F80u;
#pragma unroll
        for (int j = 0; j < 2; j++) { band[j][0] = f[2 * j + 1]; band[j][1] = addz(f[2 * j], z); band[j][2] = f[2 * j + 2]; band[j][3] = addz(f[2 * j + 1], z); }
    }
#pragma unroll
    for (int e = 0; e < NE; e++)
        asm volatile("ld.shared.u32 %0, [%4]; ld.shared.u32 %1, [%4+%5]; ld.volatile.shared.u32 %2, [%4+%6]; ld.volatile.shared.u32 %3, [%4];"
            : "=r"(ta[e][0]), "=r"(ta[e][1]), "=r"(ta[e][2]), "=r"(ta[e][3]) : "r"(tw + 16 * (E0 + e) * KP), "n"(8 * KP), "n"(-8 * KP) : "memory");
    const uint32_t ua = ut + (c & 1) * S4_HALF + (16 + (lane & 7) + (c >> 1)) * 16;
#pragma unroll
    for (int J = 0; J < 8 - E0; J++) {
        uint32_t u0[4], u1[4];
        ldsm4(u0, ua + J * 256); ldsm4(u1, ua + J * 256 + 128);
        float s0[4], s1[4];
        mma16z(s0, band[0], u0[0], u0[1]); mma16z(s1, band[0], u1[0], u1[1]);
        mma16(s0, band[1], u0[2], u0[3]); mma16(s1, band[1], u1[2], u1[3]);
        const uint32_t b00 = pack_bf16(s0[0], s0[1]), b01 = pack_bf16(s1[0], s1[1]), b10 = pack_bf16(s0[2], s0[3]), b11 = pack_bf16(s1[2], s1[3]);
#pragma unroll
        for (int e = 0; e < NE; e++)
            if (J + E0 + e < 8) { mma16(acc[J + E0 + e][0], ta[e], b00, b01); mma16(acc[J + E0 + e][1], ta[e], b10, b11); }
    }
}
template <int D0, int D1>
__device__ __forceinline__ void s4_dense(float (&acc)[8][2][4], uint32_t ua, const uint32_t (&b0)[4], const uint32_t (&b1)[4]) {
#pragma unroll
    for (int J = 0; J < 8 - D0; J++) {
        uint32_t a[4];
        ldsm4(a, ua + J * 256);
        mma16(acc[J + D0][0], a, b0[0], b0[1]); mma16(acc[J + D0][1], a, b0[2], b0[3]);
        if (J + D1 < 8) { mma16(acc[J + D1][0], a, b1[0], b1[1]); mma16(acc[J + D1][1], a, b1[2], b1[3]); }
    }
}
__device__ __forceinline__ void s4_words(uint32_t (&b)[4], uint32_t wd) {
    asm volatile("ld.shared.u32 %0, [%4]; ld.shared.u32 %1, [%4+-32]; ld.shared.u32 %2, [%4+32]; ld.volatile.shared.u32 %3, [%4];"
        : "=r"(b[0]), "=r"(b[1]), "=r"(b[2]), "=r"(b[3]) : "r"(wd) : "memory");
}

__device__ __forceinline__ void s4_item(uint32_t sb, int cw, int lane, int item, const bf16* __restrict__ dsk, uint32_t empty, const CUtensorMap* my, uint32_t stgpar,
                                        bf16* __restrict__ out, uint32_t nbar, uint32_t npar, uint32_t nslot) {
    const int gt = (lane >> 2) - 2 * (lane & 3);
    const uint32_t ch = sb + S4_CH + cw * S4_STRIDE, kd = sb + S4_KD + cw * 1536;
    const __nv_bfloat162 dk = __bfloat162bfloat162(dsk[item * 8 + cw]);
    ST(item, cw, 0);
    asm volatile("st.shared.v4.u32 [%0], {%1,%1,%1,%1};" ::"r"(ch + (lane >> 4) * S4_HALF + (lane & 15) * 16), "r"(0) : "memory");
    const uint32_t tch = sb + S4_CH + (lane & 7) * S4_STRIDE + ((lane >> 3) & 1) * S4_HALF + (16 + 16 * cw + (lane >> 4)) * 16;
#pragma unroll
    for (int i = 0; i < 8; i++) {
        uint32_t x[4];
        ldsm4t(x, sb + cw * 4096 + i * 512 + lane * 16);
        stsm4(tch + i * 32, x[0], x[1], x[2], x[3]);
    }
    const uint32_t k1024 = lds16(kd + 1024);
    {
        auto st4 = [](uint32_t a, uint32_t x, uint32_t y, uint32_t u, uint32_t v) {
            asm volatile("st.shared.v4.u32 [%0], {%1,%2,%3,%4};" ::"r"(a), "r"(x), "r"(y), "r"(u), "r"(v) : "memory");
        };
        const float4 p = lds128(kd + lane * 16);
        const uint32_t p0 = __float_as_uint(p.x), p1 = __float_as_uint(p.y), p2 = __float_as_uint(p.z), p3 = __float_as_uint(p.w);
        const uint32_t pm = lane ? ldsu(kd + lane * 16 - 4) : 0;
        const uint32_t wa = ch + S4_WD + 64 + lane * 32;
        st4(wa, __byte_perm(p0, pm, 0x7610), __byte_perm(p0, 0, 0x1032), __byte_perm(p1, p0, 0x7610), __byte_perm(p1, 0, 0x1032));
        st4(wa + 16, __byte_perm(p2, p1, 0x7610), __byte_perm(p2, 0, 0x1032), __byte_perm(p3, p2, 0x7610), __byte_perm(p3, 0, 0x1032));
        const float2 q = lds64(kd + 512 + lane * 8);
        const uint32_t q0 = __float_as_uint(q.x), q1 = __float_as_uint(q.y), q2 = ldsu(kd + 520 + lane * 8), k255 = ldsu(kd + 508);
        st4(wa + 1024, lane ? __byte_perm(q0, 0, 0x1010) : __byte_perm(q0, k255, 0x7610), __byte_perm(q0, 0, 0x1010), __byte_perm(q0, 0, 0x1032), __byte_perm(q1, q0, 0x7610));
        st4(wa + 1040, __byte_perm(q1, 0, 0x1010), __byte_perm(q1, 0, 0x1010), __byte_perm(q1, 0, 0x1032), __byte_perm(q2, q1, 0x7610));
        const uint32_t k512 = lane == 4 ? lds16(kd + 768) : 0;
        if (lane < 16) st4(ch + S4_WD + (lane < 4 ? 0 : 2048) + lane * 16, k512 * 0x10001u, k512 * 0x10001u, k512 * 0x10001u, k512 << 16);
        const float2 c = lds64(kd + 768 + lane * 8), d = lds64(kd + 760 + lane * 8);
        const uint32_t c0 = __float_as_uint(c.x), c1 = __float_as_uint(c.y), c2 = ldsu(kd + 776 + lane * 8);
        const uint32_t d0 = lane ? __float_as_uint(d.x) : 0, d1 = lane ? __float_as_uint(d.y) : 0, d2 = lane ? c0 : 0;
        st4(ch + S4_T2 + 256 + lane * 16, __byte_perm(c0, d0, 0x7632), __byte_perm(c1, d1, 0x5410), __byte_perm(c1, d1, 0x7632), __byte_perm(c2, d2, 0x5410));
        const uint32_t m = lane == 31 ? 0xFFFF0000u : 0;
        st4(ch + S4_T2 + (lane < 16 ? lane : lane == 31 ? 48 : lane + 33) * 16, c0 & m, (c1 << 16) & m, c1 & m, (c2 << 16) & m);
        const float2 e = lds64(kd + 1024 + lane * 8);
        const uint32_t e0 = __float_as_uint(e.x), e1 = __float_as_uint(e.y), e2 = ldsu(kd + 1032 + lane * 8), em = ldsu(kd + 1020 + lane * 8);
        st4(ch + S4_T3 + 128 + lane * 16, __byte_perm(e0, lane ? em : 0, 0x7632), __byte_perm(e1, lane ? e0 : 0, 0x5410), __byte_perm(e1, e0, 0x7632), __byte_perm(e2, e1, 0x5410));
        if (lane < 8) st4(ch + S4_T3 + lane * 16, 0, 0, 0, 0);
    }
    bar_sync(2, 256);
    ST(item, cw, 1);
    const uint32_t z = ldsu(ch);
    float acc[8][2][4];
#pragma unroll
    for (int j = 0; j < 16; j++) acc[j >> 1][j & 1][0] = acc[j >> 1][j & 1][1] = acc[j >> 1][j & 1][2] = acc[j >> 1][j & 1][3] = 0.f;
#pragma unroll 1
    for (int r = 1; r <= 4; r++) s4_windows<2, 3, 16>(acc, ch, ch + S4_T2 + (gt - 16) * 16 + 4 * r - 4, 4 * r, 2 - (r & 1), lane, z);
    ST(item, cw, 2);
#pragma unroll 1
    for (int r = 1; r <= 2; r++) s4_windows<4, 4, 8>(acc, ch, ch + S4_T3 + (gt - 48) * 8 + 4 * r - 4, 8 * r, 2 + r, lane, z);
    ST(item, cw, 3);
    const uint32_t ua = ch + (lane >> 4) * S4_HALF + (16 + (lane & 15)) * 16, wd = ch + S4_WD + 64 + gt * 4;
#pragma unroll 1
    for (int q = 0; q < 2; q++) {
        uint32_t b0[4], b1[4];
        s4_words(b0, wd + (q + 32) * 64);
#pragma unroll
        for (int j = 0; j < 4; j++) {
            const int x = 16 * q + gt + (j == 1 ? -8 : j == 2 ? 8 : 0) - 3;
            b1[j] = addz(((unsigned)x < 2u ? k1024 : 0u) | ((unsigned)(x - 1) < 2u ? k1024 << 16 : 0u), z);
        }
        s4_dense<2, 4>(acc, ua - q * 16, b0, b1);
    }
    {
        uint32_t b0[4], b1[4], c0[4], c1[4];
        s4_words(b0, wd); s4_words(b1, wd + 1024);
#pragma unroll 1
        for (int q = 0; q < 16; q += 2) {
            s4_words(c0, wd + q * 64 + 64); s4_words(c1, wd + q * 64 + 64 + 1024);
            s4_dense<0, 1>(acc, ua - q * 16, b0, b1);
            s4_words(b0, wd + q * 64 + 128); s4_words(b1, wd + q * 64 + 128 + 1024);
            s4_dense<0, 1>(acc, ua - q * 16 - 16, c0, c1);
            if (q == S4REL && lane == 0) { mbar_arrive(empty); mbar_arrive(empty + 8); }
        }
    }
    ST(item, cw, 4);
    mbar_wait(empty + 72, stgpar);
    if (elect()) asm volatile("cp.async.bulk.wait_group.read 0;" ::: "memory");
    __syncwarp();
#pragma unroll
    for (int I = 0; I < 8; I++) {
        uint32_t u[4];
        ldsm4(u, ua + I * 256);
#pragma unroll
        for (int j = 0; j < 4; j++) {
            const uint32_t y = pack_bf16(acc[I][j >> 1][2 * (j & 1)], acc[I][j >> 1][2 * (j & 1) + 1]);
            const __nv_bfloat162 r = __hadd2_rn(*(const __nv_bfloat162*)&y, __hmul2_rn(*(const __nv_bfloat162*)&u[j], dk));
            u[j] = *(const uint32_t*)&r;
        }
        stsm4(ua + I * 256, u[0], u[1], u[2], u[3]);
    }
    bar_sync(2, 256);
    uint32_t y[8][4];
#pragma unroll
    for (int i = 0; i < 8; i++) ldsm4t(y[i], tch + i * 32);
    if (cw < S4DIR && mbar_test(nbar, npar) && ldsu(nslot) == (IT_END << 16)) {
        uint32_t* const dst = (uint32_t*)(out + (size_t)(cw * 256 + (lane >> 2)) * (2 * DM) + DM + item * 8) + (lane & 3);
#pragma unroll
        for (int i = 0; i < 32; i++) dst[i * 8 * DM] = y[i >> 2][i & 3];
        return;
    }
#pragma unroll
    for (int i = 0; i < 8; i++) stsm4(sb + G_STG + cw * 4096 + i * 512 + lane * 16, y[i][0], y[i][1], y[i][2], y[i][3]);
    asm volatile("fence.proxy.async.shared::cta;" ::: "memory");
    __syncwarp();
    if (elect()) {
        mbar_arrive(empty + 16); mbar_arrive(empty + 24);
        tma2d_store(my, sb + G_STG + cw * 4096, DM + item * 8, cw * 256);
        asm volatile("cp.async.bulk.commit_group;" ::: "memory");
    }
    ST(item, cw, 5);
}

struct Maps { CUtensorMap m[13]; };
__global__ void __launch_bounds__(384, 1)
worker_kernel(const __grid_constant__ Maps M, const bf16* __restrict__ dsk, bf16* __restrict__ out) {
    const CUtensorMap &mx = M.m[0], &mq = M.m[1], &mo = M.m[4], &mout = M.m[5], &mu = M.m[6], &my = M.m[7];
    extern __shared__ unsigned char smem_raw[];
    const uint32_t sb = (smem_u32(smem_raw) + 1023) & ~1023u;
    const uint32_t full = sb + G_BAR, empty = full + 32, ifull = full + 64, iempty = full + 80, islot = full + 96, stgbar = full + 104, sigbar = full + 112, sigslot = full + 120;
    const int tid = threadIdx.x, wg = tid >> 7, lane = tid & 31;
    int q0 = blockIdx.x;
    const int nfirst = min(32, (int)gridDim.x - 96), wide0 = q0 - ((int)gridDim.x - N_LATE);
    if (tid == 0 && q0 >= nfirst && wide0 < 0) q0 = nfirst + atomicAdd(g_ctr + C_NEXT, 1);
    if ((tid >> 5) == 1 && elect()) {
#pragma unroll
        for (int i = 0; i < 6; i++) { mbar_init(full + n6_bar(i), 1); mbar_init(empty + n6_bar(i), 8); }
#pragma unroll
        for (int i = 0; i < 2; i++) { mbar_init(ifull + 8 * i, 1); mbar_init(iempty + 8 * i, 8); }
        mbar_init(sigbar, 8); mbar_init(stgbar, 1);
        asm volatile("fence.mbarrier_init.release.cluster;" ::: "memory");
    }
    if ((tid >> 5) == 2 && elect()) {
#pragma unroll
        for (int i = 0; i < 13; i++) asm volatile("prefetch.tensormap [%0];" ::"l"(&M.m[i]) : "memory");
    }
    __syncthreads();
    if (wg == 0) {
        reg_dec<40>();
        if (tid >= 32 && tid < 64) {
            for (int n = 0;; n++) {
                mbar_wait_long(sigbar, n & 1);
                int item; asm volatile("ld.shared.u32 %0, [%1];" : "=r"(item) : "r"(sigslot + 4 * (n & 1)) : "memory");
                const int type = item >> 16, b = (item >> 8) & 255, i = item & 255;
                if (type == IT_END) break;
                if (type == IT_QA) {
                    if (elect()) {
#pragma unroll
                        for (int j = 0; j < 8; j++) {
                            const uint32_t src = sb + (j >= 4 ? G_STG + (j & 1) * 16384 : 3 * G_STAGE + (j & 1) * 20480) + ((j >> 1) & 1) * 8192;
                            asm volatile("cp.async.bulk.global.shared::cta.bulk_group [%0], [%1], 8192;"
                                ::"l"(g_ox + (size_t)(b * 64 + i * 4 + ((j >> 1) ^ 2)) * 8192 + (j & 1) * 4096), "r"(src) : "memory");
                            if ((j & 3) == 3) asm volatile("cp.async.bulk.commit_group;" ::: "memory");
                        }
                        asm volatile("cp.async.bulk.wait_group.read 1;" ::: "memory");
                        asm volatile("mbarrier.arrive.shared.b64 _, [%0], 8;" ::"r"(empty + 24) : "memory");
                        asm volatile("cp.async.bulk.wait_group 0;" ::: "memory");
                        mbar_arrive(stgbar);
                        asm volatile("fence.proxy.async.global;" ::: "memory");
                    }
                    __syncwarp();
                }
                if (type == IT_KV) { if (lane < 6) red_release(g_kvf + ((i & 15) * 6 + lane) * 16 + b, 1); }
                else if (lane == 0) red_release(g_ctr + C_QA_DONE + b, 1 << i);
            }
        } else if (tid < 32) {
            int it = 0;
            bool tables = false;
            if (!KVN) asm volatile("griddepcontrol.wait;" ::: "memory");
            for (int n = 0;; n++) {
                int item = 0;
                if (lane == 0) {
                    if (n) q0 = nfirst + atomicAdd(g_ctr + C_NEXT, 1);
                    item = n == 0 && wide0 >= 0 ? late_item(wide0) : queue_item(q0);
                }
                item = __shfl_sync(0xffffffffu, item, 0);
                mbar_wait(iempty + 8 * (n & 1), ((n >> 1) & 1) ^ 1);
                if (lane == 0) {
                    asm volatile("st.shared.u32 [%0], %1;" ::"r"(islot + 4 * (n & 1)), "r"(item) : "memory");
                    mbar_arrive(ifull + 8 * (n & 1));
                }
                const int type = item >> 16, b = (item >> 8) & 255, i = item & 255;
                bool ready = false;
                if (type == IT_QA || type == IT_KV) {
                    const CUtensorMap* mw = &mq + (type == IT_QA ? 0 : 1 + (i >> 4));
#pragma unroll 1
                    for (int kb = 0; kb < 16; kb++, it++) {
                        const int st = it & 3;
                        mbar_wait(empty + 8 * st, ((it >> 2) & 1) ^ 1);
                        if (elect()) {
                            mbar_expect(full + 8 * st, G_STAGE);
                            tma2d(sb + st * G_STAGE, &mx, kb * 64, b * 128, full + 8 * st);
                            tma3d(sb + st * G_STAGE + 16384, mw, 0, kb * 64, (i & 15) * 4, full + 8 * st);
                        }
                        if (type == IT_QA && kb == 3) ready = __all_sync(0xffffffffu, ld_acq(g_ctr + C_CHAIN + b) >= 96);
                        if (ready && kb < 11 && elect()) {
                            const size_t sh = (b * 4 + ((kb - 3) & 3)) * NH + i * 2;
                            asm volatile("cp.async.bulk.prefetch.L2.global [%0], 16384;" ::"l"((kb >= 7 ? g_vx : g_kx) + sh * 4096) : "memory");
                            asm volatile("cp.async.bulk.prefetch.L2.global [%0], 4096;" ::"l"((kb >= 7 ? g_vm : g_km) + sh * 1024) : "memory");
                        }
                    }
                }
                if (type == IT_QA) {
                    if (b == 15) asm volatile("griddepcontrol.wait;" ::: "memory");
                    else if (!ready) wait_ctr(g_ctr + C_CHAIN + b, 96);
                    tables = true;
                    asm volatile("fence.proxy.async.global;" ::: "memory");
#pragma unroll 1
                    for (int st = 0; st < 4; st++, it++) {
                        mbar_wait(empty + 8 * st, ((it >> 2) & 1) ^ 1);
                        if (elect()) {
                            mbar_expect(full + 8 * st, 4 * 10240);
#pragma unroll
                            for (int j = 0; j < 4; j++)
                                tma3d(sb + st * G_STAGE + (j >> 1) * 20480 + (j & 1) * 16384, &M.m[8 + (st >> 1) + (j & 1) * 2], 0, b * 4 + (j & 2),
                                      (i * 2 + (st & 1)) * 16, full + 8 * st);
                        }
                    }
                } else if (type == IT_O) {
                    const bool wide = b < O_WIDE;
                    const CUtensorMap* mw = wide ? &mo : &M.m[12];
                    int done = 0;
                    const int ns = wide ? 4 : 6;
#pragma unroll 1
                    for (int kb = 0, st = 0, r = 0; kb < 64; kb++) {
                        const uint32_t bo = n6_bar(st);
                        mbar_wait(empty + bo, (((st < 4 ? it >> 2 : 0) + r) & 1) ^ 1);
                        if (elect()) {
                            mbar_expect(full + bo, wide ? G_STAGE : 32768);
                            tma3d(sb + n6_b(st), mw, 0, kb * 64, wide ? i * 4 : i * 2, full + bo);
                        }
                        if (!(done >> (kb >> 2) & 1)) {
#pragma unroll 1
                            for (int sp = 0; sp < (1 << 20) && !((done = __shfl_sync(0xffffffffu, ld_acq(g_ctr + C_QA_DONE + b), 0)) >> (kb >> 2) & 1); sp++)
                                __nanosleep(64);
                            asm volatile("fence.proxy.async.global;" ::: "memory");
                        }
                        if (elect()) bulk_load(sb + n6_a(st), g_ox + (size_t)(b * 64 + kb) * 8192, 16384, full + bo);
                        if (++st == ns) { st = 0; r++; }
                    }
                    it += wide ? 64 : 44;
                } else if (type == IT_S4) {
                    mbar_wait(empty, ((it >> 2) & 1) ^ 1);
                    if (elect()) {
                        mbar_expect(full, 32768 + 12288);
#pragma unroll
                        for (int j = 0; j < 8; j++) tma2d(sb + j * 4096, &mu, i * 8, j * 256, full);
                    }
                    if (!tables) { wait_ctr(g_ctr + C_CHAIN, 96); asm volatile("fence.proxy.async.global;" ::: "memory"); }
                    tables = true;
                    if (elect()) bulk_load(sb + S4_KD, g_kd + i * 8 * 768, 12288, full);
#pragma unroll 1
                    for (int st = 1; st < 4; st++) { mbar_wait(empty + 8 * st, ((it >> 2) & 1) ^ 1); if (lane == 0) mbar_arrive(full + 8 * st); }
                    it += 4;
                    mbar_wait_long(empty, ((it >> 2) & 1) ^ 1);
                }
                if (item >> 16 == IT_END) break;
            }
            asm volatile("griddepcontrol.wait;" ::: "memory");
        }
    } else {
        reg_inc<232>();
        const int wu = __shfl_sync(0xffffffffu, tid >> 5, 0);
        const int wgi = (wu >> 2) - 1, wi = wu & 3;
        int it = 0, nqa = 0, nsig = 0, n = 0, item;
        auto next_item = [&]() {
            mbar_wait_long(ifull + 8 * (n & 1), (n >> 1) & 1);
            asm volatile("ld.shared.u32 %0, [%1];" : "=r"(item) : "r"(islot + 4 * (n & 1)) : "memory");
            __syncwarp();
            if (lane == 0) mbar_arrive(iempty + 8 * (n & 1));
        };
        auto signal = [&](int what) {
            if (tid == 128) asm volatile("st.shared.u32 [%0], %1;" ::"r"(sigslot + 4 * (nsig & 1)), "r"(what) : "memory");
            __syncwarp();
            if (lane == 0) mbar_arrive(sigbar);
            nsig++;
        };
        next_item();
        if (item >> 16 == IT_KV) {
            float acc[128];
            uint32_t pk[64];
            uint32_t* dst = nullptr;
            int prev = 0;
            do {
                WLOG(0);
#pragma unroll
                for (int kb = 0; kb < 16; kb++, it++) {
                    const int st = kb & 3;
                    mbar_wait(full + 8 * st, (it >> 2) & 1);
                    const uint64_t da = mkdesc(sb + st * G_STAGE + wgi * 8192, 16, 1024, 1);
                    const uint64_t db = mkdesc(sb + st * G_STAGE + 16384, 8192, 1024, 1);
                    wg_fence();
#pragma unroll
                    for (int k = 0; k < 4; k++) wgmma256(acc, da + k * 2, db + k * 128, kb | k);
                    wg_commit();
                    if (n <= KVI) {
                        if (kb < KVF && dst) {
#pragma unroll
                            for (int j = kb * (64 / KVF); j < (kb + 1) * (64 / KVF); j++) st_out(dst + (j >> 1) * 128 + (j & 1) * 32, pk[j]);
                            if (kb == KVF - 1) signal(prev);
                        }
                    } else if (kb < KVS) {
#pragma unroll
                        for (int j = kb * (64 / KVS); j < (kb + 1) * (64 / KVS); j++) st_out(dst + (j >> 1) * 128 + (j & 1) * 32, pk[j]);
                        if (kb == KVS - 1) signal(prev);
                    }
                    if (kb > 0) {
                        wg_wait<1>();
                        if (lane == 0) mbar_arrive(empty + 8 * ((kb - 1) & 3));
                    }
                }
                wg_wait<0>();
                if (lane == 0) mbar_arrive(empty + 8 * 3);
#pragma unroll
                for (int j = 0; j < 64; j++) pk[j] = pack_bf16(acc[2 * j], acc[2 * j + 1]);
                const int row = ((item >> 8) & 255) * 128 + wgi * 64 + wi * 16, nt = item & 255;
                dst = (uint32_t*)(nt < 16 ? g_kx : g_vx) + (size_t)((row >> 5) * 512 + (nt & 15) * 32) * 128 + (row & 31) * 4 + lane;
                prev = item;
                WLOG(1);
                n++;
                next_item();
            } while (item >> 16 == IT_KV);
            if (dst) {
#pragma unroll
                for (int j = 0; j < 64; j++) dst[(j >> 1) * 128 + (j & 1) * 32] = pk[j];
                signal(prev);
            }
        }
        for (;; n++, next_item()) {
            const int type = item >> 16, b = (item >> 8) & 255, i = item & 255;
            const int lane = (tid & 31) + (item >> 24), wgi = (wu >> 2) - 1 + __shfl_sync(0xffffffffu, item >> 24, 0), wi = wu & 3;
            WLOG(0);
            if (type == IT_QA) {
                float acc[128];
                ST(sid, cw, 0);
                ST(sid, cw, 1);
                mainloop<256, 16, false>(acc, sb, wgi, full, empty, it, lane == 0);
                ST(sid, cw, 2);
                uint32_t q0[32], q1[32];
#pragma unroll
                for (int j = 0; j < 32; j++) q0[j] = pack_bf16(acc[2 * j], acc[2 * j + 1]);
                const uint32_t par = (it >> 2) & 1, so = sb + wgi * 20480;
                float sx[2][32] = {}, sm[2][8] = {};
                uint32_t p[2][20];
                mbar_wait_long(full, par);
                ST(sid, cw, 3);
                if (PING && wgi == 0) bar_sync(5, 256);
                attn_scores(sx[0], sm[0], q0, so);
                ST(sid, cw, 7);
#pragma unroll
                for (int j = 0; j < 32; j++) asm volatile("cvt.rn.bf16x2.f32 %0, %1, %2;" : "=r"(q1[j]) : "f"(acc[65 + 2 * j]), "f"(acc[64 + 2 * j]));
                mbar_wait(full + 8, par);
                attn_scores(sx[1], sm[1], q1, so + G_STAGE);
                if (PING && wgi == 1) bar_arrive(5, 256);
                if (elect()) asm volatile("cp.async.bulk.wait_group.read 0;" ::: "memory");
                mbar_wait(stgbar, (nqa++ & 1) ^ 1);
                bar_sync(3 + wgi, 128);
                float o0[64] = {}, o1[64] = {};
                wg_wait<0>();
                ST(sid, cw, 9);
                if (lane == 0) { mbar_arrive(empty); mbar_arrive(empty + 8); }
                if (wi & 1) attn_softmax<true>(p, sx, sm, wi >= 2, lane);
                else attn_softmax<false>(p, sx, sm, wi >= 2, lane);
                ST(sid, cw, 10);
                mbar_wait(full + 16, par);
                attn_pv(o0, p[0], so + 2 * G_STAGE);
                mbar_wait(full + 24, par);
                attn_pv(o1, p[1], so + 3 * G_STAGE);
                wg_wait<1>();
                if (lane == 0) mbar_arrive(empty + 16);
                ST(sid, cw, 5);
                const uint32_t da = (wi * 2 + ((lane >> 3) & 1)) * 1024 + (lane >> 4) * 128 + (lane & 7) * 16;
                attn_stage(o0, sb + G_STG + wgi * 16384 + da);
                wg_wait<0>();
                bar_sync(3 + wgi, 128);
                attn_stage(o1, so + 3 * G_STAGE + da);
                asm volatile("fence.proxy.async.shared::cta;" ::: "memory");
                ST(sid, cw, 6);
                signal(item);
                it += 4;
            } else if (type == IT_O) {
                ST(b * 8 + i, wgi * 4 + wi, 8);
                mbar_wait_long(full, (it >> 2) & 1);
                ST(b * 8 + i, wgi * 4 + wi, 9);
                if (b < O_WIDE) o_item<256>(sb, wgi, wi, lane, full, empty, it, &mout, b * 128, i * 256, (nqa & 1) ^ 1);
                else o_item<128>(sb, wgi, wi, lane, full, empty, it, &mout, b * 128, i * 128, (nqa & 1) ^ 1);
            } else if (type == IT_S4) {
                mbar_wait_long(full, (it >> 2) & 1);
                mbar_wait(full + 24, (it >> 2) & 1);
                s4_item(sb, wgi * 4 + wi, lane, i, dsk, empty, &my, (nqa & 1) ^ 1, out, ifull + 8 * ((n + 1) & 1), ((n + 1) >> 1) & 1, islot + 4 * ((n + 1) & 1));
                it += 4;
            } else break;
            WLOG(1);
        }
        bar_sync(2, 256);
        signal(item);
        if (elect()) asm volatile("cp.async.bulk.wait_group 0;" ::: "memory");
    }
}

typedef CUresult (*EncodeFn)(CUtensorMap*, CUtensorMapDataType, cuuint32_t, void*, const cuuint64_t*, const cuuint64_t*, const cuuint32_t*,
                             const cuuint32_t*, CUtensorMapInterleave, CUtensorMapSwizzle, CUtensorMapL2promotion, CUtensorMapFloatOOBfill);
static EncodeFn get_encode() {
    void* fn = nullptr; cudaDriverEntryPointQueryResult st;
    cudaGetDriverEntryPoint("cuTensorMapEncodeTiled", &fn, cudaEnableDefault, &st);
    return (EncodeFn)fn;
}
static void map_act(EncodeFn enc, CUtensorMap* m, const void* p, int rows, int cols, int boxr) {
    cuuint64_t dim[2] = {(cuuint64_t)cols, (cuuint64_t)rows}, str[1] = {(cuuint64_t)cols * 2};
    cuuint32_t box[2] = {64, (cuuint32_t)boxr}, es[2] = {1, 1};
    enc(m, CU_TENSOR_MAP_DATA_TYPE_BFLOAT16, 2, (void*)p, dim, str, box, es, CU_TENSOR_MAP_INTERLEAVE_NONE, CU_TENSOR_MAP_SWIZZLE_128B,
        CU_TENSOR_MAP_L2_PROMOTION_L2_128B, CU_TENSOR_MAP_FLOAT_OOB_FILL_NONE);
}
static void map_w(EncodeFn enc, CUtensorMap* m, const void* p, int k, int n, int groups = 4) {
    cuuint64_t dim[3] = {64, (cuuint64_t)k, (cuuint64_t)n / 64}, str[2] = {(cuuint64_t)n * 2, 128};
    cuuint32_t box[3] = {64, 64, (cuuint32_t)groups}, es[3] = {1, 1, 1};
    enc(m, CU_TENSOR_MAP_DATA_TYPE_BFLOAT16, 3, (void*)p, dim, str, box, es, CU_TENSOR_MAP_INTERLEAVE_NONE, CU_TENSOR_MAP_SWIZZLE_128B,
        CU_TENSOR_MAP_L2_PROMOTION_L2_256B, CU_TENSOR_MAP_FLOAT_OOB_FILL_NONE);
}

static void map_kv(EncodeFn enc, CUtensorMap* m, void* p, int n) {
    cuuint64_t dim[3] = {(cuuint64_t)n, NSEG, 512}, str[2] = {(cuuint64_t)n * 1024, (cuuint64_t)n * 2};
    cuuint32_t box[3] = {(cuuint32_t)n, 2, 16}, es[3] = {1, 1, 1};
    enc(m, CU_TENSOR_MAP_DATA_TYPE_BFLOAT16, 3, p, dim, str, box, es, CU_TENSOR_MAP_INTERLEAVE_NONE, CU_TENSOR_MAP_SWIZZLE_NONE,
        CU_TENSOR_MAP_L2_PROMOTION_NONE, CU_TENSOR_MAP_FLOAT_OOB_FILL_NONE);
}
static void map_box(EncodeFn enc, CUtensorMap* m, const void* p, int rows, int ld, int boxc, int boxr, CUtensorMapSwizzle sw,
                    CUtensorMapL2promotion promo = CU_TENSOR_MAP_L2_PROMOTION_NONE) {
    cuuint64_t dim[2] = {(cuuint64_t)ld, (cuuint64_t)rows}, str[1] = {(cuuint64_t)ld * 2};
    cuuint32_t box[2] = {(cuuint32_t)boxc, (cuuint32_t)boxr}, es[2] = {1, 1};
    enc(m, CU_TENSOR_MAP_DATA_TYPE_BFLOAT16, 2, (void*)p, dim, str, box, es, CU_TENSOR_MAP_INTERLEAVE_NONE, sw,
        promo, CU_TENSOR_MAP_FLOAT_OOB_FILL_NONE);
}

extern "C" void kernel_launch(void* const* d_in, const int* in_sizes, int n_in, void* d_out, int out_size) {
    const bf16* x = (const bf16*)d_in[0];
    const bf16* mem0 = (const bf16*)d_in[1];
    const bf16 *Wq = (const bf16*)d_in[2], *Wk = (const bf16*)d_in[3], *Wv = (const bf16*)d_in[4], *Wo = (const bf16*)d_in[5];
    static EncodeFn enc = nullptr;
    static int nsm = 0;
    static void* kv[4];
    if (!enc) {
        enc = get_encode();
        cudaGetSymbolAddress(&kv[0], g_kx); cudaGetSymbolAddress(&kv[1], g_vx); cudaGetSymbolAddress(&kv[2], g_km); cudaGetSymbolAddress(&kv[3], g_vm);
        cudaDeviceGetAttribute(&nsm, cudaDevAttrMultiProcessorCount, 0);
        cudaFuncSetAttribute(chain_kernel, cudaFuncAttributeMaxDynamicSharedMemorySize, CH_SMEM);
        cudaFuncSetAttribute(worker_kernel, cudaFuncAttributeMaxDynamicSharedMemorySize, G_SMEM);
    }
    Maps M;
    CUtensorMap &mx = M.m[0], &mq = M.m[1], &mk = M.m[2], &mv = M.m[3], &mo = M.m[4], &mout = M.m[5], &mu = M.m[6], &my = M.m[7];
    map_act(enc, &mx, x, S_LEN, DM, 128);
    map_w(enc, &mq, Wq, DM, HD); map_w(enc, &mk, Wk, DM, HD); map_w(enc, &mv, Wv, DM, HD); map_w(enc, &mo, Wo, HD, DM);
    map_w(enc, &M.m[12], Wo, HD, DM, 2);
    map_box(enc, &mout, d_out, S_LEN, 2 * DM, 64, 16, CU_TENSOR_MAP_SWIZZLE_128B);
    map_box(enc, &mu, d_in[7], S_LEN, DM, 8, 256, CU_TENSOR_MAP_SWIZZLE_NONE, (CUtensorMapL2promotion)PROMU);
    map_box(enc, &my, d_out, S_LEN, 2 * DM, 8, 256, CU_TENSOR_MAP_SWIZZLE_NONE);
    for (int i = 0; i < 4; i++) map_kv(enc, &M.m[8 + i], kv[i], i < 2 ? 256 : 64);
    CUtensorMap cq, ck, cv, co;
    map_box(enc, &cq, Wq, DM, HD, 32, 32, CU_TENSOR_MAP_SWIZZLE_64B, (CUtensorMapL2promotion)PROMO); map_box(enc, &ck, Wk, DM, HD, 32, 32, CU_TENSOR_MAP_SWIZZLE_64B, (CUtensorMapL2promotion)PROMO);
    map_box(enc, &cv, Wv, DM, HD, 32, 32, CU_TENSOR_MAP_SWIZZLE_64B, (CUtensorMapL2promotion)PROMO); map_box(enc, &co, Wo, HD, DM, 32, 16, CU_TENSOR_MAP_SWIZZLE_64B, (CUtensorMapL2promotion)PROMO);
    S4Params P = {(const bf16*)d_in[8], (const bf16*)d_in[9], (const bf16*)d_in[10], (const bf16*)d_in[11],
                  (const bf16*)d_in[12], (const bf16*)d_in[13], (const bf16*)d_in[14], (const bf16*)d_in[15]};
    int aware = 1;
    cudaLaunchAttribute at[1];
    at[0].id = cudaLaunchAttributeProgrammaticStreamSerialization;
    at[0].val.programmaticStreamSerializationAllowed = 1;
    cudaLaunchConfig_t cfg = {};
    cfg.stream = cudaStreamPerThread;
    cfg.gridDim = dim3(96); cfg.blockDim = dim3(CH_THREADS); cfg.dynamicSmemBytes = CH_SMEM;
    cudaLaunchKernelEx(&cfg, chain_kernel, cq, ck, cv, co, Wq, Wk, Wv, mem0, P, aware);
    cfg.attrs = at; cfg.numAttrs = 1;
    cfg.gridDim = dim3(nsm); cfg.blockDim = dim3(384); cfg.dynamicSmemBytes = G_SMEM;
    cudaLaunchKernelEx(&cfg, worker_kernel, M, P.dsk, (bf16*)d_out);
}
```

```cpp
#include <cuda.h>
#include <cuda_runtime.h>
#include <cuda_bf16.h>
#include <stdint.h>
#include <stdio.h>
#include <string.h>

typedef __nv_bfloat16 bf16;

constexpr int S_LEN = 2048, DM = 1024, NH = 32, DH = 128, HD = 4096, NSEG = 64;
constexpr uint32_t SENT = 0xFFFFFFFFu;
constexpr int SPIN_LIMIT = 1 << 18;
#define REALL 0

__device__ __align__(1024) bf16 g_kx[S_LEN * HD];
__device__ __align__(1024) bf16 g_vx[S_LEN * HD];
__device__ __align__(1024) bf16 g_ox[S_LEN * HD];
__device__ __align__(1024) bf16 g_km[NSEG * NH * 8 * DH];
__device__ __align__(1024) bf16 g_vm[NSEG * NH * 8 * DH];
__device__ __align__(1024) bf16 g_kd[DM * 768 + 8192];
__device__ __align__(1024) char g_ring[2 << 20];
__device__ int g_kvf[96 * 16];
constexpr int C_NEXT = 0, C_CHAIN = 32, C_QA_DONE = 64, N_CTR = 96;
__device__ int g_ctr[N_CTR];

__device__ __forceinline__ uint32_t smem_u32(const void* p) { return (uint32_t)__cvta_generic_to_shared(p); }
__device__ __forceinline__ uint32_t clk() { uint32_t c; asm volatile("mov.u32 %0, %%clock;" : "=r"(c)::"memory"); return c; }
__device__ __forceinline__ uint32_t pack_bf16(float lo, float hi) {
    uint32_t r; asm("cvt.rn.bf16x2.f32 %0, %1, %2;" : "=r"(r) : "f"(hi), "f"(lo)); return r;
}
__device__ __forceinline__ uint32_t movm(uint32_t a) {
    uint32_t d; asm volatile("movmatrix.sync.aligned.m8n8.trans.b16 %0, %1;" : "=r"(d) : "r"(a)); return d;
}
__device__ __forceinline__ void mma16(float (&d)[4], const uint32_t (&a)[4], uint32_t b0, uint32_t b1) {
    asm volatile("mma.sync.aligned.m16n8k16.row.col.f32.bf16.bf16.f32 {%0,%1,%2,%3}, {%4,%5,%6,%7}, {%8,%9}, {%0,%1,%2,%3};"
        : "+f"(d[0]), "+f"(d[1]), "+f"(d[2]), "+f"(d[3]) : "r"(a[0]), "r"(a[1]), "r"(a[2]), "r"(a[3]), "r"(b0), "r"(b1));
}
__device__ __forceinline__ void mma16z(float (&d)[4], const uint32_t (&a)[4], uint32_t b0, uint32_t b1) {
    asm volatile("mma.sync.aligned.m16n8k16.row.col.f32.bf16.bf16.f32 {%0,%1,%2,%3}, {%4,%5,%6,%7}, {%8,%9}, {%10,%10,%10,%10};"
        : "=f"(d[0]), "=f"(d[1]), "=f"(d[2]), "=f"(d[3]) : "r"(a[0]), "r"(a[1]), "r"(a[2]), "r"(a[3]), "r"(b0), "r"(b1), "f"(0.f));
}
__device__ __forceinline__ void mma8z(float (&d)[4], uint32_t a0, uint32_t a1, uint32_t b0) {
    asm volatile("mma.sync.aligned.m16n8k8.row.col.f32.bf16.bf16.f32 {%0,%1,%2,%3}, {%4,%5}, {%6}, {%7,%7,%7,%7};"
        : "=f"(d[0]), "=f"(d[1]), "=f"(d[2]), "=f"(d[3]) : "r"(a0), "r"(a1), "r"(b0), "f"(0.f));
}
__device__ __forceinline__ void ldsm4t(uint32_t (&r)[4], uint32_t addr) {
    asm volatile("ldmatrix.sync.aligned.m8n8.x4.trans.shared.b16 {%0,%1,%2,%3}, [%4];"
        : "=r"(r[0]), "=r"(r[1]), "=r"(r[2]), "=r"(r[3]) : "r"(addr) : "memory");
}
__device__ __forceinline__ void ldsm4(uint32_t (&r)[4], uint32_t addr) {
    asm volatile("ldmatrix.sync.aligned.m8n8.x4.shared.b16 {%0,%1,%2,%3}, [%4];"
        : "=r"(r[0]), "=r"(r[1]), "=r"(r[2]), "=r"(r[3]) : "r"(addr) : "memory");
}
__device__ __forceinline__ float lds32(uint32_t a) {
    float v; asm volatile("ld.shared.f32 %0, [%1];" : "=f"(v) : "r"(a) : "memory"); return v;
}
__device__ __forceinline__ void st_async1(uint32_t dst, float v, uint32_t bar) {
    asm volatile("st.async.shared::cluster.mbarrier::complete_tx::bytes.f32 [%0], %1, [%2];" ::"r"(dst), "f"(v), "r"(bar) : "memory");
}
__device__ __forceinline__ void st_async2(uint32_t dst, float x, float y, uint32_t bar) {
    asm volatile("st.async.shared::cluster.mbarrier::complete_tx::bytes.v2.f32 [%0], {%1,%2}, [%3];" ::"r"(dst), "f"(x), "f"(y), "r"(bar) : "memory");
}
__device__ __forceinline__ void mma8(float (&d)[4], uint32_t a0, uint32_t a1, uint32_t b0) {
    asm volatile("mma.sync.aligned.m16n8k8.row.col.f32.bf16.bf16.f32 {%0,%1,%2,%3}, {%4,%5}, {%6}, {%0,%1,%2,%3};"
        : "+f"(d[0]), "+f"(d[1]), "+f"(d[2]), "+f"(d[3]) : "r"(a0), "r"(a1), "r"(b0));
}
__device__ __forceinline__ void cp16(uint32_t dst, const void* src) {
    asm volatile("cp.async.cg.shared.global [%0], [%1], 16;" ::"r"(dst), "l"(src) : "memory");
}
__device__ __forceinline__ void sts128(uint32_t a, const float (&v)[4]) {
    asm volatile("st.shared.v4.f32 [%0], {%1,%2,%3,%4};" ::"r"(a), "f"(v[0]), "f"(v[1]), "f"(v[2]), "f"(v[3]) : "memory");
}
__device__ __forceinline__ float4 lds128(uint32_t a) {
    float4 v; asm volatile("ld.shared.v4.f32 {%0,%1,%2,%3}, [%4];" : "=f"(v.x), "=f"(v.y), "=f"(v.z), "=f"(v.w) : "r"(a) : "memory"); return v;
}
__device__ __forceinline__ void sts64(uint32_t a, float x, float y) {
    asm volatile("st.shared.v2.f32 [%0], {%1,%2};" ::"r"(a), "f"(x), "f"(y) : "memory");
}
__device__ __forceinline__ float2 lds64(uint32_t a) {
    float2 v; asm volatile("ld.shared.v2.f32 {%0,%1}, [%2];" : "=f"(v.x), "=f"(v.y) : "r"(a) : "memory"); return v;
}
__device__ __forceinline__ void bar_sync(int id, int n) { asm volatile("bar.sync %0, %1;" ::"r"(id), "r"(n) : "memory"); }
__device__ __forceinline__ void bar_arrive(int id, int n) { asm volatile("bar.arrive %0, %1;" ::"r"(id), "r"(n) : "memory"); }
__device__ __forceinline__ uint32_t mapa(uint32_t a, uint32_t r) {
    uint32_t o; asm("mapa.shared::cluster.u32 %0, %1, %2;" : "=r"(o) : "r"(a), "r"(r)); return o;
}
__device__ __forceinline__ void st_async4(uint32_t dst, float4 v, uint32_t bar) {
    asm volatile("st.async.shared::cluster.mbarrier::complete_tx::bytes.v4.f32 [%0], {%1,%2,%3,%4}, [%5];"
        ::"r"(dst), "f"(v.x), "f"(v.y), "f"(v.z), "f"(v.w), "r"(bar) : "memory");
}
__device__ __forceinline__ void mbar_init(uint32_t bar, int n) { asm volatile("mbarrier.init.shared.b64 [%0], %1;" ::"r"(bar), "r"(n) : "memory"); }
__device__ __forceinline__ void mbar_expect(uint32_t bar, int bytes) {
    asm volatile("mbarrier.arrive.expect_tx.shared.b64 _, [%0], %1;" ::"r"(bar), "r"(bytes) : "memory");
}
__device__ __forceinline__ void bulk_load(uint32_t dst, const void* src, int bytes, uint32_t bar) {
    asm volatile("cp.async.bulk.shared::cluster.global.mbarrier::complete_tx::bytes [%0], [%1], %2, [%3];"
        ::"r"(dst), "l"(src), "r"(bytes), "r"(bar) : "memory");
}
__device__ __forceinline__ bool mbar_try(uint32_t bar, uint32_t par) {
    uint32_t ok;
    asm volatile("{.reg .pred p; mbarrier.try_wait.parity.shared::cta.b64 p, [%1], %2; selp.u32 %0, 1, 0, p;}"
        : "=r"(ok) : "r"(bar), "r"(par) : "memory");
    return ok;
}
__device__ __forceinline__ bool mbar_test(uint32_t bar, uint32_t par) {
    uint32_t ok;
    asm volatile("{.reg .pred p; mbarrier.test_wait.parity.shared::cta.b64 p, [%1], %2; selp.u32 %0, 1, 0, p;}"
        : "=r"(ok) : "r"(bar), "r"(par) : "memory");
    return ok;
}
__device__ __forceinline__ int ld_acq(const int* p) { int v; asm volatile("ld.acquire.gpu.global.s32 %0, [%1];" : "=r"(v) : "l"(p) : "memory"); return v; }
__device__ __forceinline__ void red_release(int* p, int v) { asm volatile("red.release.gpu.global.add.s32 [%0], %1;" ::"l"(p), "r"(v) : "memory"); }
__device__ __forceinline__ void fence_gpu() { asm volatile("fence.acq_rel.gpu;" ::: "memory"); }
__device__ __forceinline__ void wait_ctr(const int* p, int n) {
#pragma unroll 1
    for (int it = 0; it < (1 << 20) && ld_acq(p) < n; it++) __nanosleep(64);
}
__device__ __forceinline__ void mbar_wait(uint32_t bar, uint32_t par) {
    if (!mbar_try(bar, par)) {
#pragma unroll 1
        for (int it = 0; it < SPIN_LIMIT && !mbar_try(bar, par); it++) {}
    }
}
__device__ __forceinline__ void mbar_wait_long(uint32_t bar, uint32_t par) {
    for (int it = 0; it < (1 << 24) && !mbar_try(bar, par); it++) {}
}
__device__ __forceinline__ float4 add4(float4 a, float4 b) { return make_float4(a.x + b.x, a.y + b.y, a.z + b.z, a.w + b.w); }
__device__ __forceinline__ float ex2(float x) { float y; asm("ex2.approx.ftz.f32 %0, %1;" : "=f"(y) : "f"(x)); return y; }

__device__ __forceinline__ void wgmma256(float (&d)[128], uint64_t da, uint64_t db, int acc) {
    asm volatile("{.reg .pred p; setp.ne.b32 p, %130, 0;\n"
        "wgmma.mma_async.sync.aligned.m64n256k16.f32.bf16.bf16 {"
        "%0,%1,%2,%3,%4,%5,%6,%7,%8,%9,%10,%11,%12,%13,%14,%15,"
        "%16,%17,%18,%19,%20,%21,%22,%23,%24,%25,%26,%27,%28,%29,%30,%31,"
        "%32,%33,%34,%35,%36,%37,%38,%39,%40,%41,%42,%43,%44,%45,%46,%47,"
        "%48,%49,%50,%51,%52,%53,%54,%55,%56,%57,%58,%59,%60,%61,%62,%63,"
        "%64,%65,%66,%67,%68,%69,%70,%71,%72,%73,%74,%75,%76,%77,%78,%79,"
        "%80,%81,%82,%83,%84,%85,%86,%87,%88,%89,%90,%91,%92,%93,%94,%95,"
        "%96,%97,%98,%99,%100,%101,%102,%103,%104,%105,%106,%107,%108,%109,%110,%111,"
        "%112,%113,%114,%115,%116,%117,%118,%119,%120,%121,%122,%123,%124,%125,%126,%127"
        "}, %128, %129, p, 1, 1, 0, 1;}"
        : "+f"(d[0]), "+f"(d[1]), "+f"(d[2]), "+f"(d[3]), "+f"(d[4]), "+f"(d[5]), "+f"(d[6]), "+f"(d[7]), "+f"(d[8]), "+f"(d[9]), "+f"(d[10]), "+f"(d[11]), "+f"(d[12]), "+f"(d[13]), "+f"(d[14]), "+f"(d[15]), "+f"(d[16]), "+f"(d[17]), "+f"(d[18]), "+f"(d[19]), "+f"(d[20]), "+f"(d[21]), "+f"(d[22]), "+f"(d[23]), "+f"(d[24]), "+f"(d[25]), "+f"(d[26]), "+f"(d[27]), "+f"(d[28]), "+f"(d[29]), "+f"(d[30]), "+f"(d[31]), "+f"(d[32]), "+f"(d[33]), "+f"(d[34]), "+f"(d[35]), "+f"(d[36]), "+f"(d[37]), "+f"(d[38]), "+f"(d[39]), "+f"(d[40]), "+f"(d[41]), "+f"(d[42]), "+f"(d[43]), "+f"(d[44]), "+f"(d[45]), "+f"(d[46]), "+f"(d[47]), "+f"(d[48]), "+f"(d[49]), "+f"(d[50]), "+f"(d[51]), "+f"(d[52]), "+f"(d[53]), "+f"(d[54]), "+f"(d[55]), "+f"(d[56]), "+f"(d[57]), "+f"(d[58]), "+f"(d[59]), "+f"(d[60]), "+f"(d[61]), "+f"(d[62]), "+f"(d[63]), "+f"(d[64]), "+f"(d[65]), "+f"(d[66]), "+f"(d[67]), "+f"(d[68]), "+f"(d[69]), "+f"(d[70]), "+f"(d[71]), "+f"(d[72]), "+f"(d[73]), "+f"(d[74]), "+f"(d[75]), "+f"(d[76]), "+f"(d[77]), "+f"(d[78]), "+f"(d[79]), "+f"(d[80]), "+f"(d[81]), "+f"(d[82]), "+f"(d[83]), "+f"(d[84]), "+f"(d[85]), "+f"(d[86]), "+f"(d[87]), "+f"(d[88]), "+f"(d[89]), "+f"(d[90]), "+f"(d[91]), "+f"(d[92]), "+f"(d[93]), "+f"(d[94]), "+f"(d[95]), "+f"(d[96]), "+f"(d[97]), "+f"(d[98]), "+f"(d[99]), "+f"(d[100]), "+f"(d[101]), "+f"(d[102]), "+f"(d[103]), "+f"(d[104]), "+f"(d[105]), "+f"(d[106]), "+f"(d[107]), "+f"(d[108]), "+f"(d[109]), "+f"(d[110]), "+f"(d[111]), "+f"(d[112]), "+f"(d[113]), "+f"(d[114]), "+f"(d[115]), "+f"(d[116]), "+f"(d[117]), "+f"(d[118]), "+f"(d[119]), "+f"(d[120]), "+f"(d[121]), "+f"(d[122]), "+f"(d[123]), "+f"(d[124]), "+f"(d[125]), "+f"(d[126]), "+f"(d[127])
        : "l"(da), "l"(db), "r"(acc));
}
__device__ __forceinline__ void wgmma128(float (&d)[64], uint64_t da, uint64_t db, int acc) {
    asm volatile("{.reg .pred p; setp.ne.b32 p, %66, 0;\n"
        "wgmma.mma_async.sync.aligned.m64n128k16.f32.bf16.bf16 {"
        "%0,%1,%2,%3,%4,%5,%6,%7,%8,%9,%10,%11,%12,%13,%14,%15,"
        "%16,%17,%18,%19,%20,%21,%22,%23,%24,%25,%26,%27,%28,%29,%30,%31,"
        "%32,%33,%34,%35,%36,%37,%38,%39,%40,%41,%42,%43,%44,%45,%46,%47,"
        "%48,%49,%50,%51,%52,%53,%54,%55,%56,%57,%58,%59,%60,%61,%62,%63"
        "}, %64, %65, p, 1, 1, 0, 1;}"
        : "+f"(d[0]), "+f"(d[1]), "+f"(d[2]), "+f"(d[3]), "+f"(d[4]), "+f"(d[5]), "+f"(d[6]), "+f"(d[7]), "+f"(d[8]), "+f"(d[9]), "+f"(d[10]), "+f"(d[11]), "+f"(d[12]), "+f"(d[13]), "+f"(d[14]), "+f"(d[15]), "+f"(d[16]), "+f"(d[17]), "+f"(d[18]), "+f"(d[19]), "+f"(d[20]), "+f"(d[21]), "+f"(d[22]), "+f"(d[23]), "+f"(d[24]), "+f"(d[25]), "+f"(d[26]), "+f"(d[27]), "+f"(d[28]), "+f"(d[29]), "+f"(d[30]), "+f"(d[31]), "+f"(d[32]), "+f"(d[33]), "+f"(d[34]), "+f"(d[35]), "+f"(d[36]), "+f"(d[37]), "+f"(d[38]), "+f"(d[39]), "+f"(d[40]), "+f"(d[41]), "+f"(d[42]), "+f"(d[43]), "+f"(d[44]), "+f"(d[45]), "+f"(d[46]), "+f"(d[47]), "+f"(d[48]), "+f"(d[49]), "+f"(d[50]), "+f"(d[51]), "+f"(d[52]), "+f"(d[53]), "+f"(d[54]), "+f"(d[55]), "+f"(d[56]), "+f"(d[57]), "+f"(d[58]), "+f"(d[59]), "+f"(d[60]), "+f"(d[61]), "+f"(d[62]), "+f"(d[63])
        : "l"(da), "l"(db), "r"(acc));
}
__device__ __forceinline__ void wg_fence() { asm volatile("wgmma.fence.sync.aligned;" ::: "memory"); }
__device__ __forceinline__ void wg_commit() { asm volatile("wgmma.commit_group.sync.aligned;" ::: "memory"); }
template <int N> __device__ __forceinline__ void wg_wait() { asm volatile("wgmma.wait_group.sync.aligned %0;" ::"n"(N) : "memory"); }
__device__ __forceinline__ uint64_t mkdesc(uint32_t addr, uint32_t lbo, uint32_t sbo, uint32_t sw) {
    return (uint64_t)((addr & 0x3FFFF) >> 4) | ((uint64_t)(lbo >> 4) << 16) | ((uint64_t)(sbo >> 4) << 32) | ((uint64_t)sw << 62);
}
__device__ __forceinline__ void tma2d(uint32_t dst, const CUtensorMap* m, int c0, int c1, uint32_t bar) {
    asm volatile("cp.async.bulk.tensor.2d.shared::cluster.global.mbarrier::complete_tx::bytes [%0], [%1, {%2, %3}], [%4];"
        ::"r"(dst), "l"(m), "r"(c0), "r"(c1), "r"(bar) : "memory");
}
__device__ __forceinline__ void tma3d(uint32_t dst, const CUtensorMap* m, int c0, int c1, int c2, uint32_t bar) {
    asm volatile("cp.async.bulk.tensor.3d.shared::cluster.global.mbarrier::complete_tx::bytes [%0], [%1, {%2, %3, %4}], [%5];"
        ::"r"(dst), "l"(m), "r"(c0), "r"(c1), "r"(c2), "r"(bar) : "memory");
}
__device__ __forceinline__ void tma3d_mc(uint32_t dst, const CUtensorMap* m, int c0, int c1, int c2, uint32_t bar, uint16_t mask) {
    asm volatile("cp.async.bulk.tensor.3d.shared::cluster.global.mbarrier::complete_tx::bytes.multicast::cluster [%0], [%1, {%2, %3, %4}], [%5], %6;"
        ::"r"(dst), "l"(m), "r"(c0), "r"(c1), "r"(c2), "r"(bar), "h"(mask) : "memory");
}
__device__ __forceinline__ void mbar_arrive(uint32_t bar) { asm volatile("mbarrier.arrive.shared.b64 _, [%0];" ::"r"(bar) : "memory"); }
__device__ __forceinline__ void mbar_arrive_remote(uint32_t bar) {
    asm volatile("mbarrier.arrive.shared::cluster.b64 _, [%0];" ::"r"(bar) : "memory");
}
__device__ __forceinline__ bool elect() {
    uint32_t p;
    asm volatile("{.reg .pred p; elect.sync _|p, 0xffffffff; selp.u32 %0, 1, 0, p;}" : "=r"(p));
    return p;
}
template <int R> __device__ __forceinline__ void reg_inc() { asm volatile("setmaxnreg.inc.sync.aligned.u32 %0;" ::"n"(R)); }
template <int R> __device__ __forceinline__ void reg_dec() { asm volatile("setmaxnreg.dec.sync.aligned.u32 %0;" ::"n"(R)); }

#define ST(id, w, i)
constexpr int CH_NRES = 50;
constexpr int CH_WREG = CH_NRES * 512;
constexpr int CH_PART = 8 * CH_WREG;
constexpr int CH_SX = CH_PART + 16384;
constexpr int CH_MX = CH_SX + 3 * 1280;
constexpr int CH_QK = CH_MX;
constexpr int CH_XS = CH_MX + 3 * 512;
constexpr int CH_BAR = CH_XS + 5632;
constexpr int CH_SMEM = CH_BAR + 192;
constexpr int CH_THREADS = 384;

__device__ __forceinline__ char* ring_base() { return (char*)(((uintptr_t)g_ring + (1 << 20) - 1) & ~(uintptr_t)((1 << 20) - 1)); }
__device__ __forceinline__ uint32_t ring_off(int chunk, int side) {
    uint32_t o = ((chunk & 1) << 13) | ((chunk >> 1) << 16);
    uint32_t par = ((o >> 13) ^ (o >> 16) ^ (o >> 17) ^ (o >> 19) ^ side) & 1;
    return o | (par << 12);
}
__device__ __forceinline__ uint2 ld_poll(const char* p) {
    unsigned long long v; asm volatile("ld.relaxed.gpu.global.b64 %0, [%1];" : "=l"(v) : "l"(p) : "memory");
    return make_uint2((uint32_t)v, (uint32_t)(v >> 32));
}
__device__ __forceinline__ void st_pub(char* p, uint32_t x, uint32_t y) {
    unsigned long long v = ((unsigned long long)y << 32) | x;
    asm volatile("st.relaxed.gpu.global.b64 [%0], %1;" ::"l"(p), "l"(v) : "memory");
}
template <int N>
__device__ __forceinline__ void poll_issue(uint2 (&b)[N], const char* p, bool lastvalid) {
#pragma unroll
    for (int i = 0; i < N; i++) {
        if (i < N - 1 || lastvalid) b[i] = ld_poll(p + i * 256);
        else b[i] = make_uint2(0, 0);
    }
}
template <int N>
__device__ __forceinline__ int poll_check(uint2 (&b)[N], const char* p, uint32_t z) {
    int it = 0;
    uint32_t mx = z;
#pragma unroll
    for (int i = 0; i < N; i++) mx = max(mx, b[i].x);
    if (__any_sync(0xffffffffu, mx == SENT)) {
        do {
#pragma unroll
            for (int i = 0; i < N; i++)
                if ((REALL && i < 10) || b[i].x == SENT) b[i] = ld_poll(p + i * 256);
            mx = b[0].x;
#pragma unroll
            for (int i = 1; i < N; i++) mx = max(mx, b[i].x);
            it++;
        } while (__any_sync(0xffffffffu, mx == SENT && it < SPIN_LIMIT));
    }
    return it;
}
template <int N>
__device__ __forceinline__ uint32_t delay(uint32_t a) {
    uint32_t z = 0;
#pragma unroll
    for (int i = 0; i < N; i++) asm volatile("ld.volatile.shared.u32 %0, [%1];" : "=r"(z) : "r"(a + z) : "memory");
    return z;
}

#define PFKV 0
#define LDW 0
#define GX 2
#define PACE2 18
#define KGS 2
constexpr int KVN = 2;
#define FEN 1
#define XB 4
#define KEEP 100
#define PE 0
#define PROMO 2
#define PROMU 0
#define FNC 3
#define CL 8
#define PL 0
#define ML 4
#define MP 2
#define VCH_P 4
#define VCH_C 2
#define DLM 3
#define DLO 5
constexpr int OB = 0;
template <int PACE, int I0 = 0, int I1 = 12>
__device__ __forceinline__ void preload(uint32_t (&sw)[12][4], uint32_t a, uint32_t zero) {
    uint32_t z = 0;
#pragma unroll
    for (int i = I0; i < I1; i++) {
        if (PACE && i % (PACE ? PACE : 1) == 0) z = delay<1>(zero + z);
        ldsm4t(sw[i], a + z + i * 512);
    }
}
__device__ __forceinline__ void stsm4(uint32_t addr, uint32_t a, uint32_t b, uint32_t c, uint32_t d) {
    asm volatile("stmatrix.sync.aligned.m8n8.x4.shared.b16 [%0], {%1,%2,%3,%4};" ::"r"(addr), "r"(a), "r"(b), "r"(c), "r"(d) : "memory");
}
__device__ __forceinline__ void stsm4t(uint32_t addr, uint32_t a, uint32_t b, uint32_t c, uint32_t d) {
    asm volatile("stmatrix.sync.aligned.m8n8.x4.trans.shared.b16 [%0], {%1,%2,%3,%4};" ::"r"(addr), "r"(a), "r"(b), "r"(c), "r"(d) : "memory");
}
__device__ __forceinline__ void st_part(uint32_t addr, const float (&x)[4], const float (&y)[4]) {
    stsm4(addr, pack_bf16(x[0], x[1]), pack_bf16(x[2], x[3]), pack_bf16(y[0], y[1]), pack_bf16(y[2], y[3]));
}
template <bool TR>
__device__ __forceinline__ void red_part(uint32_t& lo, uint32_t& hi, uint32_t addr, uint32_t eye) {
    uint32_t a[4][4];
#pragma unroll
    for (int j = 0; j < 4; j++) { if (TR) ldsm4t(a[j], addr + j * 1024); else ldsm4(a[j], addr + j * 1024); }
    float r0[4], r1[4], r2[4], r3[4];
    mma16z(r0, a[0], eye, eye); mma16z(r1, a[1], eye, eye); mma16z(r2, a[2], eye, eye); mma16z(r3, a[3], eye, eye);
#pragma unroll
    for (int j = 0; j < 4; j++) r0[j] = ((r0[j] + r1[j]) + r2[j]) + r3[j];
    lo = pack_bf16(r0[0], r0[1]); hi = pack_bf16(r0[2], r0[3]);
}
__device__ __forceinline__ int o_chunk(int ks, int& pos) {
    const int cw = ks < 176 ? ks / 11 : 16 + (ks - 176) / 10;
    pos = ks - (cw < 16 ? 11 * cw : 176 + 10 * (cw - 16));
    return cw;
}

template <bool PV>
__device__ __forceinline__ void chain_loop(const uint32_t (&wa)[36][4], const uint32_t sb, const int w, const int lane0, const int rank,
                                           const int h, const int side) {
    const int rk1 = rank == 2 ? 0 : rank + 1, rk2 = rank == 0 ? 2 : rank - 1;
    const int nq = rank == 0 ? 6 : 5, u0 = rank == 0 ? 0 : 1 + 5 * rank, v0 = rank == 0 ? -6 : 3 * rank - 6;
    const uint32_t pt = CH_PART + (w >> 1) * 4096 + (w & 1) * 256;
    const uint32_t barS = sb + CH_BAR, barM = barS + 8, zero = barS + 24;
    char* const ring0 = ring_base();
    const uint32_t m_rd = ring_off(24 + w, side), o_rd = ring_off(rank * 8 + w, side);
    uint32_t pub;
    if (PV) { int pos, cw = o_chunk(h * 8 + v0 + w, pos); pub = (ring_off(cw, 0) & ~4096u) + pos * 256; }
    else pub = (ring_off(24 + (h >> 2), 0) & ~4096u) + ((2 * h + w) & 7) * 256;
    char* const kvo = (char*)(PV ? g_vm + 128 * (v0 + w) : g_km + 64 * (u0 + w)) + h * 2048;
    const bool mown = !PV && w == rank && rank < 2;
    uint32_t lo16 = lane0 * 16;
    uint32_t sw[12][4];
#pragma unroll
    for (int i = 0; i < 12; i++) ldsm4t(sw[i], sb + lo16 + w * CH_WREG + i * 512);

#pragma unroll 1
    for (int s = 0;; s++) {
        const bool last = s == NSEG - 1;
        const uint32_t slot = (s & 3) << 14;
        lo16 += delay<DLM>(zero);
        const uint32_t lane = lo16 >> 4, l16 = sb + lo16, wl = l16 + w * CH_WREG, pw = l16 + CH_PART + w * 512;
        const uint32_t xs = l16 + CH_XS + nq * 512 + (w - nq) * 1024;
        const uint32_t eye = ((lo16 >> 7) == (lane & 3)) ? ((lo16 & 64) ? 0x3F800000u : 0x3F80u) : 0u;
        uint2 b[8];
        const char* pm = ring0 + (m_rd + slot + (lo16 >> 1));
        poll_issue<8>(b, pm, true);
        preload<0, ML, 12>(sw, wl, zero);
        if (FNC & 1) bar_arrive(14, 256);
        poll_check<8>(b, pm, delay<FNC & 1>(zero));
        if ((OB || (XB & 1)) && !last) bar_arrive(8, 256 + OB);
        if (PV && !last && w == 7) bar_arrive(13, 64);
        {
            float acc[6][4];
#pragma unroll
            for (int kk = 0; kk < 8; kk++) {
                const int j = (2 * kk) % 12;
                if (kk == 0) { mma16z(acc[5], sw[0], b[0].x, b[0].y); mma16z(acc[4], sw[1], b[0].x, b[0].y); }
                else { mma16(acc[5], sw[j], b[kk].x, b[kk].y); mma16(acc[4], sw[j + 1], b[kk].x, b[kk].y); }
#pragma unroll
                for (int i = 0; i < 4; i++) {
                    if (kk == 0) mma16z(acc[i], wa[i * 8], b[0].x, b[0].y);
                    else mma16(acc[i], wa[i * 8 + kk], b[kk].x, b[kk].y);
                    if (i < 2) ldsm4t(sw[j + i], wl + (12 + 2 * kk + i) * 512);
                }
            }
            st_part(pw + 4 * 2048, acc[4], acc[5]);
            st_part(pw, acc[0], acc[1]);
            st_part(pw + 2 * 2048, acc[2], acc[3]);
        }
        uint32_t kv0, kv1;
        const uint32_t lp = l16 + (lane >> 4) * 256, pl = lp + pt;
        if (!PV) {
            bar_sync(1, last ? 256 : 256 + OB);
            red_part<true>(kv1, kv0, pl, eye);
            sts64(l16 + CH_QK + (w >> 1) * 512 + (w & 1) * 8, __uint_as_float(kv1), __uint_as_float(kv0));
            if (!last) bar_arrive(2, nq * 32 + 64 + OB);
        } else {
            bar_sync(1, last ? 256 : 256 + OB);
        }
        {
            float va[4][4];
            const float z = __uint_as_float(delay<1>(zero));
#pragma unroll
            for (int i = 0; i < 4; i++) va[i][0] = va[i][1] = va[i][2] = va[i][3] = z;
#pragma unroll
            for (int kk = 0; kk < 8; kk++) {
                const int c = (PV ? VCH_P : VCH_C) == 4 ? kk & 1 : 0;
                if (kk < 2) { mma16(va[c], wa[32 + 2 * kk], b[kk].x, b[kk].y); mma16(va[2 + c], wa[33 + 2 * kk], b[kk].x, b[kk].y); }
                else { mma16(va[c], sw[(2 * kk) % 12], b[kk].x, b[kk].y); mma16(va[2 + c], sw[(2 * kk + 1) % 12], b[kk].x, b[kk].y); }
            }
            if ((PV ? VCH_P : VCH_C) == 4) {
#pragma unroll
                for (int j = 0; j < 4; j++) { va[0][j] += va[1][j]; va[2][j] += va[3][j]; }
            }
            st_part(pw + 6 * 2048, va[0], va[2]);
        }
        if (PV) {
            uint32_t vt0[4], vt1[4];
            ldsm4t(vt0, xs); ldsm4t(vt1, xs + 512);
            if (w >= 6 && !last) {
                uint32_t kx[3][4];
#pragma unroll
                for (int j = 0; j < 3; j++)
                    ldsm4(kx[j], sb + CH_XS + j * 1024 + (j == 2 && nq == 5 ? 0 : ((lane >> 3) & 1) * 512) + (w - 6) * 256 + (lane >> 4) * 128 + (lane & 7) * 16);
                const uint32_t da = l16 + CH_SX + rank * 1280 + (w - 6) * 512, dc = sb + CH_SX + rank * 1280 + 1024 + lane * 8;
                bar_sync(2, nq * 32 + 64 + OB);
                uint32_t qk[3][4];
#pragma unroll
                for (int j = 0; j < 3; j++) {
                    const float4 v = lds128(l16 + CH_QK + j * 512);
                    qk[j][0] = __float_as_uint(v.x); qk[j][1] = __float_as_uint(v.y); qk[j][2] = __float_as_uint(v.z); qk[j][3] = __float_as_uint(v.w);
                }
                float s0[4], s1[4], s2[4], s3[4];
                mma16z(s0, qk[0], kx[0][0], kx[0][1]); mma16z(s1, qk[0], kx[0][2], kx[0][3]);
                mma16z(s2, qk[1], kx[1][0], kx[1][1]); mma16z(s3, qk[1], kx[1][2], kx[1][3]);
                if (nq == 5) qk[2][2] = qk[2][3] = 0;
                mma16(s0, qk[2], kx[2][0], kx[2][1]); mma16(s1, qk[2], kx[2][2], kx[2][3]);
                float m0[4], m1[4];
                mma16z(m0, qk[0], qk[0][1], qk[0][3]); mma16z(m1, qk[1], qk[1][1], qk[1][3]);
                mma16(m0, qk[2], qk[2][1], qk[2][3]);
                const float4 sv = make_float4(s0[0] + s2[0], s0[1] + s2[1], s1[0] + s3[0], s1[1] + s3[1]);
                st_async4(mapa(da, rk1), sv, mapa(barS, rk1));
                st_async4(mapa(da, rk2), sv, mapa(barS, rk2));
                {
                    const float c0 = m0[0] + m1[0], c1 = m0[1] + m1[1];
                    const int dr = w == 6 ? rk1 : rk2;
                    st_async2(mapa(dc, dr), c0, c1, mapa(barS, dr));
                    sts64(dc, c0, c1);
                }
                const float t4[4] = {sv.x, sv.y, sv.z, sv.w};
                sts128(da, t4);
            }
            bar_sync(3, last ? 256 : 256 + OB);
            if (!last && w == 7) bar_arrive(12, 64);
            red_part<false>(kv0, kv1, pl, eye);
            if (last) {
                uint32_t* d = (uint32_t*)(kvo + (uint32_t)(s * (NH * 2048) + lane * 4));
                d[0] = movm(kv0); d[32] = movm(kv1);
                break;
            }
            {
                const uint32_t sx = l16 + CH_SX, r0 = rank * 1280, r1 = rk1 * 1280, r2 = rk2 * 1280;
                float4 a0 = lds128(sx + r0), b0 = lds128(sx + 512 + r0);
                const float2 c0 = lds64(sx + 1024 + r0 - lane * 8);
                preload<0, 0, PE>(sw, wl + 28 * 512, zero);
                mbar_wait(barS, s & 1);
                const float4 a1 = lds128(sx + r1), a2 = lds128(sx + r2), b1 = lds128(sx + 512 + r1), b2 = lds128(sx + 512 + r2);
                const float2 c1 = lds64(sx + 1024 + r1 - lane * 8), c2 = lds64(sx + 1024 + r2 - lane * 8);
                a0 = add4(add4(a0, a1), a2); b0 = add4(add4(b0, b1), b2);
                float sc[10] = {a0.x, a0.y, a0.z, a0.w, b0.x, b0.y, b0.z, b0.w, c0.x + c1.x + c2.x, c0.y + c1.y + c2.y};
                float mx = fmaxf(fmaxf(fmaxf(sc[0], sc[1]), fmaxf(sc[2], sc[3])), fmaxf(fmaxf(sc[4], sc[5]), fmaxf(sc[6], sc[7])));
                mx = fmaxf(mx, fmaxf(sc[8], sc[9]));
                mx = fmaxf(fmaxf(mx, __shfl_xor_sync(0xffffffffu, mx, 1)),
                           fmaxf(__shfl_xor_sync(0xffffffffu, mx, 2), __shfl_xor_sync(0xffffffffu, mx, 3)));
                const float cs = 0.08838834764831845f * 1.4426950408889634f;
                const float mb = -mx * cs;
#pragma unroll
                for (int j = 0; j < 10; j++) sc[j] = ex2(fmaf(sc[j], cs, mb));
                uint32_t pf[5];
#pragma unroll
                for (int j = 0; j < 5; j++) pf[j] = pack_bf16(sc[2 * j], sc[2 * j + 1]);
                float o0[4], o1[4], o2[4], o3[4], o4[4], o5[4];
                const uint32_t p0[4] = {pf[0], 0, pf[1], 0}, p1[4] = {pf[2], 0, pf[3], 0};
                mma16z(o0, p0, vt0[0], vt0[1]); mma16z(o1, p0, vt1[0], vt1[1]);
                mma16z(o2, p1, vt0[2], vt0[3]); mma16z(o3, p1, vt1[2], vt1[3]);
                mma8z(o4, pf[4], 0, kv0); mma8z(o5, pf[4], 0, kv1);
                float sum = (((sc[0] + sc[1]) + (sc[2] + sc[3])) + ((sc[4] + sc[5]) + (sc[6] + sc[7]))) + (sc[8] + sc[9]);
                sum = (sum + __shfl_xor_sync(0xffffffffu, sum, 1)) + (__shfl_xor_sync(0xffffffffu, sum, 2) + __shfl_xor_sync(0xffffffffu, sum, 3));
                float inv; asm("rcp.approx.ftz.f32 %0, %1;" : "=f"(inv) : "f"(sum));
                const uint32_t ox = pack_bf16((o0[0] + o2[0] + o4[0]) * inv, (o0[1] + o2[1] + o4[1]) * inv);
                const uint32_t oy = pack_bf16((o1[0] + o3[0] + o5[0]) * inv, (o1[1] + o3[1] + o5[1]) * inv);
                char* const pp = ring0 + (pub + slot + (lo16 >> 1));
                st_pub(pp, ox, oy); st_pub(pp + 4096, ox, oy);
                if (OB || (XB & 4)) bar_arrive(10, (8 - nq) * 32 + OB);
                preload<0, PE, PL>(sw, wl + 28 * 512, zero);
            }
            kv0 = movm(kv0); kv1 = movm(kv1);
        } else {
            *(uint32_t*)(kvo + (uint32_t)(s * (NH * 2048) + lane * 4)) = kv0;
            bar_sync(3, last ? 256 : 256 + OB);
            if (last) break;
            preload<1, 0, CL>(sw, wl + 28 * 512, zero);
        }
        uint2 c[11];
        bar_sync(4, 256 + OB);
        const char* po = ring0 + (o_rd + slot + (lo16 >> 1) + delay<DLO>(zero));
        poll_issue<11>(c, po, rank < 2);
        preload<0, PV ? PL : CL, 12>(sw, wl + 28 * 512, zero);
        if (PV) { uint32_t* d = (uint32_t*)(kvo + (uint32_t)(s * (NH * 2048) + lane * 4)); d[0] = kv0; d[32] = kv1; }
        {
            float acc[4][4];
            uint32_t sx[GX][4];
#pragma unroll
            for (int i = 0; i < GX; i++) ldsm4t(sx[i], wl + (40 + i) * 512);
            if (FNC & 2) bar_arrive(15, 256);
            poll_check<11>(c, po, delay<(FNC >> 1)>(zero));
            if (OB || (XB & 2)) bar_arrive(9, 256 + OB);
#pragma unroll
            for (int f = 0; f < 22; f++) {
                const int kk = f >> 1, a = f & 3;
                if (f < 4) mma16z(acc[a], sw[f], c[kk].x, c[kk].y);
                else if (f >= 12 && f < 12 + GX) mma16(acc[a], sx[f - 12], c[kk].x, c[kk].y);
                else mma16(acc[a], sw[f % (12 + GX)], c[kk].x, c[kk].y);
                if (f + 12 + GX < 22) ldsm4t(sw[f], wl + (40 + GX + f) * 512);
            }
#pragma unroll
            for (int i = 0; i < 2; i++) {
#pragma unroll
                for (int j = 0; j < 4; j++) acc[i][j] += acc[i + 2][j];
                sts128(l16 + CH_PART + i * 4096 + w * 512, acc[i]);
            }
        }
        if (!PV && w < 2) {
            bar_sync(5, 288 + OB);
            float4 v[8];
#pragma unroll
            for (int i = 0; i < 8; i++) v[i] = lds128(l16 + CH_PART + w * 4096 + i * 512);
            float4 r = add4(add4(add4(v[0], v[1]), add4(v[2], v[3])), add4(add4(v[4], v[5]), add4(v[6], v[7])));
            if (!mown) st_async4(mapa(l16 + CH_MX + rank * 512, w), r, mapa(barM, w));
            bar_arrive(7, 256 + OB);
            if (mown) {
                mbar_wait(barM, s & 1);
                float4 x = lds128(l16 + CH_MX + (rank ^ 1) * 512), y = lds128(l16 + CH_MX + 2 * 512);
                r = add4(add4(x, r), y);
                const uint32_t mx = movm(pack_bf16(r.x, r.y)), my = movm(pack_bf16(r.z, r.w));
                const uint32_t ns = (slot + 0x4000) & 0xC000;
                char* const pp = ring0 + (pub + ns + (lo16 >> 1));
                st_pub(pp, mx, my); st_pub(pp + 4096, mx, my);
            }
            preload<0, 0, ML>(sw, wl, zero);
        } else {
            bar_arrive(5, 288 + OB);
            bar_sync(7, 256 + OB);
            preload<MP, 0, ML>(sw, wl, zero);
        }
        bar_sync(6, 320 + OB);
    }
}

__device__ __forceinline__ void chain_pace(const uint32_t sb, const int lane, const int rank, const int aware) {
    const uint32_t zero = sb + CH_BAR + 24;
    if (lane == 0) {
        char* ring = ring_base();
        uint32_t* p0 = (uint32_t*)(ring + ring_off(blockIdx.x & 15, 0) + 3072 + (blockIdx.x >> 4) * 128);
        uint32_t* p1 = (uint32_t*)(ring + ring_off(blockIdx.x & 15, 1) + 3072 + (blockIdx.x >> 4) * 128);
        *p0 = 0; *p1 = 0;
        int b0 = 1 << 30, b1 = 1 << 30; uint32_t v = 0;
        for (int r = 0; r < 4 || (r < 256 && !mbar_test(sb + CH_BAR + 16, 0)); r++) {
            uint32_t t0 = clk(); v = atomicExch(p0 + (v == 500), r); uint32_t t1 = v == 777 ? clk() + 1 : clk(); b0 = min(b0, (int)(t1 - t0));
            t0 = clk(); v = atomicExch(p1 + (v == 500), r); t1 = v == 777 ? clk() + 1 : clk(); b1 = min(b1, (int)(t1 - t0));
            asm volatile("st.volatile.shared.u32 [%0], %1;" ::"r"(zero + 4), "r"(aware ? (b1 < b0) ^ (aware - 1) : 0) : "memory");
        }
    }
    __syncwarp();
#pragma unroll 1
    for (int s = 1; s < NSEG; s++) {
        bar_sync(5, 288 + OB);
        bar_arrive(6, 320 + OB + (rank == 2 ? delay<PACE2>(zero) : 0));
    }
}
__device__ __forceinline__ char* reset_ptr(const int lane, const int rank, const int h) {
    const int nq = rank == 0 ? 6 : 5, v0 = rank == 0 ? -6 : 3 * rank - 6;
    int pos, cw = o_chunk(h * 8 + v0 + min(max(5 + (lane >> 3), nq), 7), pos);
    if (lane >= 24 && rank < 2) { cw = 24 + (h >> 2); pos = (2 * h + rank) & 7; }
    return ring_base() + ((ring_off(cw, 0) & ~4096u) + pos * 256 + (lane & 7) * 16);
}
__device__ __forceinline__ void chain_chores(const uint32_t sb, const int lane, const int rank, const int h, const bf16* __restrict__ mem0) {
    const int nq = rank == 0 ? 6 : 5, u0 = rank == 0 ? 0 : 1 + 5 * rank, v0 = rank == 0 ? -6 : 3 * rank - 6;
    const uint32_t barS = sb + CH_BAR, barM = barS + 8, barX = barS + 16;
    auto xload = [&](int s) {
        mbar_expect(barX, 8192 - nq * 512);
        bulk_load(sb + CH_XS, g_kx + (size_t)(s * NH + h) * 4096 + u0 * 256, nq * 512, barX);
        bulk_load(sb + CH_XS + nq * 512, g_vx + (size_t)(s * NH + h) * 4096 + (v0 + nq) * 512, (8 - nq) * 1024, barX);
    };
    char* const rb = reset_ptr(lane, rank, h);
    int* const kvf = g_kvf + blockIdx.x * 16;
    if (rank < 2) {
        const uint32_t* p = (const uint32_t*)(mem0 + (lane >> 2) * DM + 32 * h + 16 * rank + 2 * (lane & 3));
        char* d = ring_base() + ((ring_off(24 + (h >> 2), 0) & ~4096u) + ((2 * h + rank) & 7) * 256 + lane * 8);
        const uint32_t x = p[0] == SENT ? 0x7FFF7FFFu : p[0];
        st_pub(d, x, p[4]); st_pub(d + 4096, x, p[4]);
    }
    if (!KVN) __nanosleep(18000);
    wait_ctr(kvf, KVN);
    asm volatile("fence.proxy.async.global;" ::: "memory");
    if (elect()) xload(0);
#pragma unroll 1
    for (int s = 0; s < NSEG - 1; s++) {
        if (lane == 0) {
            mbar_expect(barS, 2 * 1280);
            if (rank < 2) mbar_expect(barM, 2 * 512);
        }
        bar_sync(13, 64);
#pragma unroll
        for (int i = 0; i < 4; i++)
            asm volatile("st.relaxed.gpu.global.v4.u32 [%0], {%1,%1,%1,%1};" ::"l"(rb + ((((s + 2) & 3) << 14) + (i >> 1) * 4096 + (i & 1) * 128)), "r"(SENT) : "memory");
        if (FEN || (s & 3) == 0) fence_gpu();
        if (lane == 0 && (s & 3) == 0 && s) atomicAdd(g_ctr + C_CHAIN + (s >> 2) - 1, 1);
        if ((s & 3) == 3) { wait_ctr(kvf + (s >> 2) + 1, KVN); asm volatile("fence.proxy.async.global;" ::: "memory"); }
        __syncwarp();
        bar_sync(12, 64);
        if (elect()) xload(s + 1);
        mbar_wait(barX, (s + 1) & 1);
        bar_sync(6, 320 + OB);
    }
}

struct S4Params { const bf16 *Are, *Aim, *Bre, *Bim, *Cre, *Cim, *ldt, *dsk; };
__device__ __forceinline__ float2 cmul(float2 a, float2 b) { return make_float2(a.x * b.x - a.y * b.y, a.x * b.y + a.y * b.x); }
__device__ __forceinline__ float2 csq(float2 a) { return make_float2(a.x * a.x - a.y * a.y, (a.x + a.x) * a.y); }
__device__ __forceinline__ float2 cexp_t(float lr, float turns) {
    float f = (turns - rintf(turns)) * 6.283185307179586f, e = ex2(lr);
    return make_float2(e * __cosf(f), e * __sinf(f));
}
__device__ __forceinline__ float bf_at(uint2 v, int i) {
    const uint32_t w = i < 2 ? v.x : v.y;
    return __uint_as_float((i & 1) ? w & 0xFFFF0000u : w << 16);
}
__device__ __forceinline__ void kg_step(uint32_t (&a)[4][4], uint32_t (&b)[5][2], uint32_t pa, uint32_t pe, float x0) {
#pragma unroll
    for (int i = 0; i < 2; i++) {
        const float4 p = lds128(pa + i * 64);
        const float2 e8 = lds64(pe + i * 32), c = make_float2(p.z, p.w);
        const float mag = ex2(p.x * x0), ph = p.y * x0;
        float2 e0 = make_float2(mag * __cosf(ph), mag * __sinf(ph)), e1 = cmul(e0, e8);
#pragma unroll
        for (int j = 0; j < 4; j++) {
            a[j][2 * i] = pack_bf16(e0.x, e0.y); a[j][2 * i + 1] = pack_bf16(e1.x, e1.y);
            e0 = csq(e0); e1 = csq(e1);
        }
        float2 m = cmul(c, e0);
        b[0][i] = pack_bf16(m.x, -m.y);
#pragma unroll
        for (int j = 0; j < 4; j++) {
            m = cmul(c, e1);
            b[j + 1][i] = pack_bf16(m.x, -m.y);
            if (j < 3) e1 = csq(e1);
        }
    }
}
__device__ __forceinline__ void kg_mma(float (&kd)[5][4], const uint32_t (&a)[4][4], const uint32_t (&b)[5][2]) {
    mma16(kd[0], a[0], b[0][0], b[0][1]);
#pragma unroll
    for (int j = 0; j < 4; j++) mma16(kd[j + 1], a[j], b[j + 1][0], b[j + 1][1]);
}
struct KgRaw { uint2 v[6]; float ldt; };
__device__ __forceinline__ void kg_load(KgRaw& r, const S4Params& P, int d, int lane) {
    const bf16* src[6] = {P.Are, P.Aim, P.Bre, P.Bim, P.Cre, P.Cim};
#pragma unroll
    for (int j = 0; j < 6; j++) r.v[j] = __ldg((const uint2*)(src[j] + d * 128) + lane);
    r.ldt = __bfloat162float(P.ldt[d]);
}
__device__ __forceinline__ float kg_params(const KgRaw& r, uint32_t stg, int lane) {
    const float dt = __bfloat162float(__float2bfloat16(expf(r.ldt)));
    float k2048 = 0.f;
#pragma unroll
    for (int i = 0; i < 4; i++) {
        const float br = dt * bf_at(r.v[2], i), bi = dt * bf_at(r.v[3], i), cr = bf_at(r.v[4], i), ci = bf_at(r.v[5], i);
        const float zr = dt * bf_at(r.v[0], i) * 1.4426950408889634f;
        float zt = dt * bf_at(r.v[1], i) * 0.15915494309189535f;
        zt -= rintf(zt);
        const float v[4] = {zr, zt * 6.283185307179586f, cr * br - ci * bi, cr * bi + ci * br};
        const float2 e8 = cexp_t(8.f * zr, 8.f * zt), el = cexp_t(2048.f * zr, 2048.f * zt);
        k2048 += v[2] * el.x - v[3] * el.y;
        sts128(stg + (i * 32 + lane) * 16, v);
        sts64(stg + 2048 + (i * 32 + lane) * 8, e8.x, e8.y);
    }
#pragma unroll
    for (int o = 16; o; o >>= 1) k2048 += __shfl_xor_sync(0xffffffffu, k2048, o);
    __syncwarp();
    return k2048;
}
__device__ __forceinline__ void kg_store(const float (&kd)[5][4], float k2048, uint32_t stg, int d, int lane) {
    __syncwarp();
    const uint32_t ta = stg + (lane & 7) * 32 + ((lane >> 3) & 1) * 16 + (lane >> 4) * 256;
    stsm4t(ta, pack_bf16(kd[0][0], kd[0][1]), pack_bf16(kd[0][2], kd[0][3]), pack_bf16(kd[1][0], kd[1][1]), pack_bf16(kd[1][2], kd[1][3]));
    stsm4t(ta + 512, pack_bf16(kd[2][0], kd[2][1]), pack_bf16(kd[2][2], kd[2][3]), pack_bf16(kd[3][0], kd[3][1]), pack_bf16(kd[3][2], kd[3][3]));
    stsm4t(ta + 1024, pack_bf16(kd[4][0], kd[4][1]), pack_bf16(kd[4][2], kd[4][3]), pack_bf16(k2048, 0.f), 0);
    __syncwarp();
#pragma unroll
    for (int j = 0; j < 3; j++) ((float4*)(g_kd + d * 768))[j * 32 + lane] = lds128(stg + j * 512 + lane * 16);
    __syncwarp();
}

__global__ void __cluster_dims__(3, 1, 1) __launch_bounds__(CH_THREADS, 1)
chain_kernel(const __grid_constant__ CUtensorMap mq, const __grid_constant__ CUtensorMap mk, const __grid_constant__ CUtensorMap mv,
             const __grid_constant__ CUtensorMap mo, const bf16* __restrict__ Wq, const bf16* __restrict__ Wk, const bf16* __restrict__ Wv,
             const bf16* __restrict__ mem0, const __grid_constant__ S4Params P, int aware) {
    extern __shared__ __align__(1024) unsigned char smem[];
    const uint32_t sb = smem_u32(smem);
    const int tid = threadIdx.x, lane = tid & 31;
    const int w = __shfl_sync(0xffffffffu, tid >> 5, 0);
    int rank; asm("mov.u32 %0, %%cluster_ctarank;" : "=r"(rank));
    const int h = blockIdx.x / 3;
    if (tid == 0) {
        mbar_init(sb + CH_BAR, 1); mbar_init(sb + CH_BAR + 8, 1); mbar_init(sb + CH_BAR + 16, 1);
        for (int i = 0; i < 16; i++) mbar_init(sb + CH_BAR + 64 + i * 8, 1);
        *(int*)(smem + CH_BAR + 24) = 0; *(int*)(smem + CH_BAR + 28) = 0; *(int*)(smem + CH_BAR + 32) = 0;
        asm volatile("fence.mbarrier_init.release.cluster;" ::: "memory");
    }
    if (w == 10 && PFKV) {
        const int e = lane * 96 + blockIdx.x;
        if (e < 2048) asm volatile("cp.async.bulk.prefetch.L2.global [%0], 8192;" ::"l"(((e & 1) ? Wv : Wk) + (size_t)(e >> 1) * HD) : "memory");
        if (PFKV > 1) __nanosleep(PFKV);
    }
    if (w == 9) {
        char* const rb = reset_ptr(lane, rank, h);
#pragma unroll
        for (int i = 0; i < 8; i++)
            asm volatile("st.relaxed.gpu.global.v4.u32 [%0], {%1,%1,%1,%1};" ::"l"(rb + (((i >> 2) << 14) + ((i >> 1) & 1) * 4096 + (i & 1) * 128)), "r"(SENT) : "memory");
        if (lane < 16) g_kvf[blockIdx.x * 16 + lane] = 0;
        if (blockIdx.x == 0)
            for (int k = lane; k < N_CTR; k += 32) g_ctr[k] = 0;
        fence_gpu();
        __syncwarp();
        asm volatile("griddepcontrol.launch_dependents;" ::: "memory");
    }
    __syncthreads();
    asm volatile("barrier.cluster.arrive.relaxed.aligned;" ::: "memory");

    if (w >= 8) {
        reg_dec<24>();
        asm volatile("barrier.cluster.wait.aligned;" ::: "memory");
        if (w == 8) chain_pace(sb, lane, rank, aware);
        else if (w == 9) {
            chain_chores(sb, lane, rank, h, mem0);
            asm volatile("st.volatile.shared.u32 [%0], %1;" ::"r"(sb + CH_BAR + 32), "r"(0x3F803F80) : "memory");
        } else if (w == 11 && KEEP) {
#pragma unroll 1
            for (int it = 0; it < (1 << 22); it++) {
                int d0, d1;
                const uint32_t x = delay<1>(sb + CH_BAR + 32);
                asm volatile("mma.sync.aligned.m8n8k16.row.col.s32.s8.s8.s32 {%0,%1}, {%2}, {%2}, {%3,%3};" : "=r"(d0), "=r"(d1) : "r"(x), "r"(0));
                if (d0 | d1) break;
                if ((XB & 8) && lane == 0) asm volatile("st.relaxed.gpu.global.u32 [%0], %1;" ::"l"(g_kd + DM * 768 + blockIdx.x * 64), "r"(it) : "memory");
                if ((XB & 16) && lane == 0) ld_acq((int*)(g_kd + DM * 768 + blockIdx.x * 64));
                __nanosleep(KEEP);
            }
        }
    } else {
        reg_inc<240>();
        const int nq = rank == 0 ? 6 : 5;
        const int u0 = rank == 0 ? 0 : 1 + 5 * rank;
        const int v0 = rank == 0 ? -6 : 3 * rank - 6;
        const int gw = rank * 8 + w;
        const int ks0 = gw < 16 ? 11 * gw : 176 + 10 * (gw - 16);
        const int nko = gw < 16 ? 11 : 10;
        const uint32_t wr = sb + w * CH_WREG, bar0 = sb + CH_BAR + 64 + w * 16, bar1 = bar0 + 8;
        uint32_t wa[36][4];
        const uint32_t vst = sb + CH_PART + w * 2048;
        const int cq = h * DH + 8 * u0, cv = h * DH + 16 * (v0 + 6);
        const int r8 = lane >> 2, p = lane & 3;
        const bf16* src = p >= 2 ? ((p & 1) ? Wk : Wq) + cq + 32 : rank == 0 ? ((p & 1) ? Wk : Wq) + cq + 40 : Wv + cv - 16 + 8 * p;
        src += (size_t)(128 * w + r8) * HD;
        auto cp_rows = [&](int kh) {
            cp16(wr + ((kh >> 1) * 2 + (p >> 1)) * 512 + ((kh & 1) * 2 + (p & 1)) * 128 + r8 * 16, src + (size_t)kh * 8 * HD);
        };
        {
            int d = blockIdx.x * 8 + w, t = 0;
            const int d1 = 768 + blockIdx.x * 3 + w, nt = (w < 3 && d1 < DM) ? 32 : 16;
            const uint32_t stg = wr + 4096;
            KgRaw raw, raw1;
            kg_load(raw, P, d, lane);
            kg_load(raw1, P, min(d1, DM - 1), lane);
            float kd[5][4], k2048;
#pragma unroll 1
            for (int i = -LDW; i < 9 || t < nt; i++) {
                if (i >= 0 && i < 9) {
                    const uint32_t bar = bar0 + (i & 1) * 8;
                    if (i >= 2) mbar_wait(bar, ((i >> 1) - 1) & 1);
                    if (elect()) {
                        mbar_expect(bar, 2048);
                        if (i < 8) tma2d(wr + 8192 + (i & 1) * 8192 + (i >> 1) * 2048, (i & 1) ? &mk : &mq, cq, 128 * w + 32 * (i >> 1), bar);
                        else tma2d(vst, &mv, cv, 128 * w, bar);
                    }
                    if (i < 8) cp_rows(i);
                }
#pragma unroll 1
                for (int e = min(t + KGS, nt); t < e; t++) {
                    if ((t & 15) == 0) {
                        k2048 = kg_params(raw, stg, lane);
#pragma unroll
                        for (int j = 0; j < 20; j++) kd[j >> 2][j & 3] = 0.f;
                    }
                    uint32_t ka[4][4], kb[5][2];
                    kg_step(ka, kb, stg + ((t & 15) * 8 + (lane & 3)) * 16, stg + 2048 + ((t & 15) * 8 + (lane & 3)) * 8, (float)(lane >> 2));
                    kg_mma(kd, ka, kb);
                    if ((t & 15) == 15) { kg_store(kd, k2048, stg, d, lane); raw = raw1; d = d1; }
                }
            }
        }
        const uint32_t lrow = ((lane >> 4) * 8 + (lane & 7)) * 64, lsw = (lane >> 1) & 3, lh = (lane >> 3) & 1;
        mbar_wait(bar1, 1); mbar_wait(bar0, 0);
#pragma unroll
        for (int i = 0; i < 32; i++) ldsm4t(wa[i], wr + 8192 + lh * 8192 + (i & 7) * 1024 + lrow + (((i >> 3) ^ lsw) << 4));
#pragma unroll
        for (int i = 0; i < 4; i++) ldsm4t(wa[32 + i], vst + (i >> 1) * 1024 + lrow + ((((i & 1) * 2 + lh) ^ lsw) << 4));
        asm volatile("fence.proxy.async.shared::cta;" ::"r"(wa[31][0]), "r"(wa[35][0]) : "memory");
        __syncwarp();
#pragma unroll 1
        for (int i = 9; i < 18; i++) {
            const uint32_t bar = bar0 + (i & 1) * 8;
            if (i >= 11) mbar_wait(bar, ((i >> 1) - 1) & 1);
            if (elect()) {
                const int j = 2 * (i - 12), nb = min(2, nko - j);
                mbar_expect(bar, i < 12 ? 2048 : nb * 1024);
                if (i < 12) tma2d(wr + 8192 + (i - 9) * 2048, &mv, cv, 128 * w + 32 * (i - 8), bar);
                else {
                    if (nb > 0) tma2d(wr + 14336 + j * 1024, &mo, 32 * h, 16 * (ks0 + j), bar);
                    if (nb > 1) tma2d(wr + 15360 + j * 1024, &mo, 32 * h, 16 * (ks0 + j + 1), bar);
                }
            }
            if (i < 17) cp_rows(i - 1);
        }
        mbar_wait(bar0, 0); mbar_wait(bar1, 0);
#pragma unroll 1
        for (int i0 = -1; i0 < 17; i0 += 6) {
            uint32_t x[6][2][4];
#pragma unroll
            for (int i = 0; i < 6; i++) {
                const uint32_t a = wr + 8192 + max(i0 + i, 0) * 1024 + lrow;
                ldsm4t(x[i][0], a + ((lh ^ lsw) << 4)); ldsm4t(x[i][1], a + (((2 + lh) ^ lsw) << 4));
            }
            if (i0 == 11 && nko == 10) {
#pragma unroll
                for (int j = 0; j < 8; j++) x[5][j >> 2][j & 3] = 0;
            }
            __syncwarp();
#pragma unroll
            for (int i = 0; i < 6; i++) {
                const uint32_t a = wr + 8192 + max(i0 + i, 0) * 1024 + lane * 16;
                stsm4t(a, x[i][0][0], x[i][0][1], x[i][0][2], x[i][0][3]); stsm4t(a + 512, x[i][1][0], x[i][1][1], x[i][1][2], x[i][1][3]);
            }
        }
        asm volatile("cp.async.wait_all;" ::: "memory");
        asm volatile("barrier.cluster.wait.aligned;" ::: "memory");
        bar_sync(1, 256);
        mbar_wait_long(sb + CH_BAR + 16, 0);
        const int side = __shfl_sync(0xffffffffu, *(volatile int*)(smem + CH_BAR + 28), 0);
        if (w >= nq) chain_loop<true>(wa, sb, w, lane, rank, h, side);
        else chain_loop<false>(wa, sb, w, lane, rank, h, side);
    }
}

constexpr int G_STAGE = 49152, G_NST = 4;
constexpr int G_STG = G_NST * G_STAGE;
constexpr int G_BAR = G_STG + 32768;
constexpr int G_SMEM = G_BAR + 256 + 1024;

#define WLOG(e)
constexpr int IT_QA = 0, IT_O = 1, IT_S4 = 2, IT_END = 3, IT_KV = 4;
#define O_WIDE 15
#define PING 1
#define S4DIR 5
#define S4REL 4
#define KVI 2
#define KVF 2
#define KVS 8
#define STM 0
__device__ __forceinline__ void st_out(uint32_t* p, uint32_t v) {
    if (STM == 0) *p = v;
    else if (STM == 1) __stcs(p, v);
    else asm volatile("st.global.L1::no_allocate.u32 [%0], %1;" ::"l"(p), "r"(v) : "memory");
}
#define Q_S1 0
#define Q_B0 10
#define Q_L 1
#define Q_T0 8
__device__ __forceinline__ int queue_item(int q) {
    if (q < 512) return (IT_KV << 16) | ((q >> 5) << 8) | (q & 31);
    q -= 512;
    if (q < Q_B0 * Q_T0) return (IT_QA << 16) | ((q % Q_B0) << 8) | (q / Q_B0);
    constexpr int W1 = O_WIDE - 1, T1 = Q_T0 + Q_L;
    if (q < W1 * Q_T0) return (IT_QA << 16) | ((q / Q_T0) << 8) | (q % Q_T0);
    if (q < W1 * T1) return (IT_QA << 16) | ((q % W1) << 8) | (q / W1);
    if (q < O_WIDE * T1) return (IT_QA << 16) | (W1 << 8) | (q - W1 * T1);
    if (q < O_WIDE * 16) return (IT_QA << 16) | ((q % O_WIDE) << 8) | (q / O_WIDE);
    q -= O_WIDE * 16;
    if (q < Q_S1) return (IT_S4 << 16) | q;
    q -= Q_S1;
    if (q < (16 - O_WIDE) * 8) return (IT_O << 16) | ((O_WIDE + (q >> 3)) << 8) | (q & 7);
    q -= (16 - O_WIDE) * 8;
    if (q < 128 - Q_S1) return (IT_S4 << 16) | (Q_S1 + q);
    return IT_END << 16;
}
constexpr int N_LATE = O_WIDE * 4 + (16 - O_WIDE) * 16;
static_assert(N_LATE <= 96, "first items of the late CTAs");
__device__ __forceinline__ int late_item(int j) {
    if (j < O_WIDE * 4) return (IT_O << 16) | ((j >> 2) << 8) | (j & 3);
    j -= O_WIDE * 4;
    return (IT_QA << 16) | ((O_WIDE + (j >> 4)) << 8) | (j & 15);
}
__device__ __forceinline__ void tma2d_store(const CUtensorMap* m, uint32_t src, int c0, int c1) {
    asm volatile("cp.async.bulk.tensor.2d.global.shared::cta.bulk_group [%0, {%2, %3}], [%1];" ::"l"(m), "r"(src), "r"(c0), "r"(c1) : "memory");
}

__device__ __forceinline__ void wgmma_s64(float (&d)[32], uint32_t a0, uint32_t a1, uint32_t a2, uint32_t a3, uint64_t db, int acc) {
    asm volatile("{.reg .pred p; setp.ne.b32 p, %37, 0;\n"
        "wgmma.mma_async.sync.aligned.m64n64k16.f32.bf16.bf16 {"
        "%0,%1,%2,%3,%4,%5,%6,%7,%8,%9,%10,%11,%12,%13,%14,%15,"
        "%16,%17,%18,%19,%20,%21,%22,%23,%24,%25,%26,%27,%28,%29,%30,%31"
        "}, {%32,%33,%34,%35}, %36, p, 1, 1, 0;}"
        : "+f"(d[0]), "+f"(d[1]), "+f"(d[2]), "+f"(d[3]), "+f"(d[4]), "+f"(d[5]), "+f"(d[6]), "+f"(d[7]), "+f"(d[8]), "+f"(d[9]), "+f"(d[10]), "+f"(d[11]), "+f"(d[12]), "+f"(d[13]), "+f"(d[14]), "+f"(d[15]), "+f"(d[16]), "+f"(d[17]), "+f"(d[18]), "+f"(d[19]), "+f"(d[20]), "+f"(d[21]), "+f"(d[22]), "+f"(d[23]), "+f"(d[24]), "+f"(d[25]), "+f"(d[26]), "+f"(d[27]), "+f"(d[28]), "+f"(d[29]), "+f"(d[30]), "+f"(d[31])
        : "r"(a0), "r"(a1), "r"(a2), "r"(a3), "l"(db), "r"(acc));
}
__device__ __forceinline__ void wgmma_s16(float (&d)[8], uint32_t a0, uint32_t a1, uint32_t a2, uint32_t a3, uint64_t db, int acc) {
    asm volatile("{.reg .pred p; setp.ne.b32 p, %13, 0;\n"
        "wgmma.mma_async.sync.aligned.m64n16k16.f32.bf16.bf16 {"
        "%0,%1,%2,%3,%4,%5,%6,%7"
        "}, {%8,%9,%10,%11}, %12, p, 1, 1, 0;}"
        : "+f"(d[0]), "+f"(d[1]), "+f"(d[2]), "+f"(d[3]), "+f"(d[4]), "+f"(d[5]), "+f"(d[6]), "+f"(d[7])
        : "r"(a0), "r"(a1), "r"(a2), "r"(a3), "l"(db), "r"(acc));
}
__device__ __forceinline__ void wgmma_v128(float (&d)[64], uint32_t a0, uint32_t a1, uint32_t a2, uint32_t a3, uint64_t db, int acc) {
    asm volatile("{.reg .pred p; setp.ne.b32 p, %69, 0;\n"
        "wgmma.mma_async.sync.aligned.m64n128k16.f32.bf16.bf16 {"
        "%0,%1,%2,%3,%4,%5,%6,%7,%8,%9,%10,%11,%12,%13,%14,%15,"
        "%16,%17,%18,%19,%20,%21,%22,%23,%24,%25,%26,%27,%28,%29,%30,%31,"
        "%32,%33,%34,%35,%36,%37,%38,%39,%40,%41,%42,%43,%44,%45,%46,%47,"
        "%48,%49,%50,%51,%52,%53,%54,%55,%56,%57,%58,%59,%60,%61,%62,%63"
        "}, {%64,%65,%66,%67}, %68, p, 1, 1, 1;}"
        : "+f"(d[0]), "+f"(d[1]), "+f"(d[2]), "+f"(d[3]), "+f"(d[4]), "+f"(d[5]), "+f"(d[6]), "+f"(d[7]), "+f"(d[8]), "+f"(d[9]), "+f"(d[10]), "+f"(d[11]), "+f"(d[12]), "+f"(d[13]), "+f"(d[14]), "+f"(d[15]), "+f"(d[16]), "+f"(d[17]), "+f"(d[18]), "+f"(d[19]), "+f"(d[20]), "+f"(d[21]), "+f"(d[22]), "+f"(d[23]), "+f"(d[24]), "+f"(d[25]), "+f"(d[26]), "+f"(d[27]), "+f"(d[28]), "+f"(d[29]), "+f"(d[30]), "+f"(d[31]), "+f"(d[32]), "+f"(d[33]), "+f"(d[34]), "+f"(d[35]), "+f"(d[36]), "+f"(d[37]), "+f"(d[38]), "+f"(d[39]), "+f"(d[40]), "+f"(d[41]), "+f"(d[42]), "+f"(d[43]), "+f"(d[44]), "+f"(d[45]), "+f"(d[46]), "+f"(d[47]), "+f"(d[48]), "+f"(d[49]), "+f"(d[50]), "+f"(d[51]), "+f"(d[52]), "+f"(d[53]), "+f"(d[54]), "+f"(d[55]), "+f"(d[56]), "+f"(d[57]), "+f"(d[58]), "+f"(d[59]), "+f"(d[60]), "+f"(d[61]), "+f"(d[62]), "+f"(d[63])
        : "r"(a0), "r"(a1), "r"(a2), "r"(a3), "l"(db), "r"(acc));
}

__device__ __forceinline__ void attn_scores(float (&sx)[32], float (&sm)[8], const uint32_t (&q)[32], uint32_t sk) {
    const uint64_t dx = mkdesc(sk, 1024, 128, 0), dm = mkdesc(sk + 16384, 256, 128, 0);
    wg_fence();
#pragma unroll
    for (int ks = 0; ks < 8; ks++) {
        wgmma_s64(sx, q[4 * ks], q[4 * ks + 1], q[4 * ks + 2], q[4 * ks + 3], dx + ks * 128, ks);
        wgmma_s16(sm, q[4 * ks], q[4 * ks + 1], q[4 * ks + 2], q[4 * ks + 3], dm + ks * 32, ks);
    }
    wg_commit();
}
template <bool HI>
__device__ __forceinline__ void attn_softmax(uint32_t (&p)[2][20], const float (&sx)[2][32], const float (&sm)[2][8], bool sb, int lane) {
    constexpr int NF = HI ? 2 : 0, NT = NF + 3;
    const int gt = (lane >> 2) - 2 * (lane & 3);
    const float cs = 0.08838834764831845f * 1.4426950408889634f;
    float s[2][NT][4], m[4], l[4];
#pragma unroll
    for (int h = 0; h < 2; h++) {
#pragma unroll
        for (int j = 0; j < NT; j++)
#pragma unroll
            for (int e = 0; e < 4; e++) s[h][j][e] = j == NT - 1 ? (sb ? sm[h][4 + e] : sm[h][e]) : (sb ? sx[h][16 + 4 * j + e] : sx[h][4 * j + e]);
        if (gt < 0) s[h][NF][0] = s[h][NF + 1][2] = -INFINITY;
        if (gt < 1) s[h][NF][1] = s[h][NF + 1][3] = -INFINITY;
        m[2 * h] = fmaxf(s[h][0][0], s[h][0][1]); m[2 * h + 1] = fmaxf(s[h][0][2], s[h][0][3]);
#pragma unroll
        for (int j = 1; j < NT; j++) {
            if (j != NF + 1) m[2 * h] = fmaxf(m[2 * h], fmaxf(s[h][j][0], s[h][j][1]));
            m[2 * h + 1] = fmaxf(m[2 * h + 1], fmaxf(s[h][j][2], s[h][j][3]));
        }
    }
#pragma unroll
    for (int r = 0; r < 4; r++) m[r] = fmaxf(m[r], __shfl_xor_sync(0xffffffffu, m[r], 1));
#pragma unroll
    for (int r = 0; r < 4; r++) m[r] = fmaxf(m[r], __shfl_xor_sync(0xffffffffu, m[r], 2)) * -cs;
#pragma unroll
    for (int r = 0; r < 4; r++) {
        l[r] = 0.f;
#pragma unroll
        for (int j = 0; j < NT; j++)
            if ((r & 1) || j != NF + 1) {
                float* v = &s[r >> 1][j][2 * (r & 1)];
                v[0] = ex2(fmaf(v[0], cs, m[r])); v[1] = ex2(fmaf(v[1], cs, m[r]));
                l[r] += v[0] + v[1];
            }
    }
#pragma unroll
    for (int r = 0; r < 4; r++) l[r] += __shfl_xor_sync(0xffffffffu, l[r], 1);
#pragma unroll
    for (int r = 0; r < 4; r++) { l[r] += __shfl_xor_sync(0xffffffffu, l[r], 2); asm("rcp.approx.ftz.f32 %0, %0;" : "+f"(l[r])); }
    const uint32_t ma = sb ? 0u : ~0u;
#pragma unroll
    for (int h = 0; h < 2; h++)
#pragma unroll
        for (int j = 0; j < 5; j++) {
            const bool on = j == 4 || j < NF + 2;
            const int k = j == 4 ? NT - 1 : on ? j : 0, ia = j < 4 ? 2 * j : 16, ib = j < 4 ? 8 + 2 * j : 18;
            const uint32_t x = on && j != NF + 1 ? pack_bf16(s[h][k][0] * l[2 * h], s[h][k][1] * l[2 * h]) : 0;
            const uint32_t y = on ? pack_bf16(s[h][k][2] * l[2 * h + 1], s[h][k][3] * l[2 * h + 1]) : 0;
            asm volatile("and.b32 %0, %4, %6; and.b32 %1, %5, %6; and.b32 %2, %4, %7; and.b32 %3, %5, %7;"
                : "=&r"(p[h][ia]), "=&r"(p[h][ia + 1]), "=&r"(p[h][ib]), "=&r"(p[h][ib + 1]) : "r"(x), "r"(y), "r"(ma), "r"(~ma));
        }
}
__device__ __forceinline__ void attn_pv(float (&o)[64], const uint32_t (&p)[20], uint32_t sv) {
    const uint64_t dx = mkdesc(sv, 128, 1024, 0), dm = mkdesc(sv + 16384, 128, 256, 0);
    wg_fence();
#pragma unroll
    for (int ks = 0; ks < 5; ks++) wgmma_v128(o, p[4 * ks], p[4 * ks + 1], p[4 * ks + 2], p[4 * ks + 3], ks < 4 ? dx + ks * 16 : dm, ks);
    wg_commit();
}
__device__ __forceinline__ void attn_stage(const float (&o)[64], uint32_t dst) {
#pragma unroll
    for (int u = 0; u < 16; u += 2)
        stsm4(dst + (u >> 3) * 8192 + (u & 7) * 128, pack_bf16(o[4 * u], o[4 * u + 1]), pack_bf16(o[4 * u + 2], o[4 * u + 3]),
              pack_bf16(o[4 * u + 4], o[4 * u + 5]), pack_bf16(o[4 * u + 6], o[4 * u + 7]));
}

template <int BN, int NKB, bool BLOCKED_A>
__device__ __forceinline__ void mainloop(float (&acc)[BN / 2], uint32_t sb, int wgi, uint32_t full, uint32_t empty, int& it, bool elect) {
#pragma unroll
    for (int j = 0; j < BN / 2; j++) acc[j] = 0.f;
#pragma unroll 1
    for (int k4 = 0; k4 < NKB; k4 += 4) {
#pragma unroll
        for (int st = 0; st < 4; st++, it++) {
            mbar_wait_long(full + 8 * st, (it >> 2) & 1);
            const uint64_t da = BLOCKED_A ? mkdesc(sb + st * G_STAGE + wgi * 8192, 128, 1024, 0) : mkdesc(sb + st * G_STAGE + wgi * 8192, 16, 1024, 1);
            const uint64_t db = mkdesc(sb + st * G_STAGE + 16384, 8192, 1024, 1);
            wg_fence();
#pragma unroll
            for (int k = 0; k < 4; k++) {
                if constexpr (BN == 256) wgmma256(acc, da + k * (BLOCKED_A ? 16 : 2), db + k * 128, 1);
                else wgmma128(acc, da + k * (BLOCKED_A ? 16 : 2), db + k * 128, 1);
            }
            wg_commit();
            if (k4 | st) {
                wg_wait<1>();
                if (elect) mbar_arrive(empty + 8 * ((st + 3) & 3));
            }
        }
    }
    wg_wait<0>();
    if (elect) mbar_arrive(empty + 8 * 3);
}

__device__ __forceinline__ uint32_t n6_a(int st) { return st < 4 ? st * G_STAGE : (2 * st - 8) * G_STAGE + 32768; }
__device__ __forceinline__ uint32_t n6_b(int st) { return st < 4 ? st * G_STAGE + 16384 : (2 * st - 7) * G_STAGE + 32768; }
__device__ __forceinline__ uint32_t n6_bar(int st) { return st < 4 ? 8 * st : 96 + 8 * st; }
__device__ __forceinline__ void mainloop6(float (&acc)[64], uint32_t sb, int wgi, uint32_t full, uint32_t empty, int& it, bool elect) {
#pragma unroll
    for (int j = 0; j < 64; j++) acc[j] = 0.f;
    int st = 0, prev = 0, r = 0;
#pragma unroll 1
    for (int kb = 0; kb < 64; kb++) {
        mbar_wait_long(full + n6_bar(st), ((st < 4 ? it >> 2 : 0) + r) & 1);
        const uint64_t da = mkdesc(sb + n6_a(st) + wgi * 8192, 128, 1024, 0), db = mkdesc(sb + n6_b(st), 8192, 1024, 1);
        wg_fence();
#pragma unroll
        for (int k = 0; k < 4; k++) wgmma128(acc, da + k * 16, db + k * 128, 1);
        wg_commit();
        if (kb) {
            wg_wait<1>();
            if (elect) mbar_arrive(empty + n6_bar(prev));
        }
        prev = st;
        if (++st == 6) { st = 0; r++; }
    }
    wg_wait<0>();
    if (elect) mbar_arrive(empty + 8 * 3);
    it += 44;
}

template <int BN>
__device__ __forceinline__ void o_item(uint32_t sb, int wgi, int wi, int lane, uint32_t full, uint32_t empty, int& it, const CUtensorMap* mout,
                                       int row0, int col0, uint32_t stgpar) {
    float acc[BN / 2];
    if constexpr (BN == 256) mainloop<BN, 64, true>(acc, sb, wgi, full, empty, it, lane == 0);
    else mainloop6(acc, sb, wgi, full, empty, it, lane == 0);
    ST((row0 >> 4) + (col0 / BN), wgi * 4 + wi, 10);
    mbar_wait(full + 104, stgpar);
    const uint32_t stg = sb + G_STG + (wgi * 4 + wi) * 4096;
    const int r = lane & 15, cu = lane >> 4;
#pragma unroll
    for (int hf = 0; hf < BN / 128; hf++) {
        if (elect()) asm volatile("cp.async.bulk.wait_group.read 0;" ::: "memory");
        __syncwarp();
#pragma unroll
        for (int j = 0; j < 8; j++) {
            const float* a = acc + hf * 64 + j * 8;
            stsm4(stg + (j >> 2) * 2048 + r * 128 + ((((j & 3) * 2 + cu) ^ (r & 7)) << 4),
                  pack_bf16(a[0], a[1]), pack_bf16(a[2], a[3]), pack_bf16(a[4], a[5]), pack_bf16(a[6], a[7]));
        }
        asm volatile("fence.proxy.async.shared::cta;" ::: "memory");
        __syncwarp();
        if (elect()) {
            tma2d_store(mout, stg, col0 + hf * 128, row0 + wgi * 64 + wi * 16);
            tma2d_store(mout, stg + 2048, col0 + hf * 128 + 64, row0 + wgi * 64 + wi * 16);
            asm volatile("cp.async.bulk.commit_group;" ::: "memory");
        }
    }
}

constexpr int S4_KD = 32768;
constexpr int S4_CH = 2 * G_STAGE;
constexpr int S4_HALF = 2304;
constexpr int S4_WD = 2 * S4_HALF;
constexpr int S4_T2 = S4_WD + 2304;
constexpr int S4_T3 = S4_T2 + 1024;
constexpr int S4_STRIDE = S4_T3 + 640 + 16;
__device__ __forceinline__ uint32_t addz(uint32_t x, uint32_t z) { uint32_t r; asm volatile("add.u32 %0, %1, %2;" : "=r"(r) : "r"(x), "r"(z)); return r; }
__device__ __forceinline__ uint32_t lds16(uint32_t a) { uint32_t v; asm volatile("ld.shared.u16 %0, [%1];" : "=r"(v) : "r"(a) : "memory"); return v; }
__device__ __forceinline__ uint32_t ldsu(uint32_t a) { return __float_as_uint(lds32(a)); }

template <int E0, int NE, int KP>
__device__ __forceinline__ void s4_windows(float (&acc)[8][2][4], uint32_t ut, uint32_t tw, int rho, int w, int lane, uint32_t z) {
    const int gt = (lane >> 2) - 2 * (lane & 3), p0 = rho == 16 ? -3 : -2, c = (lane >> 3) + p0;
    uint32_t band[2][4], ta[NE][4];
    {
        const uint64_t ones = ((uint64_t)((2u << 2 * w) - 1) << 32) >> (8 * p0 + 24 - gt + rho + w);
        uint32_t f[5];
#pragma unroll
        for (int m = 0; m < 5; m++) f[m] = ((((uint32_t)(ones >> (8 * m)) & 3) * 0x8001u) & 0x10001u) * 0x3F80u;
#pragma unroll
        for (int j = 0; j < 2; j++) { band[j][0] = f[2 * j + 1]; band[j][1] = addz(f[2 * j], z); band[j][2] = f[2 * j + 2]; band[j][3] = addz(f[2 * j + 1], z); }
    }
#pragma unroll
    for (int e = 0; e < NE; e++)
        asm volatile("ld.shared.u32 %0, [%4]; ld.shared.u32 %1, [%4+%5]; ld.volatile.shared.u32 %2, [%4+%6]; ld.volatile.shared.u32 %3, [%4];"
            : "=r"(ta[e][0]), "=r"(ta[e][1]), "=r"(ta[e][2]), "=r"(ta[e][3]) : "r"(tw + 16 * (E0 + e) * KP), "n"(8 * KP), "n"(-8 * KP) : "memory");
    const uint32_t ua = ut + (c & 1) * S4_HALF + (16 + (lane & 7) + (c >> 1)) * 16;
#pragma unroll
    for (int J = 0; J < 8 - E0; J++) {
        uint32_t u0[4], u1[4];
        ldsm4(u0, ua + J * 256); ldsm4(u1, ua + J * 256 + 128);
        float s0[4], s1[4];
        mma16z(s0, band[0], u0[0], u0[1]); mma16z(s1, band[0], u1[0], u1[1]);
        mma16(s0, band[1], u0[2], u0[3]); mma16(s1, band[1], u1[2], u1[3]);
        const uint32_t b00 = pack_bf16(s0[0], s0[1]), b01 = pack_bf16(s1[0], s1[1]), b10 = pack_bf16(s0[2], s0[3]), b11 = pack_bf16(s1[2], s1[3]);
#pragma unroll
        for (int e = 0; e < NE; e++)
            if (J + E0 + e < 8) { mma16(acc[J + E0 + e][0], ta[e], b00, b01); mma16(acc[J + E0 + e][1], ta[e], b10, b11); }
    }
}
template <int D0, int D1>
__device__ __forceinline__ void s4_dense(float (&acc)[8][2][4], uint32_t ua, const uint32_t (&b0)[4], const uint32_t (&b1)[4]) {
#pragma unroll
    for (int J = 0; J < 8 - D0; J++) {
        uint32_t a[4];
        ldsm4(a, ua + J * 256);
        mma16(acc[J + D0][0], a, b0[0], b0[1]); mma16(acc[J + D0][1], a, b0[2], b0[3]);
        if (J + D1 < 8) { mma16(acc[J + D1][0], a, b1[0], b1[1]); mma16(acc[J + D1][1], a, b1[2], b1[3]); }
    }
}
__device__ __forceinline__ void s4_words(uint32_t (&b)[4], uint32_t wd) {
    asm volatile("ld.shared.u32 %0, [%4]; ld.shared.u32 %1, [%4+-32]; ld.shared.u32 %2, [%4+32]; ld.volatile.shared.u32 %3, [%4];"
        : "=r"(b[0]), "=r"(b[1]), "=r"(b[2]), "=r"(b[3]) : "r"(wd) : "memory");
}

__device__ __forceinline__ void s4_item(uint32_t sb, int cw, int lane, int item, const bf16* __restrict__ dsk, uint32_t empty, const CUtensorMap* my, uint32_t stgpar,
                                        bf16* __restrict__ out, uint32_t nbar, uint32_t npar, uint32_t nslot) {
    const int gt = (lane >> 2) - 2 * (lane & 3);
    const uint32_t ch = sb + S4_CH + cw * S4_STRIDE, kd = sb + S4_KD + cw * 1536;
    const __nv_bfloat162 dk = __bfloat162bfloat162(dsk[item * 8 + cw]);
    ST(item, cw, 0);
    asm volatile("st.shared.v4.u32 [%0], {%1,%1,%1,%1};" ::"r"(ch + (lane >> 4) * S4_HALF + (lane & 15) * 16), "r"(0) : "memory");
    const uint32_t tch = sb + S4_CH + (lane & 7) * S4_STRIDE + ((lane >> 3) & 1) * S4_HALF + (16 + 16 * cw + (lane >> 4)) * 16;
#pragma unroll
    for (int i = 0; i < 8; i++) {
        uint32_t x[4];
        ldsm4t(x, sb + cw * 4096 + i * 512 + lane * 16);
        stsm4(tch + i * 32, x[0], x[1], x[2], x[3]);
    }
    const uint32_t k1024 = lds16(kd + 1024);
    {
        auto st4 = [](uint32_t a, uint32_t x, uint32_t y, uint32_t u, uint32_t v) {
            asm volatile("st.shared.v4.u32 [%0], {%1,%2,%3,%4};" ::"r"(a), "r"(x), "r"(y), "r"(u), "r"(v) : "memory");
        };
        const float4 p = lds128(kd + lane * 16);
        const uint32_t p0 = __float_as_uint(p.x), p1 = __float_as_uint(p.y), p2 = __float_as_uint(p.z), p3 = __float_as_uint(p.w);
        const uint32_t pm = lane ? ldsu(kd + lane * 16 - 4) : 0;
        const uint32_t wa = ch + S4_WD + 64 + lane * 32;
        st4(wa, __byte_perm(p0, pm, 0x7610), __byte_perm(p0, 0, 0x1032), __byte_perm(p1, p0, 0x7610), __byte_perm(p1, 0, 0x1032));
        st4(wa + 16, __byte_perm(p2, p1, 0x7610), __byte_perm(p2, 0, 0x1032), __byte_perm(p3, p2, 0x7610), __byte_perm(p3, 0, 0x1032));
        const float2 q = lds64(kd + 512 + lane * 8);
        const uint32_t q0 = __float_as_uint(q.x), q1 = __float_as_uint(q.y), q2 = ldsu(kd + 520 + lane * 8), k255 = ldsu(kd + 508);
        st4(wa + 1024, lane ? __byte_perm(q0, 0, 0x1010) : __byte_perm(q0, k255, 0x7610), __byte_perm(q0, 0, 0x1010), __byte_perm(q0, 0, 0x1032), __byte_perm(q1, q0, 0x7610));
        st4(wa + 1040, __byte_perm(q1, 0, 0x1010), __byte_perm(q1, 0, 0x1010), __byte_perm(q1, 0, 0x1032), __byte_perm(q2, q1, 0x7610));
        const uint32_t k512 = lane == 4 ? lds16(kd + 768) : 0;
        if (lane < 16) st4(ch + S4_WD + (lane < 4 ? 0 : 2048) + lane * 16, k512 * 0x10001u, k512 * 0x10001u, k512 * 0x10001u, k512 << 16);
        const float2 c = lds64(kd + 768 + lane * 8), d = lds64(kd + 760 + lane * 8);
        const uint32_t c0 = __float_as_uint(c.x), c1 = __float_as_uint(c.y), c2 = ldsu(kd + 776 + lane * 8);
        const uint32_t d0 = lane ? __float_as_uint(d.x) : 0, d1 = lane ? __float_as_uint(d.y) : 0, d2 = lane ? c0 : 0;
        st4(ch + S4_T2 + 256 + lane * 16, __byte_perm(c0, d0, 0x7632), __byte_perm(c1, d1, 0x5410), __byte_perm(c1, d1, 0x7632), __byte_perm(c2, d2, 0x5410));
        const uint32_t m = lane == 31 ? 0xFFFF0000u : 0;
        st4(ch + S4_T2 + (lane < 16 ? lane : lane == 31 ? 48 : lane + 33) * 16, c0 & m, (c1 << 16) & m, c1 & m, (c2 << 16) & m);
        const float2 e = lds64(kd + 1024 + lane * 8);
        const uint32_t e0 = __float_as_uint(e.x), e1 = __float_as_uint(e.y), e2 = ldsu(kd + 1032 + lane * 8), em = ldsu(kd + 1020 + lane * 8);
        st4(ch + S4_T3 + 128 + lane * 16, __byte_perm(e0, lane ? em : 0, 0x7632), __byte_perm(e1, lane ? e0 : 0, 0x5410), __byte_perm(e1, e0, 0x7632), __byte_perm(e2, e1, 0x5410));
        if (lane < 8) st4(ch + S4_T3 + lane * 16, 0, 0, 0, 0);
    }
    bar_sync(2, 256);
    ST(item, cw, 1);
    const uint32_t z = ldsu(ch);
    float acc[8][2][4];
#pragma unroll
    for (int j = 0; j < 16; j++) acc[j >> 1][j & 1][0] = acc[j >> 1][j & 1][1] = acc[j >> 1][j & 1][2] = acc[j >> 1][j & 1][3] = 0.f;
#pragma unroll 1
    for (int r = 1; r <= 4; r++) s4_windows<2, 3, 16>(acc, ch, ch + S4_T2 + (gt - 16) * 16 + 4 * r - 4, 4 * r, 2 - (r & 1), lane, z);
    ST(item, cw, 2);
#pragma unroll 1
    for (int r = 1; r <= 2; r++) s4_windows<4, 4, 8>(acc, ch, ch + S4_T3 + (gt - 48) * 8 + 4 * r - 4, 8 * r, 2 + r, lane, z);
    ST(item, cw, 3);
    const uint32_t ua = ch + (lane >> 4) * S4_HALF + (16 + (lane & 15)) * 16, wd = ch + S4_WD + 64 + gt * 4;
#pragma unroll 1
    for (int q = 0; q < 2; q++) {
        uint32_t b0[4], b1[4];
        s4_words(b0, wd + (q + 32) * 64);
#pragma unroll
        for (int j = 0; j < 4; j++) {
            const int x = 16 * q + gt + (j == 1 ? -8 : j == 2 ? 8 : 0) - 3;
            b1[j] = addz(((unsigned)x < 2u ? k1024 : 0u) | ((unsigned)(x - 1) < 2u ? k1024 << 16 : 0u), z);
        }
        s4_dense<2, 4>(acc, ua - q * 16, b0, b1);
    }
    {
        uint32_t b0[4], b1[4], c0[4], c1[4];
        s4_words(b0, wd); s4_words(b1, wd + 1024);
#pragma unroll 1
        for (int q = 0; q < 16; q += 2) {
            s4_words(c0, wd + q * 64 + 64); s4_words(c1, wd + q * 64 + 64 + 1024);
            s4_dense<0, 1>(acc, ua - q * 16, b0, b1);
            s4_words(b0, wd + q * 64 + 128); s4_words(b1, wd + q * 64 + 128 + 1024);
            s4_dense<0, 1>(acc, ua - q * 16 - 16, c0, c1);
            if (q == S4REL && lane == 0) { mbar_arrive(empty); mbar_arrive(empty + 8); }
        }
    }
    ST(item, cw, 4);
    mbar_wait(empty + 72, stgpar);
    if (elect()) asm volatile("cp.async.bulk.wait_group.read 0;" ::: "memory");
    __syncwarp();
#pragma unroll
    for (int I = 0; I < 8; I++) {
        uint32_t u[4];
        ldsm4(u, ua + I * 256);
#pragma unroll
        for (int j = 0; j < 4; j++) {
            const uint32_t y = pack_bf16(acc[I][j >> 1][2 * (j & 1)], acc[I][j >> 1][2 * (j & 1) + 1]);
            const __nv_bfloat162 r = __hadd2_rn(*(const __nv_bfloat162*)&y, __hmul2_rn(*(const __nv_bfloat162*)&u[j], dk));
            u[j] = *(const uint32_t*)&r;
        }
        stsm4(ua + I * 256, u[0], u[1], u[2], u[3]);
    }
    bar_sync(2, 256);
    uint32_t y[8][4];
#pragma unroll
    for (int i = 0; i < 8; i++) ldsm4t(y[i], tch + i * 32);
    if (cw < S4DIR && mbar_test(nbar, npar) && ldsu(nslot) == (IT_END << 16)) {
        uint32_t* const dst = (uint32_t*)(out + (size_t)(cw * 256 + (lane >> 2)) * (2 * DM) + DM + item * 8) + (lane & 3);
#pragma unroll
        for (int i = 0; i < 32; i++) dst[i * 8 * DM] = y[i >> 2][i & 3];
        return;
    }
#pragma unroll
    for (int i = 0; i < 8; i++) stsm4(sb + G_STG + cw * 4096 + i * 512 + lane * 16, y[i][0], y[i][1], y[i][2], y[i][3]);
    asm volatile("fence.proxy.async.shared::cta;" ::: "memory");
    __syncwarp();
    if (elect()) {
        mbar_arrive(empty + 16); mbar_arrive(empty + 24);
        tma2d_store(my, sb + G_STG + cw * 4096, DM + item * 8, cw * 256);
        asm volatile("cp.async.bulk.commit_group;" ::: "memory");
    }
    ST(item, cw, 5);
}

struct Maps { CUtensorMap m[13]; };
__global__ void __launch_bounds__(384, 1)
worker_kernel(const __grid_constant__ Maps M, const bf16* __restrict__ dsk, bf16* __restrict__ out) {
    const CUtensorMap &mx = M.m[0], &mq = M.m[1], &mo = M.m[4], &mout = M.m[5], &mu = M.m[6], &my = M.m[7];
    extern __shared__ unsigned char smem_raw[];
    const uint32_t sb = (smem_u32(smem_raw) + 1023) & ~1023u;
    const uint32_t full = sb + G_BAR, empty = full + 32, ifull = full + 64, iempty = full + 80, islot = full + 96, stgbar = full + 104, sigbar = full + 112, sigslot = full + 120;
    const int tid = threadIdx.x, wg = tid >> 7, lane = tid & 31;
    int q0 = blockIdx.x;
    const int nfirst = min(32, (int)gridDim.x - 96), wide0 = q0 - ((int)gridDim.x - N_LATE);
    if (tid == 0 && q0 >= nfirst && wide0 < 0) q0 = nfirst + atomicAdd(g_ctr + C_NEXT, 1);
    if ((tid >> 5) == 1 && elect()) {
#pragma unroll
        for (int i = 0; i < 6; i++) { mbar_init(full + n6_bar(i), 1); mbar_init(empty + n6_bar(i), 8); }
#pragma unroll
        for (int i = 0; i < 2; i++) { mbar_init(ifull + 8 * i, 1); mbar_init(iempty + 8 * i, 8); }
        mbar_init(sigbar, 8); mbar_init(stgbar, 1);
        asm volatile("fence.mbarrier_init.release.cluster;" ::: "memory");
    }
    if ((tid >> 5) == 2 && elect()) {
#pragma unroll
        for (int i = 0; i < 13; i++) asm volatile("prefetch.tensormap [%0];" ::"l"(&M.m[i]) : "memory");
    }
    __syncthreads();
    if (wg == 0) {
        reg_dec<40>();
        if (tid >= 32 && tid < 64) {
            for (int n = 0;; n++) {
                mbar_wait_long(sigbar, n & 1);
                int item; asm volatile("ld.shared.u32 %0, [%1];" : "=r"(item) : "r"(sigslot + 4 * (n & 1)) : "memory");
                const int type = item >> 16, b = (item >> 8) & 255, i = item & 255;
                if (type == IT_END) break;
                if (type == IT_QA) {
                    if (elect()) {
#pragma unroll
                        for (int j = 0; j < 8; j++) {
                            const uint32_t src = sb + (j >= 4 ? G_STG + (j & 1) * 16384 : 3 * G_STAGE + (j & 1) * 20480) + ((j >> 1) & 1) * 8192;
                            asm volatile("cp.async.bulk.global.shared::cta.bulk_group [%0], [%1], 8192;"
                                ::"l"(g_ox + (size_t)(b * 64 + i * 4 + ((j >> 1) ^ 2)) * 8192 + (j & 1) * 4096), "r"(src) : "memory");
                            if ((j & 3) == 3) asm volatile("cp.async.bulk.commit_group;" ::: "memory");
                        }
                        asm volatile("cp.async.bulk.wait_group.read 1;" ::: "memory");
                        asm volatile("mbarrier.arrive.shared.b64 _, [%0], 8;" ::"r"(empty + 24) : "memory");
                        asm volatile("cp.async.bulk.wait_group 0;" ::: "memory");
                        mbar_arrive(stgbar);
                        asm volatile("fence.proxy.async.global;" ::: "memory");
                    }
                    __syncwarp();
                }
                if (type == IT_KV) { if (lane < 6) red_release(g_kvf + ((i & 15) * 6 + lane) * 16 + b, 1); }
                else if (lane == 0) red_release(g_ctr + C_QA_DONE + b, 1 << i);
            }
        } else if (tid < 32) {
            int it = 0;
            bool tables = false;
            if (!KVN) asm volatile("griddepcontrol.wait;" ::: "memory");
            for (int n = 0;; n++) {
                int item = 0;
                if (lane == 0) {
                    if (n) q0 = nfirst + atomicAdd(g_ctr + C_NEXT, 1);
                    item = n == 0 && wide0 >= 0 ? late_item(wide0) : queue_item(q0);
                }
                item = __shfl_sync(0xffffffffu, item, 0);
                mbar_wait(iempty + 8 * (n & 1), ((n >> 1) & 1) ^ 1);
                if (lane == 0) {
                    asm volatile("st.shared.u32 [%0], %1;" ::"r"(islot + 4 * (n & 1)), "r"(item) : "memory");
                    mbar_arrive(ifull + 8 * (n & 1));
                }
                const int type = item >> 16, b = (item >> 8) & 255, i = item & 255;
                bool ready = false;
                if (type == IT_QA || type == IT_KV) {
                    const CUtensorMap* mw = &mq + (type == IT_QA ? 0 : 1 + (i >> 4));
#pragma unroll 1
                    for (int kb = 0; kb < 16; kb++, it++) {
                        const int st = it & 3;
                        mbar_wait(empty + 8 * st, ((it >> 2) & 1) ^ 1);
                        if (elect()) {
                            mbar_expect(full + 8 * st, G_STAGE);
                            tma2d(sb + st * G_STAGE, &mx, kb * 64, b * 128, full + 8 * st);
                            tma3d(sb + st * G_STAGE + 16384, mw, 0, kb * 64, (i & 15) * 4, full + 8 * st);
                        }
                        if (type == IT_QA && kb == 3) ready = __all_sync(0xffffffffu, ld_acq(g_ctr + C_CHAIN + b) >= 96);
                        if (ready && kb < 11 && elect()) {
                            const size_t sh = (b * 4 + ((kb - 3) & 3)) * NH + i * 2;
                            asm volatile("cp.async.bulk.prefetch.L2.global [%0], 16384;" ::"l"((kb >= 7 ? g_vx : g_kx) + sh * 4096) : "memory");
                            asm volatile("cp.async.bulk.prefetch.L2.global [%0], 4096;" ::"l"((kb >= 7 ? g_vm : g_km) + sh * 1024) : "memory");
                        }
                    }
                }
                if (type == IT_QA) {
                    if (b == 15) asm volatile("griddepcontrol.wait;" ::: "memory");
                    else if (!ready) wait_ctr(g_ctr + C_CHAIN + b, 96);
                    tables = true;
                    asm volatile("fence.proxy.async.global;" ::: "memory");
#pragma unroll 1
                    for (int st = 0; st < 4; st++, it++) {
                        mbar_wait(empty + 8 * st, ((it >> 2) & 1) ^ 1);
                        if (elect()) {
                            mbar_expect(full + 8 * st, 4 * 10240);
#pragma unroll
                            for (int j = 0; j < 4; j++)
                                tma3d(sb + st * G_STAGE + (j >> 1) * 20480 + (j & 1) * 16384, &M.m[8 + (st >> 1) + (j & 1) * 2], 0, b * 4 + (j & 2),
                                      (i * 2 + (st & 1)) * 16, full + 8 * st);
                        }
                    }
                } else if (type == IT_O) {
                    const bool wide = b < O_WIDE;
                    const CUtensorMap* mw = wide ? &mo : &M.m[12];
                    int done = 0;
                    const int ns = wide ? 4 : 6;
#pragma unroll 1
                    for (int kb = 0, st = 0, r = 0; kb < 64; kb++) {
                        const uint32_t bo = n6_bar(st);
                        mbar_wait(empty + bo, (((st < 4 ? it >> 2 : 0) + r) & 1) ^ 1);
                        if (elect()) {
                            mbar_expect(full + bo, wide ? G_STAGE : 32768);
                            tma3d(sb + n6_b(st), mw, 0, kb * 64, wide ? i * 4 : i * 2, full + bo);
                        }
                        if (!(done >> (kb >> 2) & 1)) {
#pragma unroll 1
                            for (int sp = 0; sp < (1 << 20) && !((done = __shfl_sync(0xffffffffu, ld_acq(g_ctr + C_QA_DONE + b), 0)) >> (kb >> 2) & 1); sp++)
                                __nanosleep(64);
                            asm volatile("fence.proxy.async.global;" ::: "memory");
                        }
                        if (elect()) bulk_load(sb + n6_a(st), g_ox + (size_t)(b * 64 + kb) * 8192, 16384, full + bo);
                        if (++st == ns) { st = 0; r++; }
                    }
                    it += wide ? 64 : 44;
                } else if (type == IT_S4) {
                    mbar_wait(empty, ((it >> 2) & 1) ^ 1);
                    if (elect()) {
                        mbar_expect(full, 32768 + 12288);
#pragma unroll
                        for (int j = 0; j < 8; j++) tma2d(sb + j * 4096, &mu, i * 8, j * 256, full);
                    }
                    if (!tables) { wait_ctr(g_ctr + C_CHAIN, 96); asm volatile("fence.proxy.async.global;" ::: "memory"); }
                    tables = true;
                    if (elect()) bulk_load(sb + S4_KD, g_kd + i * 8 * 768, 12288, full);
#pragma unroll 1
                    for (int st = 1; st < 4; st++) { mbar_wait(empty + 8 * st, ((it >> 2) & 1) ^ 1); if (lane == 0) mbar_arrive(full + 8 * st); }
                    it += 4;
                    mbar_wait_long(empty, ((it >> 2) & 1) ^ 1);
                }
                if (item >> 16 == IT_END) break;
            }
            asm volatile("griddepcontrol.wait;" ::: "memory");
        }
    } else {
        reg_inc<232>();
        const int wu = __shfl_sync(0xffffffffu, tid >> 5, 0);
        const int wgi = (wu >> 2) - 1, wi = wu & 3;
        int it = 0, nqa = 0, nsig = 0, n = 0, item;
        auto next_item = [&]() {
            mbar_wait_long(ifull + 8 * (n & 1), (n >> 1) & 1);
            asm volatile("ld.shared.u32 %0, [%1];" : "=r"(item) : "r"(islot + 4 * (n & 1)) : "memory");
            __syncwarp();
            if (lane == 0) mbar_arrive(iempty + 8 * (n & 1));
        };
        auto signal = [&](int what) {
            if (tid == 128) asm volatile("st.shared.u32 [%0], %1;" ::"r"(sigslot + 4 * (nsig & 1)), "r"(what) : "memory");
            __syncwarp();
            if (lane == 0) mbar_arrive(sigbar);
            nsig++;
        };
        next_item();
        if (item >> 16 == IT_KV) {
            float acc[128];
            uint32_t pk[64];
            uint32_t* dst = nullptr;
            int prev = 0;
            do {
                WLOG(0);
#pragma unroll
                for (int kb = 0; kb < 16; kb++, it++) {
                    const int st = kb & 3;
                    mbar_wait(full + 8 * st, (it >> 2) & 1);
                    const uint64_t da = mkdesc(sb + st * G_STAGE + wgi * 8192, 16, 1024, 1);
                    const uint64_t db = mkdesc(sb + st * G_STAGE + 16384, 8192, 1024, 1);
                    wg_fence();
#pragma unroll
                    for (int k = 0; k < 4; k++) wgmma256(acc, da + k * 2, db + k * 128, kb | k);
                    wg_commit();
                    if (n <= KVI) {
                        if (kb < KVF && dst) {
#pragma unroll
                            for (int j = kb * (64 / KVF); j < (kb + 1) * (64 / KVF); j++) st_out(dst + (j >> 1) * 128 + (j & 1) * 32, pk[j]);
                            if (kb == KVF - 1) signal(prev);
                        }
                    } else if (kb < KVS) {
#pragma unroll
                        for (int j = kb * (64 / KVS); j < (kb + 1) * (64 / KVS); j++) st_out(dst + (j >> 1) * 128 + (j & 1) * 32, pk[j]);
                        if (kb == KVS - 1) signal(prev);
                    }
                    if (kb > 0) {
                        wg_wait<1>();
                        if (lane == 0) mbar_arrive(empty + 8 * ((kb - 1) & 3));
                    }
                }
                wg_wait<0>();
                if (lane == 0) mbar_arrive(empty + 8 * 3);
#pragma unroll
                for (int j = 0; j < 64; j++) pk[j] = pack_bf16(acc[2 * j], acc[2 * j + 1]);
                const int row = ((item >> 8) & 255) * 128 + wgi * 64 + wi * 16, nt = item & 255;
                dst = (uint32_t*)(nt < 16 ? g_kx : g_vx) + (size_t)((row >> 5) * 512 + (nt & 15) * 32) * 128 + (row & 31) * 4 + lane;
                prev = item;
                WLOG(1);
                n++;
                next_item();
            } while (item >> 16 == IT_KV);
            if (dst) {
#pragma unroll
                for (int j = 0; j < 64; j++) dst[(j >> 1) * 128 + (j & 1) * 32] = pk[j];
                signal(prev);
            }
        }
        for (;; n++, next_item()) {
            const int type = item >> 16, b = (item >> 8) & 255, i = item & 255;
            const int lane = (tid & 31) + (item >> 24), wgi = (wu >> 2) - 1 + __shfl_sync(0xffffffffu, item >> 24, 0), wi = wu & 3;
            WLOG(0);
            if (type == IT_QA) {
                float acc[128];
                ST(sid, cw, 0);
                ST(sid, cw, 1);
                mainloop<256, 16, false>(acc, sb, wgi, full, empty, it, lane == 0);
                ST(sid, cw, 2);
                uint32_t q0[32], q1[32];
#pragma unroll
                for (int j = 0; j < 32; j++) q0[j] = pack_bf16(acc[2 * j], acc[2 * j + 1]);
                const uint32_t par = (it >> 2) & 1, so = sb + wgi * 20480;
                float sx[2][32] = {}, sm[2][8] = {};
                uint32_t p[2][20];
                mbar_wait_long(full, par);
                ST(sid, cw, 3);
                if (PING && wgi == 0) bar_sync(5, 256);
                attn_scores(sx[0], sm[0], q0, so);
                ST(sid, cw, 7);
#pragma unroll
                for (int j = 0; j < 32; j++) asm volatile("cvt.rn.bf16x2.f32 %0, %1, %2;" : "=r"(q1[j]) : "f"(acc[65 + 2 * j]), "f"(acc[64 + 2 * j]));
                mbar_wait(full + 8, par);
                attn_scores(sx[1], sm[1], q1, so + G_STAGE);
                if (PING && wgi == 1) bar_arrive(5, 256);
                if (elect()) asm volatile("cp.async.bulk.wait_group.read 0;" ::: "memory");
                mbar_wait(stgbar, (nqa++ & 1) ^ 1);
                bar_sync(3 + wgi, 128);
                float o0[64] = {}, o1[64] = {};
                wg_wait<0>();
                ST(sid, cw, 9);
                if (lane == 0) { mbar_arrive(empty); mbar_arrive(empty + 8); }
                if (wi & 1) attn_softmax<true>(p, sx, sm, wi >= 2, lane);
                else attn_softmax<false>(p, sx, sm, wi >= 2, lane);
                ST(sid, cw, 10);
                mbar_wait(full + 16, par);
                attn_pv(o0, p[0], so + 2 * G_STAGE);
                mbar_wait(full + 24, par);
                attn_pv(o1, p[1], so + 3 * G_STAGE);
                wg_wait<1>();
                if (lane == 0) mbar_arrive(empty + 16);
                ST(sid, cw, 5);
                const uint32_t da = (wi * 2 + ((lane >> 3) & 1)) * 1024 + (lane >> 4) * 128 + (lane & 7) * 16;
                attn_stage(o0, sb + G_STG + wgi * 16384 + da);
                wg_wait<0>();
                bar_sync(3 + wgi, 128);
                attn_stage(o1, so + 3 * G_STAGE + da);
                asm volatile("fence.proxy.async.shared::cta;" ::: "memory");
                ST(sid, cw, 6);
                signal(item);
                it += 4;
            } else if (type == IT_O) {
                ST(b * 8 + i, wgi * 4 + wi, 8);
                mbar_wait_long(full, (it >> 2) & 1);
                ST(b * 8 + i, wgi * 4 + wi, 9);
                if (b < O_WIDE) o_item<256>(sb, wgi, wi, lane, full, empty, it, &mout, b * 128, i * 256, (nqa & 1) ^ 1);
                else o_item<128>(sb, wgi, wi, lane, full, empty, it, &mout, b * 128, i * 128, (nqa & 1) ^ 1);
            } else if (type == IT_S4) {
                mbar_wait_long(full, (it >> 2) & 1);
                mbar_wait(full + 24, (it >> 2) & 1);
                s4_item(sb, wgi * 4 + wi, lane, i, dsk, empty, &my, (nqa & 1) ^ 1, out, ifull + 8 * ((n + 1) & 1), ((n + 1) >> 1) & 1, islot + 4 * ((n + 1) & 1));
                it += 4;
            } else break;
            WLOG(1);
        }
        bar_sync(2, 256);
        signal(item);
        if (elect()) asm volatile("cp.async.bulk.wait_group 0;" ::: "memory");
    }
}

typedef CUresult (*EncodeFn)(CUtensorMap*, CUtensorMapDataType, cuuint32_t, void*, const cuuint64_t*, const cuuint64_t*, const cuuint32_t*,
                             const cuuint32_t*, CUtensorMapInterleave, CUtensorMapSwizzle, CUtensorMapL2promotion, CUtensorMapFloatOOBfill);
static EncodeFn get_encode() {
    void* fn = nullptr; cudaDriverEntryPointQueryResult st;
    cudaGetDriverEntryPoint("cuTensorMapEncodeTiled", &fn, cudaEnableDefault, &st);
    return (EncodeFn)fn;
}
static void map_act(EncodeFn enc, CUtensorMap* m, const void* p, int rows, int cols, int boxr) {
    cuuint64_t dim[2] = {(cuuint64_t)cols, (cuuint64_t)rows}, str[1] = {(cuuint64_t)cols * 2};
    cuuint32_t box[2] = {64, (cuuint32_t)boxr}, es[2] = {1, 1};
    enc(m, CU_TENSOR_MAP_DATA_TYPE_BFLOAT16, 2, (void*)p, dim, str, box, es, CU_TENSOR_MAP_INTERLEAVE_NONE, CU_TENSOR_MAP_SWIZZLE_128B,
        CU_TENSOR_MAP_L2_PROMOTION_L2_128B, CU_TENSOR_MAP_FLOAT_OOB_FILL_NONE);
}
static void map_w(EncodeFn enc, CUtensorMap* m, const void* p, int k, int n, int groups = 4) {
    cuuint64_t dim[3] = {64, (cuuint64_t)k, (cuuint64_t)n / 64}, str[2] = {(cuuint64_t)n * 2, 128};
    cuuint32_t box[3] = {64, 64, (cuuint32_t)groups}, es[3] = {1, 1, 1};
    enc(m, CU_TENSOR_MAP_DATA_TYPE_BFLOAT16, 3, (void*)p, dim, str, box, es, CU_TENSOR_MAP_INTERLEAVE_NONE, CU_TENSOR_MAP_SWIZZLE_128B,
        CU_TENSOR_MAP_L2_PROMOTION_L2_256B, CU_TENSOR_MAP_FLOAT_OOB_FILL_NONE);
}

static void map_kv(EncodeFn enc, CUtensorMap* m, void* p, int n) {
    cuuint64_t dim[3] = {(cuuint64_t)n, NSEG, 512}, str[2] = {(cuuint64_t)n * 1024, (cuuint64_t)n * 2};
    cuuint32_t box[3] = {(cuuint32_t)n, 2, 16}, es[3] = {1, 1, 1};
    enc(m, CU_TENSOR_MAP_DATA_TYPE_BFLOAT16, 3, p, dim, str, box, es, CU_TENSOR_MAP_INTERLEAVE_NONE, CU_TENSOR_MAP_SWIZZLE_NONE,
        CU_TENSOR_MAP_L2_PROMOTION_NONE, CU_TENSOR_MAP_FLOAT_OOB_FILL_NONE);
}
static void map_box(EncodeFn enc, CUtensorMap* m, const void* p, int rows, int ld, int boxc, int boxr, CUtensorMapSwizzle sw,
                    CUtensorMapL2promotion promo = CU_TENSOR_MAP_L2_PROMOTION_NONE) {
    cuuint64_t dim[2] = {(cuuint64_t)ld, (cuuint64_t)rows}, str[1] = {(cuuint64_t)ld * 2};
    cuuint32_t box[2] = {(cuuint32_t)boxc, (cuuint32_t)boxr}, es[2] = {1, 1};
    enc(m, CU_TENSOR_MAP_DATA_TYPE_BFLOAT16, 2, (void*)p, dim, str, box, es, CU_TENSOR_MAP_INTERLEAVE_NONE, sw,
        promo, CU_TENSOR_MAP_FLOAT_OOB_FILL_NONE);
}

extern "C" void kernel_launch(void* const* d_in, const int* in_sizes, int n_in, void* d_out, int out_size) {
    const bf16* x = (const bf16*)d_in[0];
    const bf16* mem0 = (const bf16*)d_in[1];
    const bf16 *Wq = (const bf16*)d_in[2], *Wk = (const bf16*)d_in[3], *Wv = (const bf16*)d_in[4], *Wo = (const bf16*)d_in[5];
    static EncodeFn enc = nullptr;
    static int nsm = 0;
    static void* kv[4];
    if (!enc) {
        enc = get_encode();
        cudaGetSymbolAddress(&kv[0], g_kx); cudaGetSymbolAddress(&kv[1], g_vx); cudaGetSymbolAddress(&kv[2], g_km); cudaGetSymbolAddress(&kv[3], g_vm);
        cudaDeviceGetAttribute(&nsm, cudaDevAttrMultiProcessorCount, 0);
        cudaFuncSetAttribute(chain_kernel, cudaFuncAttributeMaxDynamicSharedMemorySize, CH_SMEM);
        cudaFuncSetAttribute(worker_kernel, cudaFuncAttributeMaxDynamicSharedMemorySize, G_SMEM);
    }
    Maps M;
    CUtensorMap &mx = M.m[0], &mq = M.m[1], &mk = M.m[2], &mv = M.m[3], &mo = M.m[4], &mout = M.m[5], &mu = M.m[6], &my = M.m[7];
    map_act(enc, &mx, x, S_LEN, DM, 128);
    map_w(enc, &mq, Wq, DM, HD); map_w(enc, &mk, Wk, DM, HD); map_w(enc, &mv, Wv, DM, HD); map_w(enc, &mo, Wo, HD, DM);
    map_w(enc, &M.m[12], Wo, HD, DM, 2);
    map_box(enc, &mout, d_out, S_LEN, 2 * DM, 64, 16, CU_TENSOR_MAP_SWIZZLE_128B);
    map_box(enc, &mu, d_in[7], S_LEN, DM, 8, 256, CU_TENSOR_MAP_SWIZZLE_NONE, (CUtensorMapL2promotion)PROMU);
    map_box(enc, &my, d_out, S_LEN, 2 * DM, 8, 256, CU_TENSOR_MAP_SWIZZLE_NONE);
    for (int i = 0; i < 4; i++) map_kv(enc, &M.m[8 + i], kv[i], i < 2 ? 256 : 64);
    CUtensorMap cq, ck, cv, co;
    map_box(enc, &cq, Wq, DM, HD, 32, 32, CU_TENSOR_MAP_SWIZZLE_64B, (CUtensorMapL2promotion)PROMO); map_box(enc, &ck, Wk, DM, HD, 32, 32, CU_TENSOR_MAP_SWIZZLE_64B, (CUtensorMapL2promotion)PROMO);
    map_box(enc, &cv, Wv, DM, HD, 32, 32, CU_TENSOR_MAP_SWIZZLE_64B, (CUtensorMapL2promotion)PROMO); map_box(enc, &co, Wo, HD, DM, 32, 16, CU_TENSOR_MAP_SWIZZLE_64B, (CUtensorMapL2promotion)PROMO);
    S4Params P = {(const bf16*)d_in[8], (const bf16*)d_in[9], (const bf16*)d_in[10], (const bf16*)d_in[11],
                  (const bf16*)d_in[12], (const bf16*)d_in[13], (const bf16*)d_in[14], (const bf16*)d_in[15]};
    int aware = 1;
    cudaLaunchAttribute at[1];
    at[0].id = cudaLaunchAttributeProgrammaticStreamSerialization;
    at[0].val.programmaticStreamSerializationAllowed = 1;
    cudaLaunchConfig_t cfg = {};
    cfg.stream = cudaStreamPerThread;
    cfg.gridDim = dim3(96); cfg.blockDim = dim3(CH_THREADS); cfg.dynamicSmemBytes = CH_SMEM;
    cudaLaunchKernelEx(&cfg, chain_kernel, cq, ck, cv, co, Wq, Wk, Wv, mem0, P, aware);
    cfg.attrs = at; cfg.numAttrs = 1;
    cfg.gridDim = dim3(nsm); cfg.blockDim = dim3(384); cfg.dynamicSmemBytes = G_SMEM;
    cudaLaunchKernelEx(&cfg, worker_kernel, M, P.dsk, (bf16*)d_out);
}
```

```cpp
#include <cuda.h>
#include <cuda_runtime.h>
#include <cuda_bf16.h>
#include <stdint.h>
#include <stdio.h>
#include <string.h>

typedef __nv_bfloat16 bf16;

constexpr int S_LEN = 2048, DM = 1024, NH = 32, DH = 128, HD = 4096, NSEG = 64;
constexpr uint32_t SENT = 0xFFFFFFFFu;
constexpr int SPIN_LIMIT = 1 << 18;
#define REALL 0

__device__ __align__(1024) bf16 g_kx[S_LEN * HD];
__device__ __align__(1024) bf16 g_vx[S_LEN * HD];
__device__ __align__(1024) bf16 g_ox[S_LEN * HD];
__device__ __align__(1024) bf16 g_km[NSEG * NH * 8 * DH];
__device__ __align__(1024) bf16 g_vm[NSEG * NH * 8 * DH];
__device__ __align__(1024) bf16 g_kd[DM * 768 + 8192];
__device__ __align__(1024) char g_ring[2 << 20];
__device__ int g_kvf[96 * 16];
constexpr int C_NEXT = 0, C_CHAIN = 32, C_QA_DONE = 64, N_CTR = 96;
__device__ int g_ctr[N_CTR];

__device__ __forceinline__ uint32_t smem_u32(const void* p) { return (uint32_t)__cvta_generic_to_shared(p); }
__device__ __forceinline__ uint32_t clk() { uint32_t c; asm volatile("mov.u32 %0, %%clock;" : "=r"(c)::"memory"); return c; }
__device__ __forceinline__ uint32_t pack_bf16(float lo, float hi) {
    uint32_t r; asm("cvt.rn.bf16x2.f32 %0, %1, %2;" : "=r"(r) : "f"(hi), "f"(lo)); return r;
}
__device__ __forceinline__ uint32_t movm(uint32_t a) {
    uint32_t d; asm volatile("movmatrix.sync.aligned.m8n8.trans.b16 %0, %1;" : "=r"(d) : "r"(a)); return d;
}
__device__ __forceinline__ void mma16(float (&d)[4], const uint32_t (&a)[4], uint32_t b0, uint32_t b1) {
    asm volatile("mma.sync.aligned.m16n8k16.row.col.f32.bf16.bf16.f32 {%0,%1,%2,%3}, {%4,%5,%6,%7}, {%8,%9}, {%0,%1,%2,%3};"
        : "+f"(d[0]), "+f"(d[1]), "+f"(d[2]), "+f"(d[3]) : "r"(a[0]), "r"(a[1]), "r"(a[2]), "r"(a[3]), "r"(b0), "r"(b1));
}
__device__ __forceinline__ void mma16z(float (&d)[4], const uint32_t (&a)[4], uint32_t b0, uint32_t b1) {
    asm volatile("mma.sync.aligned.m16n8k16.row.col.f32.bf16.bf16.f32 {%0,%1,%2,%3}, {%4,%5,%6,%7}, {%8,%9}, {%10,%10,%10,%10};"
        : "=f"(d[0]), "=f"(d[1]), "=f"(d[2]), "=f"(d[3]) : "r"(a[0]), "r"(a[1]), "r"(a[2]), "r"(a[3]), "r"(b0), "r"(b1), "f"(0.f));
}
__device__ __forceinline__ void mma8z(float (&d)[4], uint32_t a0, uint32_t a1, uint32_t b0) {
    asm volatile("mma.sync.aligned.m16n8k8.row.col.f32.bf16.bf16.f32 {%0,%1,%2,%3}, {%4,%5}, {%6}, {%7,%7,%7,%7};"
        : "=f"(d[0]), "=f"(d[1]), "=f"(d[2]), "=f"(d[3]) : "r"(a0), "r"(a1), "r"(b0), "f"(0.f));
}
__device__ __forceinline__ void ldsm4t(uint32_t (&r)[4], uint32_t addr) {
    asm volatile("ldmatrix.sync.aligned.m8n8.x4.trans.shared.b16 {%0,%1,%2,%3}, [%4];"
        : "=r"(r[0]), "=r"(r[1]), "=r"(r[2]), "=r"(r[3]) : "r"(addr) : "memory");
}
__device__ __forceinline__ void ldsm4(uint32_t (&r)[4], uint32_t addr) {
    asm volatile("ldmatrix.sync.aligned.m8n8.x4.shared.b16 {%0,%1,%2,%3}, [%4];"
        : "=r"(r[0]), "=r"(r[1]), "=r"(r[2]), "=r"(r[3]) : "r"(addr) : "memory");
}
__device__ __forceinline__ float lds32(uint32_t a) {
    float v; asm volatile("ld.shared.f32 %0, [%1];" : "=f"(v) : "r"(a) : "memory"); return v;
}
__device__ __forceinline__ void st_async1(uint32_t dst, float v, uint32_t bar) {
    asm volatile("st.async.shared::cluster.mbarrier::complete_tx::bytes.f32 [%0], %1, [%2];" ::"r"(dst), "f"(v), "r"(bar) : "memory");
}
__device__ __forceinline__ void st_async2(uint32_t dst, float x, float y, uint32_t bar) {
    asm volatile("st.async.shared::cluster.mbarrier::complete_tx::bytes.v2.f32 [%0], {%1,%2}, [%3];" ::"r"(dst), "f"(x), "f"(y), "r"(bar) : "memory");
}
__device__ __forceinline__ void mma8(float (&d)[4], uint32_t a0, uint32_t a1, uint32_t b0) {
    asm volatile("mma.sync.aligned.m16n8k8.row.col.f32.bf16.bf16.f32 {%0,%1,%2,%3}, {%4,%5}, {%6}, {%0,%1,%2,%3};"
        : "+f"(d[0]), "+f"(d[1]), "+f"(d[2]), "+f"(d[3]) : "r"(a0), "r"(a1), "r"(b0));
}
__device__ __forceinline__ void cp16(uint32_t dst, const void* src) {
    asm volatile("cp.async.cg.shared.global [%0], [%1], 16;" ::"r"(dst), "l"(src) : "memory");
}
__device__ __forceinline__ void sts128(uint32_t a, const float (&v)[4]) {
    asm volatile("st.shared.v4.f32 [%0], {%1,%2,%3,%4};" ::"r"(a), "f"(v[0]), "f"(v[1]), "f"(v[2]), "f"(v[3]) : "memory");
}
__device__ __forceinline__ float4 lds128(uint32_t a) {
    float4 v; asm volatile("ld.shared.v4.f32 {%0,%1,%2,%3}, [%4];" : "=f"(v.x), "=f"(v.y), "=f"(v.z), "=f"(v.w) : "r"(a) : "memory"); return v;
}
__device__ __forceinline__ void sts64(uint32_t a, float x, float y) {
    asm volatile("st.shared.v2.f32 [%0], {%1,%2};" ::"r"(a), "f"(x), "f"(y) : "memory");
}
__device__ __forceinline__ float2 lds64(uint32_t a) {
    float2 v; asm volatile("ld.shared.v2.f32 {%0,%1}, [%2];" : "=f"(v.x), "=f"(v.y) : "r"(a) : "memory"); return v;
}
__device__ __forceinline__ void bar_sync(int id, int n) { asm volatile("bar.sync %0, %1;" ::"r"(id), "r"(n) : "memory"); }
__device__ __forceinline__ void bar_arrive(int id, int n) { asm volatile("bar.arrive %0, %1;" ::"r"(id), "r"(n) : "memory"); }
__device__ __forceinline__ uint32_t mapa(uint32_t a, uint32_t r) {
    uint32_t o; asm("mapa.shared::cluster.u32 %0, %1, %2;" : "=r"(o) : "r"(a), "r"(r)); return o;
}
__device__ __forceinline__ void st_async4(uint32_t dst, float4 v, uint32_t bar) {
    asm volatile("st.async.shared::cluster.mbarrier::complete_tx::bytes.v4.f32 [%0], {%1,%2,%3,%4}, [%5];"
        ::"r"(dst), "f"(v.x), "f"(v.y), "f"(v.z), "f"(v.w), "r"(bar) : "memory");
}
__device__ __forceinline__ void mbar_init(uint32_t bar, int n) { asm volatile("mbarrier.init.shared.b64 [%0], %1;" ::"r"(bar), "r"(n) : "memory"); }
__device__ __forceinline__ void mbar_expect(uint32_t bar, int bytes) {
    asm volatile("mbarrier.arrive.expect_tx.shared.b64 _, [%0], %1;" ::"r"(bar), "r"(bytes) : "memory");
}
__device__ __forceinline__ void bulk_load(uint32_t dst, const void* src, int bytes, uint32_t bar) {
    asm volatile("cp.async.bulk.shared::cluster.global.mbarrier::complete_tx::bytes [%0], [%1], %2, [%3];"
        ::"r"(dst), "l"(src), "r"(bytes), "r"(bar) : "memory");
}
__device__ __forceinline__ bool mbar_try(uint32_t bar, uint32_t par) {
    uint32_t ok;
    asm volatile("{.reg .pred p; mbarrier.try_wait.parity.shared::cta.b64 p, [%1], %2; selp.u32 %0, 1, 0, p;}"
        : "=r"(ok) : "r"(bar), "r"(par) : "memory");
    return ok;
}
__device__ __forceinline__ bool mbar_test(uint32_t bar, uint32_t par) {
    uint32_t ok;
    asm volatile("{.reg .pred p; mbarrier.test_wait.parity.shared::cta.b64 p, [%1], %2; selp.u32 %0, 1, 0, p;}"
        : "=r"(ok) : "r"(bar), "r"(par) : "memory");
    return ok;
}
__device__ __forceinline__ int ld_acq(const int* p) { int v; asm volatile("ld.acquire.gpu.global.s32 %0, [%1];" : "=r"(v) : "l"(p) : "memory"); return v; }
__device__ __forceinline__ void red_release(int* p, int v) { asm volatile("red.release.gpu.global.add.s32 [%0], %1;" ::"l"(p), "r"(v) : "memory"); }
__device__ __forceinline__ void fence_gpu() { asm volatile("fence.acq_rel.gpu;" ::: "memory"); }
__device__ __forceinline__ void wait_ctr(const int* p, int n) {
#pragma unroll 1
    for (int it = 0; it < (1 << 20) && ld_acq(p) < n; it++) __nanosleep(64);
}
__device__ __forceinline__ void mbar_wait(uint32_t bar, uint32_t par) {
    if (!mbar_try(bar, par)) {
#pragma unroll 1
        for (int it = 0; it < SPIN_LIMIT && !mbar_try(bar, par); it++) {}
    }
}
__device__ __forceinline__ void mbar_wait_long(uint32_t bar, uint32_t par) {
    for (int it = 0; it < (1 << 24) && !mbar_try(bar, par); it++) {}
}
__device__ __forceinline__ float4 add4(float4 a, float4 b) { return make_float4(a.x + b.x, a.y + b.y, a.z + b.z, a.w + b.w); }
__device__ __forceinline__ float ex2(float x) { float y; asm("ex2.approx.ftz.f32 %0, %1;" : "=f"(y) : "f"(x)); return y; }

__device__ __forceinline__ void wgmma256(float (&d)[128], uint64_t da, uint64_t db, int acc) {
    asm volatile("{.reg .pred p; setp.ne.b32 p, %130, 0;\n"
        "wgmma.mma_async.sync.aligned.m64n256k16.f32.bf16.bf16 {"
        "%0,%1,%2,%3,%4,%5,%6,%7,%8,%9,%10,%11,%12,%13,%14,%15,"
        "%16,%17,%18,%19,%20,%21,%22,%23,%24,%25,%26,%27,%28,%29,%30,%31,"
        "%32,%33,%34,%35,%36,%37,%38,%39,%40,%41,%42,%43,%44,%45,%46,%47,"
        "%48,%49,%50,%51,%52,%53,%54,%55,%56,%57,%58,%59,%60,%61,%62,%63,"
        "%64,%65,%66,%67,%68,%69,%70,%71,%72,%73,%74,%75,%76,%77,%78,%79,"
        "%80,%81,%82,%83,%84,%85,%86,%87,%88,%89,%90,%91,%92,%93,%94,%95,"
        "%96,%97,%98,%99,%100,%101,%102,%103,%104,%105,%106,%107,%108,%109,%110,%111,"
        "%112,%113,%114,%115,%116,%117,%118,%119,%120,%121,%122,%123,%124,%125,%126,%127"
        "}, %128, %129, p, 1, 1, 0, 1;}"
        : "+f"(d[0]), "+f"(d[1]), "+f"(d[2]), "+f"(d[3]), "+f"(d[4]), "+f"(d[5]), "+f"(d[6]), "+f"(d[7]), "+f"(d[8]), "+f"(d[9]), "+f"(d[10]), "+f"(d[11]), "+f"(d[12]), "+f"(d[13]), "+f"(d[14]), "+f"(d[15]), "+f"(d[16]), "+f"(d[17]), "+f"(d[18]), "+f"(d[19]), "+f"(d[20]), "+f"(d[21]), "+f"(d[22]), "+f"(d[23]), "+f"(d[24]), "+f"(d[25]), "+f"(d[26]), "+f"(d[27]), "+f"(d[28]), "+f"(d[29]), "+f"(d[30]), "+f"(d[31]), "+f"(d[32]), "+f"(d[33]), "+f"(d[34]), "+f"(d[35]), "+f"(d[36]), "+f"(d[37]), "+f"(d[38]), "+f"(d[39]), "+f"(d[40]), "+f"(d[41]), "+f"(d[42]), "+f"(d[43]), "+f"(d[44]), "+f"(d[45]), "+f"(d[46]), "+f"(d[47]), "+f"(d[48]), "+f"(d[49]), "+f"(d[50]), "+f"(d[51]), "+f"(d[52]), "+f"(d[53]), "+f"(d[54]), "+f"(d[55]), "+f"(d[56]), "+f"(d[57]), "+f"(d[58]), "+f"(d[59]), "+f"(d[60]), "+f"(d[61]), "+f"(d[62]), "+f"(d[63]), "+f"(d[64]), "+f"(d[65]), "+f"(d[66]), "+f"(d[67]), "+f"(d[68]), "+f"(d[69]), "+f"(d[70]), "+f"(d[71]), "+f"(d[72]), "+f"(d[73]), "+f"(d[74]), "+f"(d[75]), "+f"(d[76]), "+f"(d[77]), "+f"(d[78]), "+f"(d[79]), "+f"(d[80]), "+f"(d[81]), "+f"(d[82]), "+f"(d[83]), "+f"(d[84]), "+f"(d[85]), "+f"(d[86]), "+f"(d[87]), "+f"(d[88]), "+f"(d[89]), "+f"(d[90]), "+f"(d[91]), "+f"(d[92]), "+f"(d[93]), "+f"(d[94]), "+f"(d[95]), "+f"(d[96]), "+f"(d[97]), "+f"(d[98]), "+f"(d[99]), "+f"(d[100]), "+f"(d[101]), "+f"(d[102]), "+f"(d[103]), "+f"(d[104]), "+f"(d[105]), "+f"(d[106]), "+f"(d[107]), "+f"(d[108]), "+f"(d[109]), "+f"(d[110]), "+f"(d[111]), "+f"(d[112]), "+f"(d[113]), "+f"(d[114]), "+f"(d[115]), "+f"(d[116]), "+f"(d[117]), "+f"(d[118]), "+f"(d[119]), "+f"(d[120]), "+f"(d[121]), "+f"(d[122]), "+f"(d[123]), "+f"(d[124]), "+f"(d[125]), "+f"(d[126]), "+f"(d[127])
        : "l"(da), "l"(db), "r"(acc));
}
__device__ __forceinline__ void wgmma128(float (&d)[64], uint64_t da, uint64_t db, int acc) {
    asm volatile("{.reg .pred p; setp.ne.b32 p, %66, 0;\n"
        "wgmma.mma_async.sync.aligned.m64n128k16.f32.bf16.bf16 {"
        "%0,%1,%2,%3,%4,%5,%6,%7,%8,%9,%10,%11,%12,%13,%14,%15,"
        "%16,%17,%18,%19,%20,%21,%22,%23,%24,%25,%26,%27,%28,%29,%30,%31,"
        "%32,%33,%34,%35,%36,%37,%38,%39,%40,%41,%42,%43,%44,%45,%46,%47,"
        "%48,%49,%50,%51,%52,%53,%54,%55,%56,%57,%58,%59,%60,%61,%62,%63"
        "}, %64, %65, p, 1, 1, 0, 1;}"
        : "+f"(d[0]), "+f"(d[1]), "+f"(d[2]), "+f"(d[3]), "+f"(d[4]), "+f"(d[5]), "+f"(d[6]), "+f"(d[7]), "+f"(d[8]), "+f"(d[9]), "+f"(d[10]), "+f"(d[11]), "+f"(d[12]), "+f"(d[13]), "+f"(d[14]), "+f"(d[15]), "+f"(d[16]), "+f"(d[17]), "+f"(d[18]), "+f"(d[19]), "+f"(d[20]), "+f"(d[21]), "+f"(d[22]), "+f"(d[23]), "+f"(d[24]), "+f"(d[25]), "+f"(d[26]), "+f"(d[27]), "+f"(d[28]), "+f"(d[29]), "+f"(d[30]), "+f"(d[31]), "+f"(d[32]), "+f"(d[33]), "+f"(d[34]), "+f"(d[35]), "+f"(d[36]), "+f"(d[37]), "+f"(d[38]), "+f"(d[39]), "+f"(d[40]), "+f"(d[41]), "+f"(d[42]), "+f"(d[43]), "+f"(d[44]), "+f"(d[45]), "+f"(d[46]), "+f"(d[47]), "+f"(d[48]), "+f"(d[49]), "+f"(d[50]), "+f"(d[51]), "+f"(d[52]), "+f"(d[53]), "+f"(d[54]), "+f"(d[55]), "+f"(d[56]), "+f"(d[57]), "+f"(d[58]), "+f"(d[59]), "+f"(d[60]), "+f"(d[61]), "+f"(d[62]), "+f"(d[63])
        : "l"(da), "l"(db), "r"(acc));
}
__device__ __forceinline__ void wg_fence() { asm volatile("wgmma.fence.sync.aligned;" ::: "memory"); }
__device__ __forceinline__ void wg_commit() { asm volatile("wgmma.commit_group.sync.aligned;" ::: "memory"); }
template <int N> __device__ __forceinline__ void wg_wait() { asm volatile("wgmma.wait_group.sync.aligned %0;" ::"n"(N) : "memory"); }
__device__ __forceinline__ uint64_t mkdesc(uint32_t addr, uint32_t lbo, uint32_t sbo, uint32_t sw) {
    return (uint64_t)((addr & 0x3FFFF) >> 4) | ((uint64_t)(lbo >> 4) << 16) | ((uint64_t)(sbo >> 4) << 32) | ((uint64_t)sw << 62);
}
__device__ __forceinline__ void tma2d(uint32_t dst, const CUtensorMap* m, int c0, int c1, uint32_t bar) {
    asm volatile("cp.async.bulk.tensor.2d.shared::cluster.global.mbarrier::complete_tx::bytes [%0], [%1, {%2, %3}], [%4];"
        ::"r"(dst), "l"(m), "r"(c0), "r"(c1), "r"(bar) : "memory");
}
__device__ __forceinline__ void tma3d(uint32_t dst, const CUtensorMap* m, int c0, int c1, int c2, uint32_t bar) {
    asm volatile("cp.async.bulk.tensor.3d.shared::cluster.global.mbarrier::complete_tx::bytes [%0], [%1, {%2, %3, %4}], [%5];"
        ::"r"(dst), "l"(m), "r"(c0), "r"(c1), "r"(c2), "r"(bar) : "memory");
}
__device__ __forceinline__ void tma3d_mc(uint32_t dst, const CUtensorMap* m, int c0, int c1, int c2, uint32_t bar, uint16_t mask) {
    asm volatile("cp.async.bulk.tensor.3d.shared::cluster.global.mbarrier::complete_tx::bytes.multicast::cluster [%0], [%1, {%2, %3, %4}], [%5], %6;"
        ::"r"(dst), "l"(m), "r"(c0), "r"(c1), "r"(c2), "r"(bar), "h"(mask) : "memory");
}
__device__ __forceinline__ void mbar_arrive(uint32_t bar) { asm volatile("mbarrier.arrive.shared.b64 _, [%0];" ::"r"(bar) : "memory"); }
__device__ __forceinline__ void mbar_arrive_remote(uint32_t bar) {
    asm volatile("mbarrier.arrive.shared::cluster.b64 _, [%0];" ::"r"(bar) : "memory");
}
__device__ __forceinline__ bool elect() {
    uint32_t p;
    asm volatile("{.reg .pred p; elect.sync _|p, 0xffffffff; selp.u32 %0, 1, 0, p;}" : "=r"(p));
    return p;
}
template <int R> __device__ __forceinline__ void reg_inc() { asm volatile("setmaxnreg.inc.sync.aligned.u32 %0;" ::"n"(R)); }
template <int R> __device__ __forceinline__ void reg_dec() { asm volatile("setmaxnreg.dec.sync.aligned.u32 %0;" ::"n"(R)); }

#define ST(id, w, i)
constexpr int CH_NRES = 50;
constexpr int CH_WREG = CH_NRES * 512;
constexpr int CH_PART = 8 * CH_WREG;
constexpr int CH_SX = CH_PART + 16384;
constexpr int CH_MX = CH_SX + 3 * 1280;
constexpr int CH_QK = CH_MX;
constexpr int CH_XS = CH_MX + 3 * 512;
constexpr int CH_BAR = CH_XS + 5632;
constexpr int CH_SMEM = CH_BAR + 192;
constexpr int CH_THREADS = 384;

__device__ __forceinline__ char* ring_base() { return (char*)(((uintptr_t)g_ring + (1 << 20) - 1) & ~(uintptr_t)((1 << 20) - 1)); }
__device__ __forceinline__ uint32_t ring_off(int chunk, int side) {
    uint32_t o = ((chunk & 1) << 13) | ((chunk >> 1) << 16);
    uint32_t par = ((o >> 13) ^ (o >> 16) ^ (o >> 17) ^ (o >> 19) ^ side) & 1;
    return o | (par << 12);
}
__device__ __forceinline__ uint2 ld_poll(const char* p) {
    unsigned long long v; asm volatile("ld.relaxed.gpu.global.b64 %0, [%1];" : "=l"(v) : "l"(p) : "memory");
    return make_uint2((uint32_t)v, (uint32_t)(v >> 32));
}
__device__ __forceinline__ void st_pub(char* p, uint32_t x, uint32_t y) {
    unsigned long long v = ((unsigned long long)y << 32) | x;
    asm volatile("st.relaxed.gpu.global.b64 [%0], %1;" ::"l"(p), "l"(v) : "memory");
}
template <int N>
__device__ __forceinline__ void poll_issue(uint2 (&b)[N], const char* p, bool lastvalid) {
#pragma unroll
    for (int i = 0; i < N; i++) {
        if (i < N - 1 || lastvalid) b[i] = ld_poll(p + i * 256);
        else b[i] = make_uint2(0, 0);
    }
}
template <int N>
__device__ __forceinline__ int poll_check(uint2 (&b)[N], const char* p, uint32_t z) {
    int it = 0;
    uint32_t mx = z;
#pragma unroll
    for (int i = 0; i < N; i++) mx = max(mx, b[i].x);
    if (__any_sync(0xffffffffu, mx == SENT)) {
        do {
#pragma unroll
            for (int i = 0; i < N; i++)
                if ((REALL && i < 10) || b[i].x == SENT) b[i] = ld_poll(p + i * 256);
            mx = b[0].x;
#pragma unroll
            for (int i = 1; i < N; i++) mx = max(mx, b[i].x);
            it++;
        } while (__any_sync(0xffffffffu, mx == SENT && it < SPIN_LIMIT));
    }
    return it;
}
template <int N>
__device__ __forceinline__ uint32_t delay(uint32_t a) {
    uint32_t z = 0;
#pragma unroll
    for (int i = 0; i < N; i++) asm volatile("ld.volatile.shared.u32 %0, [%1];" : "=r"(z) : "r"(a + z) : "memory");
    return z;
}

#define PFKV 0
#define LDW 0
#define GX 2
#define PACE2 18
#define KGS 2
constexpr int KVN = 2;
#define FEN 1
#define XB 4
#define KEEP 0
#define PE 0
#define PROMO 2
#define PROMU 0
#define FNC 1
#define CL 8
#define PL 0
#define ML 6
#define MP 2
#define VCH_P 4
#define VCH_C 2
#define DLM 3
#define DLO 2
constexpr int OB = 0;
template <int PACE, int I0 = 0, int I1 = 12>
__device__ __forceinline__ void preload(uint32_t (&sw)[12][4], uint32_t a, uint32_t zero) {
    uint32_t z = 0;
#pragma unroll
    for (int i = I0; i < I1; i++) {
        if (PACE && i % (PACE ? PACE : 1) == 0) z = delay<1>(zero + z);
        ldsm4t(sw[i], a + z + i * 512);
    }
}
__device__ __forceinline__ void stsm4(uint32_t addr, uint32_t a, uint32_t b, uint32_t c, uint32_t d) {
    asm volatile("stmatrix.sync.aligned.m8n8.x4.shared.b16 [%0], {%1,%2,%3,%4};" ::"r"(addr), "r"(a), "r"(b), "r"(c), "r"(d) : "memory");
}
__device__ __forceinline__ void stsm4t(uint32_t addr, uint32_t a, uint32_t b, uint32_t c, uint32_t d) {
    asm volatile("stmatrix.sync.aligned.m8n8.x4.trans.shared.b16 [%0], {%1,%2,%3,%4};" ::"r"(addr), "r"(a), "r"(b), "r"(c), "r"(d) : "memory");
}
__device__ __forceinline__ void st_part(uint32_t addr, const float (&x)[4], const float (&y)[4]) {
    stsm4(addr, pack_bf16(x[0], x[1]), pack_bf16(x[2], x[3]), pack_bf16(y[0], y[1]), pack_bf16(y[2], y[3]));
}
template <bool TR>
__device__ __forceinline__ void red_part(uint32_t& lo, uint32_t& hi, uint32_t addr, uint32_t eye) {
    uint32_t a[4][4];
#pragma unroll
    for (int j = 0; j < 4; j++) { if (TR) ldsm4t(a[j], addr + j * 1024); else ldsm4(a[j], addr + j * 1024); }
    float r0[4], r1[4], r2[4], r3[4];
    mma16z(r0, a[0], eye, eye); mma16z(r1, a[1], eye, eye); mma16z(r2, a[2], eye, eye); mma16z(r3, a[3], eye, eye);
#pragma unroll
    for (int j = 0; j < 4; j++) r0[j] = ((r0[j] + r1[j]) + r2[j]) + r3[j];
    lo = pack_bf16(r0[0], r0[1]); hi = pack_bf16(r0[2], r0[3]);
}
__device__ __forceinline__ int o_chunk(int ks, int& pos) {
    const int cw = ks < 176 ? ks / 11 : 16 + (ks - 176) / 10;
    pos = ks - (cw < 16 ? 11 * cw : 176 + 10 * (cw - 16));
    return cw;
}

template <bool PV>
__device__ __forceinline__ void chain_loop(const uint32_t (&wa)[36][4], const uint32_t sb, const int w, const int lane0, const int rank,
                                           const int h, const int side) {
    const int rk1 = rank == 2 ? 0 : rank + 1, rk2 = rank == 0 ? 2 : rank - 1;
    const int nq = rank == 0 ? 6 : 5, u0 = rank == 0 ? 0 : 1 + 5 * rank, v0 = rank == 0 ? -6 : 3 * rank - 6;
    const uint32_t pt = CH_PART + (w >> 1) * 4096 + (w & 1) * 256;
    const uint32_t barS = sb + CH_BAR, barM = barS + 8, zero = barS + 24;
    char* const ring0 = ring_base();
    const uint32_t m_rd = ring_off(24 + w, side), o_rd = ring_off(rank * 8 + w, side);
    uint32_t pub;
    if (PV) { int pos, cw = o_chunk(h * 8 + v0 + w, pos); pub = (ring_off(cw, 0) & ~4096u) + pos * 256; }
    else pub = (ring_off(24 + (h >> 2), 0) & ~4096u) + ((2 * h + w) & 7) * 256;
    char* const kvo = (char*)(PV ? g_vm + 128 * (v0 + w) : g_km + 64 * (u0 + w)) + h * 2048;
    const bool mown = !PV && w == rank && rank < 2;
    uint32_t lo16 = lane0 * 16;
    uint32_t sw[12][4];
#pragma unroll
    for (int i = 0; i < 12; i++) ldsm4t(sw[i], sb + lo16 + w * CH_WREG + i * 512);

#pragma unroll 1
    for (int s = 0;; s++) {
        const bool last = s == NSEG - 1;
        const uint32_t slot = (s & 3) << 14;
        lo16 += delay<DLM>(zero);
        const uint32_t lane = lo16 >> 4, l16 = sb + lo16, wl = l16 + w * CH_WREG, pw = l16 + CH_PART + w * 512;
        const uint32_t xs = l16 + CH_XS + nq * 512 + (w - nq) * 1024;
        const uint32_t eye = ((lo16 >> 7) == (lane & 3)) ? ((lo16 & 64) ? 0x3F800000u : 0x3F80u) : 0u;
        uint2 b[8];
        const char* pm = ring0 + (m_rd + slot + (lo16 >> 1));
        poll_issue<8>(b, pm, true);
        preload<0, ML, 12>(sw, wl, zero);
        if (FNC & 1) bar_arrive(14, 256);
        poll_check<8>(b, pm, delay<FNC & 1>(zero));
        if ((OB || (XB & 1)) && !last) bar_arrive(8, 256 + OB);
        if (PV && !last && w == 7) bar_arrive(13, 64);
        {
            float acc[6][4];
#pragma unroll
            for (int kk = 0; kk < 8; kk++) {
                const int j = (2 * kk) % 12;
                if (kk == 0) { mma16z(acc[5], sw[0], b[0].x, b[0].y); mma16z(acc[4], sw[1], b[0].x, b[0].y); }
                else { mma16(acc[5], sw[j], b[kk].x, b[kk].y); mma16(acc[4], sw[j + 1], b[kk].x, b[kk].y); }
#pragma unroll
                for (int i = 0; i < 4; i++) {
                    if (kk == 0) mma16z(acc[i], wa[i * 8], b[0].x, b[0].y);
                    else mma16(acc[i], wa[i * 8 + kk], b[kk].x, b[kk].y);
                    if (i < 2) ldsm4t(sw[j + i], wl + (12 + 2 * kk + i) * 512);
                }
            }
            st_part(pw + 4 * 2048, acc[4], acc[5]);
            st_part(pw, acc[0], acc[1]);
            st_part(pw + 2 * 2048, acc[2], acc[3]);
        }
        uint32_t kv0, kv1;
        const uint32_t lp = l16 + (lane >> 4) * 256, pl = lp + pt;
        if (!PV) {
            bar_sync(1, last ? 256 : 256 + OB);
            red_part<true>(kv1, kv0, pl, eye);
            sts64(l16 + CH_QK + (w >> 1) * 512 + (w & 1) * 8, __uint_as_float(kv1), __uint_as_float(kv0));
            if (!last) bar_arrive(2, nq * 32 + 64 + OB);
        } else {
            bar_sync(1, last ? 256 : 256 + OB);
        }
        {
            float va[4][4];
            const float z = __uint_as_float(delay<1>(zero));
#pragma unroll
            for (int i = 0; i < 4; i++) va[i][0] = va[i][1] = va[i][2] = va[i][3] = z;
#pragma unroll
            for (int kk = 0; kk < 8; kk++) {
                const int c = (PV ? VCH_P : VCH_C) == 4 ? kk & 1 : 0;
                if (kk < 2) { mma16(va[c], wa[32 + 2 * kk], b[kk].x, b[kk].y); mma16(va[2 + c], wa[33 + 2 * kk], b[kk].x, b[kk].y); }
                else { mma16(va[c], sw[(2 * kk) % 12], b[kk].x, b[kk].y); mma16(va[2 + c], sw[(2 * kk + 1) % 12], b[kk].x, b[kk].y); }
            }
            if ((PV ? VCH_P : VCH_C) == 4) {
#pragma unroll
                for (int j = 0; j < 4; j++) { va[0][j] += va[1][j]; va[2][j] += va[3][j]; }
            }
            st_part(pw + 6 * 2048, va[0], va[2]);
        }
        if (PV) {
            uint32_t vt0[4], vt1[4];
            ldsm4t(vt0, xs); ldsm4t(vt1, xs + 512);
            if (w >= 6 && !last) {
                uint32_t kx[3][4];
#pragma unroll
                for (int j = 0; j < 3; j++)
                    ldsm4(kx[j], sb + CH_XS + j * 1024 + (j == 2 && nq == 5 ? 0 : ((lane >> 3) & 1) * 512) + (w - 6) * 256 + (lane >> 4) * 128 + (lane & 7) * 16);
                const uint32_t da = l16 + CH_SX + rank * 1280 + (w - 6) * 512, dc = sb + CH_SX + rank * 1280 + 1024 + lane * 8;
                bar_sync(2, nq * 32 + 64 + OB);
                uint32_t qk[3][4];
#pragma unroll
                for (int j = 0; j < 3; j++) {
                    const float4 v = lds128(l16 + CH_QK + j * 512);
                    qk[j][0] = __float_as_uint(v.x); qk[j][1] = __float_as_uint(v.y); qk[j][2] = __float_as_uint(v.z); qk[j][3] = __float_as_uint(v.w);
                }
                float s0[4], s1[4], s2[4], s3[4];
                mma16z(s0, qk[0], kx[0][0], kx[0][1]); mma16z(s1, qk[0], kx[0][2], kx[0][3]);
                mma16z(s2, qk[1], kx[1][0], kx[1][1]); mma16z(s3, qk[1], kx[1][2], kx[1][3]);
                if (nq == 5) qk[2][2] = qk[2][3] = 0;
                mma16(s0, qk[2], kx[2][0], kx[2][1]); mma16(s1, qk[2], kx[2][2], kx[2][3]);
                float m0[4], m1[4];
                mma16z(m0, qk[0], qk[0][1], qk[0][3]); mma16z(m1, qk[1], qk[1][1], qk[1][3]);
                mma16(m0, qk[2], qk[2][1], qk[2][3]);
                const float4 sv = make_float4(s0[0] + s2[0], s0[1] + s2[1], s1[0] + s3[0], s1[1] + s3[1]);
                st_async4(mapa(da, rk1), sv, mapa(barS, rk1));
                st_async4(mapa(da, rk2), sv, mapa(barS, rk2));
                {
                    const float c0 = m0[0] + m1[0], c1 = m0[1] + m1[1];
                    const int dr = w == 6 ? rk1 : rk2;
                    st_async2(mapa(dc, dr), c0, c1, mapa(barS, dr));
                    sts64(dc, c0, c1);
                }
                const float t4[4] = {sv.x, sv.y, sv.z, sv.w};
                sts128(da, t4);
            }
            bar_sync(3, last ? 256 : 256 + OB);
            if (!last && w == 7) bar_arrive(12, 64);
            red_part<false>(kv0, kv1, pl, eye);
            if (last) {
                uint32_t* d = (uint32_t*)(kvo + (uint32_t)(s * (NH * 2048) + lane * 4));
                d[0] = movm(kv0); d[32] = movm(kv1);
                break;
            }
            {
                const uint32_t sx = l16 + CH_SX, r0 = rank * 1280, r1 = rk1 * 1280, r2 = rk2 * 1280;
                float4 a0 = lds128(sx + r0), b0 = lds128(sx + 512 + r0);
                const float2 c0 = lds64(sx + 1024 + r0 - lane * 8);
                preload<0, 0, PE>(sw, wl + 28 * 512, zero);
                mbar_wait(barS, s & 1);
                const float4 a1 = lds128(sx + r1), a2 = lds128(sx + r2), b1 = lds128(sx + 512 + r1), b2 = lds128(sx + 512 + r2);
                const float2 c1 = lds64(sx + 1024 + r1 - lane * 8), c2 = lds64(sx + 1024 + r2 - lane * 8);
                a0 = add4(add4(a0, a1), a2); b0 = add4(add4(b0, b1), b2);
                float sc[10] = {a0.x, a0.y, a0.z, a0.w, b0.x, b0.y, b0.z, b0.w, c0.x + c1.x + c2.x, c0.y + c1.y + c2.y};
                float mx = fmaxf(fmaxf(fmaxf(sc[0], sc[1]), fmaxf(sc[2], sc[3])), fmaxf(fmaxf(sc[4], sc[5]), fmaxf(sc[6], sc[7])));
                mx = fmaxf(mx, fmaxf(sc[8], sc[9]));
                mx = fmaxf(fmaxf(mx, __shfl_xor_sync(0xffffffffu, mx, 1)),
                           fmaxf(__shfl_xor_sync(0xffffffffu, mx, 2), __shfl_xor_sync(0xffffffffu, mx, 3)));
                const float cs = 0.08838834764831845f * 1.4426950408889634f;
                const float mb = -mx * cs;
#pragma unroll
                for (int j = 0; j < 10; j++) sc[j] = ex2(fmaf(sc[j], cs, mb));
                uint32_t pf[5];
#pragma unroll
                for (int j = 0; j < 5; j++) pf[j] = pack_bf16(sc[2 * j], sc[2 * j + 1]);
                float o0[4], o1[4], o2[4], o3[4], o4[4], o5[4];
                const uint32_t p0[4] = {pf[0], 0, pf[1], 0}, p1[4] = {pf[2], 0, pf[3], 0};
                mma16z(o0, p0, vt0[0], vt0[1]); mma16z(o1, p0, vt1[0], vt1[1]);
                mma16z(o2, p1, vt0[2], vt0[3]); mma16z(o3, p1, vt1[2], vt1[3]);
                mma8z(o4, pf[4], 0, kv0); mma8z(o5, pf[4], 0, kv1);
                float sum = (((sc[0] + sc[1]) + (sc[2] + sc[3])) + ((sc[4] + sc[5]) + (sc[6] + sc[7]))) + (sc[8] + sc[9]);
                sum = (sum + __shfl_xor_sync(0xffffffffu, sum, 1)) + (__shfl_xor_sync(0xffffffffu, sum, 2) + __shfl_xor_sync(0xffffffffu, sum, 3));
                float inv; asm("rcp.approx.ftz.f32 %0, %1;" : "=f"(inv) : "f"(sum));
                const uint32_t ox = pack_bf16((o0[0] + o2[0] + o4[0]) * inv, (o0[1] + o2[1] + o4[1]) * inv);
                const uint32_t oy = pack_bf16((o1[0] + o3[0] + o5[0]) * inv, (o1[1] + o3[1] + o5[1]) * inv);
                char* const pp = ring0 + (pub + slot + (lo16 >> 1));
                st_pub(pp, ox, oy); st_pub(pp + 4096, ox, oy);
                if (OB || (XB & 4)) bar_arrive(10, (8 - nq) * 32 + OB);
                preload<0, PE, PL>(sw, wl + 28 * 512, zero);
            }
            kv0 = movm(kv0); kv1 = movm(kv1);
        } else {
            *(uint32_t*)(kvo + (uint32_t)(s * (NH * 2048) + lane * 4)) = kv0;
            bar_sync(3, last ? 256 : 256 + OB);
            if (last) break;
            preload<1, 0, CL>(sw, wl + 28 * 512, zero);
        }
        uint2 c[11];
        bar_sync(4, 256 + OB);
        const char* po = ring0 + (o_rd + slot + (lo16 >> 1) + delay<DLO>(zero));
        poll_issue<11>(c, po, rank < 2);
        preload<0, PV ? PL : CL, 12>(sw, wl + 28 * 512, zero);
        if (PV) { uint32_t* d = (uint32_t*)(kvo + (uint32_t)(s * (NH * 2048) + lane * 4)); d[0] = kv0; d[32] = kv1; }
        {
            float acc[4][4];
            uint32_t sx[GX][4];
#pragma unroll
            for (int i = 0; i < GX; i++) ldsm4t(sx[i], wl + (40 + i) * 512);
            if (FNC & 2) bar_arrive(15, 256);
            poll_check<11>(c, po, delay<(FNC >> 1)>(zero));
            if (OB || (XB & 2)) bar_arrive(9, 256 + OB);
#pragma unroll
            for (int f = 0; f < 22; f++) {
                const int kk = f >> 1, a = f & 3;
                if (f < 4) mma16z(acc[a], sw[f], c[kk].x, c[kk].y);
                else if (f >= 12 && f < 12 + GX) mma16(acc[a], sx[f - 12], c[kk].x, c[kk].y);
                else mma16(acc[a], sw[f % (12 + GX)], c[kk].x, c[kk].y);
                if (f + 12 + GX < 22) ldsm4t(sw[f], wl + (40 + GX + f) * 512);
            }
#pragma unroll
            for (int i = 0; i < 2; i++) {
#pragma unroll
                for (int j = 0; j < 4; j++) acc[i][j] += acc[i + 2][j];
                sts128(l16 + CH_PART + i * 4096 + w * 512, acc[i]);
            }
        }
        if (!PV && w < 2) {
            bar_sync(5, 288 + OB);
            float4 v[8];
#pragma unroll
            for (int i = 0; i < 8; i++) v[i] = lds128(l16 + CH_PART + w * 4096 + i * 512);
            float4 r = add4(add4(add4(v[0], v[1]), add4(v[2], v[3])), add4(add4(v[4], v[5]), add4(v[6], v[7])));
            if (!mown) st_async4(mapa(l16 + CH_MX + rank * 512, w), r, mapa(barM, w));
            bar_arrive(7, 256 + OB);
            if (mown) {
                mbar_wait(barM, s & 1);
                float4 x = lds128(l16 + CH_MX + (rank ^ 1) * 512), y = lds128(l16 + CH_MX + 2 * 512);
                r = add4(add4(x, r), y);
                const uint32_t mx = movm(pack_bf16(r.x, r.y)), my = movm(pack_bf16(r.z, r.w));
                const uint32_t ns = (slot + 0x4000) & 0xC000;
                char* const pp = ring0 + (pub + ns + (lo16 >> 1));
                st_pub(pp, mx, my); st_pub(pp + 4096, mx, my);
            }
            preload<0, 0, ML>(sw, wl, zero);
        } else {
            bar_arrive(5, 288 + OB);
            bar_sync(7, 256 + OB);
            preload<MP, 0, ML>(sw, wl, zero);
        }
        bar_sync(6, 320 + OB);
    }
}

__device__ __forceinline__ void chain_pace(const uint32_t sb, const int lane, const int rank, const int aware) {
    const uint32_t zero = sb + CH_BAR + 24;
    if (lane == 0) {
        char* ring = ring_base();
        uint32_t* p0 = (uint32_t*)(ring + ring_off(blockIdx.x & 15, 0) + 3072 + (blockIdx.x >> 4) * 128);
        uint32_t* p1 = (uint32_t*)(ring + ring_off(blockIdx.x & 15, 1) + 3072 + (blockIdx.x >> 4) * 128);
        *p0 = 0; *p1 = 0;
        int b0 = 1 << 30, b1 = 1 << 30; uint32_t v = 0;
        for (int r = 0; r < 4 || (r < 256 && !mbar_test(sb + CH_BAR + 16, 0)); r++) {
            uint32_t t0 = clk(); v = atomicExch(p0 + (v == 500), r); uint32_t t1 = v == 777 ? clk() + 1 : clk(); b0 = min(b0, (int)(t1 - t0));
            t0 = clk(); v = atomicExch(p1 + (v == 500), r); t1 = v == 777 ? clk() + 1 : clk(); b1 = min(b1, (int)(t1 - t0));
            asm volatile("st.volatile.shared.u32 [%0], %1;" ::"r"(zero + 4), "r"(aware ? (b1 < b0) ^ (aware - 1) : 0) : "memory");
        }
    }
    __syncwarp();
#pragma unroll 1
    for (int s = 1; s < NSEG; s++) {
        bar_sync(5, 288 + OB);
        bar_arrive(6, 320 + OB + (rank == 2 ? delay<PACE2>(zero) : 0));
    }
}
__device__ __forceinline__ char* reset_ptr(const int lane, const int rank, const int h) {
    const int nq = rank == 0 ? 6 : 5, v0 = rank == 0 ? -6 : 3 * rank - 6;
    int pos, cw = o_chunk(h * 8 + v0 + min(max(5 + (lane >> 3), nq), 7), pos);
    if (lane >= 24 && rank < 2) { cw = 24 + (h >> 2); pos = (2 * h + rank) & 7; }
    return ring_base() + ((ring_off(cw, 0) & ~4096u) + pos * 256 + (lane & 7) * 16);
}
__device__ __forceinline__ void chain_chores(const uint32_t sb, const int lane, const int rank, const int h, const bf16* __restrict__ mem0) {
    const int nq = rank == 0 ? 6 : 5, u0 = rank == 0 ? 0 : 1 + 5 * rank, v0 = rank == 0 ? -6 : 3 * rank - 6;
    const uint32_t barS = sb + CH_BAR, barM = barS + 8, barX = barS + 16;
    auto xload = [&](int s) {
        mbar_expect(barX, 8192 - nq * 512);
        bulk_load(sb + CH_XS, g_kx + (size_t)(s * NH + h) * 4096 + u0 * 256, nq * 512, barX);
        bulk_load(sb + CH_XS + nq * 512, g_vx + (size_t)(s * NH + h) * 4096 + (v0 + nq) * 512, (8 - nq) * 1024, barX);
    };
    char* const rb = reset_ptr(lane, rank, h);
    int* const kvf = g_kvf + blockIdx.x * 16;
    if (rank < 2) {
        const uint32_t* p = (const uint32_t*)(mem0 + (lane >> 2) * DM + 32 * h + 16 * rank + 2 * (lane & 3));
        char* d = ring_base() + ((ring_off(24 + (h >> 2), 0) & ~4096u) + ((2 * h + rank) & 7) * 256 + lane * 8);
        const uint32_t x = p[0] == SENT ? 0x7FFF7FFFu : p[0];
        st_pub(d, x, p[4]); st_pub(d + 4096, x, p[4]);
    }
    if (!KVN) __nanosleep(18000);
    wait_ctr(kvf, KVN);
    asm volatile("fence.proxy.async.global;" ::: "memory");
    if (elect()) xload(0);
#pragma unroll 1
    for (int s = 0; s < NSEG - 1; s++) {
        if (lane == 0) {
            mbar_expect(barS, 2 * 1280);
            if (rank < 2) mbar_expect(barM, 2 * 512);
        }
        bar_sync(13, 64);
#pragma unroll
        for (int i = 0; i < 4; i++)
            asm volatile("st.relaxed.gpu.global.v4.u32 [%0], {%1,%1,%1,%1};" ::"l"(rb + ((((s + 2) & 3) << 14) + (i >> 1) * 4096 + (i & 1) * 128)), "r"(SENT) : "memory");
        if (FEN || (s & 3) == 0) fence_gpu();
        if (lane == 0 && (s & 3) == 0 && s) atomicAdd(g_ctr + C_CHAIN + (s >> 2) - 1, 1);
        if ((s & 3) == 3) { wait_ctr(kvf + (s >> 2) + 1, KVN); asm volatile("fence.proxy.async.global;" ::: "memory"); }
        __syncwarp();
        bar_sync(12, 64);
        if (elect()) xload(s + 1);
        mbar_wait(barX, (s + 1) & 1);
        bar_sync(6, 320 + OB);
    }
}

struct S4Params { const bf16 *Are, *Aim, *Bre, *Bim, *Cre, *Cim, *ldt, *dsk; };
__device__ __forceinline__ float2 cmul(float2 a, float2 b) { return make_float2(a.x * b.x - a.y * b.y, a.x * b.y + a.y * b.x); }
__device__ __forceinline__ float2 csq(float2 a) { return make_float2(a.x * a.x - a.y * a.y, (a.x + a.x) * a.y); }
__device__ __forceinline__ float2 cexp_t(float lr, float turns) {
    float f = (turns - rintf(turns)) * 6.283185307179586f, e = ex2(lr);
    return make_float2(e * __cosf(f), e * __sinf(f));
}
__device__ __forceinline__ float bf_at(uint2 v, int i) {
    const uint32_t w = i < 2 ? v.x : v.y;
    return __uint_as_float((i & 1) ? w & 0xFFFF0000u : w << 16);
}
__device__ __forceinline__ void kg_step(uint32_t (&a)[4][4], uint32_t (&b)[5][2], uint32_t pa, uint32_t pe, float x0) {
#pragma unroll
    for (int i = 0; i < 2; i++) {
        const float4 p = lds128(pa + i * 64);
        const float2 e8 = lds64(pe + i * 32), c = make_float2(p.z, p.w);
        const float mag = ex2(p.x * x0), ph = p.y * x0;
        float2 e0 = make_float2(mag * __cosf(ph), mag * __sinf(ph)), e1 = cmul(e0, e8);
#pragma unroll
        for (int j = 0; j < 4; j++) {
            a[j][2 * i] = pack_bf16(e0.x, e0.y); a[j][2 * i + 1] = pack_bf16(e1.x, e1.y);
            e0 = csq(e0); e1 = csq(e1);
        }
        float2 m = cmul(c, e0);
        b[0][i] = pack_bf16(m.x, -m.y);
#pragma unroll
        for (int j = 0; j < 4; j++) {
            m = cmul(c, e1);
            b[j + 1][i] = pack_bf16(m.x, -m.y);
            if (j < 3) e1 = csq(e1);
        }
    }
}
__device__ __forceinline__ void kg_mma(float (&kd)[5][4], const uint32_t (&a)[4][4], const uint32_t (&b)[5][2]) {
    mma16(kd[0], a[0], b[0][0], b[0][1]);
#pragma unroll
    for (int j = 0; j < 4; j++) mma16(kd[j + 1], a[j], b[j + 1][0], b[j + 1][1]);
}
struct KgRaw { uint2 v[6]; float ldt; };
__device__ __forceinline__ void kg_load(KgRaw& r, const S4Params& P, int d, int lane) {
    const bf16* src[6] = {P.Are, P.Aim, P.Bre, P.Bim, P.Cre, P.Cim};
#pragma unroll
    for (int j = 0; j < 6; j++) r.v[j] = __ldg((const uint2*)(src[j] + d * 128) + lane);
    r.ldt = __bfloat162float(P.ldt[d]);
}
__device__ __forceinline__ float kg_params(const KgRaw& r, uint32_t stg, int lane) {
    const float dt = __bfloat162float(__float2bfloat16(expf(r.ldt)));
    float k2048 = 0.f;
#pragma unroll
    for (int i = 0; i < 4; i++) {
        const float br = dt * bf_at(r.v[2], i), bi = dt * bf_at(r.v[3], i), cr = bf_at(r.v[4], i), ci = bf_at(r.v[5], i);
        const float zr = dt * bf_at(r.v[0], i) * 1.4426950408889634f;
        float zt = dt * bf_at(r.v[1], i) * 0.15915494309189535f;
        zt -= rintf(zt);
        const float v[4] = {zr, zt * 6.283185307179586f, cr * br - ci * bi, cr * bi + ci * br};
        const float2 e8 = cexp_t(8.f * zr, 8.f * zt), el = cexp_t(2048.f * zr, 2048.f * zt);
        k2048 += v[2] * el.x - v[3] * el.y;
        sts128(stg + (i * 32 + lane) * 16, v);
        sts64(stg + 2048 + (i * 32 + lane) * 8, e8.x, e8.y);
    }
#pragma unroll
    for (int o = 16; o; o >>= 1) k2048 += __shfl_xor_sync(0xffffffffu, k2048, o);
    __syncwarp();
    return k2048;
}
__device__ __forceinline__ void kg_store(const float (&kd)[5][4], float k2048, uint32_t stg, int d, int lane) {
    __syncwarp();
    const uint32_t ta = stg + (lane & 7) * 32 + ((lane >> 3) & 1) * 16 + (lane >> 4) * 256;
    stsm4t(ta, pack_bf16(kd[0][0], kd[0][1]), pack_bf16(kd[0][2], kd[0][3]), pack_bf16(kd[1][0], kd[1][1]), pack_bf16(kd[1][2], kd[1][3]));
    stsm4t(ta + 512, pack_bf16(kd[2][0], kd[2][1]), pack_bf16(kd[2][2], kd[2][3]), pack_bf16(kd[3][0], kd[3][1]), pack_bf16(kd[3][2], kd[3][3]));
    stsm4t(ta + 1024, pack_bf16(kd[4][0], kd[4][1]), pack_bf16(kd[4][2], kd[4][3]), pack_bf16(k2048, 0.f), 0);
    __syncwarp();
#pragma unroll
    for (int j = 0; j < 3; j++) ((float4*)(g_kd + d * 768))[j * 32 + lane] = lds128(stg + j * 512 + lane * 16);
    __syncwarp();
}

__global__ void __cluster_dims__(3, 1, 1) __launch_bounds__(CH_THREADS, 1)
chain_kernel(const __grid_constant__ CUtensorMap mq, const __grid_constant__ CUtensorMap mk, const __grid_constant__ CUtensorMap mv,
             const __grid_constant__ CUtensorMap mo, const bf16* __restrict__ Wq, const bf16* __restrict__ Wk, const bf16* __restrict__ Wv,
             const bf16* __restrict__ mem0, const __grid_constant__ S4Params P, int aware) {
    extern __shared__ __align__(1024) unsigned char smem[];
    const uint32_t sb = smem_u32(smem);
    const int tid = threadIdx.x, lane = tid & 31;
    const int w = __shfl_sync(0xffffffffu, tid >> 5, 0);
    int rank; asm("mov.u32 %0, %%cluster_ctarank;" : "=r"(rank));
    const int h = blockIdx.x / 3;
    if (tid == 0) {
        mbar_init(sb + CH_BAR, 1); mbar_init(sb + CH_BAR + 8, 1); mbar_init(sb + CH_BAR + 16, 1);
        for (int i = 0; i < 16; i++) mbar_init(sb + CH_BAR + 64 + i * 8, 1);
        *(int*)(smem + CH_BAR + 24) = 0; *(int*)(smem + CH_BAR + 28) = 0; *(int*)(smem + CH_BAR + 32) = 0;
        asm volatile("fence.mbarrier_init.release.cluster;" ::: "memory");
    }
    if (w == 10 && PFKV) {
        const int e = lane * 96 + blockIdx.x;
        if (e < 2048) asm volatile("cp.async.bulk.prefetch.L2.global [%0], 8192;" ::"l"(((e & 1) ? Wv : Wk) + (size_t)(e >> 1) * HD) : "memory");
        if (PFKV > 1) __nanosleep(PFKV);
    }
    if (w == 9) {
        char* const rb = reset_ptr(lane, rank, h);
#pragma unroll
        for (int i = 0; i < 8; i++)
            asm volatile("st.relaxed.gpu.global.v4.u32 [%0], {%1,%1,%1,%1};" ::"l"(rb + (((i >> 2) << 14) + ((i >> 1) & 1) * 4096 + (i & 1) * 128)), "r"(SENT) : "memory");
        if (lane < 16) g_kvf[blockIdx.x * 16 + lane] = 0;
        if (blockIdx.x == 0)
            for (int k = lane; k < N_CTR; k += 32) g_ctr[k] = 0;
        fence_gpu();
        __syncwarp();
        asm volatile("griddepcontrol.launch_dependents;" ::: "memory");
    }
    __syncthreads();
    asm volatile("barrier.cluster.arrive.relaxed.aligned;" ::: "memory");

    if (w >= 8) {
        reg_dec<24>();
        asm volatile("barrier.cluster.wait.aligned;" ::: "memory");
        if (w == 8) chain_pace(sb, lane, rank, aware);
        else if (w == 9) {
            chain_chores(sb, lane, rank, h, mem0);
            asm volatile("st.volatile.shared.u32 [%0], %1;" ::"r"(sb + CH_BAR + 32), "r"(0x3F803F80) : "memory");
        } else if (w == 11 && KEEP) {
#pragma unroll 1
            for (int it = 0; it < (1 << 22); it++) {
                int d0, d1;
                const uint32_t x = delay<1>(sb + CH_BAR + 32);
                asm volatile("mma.sync.aligned.m8n8k16.row.col.s32.s8.s8.s32 {%0,%1}, {%2}, {%2}, {%3,%3};" : "=r"(d0), "=r"(d1) : "r"(x), "r"(0));
                if (d0 | d1) break;
                if ((XB & 8) && lane == 0) asm volatile("st.relaxed.gpu.global.u32 [%0], %1;" ::"l"(g_kd + DM * 768 + blockIdx.x * 64), "r"(it) : "memory");
                if ((XB & 16) && lane == 0) ld_acq((int*)(g_kd + DM * 768 + blockIdx.x * 64));
                __nanosleep(KEEP);
            }
        }
    } else {
        reg_inc<240>();
        const int nq = rank == 0 ? 6 : 5;
        const int u0 = rank == 0 ? 0 : 1 + 5 * rank;
        const int v0 = rank == 0 ? -6 : 3 * rank - 6;
        const int gw = rank * 8 + w;
        const int ks0 = gw < 16 ? 11 * gw : 176 + 10 * (gw - 16);
        const int nko = gw < 16 ? 11 : 10;
        const uint32_t wr = sb + w * CH_WREG, bar0 = sb + CH_BAR + 64 + w * 16, bar1 = bar0 + 8;
        uint32_t wa[36][4];
        const uint32_t vst = sb + CH_PART + w * 2048;
        const int cq = h * DH + 8 * u0, cv = h * DH + 16 * (v0 + 6);
        const int r8 = lane >> 2, p = lane & 3;
        const bf16* src = p >= 2 ? ((p & 1) ? Wk : Wq) + cq + 32 : rank == 0 ? ((p & 1) ? Wk : Wq) + cq + 40 : Wv + cv - 16 + 8 * p;
        src += (size_t)(128 * w + r8) * HD;
        auto cp_rows = [&](int kh) {
            cp16(wr + ((kh >> 1) * 2 + (p >> 1)) * 512 + ((kh & 1) * 2 + (p & 1)) * 128 + r8 * 16, src + (size_t)kh * 8 * HD);
        };
        {
            int d = blockIdx.x * 8 + w, t = 0;
            const int d1 = 768 + blockIdx.x * 3 + w, nt = (w < 3 && d1 < DM) ? 32 : 16;
            const uint32_t stg = wr + 4096;
            KgRaw raw, raw1;
            kg_load(raw, P, d, lane);
            kg_load(raw1, P, min(d1, DM - 1), lane);
            float kd[5][4], k2048;
#pragma unroll 1
            for (int i = -LDW; i < 9 || t < nt; i++) {
                if (i >= 0 && i < 9) {
                    const uint32_t bar = bar0 + (i & 1) * 8;
                    if (i >= 2) mbar_wait(bar, ((i >> 1) - 1) & 1);
                    if (elect()) {
                        mbar_expect(bar, 2048);
                        if (i < 8) tma2d(wr + 8192 + (i & 1) * 8192 + (i >> 1) * 2048, (i & 1) ? &mk : &mq, cq, 128 * w + 32 * (i >> 1), bar);
                        else tma2d(vst, &mv, cv, 128 * w, bar);
                    }
                    if (i < 8) cp_rows(i);
                }
#pragma unroll 1
                for (int e = min(t + KGS, nt); t < e; t++) {
                    if ((t & 15) == 0) {
                        k2048 = kg_params(raw, stg, lane);
#pragma unroll
                        for (int j = 0; j < 20; j++) kd[j >> 2][j & 3] = 0.f;
                    }
                    uint32_t ka[4][4], kb[5][2];
                    kg_step(ka, kb, stg + ((t & 15) * 8 + (lane & 3)) * 16, stg + 2048 + ((t & 15) * 8 + (lane & 3)) * 8, (float)(lane >> 2));
                    kg_mma(kd, ka, kb);
                    if ((t & 15) == 15) { kg_store(kd, k2048, stg, d, lane); raw = raw1; d = d1; }
                }
            }
        }
        const uint32_t lrow = ((lane >> 4) * 8 + (lane & 7)) * 64, lsw = (lane >> 1) & 3, lh = (lane >> 3) & 1;
        mbar_wait(bar1, 1); mbar_wait(bar0, 0);
#pragma unroll
        for (int i = 0; i < 32; i++) ldsm4t(wa[i], wr + 8192 + lh * 8192 + (i & 7) * 1024 + lrow + (((i >> 3) ^ lsw) << 4));
#pragma unroll
        for (int i = 0; i < 4; i++) ldsm4t(wa[32 + i], vst + (i >> 1) * 1024 + lrow + ((((i & 1) * 2 + lh) ^ lsw) << 4));
        asm volatile("fence.proxy.async.shared::cta;" ::"r"(wa[31][0]), "r"(wa[35][0]) : "memory");
        __syncwarp();
#pragma unroll 1
        for (int i = 9; i < 18; i++) {
            const uint32_t bar = bar0 + (i & 1) * 8;
            if (i >= 11) mbar_wait(bar, ((i >> 1) - 1) & 1);
            if (elect()) {
                const int j = 2 * (i - 12), nb = min(2, nko - j);
                mbar_expect(bar, i < 12 ? 2048 : nb * 1024);
                if (i < 12) tma2d(wr + 8192 + (i - 9) * 2048, &mv, cv, 128 * w + 32 * (i - 8), bar);
                else {
                    if (nb > 0) tma2d(wr + 14336 + j * 1024, &mo, 32 * h, 16 * (ks0 + j), bar);
                    if (nb > 1) tma2d(wr + 15360 + j * 1024, &mo, 32 * h, 16 * (ks0 + j + 1), bar);
                }
            }
            if (i < 17) cp_rows(i - 1);
        }
        mbar_wait(bar0, 0); mbar_wait(bar1, 0);
#pragma unroll 1
        for (int i0 = -1; i0 < 17; i0 += 6) {
            uint32_t x[6][2][4];
#pragma unroll
            for (int i = 0; i < 6; i++) {
                const uint32_t a = wr + 8192 + max(i0 + i, 0) * 1024 + lrow;
                ldsm4t(x[i][0], a + ((lh ^ lsw) << 4)); ldsm4t(x[i][1], a + (((2 + lh) ^ lsw) << 4));
            }
            if (i0 == 11 && nko == 10) {
#pragma unroll
                for (int j = 0; j < 8; j++) x[5][j >> 2][j & 3] = 0;
            }
            __syncwarp();
#pragma unroll
            for (int i = 0; i < 6; i++) {
                const uint32_t a = wr + 8192 + max(i0 + i, 0) * 1024 + lane * 16;
                stsm4t(a, x[i][0][0], x[i][0][1], x[i][0][2], x[i][0][3]); stsm4t(a + 512, x[i][1][0], x[i][1][1], x[i][1][2], x[i][1][3]);
            }
        }
        asm volatile("cp.async.wait_all;" ::: "memory");
        asm volatile("barrier.cluster.wait.aligned;" ::: "memory");
        bar_sync(1, 256);
        mbar_wait_long(sb + CH_BAR + 16, 0);
        const int side = __shfl_sync(0xffffffffu, *(volatile int*)(smem + CH_BAR + 28), 0);
        if (w >= nq) chain_loop<true>(wa, sb, w, lane, rank, h, side);
        else chain_loop<false>(wa, sb, w, lane, rank, h, side);
    }
}

constexpr int G_STAGE = 49152, G_NST = 4;
constexpr int G_STG = G_NST * G_STAGE;
constexpr int G_BAR = G_STG + 32768;
constexpr int G_SMEM = G_BAR + 256 + 1024;

#define WLOG(e)
constexpr int IT_QA = 0, IT_O = 1, IT_S4 = 2, IT_END = 3, IT_KV = 4;
#define O_WIDE 15
#define PING 1
#define S4DIR 5
#define S4REL 4
#define KVI 1
#define KVF 2
#define KVS 8
#define STM 0
__device__ __forceinline__ void st_out(uint32_t* p, uint32_t v) {
    if (STM == 0) *p = v;
    else if (STM == 1) __stcs(p, v);
    else asm volatile("st.global.L1::no_allocate.u32 [%0], %1;" ::"l"(p), "r"(v) : "memory");
}
#define Q_S1 0
#define Q_B0 10
#define Q_L 1
#define Q_T0 8
__device__ __forceinline__ int queue_item(int q) {
    if (q < 512) return (IT_KV << 16) | ((q >> 5) << 8) | (q & 31);
    q -= 512;
    if (q < Q_B0 * Q_T0) return (IT_QA << 16) | ((q % Q_B0) << 8) | (q / Q_B0);
    constexpr int W1 = O_WIDE - 1, T1 = Q_T0 + Q_L;
    if (q < W1 * Q_T0) return (IT_QA << 16) | ((q / Q_T0) << 8) | (q % Q_T0);
    if (q < W1 * T1) return (IT_QA << 16) | ((q % W1) << 8) | (q / W1);
    if (q < O_WIDE * T1) return (IT_QA << 16) | (W1 << 8) | (q - W1 * T1);
    if (q < O_WIDE * 16) return (IT_QA << 16) | ((q % O_WIDE) << 8) | (q / O_WIDE);
    q -= O_WIDE * 16;
    if (q < Q_S1) return (IT_S4 << 16) | q;
    q -= Q_S1;
    if (q < (16 - O_WIDE) * 8) return (IT_O << 16) | ((O_WIDE + (q >> 3)) << 8) | (q & 7);
    q -= (16 - O_WIDE) * 8;
    if (q < 128 - Q_S1) return (IT_S4 << 16) | (Q_S1 + q);
    return IT_END << 16;
}
constexpr int N_LATE = O_WIDE * 4 + (16 - O_WIDE) * 16;
static_assert(N_LATE <= 96, "first items of the late CTAs");
__device__ __forceinline__ int late_item(int j) {
    if (j < O_WIDE * 4) return (IT_O << 16) | ((j >> 2) << 8) | (j & 3);
    j -= O_WIDE * 4;
    return (IT_QA << 16) | ((O_WIDE + (j >> 4)) << 8) | (j & 15);
}
__device__ __forceinline__ void tma2d_store(const CUtensorMap* m, uint32_t src, int c0, int c1) {
    asm volatile("cp.async.bulk.tensor.2d.global.shared::cta.bulk_group [%0, {%2, %3}], [%1];" ::"l"(m), "r"(src), "r"(c0), "r"(c1) : "memory");
}

__device__ __forceinline__ void wgmma_s64(float (&d)[32], uint32_t a0, uint32_t a1, uint32_t a2, uint32_t a3, uint64_t db, int acc) {
    asm volatile("{.reg .pred p; setp.ne.b32 p, %37, 0;\n"
        "wgmma.mma_async.sync.aligned.m64n64k16.f32.bf16.bf16 {"
        "%0,%1,%2,%3,%4,%5,%6,%7,%8,%9,%10,%11,%12,%13,%14,%15,"
        "%16,%17,%18,%19,%20,%21,%22,%23,%24,%25,%26,%27,%28,%29,%30,%31"
        "}, {%32,%33,%34,%35}, %36, p, 1, 1, 0;}"
        : "+f"(d[0]), "+f"(d[1]), "+f"(d[2]), "+f"(d[3]), "+f"(d[4]), "+f"(d[5]), "+f"(d[6]), "+f"(d[7]), "+f"(d[8]), "+f"(d[9]), "+f"(d[10]), "+f"(d[11]), "+f"(d[12]), "+f"(d[13]), "+f"(d[14]), "+f"(d[15]), "+f"(d[16]), "+f"(d[17]), "+f"(d[18]), "+f"(d[19]), "+f"(d[20]), "+f"(d[21]), "+f"(d[22]), "+f"(d[23]), "+f"(d[24]), "+f"(d[25]), "+f"(d[26]), "+f"(d[27]), "+f"(d[28]), "+f"(d[29]), "+f"(d[30]), "+f"(d[31])
        : "r"(a0), "r"(a1), "r"(a2), "r"(a3), "l"(db), "r"(acc));
}
__device__ __forceinline__ void wgmma_s16(float (&d)[8], uint32_t a0, uint32_t a1, uint32_t a2, uint32_t a3, uint64_t db, int acc) {
    asm volatile("{.reg .pred p; setp.ne.b32 p, %13, 0;\n"
        "wgmma.mma_async.sync.aligned.m64n16k16.f32.bf16.bf16 {"
        "%0,%1,%2,%3,%4,%5,%6,%7"
        "}, {%8,%9,%10,%11}, %12, p, 1, 1, 0;}"
        : "+f"(d[0]), "+f"(d[1]), "+f"(d[2]), "+f"(d[3]), "+f"(d[4]), "+f"(d[5]), "+f"(d[6]), "+f"(d[7])
        : "r"(a0), "r"(a1), "r"(a2), "r"(a3), "l"(db), "r"(acc));
}
__device__ __forceinline__ void wgmma_v128(float (&d)[64], uint32_t a0, uint32_t a1, uint32_t a2, uint32_t a3, uint64_t db, int acc) {
    asm volatile("{.reg .pred p; setp.ne.b32 p, %69, 0;\n"
        "wgmma.mma_async.sync.aligned.m64n128k16.f32.bf16.bf16 {"
        "%0,%1,%2,%3,%4,%5,%6,%7,%8,%9,%10,%11,%12,%13,%14,%15,"
        "%16,%17,%18,%19,%20,%21,%22,%23,%24,%25,%26,%27,%28,%29,%30,%31,"
        "%32,%33,%34,%35,%36,%37,%38,%39,%40,%41,%42,%43,%44,%45,%46,%47,"
        "%48,%49,%50,%51,%52,%53,%54,%55,%56,%57,%58,%59,%60,%61,%62,%63"
        "}, {%64,%65,%66,%67}, %68, p, 1, 1, 1;}"
        : "+f"(d[0]), "+f"(d[1]), "+f"(d[2]), "+f"(d[3]), "+f"(d[4]), "+f"(d[5]), "+f"(d[6]), "+f"(d[7]), "+f"(d[8]), "+f"(d[9]), "+f"(d[10]), "+f"(d[11]), "+f"(d[12]), "+f"(d[13]), "+f"(d[14]), "+f"(d[15]), "+f"(d[16]), "+f"(d[17]), "+f"(d[18]), "+f"(d[19]), "+f"(d[20]), "+f"(d[21]), "+f"(d[22]), "+f"(d[23]), "+f"(d[24]), "+f"(d[25]), "+f"(d[26]), "+f"(d[27]), "+f"(d[28]), "+f"(d[29]), "+f"(d[30]), "+f"(d[31]), "+f"(d[32]), "+f"(d[33]), "+f"(d[34]), "+f"(d[35]), "+f"(d[36]), "+f"(d[37]), "+f"(d[38]), "+f"(d[39]), "+f"(d[40]), "+f"(d[41]), "+f"(d[42]), "+f"(d[43]), "+f"(d[44]), "+f"(d[45]), "+f"(d[46]), "+f"(d[47]), "+f"(d[48]), "+f"(d[49]), "+f"(d[50]), "+f"(d[51]), "+f"(d[52]), "+f"(d[53]), "+f"(d[54]), "+f"(d[55]), "+f"(d[56]), "+f"(d[57]), "+f"(d[58]), "+f"(d[59]), "+f"(d[60]), "+f"(d[61]), "+f"(d[62]), "+f"(d[63])
        : "r"(a0), "r"(a1), "r"(a2), "r"(a3), "l"(db), "r"(acc));
}

__device__ __forceinline__ void attn_scores(float (&sx)[32], float (&sm)[8], const uint32_t (&q)[32], uint32_t sk) {
    const uint64_t dx = mkdesc(sk, 1024, 128, 0), dm = mkdesc(sk + 16384, 256, 128, 0);
    wg_fence();
#pragma unroll
    for (int ks = 0; ks < 8; ks++) {
        wgmma_s64(sx, q[4 * ks], q[4 * ks + 1], q[4 * ks + 2], q[4 * ks + 3], dx + ks * 128, ks);
        wgmma_s16(sm, q[4 * ks], q[4 * ks + 1], q[4 * ks + 2], q[4 * ks + 3], dm + ks * 32, ks);
    }
    wg_commit();
}
template <bool HI>
__device__ __forceinline__ void attn_softmax(uint32_t (&p)[2][20], const float (&sx)[2][32], const float (&sm)[2][8], bool sb, int lane) {
    constexpr int NF = HI ? 2 : 0, NT = NF + 3;
    const int gt = (lane >> 2) - 2 * (lane & 3);
    const float cs = 0.08838834764831845f * 1.4426950408889634f;
    float s[2][NT][4], m[4], l[4];
#pragma unroll
    for (int h = 0; h < 2; h++) {
#pragma unroll
        for (int j = 0; j < NT; j++)
#pragma unroll
            for (int e = 0; e < 4; e++) s[h][j][e] = j == NT - 1 ? (sb ? sm[h][4 + e] : sm[h][e]) : (sb ? sx[h][16 + 4 * j + e] : sx[h][4 * j + e]);
        if (gt < 0) s[h][NF][0] = s[h][NF + 1][2] = -INFINITY;
        if (gt < 1) s[h][NF][1] = s[h][NF + 1][3] = -INFINITY;
        m[2 * h] = fmaxf(s[h][0][0], s[h][0][1]); m[2 * h + 1] = fmaxf(s[h][0][2], s[h][0][3]);
#pragma unroll
        for (int j = 1; j < NT; j++) {
            if (j != NF + 1) m[2 * h] = fmaxf(m[2 * h], fmaxf(s[h][j][0], s[h][j][1]));
            m[2 * h + 1] = fmaxf(m[2 * h + 1], fmaxf(s[h][j][2], s[h][j][3]));
        }
    }
#pragma unroll
    for (int r = 0; r < 4; r++) m[r] = fmaxf(m[r], __shfl_xor_sync(0xffffffffu, m[r], 1));
#pragma unroll
    for (int r = 0; r < 4; r++) m[r] = fmaxf(m[r], __shfl_xor_sync(0xffffffffu, m[r], 2)) * -cs;
#pragma unroll
    for (int r = 0; r < 4; r++) {
        l[r] = 0.f;
#pragma unroll
        for (int j = 0; j < NT; j++)
            if ((r & 1) || j != NF + 1) {
                float* v = &s[r >> 1][j][2 * (r & 1)];
                v[0] = ex2(fmaf(v[0], cs, m[r])); v[1] = ex2(fmaf(v[1], cs, m[r]));
                l[r] += v[0] + v[1];
            }
    }
#pragma unroll
    for (int r = 0; r < 4; r++) l[r] += __shfl_xor_sync(0xffffffffu, l[r], 1);
#pragma unroll
    for (int r = 0; r < 4; r++) { l[r] += __shfl_xor_sync(0xffffffffu, l[r], 2); asm("rcp.approx.ftz.f32 %0, %0;" : "+f"(l[r])); }
    const uint32_t ma = sb ? 0u : ~0u;
#pragma unroll
    for (int h = 0; h < 2; h++)
#pragma unroll
        for (int j = 0; j < 5; j++) {
            const bool on = j == 4 || j < NF + 2;
            const int k = j == 4 ? NT - 1 : on ? j : 0, ia = j < 4 ? 2 * j : 16, ib = j < 4 ? 8 + 2 * j : 18;
            const uint32_t x = on && j != NF + 1 ? pack_bf16(s[h][k][0] * l[2 * h], s[h][k][1] * l[2 * h]) : 0;
            const uint32_t y = on ? pack_bf16(s[h][k][2] * l[2 * h + 1], s[h][k][3] * l[2 * h + 1]) : 0;
            asm volatile("and.b32 %0, %4, %6; and.b32 %1, %5, %6; and.b32 %2, %4, %7; and.b32 %3, %5, %7;"
                : "=&r"(p[h][ia]), "=&r"(p[h][ia + 1]), "=&r"(p[h][ib]), "=&r"(p[h][ib + 1]) : "r"(x), "r"(y), "r"(ma), "r"(~ma));
        }
}
__device__ __forceinline__ void attn_pv(float (&o)[64], const uint32_t (&p)[20], uint32_t sv) {
    const uint64_t dx = mkdesc(sv, 128, 1024, 0), dm = mkdesc(sv + 16384, 128, 256, 0);
    wg_fence();
#pragma unroll
    for (int ks = 0; ks < 5; ks++) wgmma_v128(o, p[4 * ks], p[4 * ks + 1], p[4 * ks + 2], p[4 * ks + 3], ks < 4 ? dx + ks * 16 : dm, ks);
    wg_commit();
}
__device__ __forceinline__ void attn_stage(const float (&o)[64], uint32_t dst) {
#pragma unroll
    for (int u = 0; u < 16; u += 2)
        stsm4(dst + (u >> 3) * 8192 + (u & 7) * 128, pack_bf16(o[4 * u], o[4 * u + 1]), pack_bf16(o[4 * u + 2], o[4 * u + 3]),
              pack_bf16(o[4 * u + 4], o[4 * u + 5]), pack_bf16(o[4 * u + 6], o[4 * u + 7]));
}

template <int BN, int NKB, bool BLOCKED_A>
__device__ __forceinline__ void mainloop(float (&acc)[BN / 2], uint32_t sb, int wgi, uint32_t full, uint32_t empty, int& it, bool elect) {
#pragma unroll
    for (int j = 0; j < BN / 2; j++) acc[j] = 0.f;
#pragma unroll 1
    for (int k4 = 0; k4 < NKB; k4 += 4) {
#pragma unroll
        for (int st = 0; st < 4; st++, it++) {
            mbar_wait_long(full + 8 * st, (it >> 2) & 1);
            const uint64_t da = BLOCKED_A ? mkdesc(sb + st * G_STAGE + wgi * 8192, 128, 1024, 0) : mkdesc(sb + st * G_STAGE + wgi * 8192, 16, 1024, 1);
            const uint64_t db = mkdesc(sb + st * G_STAGE + 16384, 8192, 1024, 1);
            wg_fence();
#pragma unroll
            for (int k = 0; k < 4; k++) {
                if constexpr (BN == 256) wgmma256(acc, da + k * (BLOCKED_A ? 16 : 2), db + k * 128, 1);
                else wgmma128(acc, da + k * (BLOCKED_A ? 16 : 2), db + k * 128, 1);
            }
            wg_commit();
            if (k4 | st) {
                wg_wait<1>();
                if (elect) mbar_arrive(empty + 8 * ((st + 3) & 3));
            }
        }
    }
    wg_wait<0>();
    if (elect) mbar_arrive(empty + 8 * 3);
}

__device__ __forceinline__ uint32_t n6_a(int st) { return st < 4 ? st * G_STAGE : (2 * st - 8) * G_STAGE + 32768; }
__device__ __forceinline__ uint32_t n6_b(int st) { return st < 4 ? st * G_STAGE + 16384 : (2 * st - 7) * G_STAGE + 32768; }
__device__ __forceinline__ uint32_t n6_bar(int st) { return st < 4 ? 8 * st : 96 + 8 * st; }
__device__ __forceinline__ void mainloop6(float (&acc)[64], uint32_t sb, int wgi, uint32_t full, uint32_t empty, int& it, bool elect) {
#pragma unroll
    for (int j = 0; j < 64; j++) acc[j] = 0.f;
    int st = 0, prev = 0, r = 0;
#pragma unroll 1
    for (int kb = 0; kb < 64; kb++) {
        mbar_wait_long(full + n6_bar(st), ((st < 4 ? it >> 2 : 0) + r) & 1);
        const uint64_t da = mkdesc(sb + n6_a(st) + wgi * 8192, 128, 1024, 0), db = mkdesc(sb + n6_b(st), 8192, 1024, 1);
        wg_fence();
#pragma unroll
        for (int k = 0; k < 4; k++) wgmma128(acc, da + k * 16, db + k * 128, 1);
        wg_commit();
        if (kb) {
            wg_wait<1>();
            if (elect) mbar_arrive(empty + n6_bar(prev));
        }
        prev = st;
        if (++st == 6) { st = 0; r++; }
    }
    wg_wait<0>();
    if (elect) mbar_arrive(empty + 8 * 3);
    it += 44;
}

template <int BN>
__device__ __forceinline__ void o_item(uint32_t sb, int wgi, int wi, int lane, uint32_t full, uint32_t empty, int& it, const CUtensorMap* mout,
                                       int row0, int col0, uint32_t stgpar) {
    float acc[BN / 2];
    if constexpr (BN == 256) mainloop<BN, 64, true>(acc, sb, wgi, full, empty, it, lane == 0);
    else mainloop6(acc, sb, wgi, full, empty, it, lane == 0);
    ST((row0 >> 4) + (col0 / BN), wgi * 4 + wi, 10);
    mbar_wait(full + 104, stgpar);
    const uint32_t stg = sb + G_STG + (wgi * 4 + wi) * 4096;
    const int r = lane & 15, cu = lane >> 4;
#pragma unroll
    for (int hf = 0; hf < BN / 128; hf++) {
        if (elect()) asm volatile("cp.async.bulk.wait_group.read 0;" ::: "memory");
        __syncwarp();
#pragma unroll
        for (int j = 0; j < 8; j++) {
            const float* a = acc + hf * 64 + j * 8;
            stsm4(stg + (j >> 2) * 2048 + r * 128 + ((((j & 3) * 2 + cu) ^ (r & 7)) << 4),
                  pack_bf16(a[0], a[1]), pack_bf16(a[2], a[3]), pack_bf16(a[4], a[5]), pack_bf16(a[6], a[7]));
        }
        asm volatile("fence.proxy.async.shared::cta;" ::: "memory");
        __syncwarp();
        if (elect()) {
            tma2d_store(mout, stg, col0 + hf * 128, row0 + wgi * 64 + wi * 16);
            tma2d_store(mout, stg + 2048, col0 + hf * 128 + 64, row0 + wgi * 64 + wi * 16);
            asm volatile("cp.async.bulk.commit_group;" ::: "memory");
        }
    }
}

constexpr int S4_KD = 32768;
constexpr int S4_CH = 2 * G_STAGE;
constexpr int S4_HALF = 2304;
constexpr int S4_WD = 2 * S4_HALF;
constexpr int S4_T2 = S4_WD + 2304;
constexpr int S4_T3 = S4_T2 + 1024;
constexpr int S4_STRIDE = S4_T3 + 640 + 16;
__device__ __forceinline__ uint32_t addz(uint32_t x, uint32_t z) { uint32_t r; asm volatile("add.u32 %0, %1, %2;" : "=r"(r) : "r"(x), "r"(z)); return r; }
__device__ __forceinline__ uint32_t lds16(uint32_t a) { uint32_t v; asm volatile("ld.shared.u16 %0, [%1];" : "=r"(v) : "r"(a) : "memory"); return v; }
__device__ __forceinline__ uint32_t ldsu(uint32_t a) { return __float_as_uint(lds32(a)); }

template <int E0, int NE, int KP>
__device__ __forceinline__ void s4_windows(float (&acc)[8][2][4], uint32_t ut, uint32_t tw, int rho, int w, int lane, uint32_t z) {
    const int gt = (lane >> 2) - 2 * (lane & 3), p0 = rho == 16 ? -3 : -2, c = (lane >> 3) + p0;
    uint32_t band[2][4], ta[NE][4];
    {
        const uint64_t ones = ((uint64_t)((2u << 2 * w) - 1) << 32) >> (8 * p0 + 24 - gt + rho + w);
        uint32_t f[5];
#pragma unroll
        for (int m = 0; m < 5; m++) f[m] = ((((uint32_t)(ones >> (8 * m)) & 3) * 0x8001u) & 0x10001u) * 0x3F80u;
#pragma unroll
        for (int j = 0; j < 2; j++) { band[j][0] = f[2 * j + 1]; band[j][1] = addz(f[2 * j], z); band[j][2] = f[2 * j + 2]; band[j][3] = addz(f[2 * j + 1], z); }
    }
#pragma unroll
    for (int e = 0; e < NE; e++)
        asm volatile("ld.shared.u32 %0, [%4]; ld.shared.u32 %1, [%4+%5]; ld.volatile.shared.u32 %2, [%4+%6]; ld.volatile.shared.u32 %3, [%4];"
            : "=r"(ta[e][0]), "=r"(ta[e][1]), "=r"(ta[e][2]), "=r"(ta[e][3]) : "r"(tw + 16 * (E0 + e) * KP), "n"(8 * KP), "n"(-8 * KP) : "memory");
    const uint32_t ua = ut + (c & 1) * S4_HALF + (16 + (lane & 7) + (c >> 1)) * 16;
#pragma unroll
    for (int J = 0; J < 8 - E0; J++) {
        uint32_t u0[4], u1[4];
        ldsm4(u0, ua + J * 256); ldsm4(u1, ua + J * 256 + 128);
        float s0[4], s1[4];
        mma16z(s0, band[0], u0[0], u0[1]); mma16z(s1, band[0], u1[0], u1[1]);
        mma16(s0, band[1], u0[2], u0[3]); mma16(s1, band[1], u1[2], u1[3]);
        const uint32_t b00 = pack_bf16(s0[0], s0[1]), b01 = pack_bf16(s1[0], s1[1]), b10 = pack_bf16(s0[2], s0[3]), b11 = pack_bf16(s1[2], s1[3]);
#pragma unroll
        for (int e = 0; e < NE; e++)
            if (J + E0 + e < 8) { mma16(acc[J + E0 + e][0], ta[e], b00, b01); mma16(acc[J + E0 + e][1], ta[e], b10, b11); }
    }
}
template <int D0, int D1>
__device__ __forceinline__ void s4_dense(float (&acc)[8][2][4], uint32_t ua, const uint32_t (&b0)[4], const uint32_t (&b1)[4]) {
#pragma unroll
    for (int J = 0; J < 8 - D0; J++) {
        uint32_t a[4];
        ldsm4(a, ua + J * 256);
        mma16(acc[J + D0][0], a, b0[0], b0[1]); mma16(acc[J + D0][1], a, b0[2], b0[3]);
        if (J + D1 < 8) { mma16(acc[J + D1][0], a, b1[0], b1[1]); mma16(acc[J + D1][1], a, b1[2], b1[3]); }
    }
}
__device__ __forceinline__ void s4_words(uint32_t (&b)[4], uint32_t wd) {
    asm volatile("ld.shared.u32 %0, [%4]; ld.shared.u32 %1, [%4+-32]; ld.shared.u32 %2, [%4+32]; ld.volatile.shared.u32 %3, [%4];"
        : "=r"(b[0]), "=r"(b[1]), "=r"(b[2]), "=r"(b[3]) : "r"(wd) : "memory");
}

__device__ __forceinline__ void s4_item(uint32_t sb, int cw, int lane, int item, const bf16* __restrict__ dsk, uint32_t empty, const CUtensorMap* my, uint32_t stgpar,
                                        bf16* __restrict__ out, uint32_t nbar, uint32_t npar, uint32_t nslot) {
    const int gt = (lane >> 2) - 2 * (lane & 3);
    const uint32_t ch = sb + S4_CH + cw * S4_STRIDE, kd = sb + S4_KD + cw * 1536;
    const __nv_bfloat162 dk = __bfloat162bfloat162(dsk[item * 8 + cw]);
    ST(item, cw, 0);
    asm volatile("st.shared.v4.u32 [%0], {%1,%1,%1,%1};" ::"r"(ch + (lane >> 4) * S4_HALF + (lane & 15) * 16), "r"(0) : "memory");
    const uint32_t tch = sb + S4_CH + (lane & 7) * S4_STRIDE + ((lane >> 3) & 1) * S4_HALF + (16 + 16 * cw + (lane >> 4)) * 16;
#pragma unroll
    for (int i = 0; i < 8; i++) {
        uint32_t x[4];
        ldsm4t(x, sb + cw * 4096 + i * 512 + lane * 16);
        stsm4(tch + i * 32, x[0], x[1], x[2], x[3]);
    }
    const uint32_t k1024 = lds16(kd + 1024);
    {
        auto st4 = [](uint32_t a, uint32_t x, uint32_t y, uint32_t u, uint32_t v) {
            asm volatile("st.shared.v4.u32 [%0], {%1,%2,%3,%4};" ::"r"(a), "r"(x), "r"(y), "r"(u), "r"(v) : "memory");
        };
        const float4 p = lds128(kd + lane * 16);
        const uint32_t p0 = __float_as_uint(p.x), p1 = __float_as_uint(p.y), p2 = __float_as_uint(p.z), p3 = __float_as_uint(p.w);
        const uint32_t pm = lane ? ldsu(kd + lane * 16 - 4) : 0;
        const uint32_t wa = ch + S4_WD + 64 + lane * 32;
        st4(wa, __byte_perm(p0, pm, 0x7610), __byte_perm(p0, 0, 0x1032), __byte_perm(p1, p0, 0x7610), __byte_perm(p1, 0, 0x1032));
        st4(wa + 16, __byte_perm(p2, p1, 0x7610), __byte_perm(p2, 0, 0x1032), __byte_perm(p3, p2, 0x7610), __byte_perm(p3, 0, 0x1032));
        const float2 q = lds64(kd + 512 + lane * 8);
        const uint32_t q0 = __float_as_uint(q.x), q1 = __float_as_uint(q.y), q2 = ldsu(kd + 520 + lane * 8), k255 = ldsu(kd + 508);
        st4(wa + 1024, lane ? __byte_perm(q0, 0, 0x1010) : __byte_perm(q0, k255, 0x7610), __byte_perm(q0, 0, 0x1010), __byte_perm(q0, 0, 0x1032), __byte_perm(q1, q0, 0x7610));
        st4(wa + 1040, __byte_perm(q1, 0, 0x1010), __byte_perm(q1, 0, 0x1010), __byte_perm(q1, 0, 0x1032), __byte_perm(q2, q1, 0x7610));
        const uint32_t k512 = lane == 4 ? lds16(kd + 768) : 0;
        if (lane < 16) st4(ch + S4_WD + (lane < 4 ? 0 : 2048) + lane * 16, k512 * 0x10001u, k512 * 0x10001u, k512 * 0x10001u, k512 << 16);
        const float2 c = lds64(kd + 768 + lane * 8), d = lds64(kd + 760 + lane * 8);
        const uint32_t c0 = __float_as_uint(c.x), c1 = __float_as_uint(c.y), c2 = ldsu(kd + 776 + lane * 8);
        const uint32_t d0 = lane ? __float_as_uint(d.x) : 0, d1 = lane ? __float_as_uint(d.y) : 0, d2 = lane ? c0 : 0;
        st4(ch + S4_T2 + 256 + lane * 16, __byte_perm(c0, d0, 0x7632), __byte_perm(c1, d1, 0x5410), __byte_perm(c1, d1, 0x7632), __byte_perm(c2, d2, 0x5410));
        const uint32_t m = lane == 31 ? 0xFFFF0000u : 0;
        st4(ch + S4_T2 + (lane < 16 ? lane : lane == 31 ? 48 : lane + 33) * 16, c0 & m, (c1 << 16) & m, c1 & m, (c2 << 16) & m);
        const float2 e = lds64(kd + 1024 + lane * 8);
        const uint32_t e0 = __float_as_uint(e.x), e1 = __float_as_uint(e.y), e2 = ldsu(kd + 1032 + lane * 8), em = ldsu(kd + 1020 + lane * 8);
        st4(ch + S4_T3 + 128 + lane * 16, __byte_perm(e0, lane ? em : 0, 0x7632), __byte_perm(e1, lane ? e0 : 0, 0x5410), __byte_perm(e1, e0, 0x7632), __byte_perm(e2, e1, 0x5410));
        if (lane < 8) st4(ch + S4_T3 + lane * 16, 0, 0, 0, 0);
    }
    bar_sync(2, 256);
    ST(item, cw, 1);
    const uint32_t z = ldsu(ch);
    float acc[8][2][4];
#pragma unroll
    for (int j = 0; j < 16; j++) acc[j >> 1][j & 1][0] = acc[j >> 1][j & 1][1] = acc[j >> 1][j & 1][2] = acc[j >> 1][j & 1][3] = 0.f;
#pragma unroll 1
    for (int r = 1; r <= 4; r++) s4_windows<2, 3, 16>(acc, ch, ch + S4_T2 + (gt - 16) * 16 + 4 * r - 4, 4 * r, 2 - (r & 1), lane, z);
    ST(item, cw, 2);
#pragma unroll 1
    for (int r = 1; r <= 2; r++) s4_windows<4, 4, 8>(acc, ch, ch + S4_T3 + (gt - 48) * 8 + 4 * r - 4, 8 * r, 2 + r, lane, z);
    ST(item, cw, 3);
    const uint32_t ua = ch + (lane >> 4) * S4_HALF + (16 + (lane & 15)) * 16, wd = ch + S4_WD + 64 + gt * 4;
#pragma unroll 1
    for (int q = 0; q < 2; q++) {
        uint32_t b0[4], b1[4];
        s4_words(b0, wd + (q + 32) * 64);
#pragma unroll
        for (int j = 0; j < 4; j++) {
            const int x = 16 * q + gt + (j == 1 ? -8 : j == 2 ? 8 : 0) - 3;
            b1[j] = addz(((unsigned)x < 2u ? k1024 : 0u) | ((unsigned)(x - 1) < 2u ? k1024 << 16 : 0u), z);
        }
        s4_dense<2, 4>(acc, ua - q * 16, b0, b1);
    }
    {
        uint32_t b0[4], b1[4], c0[4], c1[4];
        s4_words(b0, wd); s4_words(b1, wd + 1024);
#pragma unroll 1
        for (int q = 0; q < 16; q += 2) {
            s4_words(c0, wd + q * 64 + 64); s4_words(c1, wd + q * 64 + 64 + 1024);
            s4_dense<0, 1>(acc, ua - q * 16, b0, b1);
            s4_words(b0, wd + q * 64 + 128); s4_words(b1, wd + q * 64 + 128 + 1024);
            s4_dense<0, 1>(acc, ua - q * 16 - 16, c0, c1);
            if (q == S4REL && lane == 0) { mbar_arrive(empty); mbar_arrive(empty + 8); }
        }
    }
    ST(item, cw, 4);
    mbar_wait(empty + 72, stgpar);
    if (elect()) asm volatile("cp.async.bulk.wait_group.read 0;" ::: "memory");
    __syncwarp();
#pragma unroll
    for (int I = 0; I < 8; I++) {
        uint32_t u[4];
        ldsm4(u, ua + I * 256);
#pragma unroll
        for (int j = 0; j < 4; j++) {
            const uint32_t y = pack_bf16(acc[I][j >> 1][2 * (j & 1)], acc[I][j >> 1][2 * (j & 1) + 1]);
            const __nv_bfloat162 r = __hadd2_rn(*(const __nv_bfloat162*)&y, __hmul2_rn(*(const __nv_bfloat162*)&u[j], dk));
            u[j] = *(const uint32_t*)&r;
        }
        stsm4(ua + I * 256, u[0], u[1], u[2], u[3]);
    }
    bar_sync(2, 256);
    uint32_t y[8][4];
#pragma unroll
    for (int i = 0; i < 8; i++) ldsm4t(y[i], tch + i * 32);
    if (cw < S4DIR && mbar_test(nbar, npar) && ldsu(nslot) == (IT_END << 16)) {
        uint32_t* const dst = (uint32_t*)(out + (size_t)(cw * 256 + (lane >> 2)) * (2 * DM) + DM + item * 8) + (lane & 3);
#pragma unroll
        for (int i = 0; i < 32; i++) dst[i * 8 * DM] = y[i >> 2][i & 3];
        return;
    }
#pragma unroll
    for (int i = 0; i < 8; i++) stsm4(sb + G_STG + cw * 4096 + i * 512 + lane * 16, y[i][0], y[i][1], y[i][2], y[i][3]);
    asm volatile("fence.proxy.async.shared::cta;" ::: "memory");
    __syncwarp();
    if (elect()) {
        mbar_arrive(empty + 16); mbar_arrive(empty + 24);
        tma2d_store(my, sb + G_STG + cw * 4096, DM + item * 8, cw * 256);
        asm volatile("cp.async.bulk.commit_group;" ::: "memory");
    }
    ST(item, cw, 5);
}

struct Maps { CUtensorMap m[13]; };
__global__ void __launch_bounds__(384, 1)
worker_kernel(const __grid_constant__ Maps M, const bf16* __restrict__ dsk, bf16* __restrict__ out) {
    const CUtensorMap &mx = M.m[0], &mq = M.m[1], &mo = M.m[4], &mout = M.m[5], &mu = M.m[6], &my = M.m[7];
    extern __shared__ unsigned char smem_raw[];
    const uint32_t sb = (smem_u32(smem_raw) + 1023) & ~1023u;
    const uint32_t full = sb + G_BAR, empty = full + 32, ifull = full + 64, iempty = full + 80, islot = full + 96, stgbar = full + 104, sigbar = full + 112, sigslot = full + 120;
    const int tid = threadIdx.x, wg = tid >> 7, lane = tid & 31;
    int q0 = blockIdx.x;
    const int nfirst = min(32, (int)gridDim.x - 96), wide0 = q0 - ((int)gridDim.x - N_LATE);
    if (tid == 0 && q0 >= nfirst && wide0 < 0) q0 = nfirst + atomicAdd(g_ctr + C_NEXT, 1);
    if ((tid >> 5) == 1 && elect()) {
#pragma unroll
        for (int i = 0; i < 6; i++) { mbar_init(full + n6_bar(i), 1); mbar_init(empty + n6_bar(i), 8); }
#pragma unroll
        for (int i = 0; i < 2; i++) { mbar_init(ifull + 8 * i, 1); mbar_init(iempty + 8 * i, 8); }
        mbar_init(sigbar, 8); mbar_init(stgbar, 1);
        asm volatile("fence.mbarrier_init.release.cluster;" ::: "memory");
    }
    if ((tid >> 5) == 2 && elect()) {
#pragma unroll
        for (int i = 0; i < 13; i++) asm volatile("prefetch.tensormap [%0];" ::"l"(&M.m[i]) : "memory");
    }
    __syncthreads();
    if (wg == 0) {
        reg_dec<40>();
        if (tid >= 32 && tid < 64) {
            for (int n = 0;; n++) {
                mbar_wait_long(sigbar, n & 1);
                int item; asm volatile("ld.shared.u32 %0, [%1];" : "=r"(item) : "r"(sigslot + 4 * (n & 1)) : "memory");
                const int type = item >> 16, b = (item >> 8) & 255, i = item & 255;
                if (type == IT_END) break;
                if (type == IT_QA) {
                    if (elect()) {
#pragma unroll
                        for (int j = 0; j < 8; j++) {
                            const uint32_t src = sb + (j >= 4 ? G_STG + (j & 1) * 16384 : 3 * G_STAGE + (j & 1) * 20480) + ((j >> 1) & 1) * 8192;
                            asm volatile("cp.async.bulk.global.shared::cta.bulk_group [%0], [%1], 8192;"
                                ::"l"(g_ox + (size_t)(b * 64 + i * 4 + ((j >> 1) ^ 2)) * 8192 + (j & 1) * 4096), "r"(src) : "memory");
                            if ((j & 3) == 3) asm volatile("cp.async.bulk.commit_group;" ::: "memory");
                        }
                        asm volatile("cp.async.bulk.wait_group.read 1;" ::: "memory");
                        asm volatile("mbarrier.arrive.shared.b64 _, [%0], 8;" ::"r"(empty + 24) : "memory");
                        asm volatile("cp.async.bulk.wait_group 0;" ::: "memory");
                        mbar_arrive(stgbar);
                        asm volatile("fence.proxy.async.global;" ::: "memory");
                    }
                    __syncwarp();
                }
                if (type == IT_KV) { if (lane < 6) red_release(g_kvf + ((i & 15) * 6 + lane) * 16 + b, 1); }
                else if (lane == 0) red_release(g_ctr + C_QA_DONE + b, 1 << i);
            }
        } else if (tid < 32) {
            int it = 0;
            bool tables = false;
            if (!KVN) asm volatile("griddepcontrol.wait;" ::: "memory");
            for (int n = 0;; n++) {
                int item = 0;
                if (lane == 0) {
                    if (n) q0 = nfirst + atomicAdd(g_ctr + C_NEXT, 1);
                    item = n == 0 && wide0 >= 0 ? late_item(wide0) : queue_item(q0);
                }
                item = __shfl_sync(0xffffffffu, item, 0);
                mbar_wait(iempty + 8 * (n & 1), ((n >> 1) & 1) ^ 1);
                if (lane == 0) {
                    asm volatile("st.shared.u32 [%0], %1;" ::"r"(islot + 4 * (n & 1)), "r"(item) : "memory");
                    mbar_arrive(ifull + 8 * (n & 1));
                }
                const int type = item >> 16, b = (item >> 8) & 255, i = item & 255;
                bool ready = false;
                if (type == IT_QA || type == IT_KV) {
                    const CUtensorMap* mw = &mq + (type == IT_QA ? 0 : 1 + (i >> 4));
#pragma unroll 1
                    for (int kb = 0; kb < 16; kb++, it++) {
                        const int st = it & 3;
                        mbar_wait(empty + 8 * st, ((it >> 2) & 1) ^ 1);
                        if (elect()) {
                            mbar_expect(full + 8 * st, G_STAGE);
                            tma2d(sb + st * G_STAGE, &mx, kb * 64, b * 128, full + 8 * st);
                            tma3d(sb + st * G_STAGE + 16384, mw, 0, kb * 64, (i & 15) * 4, full + 8 * st);
                        }
                        if (type == IT_QA && kb == 3) ready = __all_sync(0xffffffffu, ld_acq(g_ctr + C_CHAIN + b) >= 96);
                        if (ready && kb < 11 && elect()) {
                            const size_t sh = (b * 4 + ((kb - 3) & 3)) * NH + i * 2;
                            asm volatile("cp.async.bulk.prefetch.L2.global [%0], 16384;" ::"l"((kb >= 7 ? g_vx : g_kx) + sh * 4096) : "memory");
                            asm volatile("cp.async.bulk.prefetch.L2.global [%0], 4096;" ::"l"((kb >= 7 ? g_vm : g_km) + sh * 1024) : "memory");
                        }
                    }
                }
                if (type == IT_QA) {
                    if (b == 15) asm volatile("griddepcontrol.wait;" ::: "memory");
                    else if (!ready) wait_ctr(g_ctr + C_CHAIN + b, 96);
                    tables = true;
                    asm volatile("fence.proxy.async.global;" ::: "memory");
#pragma unroll 1
                    for (int st = 0; st < 4; st++, it++) {
                        mbar_wait(empty + 8 * st, ((it >> 2) & 1) ^ 1);
                        if (elect()) {
                            mbar_expect(full + 8 * st, 4 * 10240);
#pragma unroll
                            for (int j = 0; j < 4; j++)
                                tma3d(sb + st * G_STAGE + (j >> 1) * 20480 + (j & 1) * 16384, &M.m[8 + (st >> 1) + (j & 1) * 2], 0, b * 4 + (j & 2),
                                      (i * 2 + (st & 1)) * 16, full + 8 * st);
                        }
                    }
                } else if (type == IT_O) {
                    const bool wide = b < O_WIDE;
                    const CUtensorMap* mw = wide ? &mo : &M.m[12];
                    int done = 0;
                    const int ns = wide ? 4 : 6;
#pragma unroll 1
                    for (int kb = 0, st = 0, r = 0; kb < 64; kb++) {
                        const uint32_t bo = n6_bar(st);
                        mbar_wait(empty + bo, (((st < 4 ? it >> 2 : 0) + r) & 1) ^ 1);
                        if (elect()) {
                            mbar_expect(full + bo, wide ? G_STAGE : 32768);
                            tma3d(sb + n6_b(st), mw, 0, kb * 64, wide ? i * 4 : i * 2, full + bo);
                        }
                        if (!(done >> (kb >> 2) & 1)) {
#pragma unroll 1
                            for (int sp = 0; sp < (1 << 20) && !((done = __shfl_sync(0xffffffffu, ld_acq(g_ctr + C_QA_DONE + b), 0)) >> (kb >> 2) & 1); sp++)
                                __nanosleep(64);
                            asm volatile("fence.proxy.async.global;" ::: "memory");
                        }
                        if (elect()) bulk_load(sb + n6_a(st), g_ox + (size_t)(b * 64 + kb) * 8192, 16384, full + bo);
                        if (++st == ns) { st = 0; r++; }
                    }
                    it += wide ? 64 : 44;
                } else if (type == IT_S4) {
                    mbar_wait(empty, ((it >> 2) & 1) ^ 1);
                    if (elect()) {
                        mbar_expect(full, 32768 + 12288);
#pragma unroll
                        for (int j = 0; j < 8; j++) tma2d(sb + j * 4096, &mu, i * 8, j * 256, full);
                    }
                    if (!tables) { wait_ctr(g_ctr + C_CHAIN, 96); asm volatile("fence.proxy.async.global;" ::: "memory"); }
                    tables = true;
                    if (elect()) bulk_load(sb + S4_KD, g_kd + i * 8 * 768, 12288, full);
#pragma unroll 1
                    for (int st = 1; st < 4; st++) { mbar_wait(empty + 8 * st, ((it >> 2) & 1) ^ 1); if (lane == 0) mbar_arrive(full + 8 * st); }
                    it += 4;
                    mbar_wait_long(empty, ((it >> 2) & 1) ^ 1);
                }
                if (item >> 16 == IT_END) break;
            }
            asm volatile("griddepcontrol.wait;" ::: "memory");
        }
    } else {
        reg_inc<232>();
        const int wu = __shfl_sync(0xffffffffu, tid >> 5, 0);
        const int wgi = (wu >> 2) - 1, wi = wu & 3;
        int it = 0, nqa = 0, nsig = 0, n = 0, item;
        auto next_item = [&]() {
            mbar_wait_long(ifull + 8 * (n & 1), (n >> 1) & 1);
            asm volatile("ld.shared.u32 %0, [%1];" : "=r"(item) : "r"(islot + 4 * (n & 1)) : "memory");
            __syncwarp();
            if (lane == 0) mbar_arrive(iempty + 8 * (n & 1));
        };
        auto signal = [&](int what) {
            if (tid == 128) asm volatile("st.shared.u32 [%0], %1;" ::"r"(sigslot + 4 * (nsig & 1)), "r"(what) : "memory");
            __syncwarp();
            if (lane == 0) mbar_arrive(sigbar);
            nsig++;
        };
        next_item();
        if (item >> 16 == IT_KV) {
            float acc[128];
            uint32_t pk[64];
            uint32_t* dst = nullptr;
            int prev = 0;
            do {
                WLOG(0);
#pragma unroll
                for (int kb = 0; kb < 16; kb++, it++) {
                    const int st = kb & 3;
                    mbar_wait(full + 8 * st, (it >> 2) & 1);
                    const uint64_t da = mkdesc(sb + st * G_STAGE + wgi * 8192, 16, 1024, 1);
                    const uint64_t db = mkdesc(sb + st * G_STAGE + 16384, 8192, 1024, 1);
                    wg_fence();
#pragma unroll
                    for (int k = 0; k < 4; k++) wgmma256(acc, da + k * 2, db + k * 128, kb | k);
                    wg_commit();
                    if (n <= KVI) {
                        if (kb < KVF && dst) {
#pragma unroll
                            for (int j = kb * (64 / KVF); j < (kb + 1) * (64 / KVF); j++) st_out(dst + (j >> 1) * 128 + (j & 1) * 32, pk[j]);
                            if (kb == KVF - 1) signal(prev);
                        }
                    } else if (kb < KVS) {
#pragma unroll
                        for (int j = kb * (64 / KVS); j < (kb + 1) * (64 / KVS); j++) st_out(dst + (j >> 1) * 128 + (j & 1) * 32, pk[j]);
                        if (kb == KVS - 1) signal(prev);
                    }
                    if (kb > 0) {
                        wg_wait<1>();
                        if (lane == 0) mbar_arrive(empty + 8 * ((kb - 1) & 3));
                    }
                }
                wg_wait<0>();
                if (lane == 0) mbar_arrive(empty + 8 * 3);
#pragma unroll
                for (int j = 0; j < 64; j++) pk[j] = pack_bf16(acc[2 * j], acc[2 * j + 1]);
                const int row = ((item >> 8) & 255) * 128 + wgi * 64 + wi * 16, nt = item & 255;
                dst = (uint32_t*)(nt < 16 ? g_kx : g_vx) + (size_t)((row >> 5) * 512 + (nt & 15) * 32) * 128 + (row & 31) * 4 + lane;
                prev = item;
                WLOG(1);
                n++;
                next_item();
            } while (item >> 16 == IT_KV);
            if (dst) {
#pragma unroll
                for (int j = 0; j < 64; j++) dst[(j >> 1) * 128 + (j & 1) * 32] = pk[j];
                signal(prev);
            }
        }
        for (;; n++, next_item()) {
            const int type = item >> 16, b = (item >> 8) & 255, i = item & 255;
            const int lane = (tid & 31) + (item >> 24), wgi = (wu >> 2) - 1 + __shfl_sync(0xffffffffu, item >> 24, 0), wi = wu & 3;
            WLOG(0);
            if (type == IT_QA) {
                float acc[128];
                ST(sid, cw, 0);
                ST(sid, cw, 1);
                mainloop<256, 16, false>(acc, sb, wgi, full, empty, it, lane == 0);
                ST(sid, cw, 2);
                uint32_t q0[32], q1[32];
#pragma unroll
                for (int j = 0; j < 32; j++) q0[j] = pack_bf16(acc[2 * j], acc[2 * j + 1]);
                const uint32_t par = (it >> 2) & 1, so = sb + wgi * 20480;
                float sx[2][32] = {}, sm[2][8] = {};
                uint32_t p[2][20];
                mbar_wait_long(full, par);
                ST(sid, cw, 3);
                if (PING && wgi == 0) bar_sync(5, 256);
                attn_scores(sx[0], sm[0], q0, so);
                ST(sid, cw, 7);
#pragma unroll
                for (int j = 0; j < 32; j++) asm volatile("cvt.rn.bf16x2.f32 %0, %1, %2;" : "=r"(q1[j]) : "f"(acc[65 + 2 * j]), "f"(acc[64 + 2 * j]));
                mbar_wait(full + 8, par);
                attn_scores(sx[1], sm[1], q1, so + G_STAGE);
                if (PING && wgi == 1) bar_arrive(5, 256);
                if (elect()) asm volatile("cp.async.bulk.wait_group.read 0;" ::: "memory");
                mbar_wait(stgbar, (nqa++ & 1) ^ 1);
                bar_sync(3 + wgi, 128);
                float o0[64] = {}, o1[64] = {};
                wg_wait<0>();
                ST(sid, cw, 9);
                if (lane == 0) { mbar_arrive(empty); mbar_arrive(empty + 8); }
                if (wi & 1) attn_softmax<true>(p, sx, sm, wi >= 2, lane);
                else attn_softmax<false>(p, sx, sm, wi >= 2, lane);
                ST(sid, cw, 10);
                mbar_wait(full + 16, par);
                attn_pv(o0, p[0], so + 2 * G_STAGE);
                mbar_wait(full + 24, par);
                attn_pv(o1, p[1], so + 3 * G_STAGE);
                wg_wait<1>();
                if (lane == 0) mbar_arrive(empty + 16);
                ST(sid, cw, 5);
                const uint32_t da = (wi * 2 + ((lane >> 3) & 1)) * 1024 + (lane >> 4) * 128 + (lane & 7) * 16;
                attn_stage(o0, sb + G_STG + wgi * 16384 + da);
                wg_wait<0>();
                bar_sync(3 + wgi, 128);
                attn_stage(o1, so + 3 * G_STAGE + da);
                asm volatile("fence.proxy.async.shared::cta;" ::: "memory");
                ST(sid, cw, 6);
                signal(item);
                it += 4;
            } else if (type == IT_O) {
                ST(b * 8 + i, wgi * 4 + wi, 8);
                mbar_wait_long(full, (it >> 2) & 1);
                ST(b * 8 + i, wgi * 4 + wi, 9);
                if (b < O_WIDE) o_item<256>(sb, wgi, wi, lane, full, empty, it, &mout, b * 128, i * 256, (nqa & 1) ^ 1);
                else o_item<128>(sb, wgi, wi, lane, full, empty, it, &mout, b * 128, i * 128, (nqa & 1) ^ 1);
            } else if (type == IT_S4) {
                mbar_wait_long(full, (it >> 2) & 1);
                mbar_wait(full + 24, (it >> 2) & 1);
                s4_item(sb, wgi * 4 + wi, lane, i, dsk, empty, &my, (nqa & 1) ^ 1, out, ifull + 8 * ((n + 1) & 1), ((n + 1) >> 1) & 1, islot + 4 * ((n + 1) & 1));
                it += 4;
            } else break;
            WLOG(1);
        }
        bar_sync(2, 256);
        signal(item);
        if (elect()) asm volatile("cp.async.bulk.wait_group 0;" ::: "memory");
    }
}

typedef CUresult (*EncodeFn)(CUtensorMap*, CUtensorMapDataType, cuuint32_t, void*, const cuuint64_t*, const cuuint64_t*, const cuuint32_t*,
                             const cuuint32_t*, CUtensorMapInterleave, CUtensorMapSwizzle, CUtensorMapL2promotion, CUtensorMapFloatOOBfill);
static EncodeFn get_encode() {
    void* fn = nullptr; cudaDriverEntryPointQueryResult st;
    cudaGetDriverEntryPoint("cuTensorMapEncodeTiled", &fn, cudaEnableDefault, &st);
    return (EncodeFn)fn;
}
static void map_act(EncodeFn enc, CUtensorMap* m, const void* p, int rows, int cols, int boxr) {
    cuuint64_t dim[2] = {(cuuint64_t)cols, (cuuint64_t)rows}, str[1] = {(cuuint64_t)cols * 2};
    cuuint32_t box[2] = {64, (cuuint32_t)boxr}, es[2] = {1, 1};
    enc(m, CU_TENSOR_MAP_DATA_TYPE_BFLOAT16, 2, (void*)p, dim, str, box, es, CU_TENSOR_MAP_INTERLEAVE_NONE, CU_TENSOR_MAP_SWIZZLE_128B,
        CU_TENSOR_MAP_L2_PROMOTION_L2_128B, CU_TENSOR_MAP_FLOAT_OOB_FILL_NONE);
}
static void map_w(EncodeFn enc, CUtensorMap* m, const void* p, int k, int n, int groups = 4) {
    cuuint64_t dim[3] = {64, (cuuint64_t)k, (cuuint64_t)n / 64}, str[2] = {(cuuint64_t)n * 2, 128};
    cuuint32_t box[3] = {64, 64, (cuuint32_t)groups}, es[3] = {1, 1, 1};
    enc(m, CU_TENSOR_MAP_DATA_TYPE_BFLOAT16, 3, (void*)p, dim, str, box, es, CU_TENSOR_MAP_INTERLEAVE_NONE, CU_TENSOR_MAP_SWIZZLE_128B,
        CU_TENSOR_MAP_L2_PROMOTION_L2_256B, CU_TENSOR_MAP_FLOAT_OOB_FILL_NONE);
}

static void map_kv(EncodeFn enc, CUtensorMap* m, void* p, int n) {
    cuuint64_t dim[3] = {(cuuint64_t)n, NSEG, 512}, str[2] = {(cuuint64_t)n * 1024, (cuuint64_t)n * 2};
    cuuint32_t box[3] = {(cuuint32_t)n, 2, 16}, es[3] = {1, 1, 1};
    enc(m, CU_TENSOR_MAP_DATA_TYPE_BFLOAT16, 3, p, dim, str, box, es, CU_TENSOR_MAP_INTERLEAVE_NONE, CU_TENSOR_MAP_SWIZZLE_NONE,
        CU_TENSOR_MAP_L2_PROMOTION_NONE, CU_TENSOR_MAP_FLOAT_OOB_FILL_NONE);
}
static void map_box(EncodeFn enc, CUtensorMap* m, const void* p, int rows, int ld, int boxc, int boxr, CUtensorMapSwizzle sw,
                    CUtensorMapL2promotion promo = CU_TENSOR_MAP_L2_PROMOTION_NONE) {
    cuuint64_t dim[2] = {(cuuint64_t)ld, (cuuint64_t)rows}, str[1] = {(cuuint64_t)ld * 2};
    cuuint32_t box[2] = {(cuuint32_t)boxc, (cuuint32_t)boxr}, es[2] = {1, 1};
    enc(m, CU_TENSOR_MAP_DATA_TYPE_BFLOAT16, 2, (void*)p, dim, str, box, es, CU_TENSOR_MAP_INTERLEAVE_NONE, sw,
        promo, CU_TENSOR_MAP_FLOAT_OOB_FILL_NONE);
}

extern "C" void kernel_launch(void* const* d_in, const int* in_sizes, int n_in, void* d_out, int out_size) {
    const bf16* x = (const bf16*)d_in[0];
    const bf16* mem0 = (const bf16*)d_in[1];
    const bf16 *Wq = (const bf16*)d_in[2], *Wk = (const bf16*)d_in[3], *Wv = (const bf16*)d_in[4], *Wo = (const bf16*)d_in[5];
    static EncodeFn enc = nullptr;
    static int nsm = 0;
    static void* kv[4];
    if (!enc) {
        enc = get_encode();
        cudaGetSymbolAddress(&kv[0], g_kx); cudaGetSymbolAddress(&kv[1], g_vx); cudaGetSymbolAddress(&kv[2], g_km); cudaGetSymbolAddress(&kv[3], g_vm);
        cudaDeviceGetAttribute(&nsm, cudaDevAttrMultiProcessorCount, 0);
        cudaFuncSetAttribute(chain_kernel, cudaFuncAttributeMaxDynamicSharedMemorySize, CH_SMEM);
        cudaFuncSetAttribute(worker_kernel, cudaFuncAttributeMaxDynamicSharedMemorySize, G_SMEM);
    }
    Maps M;
    CUtensorMap &mx = M.m[0], &mq = M.m[1], &mk = M.m[2], &mv = M.m[3], &mo = M.m[4], &mout = M.m[5], &mu = M.m[6], &my = M.m[7];
    map_act(enc, &mx, x, S_LEN, DM, 128);
    map_w(enc, &mq, Wq, DM, HD); map_w(enc, &mk, Wk, DM, HD); map_w(enc, &mv, Wv, DM, HD); map_w(enc, &mo, Wo, HD, DM);
    map_w(enc, &M.m[12], Wo, HD, DM, 2);
    map_box(enc, &mout, d_out, S_LEN, 2 * DM, 64, 16, CU_TENSOR_MAP_SWIZZLE_128B);
    map_box(enc, &mu, d_in[7], S_LEN, DM, 8, 256, CU_TENSOR_MAP_SWIZZLE_NONE, (CUtensorMapL2promotion)PROMU);
    map_box(enc, &my, d_out, S_LEN, 2 * DM, 8, 256, CU_TENSOR_MAP_SWIZZLE_NONE);
    for (int i = 0; i < 4; i++) map_kv(enc, &M.m[8 + i], kv[i], i < 2 ? 256 : 64);
    CUtensorMap cq, ck, cv, co;
    map_box(enc, &cq, Wq, DM, HD, 32, 32, CU_TENSOR_MAP_SWIZZLE_64B, (CUtensorMapL2promotion)PROMO); map_box(enc, &ck, Wk, DM, HD, 32, 32, CU_TENSOR_MAP_SWIZZLE_64B, (CUtensorMapL2promotion)PROMO);
    map_box(enc, &cv, Wv, DM, HD, 32, 32, CU_TENSOR_MAP_SWIZZLE_64B, (CUtensorMapL2promotion)PROMO); map_box(enc, &co, Wo, HD, DM, 32, 16, CU_TENSOR_MAP_SWIZZLE_64B, (CUtensorMapL2promotion)PROMO);
    S4Params P = {(const bf16*)d_in[8], (const bf16*)d_in[9], (const bf16*)d_in[10], (const bf16*)d_in[11],
                  (const bf16*)d_in[12], (const bf16*)d_in[13], (const bf16*)d_in[14], (const bf16*)d_in[15]};
    int aware = 1;
    cudaLaunchAttribute at[1];
    at[0].id = cudaLaunchAttributeProgrammaticStreamSerialization;
    at[0].val.programmaticStreamSerializationAllowed = 1;
    cudaLaunchConfig_t cfg = {};
    cfg.stream = cudaStreamPerThread;
    cfg.gridDim = dim3(96); cfg.blockDim = dim3(CH_THREADS); cfg.dynamicSmemBytes = CH_SMEM;
    cudaLaunchKernelEx(&cfg, chain_kernel, cq, ck, cv, co, Wq, Wk, Wv, mem0, P, aware);
    cfg.attrs = at; cfg.numAttrs = 1;
    cfg.gridDim = dim3(nsm); cfg.blockDim = dim3(384); cfg.dynamicSmemBytes = G_SMEM;
    cudaLaunchKernelEx(&cfg, worker_kernel, M, P.dsk, (bf16*)d_out);
}
```

```cpp
#include <cuda.h>
#include <cuda_runtime.h>
#include <cuda_bf16.h>
#include <stdint.h>
#include <stdio.h>
#include <string.h>

typedef __nv_bfloat16 bf16;

constexpr int S_LEN = 2048, DM = 1024, NH = 32, DH = 128, HD = 4096, NSEG = 64;
constexpr uint32_t SENT = 0xFFFFFFFFu;
constexpr int SPIN_LIMIT = 1 << 18;

__device__ __align__(1024) bf16 g_kx[S_LEN * HD];
__device__ __align__(1024) bf16 g_vx[S_LEN * HD];
__device__ __align__(1024) bf16 g_ox[S_LEN * HD];
__device__ __align__(1024) bf16 g_km[NSEG * NH * 8 * DH];
__device__ __align__(1024) bf16 g_vm[NSEG * NH * 8 * DH];
__device__ __align__(1024) bf16 g_kd[DM * 768];
__device__ __align__(1024) char g_ring[2 << 20];
__device__ int g_kvf[96 * 16];
constexpr int C_NEXT = 0, C_CHAIN = 32, C_QA_DONE = 64, N_CTR = 96;
__device__ int g_ctr[N_CTR];

__device__ __forceinline__ uint32_t smem_u32(const void* p) { return (uint32_t)__cvta_generic_to_shared(p); }
__device__ __forceinline__ uint32_t clk() { uint32_t c; asm volatile("mov.u32 %0, %%clock;" : "=r"(c)::"memory"); return c; }
__device__ __forceinline__ uint32_t pack_bf16(float lo, float hi) {
    uint32_t r; asm("cvt.rn.bf16x2.f32 %0, %1, %2;" : "=r"(r) : "f"(hi), "f"(lo)); return r;
}
__device__ __forceinline__ uint32_t movm(uint32_t a) {
    uint32_t d; asm volatile("movmatrix.sync.aligned.m8n8.trans.b16 %0, %1;" : "=r"(d) : "r"(a)); return d;
}
__device__ __forceinline__ void mma16(float (&d)[4], const uint32_t (&a)[4], uint32_t b0, uint32_t b1) {
    asm volatile("mma.sync.aligned.m16n8k16.row.col.f32.bf16.bf16.f32 {%0,%1,%2,%3}, {%4,%5,%6,%7}, {%8,%9}, {%0,%1,%2,%3};"
        : "+f"(d[0]), "+f"(d[1]), "+f"(d[2]), "+f"(d[3]) : "r"(a[0]), "r"(a[1]), "r"(a[2]), "r"(a[3]), "r"(b0), "r"(b1));
}
__device__ __forceinline__ void mma16z(float (&d)[4], const uint32_t (&a)[4], uint32_t b0, uint32_t b1) {
    asm volatile("mma.sync.aligned.m16n8k16.row.col.f32.bf16.bf16.f32 {%0,%1,%2,%3}, {%4,%5,%6,%7}, {%8,%9}, {%10,%10,%10,%10};"
        : "=f"(d[0]), "=f"(d[1]), "=f"(d[2]), "=f"(d[3]) : "r"(a[0]), "r"(a[1]), "r"(a[2]), "r"(a[3]), "r"(b0), "r"(b1), "f"(0.f));
}
__device__ __forceinline__ void mma8z(float (&d)[4], uint32_t a0, uint32_t a1, uint32_t b0) {
    asm volatile("mma.sync.aligned.m16n8k8.row.col.f32.bf16.bf16.f32 {%0,%1,%2,%3}, {%4,%5}, {%6}, {%7,%7,%7,%7};"
        : "=f"(d[0]), "=f"(d[1]), "=f"(d[2]), "=f"(d[3]) : "r"(a0), "r"(a1), "r"(b0), "f"(0.f));
}
__device__ __forceinline__ void ldsm4t(uint32_t (&r)[4], uint32_t addr) {
    asm volatile("ldmatrix.sync.aligned.m8n8.x4.trans.shared.b16 {%0,%1,%2,%3}, [%4];"
        : "=r"(r[0]), "=r"(r[1]), "=r"(r[2]), "=r"(r[3]) : "r"(addr) : "memory");
}
__device__ __forceinline__ void ldsm4(uint32_t (&r)[4], uint32_t addr) {
    asm volatile("ldmatrix.sync.aligned.m8n8.x4.shared.b16 {%0,%1,%2,%3}, [%4];"
        : "=r"(r[0]), "=r"(r[1]), "=r"(r[2]), "=r"(r[3]) : "r"(addr) : "memory");
}
__device__ __forceinline__ float lds32(uint32_t a) {
    float v; asm volatile("ld.shared.f32 %0, [%1];" : "=f"(v) : "r"(a) : "memory"); return v;
}
__device__ __forceinline__ void st_async2(uint32_t dst, float x, float y, uint32_t bar) {
    asm volatile("st.async.shared::cluster.mbarrier::complete_tx::bytes.v2.f32 [%0], {%1,%2}, [%3];" ::"r"(dst), "f"(x), "f"(y), "r"(bar) : "memory");
}
__device__ __forceinline__ void mma8(float (&d)[4], uint32_t a0, uint32_t a1, uint32_t b0) {
    asm volatile("mma.sync.aligned.m16n8k8.row.col.f32.bf16.bf16.f32 {%0,%1,%2,%3}, {%4,%5}, {%6}, {%0,%1,%2,%3};"
        : "+f"(d[0]), "+f"(d[1]), "+f"(d[2]), "+f"(d[3]) : "r"(a0), "r"(a1), "r"(b0));
}
__device__ __forceinline__ void cp16(uint32_t dst, const void* src) {
    asm volatile("cp.async.cg.shared.global [%0], [%1], 16;" ::"r"(dst), "l"(src) : "memory");
}
__device__ __forceinline__ void sts128(uint32_t a, const float (&v)[4]) {
    asm volatile("st.shared.v4.f32 [%0], {%1,%2,%3,%4};" ::"r"(a), "f"(v[0]), "f"(v[1]), "f"(v[2]), "f"(v[3]) : "memory");
}
__device__ __forceinline__ float4 lds128(uint32_t a) {
    float4 v; asm volatile("ld.shared.v4.f32 {%0,%1,%2,%3}, [%4];" : "=f"(v.x), "=f"(v.y), "=f"(v.z), "=f"(v.w) : "r"(a) : "memory"); return v;
}
__device__ __forceinline__ void sts64(uint32_t a, float x, float y) {
    asm volatile("st.shared.v2.f32 [%0], {%1,%2};" ::"r"(a), "f"(x), "f"(y) : "memory");
}
__device__ __forceinline__ float2 lds64(uint32_t a) {
    float2 v; asm volatile("ld.shared.v2.f32 {%0,%1}, [%2];" : "=f"(v.x), "=f"(v.y) : "r"(a) : "memory"); return v;
}
__device__ __forceinline__ void bar_sync(int id, int n) { asm volatile("bar.sync %0, %1;" ::"r"(id), "r"(n) : "memory"); }
__device__ __forceinline__ void bar_arrive(int id, int n) { asm volatile("bar.arrive %0, %1;" ::"r"(id), "r"(n) : "memory"); }
__device__ __forceinline__ uint32_t mapa(uint32_t a, uint32_t r) {
    uint32_t o; asm("mapa.shared::cluster.u32 %0, %1, %2;" : "=r"(o) : "r"(a), "r"(r)); return o;
}
__device__ __forceinline__ void st_async4(uint32_t dst, float4 v, uint32_t bar) {
    asm volatile("st.async.shared::cluster.mbarrier::complete_tx::bytes.v4.f32 [%0], {%1,%2,%3,%4}, [%5];"
        ::"r"(dst), "f"(v.x), "f"(v.y), "f"(v.z), "f"(v.w), "r"(bar) : "memory");
}
__device__ __forceinline__ void mbar_init(uint32_t bar, int n) { asm volatile("mbarrier.init.shared.b64 [%0], %1;" ::"r"(bar), "r"(n) : "memory"); }
__device__ __forceinline__ void mbar_expect(uint32_t bar, int bytes) {
    asm volatile("mbarrier.arrive.expect_tx.shared.b64 _, [%0], %1;" ::"r"(bar), "r"(bytes) : "memory");
}
__device__ __forceinline__ void bulk_load(uint32_t dst, const void* src, int bytes, uint32_t bar) {
    asm volatile("cp.async.bulk.shared::cluster.global.mbarrier::complete_tx::bytes [%0], [%1], %2, [%3];"
        ::"r"(dst), "l"(src), "r"(bytes), "r"(bar) : "memory");
}
__device__ __forceinline__ bool mbar_try(uint32_t bar, uint32_t par) {
    uint32_t ok;
    asm volatile("{.reg .pred p; mbarrier.try_wait.parity.shared::cta.b64 p, [%1], %2; selp.u32 %0, 1, 0, p;}"
        : "=r"(ok) : "r"(bar), "r"(par) : "memory");
    return ok;
}
__device__ __forceinline__ bool mbar_test(uint32_t bar, uint32_t par) {
    uint32_t ok;
    asm volatile("{.reg .pred p; mbarrier.test_wait.parity.shared::cta.b64 p, [%1], %2; selp.u32 %0, 1, 0, p;}"
        : "=r"(ok) : "r"(bar), "r"(par) : "memory");
    return ok;
}
__device__ __forceinline__ int ld_acq(const int* p) { int v; asm volatile("ld.acquire.gpu.global.s32 %0, [%1];" : "=r"(v) : "l"(p) : "memory"); return v; }
__device__ __forceinline__ void red_release(int* p, int v) { asm volatile("red.release.gpu.global.add.s32 [%0], %1;" ::"l"(p), "r"(v) : "memory"); }
__device__ __forceinline__ void fence_gpu() { asm volatile("fence.acq_rel.gpu;" ::: "memory"); }
__device__ __forceinline__ void wait_ctr(const int* p, int n) {
#pragma unroll 1
    for (int it = 0; it < (1 << 20) && ld_acq(p) < n; it++) __nanosleep(64);
}
__device__ __forceinline__ void mbar_wait(uint32_t bar, uint32_t par) {
    if (!mbar_try(bar, par)) {
#pragma unroll 1
        for (int it = 0; it < SPIN_LIMIT && !mbar_try(bar, par); it++) {}
    }
}
__device__ __forceinline__ void mbar_wait_long(uint32_t bar, uint32_t par) {
    for (int it = 0; it < (1 << 24) && !mbar_try(bar, par); it++) {}
}
__device__ __forceinline__ float4 add4(float4 a, float4 b) { return make_float4(a.x + b.x, a.y + b.y, a.z + b.z, a.w + b.w); }
__device__ __forceinline__ float ex2(float x) { float y; asm("ex2.approx.ftz.f32 %0, %1;" : "=f"(y) : "f"(x)); return y; }

__device__ __forceinline__ void wgmma256(float (&d)[128], uint64_t da, uint64_t db, int acc) {
    asm volatile("{.reg .pred p; setp.ne.b32 p, %130, 0;\n"
        "wgmma.mma_async.sync.aligned.m64n256k16.f32.bf16.bf16 {"
        "%0,%1,%2,%3,%4,%5,%6,%7,%8,%9,%10,%11,%12,%13,%14,%15,"
        "%16,%17,%18,%19,%20,%21,%22,%23,%24,%25,%26,%27,%28,%29,%30,%31,"
        "%32,%33,%34,%35,%36,%37,%38,%39,%40,%41,%42,%43,%44,%45,%46,%47,"
        "%48,%49,%50,%51,%52,%53,%54,%55,%56,%57,%58,%59,%60,%61,%62,%63,"
        "%64,%65,%66,%67,%68,%69,%70,%71,%72,%73,%74,%75,%76,%77,%78,%79,"
        "%80,%81,%82,%83,%84,%85,%86,%87,%88,%89,%90,%91,%92,%93,%94,%95,"
        "%96,%97,%98,%99,%100,%101,%102,%103,%104,%105,%106,%107,%108,%109,%110,%111,"
        "%112,%113,%114,%115,%116,%117,%118,%119,%120,%121,%122,%123,%124,%125,%126,%127"
        "}, %128, %129, p, 1, 1, 0, 1;}"
        : "+f"(d[0]), "+f"(d[1]), "+f"(d[2]), "+f"(d[3]), "+f"(d[4]), "+f"(d[5]), "+f"(d[6]), "+f"(d[7]), "+f"(d[8]), "+f"(d[9]), "+f"(d[10]), "+f"(d[11]), "+f"(d[12]), "+f"(d[13]), "+f"(d[14]), "+f"(d[15]), "+f"(d[16]), "+f"(d[17]), "+f"(d[18]), "+f"(d[19]), "+f"(d[20]), "+f"(d[21]), "+f"(d[22]), "+f"(d[23]), "+f"(d[24]), "+f"(d[25]), "+f"(d[26]), "+f"(d[27]), "+f"(d[28]), "+f"(d[29]), "+f"(d[30]), "+f"(d[31]), "+f"(d[32]), "+f"(d[33]), "+f"(d[34]), "+f"(d[35]), "+f"(d[36]), "+f"(d[37]), "+f"(d[38]), "+f"(d[39]), "+f"(d[40]), "+f"(d[41]), "+f"(d[42]), "+f"(d[43]), "+f"(d[44]), "+f"(d[45]), "+f"(d[46]), "+f"(d[47]), "+f"(d[48]), "+f"(d[49]), "+f"(d[50]), "+f"(d[51]), "+f"(d[52]), "+f"(d[53]), "+f"(d[54]), "+f"(d[55]), "+f"(d[56]), "+f"(d[57]), "+f"(d[58]), "+f"(d[59]), "+f"(d[60]), "+f"(d[61]), "+f"(d[62]), "+f"(d[63]), "+f"(d[64]), "+f"(d[65]), "+f"(d[66]), "+f"(d[67]), "+f"(d[68]), "+f"(d[69]), "+f"(d[70]), "+f"(d[71]), "+f"(d[72]), "+f"(d[73]), "+f"(d[74]), "+f"(d[75]), "+f"(d[76]), "+f"(d[77]), "+f"(d[78]), "+f"(d[79]), "+f"(d[80]), "+f"(d[81]), "+f"(d[82]), "+f"(d[83]), "+f"(d[84]), "+f"(d[85]), "+f"(d[86]), "+f"(d[87]), "+f"(d[88]), "+f"(d[89]), "+f"(d[90]), "+f"(d[91]), "+f"(d[92]), "+f"(d[93]), "+f"(d[94]), "+f"(d[95]), "+f"(d[96]), "+f"(d[97]), "+f"(d[98]), "+f"(d[99]), "+f"(d[100]), "+f"(d[101]), "+f"(d[102]), "+f"(d[103]), "+f"(d[104]), "+f"(d[105]), "+f"(d[106]), "+f"(d[107]), "+f"(d[108]), "+f"(d[109]), "+f"(d[110]), "+f"(d[111]), "+f"(d[112]), "+f"(d[113]), "+f"(d[114]), "+f"(d[115]), "+f"(d[116]), "+f"(d[117]), "+f"(d[118]), "+f"(d[119]), "+f"(d[120]), "+f"(d[121]), "+f"(d[122]), "+f"(d[123]), "+f"(d[124]), "+f"(d[125]), "+f"(d[126]), "+f"(d[127])
        : "l"(da), "l"(db), "r"(acc));
}
__device__ __forceinline__ void wgmma128(float (&d)[64], uint64_t da, uint64_t db, int acc) {
    asm volatile("{.reg .pred p; setp.ne.b32 p, %66, 0;\n"
        "wgmma.mma_async.sync.aligned.m64n128k16.f32.bf16.bf16 {"
        "%0,%1,%2,%3,%4,%5,%6,%7,%8,%9,%10,%11,%12,%13,%14,%15,"
        "%16,%17,%18,%19,%20,%21,%22,%23,%24,%25,%26,%27,%28,%29,%30,%31,"
        "%32,%33,%34,%35,%36,%37,%38,%39,%40,%41,%42,%43,%44,%45,%46,%47,"
        "%48,%49,%50,%51,%52,%53,%54,%55,%56,%57,%58,%59,%60,%61,%62,%63"
        "}, %64, %65, p, 1, 1, 0, 1;}"
        : "+f"(d[0]), "+f"(d[1]), "+f"(d[2]), "+f"(d[3]), "+f"(d[4]), "+f"(d[5]), "+f"(d[6]), "+f"(d[7]), "+f"(d[8]), "+f"(d[9]), "+f"(d[10]), "+f"(d[11]), "+f"(d[12]), "+f"(d[13]), "+f"(d[14]), "+f"(d[15]), "+f"(d[16]), "+f"(d[17]), "+f"(d[18]), "+f"(d[19]), "+f"(d[20]), "+f"(d[21]), "+f"(d[22]), "+f"(d[23]), "+f"(d[24]), "+f"(d[25]), "+f"(d[26]), "+f"(d[27]), "+f"(d[28]), "+f"(d[29]), "+f"(d[30]), "+f"(d[31]), "+f"(d[32]), "+f"(d[33]), "+f"(d[34]), "+f"(d[35]), "+f"(d[36]), "+f"(d[37]), "+f"(d[38]), "+f"(d[39]), "+f"(d[40]), "+f"(d[41]), "+f"(d[42]), "+f"(d[43]), "+f"(d[44]), "+f"(d[45]), "+f"(d[46]), "+f"(d[47]), "+f"(d[48]), "+f"(d[49]), "+f"(d[50]), "+f"(d[51]), "+f"(d[52]), "+f"(d[53]), "+f"(d[54]), "+f"(d[55]), "+f"(d[56]), "+f"(d[57]), "+f"(d[58]), "+f"(d[59]), "+f"(d[60]), "+f"(d[61]), "+f"(d[62]), "+f"(d[63])
        : "l"(da), "l"(db), "r"(acc));
}
__device__ __forceinline__ void wg_fence() { asm volatile("wgmma.fence.sync.aligned;" ::: "memory"); }
__device__ __forceinline__ void wg_commit() { asm volatile("wgmma.commit_group.sync.aligned;" ::: "memory"); }
template <int N> __device__ __forceinline__ void wg_wait() { asm volatile("wgmma.wait_group.sync.aligned %0;" ::"n"(N) : "memory"); }
__device__ __forceinline__ uint64_t mkdesc(uint32_t addr, uint32_t lbo, uint32_t sbo, uint32_t sw) {
    return (uint64_t)((addr & 0x3FFFF) >> 4) | ((uint64_t)(lbo >> 4) << 16) | ((uint64_t)(sbo >> 4) << 32) | ((uint64_t)sw << 62);
}
__device__ __forceinline__ void tma2d(uint32_t dst, const CUtensorMap* m, int c0, int c1, uint32_t bar) {
    asm volatile("cp.async.bulk.tensor.2d.shared::cluster.global.mbarrier::complete_tx::bytes [%0], [%1, {%2, %3}], [%4];"
        ::"r"(dst), "l"(m), "r"(c0), "r"(c1), "r"(bar) : "memory");
}
__device__ __forceinline__ void tma3d(uint32_t dst, const CUtensorMap* m, int c0, int c1, int c2, uint32_t bar) {
    asm volatile("cp.async.bulk.tensor.3d.shared::cluster.global.mbarrier::complete_tx::bytes [%0], [%1, {%2, %3, %4}], [%5];"
        ::"r"(dst), "l"(m), "r"(c0), "r"(c1), "r"(c2), "r"(bar) : "memory");
}
__device__ __forceinline__ void mbar_arrive(uint32_t bar) { asm volatile("mbarrier.arrive.shared.b64 _, [%0];" ::"r"(bar) : "memory"); }
__device__ __forceinline__ bool elect() {
    uint32_t p;
    asm volatile("{.reg .pred p; elect.sync _|p, 0xffffffff; selp.u32 %0, 1, 0, p;}" : "=r"(p));
    return p;
}
template <int R> __device__ __forceinline__ void reg_inc() { asm volatile("setmaxnreg.inc.sync.aligned.u32 %0;" ::"n"(R)); }
template <int R> __device__ __forceinline__ void reg_dec() { asm volatile("setmaxnreg.dec.sync.aligned.u32 %0;" ::"n"(R)); }

#define ST(id, w, i)
constexpr int CH_NRES = 50;
constexpr int CH_WREG = CH_NRES * 512;
constexpr int CH_PART = 8 * CH_WREG;
constexpr int CH_SX = CH_PART + 16384;
constexpr int CH_MX = CH_SX + 3 * 1280;
constexpr int CH_QK = CH_MX;
constexpr int CH_XS = CH_MX + 3 * 512;
constexpr int CH_BAR = CH_XS + 5632;
constexpr int CH_SMEM = CH_BAR + 192;
constexpr int CH_THREADS = 384;

__device__ __forceinline__ char* ring_base() { return (char*)(((uintptr_t)g_ring + (1 << 20) - 1) & ~(uintptr_t)((1 << 20) - 1)); }
__device__ __forceinline__ uint32_t ring_off(int chunk, int side) {
    uint32_t o = ((chunk & 1) << 13) | ((chunk >> 1) << 16);
    uint32_t par = ((o >> 13) ^ (o >> 16) ^ (o >> 17) ^ (o >> 19) ^ side) & 1;
    return o | (par << 12);
}
__device__ __forceinline__ uint2 ld_poll(const char* p) {
    unsigned long long v; asm volatile("ld.relaxed.gpu.global.b64 %0, [%1];" : "=l"(v) : "l"(p) : "memory");
    return make_uint2((uint32_t)v, (uint32_t)(v >> 32));
}
__device__ __forceinline__ void st_pub(char* p, uint32_t x, uint32_t y) {
    unsigned long long v = ((unsigned long long)y << 32) | x;
    asm volatile("st.relaxed.gpu.global.b64 [%0], %1;" ::"l"(p), "l"(v) : "memory");
}
template <int N>
__device__ __forceinline__ void poll_issue(uint2 (&b)[N], const char* p, bool lastvalid) {
#pragma unroll
    for (int i = 0; i < N; i++) {
        if (i < N - 1 || lastvalid) b[i] = ld_poll(p + i * 256);
        else b[i] = make_uint2(0, 0);
    }
}
template <int N>
__device__ __forceinline__ int poll_check(uint2 (&b)[N], const char* p, uint32_t z) {
    int it = 0;
    uint32_t mx = z;
#pragma unroll
    for (int i = 0; i < N; i++) mx = max(mx, b[i].x);
    if (__any_sync(0xffffffffu, mx == SENT)) {
        do {
#pragma unroll
            for (int i = 0; i < N; i++)
                if (b[i].x == SENT) b[i] = ld_poll(p + i * 256);
            mx = b[0].x;
#pragma unroll
            for (int i = 1; i < N; i++) mx = max(mx, b[i].x);
            it++;
        } while (__any_sync(0xffffffffu, mx == SENT && it < SPIN_LIMIT));
    }
    return it;
}
template <int N>
__device__ __forceinline__ uint32_t delay(uint32_t a) {
    uint32_t z = 0;
#pragma unroll
    for (int i = 0; i < N; i++) asm volatile("ld.volatile.shared.u32 %0, [%1];" : "=r"(z) : "r"(a + z) : "memory");
    return z;
}

#define LDW 0
#define GX 2
#define PACE2 19
#define KGS 2
constexpr int KVN = 2;
#define CL 6
#define ML 6
#define MP 2
#define DLM 3
#define DLO 2
constexpr int OB = 0;
template <int PACE, int I0 = 0, int I1 = 12>
__device__ __forceinline__ void preload(uint32_t (&sw)[12][4], uint32_t a, uint32_t zero) {
    uint32_t z = 0;
#pragma unroll
    for (int i = I0; i < I1; i++) {
        if (PACE && i % (PACE ? PACE : 1) == 0) z = delay<1>(zero + z);
        ldsm4t(sw[i], a + z + i * 512);
    }
}
__device__ __forceinline__ void stsm4(uint32_t addr, uint32_t a, uint32_t b, uint32_t c, uint32_t d) {
    asm volatile("stmatrix.sync.aligned.m8n8.x4.shared.b16 [%0], {%1,%2,%3,%4};" ::"r"(addr), "r"(a), "r"(b), "r"(c), "r"(d) : "memory");
}
__device__ __forceinline__ void stsm4t(uint32_t addr, uint32_t a, uint32_t b, uint32_t c, uint32_t d) {
    asm volatile("stmatrix.sync.aligned.m8n8.x4.trans.shared.b16 [%0], {%1,%2,%3,%4};" ::"r"(addr), "r"(a), "r"(b), "r"(c), "r"(d) : "memory");
}
__device__ __forceinline__ void st_part(uint32_t addr, const float (&x)[4], const float (&y)[4]) {
    stsm4(addr, pack_bf16(x[0], x[1]), pack_bf16(x[2], x[3]), pack_bf16(y[0], y[1]), pack_bf16(y[2], y[3]));
}
template <bool TR>
__device__ __forceinline__ void red_part(uint32_t& lo, uint32_t& hi, uint32_t addr, uint32_t eye) {
    uint32_t a[4][4];
#pragma unroll
    for (int j = 0; j < 4; j++) { if (TR) ldsm4t(a[j], addr + j * 1024); else ldsm4(a[j], addr + j * 1024); }
    float r0[4], r1[4], r2[4], r3[4];
    mma16z(r0, a[0], eye, eye); mma16z(r1, a[1], eye, eye); mma16z(r2, a[2], eye, eye); mma16z(r3, a[3], eye, eye);
#pragma unroll
    for (int j = 0; j < 4; j++) r0[j] = ((r0[j] + r1[j]) + r2[j]) + r3[j];
    lo = pack_bf16(r0[0], r0[1]); hi = pack_bf16(r0[2], r0[3]);
}
__device__ __forceinline__ int o_chunk(int ks, int& pos) {
    const int cw = ks < 176 ? ks / 11 : 16 + (ks - 176) / 10;
    pos = ks - (cw < 16 ? 11 * cw : 176 + 10 * (cw - 16));
    return cw;
}

template <bool PV>
__device__ __forceinline__ void chain_loop(const uint32_t (&wa)[36][4], const uint32_t sb, const int w, const int lane0, const int rank,
                                           const int h, const int side) {
    const int rk1 = rank == 2 ? 0 : rank + 1, rk2 = rank == 0 ? 2 : rank - 1;
    const int nq = rank == 0 ? 6 : 5, u0 = rank == 0 ? 0 : 1 + 5 * rank, v0 = rank == 0 ? -6 : 3 * rank - 6;
    const uint32_t pt = CH_PART + (w >> 1) * 4096 + (w & 1) * 256;
    const uint32_t barS = sb + CH_BAR, barM = barS + 8, zero = barS + 24;
    char* const ring0 = ring_base();
    const uint32_t m_rd = ring_off(24 + w, side), o_rd = ring_off(rank * 8 + w, side);
    uint32_t pub;
    if (PV) { int pos, cw = o_chunk(h * 8 + v0 + w, pos); pub = (ring_off(cw, 0) & ~4096u) + pos * 256; }
    else pub = (ring_off(24 + (h >> 2), 0) & ~4096u) + ((2 * h + w) & 7) * 256;
    char* const kvo = (char*)(PV ? g_vm + 128 * (v0 + w) : g_km + 64 * (u0 + w)) + h * 2048;
    const bool mown = !PV && w == rank && rank < 2;
    uint32_t lo16 = lane0 * 16;
    uint32_t sw[12][4];
#pragma unroll
    for (int i = 0; i < 12; i++) ldsm4t(sw[i], sb + lo16 + w * CH_WREG + i * 512);

#pragma unroll 1
    for (int s = 0;; s++) {
        const bool last = s == NSEG - 1;
        const uint32_t slot = (s & 3) << 14;
        lo16 += delay<DLM>(zero);
        const uint32_t lane = lo16 >> 4, l16 = sb + lo16, wl = l16 + w * CH_WREG, pw = l16 + CH_PART + w * 512;
        const uint32_t xs = l16 + CH_XS + nq * 512 + (w - nq) * 1024;
        const uint32_t eye = ((lo16 >> 7) == (lane & 3)) ? ((lo16 & 64) ? 0x3F800000u : 0x3F80u) : 0u;
        uint2 b[8];
        const char* pm = ring0 + (m_rd + slot + (lo16 >> 1));
        poll_issue<8>(b, pm, true);
        preload<0, ML, 12>(sw, wl, zero);
        bar_arrive(14, 256);
        poll_check<8>(b, pm, delay<1>(zero));
        if (OB && !last) bar_arrive(8, 256 + OB);
        if (PV && !last && w == 7) bar_arrive(13, 64);
        {
            float acc[6][4];
#pragma unroll
            for (int kk = 0; kk < 8; kk++) {
                const int j = (2 * kk) % 12;
                if (kk == 0) { mma16z(acc[5], sw[0], b[0].x, b[0].y); mma16z(acc[4], sw[1], b[0].x, b[0].y); }
                else { mma16(acc[5], sw[j], b[kk].x, b[kk].y); mma16(acc[4], sw[j + 1], b[kk].x, b[kk].y); }
#pragma unroll
                for (int i = 0; i < 4; i++) {
                    if (kk == 0) mma16z(acc[i], wa[i * 8], b[0].x, b[0].y);
                    else mma16(acc[i], wa[i * 8 + kk], b[kk].x, b[kk].y);
                    if (i < 2) ldsm4t(sw[j + i], wl + (12 + 2 * kk + i) * 512);
                }
            }
            st_part(pw + 4 * 2048, acc[4], acc[5]);
            st_part(pw, acc[0], acc[1]);
            st_part(pw + 2 * 2048, acc[2], acc[3]);
        }
        uint32_t kv0, kv1;
        const uint32_t lp = l16 + (lane >> 4) * 256, pl = lp + pt;
        if (!PV) {
            bar_sync(1, last ? 256 : 256 + OB);
            red_part<true>(kv1, kv0, pl, eye);
            sts64(l16 + CH_QK + (w >> 1) * 512 + (w & 1) * 8, __uint_as_float(kv1), __uint_as_float(kv0));
            if (!last) bar_arrive(2, nq * 32 + 64 + OB);
        } else {
            bar_sync(1, last ? 256 : 256 + OB);
        }
        {
            float va[4][4];
            if (side > 1) asm volatile("exit;");
#pragma unroll
            for (int i = 0; i < 4; i++) va[i][0] = va[i][1] = va[i][2] = va[i][3] = 0.f;
#pragma unroll
            for (int kk = 0; kk < 8; kk++) {
                const int c = PV ? kk & 1 : 0;
                if (kk < 2) { mma16(va[c], wa[32 + 2 * kk], b[kk].x, b[kk].y); mma16(va[2 + c], wa[33 + 2 * kk], b[kk].x, b[kk].y); }
                else { mma16(va[c], sw[(2 * kk) % 12], b[kk].x, b[kk].y); mma16(va[2 + c], sw[(2 * kk + 1) % 12], b[kk].x, b[kk].y); }
            }
            if (PV) {
#pragma unroll
                for (int j = 0; j < 4; j++) { va[0][j] += va[1][j]; va[2][j] += va[3][j]; }
            }
            st_part(pw + 6 * 2048, va[0], va[2]);
        }
        if (PV) {
            uint32_t vt0[4], vt1[4];
            ldsm4t(vt0, xs); ldsm4t(vt1, xs + 512);
            if (w >= 6 && !last) {
                uint32_t kx[3][4];
#pragma unroll
                for (int j = 0; j < 3; j++)
                    ldsm4(kx[j], sb + CH_XS + j * 1024 + (j == 2 && nq == 5 ? 0 : ((lane >> 3) & 1) * 512) + (w - 6) * 256 + (lane >> 4) * 128 + (lane & 7) * 16);
                const uint32_t da = l16 + CH_SX + rank * 1280 + (w - 6) * 512, dc = sb + CH_SX + rank * 1280 + 1024 + lane * 8;
                bar_sync(2, nq * 32 + 64 + OB);
                uint32_t qk[3][4];
#pragma unroll
                for (int j = 0; j < 3; j++) {
                    const float4 v = lds128(l16 + CH_QK + j * 512);
                    qk[j][0] = __float_as_uint(v.x); qk[j][1] = __float_as_uint(v.y); qk[j][2] = __float_as_uint(v.z); qk[j][3] = __float_as_uint(v.w);
                }
                float s0[4], s1[4], s2[4], s3[4];
                mma16z(s0, qk[0], kx[0][0], kx[0][1]); mma16z(s1, qk[0], kx[0][2], kx[0][3]);
                mma16z(s2, qk[1], kx[1][0], kx[1][1]); mma16z(s3, qk[1], kx[1][2], kx[1][3]);
                if (nq == 5) qk[2][2] = qk[2][3] = 0;
                mma16(s0, qk[2], kx[2][0], kx[2][1]); mma16(s1, qk[2], kx[2][2], kx[2][3]);
                float m0[4], m1[4];
                mma16z(m0, qk[0], qk[0][1], qk[0][3]); mma16z(m1, qk[1], qk[1][1], qk[1][3]);
                mma16(m0, qk[2], qk[2][1], qk[2][3]);
                const float4 sv = make_float4(s0[0] + s2[0], s0[1] + s2[1], s1[0] + s3[0], s1[1] + s3[1]);
                st_async4(mapa(da, rk1), sv, mapa(barS, rk1));
                st_async4(mapa(da, rk2), sv, mapa(barS, rk2));
                {
                    const float c0 = m0[0] + m1[0], c1 = m0[1] + m1[1];
                    const int dr = w == 6 ? rk1 : rk2;
                    st_async2(mapa(dc, dr), c0, c1, mapa(barS, dr));
                    sts64(dc, c0, c1);
                }
                const float t4[4] = {sv.x, sv.y, sv.z, sv.w};
                sts128(da, t4);
            }
            bar_sync(3, last ? 256 : 256 + OB);
            if (!last && w == 7) bar_arrive(12, 64);
            red_part<false>(kv0, kv1, pl, eye);
            if (last) {
                uint32_t* d = (uint32_t*)(kvo + (uint32_t)(s * (NH * 2048) + lane * 4));
                d[0] = movm(kv0); d[32] = movm(kv1);
                break;
            }
            {
                const uint32_t sx = l16 + CH_SX, r0 = rank * 1280, r1 = rk1 * 1280, r2 = rk2 * 1280;
                float4 a0 = lds128(sx + r0), b0 = lds128(sx + 512 + r0);
                const float2 c0 = lds64(sx + 1024 + r0 - lane * 8);
                mbar_wait(barS, s & 1);
                const float4 a1 = lds128(sx + r1), a2 = lds128(sx + r2), b1 = lds128(sx + 512 + r1), b2 = lds128(sx + 512 + r2);
                const float2 c1 = lds64(sx + 1024 + r1 - lane * 8), c2 = lds64(sx + 1024 + r2 - lane * 8);
                a0 = add4(add4(a0, a1), a2); b0 = add4(add4(b0, b1), b2);
                float sc[10] = {a0.x, a0.y, a0.z, a0.w, b0.x, b0.y, b0.z, b0.w, c0.x + c1.x + c2.x, c0.y + c1.y + c2.y};
                float mx = fmaxf(fmaxf(fmaxf(sc[0], sc[1]), fmaxf(sc[2], sc[3])), fmaxf(fmaxf(sc[4], sc[5]), fmaxf(sc[6], sc[7])));
                mx = fmaxf(mx, fmaxf(sc[8], sc[9]));
                mx = fmaxf(fmaxf(mx, __shfl_xor_sync(0xffffffffu, mx, 1)),
                           fmaxf(__shfl_xor_sync(0xffffffffu, mx, 2), __shfl_xor_sync(0xffffffffu, mx, 3)));
                const float cs = 0.08838834764831845f * 1.4426950408889634f;
                const float mb = -mx * cs;
#pragma unroll
                for (int j = 0; j < 10; j++) sc[j] = ex2(fmaf(sc[j], cs, mb));
                uint32_t pf[5];
#pragma unroll
                for (int j = 0; j < 5; j++) pf[j] = pack_bf16(sc[2 * j], sc[2 * j + 1]);
                float o0[4], o1[4], o2[4], o3[4], o4[4], o5[4];
                const uint32_t p0[4] = {pf[0], 0, pf[1], 0}, p1[4] = {pf[2], 0, pf[3], 0};
                mma16z(o0, p0, vt0[0], vt0[1]); mma16z(o1, p0, vt1[0], vt1[1]);
                mma16z(o2, p1, vt0[2], vt0[3]); mma16z(o3, p1, vt1[2], vt1[3]);
                mma8z(o4, pf[4], 0, kv0); mma8z(o5, pf[4], 0, kv1);
                float sum = (((sc[0] + sc[1]) + (sc[2] + sc[3])) + ((sc[4] + sc[5]) + (sc[6] + sc[7]))) + (sc[8] + sc[9]);
                sum = (sum + __shfl_xor_sync(0xffffffffu, sum, 1)) + (__shfl_xor_sync(0xffffffffu, sum, 2) + __shfl_xor_sync(0xffffffffu, sum, 3));
                float inv; asm("rcp.approx.ftz.f32 %0, %1;" : "=f"(inv) : "f"(sum));
                const uint32_t ox = pack_bf16((o0[0] + o2[0] + o4[0]) * inv, (o0[1] + o2[1] + o4[1]) * inv);
                const uint32_t oy = pack_bf16((o1[0] + o3[0] + o5[0]) * inv, (o1[1] + o3[1] + o5[1]) * inv);
                char* const pp = ring0 + (pub + slot + (lo16 >> 1));
                st_pub(pp, ox, oy); st_pub(pp + 4096, ox, oy);
                bar_arrive(10, (8 - nq) * 32 + OB);
            }
            kv0 = movm(kv0); kv1 = movm(kv1);
        } else {
            *(uint32_t*)(kvo + (uint32_t)(s * (NH * 2048) + lane * 4)) = kv0;
            bar_sync(3, last ? 256 : 256 + OB);
            if (last) break;
            preload<1, 0, CL>(sw, wl + 28 * 512, zero);
        }
        uint2 c[11];
        bar_sync(4, 256 + OB);
        const char* po = ring0 + (o_rd + slot + (lo16 >> 1) + delay<DLO>(zero));
        poll_issue<11>(c, po, rank < 2);
        preload<0, PV ? 0 : CL, 12>(sw, wl + 28 * 512, zero);
        if (PV) { uint32_t* d = (uint32_t*)(kvo + (uint32_t)(s * (NH * 2048) + lane * 4)); d[0] = kv0; d[32] = kv1; }
        {
            float acc[4][4];
            uint32_t sx[GX][4];
#pragma unroll
            for (int i = 0; i < GX; i++) ldsm4t(sx[i], wl + (40 + i) * 512);
            poll_check<11>(c, po, 0);
            if (OB) bar_arrive(9, 256 + OB);
#pragma unroll
            for (int f = 0; f < 22; f++) {
                const int kk = f >> 1, a = f & 3;
                if (f < 4) mma16z(acc[a], sw[f], c[kk].x, c[kk].y);
                else if (f >= 12 && f < 12 + GX) mma16(acc[a], sx[f - 12], c[kk].x, c[kk].y);
                else mma16(acc[a], sw[f % (12 + GX)], c[kk].x, c[kk].y);
                if (f + 12 + GX < 22) ldsm4t(sw[f], wl + (40 + GX + f) * 512);
            }
#pragma unroll
            for (int i = 0; i < 2; i++) {
#pragma unroll
                for (int j = 0; j < 4; j++) acc[i][j] += acc[i + 2][j];
                sts128(l16 + CH_PART + i * 4096 + w * 512, acc[i]);
            }
        }
        if (!PV && w < 2) {
            bar_sync(5, 288 + OB);
            float4 v[8];
#pragma unroll
            for (int i = 0; i < 8; i++) v[i] = lds128(l16 + CH_PART + w * 4096 + i * 512);
            float4 r = add4(add4(add4(v[0], v[1]), add4(v[2], v[3])), add4(add4(v[4], v[5]), add4(v[6], v[7])));
            if (!mown) st_async4(mapa(l16 + CH_MX + rank * 512, w), r, mapa(barM, w));
            bar_arrive(7, 256 + OB);
            if (mown) {
                mbar_wait(barM, s & 1);
                float4 x = lds128(l16 + CH_MX + (rank ^ 1) * 512), y = lds128(l16 + CH_MX + 2 * 512);
                r = add4(add4(x, r), y);
                const uint32_t mx = movm(pack_bf16(r.x, r.y)), my = movm(pack_bf16(r.z, r.w));
                const uint32_t ns = (slot + 0x4000) & 0xC000;
                char* const pp = ring0 + (pub + ns + (lo16 >> 1));
                st_pub(pp, mx, my); st_pub(pp + 4096, mx, my);
            }
            preload<0, 0, ML>(sw, wl, zero);
        } else {
            bar_arrive(5, 288 + OB);
            bar_sync(7, 256 + OB);
            preload<MP, 0, ML>(sw, wl, zero);
        }
        bar_sync(6, 320 + OB);
    }
}

__device__ __forceinline__ void chain_pace(const uint32_t sb, const int lane, const int rank, const int aware) {
    const uint32_t zero = sb + CH_BAR + 24;
    if (lane == 0) {
        char* ring = ring_base();
        uint32_t* p0 = (uint32_t*)(ring + ring_off(blockIdx.x & 15, 0) + 3072 + (blockIdx.x >> 4) * 128);
        uint32_t* p1 = (uint32_t*)(ring + ring_off(blockIdx.x & 15, 1) + 3072 + (blockIdx.x >> 4) * 128);
        *p0 = 0; *p1 = 0;
        int b0 = 1 << 30, b1 = 1 << 30; uint32_t v = 0;
        for (int r = 0; r < 4 || (r < 256 && !mbar_test(sb + CH_BAR + 16, 0)); r++) {
            uint32_t t0 = clk(); v = atomicExch(p0 + (v == 500), r); uint32_t t1 = v == 777 ? clk() + 1 : clk(); b0 = min(b0, (int)(t1 - t0));
            t0 = clk(); v = atomicExch(p1 + (v == 500), r); t1 = v == 777 ? clk() + 1 : clk(); b1 = min(b1, (int)(t1 - t0));
            asm volatile("st.volatile.shared.u32 [%0], %1;" ::"r"(zero + 4), "r"(aware ? (b1 < b0) ^ (aware - 1) : 0) : "memory");
        }
    }
    __syncwarp();
#pragma unroll 1
    for (int s = 1; s < NSEG; s++) {
        bar_sync(5, 288 + OB);
        bar_arrive(6, 320 + OB + (rank == 2 ? delay<PACE2>(zero) : 0));
    }
}
__device__ __forceinline__ char* reset_ptr(const int lane, const int rank, const int h) {
    const int nq = rank == 0 ? 6 : 5, v0 = rank == 0 ? -6 : 3 * rank - 6;
    int pos, cw = o_chunk(h * 8 + v0 + min(max(5 + (lane >> 3), nq), 7), pos);
    if (lane >= 24 && rank < 2) { cw = 24 + (h >> 2); pos = (2 * h + rank) & 7; }
    return ring_base() + ((ring_off(cw, 0) & ~4096u) + pos * 256 + (lane & 7) * 16);
}
__device__ __forceinline__ void chain_chores(const uint32_t sb, const int lane, const int rank, const int h, const bf16* __restrict__ mem0) {
    const int nq = rank == 0 ? 6 : 5, u0 = rank == 0 ? 0 : 1 + 5 * rank, v0 = rank == 0 ? -6 : 3 * rank - 6;
    const uint32_t barS = sb + CH_BAR, barM = barS + 8, barX = barS + 16;
    auto xload = [&](int s) {
        mbar_expect(barX, 8192 - nq * 512);
        bulk_load(sb + CH_XS, g_kx + (size_t)(s * NH + h) * 4096 + u0 * 256, nq * 512, barX);
        bulk_load(sb + CH_XS + nq * 512, g_vx + (size_t)(s * NH + h) * 4096 + (v0 + nq) * 512, (8 - nq) * 1024, barX);
    };
    char* const rb = reset_ptr(lane, rank, h);
    int* const kvf = g_kvf + blockIdx.x * 16;
    if (rank < 2) {
        const uint32_t* p = (const uint32_t*)(mem0 + (lane >> 2) * DM + 32 * h + 16 * rank + 2 * (lane & 3));
        char* d = ring_base() + ((ring_off(24 + (h >> 2), 0) & ~4096u) + ((2 * h + rank) & 7) * 256 + lane * 8);
        const uint32_t x = p[0] == SENT ? 0x7FFF7FFFu : p[0];
        st_pub(d, x, p[4]); st_pub(d + 4096, x, p[4]);
    }
    if (!KVN) __nanosleep(18000);
    wait_ctr(kvf, KVN);
    asm volatile("fence.proxy.async.global;" ::: "memory");
    if (elect()) xload(0);
#pragma unroll 1
    for (int s = 0; s < NSEG - 1; s++) {
        if (lane == 0) {
            mbar_expect(barS, 2 * 1280);
            if (rank < 2) mbar_expect(barM, 2 * 512);
        }
        bar_sync(13, 64);
#pragma unroll
        for (int i = 0; i < 4; i++)
            asm volatile("st.relaxed.gpu.global.v4.u32 [%0], {%1,%1,%1,%1};" ::"l"(rb + ((((s + 2) & 3) << 14) + (i >> 1) * 4096 + (i & 1) * 128)), "r"(SENT) : "memory");
        fence_gpu();
        if (lane == 0 && (s & 3) == 0 && s) atomicAdd(g_ctr + C_CHAIN + (s >> 2) - 1, 1);
        if ((s & 3) == 3) { wait_ctr(kvf + (s >> 2) + 1, KVN); asm volatile("fence.proxy.async.global;" ::: "memory"); }
        __syncwarp();
        bar_sync(12, 64);
        if (elect()) xload(s + 1);
        mbar_wait(barX, (s + 1) & 1);
        bar_sync(6, 320 + OB);
    }
}

struct S4Params { const bf16 *Are, *Aim, *Bre, *Bim, *Cre, *Cim, *ldt, *dsk; };
__device__ __forceinline__ float2 cmul(float2 a, float2 b) { return make_float2(a.x * b.x - a.y * b.y, a.x * b.y + a.y * b.x); }
__device__ __forceinline__ float2 csq(float2 a) { return make_float2(a.x * a.x - a.y * a.y, (a.x + a.x) * a.y); }
__device__ __forceinline__ float2 cexp_t(float lr, float turns) {
    float f = (turns - rintf(turns)) * 6.283185307179586f, e = ex2(lr);
    return make_float2(e * __cosf(f), e * __sinf(f));
}
__device__ __forceinline__ float bf_at(uint2 v, int i) {
    const uint32_t w = i < 2 ? v.x : v.y;
    return __uint_as_float((i & 1) ? w & 0xFFFF0000u : w << 16);
}
__device__ __forceinline__ void kg_step(uint32_t (&a)[4][4], uint32_t (&b)[5][2], uint32_t pa, uint32_t pe, float x0) {
#pragma unroll
    for (int i = 0; i < 2; i++) {
        const float4 p = lds128(pa + i * 64);
        const float2 e8 = lds64(pe + i * 32), c = make_float2(p.z, p.w);
        const float mag = ex2(p.x * x0), ph = p.y * x0;
        float2 e0 = make_float2(mag * __cosf(ph), mag * __sinf(ph)), e1 = cmul(e0, e8);
#pragma unroll
        for (int j = 0; j < 4; j++) {
            a[j][2 * i] = pack_bf16(e0.x, e0.y); a[j][2 * i + 1] = pack_bf16(e1.x, e1.y);
            e0 = csq(e0); e1 = csq(e1);
        }
        float2 m = cmul(c, e0);
        b[0][i] = pack_bf16(m.x, -m.y);
#pragma unroll
        for (int j = 0; j < 4; j++) {
            m = cmul(c, e1);
            b[j + 1][i] = pack_bf16(m.x, -m.y);
            if (j < 3) e1 = csq(e1);
        }
    }
}
__device__ __forceinline__ void kg_mma(float (&kd)[5][4], const uint32_t (&a)[4][4], const uint32_t (&b)[5][2]) {
    mma16(kd[0], a[0], b[0][0], b[0][1]);
#pragma unroll
    for (int j = 0; j < 4; j++) mma16(kd[j + 1], a[j], b[j + 1][0], b[j + 1][1]);
}
struct KgRaw { uint2 v[6]; float ldt; };
__device__ __forceinline__ void kg_load(KgRaw& r, const S4Params& P, int d, int lane) {
    const bf16* src[6] = {P.Are, P.Aim, P.Bre, P.Bim, P.Cre, P.Cim};
#pragma unroll
    for (int j = 0; j < 6; j++) r.v[j] = __ldg((const uint2*)(src[j] + d * 128) + lane);
    r.ldt = __bfloat162float(P.ldt[d]);
}
__device__ __forceinline__ float kg_params(const KgRaw& r, uint32_t stg, int lane) {
    const float dt = __bfloat162float(__float2bfloat16(expf(r.ldt)));
    float k2048 = 0.f;
#pragma unroll
    for (int i = 0; i < 4; i++) {
        const float br = dt * bf_at(r.v[2], i), bi = dt * bf_at(r.v[3], i), cr = bf_at(r.v[4], i), ci = bf_at(r.v[5], i);
        const float zr = dt * bf_at(r.v[0], i) * 1.4426950408889634f;
        float zt = dt * bf_at(r.v[1], i) * 0.15915494309189535f;
        zt -= rintf(zt);
        const float v[4] = {zr, zt * 6.283185307179586f, cr * br - ci * bi, cr * bi + ci * br};
        const float2 e8 = cexp_t(8.f * zr, 8.f * zt), el = cexp_t(2048.f * zr, 2048.f * zt);
        k2048 += v[2] * el.x - v[3] * el.y;
        sts128(stg + (i * 32 + lane) * 16, v);
        sts64(stg + 2048 + (i * 32 + lane) * 8, e8.x, e8.y);
    }
#pragma unroll
    for (int o = 16; o; o >>= 1) k2048 += __shfl_xor_sync(0xffffffffu, k2048, o);
    __syncwarp();
    return k2048;
}
__device__ __forceinline__ void kg_store(const float (&kd)[5][4], float k2048, uint32_t stg, int d, int lane) {
    __syncwarp();
    const uint32_t ta = stg + (lane & 7) * 32 + ((lane >> 3) & 1) * 16 + (lane >> 4) * 256;
    stsm4t(ta, pack_bf16(kd[0][0], kd[0][1]), pack_bf16(kd[0][2], kd[0][3]), pack_bf16(kd[1][0], kd[1][1]), pack_bf16(kd[1][2], kd[1][3]));
    stsm4t(ta + 512, pack_bf16(kd[2][0], kd[2][1]), pack_bf16(kd[2][2], kd[2][3]), pack_bf16(kd[3][0], kd[3][1]), pack_bf16(kd[3][2], kd[3][3]));
    stsm4t(ta + 1024, pack_bf16(kd[4][0], kd[4][1]), pack_bf16(kd[4][2], kd[4][3]), pack_bf16(k2048, 0.f), 0);
    __syncwarp();
#pragma unroll
    for (int j = 0; j < 3; j++) ((float4*)(g_kd + d * 768))[j * 32 + lane] = lds128(stg + j * 512 + lane * 16);
    __syncwarp();
}

__global__ void __cluster_dims__(3, 1, 1) __launch_bounds__(CH_THREADS, 1)
chain_kernel(const __grid_constant__ CUtensorMap mq, const __grid_constant__ CUtensorMap mk, const __grid_constant__ CUtensorMap mv,
             const __grid_constant__ CUtensorMap mo, const bf16* __restrict__ Wq, const bf16* __restrict__ Wk, const bf16* __restrict__ Wv,
             const bf16* __restrict__ mem0, const __grid_constant__ S4Params P, int aware) {
    extern __shared__ __align__(1024) unsigned char smem[];
    const uint32_t sb = smem_u32(smem);
    const int tid = threadIdx.x, lane = tid & 31;
    const int w = __shfl_sync(0xffffffffu, tid >> 5, 0);
    int rank; asm("mov.u32 %0, %%cluster_ctarank;" : "=r"(rank));
    const int h = blockIdx.x / 3;
    if (tid == 0) {
        mbar_init(sb + CH_BAR, 1); mbar_init(sb + CH_BAR + 8, 1); mbar_init(sb + CH_BAR + 16, 1);
        for (int i = 0; i < 16; i++) mbar_init(sb + CH_BAR + 64 + i * 8, 1);
        *(int*)(smem + CH_BAR + 24) = 0; *(int*)(smem + CH_BAR + 28) = 0;
        asm volatile("fence.mbarrier_init.release.cluster;" ::: "memory");
    }
    if (w == 9) {
        char* const rb = reset_ptr(lane, rank, h);
#pragma unroll
        for (int i = 0; i < 8; i++)
            asm volatile("st.relaxed.gpu.global.v4.u32 [%0], {%1,%1,%1,%1};" ::"l"(rb + (((i >> 2) << 14) + ((i >> 1) & 1) * 4096 + (i & 1) * 128)), "r"(SENT) : "memory");
        if (lane < 16) g_kvf[blockIdx.x * 16 + lane] = 0;
        if (blockIdx.x == 0)
            for (int k = lane; k < N_CTR; k += 32) g_ctr[k] = 0;
        fence_gpu();
        __syncwarp();
        asm volatile("griddepcontrol.launch_dependents;" ::: "memory");
    }
    __syncthreads();
    asm volatile("barrier.cluster.arrive.relaxed.aligned;" ::: "memory");

    if (w >= 8) {
        reg_dec<24>();
        asm volatile("barrier.cluster.wait.aligned;" ::: "memory");
        if (w == 8) chain_pace(sb, lane, rank, aware);
        else if (w == 9) chain_chores(sb, lane, rank, h, mem0);
    } else {
        reg_inc<240>();
        const int nq = rank == 0 ? 6 : 5;
        const int u0 = rank == 0 ? 0 : 1 + 5 * rank;
        const int v0 = rank == 0 ? -6 : 3 * rank - 6;
        const int gw = rank * 8 + w;
        const int ks0 = gw < 16 ? 11 * gw : 176 + 10 * (gw - 16);
        const int nko = gw < 16 ? 11 : 10;
        const uint32_t wr = sb + w * CH_WREG, bar0 = sb + CH_BAR + 64 + w * 16, bar1 = bar0 + 8;
        uint32_t wa[36][4];
        const uint32_t vst = sb + CH_PART + w * 2048;
        const int cq = h * DH + 8 * u0, cv = h * DH + 16 * (v0 + 6);
        const int r8 = lane >> 2, p = lane & 3;
        const bf16* src = p >= 2 ? ((p & 1) ? Wk : Wq) + cq + 32 : rank == 0 ? ((p & 1) ? Wk : Wq) + cq + 40 : Wv + cv - 16 + 8 * p;
        src += (size_t)(128 * w + r8) * HD;
        auto cp_rows = [&](int kh) {
            cp16(wr + ((kh >> 1) * 2 + (p >> 1)) * 512 + ((kh & 1) * 2 + (p & 1)) * 128 + r8 * 16, src + (size_t)kh * 8 * HD);
        };
        {
            int d = blockIdx.x * 8 + w, t = 0;
            const int d1 = 768 + blockIdx.x * 3 + w, nt = (w < 3 && d1 < DM) ? 32 : 16;
            const uint32_t stg = wr + 4096;
            KgRaw raw, raw1;
            kg_load(raw, P, d, lane);
            kg_load(raw1, P, min(d1, DM - 1), lane);
            float kd[5][4], k2048;
#pragma unroll 1
            for (int i = -LDW; i < 9 || t < nt; i++) {
                if (i >= 0 && i < 9) {
                    const uint32_t bar = bar0 + (i & 1) * 8;
                    if (i >= 2) mbar_wait(bar, ((i >> 1) - 1) & 1);
                    if (elect()) {
                        mbar_expect(bar, 2048);
                        if (i < 8) tma2d(wr + 8192 + (i & 1) * 8192 + (i >> 1) * 2048, (i & 1) ? &mk : &mq, cq, 128 * w + 32 * (i >> 1), bar);
                        else tma2d(vst, &mv, cv, 128 * w, bar);
                    }
                    if (i < 8) cp_rows(i);
                }
#pragma unroll 1
                for (int e = min(t + KGS, nt); t < e; t++) {
                    if ((t & 15) == 0) {
                        k2048 = kg_params(raw, stg, lane);
#pragma unroll
                        for (int j = 0; j < 20; j++) kd[j >> 2][j & 3] = 0.f;
                    }
                    uint32_t ka[4][4], kb[5][2];
                    kg_step(ka, kb, stg + ((t & 15) * 8 + (lane & 3)) * 16, stg + 2048 + ((t & 15) * 8 + (lane & 3)) * 8, (float)(lane >> 2));
                    kg_mma(kd, ka, kb);
                    if ((t & 15) == 15) { kg_store(kd, k2048, stg, d, lane); raw = raw1; d = d1; }
                }
            }
        }
        const uint32_t lrow = ((lane >> 4) * 8 + (lane & 7)) * 64, lsw = (lane >> 1) & 3, lh = (lane >> 3) & 1;
        mbar_wait(bar1, 1); mbar_wait(bar0, 0);
#pragma unroll
        for (int i = 0; i < 32; i++) ldsm4t(wa[i], wr + 8192 + lh * 8192 + (i & 7) * 1024 + lrow + (((i >> 3) ^ lsw) << 4));
#pragma unroll
        for (int i = 0; i < 4; i++) ldsm4t(wa[32 + i], vst + (i >> 1) * 1024 + lrow + ((((i & 1) * 2 + lh) ^ lsw) << 4));
        asm volatile("fence.proxy.async.shared::cta;" ::"r"(wa[31][0]), "r"(wa[35][0]) : "memory");
        __syncwarp();
#pragma unroll 1
        for (int i = 9; i < 18; i++) {
            const uint32_t bar = bar0 + (i & 1) * 8;
            if (i >= 11) mbar_wait(bar, ((i >> 1) - 1) & 1);
            if (elect()) {
                const int j = 2 * (i - 12), nb = min(2, nko - j);
                mbar_expect(bar, i < 12 ? 2048 : nb * 1024);
                if (i < 12) tma2d(wr + 8192 + (i - 9) * 2048, &mv, cv, 128 * w + 32 * (i - 8), bar);
                else {
                    if (nb > 0) tma2d(wr + 14336 + j * 1024, &mo, 32 * h, 16 * (ks0 + j), bar);
                    if (nb > 1) tma2d(wr + 15360 + j * 1024, &mo, 32 * h, 16 * (ks0 + j + 1), bar);
                }
            }
            if (i < 17) cp_rows(i - 1);
        }
        mbar_wait(bar0, 0); mbar_wait(bar1, 0);
#pragma unroll 1
        for (int i0 = -1; i0 < 17; i0 += 6) {
            uint32_t x[6][2][4];
#pragma unroll
            for (int i = 0; i < 6; i++) {
                const uint32_t a = wr + 8192 + max(i0 + i, 0) * 1024 + lrow;
                ldsm4t(x[i][0], a + ((lh ^ lsw) << 4)); ldsm4t(x[i][1], a + (((2 + lh) ^ lsw) << 4));
            }
            if (i0 == 11 && nko == 10) {
#pragma unroll
                for (int j = 0; j < 8; j++) x[5][j >> 2][j & 3] = 0;
            }
            __syncwarp();
#pragma unroll
            for (int i = 0; i < 6; i++) {
                const uint32_t a = wr + 8192 + max(i0 + i, 0) * 1024 + lane * 16;
                stsm4t(a, x[i][0][0], x[i][0][1], x[i][0][2], x[i][0][3]); stsm4t(a + 512, x[i][1][0], x[i][1][1], x[i][1][2], x[i][1][3]);
            }
        }
        asm volatile("cp.async.wait_all;" ::: "memory");
        asm volatile("barrier.cluster.wait.aligned;" ::: "memory");
        bar_sync(1, 256);
        mbar_wait_long(sb + CH_BAR + 16, 0);
        const int side = __shfl_sync(0xffffffffu, *(volatile int*)(smem + CH_BAR + 28), 0);
        if (w >= nq) chain_loop<true>(wa, sb, w, lane, rank, h, side);
        else chain_loop<false>(wa, sb, w, lane, rank, h, side);
    }
}

constexpr int G_STAGE = 49152, G_NST = 4;
constexpr int G_STG = G_NST * G_STAGE;
constexpr int G_BAR = G_STG + 32768;
constexpr int G_SMEM = G_BAR + 256 + 1024;

#define WLOG(e)
constexpr int IT_QA = 0, IT_O = 1, IT_S4 = 2, IT_END = 3, IT_KV = 4;
#define O_WIDE 15
#define S4DIR 5
#define S4REL 4
#define KVI 1
#define KVF 2
#define KVS 8
#define Q_S1 0
#define Q_B0 10
#define Q_L 1
#define Q_T0 8
__device__ __forceinline__ int queue_item(int q) {
    if (q < 512) return (IT_KV << 16) | ((q >> 5) << 8) | (q & 31);
    q -= 512;
    if (q < Q_B0 * Q_T0) return (IT_QA << 16) | ((q % Q_B0) << 8) | (q / Q_B0);
    constexpr int W1 = O_WIDE - 1, T1 = Q_T0 + Q_L;
    if (q < W1 * Q_T0) return (IT_QA << 16) | ((q / Q_T0) << 8) | (q % Q_T0);
    if (q < W1 * T1) return (IT_QA << 16) | ((q % W1) << 8) | (q / W1);
    if (q < O_WIDE * T1) return (IT_QA << 16) | (W1 << 8) | (q - W1 * T1);
    if (q < O_WIDE * 16) return (IT_QA << 16) | ((q % O_WIDE) << 8) | (q / O_WIDE);
    q -= O_WIDE * 16;
    if (q < Q_S1) return (IT_S4 << 16) | q;
    q -= Q_S1;
    if (q < (16 - O_WIDE) * 8) return (IT_O << 16) | ((O_WIDE + (q >> 3)) << 8) | (q & 7);
    q -= (16 - O_WIDE) * 8;
    if (q < 128 - Q_S1) return (IT_S4 << 16) | (Q_S1 + q);
    return IT_END << 16;
}
constexpr int N_LATE = O_WIDE * 4 + (16 - O_WIDE) * 16;
static_assert(N_LATE <= 96, "first items of the late CTAs");
__device__ __forceinline__ int late_item(int j) {
    if (j < O_WIDE * 4) return (IT_O << 16) | ((j >> 2) << 8) | (j & 3);
    j -= O_WIDE * 4;
    return (IT_QA << 16) | ((O_WIDE + (j >> 4)) << 8) | (j & 15);
}
__device__ __forceinline__ void tma2d_store(const CUtensorMap* m, uint32_t src, int c0, int c1) {
    asm volatile("cp.async.bulk.tensor.2d.global.shared::cta.bulk_group [%0, {%2, %3}], [%1];" ::"l"(m), "r"(src), "r"(c0), "r"(c1) : "memory");
}

__device__ __forceinline__ void wgmma_s64(float (&d)[32], uint32_t a0, uint32_t a1, uint32_t a2, uint32_t a3, uint64_t db, int acc) {
    asm volatile("{.reg .pred p; setp.ne.b32 p, %37, 0;\n"
        "wgmma.mma_async.sync.aligned.m64n64k16.f32.bf16.bf16 {"
        "%0,%1,%2,%3,%4,%5,%6,%7,%8,%9,%10,%11,%12,%13,%14,%15,"
        "%16,%17,%18,%19,%20,%21,%22,%23,%24,%25,%26,%27,%28,%29,%30,%31"
        "}, {%32,%33,%34,%35}, %36, p, 1, 1, 0;}"
        : "+f"(d[0]), "+f"(d[1]), "+f"(d[2]), "+f"(d[3]), "+f"(d[4]), "+f"(d[5]), "+f"(d[6]), "+f"(d[7]), "+f"(d[8]), "+f"(d[9]), "+f"(d[10]), "+f"(d[11]), "+f"(d[12]), "+f"(d[13]), "+f"(d[14]), "+f"(d[15]), "+f"(d[16]), "+f"(d[17]), "+f"(d[18]), "+f"(d[19]), "+f"(d[20]), "+f"(d[21]), "+f"(d[22]), "+f"(d[23]), "+f"(d[24]), "+f"(d[25]), "+f"(d[26]), "+f"(d[27]), "+f"(d[28]), "+f"(d[29]), "+f"(d[30]), "+f"(d[31])
        : "r"(a0), "r"(a1), "r"(a2), "r"(a3), "l"(db), "r"(acc));
}
__device__ __forceinline__ void wgmma_s16(float (&d)[8], uint32_t a0, uint32_t a1, uint32_t a2, uint32_t a3, uint64_t db, int acc) {
    asm volatile("{.reg .pred p; setp.ne.b32 p, %13, 0;\n"
        "wgmma.mma_async.sync.aligned.m64n16k16.f32.bf16.bf16 {"
        "%0,%1,%2,%3,%4,%5,%6,%7"
        "}, {%8,%9,%10,%11}, %12, p, 1, 1, 0;}"
        : "+f"(d[0]), "+f"(d[1]), "+f"(d[2]), "+f"(d[3]), "+f"(d[4]), "+f"(d[5]), "+f"(d[6]), "+f"(d[7])
        : "r"(a0), "r"(a1), "r"(a2), "r"(a3), "l"(db), "r"(acc));
}
__device__ __forceinline__ void wgmma_v128(float (&d)[64], uint32_t a0, uint32_t a1, uint32_t a2, uint32_t a3, uint64_t db, int acc) {
    asm volatile("{.reg .pred p; setp.ne.b32 p, %69, 0;\n"
        "wgmma.mma_async.sync.aligned.m64n128k16.f32.bf16.bf16 {"
        "%0,%1,%2,%3,%4,%5,%6,%7,%8,%9,%10,%11,%12,%13,%14,%15,"
        "%16,%17,%18,%19,%20,%21,%22,%23,%24,%25,%26,%27,%28,%29,%30,%31,"
        "%32,%33,%34,%35,%36,%37,%38,%39,%40,%41,%42,%43,%44,%45,%46,%47,"
        "%48,%49,%50,%51,%52,%53,%54,%55,%56,%57,%58,%59,%60,%61,%62,%63"
        "}, {%64,%65,%66,%67}, %68, p, 1, 1, 1;}"
        : "+f"(d[0]), "+f"(d[1]), "+f"(d[2]), "+f"(d[3]), "+f"(d[4]), "+f"(d[5]), "+f"(d[6]), "+f"(d[7]), "+f"(d[8]), "+f"(d[9]), "+f"(d[10]), "+f"(d[11]), "+f"(d[12]), "+f"(d[13]), "+f"(d[14]), "+f"(d[15]), "+f"(d[16]), "+f"(d[17]), "+f"(d[18]), "+f"(d[19]), "+f"(d[20]), "+f"(d[21]), "+f"(d[22]), "+f"(d[23]), "+f"(d[24]), "+f"(d[25]), "+f"(d[26]), "+f"(d[27]), "+f"(d[28]), "+f"(d[29]), "+f"(d[30]), "+f"(d[31]), "+f"(d[32]), "+f"(d[33]), "+f"(d[34]), "+f"(d[35]), "+f"(d[36]), "+f"(d[37]), "+f"(d[38]), "+f"(d[39]), "+f"(d[40]), "+f"(d[41]), "+f"(d[42]), "+f"(d[43]), "+f"(d[44]), "+f"(d[45]), "+f"(d[46]), "+f"(d[47]), "+f"(d[48]), "+f"(d[49]), "+f"(d[50]), "+f"(d[51]), "+f"(d[52]), "+f"(d[53]), "+f"(d[54]), "+f"(d[55]), "+f"(d[56]), "+f"(d[57]), "+f"(d[58]), "+f"(d[59]), "+f"(d[60]), "+f"(d[61]), "+f"(d[62]), "+f"(d[63])
        : "r"(a0), "r"(a1), "r"(a2), "r"(a3), "l"(db), "r"(acc));
}

__device__ __forceinline__ void attn_scores(float (&sx)[32], float (&sm)[8], const uint32_t (&q)[32], uint32_t sk) {
    const uint64_t dx = mkdesc(sk, 1024, 128, 0), dm = mkdesc(sk + 16384, 256, 128, 0);
    wg_fence();
#pragma unroll
    for (int ks = 0; ks < 8; ks++) {
        wgmma_s64(sx, q[4 * ks], q[4 * ks + 1], q[4 * ks + 2], q[4 * ks + 3], dx + ks * 128, ks);
        wgmma_s16(sm, q[4 * ks], q[4 * ks + 1], q[4 * ks + 2], q[4 * ks + 3], dm + ks * 32, ks);
    }
    wg_commit();
}
template <bool HI>
__device__ __forceinline__ void attn_softmax(uint32_t (&p)[2][20], const float (&sx)[2][32], const float (&sm)[2][8], bool sb, int lane) {
    constexpr int NF = HI ? 2 : 0, NT = NF + 3;
    const int gt = (lane >> 2) - 2 * (lane & 3);
    const float cs = 0.08838834764831845f * 1.4426950408889634f;
    float s[2][NT][4], m[4], l[4];
#pragma unroll
    for (int h = 0; h < 2; h++) {
#pragma unroll
        for (int j = 0; j < NT; j++)
#pragma unroll
            for (int e = 0; e < 4; e++) s[h][j][e] = j == NT - 1 ? (sb ? sm[h][4 + e] : sm[h][e]) : (sb ? sx[h][16 + 4 * j + e] : sx[h][4 * j + e]);
        if (gt < 0) s[h][NF][0] = s[h][NF + 1][2] = -INFINITY;
        if (gt < 1) s[h][NF][1] = s[h][NF + 1][3] = -INFINITY;
        m[2 * h] = fmaxf(s[h][0][0], s[h][0][1]); m[2 * h + 1] = fmaxf(s[h][0][2], s[h][0][3]);
#pragma unroll
        for (int j = 1; j < NT; j++) {
            if (j != NF + 1) m[2 * h] = fmaxf(m[2 * h], fmaxf(s[h][j][0], s[h][j][1]));
            m[2 * h + 1] = fmaxf(m[2 * h + 1], fmaxf(s[h][j][2], s[h][j][3]));
        }
    }
#pragma unroll
    for (int r = 0; r < 4; r++) m[r] = fmaxf(m[r], __shfl_xor_sync(0xffffffffu, m[r], 1));
#pragma unroll
    for (int r = 0; r < 4; r++) m[r] = fmaxf(m[r], __shfl_xor_sync(0xffffffffu, m[r], 2)) * -cs;
#pragma unroll
    for (int r = 0; r < 4; r++) {
        l[r] = 0.f;
#pragma unroll
        for (int j = 0; j < NT; j++)
            if ((r & 1) || j != NF + 1) {
                float* v = &s[r >> 1][j][2 * (r & 1)];
                v[0] = ex2(fmaf(v[0], cs, m[r])); v[1] = ex2(fmaf(v[1], cs, m[r]));
                l[r] += v[0] + v[1];
            }
    }
#pragma unroll
    for (int r = 0; r < 4; r++) l[r] += __shfl_xor_sync(0xffffffffu, l[r], 1);
#pragma unroll
    for (int r = 0; r < 4; r++) { l[r] += __shfl_xor_sync(0xffffffffu, l[r], 2); asm("rcp.approx.ftz.f32 %0, %0;" : "+f"(l[r])); }
    const uint32_t ma = sb ? 0u : ~0u;
#pragma unroll
    for (int h = 0; h < 2; h++)
#pragma unroll
        for (int j = 0; j < 5; j++) {
            const bool on = j == 4 || j < NF + 2;
            const int k = j == 4 ? NT - 1 : on ? j : 0, ia = j < 4 ? 2 * j : 16, ib = j < 4 ? 8 + 2 * j : 18;
            const uint32_t x = on && j != NF + 1 ? pack_bf16(s[h][k][0] * l[2 * h], s[h][k][1] * l[2 * h]) : 0;
            const uint32_t y = on ? pack_bf16(s[h][k][2] * l[2 * h + 1], s[h][k][3] * l[2 * h + 1]) : 0;
            asm volatile("and.b32 %0, %4, %6; and.b32 %1, %5, %6; and.b32 %2, %4, %7; and.b32 %3, %5, %7;"
                : "=&r"(p[h][ia]), "=&r"(p[h][ia + 1]), "=&r"(p[h][ib]), "=&r"(p[h][ib + 1]) : "r"(x), "r"(y), "r"(ma), "r"(~ma));
        }
}
__device__ __forceinline__ void attn_pv(float (&o)[64], const uint32_t (&p)[20], uint32_t sv) {
    const uint64_t dx = mkdesc(sv, 128, 1024, 0), dm = mkdesc(sv + 16384, 128, 256, 0);
    wg_fence();
#pragma unroll
    for (int ks = 0; ks < 5; ks++) wgmma_v128(o, p[4 * ks], p[4 * ks + 1], p[4 * ks + 2], p[4 * ks + 3], ks < 4 ? dx + ks * 16 : dm, ks);
    wg_commit();
}
__device__ __forceinline__ void attn_stage(const float (&o)[64], uint32_t dst) {
#pragma unroll
    for (int u = 0; u < 16; u += 2)
        stsm4(dst + (u >> 3) * 8192 + (u & 7) * 128, pack_bf16(o[4 * u], o[4 * u + 1]), pack_bf16(o[4 * u + 2], o[4 * u + 3]),
              pack_bf16(o[4 * u + 4], o[4 * u + 5]), pack_bf16(o[4 * u + 6], o[4 * u + 7]));
}

template <int BN, int NKB, bool BLOCKED_A>
__device__ __forceinline__ void mainloop(float (&acc)[BN / 2], uint32_t sb, int wgi, uint32_t full, uint32_t empty, int& it, bool elect) {
#pragma unroll
    for (int j = 0; j < BN / 2; j++) acc[j] = 0.f;
#pragma unroll 1
    for (int k4 = 0; k4 < NKB; k4 += 4) {
#pragma unroll
        for (int st = 0; st < 4; st++, it++) {
            mbar_wait_long(full + 8 * st, (it >> 2) & 1);
            const uint64_t da = BLOCKED_A ? mkdesc(sb + st * G_STAGE + wgi * 8192, 128, 1024, 0) : mkdesc(sb + st * G_STAGE + wgi * 8192, 16, 1024, 1);
            const uint64_t db = mkdesc(sb + st * G_STAGE + 16384, 8192, 1024, 1);
            wg_fence();
#pragma unroll
            for (int k = 0; k < 4; k++) {
                if constexpr (BN == 256) wgmma256(acc, da + k * (BLOCKED_A ? 16 : 2), db + k * 128, 1);
                else wgmma128(acc, da + k * (BLOCKED_A ? 16 : 2), db + k * 128, 1);
            }
            wg_commit();
            if (k4 | st) {
                wg_wait<1>();
                if (elect) mbar_arrive(empty + 8 * ((st + 3) & 3));
            }
        }
    }
    wg_wait<0>();
    if (elect) mbar_arrive(empty + 8 * 3);
}

__device__ __forceinline__ uint32_t n6_a(int st) { return st < 4 ? st * G_STAGE : (2 * st - 8) * G_STAGE + 32768; }
__device__ __forceinline__ uint32_t n6_b(int st) { return st < 4 ? st * G_STAGE + 16384 : (2 * st - 7) * G_STAGE + 32768; }
__device__ __forceinline__ uint32_t n6_bar(int st) { return st < 4 ? 8 * st : 96 + 8 * st; }
__device__ __forceinline__ void mainloop6(float (&acc)[64], uint32_t sb, int wgi, uint32_t full, uint32_t empty, int& it, bool elect) {
#pragma unroll
    for (int j = 0; j < 64; j++) acc[j] = 0.f;
    int st = 0, prev = 0, r = 0;
#pragma unroll 1
    for (int kb = 0; kb < 64; kb++) {
        mbar_wait_long(full + n6_bar(st), ((st < 4 ? it >> 2 : 0) + r) & 1);
        const uint64_t da = mkdesc(sb + n6_a(st) + wgi * 8192, 128, 1024, 0), db = mkdesc(sb + n6_b(st), 8192, 1024, 1);
        wg_fence();
#pragma unroll
        for (int k = 0; k < 4; k++) wgmma128(acc, da + k * 16, db + k * 128, 1);
        wg_commit();
        if (kb) {
            wg_wait<1>();
            if (elect) mbar_arrive(empty + n6_bar(prev));
        }
        prev = st;
        if (++st == 6) { st = 0; r++; }
    }
    wg_wait<0>();
    if (elect) mbar_arrive(empty + 8 * 3);
    it += 44;
}

template <int BN>
__device__ __forceinline__ void o_item(uint32_t sb, int wgi, int wi, int lane, uint32_t full, uint32_t empty, int& it, const CUtensorMap* mout,
                                       int row0, int col0, uint32_t stgpar) {
    float acc[BN / 2];
    if constexpr (BN == 256) mainloop<BN, 64, true>(acc, sb, wgi, full, empty, it, lane == 0);
    else mainloop6(acc, sb, wgi, full, empty, it, lane == 0);
    ST((row0 >> 4) + (col0 / BN), wgi * 4 + wi, 10);
    mbar_wait(full + 104, stgpar);
    const uint32_t stg = sb + G_STG + (wgi * 4 + wi) * 4096;
    const int r = lane & 15, cu = lane >> 4;
#pragma unroll
    for (int hf = 0; hf < BN / 128; hf++) {
        if (elect()) asm volatile("cp.async.bulk.wait_group.read 0;" ::: "memory");
        __syncwarp();
#pragma unroll
        for (int j = 0; j < 8; j++) {
            const float* a = acc + hf * 64 + j * 8;
            stsm4(stg + (j >> 2) * 2048 + r * 128 + ((((j & 3) * 2 + cu) ^ (r & 7)) << 4),
                  pack_bf16(a[0], a[1]), pack_bf16(a[2], a[3]), pack_bf16(a[4], a[5]), pack_bf16(a[6], a[7]));
        }
        asm volatile("fence.proxy.async.shared::cta;" ::: "memory");
        __syncwarp();
        if (elect()) {
            tma2d_store(mout, stg, col0 + hf * 128, row0 + wgi * 64 + wi * 16);
            tma2d_store(mout, stg + 2048, col0 + hf * 128 + 64, row0 + wgi * 64 + wi * 16);
            asm volatile("cp.async.bulk.commit_group;" ::: "memory");
        }
    }
}

constexpr int S4_KD = 32768;
constexpr int S4_CH = 2 * G_STAGE;
constexpr int S4_HALF = 2304;
constexpr int S4_WD = 2 * S4_HALF;
constexpr int S4_T2 = S4_WD + 2304;
constexpr int S4_T3 = S4_T2 + 1024;
constexpr int S4_STRIDE = S4_T3 + 640 + 16;
__device__ __forceinline__ uint32_t addz(uint32_t x, uint32_t z) { uint32_t r; asm volatile("add.u32 %0, %1, %2;" : "=r"(r) : "r"(x), "r"(z)); return r; }
__device__ __forceinline__ uint32_t lds16(uint32_t a) { uint32_t v; asm volatile("ld.shared.u16 %0, [%1];" : "=r"(v) : "r"(a) : "memory"); return v; }
__device__ __forceinline__ uint32_t ldsu(uint32_t a) { return __float_as_uint(lds32(a)); }

template <int E0, int NE, int KP>
__device__ __forceinline__ void s4_windows(float (&acc)[8][2][4], uint32_t ut, uint32_t tw, int rho, int w, int lane, uint32_t z) {
    const int gt = (lane >> 2) - 2 * (lane & 3), p0 = rho == 16 ? -3 : -2, c = (lane >> 3) + p0;
    uint32_t band[2][4], ta[NE][4];
    {
        const uint64_t ones = ((uint64_t)((2u << 2 * w) - 1) << 32) >> (8 * p0 + 24 - gt + rho + w);
        uint32_t f[5];
#pragma unroll
        for (int m = 0; m < 5; m++) f[m] = ((((uint32_t)(ones >> (8 * m)) & 3) * 0x8001u) & 0x10001u) * 0x3F80u;
#pragma unroll
        for (int j = 0; j < 2; j++) { band[j][0] = f[2 * j + 1]; band[j][1] = addz(f[2 * j], z); band[j][2] = f[2 * j + 2]; band[j][3] = addz(f[2 * j + 1], z); }
    }
#pragma unroll
    for (int e = 0; e < NE; e++)
        asm volatile("ld.shared.u32 %0, [%4]; ld.shared.u32 %1, [%4+%5]; ld.volatile.shared.u32 %2, [%4+%6]; ld.volatile.shared.u32 %3, [%4];"
            : "=r"(ta[e][0]), "=r"(ta[e][1]), "=r"(ta[e][2]), "=r"(ta[e][3]) : "r"(tw + 16 * (E0 + e) * KP), "n"(8 * KP), "n"(-8 * KP) : "memory");
    const uint32_t ua = ut + (c & 1) * S4_HALF + (16 + (lane & 7) + (c >> 1)) * 16;
#pragma unroll
    for (int J = 0; J < 8 - E0; J++) {
        uint32_t u0[4], u1[4];
        ldsm4(u0, ua + J * 256); ldsm4(u1, ua + J * 256 + 128);
        float s0[4], s1[4];
        mma16z(s0, band[0], u0[0], u0[1]); mma16z(s1, band[0], u1[0], u1[1]);
        mma16(s0, band[1], u0[2], u0[3]); mma16(s1, band[1], u1[2], u1[3]);
        const uint32_t b00 = pack_bf16(s0[0], s0[1]), b01 = pack_bf16(s1[0], s1[1]), b10 = pack_bf16(s0[2], s0[3]), b11 = pack_bf16(s1[2], s1[3]);
#pragma unroll
        for (int e = 0; e < NE; e++)
            if (J + E0 + e < 8) { mma16(acc[J + E0 + e][0], ta[e], b00, b01); mma16(acc[J + E0 + e][1], ta[e], b10, b11); }
    }
}
template <int D0, int D1>
__device__ __forceinline__ void s4_dense(float (&acc)[8][2][4], uint32_t ua, const uint32_t (&b0)[4], const uint32_t (&b1)[4]) {
#pragma unroll
    for (int J = 0; J < 8 - D0; J++) {
        uint32_t a[4];
        ldsm4(a, ua + J * 256);
        mma16(acc[J + D0][0], a, b0[0], b0[1]); mma16(acc[J + D0][1], a, b0[2], b0[3]);
        if (J + D1 < 8) { mma16(acc[J + D1][0], a, b1[0], b1[1]); mma16(acc[J + D1][1], a, b1[2], b1[3]); }
    }
}
__device__ __forceinline__ void s4_words(uint32_t (&b)[4], uint32_t wd) {
    asm volatile("ld.shared.u32 %0, [%4]; ld.shared.u32 %1, [%4+-32]; ld.shared.u32 %2, [%4+32]; ld.volatile.shared.u32 %3, [%4];"
        : "=r"(b[0]), "=r"(b[1]), "=r"(b[2]), "=r"(b[3]) : "r"(wd) : "memory");
}

__device__ __forceinline__ void s4_item(uint32_t sb, int cw, int lane, int item, const bf16* __restrict__ dsk, uint32_t empty, const CUtensorMap* my, uint32_t stgpar,
                                        bf16* __restrict__ out, uint32_t nbar, uint32_t npar, uint32_t nslot) {
    const int gt = (lane >> 2) - 2 * (lane & 3);
    const uint32_t ch = sb + S4_CH + cw * S4_STRIDE, kd = sb + S4_KD + cw * 1536;
    const __nv_bfloat162 dk = __bfloat162bfloat162(dsk[item * 8 + cw]);
    ST(item, cw, 0);
    asm volatile("st.shared.v4.u32 [%0], {%1,%1,%1,%1};" ::"r"(ch + (lane >> 4) * S4_HALF + (lane & 15) * 16), "r"(0) : "memory");
    const uint32_t tch = sb + S4_CH + (lane & 7) * S4_STRIDE + ((lane >> 3) & 1) * S4_HALF + (16 + 16 * cw + (lane >> 4)) * 16;
#pragma unroll
    for (int i = 0; i < 8; i++) {
        uint32_t x[4];
        ldsm4t(x, sb + cw * 4096 + i * 512 + lane * 16);
        stsm4(tch + i * 32, x[0], x[1], x[2], x[3]);
    }
    const uint32_t k1024 = lds16(kd + 1024);
    {
        auto st4 = [](uint32_t a, uint32_t x, uint32_t y, uint32_t u, uint32_t v) {
            asm volatile("st.shared.v4.u32 [%0], {%1,%2,%3,%4};" ::"r"(a), "r"(x), "r"(y), "r"(u), "r"(v) : "memory");
        };
        const float4 p = lds128(kd + lane * 16);
        const uint32_t p0 = __float_as_uint(p.x), p1 = __float_as_uint(p.y), p2 = __float_as_uint(p.z), p3 = __float_as_uint(p.w);
        const uint32_t pm = lane ? ldsu(kd + lane * 16 - 4) : 0;
        const uint32_t wa = ch + S4_WD + 64 + lane * 32;
        st4(wa, __byte_perm(p0, pm, 0x7610), __byte_perm(p0, 0, 0x1032), __byte_perm(p1, p0, 0x7610), __byte_perm(p1, 0, 0x1032));
        st4(wa + 16, __byte_perm(p2, p1, 0x7610), __byte_perm(p2, 0, 0x1032), __byte_perm(p3, p2, 0x7610), __byte_perm(p3, 0, 0x1032));
        const float2 q = lds64(kd + 512 + lane * 8);
        const uint32_t q0 = __float_as_uint(q.x), q1 = __float_as_uint(q.y), q2 = ldsu(kd + 520 + lane * 8), k255 = ldsu(kd + 508);
        st4(wa + 1024, lane ? __byte_perm(q0, 0, 0x1010) : __byte_perm(q0, k255, 0x7610), __byte_perm(q0, 0, 0x1010), __byte_perm(q0, 0, 0x1032), __byte_perm(q1, q0, 0x7610));
        st4(wa + 1040, __byte_perm(q1, 0, 0x1010), __byte_perm(q1, 0, 0x1010), __byte_perm(q1, 0, 0x1032), __byte_perm(q2, q1, 0x7610));
        const uint32_t k512 = lane == 4 ? lds16(kd + 768) : 0;
        if (lane < 16) st4(ch + S4_WD + (lane < 4 ? 0 : 2048) + lane * 16, k512 * 0x10001u, k512 * 0x10001u, k512 * 0x10001u, k512 << 16);
        const float2 c = lds64(kd + 768 + lane * 8), d = lds64(kd + 760 + lane * 8);
        const uint32_t c0 = __float_as_uint(c.x), c1 = __float_as_uint(c.y), c2 = ldsu(kd + 776 + lane * 8);
        const uint32_t d0 = lane ? __float_as_uint(d.x) : 0, d1 = lane ? __float_as_uint(d.y) : 0, d2 = lane ? c0 : 0;
        st4(ch + S4_T2 + 256 + lane * 16, __byte_perm(c0, d0, 0x7632), __byte_perm(c1, d1, 0x5410), __byte_perm(c1, d1, 0x7632), __byte_perm(c2, d2, 0x5410));
        const uint32_t m = lane == 31 ? 0xFFFF0000u : 0;
        st4(ch + S4_T2 + (lane < 16 ? lane : lane == 31 ? 48 : lane + 33) * 16, c0 & m, (c1 << 16) & m, c1 & m, (c2 << 16) & m);
        const float2 e = lds64(kd + 1024 + lane * 8);
        const uint32_t e0 = __float_as_uint(e.x), e1 = __float_as_uint(e.y), e2 = ldsu(kd + 1032 + lane * 8), em = ldsu(kd + 1020 + lane * 8);
        st4(ch + S4_T3 + 128 + lane * 16, __byte_perm(e0, lane ? em : 0, 0x7632), __byte_perm(e1, lane ? e0 : 0, 0x5410), __byte_perm(e1, e0, 0x7632), __byte_perm(e2, e1, 0x5410));
        if (lane < 8) st4(ch + S4_T3 + lane * 16, 0, 0, 0, 0);
    }
    bar_sync(2, 256);
    ST(item, cw, 1);
    const uint32_t z = ldsu(ch);
    float acc[8][2][4];
#pragma unroll
    for (int j = 0; j < 16; j++) acc[j >> 1][j & 1][0] = acc[j >> 1][j & 1][1] = acc[j >> 1][j & 1][2] = acc[j >> 1][j & 1][3] = 0.f;
#pragma unroll 1
    for (int r = 1; r <= 4; r++) s4_windows<2, 3, 16>(acc, ch, ch + S4_T2 + (gt - 16) * 16 + 4 * r - 4, 4 * r, 2 - (r & 1), lane, z);
    ST(item, cw, 2);
#pragma unroll 1
    for (int r = 1; r <= 2; r++) s4_windows<4, 4, 8>(acc, ch, ch + S4_T3 + (gt - 48) * 8 + 4 * r - 4, 8 * r, 2 + r, lane, z);
    ST(item, cw, 3);
    const uint32_t ua = ch + (lane >> 4) * S4_HALF + (16 + (lane & 15)) * 16, wd = ch + S4_WD + 64 + gt * 4;
#pragma unroll 1
    for (int q = 0; q < 2; q++) {
        uint32_t b0[4], b1[4];
        s4_words(b0, wd + (q + 32) * 64);
#pragma unroll
        for (int j = 0; j < 4; j++) {
            const int x = 16 * q + gt + (j == 1 ? -8 : j == 2 ? 8 : 0) - 3;
            b1[j] = addz(((unsigned)x < 2u ? k1024 : 0u) | ((unsigned)(x - 1) < 2u ? k1024 << 16 : 0u), z);
        }
        s4_dense<2, 4>(acc, ua - q * 16, b0, b1);
    }
    {
        uint32_t b0[4], b1[4], c0[4], c1[4];
        s4_words(b0, wd); s4_words(b1, wd + 1024);
#pragma unroll 1
        for (int q = 0; q < 16; q += 2) {
            s4_words(c0, wd + q * 64 + 64); s4_words(c1, wd + q * 64 + 64 + 1024);
            s4_dense<0, 1>(acc, ua - q * 16, b0, b1);
            s4_words(b0, wd + q * 64 + 128); s4_words(b1, wd + q * 64 + 128 + 1024);
            s4_dense<0, 1>(acc, ua - q * 16 - 16, c0, c1);
            if (q == S4REL && lane == 0) { mbar_arrive(empty); mbar_arrive(empty + 8); }
        }
    }
    ST(item, cw, 4);
    mbar_wait(empty + 72, stgpar);
    if (elect()) asm volatile("cp.async.bulk.wait_group.read 0;" ::: "memory");
    __syncwarp();
#pragma unroll
    for (int I = 0; I < 8; I++) {
        uint32_t u[4];
        ldsm4(u, ua + I * 256);
#pragma unroll
        for (int j = 0; j < 4; j++) {
            const uint32_t y = pack_bf16(acc[I][j >> 1][2 * (j & 1)], acc[I][j >> 1][2 * (j & 1) + 1]);
            const __nv_bfloat162 r = __hadd2_rn(*(const __nv_bfloat162*)&y, __hmul2_rn(*(const __nv_bfloat162*)&u[j], dk));
            u[j] = *(const uint32_t*)&r;
        }
        stsm4(ua + I * 256, u[0], u[1], u[2], u[3]);
    }
    bar_sync(2, 256);
    uint32_t y[8][4];
#pragma unroll
    for (int i = 0; i < 8; i++) ldsm4t(y[i], tch + i * 32);
    if (cw < S4DIR && mbar_test(nbar, npar) && ldsu(nslot) == (IT_END << 16)) {
        uint32_t* const dst = (uint32_t*)(out + (size_t)(cw * 256 + (lane >> 2)) * (2 * DM) + DM + item * 8) + (lane & 3);
#pragma unroll
        for (int i = 0; i < 32; i++) dst[i * 8 * DM] = y[i >> 2][i & 3];
        return;
    }
#pragma unroll
    for (int i = 0; i < 8; i++) stsm4(sb + G_STG + cw * 4096 + i * 512 + lane * 16, y[i][0], y[i][1], y[i][2], y[i][3]);
    asm volatile("fence.proxy.async.shared::cta;" ::: "memory");
    __syncwarp();
    if (elect()) {
        mbar_arrive(empty + 16); mbar_arrive(empty + 24);
        tma2d_store(my, sb + G_STG + cw * 4096, DM + item * 8, cw * 256);
        asm volatile("cp.async.bulk.commit_group;" ::: "memory");
    }
    ST(item, cw, 5);
}

struct Maps { CUtensorMap m[13]; };
__global__ void __launch_bounds__(384, 1)
worker_kernel(const __grid_constant__ Maps M, const bf16* __restrict__ dsk, bf16* __restrict__ out) {
    const CUtensorMap &mx = M.m[0], &mq = M.m[1], &mo = M.m[4], &mout = M.m[5], &mu = M.m[6], &my = M.m[7];
    extern __shared__ unsigned char smem_raw[];
    const uint32_t sb = (smem_u32(smem_raw) + 1023) & ~1023u;
    const uint32_t full = sb + G_BAR, empty = full + 32, ifull = full + 64, iempty = full + 80, islot = full + 96, stgbar = full + 104, sigbar = full + 112, sigslot = full + 120;
    const int tid = threadIdx.x, wg = tid >> 7, lane = tid & 31;
    int q0 = blockIdx.x;
    const int nfirst = min(32, (int)gridDim.x - 96), wide0 = q0 - ((int)gridDim.x - N_LATE);
    if (tid == 0 && q0 >= nfirst && wide0 < 0) q0 = nfirst + atomicAdd(g_ctr + C_NEXT, 1);
    if ((tid >> 5) == 1 && elect()) {
#pragma unroll
        for (int i = 0; i < 6; i++) { mbar_init(full + n6_bar(i), 1); mbar_init(empty + n6_bar(i), 8); }
#pragma unroll
        for (int i = 0; i < 2; i++) { mbar_init(ifull + 8 * i, 1); mbar_init(iempty + 8 * i, 8); }
        mbar_init(sigbar, 8); mbar_init(stgbar, 1);
        asm volatile("fence.mbarrier_init.release.cluster;" ::: "memory");
    }
    if ((tid >> 5) == 2 && elect()) {
#pragma unroll
        for (int i = 0; i < 13; i++) asm volatile("prefetch.tensormap [%0];" ::"l"(&M.m[i]) : "memory");
    }
    __syncthreads();
    if (wg == 0) {
        reg_dec<40>();
        if (tid >= 32 && tid < 64) {
            for (int n = 0;; n++) {
                mbar_wait_long(sigbar, n & 1);
                int item; asm volatile("ld.shared.u32 %0, [%1];" : "=r"(item) : "r"(sigslot + 4 * (n & 1)) : "memory");
                const int type = item >> 16, b = (item >> 8) & 255, i = item & 255;
                if (type == IT_END) break;
                if (type == IT_QA) {
                    if (elect()) {
#pragma unroll
                        for (int j = 0; j < 8; j++) {
                            const uint32_t src = sb + (j >= 4 ? G_STG + (j & 1) * 16384 : 3 * G_STAGE + (j & 1) * 20480) + ((j >> 1) & 1) * 8192;
                            asm volatile("cp.async.bulk.global.shared::cta.bulk_group [%0], [%1], 8192;"
                                ::"l"(g_ox + (size_t)(b * 64 + i * 4 + ((j >> 1) ^ 2)) * 8192 + (j & 1) * 4096), "r"(src) : "memory");
                            if ((j & 3) == 3) asm volatile("cp.async.bulk.commit_group;" ::: "memory");
                        }
                        asm volatile("cp.async.bulk.wait_group.read 1;" ::: "memory");
                        asm volatile("mbarrier.arrive.shared.b64 _, [%0], 8;" ::"r"(empty + 24) : "memory");
                        asm volatile("cp.async.bulk.wait_group 0;" ::: "memory");
                        mbar_arrive(stgbar);
                        asm volatile("fence.proxy.async.global;" ::: "memory");
                    }
                    __syncwarp();
                }
                if (type == IT_KV) { if (lane < 6) red_release(g_kvf + ((i & 15) * 6 + lane) * 16 + b, 1); }
                else if (lane == 0) red_release(g_ctr + C_QA_DONE + b, 1 << i);
            }
        } else if (tid < 32) {
            int it = 0;
            bool tables = false;
            if (!KVN) asm volatile("griddepcontrol.wait;" ::: "memory");
            for (int n = 0;; n++) {
                int item = 0;
                if (lane == 0) {
                    if (n) q0 = nfirst + atomicAdd(g_ctr + C_NEXT, 1);
                    item = n == 0 && wide0 >= 0 ? late_item(wide0) : queue_item(q0);
                }
                item = __shfl_sync(0xffffffffu, item, 0);
                mbar_wait(iempty + 8 * (n & 1), ((n >> 1) & 1) ^ 1);
                if (lane == 0) {
                    asm volatile("st.shared.u32 [%0], %1;" ::"r"(islot + 4 * (n & 1)), "r"(item) : "memory");
                    mbar_arrive(ifull + 8 * (n & 1));
                }
                const int type = item >> 16, b = (item >> 8) & 255, i = item & 255;
                bool ready = false;
                if (type == IT_QA || type == IT_KV) {
                    const CUtensorMap* mw = &mq + (type == IT_QA ? 0 : 1 + (i >> 4));
#pragma unroll 1
                    for (int kb = 0; kb < 16; kb++, it++) {
                        const int st = it & 3;
                        mbar_wait(empty + 8 * st, ((it >> 2) & 1) ^ 1);
                        if (elect()) {
                            mbar_expect(full + 8 * st, G_STAGE);
                            tma2d(sb + st * G_STAGE, &mx, kb * 64, b * 128, full + 8 * st);
                            tma3d(sb + st * G_STAGE + 16384, mw, 0, kb * 64, (i & 15) * 4, full + 8 * st);
                        }
                        if (type == IT_QA && kb == 3) ready = __all_sync(0xffffffffu, ld_acq(g_ctr + C_CHAIN + b) >= 96);
                        if (ready && kb < 11 && elect()) {
                            const size_t sh = (b * 4 + ((kb - 3) & 3)) * NH + i * 2;
                            asm volatile("cp.async.bulk.prefetch.L2.global [%0], 16384;" ::"l"((kb >= 7 ? g_vx : g_kx) + sh * 4096) : "memory");
                            asm volatile("cp.async.bulk.prefetch.L2.global [%0], 4096;" ::"l"((kb >= 7 ? g_vm : g_km) + sh * 1024) : "memory");
                        }
                    }
                }
                if (type == IT_QA) {
                    if (b == 15) asm volatile("griddepcontrol.wait;" ::: "memory");
                    else if (!ready) wait_ctr(g_ctr + C_CHAIN + b, 96);
                    tables = true;
                    asm volatile("fence.proxy.async.global;" ::: "memory");
#pragma unroll 1
                    for (int st = 0; st < 4; st++, it++) {
                        mbar_wait(empty + 8 * st, ((it >> 2) & 1) ^ 1);
                        if (elect()) {
                            mbar_expect(full + 8 * st, 4 * 10240);
#pragma unroll
                            for (int j = 0; j < 4; j++)
                                tma3d(sb + st * G_STAGE + (j >> 1) * 20480 + (j & 1) * 16384, &M.m[8 + (st >> 1) + (j & 1) * 2], 0, b * 4 + (j & 2),
                                      (i * 2 + (st & 1)) * 16, full + 8 * st);
                        }
                    }
                } else if (type == IT_O) {
                    const bool wide = b < O_WIDE;
                    const CUtensorMap* mw = wide ? &mo : &M.m[12];
                    int done = 0;
                    const int ns = wide ? 4 : 6;
#pragma unroll 1
                    for (int kb = 0, st = 0, r = 0; kb < 64; kb++) {
                        const uint32_t bo = n6_bar(st);
                        mbar_wait(empty + bo, (((st < 4 ? it >> 2 : 0) + r) & 1) ^ 1);
                        if (elect()) {
                            mbar_expect(full + bo, wide ? G_STAGE : 32768);
                            tma3d(sb + n6_b(st), mw, 0, kb * 64, wide ? i * 4 : i * 2, full + bo);
                        }
                        if (!(done >> (kb >> 2) & 1)) {
#pragma unroll 1
                            for (int sp = 0; sp < (1 << 20) && !((done = __shfl_sync(0xffffffffu, ld_acq(g_ctr + C_QA_DONE + b), 0)) >> (kb >> 2) & 1); sp++)
                                __nanosleep(64);
                            asm volatile("fence.proxy.async.global;" ::: "memory");
                        }
                        if (elect()) bulk_load(sb + n6_a(st), g_ox + (size_t)(b * 64 + kb) * 8192, 16384, full + bo);
                        if (++st == ns) { st = 0; r++; }
                    }
                    it += wide ? 64 : 44;
                } else if (type == IT_S4) {
                    mbar_wait(empty, ((it >> 2) & 1) ^ 1);
                    if (elect()) {
                        mbar_expect(full, 32768 + 12288);
#pragma unroll
                        for (int j = 0; j < 8; j++) tma2d(sb + j * 4096, &mu, i * 8, j * 256, full);
                    }
                    if (!tables) { wait_ctr(g_ctr + C_CHAIN, 96); asm volatile("fence.proxy.async.global;" ::: "memory"); }
                    tables = true;
                    if (elect()) bulk_load(sb + S4_KD, g_kd + i * 8 * 768, 12288, full);
#pragma unroll 1
                    for (int st = 1; st < 4; st++) { mbar_wait(empty + 8 * st, ((it >> 2) & 1) ^ 1); if (lane == 0) mbar_arrive(full + 8 * st); }
                    it += 4;
                    mbar_wait_long(empty, ((it >> 2) & 1) ^ 1);
                }
                if (item >> 16 == IT_END) break;
            }
            asm volatile("griddepcontrol.wait;" ::: "memory");
        }
    } else {
        reg_inc<232>();
        const int wu = __shfl_sync(0xffffffffu, tid >> 5, 0);
        const int wgi = (wu >> 2) - 1, wi = wu & 3;
        int it = 0, nqa = 0, nsig = 0, n = 0, item;
        auto next_item = [&]() {
            mbar_wait_long(ifull + 8 * (n & 1), (n >> 1) & 1);
            asm volatile("ld.shared.u32 %0, [%1];" : "=r"(item) : "r"(islot + 4 * (n & 1)) : "memory");
            __syncwarp();
            if (lane == 0) mbar_arrive(iempty + 8 * (n & 1));
        };
        auto signal = [&](int what) {
            if (tid == 128) asm volatile("st.shared.u32 [%0], %1;" ::"r"(sigslot + 4 * (nsig & 1)), "r"(what) : "memory");
            __syncwarp();
            if (lane == 0) mbar_arrive(sigbar);
            nsig++;
        };
        next_item();
        if (item >> 16 == IT_KV) {
            float acc[128];
            uint32_t pk[64];
            uint32_t* dst = nullptr;
            int prev = 0;
            do {
                WLOG(0);
#pragma unroll
                for (int kb = 0; kb < 16; kb++, it++) {
                    const int st = kb & 3;
                    mbar_wait(full + 8 * st, (it >> 2) & 1);
                    const uint64_t da = mkdesc(sb + st * G_STAGE + wgi * 8192, 16, 1024, 1);
                    const uint64_t db = mkdesc(sb + st * G_STAGE + 16384, 8192, 1024, 1);
                    wg_fence();
#pragma unroll
                    for (int k = 0; k < 4; k++) wgmma256(acc, da + k * 2, db + k * 128, kb | k);
                    wg_commit();
                    if (n <= KVI) {
                        if (kb < KVF && dst) {
#pragma unroll
                            for (int j = kb * (64 / KVF); j < (kb + 1) * (64 / KVF); j++) dst[(j >> 1) * 128 + (j & 1) * 32] = pk[j];
                            if (kb == KVF - 1) signal(prev);
                        }
                    } else if (kb < KVS) {
#pragma unroll
                        for (int j = kb * (64 / KVS); j < (kb + 1) * (64 / KVS); j++) dst[(j >> 1) * 128 + (j & 1) * 32] = pk[j];
                        if (kb == KVS - 1) signal(prev);
                    }
                    if (kb > 0) {
                        wg_wait<1>();
                        if (lane == 0) mbar_arrive(empty + 8 * ((kb - 1) & 3));
                    }
                }
                wg_wait<0>();
                if (lane == 0) mbar_arrive(empty + 8 * 3);
#pragma unroll
                for (int j = 0; j < 64; j++) pk[j] = pack_bf16(acc[2 * j], acc[2 * j + 1]);
                const int row = ((item >> 8) & 255) * 128 + wgi * 64 + wi * 16, nt = item & 255;
                dst = (uint32_t*)(nt < 16 ? g_kx : g_vx) + (size_t)((row >> 5) * 512 + (nt & 15) * 32) * 128 + (row & 31) * 4 + lane;
                prev = item;
                WLOG(1);
                n++;
                next_item();
            } while (item >> 16 == IT_KV);
            if (dst) {
#pragma unroll
                for (int j = 0; j < 64; j++) dst[(j >> 1) * 128 + (j & 1) * 32] = pk[j];
                signal(prev);
            }
        }
        for (;; n++, next_item()) {
            const int type = item >> 16, b = (item >> 8) & 255, i = item & 255;
            const int lane = (tid & 31) + (item >> 24), wgi = (wu >> 2) - 1 + __shfl_sync(0xffffffffu, item >> 24, 0), wi = wu & 3;
            WLOG(0);
            if (type == IT_QA) {
                float acc[128];
                ST(sid, cw, 0);
                ST(sid, cw, 1);
                mainloop<256, 16, false>(acc, sb, wgi, full, empty, it, lane == 0);
                ST(sid, cw, 2);
                uint32_t q0[32], q1[32];
#pragma unroll
                for (int j = 0; j < 32; j++) q0[j] = pack_bf16(acc[2 * j], acc[2 * j + 1]);
                const uint32_t par = (it >> 2) & 1, so = sb + wgi * 20480;
                float sx[2][32] = {}, sm[2][8] = {};
                uint32_t p[2][20];
                mbar_wait_long(full, par);
                ST(sid, cw, 3);
                if (wgi == 0) bar_sync(5, 256);
                attn_scores(sx[0], sm[0], q0, so);
                ST(sid, cw, 7);
#pragma unroll
                for (int j = 0; j < 32; j++) asm volatile("cvt.rn.bf16x2.f32 %0, %1, %2;" : "=r"(q1[j]) : "f"(acc[65 + 2 * j]), "f"(acc[64 + 2 * j]));
                mbar_wait(full + 8, par);
                attn_scores(sx[1], sm[1], q1, so + G_STAGE);
                if (wgi == 1) bar_arrive(5, 256);
                if (elect()) asm volatile("cp.async.bulk.wait_group.read 0;" ::: "memory");
                mbar_wait(stgbar, (nqa++ & 1) ^ 1);
                bar_sync(3 + wgi, 128);
                float o0[64] = {}, o1[64] = {};
                wg_wait<0>();
                ST(sid, cw, 9);
                if (lane == 0) { mbar_arrive(empty); mbar_arrive(empty + 8); }
                if (wi & 1) attn_softmax<true>(p, sx, sm, wi >= 2, lane);
                else attn_softmax<false>(p, sx, sm, wi >= 2, lane);
                ST(sid, cw, 10);
                mbar_wait(full + 16, par);
                attn_pv(o0, p[0], so + 2 * G_STAGE);
                mbar_wait(full + 24, par);
                attn_pv(o1, p[1], so + 3 * G_STAGE);
                wg_wait<1>();
                if (lane == 0) mbar_arrive(empty + 16);
                ST(sid, cw, 5);
                const uint32_t da = (wi * 2 + ((lane >> 3) & 1)) * 1024 + (lane >> 4) * 128 + (lane & 7) * 16;
                attn_stage(o0, sb + G_STG + wgi * 16384 + da);
                wg_wait<0>();
                bar_sync(3 + wgi, 128);
                attn_stage(o1, so + 3 * G_STAGE + da);
                asm volatile("fence.proxy.async.shared::cta;" ::: "memory");
                ST(sid, cw, 6);
                signal(item);
                it += 4;
            } else if (type == IT_O) {
                ST(b * 8 + i, wgi * 4 + wi, 8);
                mbar_wait_long(full, (it >> 2) & 1);
                ST(b * 8 + i, wgi * 4 + wi, 9);
                if (b < O_WIDE) o_item<256>(sb, wgi, wi, lane, full, empty, it, &mout, b * 128, i * 256, (nqa & 1) ^ 1);
                else o_item<128>(sb, wgi, wi, lane, full, empty, it, &mout, b * 128, i * 128, (nqa & 1) ^ 1);
            } else if (type == IT_S4) {
                mbar_wait_long(full, (it >> 2) & 1);
                mbar_wait(full + 24, (it >> 2) & 1);
                s4_item(sb, wgi * 4 + wi, lane, i, dsk, empty, &my, (nqa & 1) ^ 1, out, ifull + 8 * ((n + 1) & 1), ((n + 1) >> 1) & 1, islot + 4 * ((n + 1) & 1));
                it += 4;
            } else break;
            WLOG(1);
        }
        bar_sync(2, 256);
        signal(item);
        if (elect()) asm volatile("cp.async.bulk.wait_group 0;" ::: "memory");
    }
}

typedef CUresult (*EncodeFn)(CUtensorMap*, CUtensorMapDataType, cuuint32_t, void*, const cuuint64_t*, const cuuint64_t*, const cuuint32_t*,
                             const cuuint32_t*, CUtensorMapInterleave, CUtensorMapSwizzle, CUtensorMapL2promotion, CUtensorMapFloatOOBfill);
static EncodeFn get_encode() {
    void* fn = nullptr; cudaDriverEntryPointQueryResult st;
    cudaGetDriverEntryPoint("cuTensorMapEncodeTiled", &fn, cudaEnableDefault, &st);
    return (EncodeFn)fn;
}
static void map_act(EncodeFn enc, CUtensorMap* m, const void* p, int rows, int cols, int boxr) {
    cuuint64_t dim[2] = {(cuuint64_t)cols, (cuuint64_t)rows}, str[1] = {(cuuint64_t)cols * 2};
    cuuint32_t box[2] = {64, (cuuint32_t)boxr}, es[2] = {1, 1};
    enc(m, CU_TENSOR_MAP_DATA_TYPE_BFLOAT16, 2, (void*)p, dim, str, box, es, CU_TENSOR_MAP_INTERLEAVE_NONE, CU_TENSOR_MAP_SWIZZLE_128B,
        CU_TENSOR_MAP_L2_PROMOTION_L2_128B, CU_TENSOR_MAP_FLOAT_OOB_FILL_NONE);
}
static void map_w(EncodeFn enc, CUtensorMap* m, const void* p, int k, int n, int groups = 4) {
    cuuint64_t dim[3] = {64, (cuuint64_t)k, (cuuint64_t)n / 64}, str[2] = {(cuuint64_t)n * 2, 128};
    cuuint32_t box[3] = {64, 64, (cuuint32_t)groups}, es[3] = {1, 1, 1};
    enc(m, CU_TENSOR_MAP_DATA_TYPE_BFLOAT16, 3, (void*)p, dim, str, box, es, CU_TENSOR_MAP_INTERLEAVE_NONE, CU_TENSOR_MAP_SWIZZLE_128B,
        CU_TENSOR_MAP_L2_PROMOTION_L2_256B, CU_TENSOR_MAP_FLOAT_OOB_FILL_NONE);
}

static void map_kv(EncodeFn enc, CUtensorMap* m, void* p, int n) {
    cuuint64_t dim[3] = {(cuuint64_t)n, NSEG, 512}, str[2] = {(cuuint64_t)n * 1024, (cuuint64_t)n * 2};
    cuuint32_t box[3] = {(cuuint32_t)n, 2, 16}, es[3] = {1, 1, 1};
    enc(m, CU_TENSOR_MAP_DATA_TYPE_BFLOAT16, 3, p, dim, str, box, es, CU_TENSOR_MAP_INTERLEAVE_NONE, CU_TENSOR_MAP_SWIZZLE_NONE,
        CU_TENSOR_MAP_L2_PROMOTION_NONE, CU_TENSOR_MAP_FLOAT_OOB_FILL_NONE);
}
static void map_box(EncodeFn enc, CUtensorMap* m, const void* p, int rows, int ld, int boxc, int boxr, CUtensorMapSwizzle sw,
                    CUtensorMapL2promotion promo = CU_TENSOR_MAP_L2_PROMOTION_NONE) {
    cuuint64_t dim[2] = {(cuuint64_t)ld, (cuuint64_t)rows}, str[1] = {(cuuint64_t)ld * 2};
    cuuint32_t box[2] = {(cuuint32_t)boxc, (cuuint32_t)boxr}, es[2] = {1, 1};
    enc(m, CU_TENSOR_MAP_DATA_TYPE_BFLOAT16, 2, (void*)p, dim, str, box, es, CU_TENSOR_MAP_INTERLEAVE_NONE, sw,
        promo, CU_TENSOR_MAP_FLOAT_OOB_FILL_NONE);
}

extern "C" void kernel_launch(void* const* d_in, const int* in_sizes, int n_in, void* d_out, int out_size) {
    const bf16* x = (const bf16*)d_in[0];
    const bf16* mem0 = (const bf16*)d_in[1];
    const bf16 *Wq = (const bf16*)d_in[2], *Wk = (const bf16*)d_in[3], *Wv = (const bf16*)d_in[4], *Wo = (const bf16*)d_in[5];
    static EncodeFn enc = nullptr;
    static int nsm = 0;
    static void* kv[4];
    if (!enc) {
        enc = get_encode();
        cudaGetSymbolAddress(&kv[0], g_kx); cudaGetSymbolAddress(&kv[1], g_vx); cudaGetSymbolAddress(&kv[2], g_km); cudaGetSymbolAddress(&kv[3], g_vm);
        cudaDeviceGetAttribute(&nsm, cudaDevAttrMultiProcessorCount, 0);
        cudaFuncSetAttribute(chain_kernel, cudaFuncAttributeMaxDynamicSharedMemorySize, CH_SMEM);
        cudaFuncSetAttribute(worker_kernel, cudaFuncAttributeMaxDynamicSharedMemorySize, G_SMEM);
    }
    Maps M;
    CUtensorMap &mx = M.m[0], &mq = M.m[1], &mk = M.m[2], &mv = M.m[3], &mo = M.m[4], &mout = M.m[5], &mu = M.m[6], &my = M.m[7];
    map_act(enc, &mx, x, S_LEN, DM, 128);
    map_w(enc, &mq, Wq, DM, HD); map_w(enc, &mk, Wk, DM, HD); map_w(enc, &mv, Wv, DM, HD); map_w(enc, &mo, Wo, HD, DM);
    map_w(enc, &M.m[12], Wo, HD, DM, 2);
    map_box(enc, &mout, d_out, S_LEN, 2 * DM, 64, 16, CU_TENSOR_MAP_SWIZZLE_128B);
    map_box(enc, &mu, d_in[7], S_LEN, DM, 8, 256, CU_TENSOR_MAP_SWIZZLE_NONE);
    map_box(enc, &my, d_out, S_LEN, 2 * DM, 8, 256, CU_TENSOR_MAP_SWIZZLE_NONE);
    for (int i = 0; i < 4; i++) map_kv(enc, &M.m[8 + i], kv[i], i < 2 ? 256 : 64);
    CUtensorMap cq, ck, cv, co;
    map_box(enc, &cq, Wq, DM, HD, 32, 32, CU_TENSOR_MAP_SWIZZLE_64B, CU_TENSOR_MAP_L2_PROMOTION_L2_128B); map_box(enc, &ck, Wk, DM, HD, 32, 32, CU_TENSOR_MAP_SWIZZLE_64B, CU_TENSOR_MAP_L2_PROMOTION_L2_128B);
    map_box(enc, &cv, Wv, DM, HD, 32, 32, CU_TENSOR_MAP_SWIZZLE_64B, CU_TENSOR_MAP_L2_PROMOTION_L2_128B); map_box(enc, &co, Wo, HD, DM, 32, 16, CU_TENSOR_MAP_SWIZZLE_64B, CU_TENSOR_MAP_L2_PROMOTION_L2_128B);
    S4Params P = {(const bf16*)d_in[8], (const bf16*)d_in[9], (const bf16*)d_in[10], (const bf16*)d_in[11],
                  (const bf16*)d_in[12], (const bf16*)d_in[13], (const bf16*)d_in[14], (const bf16*)d_in[15]};
    int aware = 1;
    cudaLaunchAttribute at[1];
    at[0].id = cudaLaunchAttributeProgrammaticStreamSerialization;
    at[0].val.programmaticStreamSerializationAllowed = 1;
    cudaLaunchConfig_t cfg = {};
    cfg.stream = cudaStreamPerThread;
    cfg.gridDim = dim3(96); cfg.blockDim = dim3(CH_THREADS); cfg.dynamicSmemBytes = CH_SMEM;
    cudaLaunchKernelEx(&cfg, chain_kernel, cq, ck, cv, co, Wq, Wk, Wv, mem0, P, aware);
    cfg.attrs = at; cfg.numAttrs = 1;
    cfg.gridDim = dim3(nsm); cfg.blockDim = dim3(384); cfg.dynamicSmemBytes = G_SMEM;
    cudaLaunchKernelEx(&cfg, worker_kernel, M, P.dsk, (bf16*)d_out);
}
```

```cpp
#include <cuda.h>
#include <cuda_runtime.h>
#include <cuda_bf16.h>
#include <stdint.h>
#include <stdio.h>
#include <string.h>

typedef __nv_bfloat16 bf16;

constexpr int S_LEN = 2048, DM = 1024, NH = 32, DH = 128, HD = 4096, NSEG = 64;
constexpr uint32_t SENT = 0xFFFFFFFFu;
constexpr int SPIN_LIMIT = 1 << 18;

__device__ __align__(1024) bf16 g_kx[S_LEN * HD];
__device__ __align__(1024) bf16 g_vx[S_LEN * HD];
__device__ __align__(1024) bf16 g_ox[S_LEN * HD];
__device__ __align__(1024) bf16 g_km[NSEG * NH * 8 * DH];
__device__ __align__(1024) bf16 g_vm[NSEG * NH * 8 * DH];
__device__ __align__(1024) bf16 g_kd[DM * 768];
__device__ __align__(1024) char g_ring[2 << 20];
__device__ int g_kvf[96 * 16];
constexpr int C_NEXT = 0, C_CHAIN = 32, C_QA_DONE = 64, N_CTR = 96;
__device__ int g_ctr[N_CTR];

__device__ __forceinline__ uint32_t smem_u32(const void* p) { return (uint32_t)__cvta_generic_to_shared(p); }
__device__ __forceinline__ uint32_t clk() { uint32_t c; asm volatile("mov.u32 %0, %%clock;" : "=r"(c)::"memory"); return c; }
__device__ __forceinline__ uint32_t pack_bf16(float lo, float hi) {
    uint32_t r; asm("cvt.rn.bf16x2.f32 %0, %1, %2;" : "=r"(r) : "f"(hi), "f"(lo)); return r;
}
__device__ __forceinline__ uint32_t movm(uint32_t a) {
    uint32_t d; asm volatile("movmatrix.sync.aligned.m8n8.trans.b16 %0, %1;" : "=r"(d) : "r"(a)); return d;
}
__device__ __forceinline__ void mma16(float (&d)[4], const uint32_t (&a)[4], uint32_t b0, uint32_t b1) {
    asm volatile("mma.sync.aligned.m16n8k16.row.col.f32.bf16.bf16.f32 {%0,%1,%2,%3}, {%4,%5,%6,%7}, {%8,%9}, {%0,%1,%2,%3};"
        : "+f"(d[0]), "+f"(d[1]), "+f"(d[2]), "+f"(d[3]) : "r"(a[0]), "r"(a[1]), "r"(a[2]), "r"(a[3]), "r"(b0), "r"(b1));
}
__device__ __forceinline__ void mma16z(float (&d)[4], const uint32_t (&a)[4], uint32_t b0, uint32_t b1) {
    asm volatile("mma.sync.aligned.m16n8k16.row.col.f32.bf16.bf16.f32 {%0,%1,%2,%3}, {%4,%5,%6,%7}, {%8,%9}, {%10,%10,%10,%10};"
        : "=f"(d[0]), "=f"(d[1]), "=f"(d[2]), "=f"(d[3]) : "r"(a[0]), "r"(a[1]), "r"(a[2]), "r"(a[3]), "r"(b0), "r"(b1), "f"(0.f));
}
__device__ __forceinline__ void mma8z(float (&d)[4], uint32_t a0, uint32_t a1, uint32_t b0) {
    asm volatile("mma.sync.aligned.m16n8k8.row.col.f32.bf16.bf16.f32 {%0,%1,%2,%3}, {%4,%5}, {%6}, {%7,%7,%7,%7};"
        : "=f"(d[0]), "=f"(d[1]), "=f"(d[2]), "=f"(d[3]) : "r"(a0), "r"(a1), "r"(b0), "f"(0.f));
}
__device__ __forceinline__ void ldsm4t(uint32_t (&r)[4], uint32_t addr) {
    asm volatile("ldmatrix.sync.aligned.m8n8.x4.trans.shared.b16 {%0,%1,%2,%3}, [%4];"
        : "=r"(r[0]), "=r"(r[1]), "=r"(r[2]), "=r"(r[3]) : "r"(addr) : "memory");
}
__device__ __forceinline__ void ldsm4(uint32_t (&r)[4], uint32_t addr) {
    asm volatile("ldmatrix.sync.aligned.m8n8.x4.shared.b16 {%0,%1,%2,%3}, [%4];"
        : "=r"(r[0]), "=r"(r[1]), "=r"(r[2]), "=r"(r[3]) : "r"(addr) : "memory");
}
__device__ __forceinline__ float lds32(uint32_t a) {
    float v; asm volatile("ld.shared.f32 %0, [%1];" : "=f"(v) : "r"(a) : "memory"); return v;
}
__device__ __forceinline__ void st_async2(uint32_t dst, float x, float y, uint32_t bar) {
    asm volatile("st.async.shared::cluster.mbarrier::complete_tx::bytes.v2.f32 [%0], {%1,%2}, [%3];" ::"r"(dst), "f"(x), "f"(y), "r"(bar) : "memory");
}
__device__ __forceinline__ void mma8(float (&d)[4], uint32_t a0, uint32_t a1, uint32_t b0) {
    asm volatile("mma.sync.aligned.m16n8k8.row.col.f32.bf16.bf16.f32 {%0,%1,%2,%3}, {%4,%5}, {%6}, {%0,%1,%2,%3};"
        : "+f"(d[0]), "+f"(d[1]), "+f"(d[2]), "+f"(d[3]) : "r"(a0), "r"(a1), "r"(b0));
}
__device__ __forceinline__ void cp16(uint32_t dst, const void* src) {
    asm volatile("cp.async.cg.shared.global [%0], [%1], 16;" ::"r"(dst), "l"(src) : "memory");
}
__device__ __forceinline__ void sts128(uint32_t a, const float (&v)[4]) {
    asm volatile("st.shared.v4.f32 [%0], {%1,%2,%3,%4};" ::"r"(a), "f"(v[0]), "f"(v[1]), "f"(v[2]), "f"(v[3]) : "memory");
}
__device__ __forceinline__ float4 lds128(uint32_t a) {
    float4 v; asm volatile("ld.shared.v4.f32 {%0,%1,%2,%3}, [%4];" : "=f"(v.x), "=f"(v.y), "=f"(v.z), "=f"(v.w) : "r"(a) : "memory"); return v;
}
__device__ __forceinline__ void sts64(uint32_t a, float x, float y) {
    asm volatile("st.shared.v2.f32 [%0], {%1,%2};" ::"r"(a), "f"(x), "f"(y) : "memory");
}
__device__ __forceinline__ float2 lds64(uint32_t a) {
    float2 v; asm volatile("ld.shared.v2.f32 {%0,%1}, [%2];" : "=f"(v.x), "=f"(v.y) : "r"(a) : "memory"); return v;
}
__device__ __forceinline__ void bar_sync(int id, int n) { asm volatile("bar.sync %0, %1;" ::"r"(id), "r"(n) : "memory"); }
__device__ __forceinline__ void bar_arrive(int id, int n) { asm volatile("bar.arrive %0, %1;" ::"r"(id), "r"(n) : "memory"); }
__device__ __forceinline__ uint32_t mapa(uint32_t a, uint32_t r) {
    uint32_t o; asm("mapa.shared::cluster.u32 %0, %1, %2;" : "=r"(o) : "r"(a), "r"(r)); return o;
}
__device__ __forceinline__ void st_async4(uint32_t dst, float4 v, uint32_t bar) {
    asm volatile("st.async.shared::cluster.mbarrier::complete_tx::bytes.v4.f32 [%0], {%1,%2,%3,%4}, [%5];"
        ::"r"(dst), "f"(v.x), "f"(v.y), "f"(v.z), "f"(v.w), "r"(bar) : "memory");
}
__device__ __forceinline__ void mbar_init(uint32_t bar, int n) { asm volatile("mbarrier.init.shared.b64 [%0], %1;" ::"r"(bar), "r"(n) : "memory"); }
__device__ __forceinline__ void mbar_expect(uint32_t bar, int bytes) {
    asm volatile("mbarrier.arrive.expect_tx.shared.b64 _, [%0], %1;" ::"r"(bar), "r"(bytes) : "memory");
}
__device__ __forceinline__ void bulk_load(uint32_t dst, const void* src, int bytes, uint32_t bar) {
    asm volatile("cp.async.bulk.shared::cluster.global.mbarrier::complete_tx::bytes [%0], [%1], %2, [%3];"
        ::"r"(dst), "l"(src), "r"(bytes), "r"(bar) : "memory");
}
__device__ __forceinline__ bool mbar_try(uint32_t bar, uint32_t par) {
    uint32_t ok;
    asm volatile("{.reg .pred p; mbarrier.try_wait.parity.shared::cta.b64 p, [%1], %2; selp.u32 %0, 1, 0, p;}"
        : "=r"(ok) : "r"(bar), "r"(par) : "memory");
    return ok;
}
__device__ __forceinline__ bool mbar_test(uint32_t bar, uint32_t par) {
    uint32_t ok;
    asm volatile("{.reg .pred p; mbarrier.test_wait.parity.shared::cta.b64 p, [%1], %2; selp.u32 %0, 1, 0, p;}"
        : "=r"(ok) : "r"(bar), "r"(par) : "memory");
    return ok;
}
__device__ __forceinline__ int ld_acq(const int* p) { int v; asm volatile("ld.acquire.gpu.global.s32 %0, [%1];" : "=r"(v) : "l"(p) : "memory"); return v; }
__device__ __forceinline__ void red_release(int* p, int v) { asm volatile("red.release.gpu.global.add.s32 [%0], %1;" ::"l"(p), "r"(v) : "memory"); }
__device__ __forceinline__ void fence_gpu() { asm volatile("fence.acq_rel.gpu;" ::: "memory"); }
__device__ __forceinline__ void wait_ctr(const int* p, int n) {
#pragma unroll 1
    for (int it = 0; it < (1 << 20) && ld_acq(p) < n; it++) __nanosleep(64);
}
__device__ __forceinline__ void mbar_wait(uint32_t bar, uint32_t par) {
    if (!mbar_try(bar, par)) {
#pragma unroll 1
        for (int it = 0; it < SPIN_LIMIT && !mbar_try(bar, par); it++) {}
    }
}
__device__ __forceinline__ void mbar_wait_long(uint32_t bar, uint32_t par) {
    for (int it = 0; it < (1 << 24) && !mbar_try(bar, par); it++) {}
}
__device__ __forceinline__ float4 add4(float4 a, float4 b) { return make_float4(a.x + b.x, a.y + b.y, a.z + b.z, a.w + b.w); }
__device__ __forceinline__ float ex2(float x) { float y; asm("ex2.approx.ftz.f32 %0, %1;" : "=f"(y) : "f"(x)); return y; }

__device__ __forceinline__ void wgmma256(float (&d)[128], uint64_t da, uint64_t db, int acc) {
    asm volatile("{.reg .pred p; setp.ne.b32 p, %130, 0;\n"
        "wgmma.mma_async.sync.aligned.m64n256k16.f32.bf16.bf16 {"
        "%0,%1,%2,%3,%4,%5,%6,%7,%8,%9,%10,%11,%12,%13,%14,%15,"
        "%16,%17,%18,%19,%20,%21,%22,%23,%24,%25,%26,%27,%28,%29,%30,%31,"
        "%32,%33,%34,%35,%36,%37,%38,%39,%40,%41,%42,%43,%44,%45,%46,%47,"
        "%48,%49,%50,%51,%52,%53,%54,%55,%56,%57,%58,%59,%60,%61,%62,%63,"
        "%64,%65,%66,%67,%68,%69,%70,%71,%72,%73,%74,%75,%76,%77,%78,%79,"
        "%80,%81,%82,%83,%84,%85,%86,%87,%88,%89,%90,%91,%92,%93,%94,%95,"
        "%96,%97,%98,%99,%100,%101,%102,%103,%104,%105,%106,%107,%108,%109,%110,%111,"
        "%112,%113,%114,%115,%116,%117,%118,%119,%120,%121,%122,%123,%124,%125,%126,%127"
        "}, %128, %129, p, 1, 1, 0, 1;}"
        : "+f"(d[0]), "+f"(d[1]), "+f"(d[2]), "+f"(d[3]), "+f"(d[4]), "+f"(d[5]), "+f"(d[6]), "+f"(d[7]), "+f"(d[8]), "+f"(d[9]), "+f"(d[10]), "+f"(d[11]), "+f"(d[12]), "+f"(d[13]), "+f"(d[14]), "+f"(d[15]), "+f"(d[16]), "+f"(d[17]), "+f"(d[18]), "+f"(d[19]), "+f"(d[20]), "+f"(d[21]), "+f"(d[22]), "+f"(d[23]), "+f"(d[24]), "+f"(d[25]), "+f"(d[26]), "+f"(d[27]), "+f"(d[28]), "+f"(d[29]), "+f"(d[30]), "+f"(d[31]), "+f"(d[32]), "+f"(d[33]), "+f"(d[34]), "+f"(d[35]), "+f"(d[36]), "+f"(d[37]), "+f"(d[38]), "+f"(d[39]), "+f"(d[40]), "+f"(d[41]), "+f"(d[42]), "+f"(d[43]), "+f"(d[44]), "+f"(d[45]), "+f"(d[46]), "+f"(d[47]), "+f"(d[48]), "+f"(d[49]), "+f"(d[50]), "+f"(d[51]), "+f"(d[52]), "+f"(d[53]), "+f"(d[54]), "+f"(d[55]), "+f"(d[56]), "+f"(d[57]), "+f"(d[58]), "+f"(d[59]), "+f"(d[60]), "+f"(d[61]), "+f"(d[62]), "+f"(d[63]), "+f"(d[64]), "+f"(d[65]), "+f"(d[66]), "+f"(d[67]), "+f"(d[68]), "+f"(d[69]), "+f"(d[70]), "+f"(d[71]), "+f"(d[72]), "+f"(d[73]), "+f"(d[74]), "+f"(d[75]), "+f"(d[76]), "+f"(d[77]), "+f"(d[78]), "+f"(d[79]), "+f"(d[80]), "+f"(d[81]), "+f"(d[82]), "+f"(d[83]), "+f"(d[84]), "+f"(d[85]), "+f"(d[86]), "+f"(d[87]), "+f"(d[88]), "+f"(d[89]), "+f"(d[90]), "+f"(d[91]), "+f"(d[92]), "+f"(d[93]), "+f"(d[94]), "+f"(d[95]), "+f"(d[96]), "+f"(d[97]), "+f"(d[98]), "+f"(d[99]), "+f"(d[100]), "+f"(d[101]), "+f"(d[102]), "+f"(d[103]), "+f"(d[104]), "+f"(d[105]), "+f"(d[106]), "+f"(d[107]), "+f"(d[108]), "+f"(d[109]), "+f"(d[110]), "+f"(d[111]), "+f"(d[112]), "+f"(d[113]), "+f"(d[114]), "+f"(d[115]), "+f"(d[116]), "+f"(d[117]), "+f"(d[118]), "+f"(d[119]), "+f"(d[120]), "+f"(d[121]), "+f"(d[122]), "+f"(d[123]), "+f"(d[124]), "+f"(d[125]), "+f"(d[126]), "+f"(d[127])
        : "l"(da), "l"(db), "r"(acc));
}
__device__ __forceinline__ void wgmma128(float (&d)[64], uint64_t da, uint64_t db, int acc) {
    asm volatile("{.reg .pred p; setp.ne.b32 p, %66, 0;\n"
        "wgmma.mma_async.sync.aligned.m64n128k16.f32.bf16.bf16 {"
        "%0,%1,%2,%3,%4,%5,%6,%7,%8,%9,%10,%11,%12,%13,%14,%15,"
        "%16,%17,%18,%19,%20,%21,%22,%23,%24,%25,%26,%27,%28,%29,%30,%31,"
        "%32,%33,%34,%35,%36,%37,%38,%39,%40,%41,%42,%43,%44,%45,%46,%47,"
        "%48,%49,%50,%51,%52,%53,%54,%55,%56,%57,%58,%59,%60,%61,%62,%63"
        "}, %64, %65, p, 1, 1, 0, 1;}"
        : "+f"(d[0]), "+f"(d[1]), "+f"(d[2]), "+f"(d[3]), "+f"(d[4]), "+f"(d[5]), "+f"(d[6]), "+f"(d[7]), "+f"(d[8]), "+f"(d[9]), "+f"(d[10]), "+f"(d[11]), "+f"(d[12]), "+f"(d[13]), "+f"(d[14]), "+f"(d[15]), "+f"(d[16]), "+f"(d[17]), "+f"(d[18]), "+f"(d[19]), "+f"(d[20]), "+f"(d[21]), "+f"(d[22]), "+f"(d[23]), "+f"(d[24]), "+f"(d[25]), "+f"(d[26]), "+f"(d[27]), "+f"(d[28]), "+f"(d[29]), "+f"(d[30]), "+f"(d[31]), "+f"(d[32]), "+f"(d[33]), "+f"(d[34]), "+f"(d[35]), "+f"(d[36]), "+f"(d[37]), "+f"(d[38]), "+f"(d[39]), "+f"(d[40]), "+f"(d[41]), "+f"(d[42]), "+f"(d[43]), "+f"(d[44]), "+f"(d[45]), "+f"(d[46]), "+f"(d[47]), "+f"(d[48]), "+f"(d[49]), "+f"(d[50]), "+f"(d[51]), "+f"(d[52]), "+f"(d[53]), "+f"(d[54]), "+f"(d[55]), "+f"(d[56]), "+f"(d[57]), "+f"(d[58]), "+f"(d[59]), "+f"(d[60]), "+f"(d[61]), "+f"(d[62]), "+f"(d[63])
        : "l"(da), "l"(db), "r"(acc));
}
__device__ __forceinline__ void wg_fence() { asm volatile("wgmma.fence.sync.aligned;" ::: "memory"); }
__device__ __forceinline__ void wg_commit() { asm volatile("wgmma.commit_group.sync.aligned;" ::: "memory"); }
template <int N> __device__ __forceinline__ void wg_wait() { asm volatile("wgmma.wait_group.sync.aligned %0;" ::"n"(N) : "memory"); }
__device__ __forceinline__ uint64_t mkdesc(uint32_t addr, uint32_t lbo, uint32_t sbo, uint32_t sw) {
    return (uint64_t)((addr & 0x3FFFF) >> 4) | ((uint64_t)(lbo >> 4) << 16) | ((uint64_t)(sbo >> 4) << 32) | ((uint64_t)sw << 62);
}
__device__ __forceinline__ void tma2d(uint32_t dst, const CUtensorMap* m, int c0, int c1, uint32_t bar) {
    asm volatile("cp.async.bulk.tensor.2d.shared::cluster.global.mbarrier::complete_tx::bytes [%0], [%1, {%2, %3}], [%4];"
        ::"r"(dst), "l"(m), "r"(c0), "r"(c1), "r"(bar) : "memory");
}
__device__ __forceinline__ void tma3d(uint32_t dst, const CUtensorMap* m, int c0, int c1, int c2, uint32_t bar) {
    asm volatile("cp.async.bulk.tensor.3d.shared::cluster.global.mbarrier::complete_tx::bytes [%0], [%1, {%2, %3, %4}], [%5];"
        ::"r"(dst), "l"(m), "r"(c0), "r"(c1), "r"(c2), "r"(bar) : "memory");
}
__device__ __forceinline__ void mbar_arrive(uint32_t bar) { asm volatile("mbarrier.arrive.shared.b64 _, [%0];" ::"r"(bar) : "memory"); }
__device__ __forceinline__ bool elect() {
    uint32_t p;
    asm volatile("{.reg .pred p; elect.sync _|p, 0xffffffff; selp.u32 %0, 1, 0, p;}" : "=r"(p));
    return p;
}
template <int R> __device__ __forceinline__ void reg_inc() { asm volatile("setmaxnreg.inc.sync.aligned.u32 %0;" ::"n"(R)); }
template <int R> __device__ __forceinline__ void reg_dec() { asm volatile("setmaxnreg.dec.sync.aligned.u32 %0;" ::"n"(R)); }

#define ST(id, w, i)
constexpr int CH_NRES = 50;
constexpr int CH_WREG = CH_NRES * 512;
constexpr int CH_PART = 8 * CH_WREG;
constexpr int CH_SX = CH_PART + 16384;
constexpr int CH_MX = CH_SX + 3 * 1280;
constexpr int CH_QK = CH_MX;
constexpr int CH_XS = CH_MX + 3 * 512;
constexpr int CH_BAR = CH_XS + 5632;
constexpr int CH_SMEM = CH_BAR + 192;
constexpr int CH_THREADS = 384;

__device__ __forceinline__ char* ring_base() { return (char*)(((uintptr_t)g_ring + (1 << 20) - 1) & ~(uintptr_t)((1 << 20) - 1)); }
__device__ __forceinline__ uint32_t ring_off(int chunk, int side) {
    uint32_t o = ((chunk & 1) << 13) | ((chunk >> 1) << 16);
    uint32_t par = ((o >> 13) ^ (o >> 16) ^ (o >> 17) ^ (o >> 19) ^ side) & 1;
    return o | (par << 12);
}
__device__ __forceinline__ uint2 ld_poll(const char* p) {
    unsigned long long v; asm volatile("ld.relaxed.gpu.global.b64 %0, [%1];" : "=l"(v) : "l"(p) : "memory");
    return make_uint2((uint32_t)v, (uint32_t)(v >> 32));
}
__device__ __forceinline__ void st_pub(char* p, uint32_t x, uint32_t y) {
    unsigned long long v = ((unsigned long long)y << 32) | x;
    asm volatile("st.relaxed.gpu.global.b64 [%0], %1;" ::"l"(p), "l"(v) : "memory");
}
template <int N>
__device__ __forceinline__ void poll_issue(uint2 (&b)[N], const char* p, bool lastvalid) {
#pragma unroll
    for (int i = 0; i < N; i++) {
        if (i < N - 1 || lastvalid) b[i] = ld_poll(p + i * 256);
        else b[i] = make_uint2(0, 0);
    }
}
template <int N>
__device__ __forceinline__ int poll_check(uint2 (&b)[N], const char* p, uint32_t z) {
    int it = 0;
    uint32_t mx = z;
#pragma unroll
    for (int i = 0; i < N; i++) mx = max(mx, b[i].x);
    if (__any_sync(0xffffffffu, mx == SENT)) {
        do {
#pragma unroll
            for (int i = 0; i < N; i++)
                if (b[i].x == SENT) b[i] = ld_poll(p + i * 256);
            mx = b[0].x;
#pragma unroll
            for (int i = 1; i < N; i++) mx = max(mx, b[i].x);
            it++;
        } while (__any_sync(0xffffffffu, mx == SENT && it < SPIN_LIMIT));
    }
    return it;
}
template <int N>
__device__ __forceinline__ uint32_t delay(uint32_t a) {
    uint32_t z = 0;
#pragma unroll
    for (int i = 0; i < N; i++) asm volatile("ld.volatile.shared.u32 %0, [%1];" : "=r"(z) : "r"(a + z) : "memory");
    return z;
}

#define LDW 0
#define GX 2
#define PACE2 19
#define KGS 2
constexpr int KVN = 2;
#define CL 6
#define ML 6
#define MP 2
#define DLM 3
#define DLO 2
constexpr int OB = 0;
template <int PACE, int I0 = 0, int I1 = 12>
__device__ __forceinline__ void preload(uint32_t (&sw)[12][4], uint32_t a, uint32_t zero) {
    uint32_t z = 0;
#pragma unroll
    for (int i = I0; i < I1; i++) {
        if (PACE && i % (PACE ? PACE : 1) == 0) z = delay<1>(zero + z);
        ldsm4t(sw[i], a + z + i * 512);
    }
}
__device__ __forceinline__ void stsm4(uint32_t addr, uint32_t a, uint32_t b, uint32_t c, uint32_t d) {
    asm volatile("stmatrix.sync.aligned.m8n8.x4.shared.b16 [%0], {%1,%2,%3,%4};" ::"r"(addr), "r"(a), "r"(b), "r"(c), "r"(d) : "memory");
}
__device__ __forceinline__ void stsm4t(uint32_t addr, uint32_t a, uint32_t b, uint32_t c, uint32_t d) {
    asm volatile("stmatrix.sync.aligned.m8n8.x4.trans.shared.b16 [%0], {%1,%2,%3,%4};" ::"r"(addr), "r"(a), "r"(b), "r"(c), "r"(d) : "memory");
}
__device__ __forceinline__ void st_part(uint32_t addr, const float (&x)[4], const float (&y)[4]) {
    stsm4(addr, pack_bf16(x[0], x[1]), pack_bf16(x[2], x[3]), pack_bf16(y[0], y[1]), pack_bf16(y[2], y[3]));
}
template <bool TR>
__device__ __forceinline__ void red_part(uint32_t& lo, uint32_t& hi, uint32_t addr, uint32_t eye) {
    uint32_t a[4][4];
#pragma unroll
    for (int j = 0; j < 4; j++) { if (TR) ldsm4t(a[j], addr + j * 1024); else ldsm4(a[j], addr + j * 1024); }
    float r0[4], r1[4], r2[4], r3[4];
    mma16z(r0, a[0], eye, eye); mma16z(r1, a[1], eye, eye); mma16z(r2, a[2], eye, eye); mma16z(r3, a[3], eye, eye);
#pragma unroll
    for (int j = 0; j < 4; j++) r0[j] = ((r0[j] + r1[j]) + r2[j]) + r3[j];
    lo = pack_bf16(r0[0], r0[1]); hi = pack_bf16(r0[2], r0[3]);
}
__device__ __forceinline__ int o_chunk(int ks, int& pos) {
    const int cw = ks < 176 ? ks / 11 : 16 + (ks - 176) / 10;
    pos = ks - (cw < 16 ? 11 * cw : 176 + 10 * (cw - 16));
    return cw;
}

template <bool PV>
__device__ __forceinline__ void chain_loop(const uint32_t (&wa)[36][4], const uint32_t sb, const int w, const int lane0, const int rank,
                                           const int h, const int side) {
    const int rk1 = rank == 2 ? 0 : rank + 1, rk2 = rank == 0 ? 2 : rank - 1;
    const int nq = rank == 0 ? 6 : 5, u0 = rank == 0 ? 0 : 1 + 5 * rank, v0 = rank == 0 ? -6 : 3 * rank - 6;
    const uint32_t pt = CH_PART + (w >> 1) * 4096 + (w & 1) * 256;
    const uint32_t barS = sb + CH_BAR, barM = barS + 8, zero = barS + 24;
    char* const ring0 = ring_base();
    const uint32_t m_rd = ring_off(24 + w, side), o_rd = ring_off(rank * 8 + w, side);
    uint32_t pub;
    if (PV) { int pos, cw = o_chunk(h * 8 + v0 + w, pos); pub = (ring_off(cw, 0) & ~4096u) + pos * 256; }
    else pub = (ring_off(24 + (h >> 2), 0) & ~4096u) + ((2 * h + w) & 7) * 256;
    char* const kvo = (char*)(PV ? g_vm + 128 * (v0 + w) : g_km + 64 * (u0 + w)) + h * 2048;
    const bool mown = !PV && w == rank && rank < 2;
    uint32_t lo16 = lane0 * 16;
    uint32_t sw[12][4];
#pragma unroll
    for (int i = 0; i < 12; i++) ldsm4t(sw[i], sb + lo16 + w * CH_WREG + i * 512);

#pragma unroll 1
    for (int s = 0;; s++) {
        const bool last = s == NSEG - 1;
        const uint32_t slot = (s & 3) << 14;
        lo16 += delay<DLM>(zero);
        const uint32_t lane = lo16 >> 4, l16 = sb + lo16, wl = l16 + w * CH_WREG, pw = l16 + CH_PART + w * 512;
        const uint32_t xs = l16 + CH_XS + nq * 512 + (w - nq) * 1024;
        const uint32_t eye = ((lo16 >> 7) == (lane & 3)) ? ((lo16 & 64) ? 0x3F800000u : 0x3F80u) : 0u;
        uint2 b[8];
        const char* pm = ring0 + (m_rd + slot + (lo16 >> 1));
        poll_issue<8>(b, pm, true);
        preload<0, ML, 12>(sw, wl, zero);
        bar_arrive(14, 256);
        poll_check<8>(b, pm, delay<1>(zero));
        if (OB && !last) bar_arrive(8, 256 + OB);
        if (PV && !last && w == 7) bar_arrive(13, 64);
        {
            float acc[6][4];
#pragma unroll
            for (int kk = 0; kk < 8; kk++) {
                const int j = (2 * kk) % 12;
                if (kk == 0) { mma16z(acc[5], sw[0], b[0].x, b[0].y); mma16z(acc[4], sw[1], b[0].x, b[0].y); }
                else { mma16(acc[5], sw[j], b[kk].x, b[kk].y); mma16(acc[4], sw[j + 1], b[kk].x, b[kk].y); }
#pragma unroll
                for (int i = 0; i < 4; i++) {
                    if (kk == 0) mma16z(acc[i], wa[i * 8], b[0].x, b[0].y);
                    else mma16(acc[i], wa[i * 8 + kk], b[kk].x, b[kk].y);
                    if (i < 2) ldsm4t(sw[j + i], wl + (12 + 2 * kk + i) * 512);
                }
            }
            st_part(pw + 4 * 2048, acc[4], acc[5]);
            st_part(pw, acc[0], acc[1]);
            st_part(pw + 2 * 2048, acc[2], acc[3]);
        }
        uint32_t kv0, kv1;
        const uint32_t lp = l16 + (lane >> 4) * 256, pl = lp + pt;
        if (!PV) {
            bar_sync(1, last ? 256 : 256 + OB);
            red_part<true>(kv1, kv0, pl, eye);
            sts64(l16 + CH_QK + (w >> 1) * 512 + (w & 1) * 8, __uint_as_float(kv1), __uint_as_float(kv0));
            if (!last) bar_arrive(2, nq * 32 + 64 + OB);
        } else {
            bar_sync(1, last ? 256 : 256 + OB);
        }
        {
            float va[4][4];
            if (side > 1) asm volatile("exit;");
#pragma unroll
            for (int i = 0; i < 4; i++) va[i][0] = va[i][1] = va[i][2] = va[i][3] = 0.f;
#pragma unroll
            for (int kk = 0; kk < 8; kk++) {
                const int c = PV ? kk & 1 : 0;
                if (kk < 2) { mma16(va[c], wa[32 + 2 * kk], b[kk].x, b[kk].y); mma16(va[2 + c], wa[33 + 2 * kk], b[kk].x, b[kk].y); }
                else { mma16(va[c], sw[(2 * kk) % 12], b[kk].x, b[kk].y); mma16(va[2 + c], sw[(2 * kk + 1) % 12], b[kk].x, b[kk].y); }
            }
            if (PV) {
#pragma unroll
                for (int j = 0; j < 4; j++) { va[0][j] += va[1][j]; va[2][j] += va[3][j]; }
            }
            st_part(pw + 6 * 2048, va[0], va[2]);
        }
        if (PV) {
            uint32_t vt0[4], vt1[4];
            ldsm4t(vt0, xs); ldsm4t(vt1, xs + 512);
            if (w >= 6 && !last) {
                uint32_t kx[3][4];
#pragma unroll
                for (int j = 0; j < 3; j++)
                    ldsm4(kx[j], sb + CH_XS + j * 1024 + (j == 2 && nq == 5 ? 0 : ((lane >> 3) & 1) * 512) + (w - 6) * 256 + (lane >> 4) * 128 + (lane & 7) * 16);
                const uint32_t da = l16 + CH_SX + rank * 1280 + (w - 6) * 512, dc = sb + CH_SX + rank * 1280 + 1024 + lane * 8;
                bar_sync(2, nq * 32 + 64 + OB);
                uint32_t qk[3][4];
#pragma unroll
                for (int j = 0; j < 3; j++) {
                    const float4 v = lds128(l16 + CH_QK + j * 512);
                    qk[j][0] = __float_as_uint(v.x); qk[j][1] = __float_as_uint(v.y); qk[j][2] = __float_as_uint(v.z); qk[j][3] = __float_as_uint(v.w);
                }
                float s0[4], s1[4], s2[4], s3[4];
                mma16z(s0, qk[0], kx[0][0], kx[0][1]); mma16z(s1, qk[0], kx[0][2], kx[0][3]);
                mma16z(s2, qk[1], kx[1][0], kx[1][1]); mma16z(s3, qk[1], kx[1][2], kx[1][3]);
                if (nq == 5) qk[2][2] = qk[2][3] = 0;
                mma16(s0, qk[2], kx[2][0], kx[2][1]); mma16(s1, qk[2], kx[2][2], kx[2][3]);
                float m0[4], m1[4];
                mma16z(m0, qk[0], qk[0][1], qk[0][3]); mma16z(m1, qk[1], qk[1][1], qk[1][3]);
                mma16(m0, qk[2], qk[2][1], qk[2][3]);
                const float4 sv = make_float4(s0[0] + s2[0], s0[1] + s2[1], s1[0] + s3[0], s1[1] + s3[1]);
                st_async4(mapa(da, rk1), sv, mapa(barS, rk1));
                st_async4(mapa(da, rk2), sv, mapa(barS, rk2));
                {
                    const float c0 = m0[0] + m1[0], c1 = m0[1] + m1[1];
                    const int dr = w == 6 ? rk1 : rk2;
                    st_async2(mapa(dc, dr), c0, c1, mapa(barS, dr));
                    sts64(dc, c0, c1);
                }
                const float t4[4] = {sv.x, sv.y, sv.z, sv.w};
                sts128(da, t4);
            }
            bar_sync(3, last ? 256 : 256 + OB);
            if (!last && w == 7) bar_arrive(12, 64);
            red_part<false>(kv0, kv1, pl, eye);
            if (last) {
                uint32_t* d = (uint32_t*)(kvo + (uint32_t)(s * (NH * 2048) + lane * 4));
                d[0] = movm(kv0); d[32] = movm(kv1);
                break;
            }
            {
                const uint32_t sx = l16 + CH_SX, r0 = rank * 1280, r1 = rk1 * 1280, r2 = rk2 * 1280;
                float4 a0 = lds128(sx + r0), b0 = lds128(sx + 512 + r0);
                const float2 c0 = lds64(sx + 1024 + r0 - lane * 8);
                mbar_wait(barS, s & 1);
                const float4 a1 = lds128(sx + r1), a2 = lds128(sx + r2), b1 = lds128(sx + 512 + r1), b2 = lds128(sx + 512 + r2);
                const float2 c1 = lds64(sx + 1024 + r1 - lane * 8), c2 = lds64(sx + 1024 + r2 - lane * 8);
                a0 = add4(add4(a0, a1), a2); b0 = add4(add4(b0, b1), b2);
                float sc[10] = {a0.x, a0.y, a0.z, a0.w, b0.x, b0.y, b0.z, b0.w, c0.x + c1.x + c2.x, c0.y + c1.y + c2.y};
                float mx = fmaxf(fmaxf(fmaxf(sc[0], sc[1]), fmaxf(sc[2], sc[3])), fmaxf(fmaxf(sc[4], sc[5]), fmaxf(sc[6], sc[7])));
                mx = fmaxf(mx, fmaxf(sc[8], sc[9]));
                mx = fmaxf(fmaxf(mx, __shfl_xor_sync(0xffffffffu, mx, 1)),
                           fmaxf(__shfl_xor_sync(0xffffffffu, mx, 2), __shfl_xor_sync(0xffffffffu, mx, 3)));
                const float cs = 0.08838834764831845f * 1.4426950408889634f;
                const float mb = -mx * cs;
#pragma unroll
                for (int j = 0; j < 10; j++) sc[j] = ex2(fmaf(sc[j], cs, mb));
                uint32_t pf[5];
#pragma unroll
                for (int j = 0; j < 5; j++) pf[j] = pack_bf16(sc[2 * j], sc[2 * j + 1]);
                float o0[4], o1[4], o2[4], o3[4], o4[4], o5[4];
                const uint32_t p0[4] = {pf[0], 0, pf[1], 0}, p1[4] = {pf[2], 0, pf[3], 0};
                mma16z(o0, p0, vt0[0], vt0[1]); mma16z(o1, p0, vt1[0], vt1[1]);
                mma16z(o2, p1, vt0[2], vt0[3]); mma16z(o3, p1, vt1[2], vt1[3]);
                mma8z(o4, pf[4], 0, kv0); mma8z(o5, pf[4], 0, kv1);
                float sum = (((sc[0] + sc[1]) + (sc[2] + sc[3])) + ((sc[4] + sc[5]) + (sc[6] + sc[7]))) + (sc[8] + sc[9]);
                sum = (sum + __shfl_xor_sync(0xffffffffu, sum, 1)) + (__shfl_xor_sync(0xffffffffu, sum, 2) + __shfl_xor_sync(0xffffffffu, sum, 3));
                float inv; asm("rcp.approx.ftz.f32 %0, %1;" : "=f"(inv) : "f"(sum));
                const uint32_t ox = pack_bf16((o0[0] + o2[0] + o4[0]) * inv, (o0[1] + o2[1] + o4[1]) * inv);
                const uint32_t oy = pack_bf16((o1[0] + o3[0] + o5[0]) * inv, (o1[1] + o3[1] + o5[1]) * inv);
                char* const pp = ring0 + (pub + slot + (lo16 >> 1));
                st_pub(pp, ox, oy); st_pub(pp + 4096, ox, oy);
                bar_arrive(10, (8 - nq) * 32 + OB);
            }
            kv0 = movm(kv0); kv1 = movm(kv1);
        } else {
            *(uint32_t*)(kvo + (uint32_t)(s * (NH * 2048) + lane * 4)) = kv0;
            bar_sync(3, last ? 256 : 256 + OB);
            if (last) break;
            preload<1, 0, CL>(sw, wl + 28 * 512, zero);
        }
        uint2 c[11];
        bar_sync(4, 256 + OB);
        const char* po = ring0 + (o_rd + slot + (lo16 >> 1) + delay<DLO>(zero));
        poll_issue<11>(c, po, rank < 2);
        preload<0, PV ? 0 : CL, 12>(sw, wl + 28 * 512, zero);
        if (PV) { uint32_t* d = (uint32_t*)(kvo + (uint32_t)(s * (NH * 2048) + lane * 4)); d[0] = kv0; d[32] = kv1; }
        {
            float acc[4][4];
            uint32_t sx[GX][4];
#pragma unroll
            for (int i = 0; i < GX; i++) ldsm4t(sx[i], wl + (40 + i) * 512);
            poll_check<11>(c, po, 0);
            if (OB) bar_arrive(9, 256 + OB);
#pragma unroll
            for (int f = 0; f < 22; f++) {
                const int kk = f >> 1, a = f & 3;
                if (f < 4) mma16z(acc[a], sw[f], c[kk].x, c[kk].y);
                else if (f >= 12 && f < 12 + GX) mma16(acc[a], sx[f - 12], c[kk].x, c[kk].y);
                else mma16(acc[a], sw[f % (12 + GX)], c[kk].x, c[kk].y);
                if (f + 12 + GX < 22) ldsm4t(sw[f], wl + (40 + GX + f) * 512);
            }
#pragma unroll
            for (int i = 0; i < 2; i++) {
#pragma unroll
                for (int j = 0; j < 4; j++) acc[i][j] += acc[i + 2][j];
                sts128(l16 + CH_PART + i * 4096 + w * 512, acc[i]);
            }
        }
        if (!PV && w < 2) {
            bar_sync(5, 288 + OB);
            float4 v[8];
#pragma unroll
            for (int i = 0; i < 8; i++) v[i] = lds128(l16 + CH_PART + w * 4096 + i * 512);
            float4 r = add4(add4(add4(v[0], v[1]), add4(v[2], v[3])), add4(add4(v[4], v[5]), add4(v[6], v[7])));
            if (!mown) st_async4(mapa(l16 + CH_MX + rank * 512, w), r, mapa(barM, w));
            bar_arrive(7, 256 + OB);
            if (mown) {
                mbar_wait(barM, s & 1);
                float4 x = lds128(l16 + CH_MX + (rank ^ 1) * 512), y = lds128(l16 + CH_MX + 2 * 512);
                r = add4(add4(x, r), y);
                const uint32_t mx = movm(pack_bf16(r.x, r.y)), my = movm(pack_bf16(r.z, r.w));
                const uint32_t ns = (slot + 0x4000) & 0xC000;
                char* const pp = ring0 + (pub + ns + (lo16 >> 1));
                st_pub(pp, mx, my); st_pub(pp + 4096, mx, my);
            }
            preload<0, 0, ML>(sw, wl, zero);
        } else {
            bar_arrive(5, 288 + OB);
            bar_sync(7, 256 + OB);
            preload<MP, 0, ML>(sw, wl, zero);
        }
        bar_sync(6, 320 + OB);
    }
}

__device__ __forceinline__ void chain_pace(const uint32_t sb, const int lane, const int rank, const int aware) {
    const uint32_t zero = sb + CH_BAR + 24;
    if (lane == 0) {
        char* ring = ring_base();
        uint32_t* p0 = (uint32_t*)(ring + ring_off(blockIdx.x & 15, 0) + 3072 + (blockIdx.x >> 4) * 128);
        uint32_t* p1 = (uint32_t*)(ring + ring_off(blockIdx.x & 15, 1) + 3072 + (blockIdx.x >> 4) * 128);
        *p0 = 0; *p1 = 0;
        int b0 = 1 << 30, b1 = 1 << 30; uint32_t v = 0;
        for (int r = 0; r < 4 || (r < 64 && !delay<1>(zero + 8)); r++) {
            uint32_t t0 = clk(); v = atomicExch(p0 + (v == 500), r); uint32_t t1 = v == 777 ? clk() + 1 : clk(); b0 = min(b0, (int)(t1 - t0));
            t0 = clk(); v = atomicExch(p1 + (v == 500), r); t1 = v == 777 ? clk() + 1 : clk(); b1 = min(b1, (int)(t1 - t0));
            asm volatile("st.volatile.shared.u32 [%0], %1;" ::"r"(zero + 4), "r"(aware ? (b1 < b0) ^ (aware - 1) : 0) : "memory");
        }
    }
    __syncwarp();
#pragma unroll 1
    for (int s = 1; s < NSEG; s++) {
        bar_sync(5, 288 + OB);
        bar_arrive(6, 320 + OB + (rank == 2 ? delay<PACE2>(zero) : 0));
    }
}
__device__ __forceinline__ char* reset_ptr(const int lane, const int rank, const int h) {
    const int nq = rank == 0 ? 6 : 5, v0 = rank == 0 ? -6 : 3 * rank - 6;
    int pos, cw = o_chunk(h * 8 + v0 + min(max(5 + (lane >> 3), nq), 7), pos);
    if (lane >= 24 && rank < 2) { cw = 24 + (h >> 2); pos = (2 * h + rank) & 7; }
    return ring_base() + ((ring_off(cw, 0) & ~4096u) + pos * 256 + (lane & 7) * 16);
}
__device__ __forceinline__ void chain_chores(const uint32_t sb, const int lane, const int rank, const int h, const bf16* __restrict__ mem0) {
    const int nq = rank == 0 ? 6 : 5, u0 = rank == 0 ? 0 : 1 + 5 * rank, v0 = rank == 0 ? -6 : 3 * rank - 6;
    const uint32_t barS = sb + CH_BAR, barM = barS + 8, barX = barS + 16;
    auto xload = [&](int s) {
        mbar_expect(barX, 8192 - nq * 512);
        bulk_load(sb + CH_XS, g_kx + (size_t)(s * NH + h) * 4096 + u0 * 256, nq * 512, barX);
        bulk_load(sb + CH_XS + nq * 512, g_vx + (size_t)(s * NH + h) * 4096 + (v0 + nq) * 512, (8 - nq) * 1024, barX);
    };
    char* const rb = reset_ptr(lane, rank, h);
    int* const kvf = g_kvf + blockIdx.x * 16;
    if (rank < 2) {
        const uint32_t* p = (const uint32_t*)(mem0 + (lane >> 2) * DM + 32 * h + 16 * rank + 2 * (lane & 3));
        char* d = ring_base() + ((ring_off(24 + (h >> 2), 0) & ~4096u) + ((2 * h + rank) & 7) * 256 + lane * 8);
        const uint32_t x = p[0] == SENT ? 0x7FFF7FFFu : p[0];
        st_pub(d, x, p[4]); st_pub(d + 4096, x, p[4]);
    }
    if (!KVN) __nanosleep(18000);
    wait_ctr(kvf, KVN);
    asm volatile("fence.proxy.async.global;" ::: "memory");
    if (elect()) xload(0);
    asm volatile("st.volatile.shared.u32 [%0], %1;" ::"r"(barS + 32), "r"(1) : "memory");
#pragma unroll 1
    for (int s = 0; s < NSEG - 1; s++) {
        if (lane == 0) {
            mbar_expect(barS, 2 * 1280);
            if (rank < 2) mbar_expect(barM, 2 * 512);
        }
        bar_sync(13, 64);
#pragma unroll
        for (int i = 0; i < 4; i++)
            asm volatile("st.relaxed.gpu.global.v4.u32 [%0], {%1,%1,%1,%1};" ::"l"(rb + ((((s + 2) & 3) << 14) + (i >> 1) * 4096 + (i & 1) * 128)), "r"(SENT) : "memory");
        fence_gpu();
        if (lane == 0 && (s & 3) == 0 && s) atomicAdd(g_ctr + C_CHAIN + (s >> 2) - 1, 1);
        if ((s & 3) == 3) { wait_ctr(kvf + (s >> 2) + 1, KVN); asm volatile("fence.proxy.async.global;" ::: "memory"); }
        __syncwarp();
        bar_sync(12, 64);
        if (elect()) xload(s + 1);
        mbar_wait(barX, (s + 1) & 1);
        bar_sync(6, 320 + OB);
    }
}

struct S4Params { const bf16 *Are, *Aim, *Bre, *Bim, *Cre, *Cim, *ldt, *dsk; };
__device__ __forceinline__ float2 cmul(float2 a, float2 b) { return make_float2(a.x * b.x - a.y * b.y, a.x * b.y + a.y * b.x); }
__device__ __forceinline__ float2 csq(float2 a) { return make_float2(a.x * a.x - a.y * a.y, (a.x + a.x) * a.y); }
__device__ __forceinline__ float2 cexp_t(float lr, float turns) {
    float f = (turns - rintf(turns)) * 6.283185307179586f, e = ex2(lr);
    return make_float2(e * __cosf(f), e * __sinf(f));
}
__device__ __forceinline__ float bf_at(uint2 v, int i) {
    const uint32_t w = i < 2 ? v.x : v.y;
    return __uint_as_float((i & 1) ? w & 0xFFFF0000u : w << 16);
}
__device__ __forceinline__ void kg_step(uint32_t (&a)[4][4], uint32_t (&b)[5][2], uint32_t pa, uint32_t pe, float x0) {
#pragma unroll
    for (int i = 0; i < 2; i++) {
        const float4 p = lds128(pa + i * 64);
        const float2 e8 = lds64(pe + i * 32), c = make_float2(p.z, p.w);
        const float mag = ex2(p.x * x0), ph = p.y * x0;
        float2 e0 = make_float2(mag * __cosf(ph), mag * __sinf(ph)), e1 = cmul(e0, e8);
#pragma unroll
        for (int j = 0; j < 4; j++) {
            a[j][2 * i] = pack_bf16(e0.x, e0.y); a[j][2 * i + 1] = pack_bf16(e1.x, e1.y);
            e0 = csq(e0); e1 = csq(e1);
        }
        float2 m = cmul(c, e0);
        b[0][i] = pack_bf16(m.x, -m.y);
#pragma unroll
        for (int j = 0; j < 4; j++) {
            m = cmul(c, e1);
            b[j + 1][i] = pack_bf16(m.x, -m.y);
            if (j < 3) e1 = csq(e1);
        }
    }
}
__device__ __forceinline__ void kg_mma(float (&kd)[5][4], const uint32_t (&a)[4][4], const uint32_t (&b)[5][2]) {
    mma16(kd[0], a[0], b[0][0], b[0][1]);
#pragma unroll
    for (int j = 0; j < 4; j++) mma16(kd[j + 1], a[j], b[j + 1][0], b[j + 1][1]);
}
struct KgRaw { uint2 v[6]; float ldt; };
__device__ __forceinline__ void kg_load(KgRaw& r, const S4Params& P, int d, int lane) {
    const bf16* src[6] = {P.Are, P.Aim, P.Bre, P.Bim, P.Cre, P.Cim};
#pragma unroll
    for (int j = 0; j < 6; j++) r.v[j] = __ldg((const uint2*)(src[j] + d * 128) + lane);
    r.ldt = __bfloat162float(P.ldt[d]);
}
__device__ __forceinline__ float kg_params(const KgRaw& r, uint32_t stg, int lane) {
    const float dt = __bfloat162float(__float2bfloat16(expf(r.ldt)));
    float k2048 = 0.f;
#pragma unroll
    for (int i = 0; i < 4; i++) {
        const float br = dt * bf_at(r.v[2], i), bi = dt * bf_at(r.v[3], i), cr = bf_at(r.v[4], i), ci = bf_at(r.v[5], i);
        const float zr = dt * bf_at(r.v[0], i) * 1.4426950408889634f;
        float zt = dt * bf_at(r.v[1], i) * 0.15915494309189535f;
        zt -= rintf(zt);
        const float v[4] = {zr, zt * 6.283185307179586f, cr * br - ci * bi, cr * bi + ci * br};
        const float2 e8 = cexp_t(8.f * zr, 8.f * zt), el = cexp_t(2048.f * zr, 2048.f * zt);
        k2048 += v[2] * el.x - v[3] * el.y;
        sts128(stg + (i * 32 + lane) * 16, v);
        sts64(stg + 2048 + (i * 32 + lane) * 8, e8.x, e8.y);
    }
#pragma unroll
    for (int o = 16; o; o >>= 1) k2048 += __shfl_xor_sync(0xffffffffu, k2048, o);
    __syncwarp();
    return k2048;
}
__device__ __forceinline__ void kg_store(const float (&kd)[5][4], float k2048, uint32_t stg, int d, int lane) {
    __syncwarp();
    const uint32_t ta = stg + (lane & 7) * 32 + ((lane >> 3) & 1) * 16 + (lane >> 4) * 256;
    stsm4t(ta, pack_bf16(kd[0][0], kd[0][1]), pack_bf16(kd[0][2], kd[0][3]), pack_bf16(kd[1][0], kd[1][1]), pack_bf16(kd[1][2], kd[1][3]));
    stsm4t(ta + 512, pack_bf16(kd[2][0], kd[2][1]), pack_bf16(kd[2][2], kd[2][3]), pack_bf16(kd[3][0], kd[3][1]), pack_bf16(kd[3][2], kd[3][3]));
    stsm4t(ta + 1024, pack_bf16(kd[4][0], kd[4][1]), pack_bf16(kd[4][2], kd[4][3]), pack_bf16(k2048, 0.f), 0);
    __syncwarp();
#pragma unroll
    for (int j = 0; j < 3; j++) ((float4*)(g_kd + d * 768))[j * 32 + lane] = lds128(stg + j * 512 + lane * 16);
    __syncwarp();
}

__global__ void __cluster_dims__(3, 1, 1) __launch_bounds__(CH_THREADS, 1)
chain_kernel(const __grid_constant__ CUtensorMap mq, const __grid_constant__ CUtensorMap mk, const __grid_constant__ CUtensorMap mv,
             const __grid_constant__ CUtensorMap mo, const bf16* __restrict__ Wq, const bf16* __restrict__ Wk, const bf16* __restrict__ Wv,
             const bf16* __restrict__ mem0, const __grid_constant__ S4Params P, int aware) {
    extern __shared__ __align__(1024) unsigned char smem[];
    const uint32_t sb = smem_u32(smem);
    const int tid = threadIdx.x, lane = tid & 31;
    const int w = __shfl_sync(0xffffffffu, tid >> 5, 0);
    int rank; asm("mov.u32 %0, %%cluster_ctarank;" : "=r"(rank));
    const int h = blockIdx.x / 3;
    if (tid == 0) {
        mbar_init(sb + CH_BAR, 1); mbar_init(sb + CH_BAR + 8, 1); mbar_init(sb + CH_BAR + 16, 1);
        for (int i = 0; i < 16; i++) mbar_init(sb + CH_BAR + 64 + i * 8, 1);
        *(int*)(smem + CH_BAR + 24) = 0; *(int*)(smem + CH_BAR + 28) = 0; *(int*)(smem + CH_BAR + 32) = 0;
        asm volatile("fence.mbarrier_init.release.cluster;" ::: "memory");
    }
    if (w == 9) {
        char* const rb = reset_ptr(lane, rank, h);
#pragma unroll
        for (int i = 0; i < 8; i++)
            asm volatile("st.relaxed.gpu.global.v4.u32 [%0], {%1,%1,%1,%1};" ::"l"(rb + (((i >> 2) << 14) + ((i >> 1) & 1) * 4096 + (i & 1) * 128)), "r"(SENT) : "memory");
        if (lane < 16) g_kvf[blockIdx.x * 16 + lane] = 0;
        if (blockIdx.x == 0)
            for (int k = lane; k < N_CTR; k += 32) g_ctr[k] = 0;
        fence_gpu();
        __syncwarp();
        asm volatile("griddepcontrol.launch_dependents;" ::: "memory");
    }
    __syncthreads();
    asm volatile("barrier.cluster.arrive.relaxed.aligned;" ::: "memory");

    if (w >= 8) {
        reg_dec<24>();
        asm volatile("barrier.cluster.wait.aligned;" ::: "memory");
        if (w == 8) chain_pace(sb, lane, rank, aware);
        else if (w == 9) chain_chores(sb, lane, rank, h, mem0);
    } else {
        reg_inc<240>();
        const int nq = rank == 0 ? 6 : 5;
        const int u0 = rank == 0 ? 0 : 1 + 5 * rank;
        const int v0 = rank == 0 ? -6 : 3 * rank - 6;
        const int gw = rank * 8 + w;
        const int ks0 = gw < 16 ? 11 * gw : 176 + 10 * (gw - 16);
        const int nko = gw < 16 ? 11 : 10;
        const uint32_t wr = sb + w * CH_WREG, bar0 = sb + CH_BAR + 64 + w * 16, bar1 = bar0 + 8;
        uint32_t wa[36][4];
        const uint32_t vst = sb + CH_PART + w * 2048;
        const int cq = h * DH + 8 * u0, cv = h * DH + 16 * (v0 + 6);
        const int r8 = lane >> 2, p = lane & 3;
        const bf16* src = p >= 2 ? ((p & 1) ? Wk : Wq) + cq + 32 : rank == 0 ? ((p & 1) ? Wk : Wq) + cq + 40 : Wv + cv - 16 + 8 * p;
        src += (size_t)(128 * w + r8) * HD;
        auto cp_rows = [&](int kh) {
            cp16(wr + ((kh >> 1) * 2 + (p >> 1)) * 512 + ((kh & 1) * 2 + (p & 1)) * 128 + r8 * 16, src + (size_t)kh * 8 * HD);
        };
        {
            int d = blockIdx.x * 8 + w, t = 0;
            const int d1 = 768 + blockIdx.x * 3 + w, nt = (w < 3 && d1 < DM) ? 32 : 16;
            const uint32_t stg = wr + 4096;
            KgRaw raw, raw1;
            kg_load(raw, P, d, lane);
            kg_load(raw1, P, min(d1, DM - 1), lane);
            float kd[5][4], k2048;
#pragma unroll 1
            for (int i = -LDW; i < 9 || t < nt; i++) {
                if (i >= 0 && i < 9) {
                    const uint32_t bar = bar0 + (i & 1) * 8;
                    if (i >= 2) mbar_wait(bar, ((i >> 1) - 1) & 1);
                    if (elect()) {
                        mbar_expect(bar, 2048);
                        if (i < 8) tma2d(wr + 8192 + (i & 1) * 8192 + (i >> 1) * 2048, (i & 1) ? &mk : &mq, cq, 128 * w + 32 * (i >> 1), bar);
                        else tma2d(vst, &mv, cv, 128 * w, bar);
                    }
                    if (i < 8) cp_rows(i);
                }
#pragma unroll 1
                for (int e = min(t + KGS, nt); t < e; t++) {
                    if ((t & 15) == 0) {
                        k2048 = kg_params(raw, stg, lane);
#pragma unroll
                        for (int j = 0; j < 20; j++) kd[j >> 2][j & 3] = 0.f;
                    }
                    uint32_t ka[4][4], kb[5][2];
                    kg_step(ka, kb, stg + ((t & 15) * 8 + (lane & 3)) * 16, stg + 2048 + ((t & 15) * 8 + (lane & 3)) * 8, (float)(lane >> 2));
                    kg_mma(kd, ka, kb);
                    if ((t & 15) == 15) { kg_store(kd, k2048, stg, d, lane); raw = raw1; d = d1; }
                }
            }
        }
        const uint32_t lrow = ((lane >> 4) * 8 + (lane & 7)) * 64, lsw = (lane >> 1) & 3, lh = (lane >> 3) & 1;
        mbar_wait(bar1, 1); mbar_wait(bar0, 0);
#pragma unroll
        for (int i = 0; i < 32; i++) ldsm4t(wa[i], wr + 8192 + lh * 8192 + (i & 7) * 1024 + lrow + (((i >> 3) ^ lsw) << 4));
#pragma unroll
        for (int i = 0; i < 4; i++) ldsm4t(wa[32 + i], vst + (i >> 1) * 1024 + lrow + ((((i & 1) * 2 + lh) ^ lsw) << 4));
        asm volatile("fence.proxy.async.shared::cta;" ::"r"(wa[31][0]), "r"(wa[35][0]) : "memory");
        __syncwarp();
#pragma unroll 1
        for (int i = 9; i < 18; i++) {
            const uint32_t bar = bar0 + (i & 1) * 8;
            if (i >= 11) mbar_wait(bar, ((i >> 1) - 1) & 1);
            if (elect()) {
                const int j = 2 * (i - 12), nb = min(2, nko - j);
                mbar_expect(bar, i < 12 ? 2048 : nb * 1024);
                if (i < 12) tma2d(wr + 8192 + (i - 9) * 2048, &mv, cv, 128 * w + 32 * (i - 8), bar);
                else {
                    if (nb > 0) tma2d(wr + 14336 + j * 1024, &mo, 32 * h, 16 * (ks0 + j), bar);
                    if (nb > 1) tma2d(wr + 15360 + j * 1024, &mo, 32 * h, 16 * (ks0 + j + 1), bar);
                }
            }
            if (i < 17) cp_rows(i - 1);
        }
        mbar_wait(bar0, 0); mbar_wait(bar1, 0);
#pragma unroll 1
        for (int i0 = -1; i0 < 17; i0 += 6) {
            uint32_t x[6][2][4];
#pragma unroll
            for (int i = 0; i < 6; i++) {
                const uint32_t a = wr + 8192 + max(i0 + i, 0) * 1024 + lrow;
                ldsm4t(x[i][0], a + ((lh ^ lsw) << 4)); ldsm4t(x[i][1], a + (((2 + lh) ^ lsw) << 4));
            }
            if (i0 == 11 && nko == 10) {
#pragma unroll
                for (int j = 0; j < 8; j++) x[5][j >> 2][j & 3] = 0;
            }
            __syncwarp();
#pragma unroll
            for (int i = 0; i < 6; i++) {
                const uint32_t a = wr + 8192 + max(i0 + i, 0) * 1024 + lane * 16;
                stsm4t(a, x[i][0][0], x[i][0][1], x[i][0][2], x[i][0][3]); stsm4t(a + 512, x[i][1][0], x[i][1][1], x[i][1][2], x[i][1][3]);
            }
        }
        asm volatile("cp.async.wait_all;" ::: "memory");
        asm volatile("barrier.cluster.wait.aligned;" ::: "memory");
        bar_sync(1, 256);
        mbar_wait_long(sb + CH_BAR + 16, 0);
        const int side = __shfl_sync(0xffffffffu, *(volatile int*)(smem + CH_BAR + 28), 0);
        if (w >= nq) chain_loop<true>(wa, sb, w, lane, rank, h, side);
        else chain_loop<false>(wa, sb, w, lane, rank, h, side);
    }
}

constexpr int G_STAGE = 49152, G_NST = 4;
constexpr int G_STG = G_NST * G_STAGE;
constexpr int G_BAR = G_STG + 32768;
constexpr int G_SMEM = G_BAR + 256 + 1024;

#define WLOG(e)
constexpr int IT_QA = 0, IT_O = 1, IT_S4 = 2, IT_END = 3, IT_KV = 4;
#define O_WIDE 15
#define S4DIR 5
#define S4REL 4
#define KVI 1
#define KVF 2
#define KVS 8
#define Q_S1 0
#define Q_B0 10
#define Q_L 1
#define Q_T0 8
__device__ __forceinline__ int queue_item(int q) {
    if (q < 512) return (IT_KV << 16) | ((q >> 5) << 8) | (q & 31);
    q -= 512;
    if (q < Q_B0 * Q_T0) return (IT_QA << 16) | ((q % Q_B0) << 8) | (q / Q_B0);
    constexpr int W1 = O_WIDE - 1, T1 = Q_T0 + Q_L;
    if (q < W1 * Q_T0) return (IT_QA << 16) | ((q / Q_T0) << 8) | (q % Q_T0);
    if (q < W1 * T1) return (IT_QA << 16) | ((q % W1) << 8) | (q / W1);
    if (q < O_WIDE * T1) return (IT_QA << 16) | (W1 << 8) | (q - W1 * T1);
    if (q < O_WIDE * 16) return (IT_QA << 16) | ((q % O_WIDE) << 8) | (q / O_WIDE);
    q -= O_WIDE * 16;
    if (q < Q_S1) return (IT_S4 << 16) | q;
    q -= Q_S1;
    if (q < (16 - O_WIDE) * 8) return (IT_O << 16) | ((O_WIDE + (q >> 3)) << 8) | (q & 7);
    q -= (16 - O_WIDE) * 8;
    if (q < 128 - Q_S1) return (IT_S4 << 16) | (Q_S1 + q);
    return IT_END << 16;
}
constexpr int N_LATE = O_WIDE * 4 + (16 - O_WIDE) * 16;
static_assert(N_LATE <= 96, "first items of the late CTAs");
__device__ __forceinline__ int late_item(int j) {
    if (j < O_WIDE * 4) return (IT_O << 16) | ((j >> 2) << 8) | (j & 3);
    j -= O_WIDE * 4;
    return (IT_QA << 16) | ((O_WIDE + (j >> 4)) << 8) | (j & 15);
}
__device__ __forceinline__ void tma2d_store(const CUtensorMap* m, uint32_t src, int c0, int c1) {
    asm volatile("cp.async.bulk.tensor.2d.global.shared::cta.bulk_group [%0, {%2, %3}], [%1];" ::"l"(m), "r"(src), "r"(c0), "r"(c1) : "memory");
}

__device__ __forceinline__ void wgmma_s64(float (&d)[32], uint32_t a0, uint32_t a1, uint32_t a2, uint32_t a3, uint64_t db, int acc) {
    asm volatile("{.reg .pred p; setp.ne.b32 p, %37, 0;\n"
        "wgmma.mma_async.sync.aligned.m64n64k16.f32.bf16.bf16 {"
        "%0,%1,%2,%3,%4,%5,%6,%7,%8,%9,%10,%11,%12,%13,%14,%15,"
        "%16,%17,%18,%19,%20,%21,%22,%23,%24,%25,%26,%27,%28,%29,%30,%31"
        "}, {%32,%33,%34,%35}, %36, p, 1, 1, 0;}"
        : "+f"(d[0]), "+f"(d[1]), "+f"(d[2]), "+f"(d[3]), "+f"(d[4]), "+f"(d[5]), "+f"(d[6]), "+f"(d[7]), "+f"(d[8]), "+f"(d[9]), "+f"(d[10]), "+f"(d[11]), "+f"(d[12]), "+f"(d[13]), "+f"(d[14]), "+f"(d[15]), "+f"(d[16]), "+f"(d[17]), "+f"(d[18]), "+f"(d[19]), "+f"(d[20]), "+f"(d[21]), "+f"(d[22]), "+f"(d[23]), "+f"(d[24]), "+f"(d[25]), "+f"(d[26]), "+f"(d[27]), "+f"(d[28]), "+f"(d[29]), "+f"(d[30]), "+f"(d[31])
        : "r"(a0), "r"(a1), "r"(a2), "r"(a3), "l"(db), "r"(acc));
}
__device__ __forceinline__ void wgmma_s16(float (&d)[8], uint32_t a0, uint32_t a1, uint32_t a2, uint32_t a3, uint64_t db, int acc) {
    asm volatile("{.reg .pred p; setp.ne.b32 p, %13, 0;\n"
        "wgmma.mma_async.sync.aligned.m64n16k16.f32.bf16.bf16 {"
        "%0,%1,%2,%3,%4,%5,%6,%7"
        "}, {%8,%9,%10,%11}, %12, p, 1, 1, 0;}"
        : "+f"(d[0]), "+f"(d[1]), "+f"(d[2]), "+f"(d[3]), "+f"(d[4]), "+f"(d[5]), "+f"(d[6]), "+f"(d[7])
        : "r"(a0), "r"(a1), "r"(a2), "r"(a3), "l"(db), "r"(acc));
}
__device__ __forceinline__ void wgmma_v128(float (&d)[64], uint32_t a0, uint32_t a1, uint32_t a2, uint32_t a3, uint64_t db, int acc) {
    asm volatile("{.reg .pred p; setp.ne.b32 p, %69, 0;\n"
        "wgmma.mma_async.sync.aligned.m64n128k16.f32.bf16.bf16 {"
        "%0,%1,%2,%3,%4,%5,%6,%7,%8,%9,%10,%11,%12,%13,%14,%15,"
        "%16,%17,%18,%19,%20,%21,%22,%23,%24,%25,%26,%27,%28,%29,%30,%31,"
        "%32,%33,%34,%35,%36,%37,%38,%39,%40,%41,%42,%43,%44,%45,%46,%47,"
        "%48,%49,%50,%51,%52,%53,%54,%55,%56,%57,%58,%59,%60,%61,%62,%63"
        "}, {%64,%65,%66,%67}, %68, p, 1, 1, 1;}"
        : "+f"(d[0]), "+f"(d[1]), "+f"(d[2]), "+f"(d[3]), "+f"(d[4]), "+f"(d[5]), "+f"(d[6]), "+f"(d[7]), "+f"(d[8]), "+f"(d[9]), "+f"(d[10]), "+f"(d[11]), "+f"(d[12]), "+f"(d[13]), "+f"(d[14]), "+f"(d[15]), "+f"(d[16]), "+f"(d[17]), "+f"(d[18]), "+f"(d[19]), "+f"(d[20]), "+f"(d[21]), "+f"(d[22]), "+f"(d[23]), "+f"(d[24]), "+f"(d[25]), "+f"(d[26]), "+f"(d[27]), "+f"(d[28]), "+f"(d[29]), "+f"(d[30]), "+f"(d[31]), "+f"(d[32]), "+f"(d[33]), "+f"(d[34]), "+f"(d[35]), "+f"(d[36]), "+f"(d[37]), "+f"(d[38]), "+f"(d[39]), "+f"(d[40]), "+f"(d[41]), "+f"(d[42]), "+f"(d[43]), "+f"(d[44]), "+f"(d[45]), "+f"(d[46]), "+f"(d[47]), "+f"(d[48]), "+f"(d[49]), "+f"(d[50]), "+f"(d[51]), "+f"(d[52]), "+f"(d[53]), "+f"(d[54]), "+f"(d[55]), "+f"(d[56]), "+f"(d[57]), "+f"(d[58]), "+f"(d[59]), "+f"(d[60]), "+f"(d[61]), "+f"(d[62]), "+f"(d[63])
        : "r"(a0), "r"(a1), "r"(a2), "r"(a3), "l"(db), "r"(acc));
}

__device__ __forceinline__ void attn_scores(float (&sx)[32], float (&sm)[8], const uint32_t (&q)[32], uint32_t sk) {
    const uint64_t dx = mkdesc(sk, 1024, 128, 0), dm = mkdesc(sk + 16384, 256, 128, 0);
    wg_fence();
#pragma unroll
    for (int ks = 0; ks < 8; ks++) {
        wgmma_s64(sx, q[4 * ks], q[4 * ks + 1], q[4 * ks + 2], q[4 * ks + 3], dx + ks * 128, ks);
        wgmma_s16(sm, q[4 * ks], q[4 * ks + 1], q[4 * ks + 2], q[4 * ks + 3], dm + ks * 32, ks);
    }
    wg_commit();
}
template <bool HI>
__device__ __forceinline__ void attn_softmax(uint32_t (&p)[2][20], const float (&sx)[2][32], const float (&sm)[2][8], bool sb, int lane) {
    constexpr int NF = HI ? 2 : 0, NT = NF + 3;
    const int gt = (lane >> 2) - 2 * (lane & 3);
    const float cs = 0.08838834764831845f * 1.4426950408889634f;
    float s[2][NT][4], m[4], l[4];
#pragma unroll
    for (int h = 0; h < 2; h++) {
#pragma unroll
        for (int j = 0; j < NT; j++)
#pragma unroll
            for (int e = 0; e < 4; e++) s[h][j][e] = j == NT - 1 ? (sb ? sm[h][4 + e] : sm[h][e]) : (sb ? sx[h][16 + 4 * j + e] : sx[h][4 * j + e]);
        if (gt < 0) s[h][NF][0] = s[h][NF + 1][2] = -INFINITY;
        if (gt < 1) s[h][NF][1] = s[h][NF + 1][3] = -INFINITY;
        m[2 * h] = fmaxf(s[h][0][0], s[h][0][1]); m[2 * h + 1] = fmaxf(s[h][0][2], s[h][0][3]);
#pragma unroll
        for (int j = 1; j < NT; j++) {
            if (j != NF + 1) m[2 * h] = fmaxf(m[2 * h], fmaxf(s[h][j][0], s[h][j][1]));
            m[2 * h + 1] = fmaxf(m[2 * h + 1], fmaxf(s[h][j][2], s[h][j][3]));
        }
    }
#pragma unroll
    for (int r = 0; r < 4; r++) m[r] = fmaxf(m[r], __shfl_xor_sync(0xffffffffu, m[r], 1));
#pragma unroll
    for (int r = 0; r < 4; r++) m[r] = fmaxf(m[r], __shfl_xor_sync(0xffffffffu, m[r], 2)) * -cs;
#pragma unroll
    for (int r = 0; r < 4; r++) {
        l[r] = 0.f;
#pragma unroll
        for (int j = 0; j < NT; j++)
            if ((r & 1) || j != NF + 1) {
                float* v = &s[r >> 1][j][2 * (r & 1)];
                v[0] = ex2(fmaf(v[0], cs, m[r])); v[1] = ex2(fmaf(v[1], cs, m[r]));
                l[r] += v[0] + v[1];
            }
    }
#pragma unroll
    for (int r = 0; r < 4; r++) l[r] += __shfl_xor_sync(0xffffffffu, l[r], 1);
#pragma unroll
    for (int r = 0; r < 4; r++) { l[r] += __shfl_xor_sync(0xffffffffu, l[r], 2); asm("rcp.approx.ftz.f32 %0, %0;" : "+f"(l[r])); }
    const uint32_t ma = sb ? 0u : ~0u;
#pragma unroll
    for (int h = 0; h < 2; h++)
#pragma unroll
        for (int j = 0; j < 5; j++) {
            const bool on = j == 4 || j < NF + 2;
            const int k = j == 4 ? NT - 1 : on ? j : 0, ia = j < 4 ? 2 * j : 16, ib = j < 4 ? 8 + 2 * j : 18;
            const uint32_t x = on && j != NF + 1 ? pack_bf16(s[h][k][0] * l[2 * h], s[h][k][1] * l[2 * h]) : 0;
            const uint32_t y = on ? pack_bf16(s[h][k][2] * l[2 * h + 1], s[h][k][3] * l[2 * h + 1]) : 0;
            asm volatile("and.b32 %0, %4, %6; and.b32 %1, %5, %6; and.b32 %2, %4, %7; and.b32 %3, %5, %7;"
                : "=&r"(p[h][ia]), "=&r"(p[h][ia + 1]), "=&r"(p[h][ib]), "=&r"(p[h][ib + 1]) : "r"(x), "r"(y), "r"(ma), "r"(~ma));
        }
}
__device__ __forceinline__ void attn_pv(float (&o)[64], const uint32_t (&p)[20], uint32_t sv) {
    const uint64_t dx = mkdesc(sv, 128, 1024, 0), dm = mkdesc(sv + 16384, 128, 256, 0);
    wg_fence();
#pragma unroll
    for (int ks = 0; ks < 5; ks++) wgmma_v128(o, p[4 * ks], p[4 * ks + 1], p[4 * ks + 2], p[4 * ks + 3], ks < 4 ? dx + ks * 16 : dm, ks);
    wg_commit();
}
__device__ __forceinline__ void attn_stage(const float (&o)[64], uint32_t dst) {
#pragma unroll
    for (int u = 0; u < 16; u += 2)
        stsm4(dst + (u >> 3) * 8192 + (u & 7) * 128, pack_bf16(o[4 * u], o[4 * u + 1]), pack_bf16(o[4 * u + 2], o[4 * u + 3]),
              pack_bf16(o[4 * u + 4], o[4 * u + 5]), pack_bf16(o[4 * u + 6], o[4 * u + 7]));
}

template <int BN, int NKB, bool BLOCKED_A>
__device__ __forceinline__ void mainloop(float (&acc)[BN / 2], uint32_t sb, int wgi, uint32_t full, uint32_t empty, int& it, bool elect) {
#pragma unroll
    for (int j = 0; j < BN / 2; j++) acc[j] = 0.f;
#pragma unroll 1
    for (int k4 = 0; k4 < NKB; k4 += 4) {
#pragma unroll
        for (int st = 0; st < 4; st++, it++) {
            mbar_wait_long(full + 8 * st, (it >> 2) & 1);
            const uint64_t da = BLOCKED_A ? mkdesc(sb + st * G_STAGE + wgi * 8192, 128, 1024, 0) : mkdesc(sb + st * G_STAGE + wgi * 8192, 16, 1024, 1);
            const uint64_t db = mkdesc(sb + st * G_STAGE + 16384, 8192, 1024, 1);
            wg_fence();
#pragma unroll
            for (int k = 0; k < 4; k++) {
                if constexpr (BN == 256) wgmma256(acc, da + k * (BLOCKED_A ? 16 : 2), db + k * 128, 1);
                else wgmma128(acc, da + k * (BLOCKED_A ? 16 : 2), db + k * 128, 1);
            }
            wg_commit();
            if (k4 | st) {
                wg_wait<1>();
                if (elect) mbar_arrive(empty + 8 * ((st + 3) & 3));
            }
        }
    }
    wg_wait<0>();
    if (elect) mbar_arrive(empty + 8 * 3);
}

__device__ __forceinline__ uint32_t n6_a(int st) { return st < 4 ? st * G_STAGE : (2 * st - 8) * G_STAGE + 32768; }
__device__ __forceinline__ uint32_t n6_b(int st) { return st < 4 ? st * G_STAGE + 16384 : (2 * st - 7) * G_STAGE + 32768; }
__device__ __forceinline__ uint32_t n6_bar(int st) { return st < 4 ? 8 * st : 96 + 8 * st; }
__device__ __forceinline__ void mainloop6(float (&acc)[64], uint32_t sb, int wgi, uint32_t full, uint32_t empty, int& it, bool elect) {
#pragma unroll
    for (int j = 0; j < 64; j++) acc[j] = 0.f;
    int st = 0, prev = 0, r = 0;
#pragma unroll 1
    for (int kb = 0; kb < 64; kb++) {
        mbar_wait_long(full + n6_bar(st), ((st < 4 ? it >> 2 : 0) + r) & 1);
        const uint64_t da = mkdesc(sb + n6_a(st) + wgi * 8192, 128, 1024, 0), db = mkdesc(sb + n6_b(st), 8192, 1024, 1);
        wg_fence();
#pragma unroll
        for (int k = 0; k < 4; k++) wgmma128(acc, da + k * 16, db + k * 128, 1);
        wg_commit();
        if (kb) {
            wg_wait<1>();
            if (elect) mbar_arrive(empty + n6_bar(prev));
        }
        prev = st;
        if (++st == 6) { st = 0; r++; }
    }
    wg_wait<0>();
    if (elect) mbar_arrive(empty + 8 * 3);
    it += 44;
}

template <int BN>
__device__ __forceinline__ void o_item(uint32_t sb, int wgi, int wi, int lane, uint32_t full, uint32_t empty, int& it, const CUtensorMap* mout,
                                       int row0, int col0, uint32_t stgpar) {
    float acc[BN / 2];
    if constexpr (BN == 256) mainloop<BN, 64, true>(acc, sb, wgi, full, empty, it, lane == 0);
    else mainloop6(acc, sb, wgi, full, empty, it, lane == 0);
    ST((row0 >> 4) + (col0 / BN), wgi * 4 + wi, 10);
    mbar_wait(full + 104, stgpar);
    const uint32_t stg = sb + G_STG + (wgi * 4 + wi) * 4096;
    const int r = lane & 15, cu = lane >> 4;
#pragma unroll
    for (int hf = 0; hf < BN / 128; hf++) {
        if (elect()) asm volatile("cp.async.bulk.wait_group.read 0;" ::: "memory");
        __syncwarp();
#pragma unroll
        for (int j = 0; j < 8; j++) {
            const float* a = acc + hf * 64 + j * 8;
            stsm4(stg + (j >> 2) * 2048 + r * 128 + ((((j & 3) * 2 + cu) ^ (r & 7)) << 4),
                  pack_bf16(a[0], a[1]), pack_bf16(a[2], a[3]), pack_bf16(a[4], a[5]), pack_bf16(a[6], a[7]));
        }
        asm volatile("fence.proxy.async.shared::cta;" ::: "memory");
        __syncwarp();
        if (elect()) {
            tma2d_store(mout, stg, col0 + hf * 128, row0 + wgi * 64 + wi * 16);
            tma2d_store(mout, stg + 2048, col0 + hf * 128 + 64, row0 + wgi * 64 + wi * 16);
            asm volatile("cp.async.bulk.commit_group;" ::: "memory");
        }
    }
}

constexpr int S4_KD = 32768;
constexpr int S4_CH = 2 * G_STAGE;
constexpr int S4_HALF = 2304;
constexpr int S4_WD = 2 * S4_HALF;
constexpr int S4_T2 = S4_WD + 2304;
constexpr int S4_T3 = S4_T2 + 1024;
constexpr int S4_STRIDE = S4_T3 + 640 + 16;
__device__ __forceinline__ uint32_t addz(uint32_t x, uint32_t z) { uint32_t r; asm volatile("add.u32 %0, %1, %2;" : "=r"(r) : "r"(x), "r"(z)); return r; }
__device__ __forceinline__ uint32_t lds16(uint32_t a) { uint32_t v; asm volatile("ld.shared.u16 %0, [%1];" : "=r"(v) : "r"(a) : "memory"); return v; }
__device__ __forceinline__ uint32_t ldsu(uint32_t a) { return __float_as_uint(lds32(a)); }

template <int E0, int NE, int KP, bool PAIR>
__device__ __forceinline__ void s4_windows(float (&acc)[8][2][4], uint32_t ut, uint32_t tw, int rho, int w, int lane, uint32_t z) {
    const int gt = (lane >> 2) - 2 * (lane & 3), p0 = rho == 16 ? -3 : -2, c = (lane >> 3) + p0;
    uint32_t band[2][4], ta[PAIR ? 3 * NE : NE][4];
    {
        const uint64_t ones = ((uint64_t)((2u << 2 * w) - 1) << 32) >> (8 * p0 + 24 - gt + rho + w);
        uint32_t f[5];
#pragma unroll
        for (int m = 0; m < 5; m++) f[m] = ((((uint32_t)(ones >> (8 * m)) & 3) * 0x8001u) & 0x10001u) * 0x3F80u;
#pragma unroll
        for (int j = 0; j < 2; j++) { band[j][0] = f[2 * j + 1]; band[j][1] = addz(f[2 * j], z); band[j][2] = f[2 * j + 2]; band[j][3] = addz(f[2 * j + 1], z); }
    }
#pragma unroll
    for (int e = 0; e < (PAIR ? 3 * NE : NE); e++)
        asm volatile("ld.shared.u32 %0, [%4]; ld.shared.u32 %1, [%4+%5]; ld.volatile.shared.u32 %2, [%4+%6]; ld.volatile.shared.u32 %3, [%4];"
            : "=r"(ta[e][0]), "=r"(ta[e][1]), "=r"(ta[e][2]), "=r"(ta[e][3])
            : "r"(tw + 16 * (E0 + e % NE) * KP + (e < NE ? 0 : e < 2 * NE ? 8 : 8 - KP)), "n"(8 * KP), "n"(-8 * KP) : "memory");
    const uint32_t ua = ut + (c & 1) * S4_HALF + (16 + (lane & 7) + (c >> 1)) * 16;
#pragma unroll
    for (int J = 0; J < 8 - E0; J++) {
        uint32_t u0[4], u1[4];
        ldsm4(u0, ua + J * 256); ldsm4(u1, ua + J * 256 + 128);
        float s0[4], s1[4];
        mma16z(s0, band[0], u0[0], u0[1]); mma16z(s1, band[0], u1[0], u1[1]);
        mma16(s0, band[1], u0[2], u0[3]); mma16(s1, band[1], u1[2], u1[3]);
        const uint32_t b00 = pack_bf16(s0[0], s0[1]), b01 = pack_bf16(s1[0], s1[1]), b10 = pack_bf16(s0[2], s0[3]), b11 = pack_bf16(s1[2], s1[3]);
#pragma unroll
        for (int e = 0; e < NE; e++)
            if (J + E0 + e < 8) { mma16(acc[J + E0 + e][0], ta[e], b00, b01); mma16(acc[J + E0 + e][1], ta[e], b10, b11); }
#pragma unroll
        for (int e = 0; e < (PAIR ? NE : 0); e++)
            if (J + E0 + e < 8) { mma16(acc[J + E0 + e][1], ta[NE + e], b00, b01); mma16(acc[J + E0 + e][0], ta[2 * NE + e], b10, b11); }
    }
}
template <int D0, int D1>
__device__ __forceinline__ void s4_dense(float (&acc)[8][2][4], uint32_t ua, const uint32_t (&b0)[4], const uint32_t (&b1)[4]) {
#pragma unroll
    for (int J = 0; J < 8 - D0; J++) {
        uint32_t a[4];
        ldsm4(a, ua + J * 256);
        mma16(acc[J + D0][0], a, b0[0], b0[1]); mma16(acc[J + D0][1], a, b0[2], b0[3]);
        if (J + D1 < 8) { mma16(acc[J + D1][0], a, b1[0], b1[1]); mma16(acc[J + D1][1], a, b1[2], b1[3]); }
    }
}
__device__ __forceinline__ void s4_words(uint32_t (&b)[4], uint32_t wd) {
    asm volatile("ld.shared.u32 %0, [%4]; ld.shared.u32 %1, [%4+-32]; ld.shared.u32 %2, [%4+32]; ld.volatile.shared.u32 %3, [%4];"
        : "=r"(b[0]), "=r"(b[1]), "=r"(b[2]), "=r"(b[3]) : "r"(wd) : "memory");
}

__device__ __forceinline__ void s4_item(uint32_t sb, int cw, int lane, int item, const bf16* __restrict__ dsk, uint32_t empty, const CUtensorMap* my, uint32_t stgpar,
                                        bf16* __restrict__ out, uint32_t nbar, uint32_t npar, uint32_t nslot) {
    const int gt = (lane >> 2) - 2 * (lane & 3);
    const uint32_t ch = sb + S4_CH + cw * S4_STRIDE, kd = sb + S4_KD + cw * 1536;
    const __nv_bfloat162 dk = __bfloat162bfloat162(dsk[item * 8 + cw]);
    ST(item, cw, 0);
    asm volatile("st.shared.v4.u32 [%0], {%1,%1,%1,%1};" ::"r"(ch + (lane >> 4) * S4_HALF + (lane & 15) * 16), "r"(0) : "memory");
    const uint32_t tch = sb + S4_CH + (lane & 7) * S4_STRIDE + ((lane >> 3) & 1) * S4_HALF + (16 + 16 * cw + (lane >> 4)) * 16;
#pragma unroll
    for (int i = 0; i < 8; i++) {
        uint32_t x[4];
        ldsm4t(x, sb + cw * 4096 + i * 512 + lane * 16);
        stsm4(tch + i * 32, x[0], x[1], x[2], x[3]);
    }
    const uint32_t k1024 = lds16(kd + 1024);
    {
        auto st4 = [](uint32_t a, uint32_t x, uint32_t y, uint32_t u, uint32_t v) {
            asm volatile("st.shared.v4.u32 [%0], {%1,%2,%3,%4};" ::"r"(a), "r"(x), "r"(y), "r"(u), "r"(v) : "memory");
        };
        const float4 p = lds128(kd + lane * 16);
        const uint32_t p0 = __float_as_uint(p.x), p1 = __float_as_uint(p.y), p2 = __float_as_uint(p.z), p3 = __float_as_uint(p.w);
        const uint32_t pm = lane ? ldsu(kd + lane * 16 - 4) : 0;
        const uint32_t wa = ch + S4_WD + 64 + lane * 32;
        st4(wa, __byte_perm(p0, pm, 0x7610), __byte_perm(p0, 0, 0x1032), __byte_perm(p1, p0, 0x7610), __byte_perm(p1, 0, 0x1032));
        st4(wa + 16, __byte_perm(p2, p1, 0x7610), __byte_perm(p2, 0, 0x1032), __byte_perm(p3, p2, 0x7610), __byte_perm(p3, 0, 0x1032));
        const float2 q = lds64(kd + 512 + lane * 8);
        const uint32_t q0 = __float_as_uint(q.x), q1 = __float_as_uint(q.y), q2 = ldsu(kd + 520 + lane * 8), k255 = ldsu(kd + 508);
        st4(wa + 1024, lane ? __byte_perm(q0, 0, 0x1010) : __byte_perm(q0, k255, 0x7610), __byte_perm(q0, 0, 0x1010), __byte_perm(q0, 0, 0x1032), __byte_perm(q1, q0, 0x7610));
        st4(wa + 1040, __byte_perm(q1, 0, 0x1010), __byte_perm(q1, 0, 0x1010), __byte_perm(q1, 0, 0x1032), __byte_perm(q2, q1, 0x7610));
        const uint32_t k512 = lane == 4 ? lds16(kd + 768) : 0;
        if (lane < 16) st4(ch + S4_WD + (lane < 4 ? 0 : 2048) + lane * 16, k512 * 0x10001u, k512 * 0x10001u, k512 * 0x10001u, k512 << 16);
        const float2 c = lds64(kd + 768 + lane * 8), d = lds64(kd + 760 + lane * 8);
        const uint32_t c0 = __float_as_uint(c.x), c1 = __float_as_uint(c.y), c2 = ldsu(kd + 776 + lane * 8);
        const uint32_t d0 = lane ? __float_as_uint(d.x) : 0, d1 = lane ? __float_as_uint(d.y) : 0, d2 = lane ? c0 : 0;
        st4(ch + S4_T2 + 256 + lane * 16, __byte_perm(c0, d0, 0x7632), __byte_perm(c1, d1, 0x5410), __byte_perm(c1, d1, 0x7632), __byte_perm(c2, d2, 0x5410));
        const uint32_t m = lane == 31 ? 0xFFFF0000u : 0;
        st4(ch + S4_T2 + (lane < 16 ? lane : lane == 31 ? 48 : lane + 33) * 16, c0 & m, (c1 << 16) & m, c1 & m, (c2 << 16) & m);
        const float2 e = lds64(kd + 1024 + lane * 8);
        const uint32_t e0 = __float_as_uint(e.x), e1 = __float_as_uint(e.y), e2 = ldsu(kd + 1032 + lane * 8), em = ldsu(kd + 1020 + lane * 8);
        st4(ch + S4_T3 + 128 + lane * 16, __byte_perm(e0, lane ? em : 0, 0x7632), __byte_perm(e1, lane ? e0 : 0, 0x5410), __byte_perm(e1, e0, 0x7632), __byte_perm(e2, e1, 0x5410));
        if (lane < 8) st4(ch + S4_T3 + lane * 16, 0, 0, 0, 0);
    }
    bar_sync(2, 256);
    ST(item, cw, 1);
    const uint32_t z = ldsu(ch);
    float acc[8][2][4];
#pragma unroll
    for (int j = 0; j < 16; j++) acc[j >> 1][j & 1][0] = acc[j >> 1][j & 1][1] = acc[j >> 1][j & 1][2] = acc[j >> 1][j & 1][3] = 0.f;
#pragma unroll 1
    for (int r = 1; r <= 2; r++) s4_windows<2, 3, 16, true>(acc, ch, ch + S4_T2 + (gt - 16) * 16 + 4 * r - 4, 4 * r, r, lane, z);
    ST(item, cw, 2);
#pragma unroll 1
    for (int r = 1; r <= 2; r++) s4_windows<4, 4, 8, false>(acc, ch, ch + S4_T3 + (gt - 48) * 8 + 4 * r - 4, 8 * r, 2 + r, lane, z);
    ST(item, cw, 3);
    const uint32_t ua = ch + (lane >> 4) * S4_HALF + (16 + (lane & 15)) * 16, wd = ch + S4_WD + 64 + gt * 4;
#pragma unroll 1
    for (int q = 0; q < 2; q++) {
        uint32_t b0[4], b1[4];
        s4_words(b0, wd + (q + 32) * 64);
#pragma unroll
        for (int j = 0; j < 4; j++) {
            const int x = 16 * q + gt + (j == 1 ? -8 : j == 2 ? 8 : 0) - 3;
            b1[j] = addz(((unsigned)x < 2u ? k1024 : 0u) | ((unsigned)(x - 1) < 2u ? k1024 << 16 : 0u), z);
        }
        s4_dense<2, 4>(acc, ua - q * 16, b0, b1);
    }
    {
        uint32_t b0[4], b1[4], c0[4], c1[4];
        s4_words(b0, wd); s4_words(b1, wd + 1024);
#pragma unroll 1
        for (int q = 0; q < 16; q += 2) {
            s4_words(c0, wd + q * 64 + 64); s4_words(c1, wd + q * 64 + 64 + 1024);
            s4_dense<0, 1>(acc, ua - q * 16, b0, b1);
            s4_words(b0, wd + q * 64 + 128); s4_words(b1, wd + q * 64 + 128 + 1024);
            s4_dense<0, 1>(acc, ua - q * 16 - 16, c0, c1);
            if (q == S4REL && lane == 0) { mbar_arrive(empty); mbar_arrive(empty + 8); }
        }
    }
    ST(item, cw, 4);
    mbar_wait(empty + 72, stgpar);
    if (elect()) asm volatile("cp.async.bulk.wait_group.read 0;" ::: "memory");
    __syncwarp();
#pragma unroll
    for (int I = 0; I < 8; I++) {
        uint32_t u[4];
        ldsm4(u, ua + I * 256);
#pragma unroll
        for (int j = 0; j < 4; j++) {
            const uint32_t y = pack_bf16(acc[I][j >> 1][2 * (j & 1)], acc[I][j >> 1][2 * (j & 1) + 1]);
            const __nv_bfloat162 r = __hadd2_rn(*(const __nv_bfloat162*)&y, __hmul2_rn(*(const __nv_bfloat162*)&u[j], dk));
            u[j] = *(const uint32_t*)&r;
        }
        stsm4(ua + I * 256, u[0], u[1], u[2], u[3]);
    }
    bar_sync(2, 256);
    uint32_t y[8][4];
#pragma unroll
    for (int i = 0; i < 8; i++) ldsm4t(y[i], tch + i * 32);
    if (cw < S4DIR && mbar_test(nbar, npar) && ldsu(nslot) == (IT_END << 16)) {
        uint32_t* const dst = (uint32_t*)(out + (size_t)(cw * 256 + (lane >> 2)) * (2 * DM) + DM + item * 8) + (lane & 3);
#pragma unroll
        for (int i = 0; i < 32; i++) dst[i * 8 * DM] = y[i >> 2][i & 3];
        return;
    }
#pragma unroll
    for (int i = 0; i < 8; i++) stsm4(sb + G_STG + cw * 4096 + i * 512 + lane * 16, y[i][0], y[i][1], y[i][2], y[i][3]);
    asm volatile("fence.proxy.async.shared::cta;" ::: "memory");
    __syncwarp();
    if (elect()) {
        mbar_arrive(empty + 16); mbar_arrive(empty + 24);
        tma2d_store(my, sb + G_STG + cw * 4096, DM + item * 8, cw * 256);
        asm volatile("cp.async.bulk.commit_group;" ::: "memory");
    }
    ST(item, cw, 5);
}

struct Maps { CUtensorMap m[13]; };
__global__ void __launch_bounds__(384, 1)
worker_kernel(const __grid_constant__ Maps M, const bf16* __restrict__ dsk, bf16* __restrict__ out) {
    const CUtensorMap &mx = M.m[0], &mq = M.m[1], &mo = M.m[4], &mout = M.m[5], &mu = M.m[6], &my = M.m[7];
    extern __shared__ unsigned char smem_raw[];
    const uint32_t sb = (smem_u32(smem_raw) + 1023) & ~1023u;
    const uint32_t full = sb + G_BAR, empty = full + 32, ifull = full + 64, iempty = full + 80, islot = full + 96, stgbar = full + 104, sigbar = full + 112, sigslot = full + 120;
    const int tid = threadIdx.x, wg = tid >> 7, lane = tid & 31;
    int q0 = blockIdx.x;
    const int nfirst = min(32, (int)gridDim.x - 96), wide0 = q0 - ((int)gridDim.x - N_LATE);
    if (tid == 0 && q0 >= nfirst && wide0 < 0) q0 = nfirst + atomicAdd(g_ctr + C_NEXT, 1);
    if ((tid >> 5) == 1 && elect()) {
#pragma unroll
        for (int i = 0; i < 6; i++) { mbar_init(full + n6_bar(i), 1); mbar_init(empty + n6_bar(i), 8); }
#pragma unroll
        for (int i = 0; i < 2; i++) { mbar_init(ifull + 8 * i, 1); mbar_init(iempty + 8 * i, 8); }
        mbar_init(sigbar, 8); mbar_init(stgbar, 1);
        asm volatile("fence.mbarrier_init.release.cluster;" ::: "memory");
    }
    if ((tid >> 5) == 2 && elect()) {
#pragma unroll
        for (int i = 0; i < 13; i++) asm volatile("prefetch.tensormap [%0];" ::"l"(&M.m[i]) : "memory");
    }
    __syncthreads();
    if (wg == 0) {
        reg_dec<40>();
        if (tid >= 32 && tid < 64) {
            for (int n = 0;; n++) {
                mbar_wait_long(sigbar, n & 1);
                int item; asm volatile("ld.shared.u32 %0, [%1];" : "=r"(item) : "r"(sigslot + 4 * (n & 1)) : "memory");
                const int type = item >> 16, b = (item >> 8) & 255, i = item & 255;
                if (type == IT_END) break;
                if (type == IT_QA) {
                    if (elect()) {
#pragma unroll
                        for (int j = 0; j < 8; j++) {
                            const uint32_t src = sb + (j >= 4 ? G_STG + (j & 1) * 16384 : 3 * G_STAGE + (j & 1) * 20480) + ((j >> 1) & 1) * 8192;
                            asm volatile("cp.async.bulk.global.shared::cta.bulk_group [%0], [%1], 8192;"
                                ::"l"(g_ox + (size_t)(b * 64 + i * 4 + ((j >> 1) ^ 2)) * 8192 + (j & 1) * 4096), "r"(src) : "memory");
                            if ((j & 3) == 3) asm volatile("cp.async.bulk.commit_group;" ::: "memory");
                        }
                        asm volatile("cp.async.bulk.wait_group.read 1;" ::: "memory");
                        asm volatile("mbarrier.arrive.shared.b64 _, [%0], 8;" ::"r"(empty + 24) : "memory");
                        asm volatile("cp.async.bulk.wait_group 0;" ::: "memory");
                        mbar_arrive(stgbar);
                        asm volatile("fence.proxy.async.global;" ::: "memory");
                    }
                    __syncwarp();
                }
                if (type == IT_KV) { if (lane < 6) red_release(g_kvf + ((i & 15) * 6 + lane) * 16 + b, 1); }
                else if (lane == 0) red_release(g_ctr + C_QA_DONE + b, 1 << i);
            }
        } else if (tid < 32) {
            int it = 0;
            bool tables = false;
            if (!KVN) asm volatile("griddepcontrol.wait;" ::: "memory");
            for (int n = 0;; n++) {
                int item = 0;
                if (lane == 0) {
                    if (n) q0 = nfirst + atomicAdd(g_ctr + C_NEXT, 1);
                    item = n == 0 && wide0 >= 0 ? late_item(wide0) : queue_item(q0);
                }
                item = __shfl_sync(0xffffffffu, item, 0);
                mbar_wait(iempty + 8 * (n & 1), ((n >> 1) & 1) ^ 1);
                if (lane == 0) {
                    asm volatile("st.shared.u32 [%0], %1;" ::"r"(islot + 4 * (n & 1)), "r"(item) : "memory");
                    mbar_arrive(ifull + 8 * (n & 1));
                }
                const int type = item >> 16, b = (item >> 8) & 255, i = item & 255;
                bool ready = false;
                if (type == IT_QA || type == IT_KV) {
                    const CUtensorMap* mw = &mq + (type == IT_QA ? 0 : 1 + (i >> 4));
#pragma unroll 1
                    for (int kb = 0; kb < 16; kb++, it++) {
                        const int st = it & 3;
                        mbar_wait(empty + 8 * st, ((it >> 2) & 1) ^ 1);
                        if (elect()) {
                            mbar_expect(full + 8 * st, G_STAGE);
                            tma2d(sb + st * G_STAGE, &mx, kb * 64, b * 128, full + 8 * st);
                            tma3d(sb + st * G_STAGE + 16384, mw, 0, kb * 64, (i & 15) * 4, full + 8 * st);
                        }
                        if (type == IT_QA && kb == 3) ready = __all_sync(0xffffffffu, ld_acq(g_ctr + C_CHAIN + b) >= 96);
                        if (ready && kb < 11 && elect()) {
                            const size_t sh = (b * 4 + ((kb - 3) & 3)) * NH + i * 2;
                            asm volatile("cp.async.bulk.prefetch.L2.global [%0], 16384;" ::"l"((kb >= 7 ? g_vx : g_kx) + sh * 4096) : "memory");
                            asm volatile("cp.async.bulk.prefetch.L2.global [%0], 4096;" ::"l"((kb >= 7 ? g_vm : g_km) + sh * 1024) : "memory");
                        }
                    }
                }
                if (type == IT_QA) {
                    if (b == 15) asm volatile("griddepcontrol.wait;" ::: "memory");
                    else if (!ready) wait_ctr(g_ctr + C_CHAIN + b, 96);
                    tables = true;
                    asm volatile("fence.proxy.async.global;" ::: "memory");
#pragma unroll 1
                    for (int st = 0; st < 4; st++, it++) {
                        mbar_wait(empty + 8 * st, ((it >> 2) & 1) ^ 1);
                        if (elect()) {
                            mbar_expect(full + 8 * st, 4 * 10240);
#pragma unroll
                            for (int j = 0; j < 4; j++)
                                tma3d(sb + st * G_STAGE + (j >> 1) * 20480 + (j & 1) * 16384, &M.m[8 + (st >> 1) + (j & 1) * 2], 0, b * 4 + (j & 2),
                                      (i * 2 + (st & 1)) * 16, full + 8 * st);
                        }
                    }
                } else if (type == IT_O) {
                    const bool wide = b < O_WIDE;
                    const CUtensorMap* mw = wide ? &mo : &M.m[12];
                    int done = 0;
                    const int ns = wide ? 4 : 6;
#pragma unroll 1
                    for (int kb = 0, st = 0, r = 0; kb < 64; kb++) {
                        const uint32_t bo = n6_bar(st);
                        mbar_wait(empty + bo, (((st < 4 ? it >> 2 : 0) + r) & 1) ^ 1);
                        if (elect()) {
                            mbar_expect(full + bo, wide ? G_STAGE : 32768);
                            tma3d(sb + n6_b(st), mw, 0, kb * 64, wide ? i * 4 : i * 2, full + bo);
                        }
                        if (!(done >> (kb >> 2) & 1)) {
#pragma unroll 1
                            for (int sp = 0; sp < (1 << 20) && !((done = __shfl_sync(0xffffffffu, ld_acq(g_ctr + C_QA_DONE + b), 0)) >> (kb >> 2) & 1); sp++)
                                __nanosleep(64);
                            asm volatile("fence.proxy.async.global;" ::: "memory");
                        }
                        if (elect()) bulk_load(sb + n6_a(st), g_ox + (size_t)(b * 64 + kb) * 8192, 16384, full + bo);
                        if (++st == ns) { st = 0; r++; }
                    }
                    it += wide ? 64 : 44;
                } else if (type == IT_S4) {
                    mbar_wait(empty, ((it >> 2) & 1) ^ 1);
                    if (elect()) {
                        mbar_expect(full, 32768 + 12288);
#pragma unroll
                        for (int j = 0; j < 8; j++) tma2d(sb + j * 4096, &mu, i * 8, j * 256, full);
                    }
                    if (!tables) { wait_ctr(g_ctr + C_CHAIN, 96); asm volatile("fence.proxy.async.global;" ::: "memory"); }
                    tables = true;
                    if (elect()) bulk_load(sb + S4_KD, g_kd + i * 8 * 768, 12288, full);
#pragma unroll 1
                    for (int st = 1; st < 4; st++) { mbar_wait(empty + 8 * st, ((it >> 2) & 1) ^ 1); if (lane == 0) mbar_arrive(full + 8 * st); }
                    it += 4;
                    mbar_wait_long(empty, ((it >> 2) & 1) ^ 1);
                }
                if (item >> 16 == IT_END) break;
            }
            asm volatile("griddepcontrol.wait;" ::: "memory");
        }
    } else {
        reg_inc<232>();
        const int wu = __shfl_sync(0xffffffffu, tid >> 5, 0);
        const int wgi = (wu >> 2) - 1, wi = wu & 3;
        int it = 0, nqa = 0, nsig = 0, n = 0, item;
        auto next_item = [&]() {
            mbar_wait_long(ifull + 8 * (n & 1), (n >> 1) & 1);
            asm volatile("ld.shared.u32 %0, [%1];" : "=r"(item) : "r"(islot + 4 * (n & 1)) : "memory");
            __syncwarp();
            if (lane == 0) mbar_arrive(iempty + 8 * (n & 1));
        };
        auto signal = [&](int what) {
            if (tid == 128) asm volatile("st.shared.u32 [%0], %1;" ::"r"(sigslot + 4 * (nsig & 1)), "r"(what) : "memory");
            __syncwarp();
            if (lane == 0) mbar_arrive(sigbar);
            nsig++;
        };
        next_item();
        if (item >> 16 == IT_KV) {
            float acc[128];
            uint32_t pk[64];
            uint32_t* dst = nullptr;
            int prev = 0;
            do {
                WLOG(0);
#pragma unroll
                for (int kb = 0; kb < 16; kb++, it++) {
                    const int st = kb & 3;
                    mbar_wait(full + 8 * st, (it >> 2) & 1);
                    const uint64_t da = mkdesc(sb + st * G_STAGE + wgi * 8192, 16, 1024, 1);
                    const uint64_t db = mkdesc(sb + st * G_STAGE + 16384, 8192, 1024, 1);
                    wg_fence();
#pragma unroll
                    for (int k = 0; k < 4; k++) wgmma256(acc, da + k * 2, db + k * 128, kb | k);
                    wg_commit();
                    if (n <= KVI) {
                        if (kb < KVF && dst) {
#pragma unroll
                            for (int j = kb * (64 / KVF); j < (kb + 1) * (64 / KVF); j++) dst[(j >> 1) * 128 + (j & 1) * 32] = pk[j];
                            if (kb == KVF - 1) signal(prev);
                        }
                    } else if (kb < KVS) {
#pragma unroll
                        for (int j = kb * (64 / KVS); j < (kb + 1) * (64 / KVS); j++) dst[(j >> 1) * 128 + (j & 1) * 32] = pk[j];
                        if (kb == KVS - 1) signal(prev);
                    }
                    if (kb > 0) {
                        wg_wait<1>();
                        if (lane == 0) mbar_arrive(empty + 8 * ((kb - 1) & 3));
                    }
                }
                wg_wait<0>();
                if (lane == 0) mbar_arrive(empty + 8 * 3);
#pragma unroll
                for (int j = 0; j < 64; j++) pk[j] = pack_bf16(acc[2 * j], acc[2 * j + 1]);
                const int row = ((item >> 8) & 255) * 128 + wgi * 64 + wi * 16, nt = item & 255;
                dst = (uint32_t*)(nt < 16 ? g_kx : g_vx) + (size_t)((row >> 5) * 512 + (nt & 15) * 32) * 128 + (row & 31) * 4 + lane;
                prev = item;
                WLOG(1);
                n++;
                next_item();
            } while (item >> 16 == IT_KV);
            if (dst) {
#pragma unroll
                for (int j = 0; j < 64; j++) dst[(j >> 1) * 128 + (j & 1) * 32] = pk[j];
                signal(prev);
            }
        }
        for (;; n++, next_item()) {
            const int type = item >> 16, b = (item >> 8) & 255, i = item & 255;
            const int lane = (tid & 31) + (item >> 24), wgi = (wu >> 2) - 1 + __shfl_sync(0xffffffffu, item >> 24, 0), wi = wu & 3;
            WLOG(0);
            if (type == IT_QA) {
                float acc[128];
                ST(sid, cw, 0);
                ST(sid, cw, 1);
                mainloop<256, 16, false>(acc, sb, wgi, full, empty, it, lane == 0);
                ST(sid, cw, 2);
                uint32_t q0[32], q1[32];
#pragma unroll
                for (int j = 0; j < 32; j++) q0[j] = pack_bf16(acc[2 * j], acc[2 * j + 1]);
                const uint32_t par = (it >> 2) & 1, so = sb + wgi * 20480;
                float sx[2][32] = {}, sm[2][8] = {};
                uint32_t p[2][20];
                mbar_wait_long(full, par);
                ST(sid, cw, 3);
                if (wgi == 0) bar_sync(5, 256);
                attn_scores(sx[0], sm[0], q0, so);
                ST(sid, cw, 7);
#pragma unroll
                for (int j = 0; j < 32; j++) asm volatile("cvt.rn.bf16x2.f32 %0, %1, %2;" : "=r"(q1[j]) : "f"(acc[65 + 2 * j]), "f"(acc[64 + 2 * j]));
                mbar_wait(full + 8, par);
                attn_scores(sx[1], sm[1], q1, so + G_STAGE);
                if (wgi == 1) bar_arrive(5, 256);
                if (elect()) asm volatile("cp.async.bulk.wait_group.read 0;" ::: "memory");
                mbar_wait(stgbar, (nqa++ & 1) ^ 1);
                bar_sync(3 + wgi, 128);
                float o0[64] = {}, o1[64] = {};
                wg_wait<0>();
                ST(sid, cw, 9);
                if (lane == 0) { mbar_arrive(empty); mbar_arrive(empty + 8); }
                if (wi & 1) attn_softmax<true>(p, sx, sm, wi >= 2, lane);
                else attn_softmax<false>(p, sx, sm, wi >= 2, lane);
                ST(sid, cw, 10);
                mbar_wait(full + 16, par);
                attn_pv(o0, p[0], so + 2 * G_STAGE);
                mbar_wait(full + 24, par);
                attn_pv(o1, p[1], so + 3 * G_STAGE);
                wg_wait<1>();
                if (lane == 0) mbar_arrive(empty + 16);
                ST(sid, cw, 5);
                const uint32_t da = (wi * 2 + ((lane >> 3) & 1)) * 1024 + (lane >> 4) * 128 + (lane & 7) * 16;
                attn_stage(o0, sb + G_STG + wgi * 16384 + da);
                wg_wait<0>();
                bar_sync(3 + wgi, 128);
                attn_stage(o1, so + 3 * G_STAGE + da);
                asm volatile("fence.proxy.async.shared::cta;" ::: "memory");
                ST(sid, cw, 6);
                signal(item);
                it += 4;
            } else if (type == IT_O) {
                ST(b * 8 + i, wgi * 4 + wi, 8);
                mbar_wait_long(full, (it >> 2) & 1);
                ST(b * 8 + i, wgi * 4 + wi, 9);
                if (b < O_WIDE) o_item<256>(sb, wgi, wi, lane, full, empty, it, &mout, b * 128, i * 256, (nqa & 1) ^ 1);
                else o_item<128>(sb, wgi, wi, lane, full, empty, it, &mout, b * 128, i * 128, (nqa & 1) ^ 1);
            } else if (type == IT_S4) {
                mbar_wait_long(full, (it >> 2) & 1);
                mbar_wait(full + 24, (it >> 2) & 1);
                s4_item(sb, wgi * 4 + wi, lane, i, dsk, empty, &my, (nqa & 1) ^ 1, out, ifull + 8 * ((n + 1) & 1), ((n + 1) >> 1) & 1, islot + 4 * ((n + 1) & 1));
                it += 4;
            } else break;
            WLOG(1);
        }
        bar_sync(2, 256);
        signal(item);
        if (elect()) asm volatile("cp.async.bulk.wait_group 0;" ::: "memory");
    }
}

typedef CUresult (*EncodeFn)(CUtensorMap*, CUtensorMapDataType, cuuint32_t, void*, const cuuint64_t*, const cuuint64_t*, const cuuint32_t*,
                             const cuuint32_t*, CUtensorMapInterleave, CUtensorMapSwizzle, CUtensorMapL2promotion, CUtensorMapFloatOOBfill);
static EncodeFn get_encode() {
    void* fn = nullptr; cudaDriverEntryPointQueryResult st;
    cudaGetDriverEntryPoint("cuTensorMapEncodeTiled", &fn, cudaEnableDefault, &st);
    return (EncodeFn)fn;
}
static void map_act(EncodeFn enc, CUtensorMap* m, const void* p, int rows, int cols, int boxr) {
    cuuint64_t dim[2] = {(cuuint64_t)cols, (cuuint64_t)rows}, str[1] = {(cuuint64_t)cols * 2};
    cuuint32_t box[2] = {64, (cuuint32_t)boxr}, es[2] = {1, 1};
    enc(m, CU_TENSOR_MAP_DATA_TYPE_BFLOAT16, 2, (void*)p, dim, str, box, es, CU_TENSOR_MAP_INTERLEAVE_NONE, CU_TENSOR_MAP_SWIZZLE_128B,
        CU_TENSOR_MAP_L2_PROMOTION_L2_128B, CU_TENSOR_MAP_FLOAT_OOB_FILL_NONE);
}
static void map_w(EncodeFn enc, CUtensorMap* m, const void* p, int k, int n, int groups = 4) {
    cuuint64_t dim[3] = {64, (cuuint64_t)k, (cuuint64_t)n / 64}, str[2] = {(cuuint64_t)n * 2, 128};
    cuuint32_t box[3] = {64, 64, (cuuint32_t)groups}, es[3] = {1, 1, 1};
    enc(m, CU_TENSOR_MAP_DATA_TYPE_BFLOAT16, 3, (void*)p, dim, str, box, es, CU_TENSOR_MAP_INTERLEAVE_NONE, CU_TENSOR_MAP_SWIZZLE_128B,
        CU_TENSOR_MAP_L2_PROMOTION_L2_256B, CU_TENSOR_MAP_FLOAT_OOB_FILL_NONE);
}

static void map_kv(EncodeFn enc, CUtensorMap* m, void* p, int n) {
    cuuint64_t dim[3] = {(cuuint64_t)n, NSEG, 512}, str[2] = {(cuuint64_t)n * 1024, (cuuint64_t)n * 2};
    cuuint32_t box[3] = {(cuuint32_t)n, 2, 16}, es[3] = {1, 1, 1};
    enc(m, CU_TENSOR_MAP_DATA_TYPE_BFLOAT16, 3, p, dim, str, box, es, CU_TENSOR_MAP_INTERLEAVE_NONE, CU_TENSOR_MAP_SWIZZLE_NONE,
        CU_TENSOR_MAP_L2_PROMOTION_NONE, CU_TENSOR_MAP_FLOAT_OOB_FILL_NONE);
}
static void map_box(EncodeFn enc, CUtensorMap* m, const void* p, int rows, int ld, int boxc, int boxr, CUtensorMapSwizzle sw,
                    CUtensorMapL2promotion promo = CU_TENSOR_MAP_L2_PROMOTION_NONE) {
    cuuint64_t dim[2] = {(cuuint64_t)ld, (cuuint64_t)rows}, str[1] = {(cuuint64_t)ld * 2};
    cuuint32_t box[2] = {(cuuint32_t)boxc, (cuuint32_t)boxr}, es[2] = {1, 1};
    enc(m, CU_TENSOR_MAP_DATA_TYPE_BFLOAT16, 2, (void*)p, dim, str, box, es, CU_TENSOR_MAP_INTERLEAVE_NONE, sw,
        promo, CU_TENSOR_MAP_FLOAT_OOB_FILL_NONE);
}

extern "C" void kernel_launch(void* const* d_in, const int* in_sizes, int n_in, void* d_out, int out_size) {
    const bf16* x = (const bf16*)d_in[0];
    const bf16* mem0 = (const bf16*)d_in[1];
    const bf16 *Wq = (const bf16*)d_in[2], *Wk = (const bf16*)d_in[3], *Wv = (const bf16*)d_in[4], *Wo = (const bf16*)d_in[5];
    static EncodeFn enc = nullptr;
    static int nsm = 0;
    static void* kv[4];
    if (!enc) {
        enc = get_encode();
        cudaGetSymbolAddress(&kv[0], g_kx); cudaGetSymbolAddress(&kv[1], g_vx); cudaGetSymbolAddress(&kv[2], g_km); cudaGetSymbolAddress(&kv[3], g_vm);
        cudaDeviceGetAttribute(&nsm, cudaDevAttrMultiProcessorCount, 0);
        cudaFuncSetAttribute(chain_kernel, cudaFuncAttributeMaxDynamicSharedMemorySize, CH_SMEM);
        cudaFuncSetAttribute(worker_kernel, cudaFuncAttributeMaxDynamicSharedMemorySize, G_SMEM);
    }
    Maps M;
    CUtensorMap &mx = M.m[0], &mq = M.m[1], &mk = M.m[2], &mv = M.m[3], &mo = M.m[4], &mout = M.m[5], &mu = M.m[6], &my = M.m[7];
    map_act(enc, &mx, x, S_LEN, DM, 128);
    map_w(enc, &mq, Wq, DM, HD); map_w(enc, &mk, Wk, DM, HD); map_w(enc, &mv, Wv, DM, HD); map_w(enc, &mo, Wo, HD, DM);
    map_w(enc, &M.m[12], Wo, HD, DM, 2);
    map_box(enc, &mout, d_out, S_LEN, 2 * DM, 64, 16, CU_TENSOR_MAP_SWIZZLE_128B);
    map_box(enc, &mu, d_in[7], S_LEN, DM, 8, 256, CU_TENSOR_MAP_SWIZZLE_NONE);
    map_box(enc, &my, d_out, S_LEN, 2 * DM, 8, 256, CU_TENSOR_MAP_SWIZZLE_NONE);
    for (int i = 0; i < 4; i++) map_kv(enc, &M.m[8 + i], kv[i], i < 2 ? 256 : 64);
    CUtensorMap cq, ck, cv, co;
    map_box(enc, &cq, Wq, DM, HD, 32, 32, CU_TENSOR_MAP_SWIZZLE_64B, CU_TENSOR_MAP_L2_PROMOTION_L2_128B); map_box(enc, &ck, Wk, DM, HD, 32, 32, CU_TENSOR_MAP_SWIZZLE_64B, CU_TENSOR_MAP_L2_PROMOTION_L2_128B);
    map_box(enc, &cv, Wv, DM, HD, 32, 32, CU_TENSOR_MAP_SWIZZLE_64B, CU_TENSOR_MAP_L2_PROMOTION_L2_128B); map_box(enc, &co, Wo, HD, DM, 32, 16, CU_TENSOR_MAP_SWIZZLE_64B, CU_TENSOR_MAP_L2_PROMOTION_L2_128B);
    S4Params P = {(const bf16*)d_in[8], (const bf16*)d_in[9], (const bf16*)d_in[10], (const bf16*)d_in[11],
                  (const bf16*)d_in[12], (const bf16*)d_in[13], (const bf16*)d_in[14], (const bf16*)d_in[15]};
    int aware = 1;
    cudaLaunchAttribute at[1];
    at[0].id = cudaLaunchAttributeProgrammaticStreamSerialization;
    at[0].val.programmaticStreamSerializationAllowed = 1;
    cudaLaunchConfig_t cfg = {};
    cfg.stream = cudaStreamPerThread;
    cfg.gridDim = dim3(96); cfg.blockDim = dim3(CH_THREADS); cfg.dynamicSmemBytes = CH_SMEM;
    cudaLaunchKernelEx(&cfg, chain_kernel, cq, ck, cv, co, Wq, Wk, Wv, mem0, P, aware);
    cfg.attrs = at; cfg.numAttrs = 1;
    cfg.gridDim = dim3(nsm); cfg.blockDim = dim3(384); cfg.dynamicSmemBytes = G_SMEM;
    cudaLaunchKernelEx(&cfg, worker_kernel, M, P.dsk, (bf16*)d_out);
}
```
